```python
import torch

def _softmax(x, axis=-1):
    return torch.softmax(x, dim=axis)
def _gelu(x):
    return torch.nn.functional.gelu(x, approximate="tanh")
def _silu(x):
    return torch.nn.functional.silu(x)
def _sigmoid(x):
    return torch.sigmoid(x)
def _layernorm(x, axis=-1, eps=1e-5):
    m = x.mean(dim=axis, keepdim=True)
    v = x.var(dim=axis, keepdim=True, unbiased=False)
    return (x - m) / torch.sqrt(v + eps)
def _scatter_add(tgt, idx, src, axis=0):
    return tgt.clone().index_add_(axis, idx, src)
def _segment_sum(src, seg, n):
    out = torch.zeros((n,) + src.shape[1:], dtype=src.dtype)
    return out.index_add_(0, seg, src)
def _pad(x, pw):
    flat = tuple(v for pair in reversed(pw) for v in pair)
    return torch.nn.functional.pad(x, flat)

kernel_name = 'interleave_layers__sliding_local_dilated__dense_activation_gelu__prompt'

def setup_inputs():

    _w = (lambda a: (lambda t: t.to(torch.bfloat16) if t.is_floating_point() else t)(torch.as_tensor(a)))
    def _A_setup():
        B, S, D = 1, 2048, 1024
        return {
            "x": _w((lambda *s: torch.randn(*s, dtype=torch.bfloat16) * 0.05)(B, S, D)),
            "wqkv": _w((lambda *s: torch.randn(*s, dtype=torch.bfloat16) * 0.05)(D, 3 * D)),
            "wo": _w((lambda *s: torch.randn(*s, dtype=torch.bfloat16) * 0.05)(D, D)),
        }
    _A_in = _A_setup()

    def _B_setup():
        B, S, D, F = 1, 2048, 1024, 3584
        return {
            "x": _w((lambda *s: torch.randn(*s, dtype=torch.bfloat16) * 0.05)(B, S, D)),
            "w1": _w((lambda *s: torch.randn(*s, dtype=torch.bfloat16) * 1.6)(D, F) * (D ** -0.5)),
            "b1": _w((lambda *s: torch.randn(*s, dtype=torch.bfloat16) * 1.6)(F) * 0.01),
            "w2": _w((lambda *s: torch.randn(*s, dtype=torch.bfloat16) * 1.6)(F, D) * (F ** -0.5)),
            "b2": _w((lambda *s: torch.randn(*s, dtype=torch.bfloat16) * 1.6)(D) * 0.01),
        }
    _B_in = _B_setup()

    return {
        "A_x": _A_in["x"],
        "A_wqkv": _A_in["wqkv"],
        "A_wo": _A_in["wo"],
        "B_x": _B_in["x"],
        "B_w1": _B_in["w1"],
        "B_b1": _B_in["b1"],
        "B_w2": _B_in["w2"],
        "B_b2": _B_in["b2"],
    }

def reference(A_x, A_wqkv, A_wo, B_x, B_w1, B_b1, B_w2, B_b2):
    def _A_ref(x, wqkv, wo):
        B, S, D = x.shape
        H = 32; Dh = D // H
        W, dil = 8, 2
        qkv = (lambda x, *d: x.permute(*d))((x @ wqkv).reshape(B, S, 3, H, Dh), 2, 0, 3, 1, 4)
        q, k, v = qkv[0], qkv[1], qkv[2]
        scale = Dh ** -0.5
        pos = torch.arange(S)
        off = torch.arange(W) * dil
        idx = pos[:, None] - off[None, :]
        mask = idx >= 0
        idx_c = torch.where(mask, idx, 0).reshape(-1)
        kg = k[:, :, idx_c, :].reshape(B, H, S, W, Dh)
        vg = v[:, :, idx_c, :].reshape(B, H, S, W, Dh)
        logits = torch.einsum("bhsd,bhswd->bhsw", q, kg) * scale
        logits = torch.where(mask[None, None, :, :], logits, -1e9)
        attn = _softmax(logits, axis=-1)
        o = torch.einsum("bhsw,bhswd->bhsd", attn, vg)
        return (lambda x, *d: x.permute(*d))(o, 0, 2, 1, 3).reshape(B, S, D) @ wo

    def _B_ref(x, w1, b1, w2, b2):
        h = torch.einsum("bsd,df->bsf", x, w1) + b1
        h = _gelu(h)
        return torch.einsum("bsf,fd->bsd", h, w2) + b2

    x = A_x
    x = x + _A_ref(_layernorm(x, axis=-1), A_wqkv, A_wo)
    x = x + _B_ref(_layernorm(x, axis=-1), B_w1, B_b1, B_w2, B_b2)
    x = x + _A_ref(_layernorm(x, axis=-1), A_wqkv, A_wo)
    x = x + _B_ref(_layernorm(x, axis=-1), B_w1, B_b1, B_w2, B_b2)
    return x
```

```cpp
#include <cuda_runtime.h>
#include <cuda_bf16.h>
#include <cuda.h>
#include <stdint.h>

namespace {

constexpr int SEQ = 2048, DM = 1024, FF = 3584;
constexpr int NCTA = 128;
constexpr int NBAR = 5;

constexpr uint32_t RING_UNITS = 20, UNIT = 8192;
constexpr uint32_t OFF_X   = RING_UNITS * UNIT;
constexpr uint32_t OFF_STG = OFF_X + 32768;
constexpr uint32_t OFF_EXC = OFF_STG + 16384;
constexpr uint32_t OFF_CSQ = OFF_EXC + 12288;
constexpr uint32_t OFF_CSF = OFF_CSQ + 1536;
constexpr uint32_t OFF_ROW = OFF_CSF + 3584;
constexpr uint32_t OFF_BAR = OFF_ROW + 1024;
constexpr uint32_t SMEM_BYTES = OFF_BAR + 128;

constexpr int BAR_ORDER = 1, BAR_GUARD = 3, BAR_WG = 5;

struct Params {
  CUtensorMap xin_ld, out_ld, out_st, att_ld, att_st, h_ld, h_st, wqkv, wo, w1a, w1b, w2;
  const __nv_bfloat16 *wqkv_p, *w1_p, *b1, *b2;
};

__device__ __nv_bfloat16 g_att[SEQ * DM];
__device__ __nv_bfloat16 g_h[SEQ * FF];
__device__ float4 g_stats[4 * SEQ * 4];
__device__ uint4 g_halo[2 * 2 * 16 * 8 * 256];
__device__ float g_csp[16 * (3 * DM + FF)];
__device__ uint32_t g_flags[15 * 16 * 32];
__device__ uint32_t g_hflag[2 * 2 * 16 * 8];
__device__ uint32_t g_cflag[2 * 8 * 32];
__device__ uint32_t g_epoch[NCTA];
#define PROF_T(idx)

__device__ __forceinline__ void mbar_init(uint32_t bar, int cnt) {
  asm volatile("mbarrier.init.shared::cta.b64 [%0], %1;" ::"r"(bar), "r"(cnt));
}
__device__ __forceinline__ void mbar_expect_tx(uint32_t bar, uint32_t bytes) {
  asm volatile("mbarrier.arrive.expect_tx.shared::cta.b64 _, [%0], %1;" ::"r"(bar), "r"(bytes) : "memory");
}
__device__ __forceinline__ void mbar_arrive(uint32_t bar) {
  asm volatile("mbarrier.arrive.shared::cta.b64 _, [%0];" ::"r"(bar) : "memory");
}
__device__ __forceinline__ void mbar_wait(uint32_t bar, uint32_t parity) {
  asm volatile(
      "{\n.reg .pred p;\n.reg .u32 it;\nmov.u32 it, 0;\n"
      "WAIT_LOOP:\n"
      "mbarrier.try_wait.parity.shared::cta.b64 p, [%0], %1;\n"
      "@p bra WAIT_DONE;\n"
      "add.u32 it, it, 1;\n"
      "setp.lt.u32 p, it, 0x400000;\n"
      "@p bra WAIT_LOOP;\n"
      "trap;\n"
      "WAIT_DONE:\n}"
      ::"r"(bar), "r"(parity) : "memory");
}
__device__ __forceinline__ void bar_sync(int id, int n) { asm volatile("bar.sync %0, %1;" ::"r"(id), "r"(n) : "memory"); }
__device__ __forceinline__ void bar_arrive(int id, int n) { asm volatile("bar.arrive %0, %1;" ::"r"(id), "r"(n) : "memory"); }
__device__ __forceinline__ void tma_ld2(uint32_t dst, const CUtensorMap* m, uint32_t bar, int c0, int c1) {
  asm volatile("cp.async.bulk.tensor.2d.shared::cluster.global.mbarrier::complete_tx::bytes [%0], [%1, {%3, %4}], [%2];"
               ::"r"(dst), "l"(m), "r"(bar), "r"(c0), "r"(c1) : "memory");
}
__device__ __forceinline__ void tma_ld3(uint32_t dst, const CUtensorMap* m, uint32_t bar, int c0, int c1, int c2) {
  asm volatile("cp.async.bulk.tensor.3d.shared::cluster.global.mbarrier::complete_tx::bytes [%0], [%1, {%3, %4, %5}], [%2];"
               ::"r"(dst), "l"(m), "r"(bar), "r"(c0), "r"(c1), "r"(c2) : "memory");
}
__device__ __forceinline__ void tma_pf3(const CUtensorMap* m, int c0, int c1, int c2) {
  asm volatile("cp.async.bulk.prefetch.tensor.3d.L2.global [%0, {%1, %2, %3}];" ::"l"(m), "r"(c0), "r"(c1), "r"(c2) : "memory");
}
__device__ __forceinline__ void tma_st2(const CUtensorMap* m, uint32_t src, int c0, int c1) {
  asm volatile("cp.async.bulk.tensor.2d.global.shared::cta.bulk_group [%0, {%2, %3}], [%1];"
               ::"l"(m), "r"(src), "r"(c0), "r"(c1) : "memory");
}
__device__ __forceinline__ void bulk_commit() { asm volatile("cp.async.bulk.commit_group;" ::: "memory"); }
__device__ __forceinline__ void bulk_wait_read() { asm volatile("cp.async.bulk.wait_group.read 0;" ::: "memory"); }
__device__ __forceinline__ void bulk_wait_all() { asm volatile("cp.async.bulk.wait_group 0;" ::: "memory"); }
__device__ __forceinline__ void fence_async_smem() { asm volatile("fence.proxy.async.shared::cta;" ::: "memory"); }
__device__ __forceinline__ void fence_async_global() { asm volatile("fence.proxy.async.global;" ::: "memory"); }
__device__ __forceinline__ void st_release(uint32_t* p, uint32_t v) {
  asm volatile("st.release.gpu.global.u32 [%0], %1;" ::"l"(p), "r"(v) : "memory");
}
__device__ __forceinline__ uint32_t pack_bf16(float lo, float hi) {
  uint32_t r;
  asm("cvt.rn.bf16x2.f32 %0, %1, %2;" : "=r"(r) : "f"(hi), "f"(lo));
  return r;
}
__device__ __forceinline__ float bf_lo(uint32_t v) { return __uint_as_float(v << 16); }
__device__ __forceinline__ float bf_hi(uint32_t v) { return __uint_as_float(v & 0xffff0000u); }
__device__ __forceinline__ void stsm4(uint32_t addr, uint32_t r0, uint32_t r1, uint32_t r2, uint32_t r3) {
  asm volatile("stmatrix.sync.aligned.m8n8.x4.shared.b16 [%0], {%1, %2, %3, %4};"
               ::"r"(addr), "r"(r0), "r"(r1), "r"(r2), "r"(r3) : "memory");
}
__device__ __forceinline__ void ldsm4(uint32_t addr, uint32_t& r0, uint32_t& r1, uint32_t& r2, uint32_t& r3) {
  asm volatile("ldmatrix.sync.aligned.m8n8.x4.shared.b16 {%0, %1, %2, %3}, [%4];"
               : "=r"(r0), "=r"(r1), "=r"(r2), "=r"(r3) : "r"(addr) : "memory");
}
__device__ __forceinline__ uint32_t movtrans(uint32_t a) {
  uint32_t d;
  asm volatile("movmatrix.sync.aligned.m8n8.trans.b16 %0, %1;" : "=r"(d) : "r"(a));
  return d;
}
__device__ __forceinline__ void mma16816(float (&c)[4], uint32_t a0, uint32_t a1, uint32_t a2, uint32_t a3, uint32_t b0, uint32_t b1) {
  asm volatile("mma.sync.aligned.m16n8k16.row.col.f32.bf16.bf16.f32 {%0,%1,%2,%3}, {%4,%5,%6,%7}, {%8,%9}, {%0,%1,%2,%3};"
               : "+f"(c[0]), "+f"(c[1]), "+f"(c[2]), "+f"(c[3])
               : "r"(a0), "r"(a1), "r"(a2), "r"(a3), "r"(b0), "r"(b1));
}
__device__ __forceinline__ float2 lds_f2(uint32_t a) {
  float2 v;
  asm volatile("ld.shared.v2.f32 {%0, %1}, [%2];" : "=f"(v.x), "=f"(v.y) : "r"(a) : "memory");
  return v;
}
__device__ __forceinline__ float4 lds_f4(uint32_t a) {
  float4 v;
  asm volatile("ld.shared.v4.f32 {%0, %1, %2, %3}, [%4];" : "=f"(v.x), "=f"(v.y), "=f"(v.z), "=f"(v.w) : "r"(a) : "memory");
  return v;
}
__device__ __forceinline__ float lds_f(uint32_t a) {
  float v;
  asm volatile("ld.shared.f32 %0, [%1];" : "=f"(v) : "r"(a) : "memory");
  return v;
}
__device__ __forceinline__ void sts_f(uint32_t a, float v) { asm volatile("st.shared.f32 [%0], %1;" ::"r"(a), "f"(v) : "memory"); }
__device__ __forceinline__ void sts_f2(uint32_t a, float x, float y) {
  asm volatile("st.shared.v2.f32 [%0], {%1, %2};" ::"r"(a), "f"(x), "f"(y) : "memory");
}
__device__ __forceinline__ void sts_u4(uint32_t a, uint32_t x, uint32_t y, uint32_t z, uint32_t w) {
  asm volatile("st.shared.v4.u32 [%0], {%1, %2, %3, %4};" ::"r"(a), "r"(x), "r"(y), "r"(z), "r"(w) : "memory");
}
__device__ __forceinline__ void lds_u4(uint32_t a, uint32_t& x, uint32_t& y, uint32_t& z, uint32_t& w) {
  asm volatile("ld.shared.v4.u32 {%0, %1, %2, %3}, [%4];" : "=r"(x), "=r"(y), "=r"(z), "=r"(w) : "r"(a) : "memory");
}
__device__ __forceinline__ float ex2(float x) {
  float y;
  asm("ex2.approx.ftz.f32 %0, %1;" : "=f"(y) : "f"(x));
  return y;
}
__device__ __forceinline__ float rcp_hw(float x) {
  float y;
  asm("rcp.approx.ftz.f32 %0, %1;" : "=f"(y) : "f"(x));
  return y;
}
__device__ __forceinline__ float tanh_hw(float x) {
  float y;
  asm("tanh.approx.f32 %0, %1;" : "=f"(y) : "f"(x));
  return y;
}
__device__ __forceinline__ float quad_sum(float v) {
  v += __shfl_xor_sync(0xffffffffu, v, 1);
  return v + __shfl_xor_sync(0xffffffffu, v, 2);
}
__device__ __forceinline__ float quad_max(float v) {
  v = fmaxf(v, __shfl_xor_sync(0xffffffffu, v, 1));
  return fmaxf(v, __shfl_xor_sync(0xffffffffu, v, 2));
}

template<int N> __device__ __forceinline__ void wgmma_ss(float (&d)[N/2], uint64_t da, uint64_t db, int scale_d);
template<> __device__ __forceinline__ void wgmma_ss<128>(float (&d)[64], uint64_t da, uint64_t db, int scale_d) {
  asm volatile("{\n.reg .pred p;\nsetp.ne.b32 p, %66, 0;\n"
    "wgmma.mma_async.sync.aligned.m64n128k16.f32.bf16.bf16 {%0, %1, %2, %3, %4, %5, %6, %7, %8, %9, %10, %11, %12, %13, %14, %15, %16, %17, %18, %19, %20, %21, %22, %23, %24, %25, %26, %27, %28, %29, %30, %31, %32, %33, %34, %35, %36, %37, %38, %39, %40, %41, %42, %43, %44, %45, %46, %47, %48, %49, %50, %51, %52, %53, %54, %55, %56, %57, %58, %59, %60, %61, %62, %63}, %64, %65, p, 1, 1, 0, 1;\n}\n"
    : "+f"(d[0]), "+f"(d[1]), "+f"(d[2]), "+f"(d[3]), "+f"(d[4]), "+f"(d[5]), "+f"(d[6]), "+f"(d[7]), "+f"(d[8]), "+f"(d[9]), "+f"(d[10]), "+f"(d[11]), "+f"(d[12]), "+f"(d[13]), "+f"(d[14]), "+f"(d[15]), "+f"(d[16]), "+f"(d[17]), "+f"(d[18]), "+f"(d[19]), "+f"(d[20]), "+f"(d[21]), "+f"(d[22]), "+f"(d[23]), "+f"(d[24]), "+f"(d[25]), "+f"(d[26]), "+f"(d[27]), "+f"(d[28]), "+f"(d[29]), "+f"(d[30]), "+f"(d[31]), "+f"(d[32]), "+f"(d[33]), "+f"(d[34]), "+f"(d[35]), "+f"(d[36]), "+f"(d[37]), "+f"(d[38]), "+f"(d[39]), "+f"(d[40]), "+f"(d[41]), "+f"(d[42]), "+f"(d[43]), "+f"(d[44]), "+f"(d[45]), "+f"(d[46]), "+f"(d[47]), "+f"(d[48]), "+f"(d[49]), "+f"(d[50]), "+f"(d[51]), "+f"(d[52]), "+f"(d[53]), "+f"(d[54]), "+f"(d[55]), "+f"(d[56]), "+f"(d[57]), "+f"(d[58]), "+f"(d[59]), "+f"(d[60]), "+f"(d[61]), "+f"(d[62]), "+f"(d[63])
    : "l"(da), "l"(db), "r"(scale_d));
}

template<> __device__ __forceinline__ void wgmma_ss<192>(float (&d)[96], uint64_t da, uint64_t db, int scale_d) {
  asm volatile("{\n.reg .pred p;\nsetp.ne.b32 p, %98, 0;\n"
    "wgmma.mma_async.sync.aligned.m64n192k16.f32.bf16.bf16 {%0, %1, %2, %3, %4, %5, %6, %7, %8, %9, %10, %11, %12, %13, %14, %15, %16, %17, %18, %19, %20, %21, %22, %23, %24, %25, %26, %27, %28, %29, %30, %31, %32, %33, %34, %35, %36, %37, %38, %39, %40, %41, %42, %43, %44, %45, %46, %47, %48, %49, %50, %51, %52, %53, %54, %55, %56, %57, %58, %59, %60, %61, %62, %63, %64, %65, %66, %67, %68, %69, %70, %71, %72, %73, %74, %75, %76, %77, %78, %79, %80, %81, %82, %83, %84, %85, %86, %87, %88, %89, %90, %91, %92, %93, %94, %95}, %96, %97, p, 1, 1, 0, 1;\n}\n"
    : "+f"(d[0]), "+f"(d[1]), "+f"(d[2]), "+f"(d[3]), "+f"(d[4]), "+f"(d[5]), "+f"(d[6]), "+f"(d[7]), "+f"(d[8]), "+f"(d[9]), "+f"(d[10]), "+f"(d[11]), "+f"(d[12]), "+f"(d[13]), "+f"(d[14]), "+f"(d[15]), "+f"(d[16]), "+f"(d[17]), "+f"(d[18]), "+f"(d[19]), "+f"(d[20]), "+f"(d[21]), "+f"(d[22]), "+f"(d[23]), "+f"(d[24]), "+f"(d[25]), "+f"(d[26]), "+f"(d[27]), "+f"(d[28]), "+f"(d[29]), "+f"(d[30]), "+f"(d[31]), "+f"(d[32]), "+f"(d[33]), "+f"(d[34]), "+f"(d[35]), "+f"(d[36]), "+f"(d[37]), "+f"(d[38]), "+f"(d[39]), "+f"(d[40]), "+f"(d[41]), "+f"(d[42]), "+f"(d[43]), "+f"(d[44]), "+f"(d[45]), "+f"(d[46]), "+f"(d[47]), "+f"(d[48]), "+f"(d[49]), "+f"(d[50]), "+f"(d[51]), "+f"(d[52]), "+f"(d[53]), "+f"(d[54]), "+f"(d[55]), "+f"(d[56]), "+f"(d[57]), "+f"(d[58]), "+f"(d[59]), "+f"(d[60]), "+f"(d[61]), "+f"(d[62]), "+f"(d[63]), "+f"(d[64]), "+f"(d[65]), "+f"(d[66]), "+f"(d[67]), "+f"(d[68]), "+f"(d[69]), "+f"(d[70]), "+f"(d[71]), "+f"(d[72]), "+f"(d[73]), "+f"(d[74]), "+f"(d[75]), "+f"(d[76]), "+f"(d[77]), "+f"(d[78]), "+f"(d[79]), "+f"(d[80]), "+f"(d[81]), "+f"(d[82]), "+f"(d[83]), "+f"(d[84]), "+f"(d[85]), "+f"(d[86]), "+f"(d[87]), "+f"(d[88]), "+f"(d[89]), "+f"(d[90]), "+f"(d[91]), "+f"(d[92]), "+f"(d[93]), "+f"(d[94]), "+f"(d[95])
    : "l"(da), "l"(db), "r"(scale_d));
}

template <int R>
__device__ __forceinline__ void pin_regs(float (&a)[2][R]) {
#pragma unroll
  for (int m = 0; m < 2; m++)
#pragma unroll
    for (int i = 0; i < R; i++) asm volatile("" : "+f"(a[m][i])::"memory");
}

struct Ctx {
  uint32_t sb;
  int m, n, wg, w, lane;
};
__device__ __forceinline__ Ctx make_ctx(uint32_t sb, int mn) {
  int tid;
  asm volatile("mov.u32 %0, %%tid.x;" : "=r"(tid));
  asm volatile("" : "+r"(mn), "+r"(sb));
  return Ctx{sb, mn >> 3, mn & 7, tid >> 7, (tid >> 5) & 3, tid & 31};
}
#define UNPACK_CTX(c) const uint32_t sb = c.sb; const int m = c.m, n = c.n, wg = c.wg, w = c.w, lane = c.lane

__device__ __forceinline__ uint32_t poll_line(const uint32_t* line, uint32_t tag, uint32_t need, int lane) {
  uint32_t mask;
  asm volatile(
      "{\n.reg .pred p;\n.reg .u32 it, v;\nmov.u32 it, 0;\n"
      "POLL_LOOP:\n"
      "ld.acquire.gpu.global.u32 v, [%1];\n"
      "setp.eq.u32 p, v, %2;\n"
      "vote.sync.ballot.b32 %0, p, 0xffffffff;\n"
      "and.b32 v, %0, %3;\n"
      "setp.eq.u32 p, v, %3;\n"
      "@p bra.uni POLL_DONE;\n"
      "add.u32 it, it, 1;\n"
      "setp.lt.u32 p, it, 0x400000;\n"
      "@p bra.uni POLL_LOOP;\n"
      "trap;\n"
      "POLL_DONE:\n"
      "bar.warp.sync 0xffffffff;\n}"
      : "=&r"(mask) : "l"(line + lane), "r"(tag), "r"(need) : "memory");
  return mask;
}

constexpr int STAGES_PER_LAYER = 152, UNITS_PER_LAYER = 660;
__device__ __forceinline__ int tile_z(int t) { return (t == 0 || t == 1 || t == 3) ? 5 : 4; }
__device__ __forceinline__ int tile_nkb(int t) { return t == 6 ? 56 : 16; }
__device__ __forceinline__ int tile_p0(int t) {
  return t == 0 ? 0 : t == 1 ? 80 : t == 2 ? 160 : t == 3 ? 225 : t == 4 ? 308 : t == 5 ? 372 : 436;
}
__device__ __forceinline__ int korder(int t, int j, int n) {
  const int np2 = n & 6;
  if (t == 2) return (((np2 + j) & 7) << 1) + (j >> 3);
  if (t == 6) {
    if (j < 24) { int q = j / 3; return 7 * ((np2 + q) & 7) + (j - 3 * q); }
    int jj = j - 24;
    return 7 * ((np2 + (jj >> 1)) & 7) + 3 + ((jj >> 4) << 1) + (jj & 1);
  }
  return j < 4 ? 2 * np2 + ((j + 2 * (n & 1)) & 3) : (2 * np2 + j) & 15;
}

struct Reclaim {
  int g = 0, t = 0, j = 0, p = 0, base = 0, b = 0, ph = 0;
  __device__ __forceinline__ void wait_for(int g_new, int p_end, uint32_t empty0) {
    while (p < p_end - (int)RING_UNITS || g <= g_new - NBAR) {
      mbar_wait(empty0 + 8 * b, ph);
      if (++b == NBAR) { b = 0; ph ^= 1; }
      g++;
      p += tile_z(t);
      if (++j == tile_nkb(t)) {
        j = 0;
        if (++t == 7) { t = 0; base += UNITS_PER_LAYER; }
        p = base + tile_p0(t);
      }
    }
  }
};

__device__ __forceinline__ void weight_coords(const Params& p, int t, int n, const CUtensorMap*& map, int& c0, int& c2) {
  c0 = 0;
  if (t < 2) { map = &p.wqkv; c0 = 128 * n + 64 * t; c2 = 0; }
  else if (t == 2) { map = &p.wo; c2 = 2 * n; }
  else if (t == 3) { map = &p.w1a; c2 = 7 * n; }
  else if (t < 6) { map = &p.w1b; c2 = 7 * n + 2 * t - 5; }
  else { map = &p.w2; c2 = 2 * n; }
}

template <int N, bool PREINIT>
__device__ __forceinline__ void mainloop(float (&acc)[2][N / 2], uint32_t sb, int i, bool ownx) {
  constexpr int Z = 2 + N / 64;
  const int wg = i & 1, lane = threadIdx.x & 31;
  const int layer = i >= 7, t = i - 7 * layer;
  const int nkb = tile_nkb(t);
  const int g0 = layer * STAGES_PER_LAYER + 16 * t;
  int b = g0 % NBAR, ph = (g0 / NBAR) & 1, pos = tile_p0(t) % RING_UNITS;
  const uint32_t full0 = sb + OFF_BAR, empty0 = full0 + 8 * NBAR;
  constexpr uint64_t DA = (1ull << 62) | ((uint64_t)(2048 >> 4) << 32) | (1ull << 16);
  constexpr uint64_t DB = (1ull << 62) | ((uint64_t)(1024 >> 4) << 32) | ((uint64_t)(8192 >> 4) << 16);
  if (!PREINIT) {
#pragma unroll
    for (int r = 0; r < N / 2; r++) acc[0][r] = acc[1][r] = 0.f;
  }
  pin_regs(acc);
  if (i > 0) bar_sync(BAR_ORDER + wg, 256);
  if (t == 0 || t == 3) mbar_wait(empty0 + 8 * NBAR, t == 3);
  int prev_b = 0;
#pragma unroll 1
  for (int j = 0; j < nkb; j++) {
    mbar_wait(full0 + 8 * b, ph);
    if (j == 0) PROF_T(4 + i * 4);
    const uint32_t slot = sb + pos * UNIT;
    const uint32_t aa = (ownx && j < 2) ? sb + OFF_X + j * 16384 : slot;
    const uint64_t da = DA | (uint64_t)((aa & 0x3FFFF) >> 4);
    const uint64_t db = DB | (uint64_t)(((slot + 16384) & 0x3FFFF) >> 4);
    asm volatile("wgmma.fence.sync.aligned;" ::: "memory");
#pragma unroll
    for (int k = 0; k < 4; k++) {
      wgmma_ss<N>(acc[0], da + 2 * k, db + 128 * k, 1);
      wgmma_ss<N>(acc[1], da + 64 + 2 * k, db + 128 * k, 1);
    }
    asm volatile("wgmma.commit_group.sync.aligned;" ::: "memory");
    if (j == nkb - 1 && i < 13) bar_arrive(BAR_ORDER + (wg ^ 1), 256);
    asm volatile("wgmma.wait_group.sync.aligned 1;" ::: "memory");
    if (j > 0 && lane == 0) mbar_arrive(empty0 + 8 * prev_b);
    prev_b = b;
    if (++b == NBAR) { b = 0; ph ^= 1; }
    pos += Z;
    if (pos >= (int)RING_UNITS) pos -= RING_UNITS;
  }
  asm volatile("wgmma.wait_group.sync.aligned 0;" ::: "memory");
  pin_regs(acc);
  if (lane == 0) mbar_arrive(empty0 + 8 * prev_b);
  PROF_T(5 + i * 4);
}

#define ACC(q, j, e) acc[(q) & 1][4 * (j) + 2 * ((q) >> 1) + (e)]

__device__ __forceinline__ void write_partial_stats(const uint32_t (&xp)[4][16], int ln, int row0, int n, int lane) {
#pragma unroll
  for (int q = 0; q < 4; q++) {
    float s0 = 0.f, s1 = 0.f;
#pragma unroll
    for (int j = 0; j < 16; j++) { s0 += bf_lo(xp[q][j]); s1 += bf_hi(xp[q][j]); }
    const float s = quad_sum(s0 + s1), mu = s * (1.f / 128.f);
    float m0 = 0.f, m1 = 0.f;
#pragma unroll
    for (int j = 0; j < 16; j++) {
      const float a = bf_lo(xp[q][j]) - mu, c = bf_hi(xp[q][j]) - mu;
      m0 = fmaf(a, a, m0);
      m1 = fmaf(c, c, m1);
    }
    const float m2 = quad_sum(m0 + m1);
    if ((lane & 3) == 0)
      reinterpret_cast<float2*>(g_stats)[(size_t)(ln * SEQ + row0 + 8 * q + (lane >> 2)) * 8 + n] = make_float2(s, m2);
  }
}

__device__ __forceinline__ void row_stats(float (&rs)[4], float (&rm)[4], bool fresh, uint32_t sb, int ln, int line, int m,
                                          int w, int lane, uint32_t tag) {
  const uint32_t tab = sb + OFF_ROW + (32 * w + (lane >> 2)) * 8;
  if (fresh) {
    poll_line(g_flags + (line * 16 + m) * 32, tag, 0x11111111u << w, lane);
    float4 v[4];
#pragma unroll
    for (int q = 0; q < 4; q++) v[q] = __ldcg(g_stats + (size_t)(ln * SEQ + 128 * m + 32 * w + 8 * q + (lane >> 2)) * 4 + (lane & 3));
#pragma unroll
    for (int q = 0; q < 4; q++) {
      const float mean = quad_sum(v[q].x + v[q].z) * (1.f / DM);
      const float d0 = v[q].x * (1.f / 128.f) - mean, d1 = v[q].z * (1.f / 128.f) - mean;
      const float m2 = quad_sum(v[q].y + v[q].w + 128.f * (d0 * d0 + d1 * d1));
      rs[q] = rsqrtf(m2 * (1.f / DM) + 1e-5f);
      rm[q] = rs[q] * mean;
      if ((lane & 3) == 0) sts_f2(tab + q * 64, rs[q], rm[q]);
    }
  } else {
#pragma unroll
    for (int q = 0; q < 4; q++) {
      const float2 v = lds_f2(tab + q * 64);
      rs[q] = v.x;
      rm[q] = v.y;
    }
  }
}

__device__ __forceinline__ void attn_group(const uint32_t* qa, const uint32_t* qb, const uint32_t* k0, const uint32_t* k1,
                                           const uint32_t* k2, const uint32_t* k3, const uint32_t* v0, const uint32_t* v1,
                                           const uint32_t* v2, const uint32_t* v3, uint32_t* oa, uint32_t* ob,
                                           bool prev_valid, int lane) {
  float s[4][4];
#pragma unroll
  for (int kb = 0; kb < 4; kb++) {
    const uint32_t* kk = kb == 0 ? k0 : kb == 1 ? k1 : kb == 2 ? k2 : k3;
    s[kb][0] = s[kb][1] = s[kb][2] = s[kb][3] = 0.f;
    mma16816(s[kb], qa[0], qb[0], qa[1], qb[1], kk[0], kk[1]);
    mma16816(s[kb], qa[2], qb[2], qa[3], qb[3], kk[2], kk[3]);
  }
  const bool par = (lane >> 2) & 1;
  const bool early = (lane & 3) > (lane >> 3);
  constexpr float NEG = -1e30f;
  constexpr float SC = 0.17677669529663687f * 1.4426950408889634f;
  float la = par ? s[1][1] : s[1][0];
  float lb = early ? (par ? s[0][1] : s[0][0]) : (par ? s[2][1] : s[2][0]);
  float ha = par ? s[2][3] : s[2][2];
  float hb = early ? (par ? s[1][3] : s[1][2]) : (par ? s[3][3] : s[3][2]);
  if (!prev_valid) {
    la = NEG;
    if (early) { lb = NEG; hb = NEG; }
  }
  const float ml = quad_max(fmaxf(la, lb)), mh = quad_max(fmaxf(ha, hb));
  la = ex2((la - ml) * SC); lb = ex2((lb - ml) * SC);
  ha = ex2((ha - mh) * SC); hb = ex2((hb - mh) * SC);
  const float il = rcp_hw(quad_sum(la + lb)), ih = rcp_hw(quad_sum(ha + hb));
  const int sh = par ? 16 : 0;
  const uint32_t pla = pack_bf16(la * il, 0.f) << sh, plb = pack_bf16(lb * il, 0.f) << sh;
  const uint32_t pha = pack_bf16(ha * ih, 0.f) << sh, phb = pack_bf16(hb * ih, 0.f) << sh;
  const uint32_t e_l = early ? plb : 0u, e_h = early ? phb : 0u, l_l = early ? 0u : plb, l_h = early ? 0u : phb;
#pragma unroll
  for (int jn = 0; jn < 4; jn++) {
    float o[4] = {0.f, 0.f, 0.f, 0.f};
    mma16816(o, e_l, 0u, pla, e_h, v0[jn], v1[jn]);
    mma16816(o, l_l, pha, 0u, l_h, v2[jn], v3[jn]);
    oa[jn] = pack_bf16(o[0], o[1]);
    ob[jn] = pack_bf16(o[2], o[3]);
  }
}

template <int NCH, bool QKV>
__device__ __forceinline__ void colsum_partial(const __nv_bfloat16* W, uint32_t sb, int m, int n, int wg, int tid, uint32_t tag) {
  constexpr int LD = QKV ? 3 * DM : FF;
  const int cg = tid & 7, rg = tid >> 3, lane = tid & 31, w = tid >> 5;
  uint4 v[NCH][4];
#pragma unroll
  for (int c = 0; c < NCH; c++) {
    const int col = QKV ? (c >> 1) * DM + 128 * n + (c & 1) * 64 : 448 * n + 64 * c;
#pragma unroll
    for (int r = 0; r < 4; r++)
      v[c][r] = __ldcg(reinterpret_cast<const uint4*>(W + (size_t)(64 * m + 4 * rg + r) * LD + col + 8 * cg));
  }
  bar_sync(BAR_WG + wg, 128);
#pragma unroll
  for (int c = 0; c < NCH; c++) {
    float a[8];
#pragma unroll
    for (int e = 0; e < 4; e++) {
      float lo = 0.f, hi = 0.f;
#pragma unroll
      for (int r = 0; r < 4; r++) {
        const uint32_t u = e == 0 ? v[c][r].x : e == 1 ? v[c][r].y : e == 2 ? v[c][r].z : v[c][r].w;
        lo += bf_lo(u);
        hi += bf_hi(u);
      }
      a[2 * e] = lo;
      a[2 * e + 1] = hi;
    }
    const bool u8 = lane & 8, u16 = lane & 16;
    float h4[4], h2[2];
#pragma unroll
    for (int e = 0; e < 4; e++) h4[e] = (u8 ? a[4 + e] : a[e]) + __shfl_xor_sync(0xffffffffu, u8 ? a[e] : a[4 + e], 8);
#pragma unroll
    for (int e = 0; e < 2; e++) h2[e] = (u16 ? h4[2 + e] : h4[e]) + __shfl_xor_sync(0xffffffffu, u16 ? h4[e] : h4[2 + e], 16);
    sts_f2(sb + OFF_EXC + (w * 448 + c * 64 + cg * 8 + (u8 ? 4 : 0) + (u16 ? 2 : 0)) * 4, h2[0], h2[1]);
  }
  bar_sync(BAR_WG + wg, 128);
  float* dst = g_csp + m * (3 * DM + FF) + (QKV ? 384 * n : 3 * DM + 448 * n);
  for (int c = tid; c < NCH * 64; c += 128) {
    const uint32_t a = sb + OFF_EXC + c * 4;
    dst[c] = (lds_f(a) + lds_f(a + 1792)) + (lds_f(a + 3584) + lds_f(a + 5376));
  }
  bar_sync(BAR_WG + wg, 128);
  if (tid == 0) st_release(g_cflag + ((QKV ? 0 : 8) + n) * 32 + m, tag);
}

template <int NCH, bool QKV>
__device__ __forceinline__ void colsum_gather(const Params& p, uint32_t sb, int n, int tid, uint32_t tag) {
  poll_line(g_cflag + ((QKV ? 0 : 8) + n) * 32, tag, 0xffffu, tid & 31);
  const float* src = g_csp + (QKV ? 384 * n : 3 * DM + 448 * n);
  for (int c = tid; c < NCH * 64; c += 128) {
    float v[16];
#pragma unroll
    for (int mm = 0; mm < 16; mm++) v[mm] = __ldcg(src + mm * (3 * DM + FF) + c);
    float s = 0.f;
#pragma unroll
    for (int mm = 0; mm < 16; mm++) s += v[mm];
    if (QKV) {
      sts_f(sb + OFF_CSQ + ((((c >> 6) & 1) * 3 + (c >> 7)) * 64 + (c & 63)) * 4, s);
    } else {
      const uint32_t a = sb + OFF_CSF + (c >> 1) * 16 + (c & 1) * 4;
      sts_f(a, s);
      sts_f(a + 8, __bfloat162float(p.b1[448 * n + c]));
    }
  }
}

template <int N>
__device__ __forceinline__ void ffn1_tile(const Params& p, uint32_t sb0, int i, int mn, uint32_t tag) {
  float acc[2][N / 2];
  mainloop<N, false>(acc, sb0, i, true);
  asm volatile("" : "+r"(i));
  const int layer = i >= 7, t = i - 7 * layer;
  const Ctx ctx = make_ctx(sb0, mn);
  UNPACK_CTX(ctx);
  bar_sync(BAR_GUARD + wg, 256);
  float rs[4], rm[4];
  row_stats(rs, rm, t == 3, sb, 2 * layer + 1, 1 + 7 * layer + 2, m, w, lane, tag);
  const int col0 = t == 3 ? 0 : t == 4 ? 192 : 320;
  const uint32_t stg = sb + OFF_STG + w * 4096;
  const uint32_t ctab = sb + OFF_CSF + (col0 / 2 + (lane & 3)) * 16;
#pragma unroll
  for (int c = 0; c < N / 64; c++) {
    uint32_t hp[8][4];
#pragma unroll
    for (int jj = 0; jj < 8; jj++) {
      const int j = c * 8 + jj;
      const float4 cb = lds_f4(ctab + j * 64);
#pragma unroll
      for (int q = 0; q < 4; q++) {
        float y[2];
#pragma unroll
        for (int e = 0; e < 2; e++) {
          const float x = fmaf(ACC(q, j, e), rs[q], fmaf(-rm[q], e ? cb.y : cb.x, e ? cb.w : cb.z));
          const float u = x * fmaf(x * x, 0.7978845608028654f * 0.044715f, 0.7978845608028654f);
          const float hx = 0.5f * x;
          y[e] = fmaf(hx, tanh_hw(u), hx);
        }
        hp[jj][q] = pack_bf16(y[0], y[1]);
      }
    }
    if (c > 0) {
      if (lane == 0) bulk_wait_read();
      __syncwarp();
    }
#pragma unroll
    for (int jj = 0; jj < 8; jj++)
      stsm4(stg + lane * 128 + ((jj ^ (lane & 7)) << 4), hp[jj][0], hp[jj][1], hp[jj][2], hp[jj][3]);
    fence_async_smem();
    __syncwarp();
    if (lane == 0) {
      tma_st2(&p.h_st, stg, 448 * n + col0 + 64 * c, 128 * m + 32 * w);
      bulk_commit();
    }
  }
  if (lane == 0) {
    bulk_wait_all();
    st_release(g_flags + ((1 + i) * 16 + m) * 32 + 4 * n + w, tag);
  }
  __syncwarp();
  bar_arrive(BAR_GUARD + (wg ^ 1), 256);
}

__device__ __forceinline__ void resid_tile(const Params& p, uint32_t sb0, int i, int mn, uint32_t tag) {
  const int layer = i >= 7, t = i - 7 * layer;
  const Ctx ctx = make_ctx(sb0, mn);
  UNPACK_CTX(ctx);
  const uint32_t xrow = sb + OFF_X + w * 4096 + lane * 128;
  float acc[2][64];
#pragma unroll
  for (int j = 0; j < 16; j++) {
    uint32_t r[4], bb = 0;
    ldsm4(xrow + (j >> 3) * 16384 + (((j & 7) ^ (lane & 7)) << 4), r[0], r[1], r[2], r[3]);
    if (t == 6) bb = __ldg(reinterpret_cast<const uint32_t*>(p.b2 + 128 * n + 8 * j + 2 * (lane & 3)));
#pragma unroll
    for (int q = 0; q < 4; q++) {
      ACC(q, j, 0) = bf_lo(r[q]) + bf_lo(bb);
      ACC(q, j, 1) = bf_hi(r[q]) + bf_hi(bb);
    }
  }
  mainloop<128, true>(acc, sb0, i, false);
  uint32_t xp[4][16];
#pragma unroll
  for (int j = 0; j < 16; j++) {
#pragma unroll
    for (int q = 0; q < 4; q++) xp[q][j] = pack_bf16(ACC(q, j, 0), ACC(q, j, 1));
    stsm4(xrow + (j >> 3) * 16384 + (((j & 7) ^ (lane & 7)) << 4), xp[0][j], xp[1][j], xp[2][j], xp[3][j]);
  }
  fence_async_smem();
  __syncwarp();
  if (lane == 0) {
    mbar_arrive(sb + OFF_BAR + 16 * NBAR);
    tma_st2(&p.out_st, sb + OFF_X + w * 4096, 128 * n, 128 * m + 32 * w);
    tma_st2(&p.out_st, sb + OFF_X + 16384 + w * 4096, 128 * n + 64, 128 * m + 32 * w);
    bulk_commit();
  }
  if (i < 13) {
    write_partial_stats(xp, 2 * layer + (t == 2 ? 1 : 2), 128 * m + 32 * w, n, lane);
    __syncwarp();
    if (lane == 0) {
      bulk_wait_all();
      st_release(g_flags + ((1 + i) * 16 + m) * 32 + 4 * n + w, tag);
    }
    __syncwarp();
  } else if (lane == 0) {
    bulk_wait_read();
  }
  bar_sync(BAR_GUARD + wg, 256);
  if (i == 2) colsum_gather<7, false>(p, sb, n, w * 32 + lane, tag);
  if (i < 13) bar_arrive(BAR_GUARD + (wg ^ 1), 256);
}

__device__ __forceinline__ void qkv_tile(const Params& p, uint32_t sb0, int i, int mn, uint32_t tag) {
  float acc[2][96];
  mainloop<192, false>(acc, sb0, i, true);
  asm volatile("" : "+r"(i));
  const int layer = i >= 7, t = i - 7 * layer;
  const Ctx ctx = make_ctx(sb0, mn);
  UNPACK_CTX(ctx);
  uint32_t Q[4][8], K[4][8], V[4][8];
  {
    bar_sync(BAR_GUARD + wg, 256);
    float rs[4], rm[4];
    row_stats(rs, rm, t == 0, sb, 2 * layer, 7 * layer, m, w, lane, tag);
    const uint32_t ctab = sb + OFF_CSQ + (t * 192 + 2 * (lane & 3)) * 4;
#pragma unroll
    for (int jj = 0; jj < 24; jj++) {
      const int j = (jj + 8) % 24;
      const float2 cs = lds_f2(ctab + j * 32);
#pragma unroll
      for (int q = 0; q < 4; q++) {
        const uint32_t u = pack_bf16(fmaf(ACC(q, j, 0), rs[q], -rm[q] * cs.x), fmaf(ACC(q, j, 1), rs[q], -rm[q] * cs.y));
        if (j < 8) Q[q][j] = u;
        else if (j < 16) K[q][j - 8] = u;
        else V[q][j - 16] = movtrans(u);
      }
      if (jj == 15) {
        if (w < 3) {
          const uint32_t e = sb + OFF_EXC + w * 4096 + lane * 16;
#pragma unroll
          for (int h = 0; h < 2; h++) {
            sts_u4(e + (0 + h) * 512, K[2][4 * h], K[2][4 * h + 1], K[2][4 * h + 2], K[2][4 * h + 3]);
            sts_u4(e + (2 + h) * 512, K[3][4 * h], K[3][4 * h + 1], K[3][4 * h + 2], K[3][4 * h + 3]);
            sts_u4(e + (4 + h) * 512, V[2][4 * h], V[2][4 * h + 1], V[2][4 * h + 2], V[2][4 * h + 3]);
            sts_u4(e + (6 + h) * 512, V[3][4 * h], V[3][4 * h + 1], V[3][4 * h + 2], V[3][4 * h + 3]);
          }
        } else if (m < 15) {
          const int slot = ((layer * 2 + t) * 16 + m) * 8 + n;
          uint4* e = g_halo + slot * 256 + lane;
#pragma unroll
          for (int h = 0; h < 2; h++) {
            e[(0 + h) * 32] = make_uint4(K[2][4 * h], K[2][4 * h + 1], K[2][4 * h + 2], K[2][4 * h + 3]);
            e[(2 + h) * 32] = make_uint4(K[3][4 * h], K[3][4 * h + 1], K[3][4 * h + 2], K[3][4 * h + 3]);
            e[(4 + h) * 32] = make_uint4(V[2][4 * h], V[2][4 * h + 1], V[2][4 * h + 2], V[2][4 * h + 3]);
            e[(6 + h) * 32] = make_uint4(V[3][4 * h], V[3][4 * h + 1], V[3][4 * h + 2], V[3][4 * h + 3]);
          }
          __syncwarp();
          if (lane == 0) st_release(g_hflag + slot, tag);
          __syncwarp();
        }
      }
    }
  }
  uint32_t O[4][8];
#pragma unroll
  for (int h = 0; h < 2; h++)
    attn_group(&Q[2][4 * h], &Q[3][4 * h], &K[0][4 * h], &K[1][4 * h], &K[2][4 * h], &K[3][4 * h], &V[0][4 * h], &V[1][4 * h],
               &V[2][4 * h], &V[3][4 * h], &O[2][4 * h], &O[3][4 * h], true, lane);
  bar_sync(BAR_WG + wg, 128);
  uint32_t P[8][4];
  if (w > 0) {
    const uint32_t e = sb + OFF_EXC + (w - 1) * 4096 + lane * 16;
#pragma unroll
    for (int r = 0; r < 8; r++) lds_u4(e + r * 512, P[r][0], P[r][1], P[r][2], P[r][3]);
  } else if (m > 0) {
    const int slot = ((layer * 2 + t) * 16 + m - 1) * 8 + n;
    poll_line(g_hflag + slot, tag, 1u, 0);
#pragma unroll
    for (int r = 0; r < 8; r++) {
      const uint4 v = __ldcg(g_halo + slot * 256 + r * 32 + lane);
      P[r][0] = v.x; P[r][1] = v.y; P[r][2] = v.z; P[r][3] = v.w;
    }
  } else {
#pragma unroll
    for (int r = 0; r < 8; r++) P[r][0] = P[r][1] = P[r][2] = P[r][3] = 0u;
  }
  __syncwarp();
#pragma unroll
  for (int h = 0; h < 2; h++)
    attn_group(&Q[0][4 * h], &Q[1][4 * h], P[0 + h], P[2 + h], &K[0][4 * h], &K[1][4 * h], P[4 + h], P[6 + h],
               &V[0][4 * h], &V[1][4 * h], &O[0][4 * h], &O[1][4 * h], (m | w) != 0, lane);
  const uint32_t stg = sb + OFF_STG + w * 4096;
#pragma unroll
  for (int j = 0; j < 8; j++) stsm4(stg + lane * 128 + ((j ^ (lane & 7)) << 4), O[0][j], O[1][j], O[2][j], O[3][j]);
  fence_async_smem();
  __syncwarp();
  if (lane == 0) {
    tma_st2(&p.att_st, stg, 128 * n + 64 * t, 128 * m + 32 * w);
    bulk_commit();
    bulk_wait_all();
    st_release(g_flags + ((1 + i) * 16 + m) * 32 + 4 * n + w, tag);
  }
  __syncwarp();
  if (i == 0) colsum_partial<7, false>(p.w1_p, sb, m, n, wg, w * 32 + lane, tag);
  bar_arrive(BAR_GUARD + (wg ^ 1), 256);
}

__global__ void __cluster_dims__(2, 1, 1) __launch_bounds__(384, 1) fused_layers_kernel(const __grid_constant__ Params p) {
  extern __shared__ __align__(1024) uint8_t smem_raw[];
  const uint32_t sb = (uint32_t)__cvta_generic_to_shared(smem_raw);
  const int tid = threadIdx.x, lane = tid & 31, wg = tid >> 7, w = (tid >> 5) & 3;

  int m, n;
  {
    const int c = blockIdx.x >> 1;
    int g, j;
    if (c < 4) { g = 0; j = 4 + c; }
    else if (c < 36) { g = (c - 4) & 7; j = (c - 4) >> 3; }
    else { g = 1 + (c - 36) % 7; j = 4 + (c - 36) / 7; }
    m = (g >> 2) * 8 + j;
    n = (g & 3) * 2 + (blockIdx.x & 1);
  }
  const uint32_t full0 = sb + OFF_BAR, empty0 = full0 + 8 * NBAR, xready = full0 + 16 * NBAR;
  if (tid == 0) {
    for (int s = 0; s < NBAR; s++) {
      mbar_init(full0 + 8 * s, 2);
      mbar_init(empty0 + 8 * s, 4);
    }
    mbar_init(xready, 4);
    asm volatile("fence.mbarrier_init.release.cluster;" ::: "memory");
    fence_async_smem();
  }
  __syncthreads();

  if (wg == 2) {
    asm volatile("setmaxnreg.dec.sync.aligned.u32 40;");
    if (w == 0) {
      if (lane == 0) {
        Reclaim rc;
        int g = 0, b = 0;
        for (int i = 0; i < 14; i++) {
          const int layer = i >= 7, t = i - 7 * layer, z = tile_z(t), nkb = tile_nkb(t);
          const CUtensorMap* map; int c0, c2;
          weight_coords(p, t, n, map, c0, c2);
          int pp = layer * UNITS_PER_LAYER + tile_p0(t), pos = tile_p0(t) % RING_UNITS;
          for (int j = 0; j < nkb; j++) {
            rc.wait_for(g, pp + z, empty0);
            mbar_expect_tx(full0 + 8 * b, (z - 2) * UNIT);
            tma_ld3(sb + pos * UNIT + 16384, map, full0 + 8 * b, c0, 64 * korder(t, j, n), c2);
            if (j == 4 && i < 13) {
              const int t2 = t == 6 ? 0 : t + 1;
              const CUtensorMap* map2; int d0, d2;
              weight_coords(p, t2, n, map2, d0, d2);
              for (int kb = m; kb < tile_nkb(t2); kb += 16) tma_pf3(map2, d0, 64 * kb, d2);
            }
            g++;
            if (++b == NBAR) b = 0;
            pp += z; pos += z;
            if (pos >= (int)RING_UNITS) pos -= RING_UNITS;
          }
        }
      }
    } else if (w == 1) {
      if (lane == 0) {
        mbar_expect_tx(xready, 32768);
        tma_ld2(sb + OFF_X, &p.xin_ld, xready, 128 * n, 128 * m);
        tma_ld2(sb + OFF_X + 16384, &p.xin_ld, xready, 128 * n + 64, 128 * m);
        mbar_arrive(xready); mbar_arrive(xready); mbar_arrive(xready);
      }
      const uint32_t tag = __ldcg(g_epoch + blockIdx.x) + 1;
      Reclaim rc;
      int g = 0, b = 0, cur_line = -1;
      uint32_t mask = 0;
      for (int i = 0; i < 14; i++) {
        const int layer = i >= 7, t = i - 7 * layer, z = tile_z(t), nkb = tile_nkb(t);
        const bool ownx = t != 2 && t != 6;
        const CUtensorMap* map = t == 2 ? &p.att_ld : t == 6 ? &p.h_ld : i < 2 ? &p.xin_ld : &p.out_ld;
        int pp = layer * UNITS_PER_LAYER + tile_p0(t), pos = tile_p0(t) % RING_UNITS;
        for (int j = 0; j < nkb; j++) {
          rc.wait_for(g, pp + z, empty0);
          if (ownx && j < 2) {
            if (lane == 0) mbar_arrive(full0 + 8 * b);
          } else {
            const int kb = korder(t, j, n);
            if (i >= 2) {
              int line, src;
              if (t < 2) { line = 7; src = kb >> 1; }
              else if (t == 2) { line = 1 + 7 * layer + (kb & 1); src = kb >> 1; }
              else if (t < 6) { line = 3 + 7 * layer; src = kb >> 1; }
              else { line = 4 + 7 * layer + (j >= 24) + (j >= 40); src = kb / 7; }
              if (line != cur_line) { cur_line = line; mask = 0; }
              const uint32_t need = 0xFu << (4 * src);
              if ((mask & need) != need) {
                mask = poll_line(g_flags + (line * 16 + m) * 32, tag, need, lane);
                fence_async_global();
              }
            }
            if (lane == 0) {
              mbar_expect_tx(full0 + 8 * b, 16384);
              tma_ld2(sb + pos * UNIT, map, full0 + 8 * b, 64 * kb, 128 * m);
            }
          }
          __syncwarp();
          g++;
          if (++b == NBAR) b = 0;
          pp += z; pos += z;
          if (pos >= (int)RING_UNITS) pos -= RING_UNITS;
        }
      }
    }
  } else {
    asm volatile("setmaxnreg.inc.sync.aligned.u32 232;");
    const uint32_t tag = __ldcg(g_epoch + blockIdx.x) + 1;
    if (wg == 1) {
      mbar_wait(xready, 0);
      uint32_t xp[4][16];
      const uint32_t xrow = sb + OFF_X + w * 4096 + lane * 128;
#pragma unroll
      for (int j = 0; j < 16; j++)
        ldsm4(xrow + (j >> 3) * 16384 + (((j & 7) ^ (lane & 7)) << 4), xp[0][j], xp[1][j], xp[2][j], xp[3][j]);
      write_partial_stats(xp, 0, 128 * m + 32 * w, n, lane);
      __syncwarp();
      if (lane == 0) st_release(g_flags + m * 32 + 4 * n + w, tag);
      __syncwarp();
      colsum_partial<6, true>(p.wqkv_p, sb, m, n, wg, tid & 127, tag);
      colsum_gather<6, true>(p, sb, n, tid & 127, tag);
      PROF_T(3);
      bar_arrive(BAR_GUARD + 0, 256);
    }
    const int mn = m * 8 + n;
#pragma unroll 1
    for (int i = wg; i < 14; i += 2) {
      const int t = i >= 7 ? i - 7 : i;
      if (t < 2) qkv_tile(p, sb, i, mn, tag);
      else if (t == 2 || t == 6) resid_tile(p, sb, i, mn, tag);
      else if (t == 3) ffn1_tile<192>(p, sb, i, mn, tag);
      else ffn1_tile<128>(p, sb, i, mn, tag);
      PROF_T(6 + i * 4);
    }
    if (threadIdx.x == 128) {
      g_epoch[blockIdx.x] = tag;
    }
  }
}

typedef CUresult (*EncodeFn)(CUtensorMap*, CUtensorMapDataType, cuuint32_t, void*, const cuuint64_t*, const cuuint64_t*,
                             const cuuint32_t*, const cuuint32_t*, CUtensorMapInterleave, CUtensorMapSwizzle,
                             CUtensorMapL2promotion, CUtensorMapFloatOOBfill);

void make_2d(EncodeFn enc, CUtensorMap* m, const void* ptr, uint64_t cols, uint64_t rows, uint32_t box_rows) {
  cuuint64_t d[2] = {cols, rows}, st[1] = {cols * 2};
  cuuint32_t b[2] = {64, box_rows}, e[2] = {1, 1};
  enc(m, CU_TENSOR_MAP_DATA_TYPE_BFLOAT16, 2, const_cast<void*>(ptr), d, st, b, e, CU_TENSOR_MAP_INTERLEAVE_NONE,
      CU_TENSOR_MAP_SWIZZLE_128B, CU_TENSOR_MAP_L2_PROMOTION_L2_128B, CU_TENSOR_MAP_FLOAT_OOB_FILL_NONE);
}
void make_3d(EncodeFn enc, CUtensorMap* m, const void* ptr, uint64_t d0, uint64_t rows, uint64_t d2, uint64_t row_bytes,
             uint64_t chunk_bytes, uint32_t box_chunks) {
  cuuint64_t d[3] = {d0, rows, d2}, st[2] = {row_bytes, chunk_bytes};
  cuuint32_t b[3] = {64, 64, box_chunks}, e[3] = {1, 1, 1};
  enc(m, CU_TENSOR_MAP_DATA_TYPE_BFLOAT16, 3, const_cast<void*>(ptr), d, st, b, e, CU_TENSOR_MAP_INTERLEAVE_NONE,
      CU_TENSOR_MAP_SWIZZLE_128B, CU_TENSOR_MAP_L2_PROMOTION_L2_128B, CU_TENSOR_MAP_FLOAT_OOB_FILL_NONE);
}

}

extern "C" void kernel_launch(void* const* d_in, const int* in_sizes, int n_in, void* d_out, int out_size) {
  (void)in_sizes; (void)n_in; (void)out_size;
  static EncodeFn enc = nullptr;
  static void *att = nullptr, *hbuf = nullptr;
  if (!enc) {
    void* fn = nullptr;
    cudaDriverEntryPointQueryResult q;
    cudaGetDriverEntryPoint("cuTensorMapEncodeTiled", &fn, cudaEnableDefault, &q);
    enc = (EncodeFn)fn;
    cudaGetSymbolAddress(&att, g_att);
    cudaGetSymbolAddress(&hbuf, g_h);
    cudaFuncSetAttribute(fused_layers_kernel, cudaFuncAttributeMaxDynamicSharedMemorySize, SMEM_BYTES);
  }
  Params p;
  make_2d(enc, &p.xin_ld, d_in[0], DM, SEQ, 128);
  make_2d(enc, &p.out_ld, d_out, DM, SEQ, 128);
  make_2d(enc, &p.out_st, d_out, DM, SEQ, 32);
  make_2d(enc, &p.att_ld, att, DM, SEQ, 128);
  make_2d(enc, &p.att_st, att, DM, SEQ, 32);
  make_2d(enc, &p.h_ld, hbuf, FF, SEQ, 128);
  make_2d(enc, &p.h_st, hbuf, FF, SEQ, 32);
  make_3d(enc, &p.wqkv, d_in[1], DM, DM, 3, 3 * DM * 2, DM * 2, 3);
  make_3d(enc, &p.wo, d_in[2], 64, DM, DM / 64, DM * 2, 128, 2);
  make_3d(enc, &p.w1a, d_in[4], 64, DM, FF / 64, FF * 2, 128, 3);
  make_3d(enc, &p.w1b, d_in[4], 64, DM, FF / 64, FF * 2, 128, 2);
  make_3d(enc, &p.w2, d_in[6], 64, FF, DM / 64, DM * 2, 128, 2);
  p.wqkv_p = (const __nv_bfloat16*)d_in[1];
  p.w1_p = (const __nv_bfloat16*)d_in[4];
  p.b1 = (const __nv_bfloat16*)d_in[5];
  p.b2 = (const __nv_bfloat16*)d_in[7];
  fused_layers_kernel<<<NCTA, 384, SMEM_BYTES>>>(p);
}
```

```cpp
#include <cuda_runtime.h>
#include <cuda_bf16.h>
#include <cuda.h>
#include <stdint.h>

namespace {

constexpr int SEQ = 2048, DM = 1024, FF = 3584;
constexpr int NCTA = 128;
constexpr int NBAR = 5;

constexpr uint32_t RING_UNITS = 20, UNIT = 8192;
constexpr uint32_t OFF_X   = RING_UNITS * UNIT;
constexpr uint32_t OFF_STG = OFF_X + 32768;
constexpr uint32_t OFF_EXC = OFF_STG + 16384;
constexpr uint32_t OFF_CSQ = OFF_EXC + 12288;
constexpr uint32_t OFF_CSF = OFF_CSQ + 1536;
constexpr uint32_t OFF_ROW = OFF_CSF + 3584;
constexpr uint32_t OFF_BAR = OFF_ROW + 1024;
constexpr uint32_t SMEM_BYTES = OFF_BAR + 128;

constexpr int BAR_ORDER = 1, BAR_GUARD = 3, BAR_WG = 5;

struct Params {
  CUtensorMap xin_ld, out_ld, out_st, att_ld, att_st, h_ld, h_st, wqkv, wo, w1a, w1b, w2;
  const __nv_bfloat16 *wqkv_p, *w1_p, *b1, *b2;
  int by_smid;
};

__device__ __nv_bfloat16 g_att[SEQ * DM];
__device__ __nv_bfloat16 g_h[SEQ * FF];
__device__ float4 g_stats[4 * SEQ * 4];
__device__ uint4 g_halo[2 * 2 * 16 * 8 * 256];
__device__ float g_csp[16 * (3 * DM + FF)];
__device__ uint32_t g_flags[15 * 16 * 32];
__device__ uint32_t g_hflag[2 * 2 * 16 * 8];
__device__ uint32_t g_cflag[2 * 8 * 32];
__device__ uint32_t g_epoch[NCTA + 4];
#define PROF_T(idx)

__device__ __forceinline__ void mbar_init(uint32_t bar, int cnt) {
  asm volatile("mbarrier.init.shared::cta.b64 [%0], %1;" ::"r"(bar), "r"(cnt));
}
__device__ __forceinline__ void mbar_expect_tx(uint32_t bar, uint32_t bytes) {
  asm volatile("mbarrier.arrive.expect_tx.shared::cta.b64 _, [%0], %1;" ::"r"(bar), "r"(bytes) : "memory");
}
__device__ __forceinline__ void mbar_arrive(uint32_t bar) {
  asm volatile("mbarrier.arrive.shared::cta.b64 _, [%0];" ::"r"(bar) : "memory");
}
__device__ __forceinline__ void mbar_wait(uint32_t bar, uint32_t parity) {
  asm volatile(
      "{\n.reg .pred p;\n.reg .u32 it;\nmov.u32 it, 0;\n"
      "WAIT_LOOP:\n"
      "mbarrier.try_wait.parity.shared::cta.b64 p, [%0], %1;\n"
      "@p bra WAIT_DONE;\n"
      "add.u32 it, it, 1;\n"
      "setp.lt.u32 p, it, 0x400000;\n"
      "@p bra WAIT_LOOP;\n"
      "trap;\n"
      "WAIT_DONE:\n}"
      ::"r"(bar), "r"(parity) : "memory");
}
__device__ __forceinline__ void bar_sync(int id, int n) { asm volatile("bar.sync %0, %1;" ::"r"(id), "r"(n) : "memory"); }
__device__ __forceinline__ void bar_arrive(int id, int n) { asm volatile("bar.arrive %0, %1;" ::"r"(id), "r"(n) : "memory"); }
__device__ __forceinline__ void tma_ld2(uint32_t dst, const CUtensorMap* m, uint32_t bar, int c0, int c1) {
  asm volatile("cp.async.bulk.tensor.2d.shared::cluster.global.mbarrier::complete_tx::bytes [%0], [%1, {%3, %4}], [%2];"
               ::"r"(dst), "l"(m), "r"(bar), "r"(c0), "r"(c1) : "memory");
}
__device__ __forceinline__ void tma_ld3(uint32_t dst, const CUtensorMap* m, uint32_t bar, int c0, int c1, int c2) {
  asm volatile("cp.async.bulk.tensor.3d.shared::cluster.global.mbarrier::complete_tx::bytes [%0], [%1, {%3, %4, %5}], [%2];"
               ::"r"(dst), "l"(m), "r"(bar), "r"(c0), "r"(c1), "r"(c2) : "memory");
}
__device__ __forceinline__ void tma_pf3(const CUtensorMap* m, int c0, int c1, int c2) {
  asm volatile("cp.async.bulk.prefetch.tensor.3d.L2.global [%0, {%1, %2, %3}];" ::"l"(m), "r"(c0), "r"(c1), "r"(c2) : "memory");
}
__device__ __forceinline__ void tma_st2(const CUtensorMap* m, uint32_t src, int c0, int c1) {
  asm volatile("cp.async.bulk.tensor.2d.global.shared::cta.bulk_group [%0, {%2, %3}], [%1];"
               ::"l"(m), "r"(src), "r"(c0), "r"(c1) : "memory");
}
__device__ __forceinline__ void bulk_commit() { asm volatile("cp.async.bulk.commit_group;" ::: "memory"); }
__device__ __forceinline__ void bulk_wait_read() { asm volatile("cp.async.bulk.wait_group.read 0;" ::: "memory"); }
__device__ __forceinline__ void bulk_wait_all() { asm volatile("cp.async.bulk.wait_group 0;" ::: "memory"); }
__device__ __forceinline__ void fence_async_smem() { asm volatile("fence.proxy.async.shared::cta;" ::: "memory"); }
__device__ __forceinline__ void fence_async_global() { asm volatile("fence.proxy.async.global;" ::: "memory"); }
__device__ __forceinline__ void st_release(uint32_t* p, uint32_t v) {
  asm volatile("st.release.gpu.global.u32 [%0], %1;" ::"l"(p), "r"(v) : "memory");
}
__device__ __forceinline__ uint32_t pack_bf16(float lo, float hi) {
  uint32_t r;
  asm("cvt.rn.bf16x2.f32 %0, %1, %2;" : "=r"(r) : "f"(hi), "f"(lo));
  return r;
}
__device__ __forceinline__ float bf_lo(uint32_t v) { return __uint_as_float(v << 16); }
__device__ __forceinline__ float bf_hi(uint32_t v) { return __uint_as_float(v & 0xffff0000u); }
__device__ __forceinline__ void stsm4(uint32_t addr, uint32_t r0, uint32_t r1, uint32_t r2, uint32_t r3) {
  asm volatile("stmatrix.sync.aligned.m8n8.x4.shared.b16 [%0], {%1, %2, %3, %4};"
               ::"r"(addr), "r"(r0), "r"(r1), "r"(r2), "r"(r3) : "memory");
}
__device__ __forceinline__ void ldsm4(uint32_t addr, uint32_t& r0, uint32_t& r1, uint32_t& r2, uint32_t& r3) {
  asm volatile("ldmatrix.sync.aligned.m8n8.x4.shared.b16 {%0, %1, %2, %3}, [%4];"
               : "=r"(r0), "=r"(r1), "=r"(r2), "=r"(r3) : "r"(addr) : "memory");
}
__device__ __forceinline__ uint32_t movtrans(uint32_t a) {
  uint32_t d;
  asm volatile("movmatrix.sync.aligned.m8n8.trans.b16 %0, %1;" : "=r"(d) : "r"(a));
  return d;
}
__device__ __forceinline__ void mma16816(float (&c)[4], uint32_t a0, uint32_t a1, uint32_t a2, uint32_t a3, uint32_t b0, uint32_t b1) {
  asm volatile("mma.sync.aligned.m16n8k16.row.col.f32.bf16.bf16.f32 {%0,%1,%2,%3}, {%4,%5,%6,%7}, {%8,%9}, {%0,%1,%2,%3};"
               : "+f"(c[0]), "+f"(c[1]), "+f"(c[2]), "+f"(c[3])
               : "r"(a0), "r"(a1), "r"(a2), "r"(a3), "r"(b0), "r"(b1));
}
__device__ __forceinline__ float2 lds_f2(uint32_t a) {
  float2 v;
  asm volatile("ld.shared.v2.f32 {%0, %1}, [%2];" : "=f"(v.x), "=f"(v.y) : "r"(a) : "memory");
  return v;
}
__device__ __forceinline__ float4 lds_f4(uint32_t a) {
  float4 v;
  asm volatile("ld.shared.v4.f32 {%0, %1, %2, %3}, [%4];" : "=f"(v.x), "=f"(v.y), "=f"(v.z), "=f"(v.w) : "r"(a) : "memory");
  return v;
}
__device__ __forceinline__ float lds_f(uint32_t a) {
  float v;
  asm volatile("ld.shared.f32 %0, [%1];" : "=f"(v) : "r"(a) : "memory");
  return v;
}
__device__ __forceinline__ void sts_f2(uint32_t a, float x, float y) {
  asm volatile("st.shared.v2.f32 [%0], {%1, %2};" ::"r"(a), "f"(x), "f"(y) : "memory");
}
__device__ __forceinline__ void lds_u4(uint32_t a, uint32_t& x, uint32_t& y, uint32_t& z, uint32_t& w) {
  asm volatile("ld.shared.v4.u32 {%0, %1, %2, %3}, [%4];" : "=r"(x), "=r"(y), "=r"(z), "=r"(w) : "r"(a) : "memory");
}
__device__ __forceinline__ float ex2(float x) {
  float y;
  asm("ex2.approx.ftz.f32 %0, %1;" : "=f"(y) : "f"(x));
  return y;
}
__device__ __forceinline__ float rcp_hw(float x) {
  float y;
  asm("rcp.approx.ftz.f32 %0, %1;" : "=f"(y) : "f"(x));
  return y;
}
__device__ __forceinline__ float tanh_hw(float x) {
  float y;
  asm("tanh.approx.f32 %0, %1;" : "=f"(y) : "f"(x));
  return y;
}
__device__ __forceinline__ float quad_sum(float v) {
  v += __shfl_xor_sync(0xffffffffu, v, 1);
  return v + __shfl_xor_sync(0xffffffffu, v, 2);
}
__device__ __forceinline__ float quad_max(float v) {
  v = fmaxf(v, __shfl_xor_sync(0xffffffffu, v, 1));
  return fmaxf(v, __shfl_xor_sync(0xffffffffu, v, 2));
}

template <int N> __device__ __forceinline__ void wgmma_ss(float (&d)[96], uint64_t da, uint64_t db);
template <> __device__ __forceinline__ void wgmma_ss<128>(float (&d)[96], uint64_t da, uint64_t db) {
  asm volatile(
      "wgmma.mma_async.sync.aligned.m64n128k16.f32.bf16.bf16 {%0, %1, %2, %3, %4, %5, %6, %7, %8, %9, %10, %11, %12, %13, %14, %15, %16, %17, %18, %19, %20, %21, %22, %23, %24, %25, %26, %27, %28, %29, %30, %31, %32, %33, %34, %35, %36, %37, %38, %39, %40, %41, %42, %43, %44, %45, %46, %47, %48, %49, %50, %51, %52, %53, %54, %55, %56, %57, %58, %59, %60, %61, %62, %63}, %64, %65, 1, 1, 1, 0, 1;"
      : "+f"(d[0]), "+f"(d[1]), "+f"(d[2]), "+f"(d[3]), "+f"(d[4]), "+f"(d[5]), "+f"(d[6]), "+f"(d[7]), "+f"(d[8]), "+f"(d[9]), "+f"(d[10]), "+f"(d[11]), "+f"(d[12]), "+f"(d[13]), "+f"(d[14]), "+f"(d[15]), "+f"(d[16]), "+f"(d[17]), "+f"(d[18]), "+f"(d[19]), "+f"(d[20]), "+f"(d[21]), "+f"(d[22]), "+f"(d[23]), "+f"(d[24]), "+f"(d[25]), "+f"(d[26]), "+f"(d[27]), "+f"(d[28]), "+f"(d[29]), "+f"(d[30]), "+f"(d[31]), "+f"(d[32]), "+f"(d[33]), "+f"(d[34]), "+f"(d[35]), "+f"(d[36]), "+f"(d[37]), "+f"(d[38]), "+f"(d[39]), "+f"(d[40]), "+f"(d[41]), "+f"(d[42]), "+f"(d[43]), "+f"(d[44]), "+f"(d[45]), "+f"(d[46]), "+f"(d[47]), "+f"(d[48]), "+f"(d[49]), "+f"(d[50]), "+f"(d[51]), "+f"(d[52]), "+f"(d[53]), "+f"(d[54]), "+f"(d[55]), "+f"(d[56]), "+f"(d[57]), "+f"(d[58]), "+f"(d[59]), "+f"(d[60]), "+f"(d[61]), "+f"(d[62]), "+f"(d[63])
      : "l"(da), "l"(db));
}

template <> __device__ __forceinline__ void wgmma_ss<192>(float (&d)[96], uint64_t da, uint64_t db) {
  asm volatile(
      "wgmma.mma_async.sync.aligned.m64n192k16.f32.bf16.bf16 {%0, %1, %2, %3, %4, %5, %6, %7, %8, %9, %10, %11, %12, %13, %14, %15, %16, %17, %18, %19, %20, %21, %22, %23, %24, %25, %26, %27, %28, %29, %30, %31, %32, %33, %34, %35, %36, %37, %38, %39, %40, %41, %42, %43, %44, %45, %46, %47, %48, %49, %50, %51, %52, %53, %54, %55, %56, %57, %58, %59, %60, %61, %62, %63, %64, %65, %66, %67, %68, %69, %70, %71, %72, %73, %74, %75, %76, %77, %78, %79, %80, %81, %82, %83, %84, %85, %86, %87, %88, %89, %90, %91, %92, %93, %94, %95}, %96, %97, 1, 1, 1, 0, 1;"
      : "+f"(d[0]), "+f"(d[1]), "+f"(d[2]), "+f"(d[3]), "+f"(d[4]), "+f"(d[5]), "+f"(d[6]), "+f"(d[7]), "+f"(d[8]), "+f"(d[9]), "+f"(d[10]), "+f"(d[11]), "+f"(d[12]), "+f"(d[13]), "+f"(d[14]), "+f"(d[15]), "+f"(d[16]), "+f"(d[17]), "+f"(d[18]), "+f"(d[19]), "+f"(d[20]), "+f"(d[21]), "+f"(d[22]), "+f"(d[23]), "+f"(d[24]), "+f"(d[25]), "+f"(d[26]), "+f"(d[27]), "+f"(d[28]), "+f"(d[29]), "+f"(d[30]), "+f"(d[31]), "+f"(d[32]), "+f"(d[33]), "+f"(d[34]), "+f"(d[35]), "+f"(d[36]), "+f"(d[37]), "+f"(d[38]), "+f"(d[39]), "+f"(d[40]), "+f"(d[41]), "+f"(d[42]), "+f"(d[43]), "+f"(d[44]), "+f"(d[45]), "+f"(d[46]), "+f"(d[47]), "+f"(d[48]), "+f"(d[49]), "+f"(d[50]), "+f"(d[51]), "+f"(d[52]), "+f"(d[53]), "+f"(d[54]), "+f"(d[55]), "+f"(d[56]), "+f"(d[57]), "+f"(d[58]), "+f"(d[59]), "+f"(d[60]), "+f"(d[61]), "+f"(d[62]), "+f"(d[63]), "+f"(d[64]), "+f"(d[65]), "+f"(d[66]), "+f"(d[67]), "+f"(d[68]), "+f"(d[69]), "+f"(d[70]), "+f"(d[71]), "+f"(d[72]), "+f"(d[73]), "+f"(d[74]), "+f"(d[75]), "+f"(d[76]), "+f"(d[77]), "+f"(d[78]), "+f"(d[79]), "+f"(d[80]), "+f"(d[81]), "+f"(d[82]), "+f"(d[83]), "+f"(d[84]), "+f"(d[85]), "+f"(d[86]), "+f"(d[87]), "+f"(d[88]), "+f"(d[89]), "+f"(d[90]), "+f"(d[91]), "+f"(d[92]), "+f"(d[93]), "+f"(d[94]), "+f"(d[95])
      : "l"(da), "l"(db));
}

template <int R>
__device__ __forceinline__ void pin_regs(float (&a)[2][96]) {
#pragma unroll
  for (int m = 0; m < 2; m++)
#pragma unroll
    for (int i = 0; i < R; i++) asm volatile("" : "+f"(a[m][i])::"memory");
}

struct Ctx {
  uint32_t sb;
  int m, n, wg, w, lane;
};
__device__ __forceinline__ Ctx make_ctx(uint32_t sb, int mn) {
  int tid;
  asm volatile("mov.u32 %0, %%tid.x;" : "=r"(tid));
  asm volatile("" : "+r"(mn), "+r"(sb));
  return Ctx{sb, mn >> 3, mn & 7, tid >> 7, (tid >> 5) & 3, tid & 31};
}
#define UNPACK_CTX(c) const uint32_t sb = c.sb; const int m = c.m, n = c.n, wg = c.wg, w = c.w, lane = c.lane

__device__ __forceinline__ uint32_t poll_line(const uint32_t* line, uint32_t tag, uint32_t need, int lane) {
  uint32_t mask;
  asm volatile(
      "{\n.reg .pred p;\n.reg .u32 it, v;\nmov.u32 it, 0;\n"
      "POLL_LOOP:\n"
      "ld.acquire.gpu.global.u32 v, [%1];\n"
      "setp.eq.u32 p, v, %2;\n"
      "vote.sync.ballot.b32 %0, p, 0xffffffff;\n"
      "and.b32 v, %0, %3;\n"
      "setp.eq.u32 p, v, %3;\n"
      "@p bra.uni POLL_DONE;\n"
      "add.u32 it, it, 1;\n"
      "setp.lt.u32 p, it, 0x400000;\n"
      "@p bra.uni POLL_LOOP;\n"
      "trap;\n"
      "POLL_DONE:\n"
      "bar.warp.sync 0xffffffff;\n}"
      : "=&r"(mask) : "l"(line + lane), "r"(tag), "r"(need) : "memory");
  return mask;
}

constexpr int STAGES_PER_LAYER = 152;
__device__ __forceinline__ int nib(uint64_t v, int i) { return (int)(v >> (4 * i)) & 15; }
__device__ __forceinline__ bool tile_wide(int t) { return (0xB >> t) & 1; }
__device__ __forceinline__ int tile_pos0(int t) { return t < 3 ? 0 : t == 3 ? 5 : 4 * t - 8; }
constexpr uint64_t SEG_TILE = 0x6665432210ull, SEG_PERIOD = 0x2232221122ull, SEG_ADD = 0x5300001000ull;
constexpr uint64_t SEG_LINE = 0x6543332100ull;

__device__ __forceinline__ void weight_coords(const Params& p, int t, int n, const CUtensorMap*& map, int& c0, int& c2) {
  map = &p.wqkv + nib(0x4332100ull, t);
  c0 = t < 2 ? 128 * n + 64 * t : 0;
  c2 = t < 2 ? 0 : (t == 2 || t == 6) ? 2 * n : 7 * n + nib(0x530000ull, t);
}

template <bool IS_A>
__device__ __forceinline__ void producer(const Params& p, uint32_t sb, int m, int n, int lane, uint32_t tag) {
  const uint32_t full0 = sb + OFF_BAR, empty0 = full0 + 8 * NBAR;
  int inflight = 0, b = 0, rb = 0, rph = 0, pos = 0;
#pragma unroll 1
  for (int sg = 0; sg < 20; sg++) {
    const int layer = sg >= 10, s = sg - 10 * layer;
    const int t = nib(SEG_TILE, s), period = nib(SEG_PERIOD, s), add = nib(SEG_ADD, s);
    const bool wide = tile_wide(t), ownx = t != 2 && t != 6;
    const int z = wide ? 5 : 4, mul = t == 6 ? 7 : 2;
    int short_left = wide ? 99 : (s == 2 || s == 5) ? 4 : 0;
    if (s == 4 || s == 5) pos = tile_pos0(t);
    const CUtensorMap* map;
    int c0, c2;
    const uint32_t* line = g_flags + ((7 * layer + nib(SEG_LINE, s)) * 16 + m) * 32;
    uint32_t mask = sg < 2 ? 0xffffffffu : 0u;
    if (IS_A) {
      map = t == 2 ? &p.att_ld : t == 6 ? &p.h_ld : sg < 2 ? &p.xin_ld : &p.out_ld;
    } else {
      if (sg > 0 && sg < 17 && add == 0) {
        weight_coords(p, t == 6 ? 0 : t + 1, n, map, c0, c2);
        for (int kb = m; kb < (t == 5 ? 56 : 16); kb += 16) tma_pf3(map, c0, 64 * kb, c2);
      }
      weight_coords(p, t, n, map, c0, c2);
    }
#pragma unroll 1
    for (int q = 0; q < 8; q++) {
      int src = ((n & 6) + q) & 7;
      if (ownx && q < 2) src ^= n & 1;
      const bool own = ownx && q == 0;
      if (IS_A && !own) {
        const uint32_t need = 0xFu << (4 * src);
        if ((mask & need) != need) {
          mask = poll_line(line, tag, need, lane);
          fence_async_global();
        }
      }
      int kc = 64 * (mul * src + add);
#pragma unroll 1
      for (int a = 0; a < period; a++) {
        const int lag = short_left > 0 ? 3 : 4;
        short_left--;
        if (inflight > lag) {
          mbar_wait(empty0 + 8 * rb, rph);
          if (++rb == NBAR) { rb = 0; rph ^= 1; }
          if (--inflight > lag) {
            mbar_wait(empty0 + 8 * rb, rph);
            if (++rb == NBAR) { rb = 0; rph ^= 1; }
            inflight--;
          }
        }
        const uint32_t fb = full0 + 8 * b, slot = sb + pos * UNIT;
        if (IS_A) {
          if (lane == 0) {
            if (own) {
              mbar_arrive(fb);
            } else {
              mbar_expect_tx(fb, 16384);
              tma_ld2(slot + (z - 2) * UNIT, map, fb, kc, 128 * m);
            }
          }
        } else {
          mbar_expect_tx(fb, (z - 2) * UNIT);
          tma_ld3(slot, map, fb, c0, kc, c2);
        }
        kc += 64;
        inflight++;
        if (++b == NBAR) b = 0;
        pos += z;
        if (pos >= (int)RING_UNITS) pos -= RING_UNITS;
      }
    }
  }
}

template <int N>
__device__ __forceinline__ void mainloop(float (&acc)[2][96], uint32_t sb, int i, int mn) {
  constexpr int Z = 2 + N / 64;
  const int wg = i & 1, lane = threadIdx.x & 31;
  const int layer = i >= 7, t = i - 7 * layer;
  const int nkb = t == 6 ? 56 : 16;
  const int nown = (t == 2 || t == 6) ? 0 : 2;
  const int g0 = layer * STAGES_PER_LAYER + 16 * t;
  int b = g0 % NBAR, ph = (g0 / NBAR) & 1, pos = tile_pos0(t);
  const uint32_t full0 = sb + OFF_BAR, empty0 = full0 + 8 * NBAR;
  constexpr uint64_t DA = (1ull << 62) | ((uint64_t)(2048 >> 4) << 32) | (1ull << 16);
  constexpr uint64_t DB = (1ull << 62) | ((uint64_t)(1024 >> 4) << 32) | ((uint64_t)(8192 >> 4) << 16);
  pin_regs<N / 2>(acc);
  if (i > 0) bar_sync(BAR_ORDER + wg, 256);
  if (N == 192 && t != 1) mbar_wait(empty0 + 8 * NBAR, t == 3);
  int prev_b = 0;
#pragma unroll 1
  for (int j = 0; j < nkb; j++) {
    mbar_wait(full0 + 8 * b, ph);
    if (j == 0) PROF_T(4 + i * 4);
    const uint32_t slot = (sb & 0x3FFFF) + pos * UNIT;
    const uint32_t aa = j < nown ? (sb & 0x3FFFF) + OFF_X + j * 16384 : slot + (Z - 2) * UNIT;
    const uint64_t da = DA | (uint64_t)(aa >> 4);
    const uint64_t db = DB | (uint64_t)(slot >> 4);
    asm volatile("wgmma.fence.sync.aligned;" ::: "memory");
#pragma unroll
    for (int k = 0; k < 4; k++) {
      wgmma_ss<N>(acc[0], da + 2 * k, db + 128 * k);
      wgmma_ss<N>(acc[1], da + 64 + 2 * k, db + 128 * k);
    }
    asm volatile("wgmma.commit_group.sync.aligned;" ::: "memory");
    if (j == nkb - 1 && i < 13) bar_arrive(BAR_ORDER + (wg ^ 1), 256);
    asm volatile("wgmma.wait_group.sync.aligned 1;" ::: "memory");
    if (j > 0 && lane == 0) mbar_arrive(empty0 + 8 * prev_b);
    prev_b = b;
    if (++b == NBAR) { b = 0; ph ^= 1; }
    pos += Z;
    if (pos >= (int)RING_UNITS) pos -= RING_UNITS;
  }
  asm volatile("wgmma.wait_group.sync.aligned 0;" ::: "memory");
  pin_regs<N / 2>(acc);
  if (lane == 0) mbar_arrive(empty0 + 8 * prev_b);
  PROF_T(5 + i * 4);
}

#define ACC(q, j, e) acc[(q) & 1][4 * (j) + 2 * ((q) >> 1) + (e)]

__device__ __forceinline__ void write_partial_stats(const Ctx& c, int ln) {
  const uint32_t xrow = c.sb + OFF_X + c.w * 4096 + c.lane * 128;
  uint32_t u[4];
  lds_u4(xrow, u[0], u[1], u[2], u[3]);
  const float x0 = bf_lo(u[0]);
  float s0 = 0.f, s1 = 0.f, q0 = 0.f, q1 = 0.f;
#pragma unroll 2
  for (int j = 0; j < 16; j++) {
    lds_u4(xrow + (j >> 3) * 16384 + (((j & 7) ^ (c.lane & 7)) << 4), u[0], u[1], u[2], u[3]);
#pragma unroll
    for (int e = 0; e < 4; e++) {
      const float a = bf_lo(u[e]) - x0, d = bf_hi(u[e]) - x0;
      s0 += a; s1 += d;
      q0 = fmaf(a, a, q0); q1 = fmaf(d, d, q1);
    }
  }
  const float s = s0 + s1;
  reinterpret_cast<float2*>(g_stats)[(size_t)(ln * SEQ + 128 * c.m + 32 * c.w + c.lane) * 8 + c.n] =
      make_float2(fmaf(128.f, x0, s), fmaxf(q0 + q1 - s * s * (1.f / 128.f), 0.f));
}

__device__ __forceinline__ void row_stats(float (&rs)[4], float (&rm)[4], bool fresh, uint32_t sb, int ln, int line, int m,
                                          int w, int lane, uint32_t tag) {
  const uint32_t tab = sb + OFF_ROW + (32 * w + (lane >> 2)) * 8;
  if (fresh) {
    poll_line(g_flags + (line * 16 + m) * 32, tag, 0x11111111u << w, lane);
    float4 v[4];
#pragma unroll
    for (int q = 0; q < 4; q++) v[q] = __ldcg(g_stats + (size_t)(ln * SEQ + 128 * m + 32 * w + 8 * q + (lane >> 2)) * 4 + (lane & 3));
#pragma unroll
    for (int q = 0; q < 4; q++) {
      const float mean = quad_sum(v[q].x + v[q].z) * (1.f / DM);
      const float d0 = v[q].x * (1.f / 128.f) - mean, d1 = v[q].z * (1.f / 128.f) - mean;
      const float m2 = quad_sum(v[q].y + v[q].w + 128.f * (d0 * d0 + d1 * d1));
      rs[q] = rsqrtf(m2 * (1.f / DM) + 1e-5f);
      rm[q] = rs[q] * mean;
      if ((lane & 3) == 0) sts_f2(tab + q * 64, rs[q], rm[q]);
    }
  } else {
#pragma unroll
    for (int q = 0; q < 4; q++) {
      const float2 v = lds_f2(tab + q * 64);
      rs[q] = v.x;
      rm[q] = v.y;
    }
  }
}

__device__ __forceinline__ void attn_group(const uint32_t* qa, const uint32_t* qb, const uint32_t* k0, const uint32_t* k1,
                                           const uint32_t* k2, const uint32_t* k3, const uint32_t* v0, const uint32_t* v1,
                                           const uint32_t* v2, const uint32_t* v3, uint32_t* oa, uint32_t* ob,
                                           bool prev_valid, int lane) {
  float s[4][4];
#pragma unroll
  for (int kb = 0; kb < 4; kb++) {
    const uint32_t* kk = kb == 0 ? k0 : kb == 1 ? k1 : kb == 2 ? k2 : k3;
    s[kb][0] = s[kb][1] = s[kb][2] = s[kb][3] = 0.f;
    mma16816(s[kb], qa[0], qb[0], qa[1], qb[1], kk[0], kk[1]);
    mma16816(s[kb], qa[2], qb[2], qa[3], qb[3], kk[2], kk[3]);
  }
  const bool par = (lane >> 2) & 1;
  const bool early = (lane & 3) > (lane >> 3);
  constexpr float NEG = -1e30f;
  constexpr float SC = 0.17677669529663687f * 1.4426950408889634f;
  float la = par ? s[1][1] : s[1][0];
  float lb = early ? (par ? s[0][1] : s[0][0]) : (par ? s[2][1] : s[2][0]);
  float ha = par ? s[2][3] : s[2][2];
  float hb = early ? (par ? s[1][3] : s[1][2]) : (par ? s[3][3] : s[3][2]);
  if (!prev_valid) {
    la = NEG;
    if (early) { lb = NEG; hb = NEG; }
  }
  const float ml = quad_max(fmaxf(la, lb)), mh = quad_max(fmaxf(ha, hb));
  la = ex2((la - ml) * SC); lb = ex2((lb - ml) * SC);
  ha = ex2((ha - mh) * SC); hb = ex2((hb - mh) * SC);
  const float il = rcp_hw(quad_sum(la + lb)), ih = rcp_hw(quad_sum(ha + hb));
  const int sh = par ? 16 : 0;
  const uint32_t pla = pack_bf16(la * il, 0.f) << sh, plb = pack_bf16(lb * il, 0.f) << sh;
  const uint32_t pha = pack_bf16(ha * ih, 0.f) << sh, phb = pack_bf16(hb * ih, 0.f) << sh;
  const uint32_t e_l = early ? plb : 0u, e_h = early ? phb : 0u, l_l = early ? 0u : plb, l_h = early ? 0u : phb;
#pragma unroll
  for (int jn = 0; jn < 4; jn++) {
    float o[4] = {0.f, 0.f, 0.f, 0.f};
    mma16816(o, e_l, 0u, pla, e_h, v0[jn], v1[jn]);
    mma16816(o, l_l, pha, 0u, l_h, v2[jn], v3[jn]);
    oa[jn] = pack_bf16(o[0], o[1]);
    ob[jn] = pack_bf16(o[2], o[3]);
  }
}

__device__ __forceinline__ void colsum_partial(const Params& p, const Ctx& cx, bool qkv, uint32_t tag) {
  UNPACK_CTX(cx);
  const int tid = w * 32 + lane, cg = tid & 7, rg = tid >> 3;
  const int ld = qkv ? 3 * DM : FF;
  const __nv_bfloat16* W = (qkv ? p.wqkv_p + 128 * n : p.w1_p + 448 * n) + (size_t)(64 * m + 4 * rg) * ld + 8 * cg;
  const int nch = qkv ? 6 : 7;
  for (int c = 0; c < nch; c++) {
    const int col = qkv ? (c >> 1) * DM + (c & 1) * 64 : 64 * c;
    if ((lane & 7) < 4) asm volatile("prefetch.global.L2 [%0];" ::"l"(W + (size_t)(lane & 3) * ld + col - 8 * cg));
  }
  bar_sync(BAR_WG + wg, 128);
#pragma unroll 2
  for (int c = 0; c < nch; c++) {
    const int col = qkv ? (c >> 1) * DM + (c & 1) * 64 : 64 * c;
    uint4 v[4];
#pragma unroll
    for (int r = 0; r < 4; r++) v[r] = __ldcg(reinterpret_cast<const uint4*>(W + (size_t)r * ld + col));
    float a[8];
#pragma unroll
    for (int e = 0; e < 4; e++) {
      float lo = 0.f, hi = 0.f;
#pragma unroll
      for (int r = 0; r < 4; r++) {
        const uint32_t u = e == 0 ? v[r].x : e == 1 ? v[r].y : e == 2 ? v[r].z : v[r].w;
        lo += bf_lo(u);
        hi += bf_hi(u);
      }
      a[2 * e] = lo;
      a[2 * e + 1] = hi;
    }
    const bool u8 = lane & 8, u16 = lane & 16;
    float h4[4], h2[2];
#pragma unroll
    for (int e = 0; e < 4; e++) h4[e] = (u8 ? a[4 + e] : a[e]) + __shfl_xor_sync(0xffffffffu, u8 ? a[e] : a[4 + e], 8);
#pragma unroll
    for (int e = 0; e < 2; e++) h2[e] = (u16 ? h4[2 + e] : h4[e]) + __shfl_xor_sync(0xffffffffu, u16 ? h4[e] : h4[2 + e], 16);
    sts_f2(sb + OFF_EXC + (w * 448 + c * 64 + cg * 8 + (u8 ? 4 : 0) + (u16 ? 2 : 0)) * 4, h2[0], h2[1]);
  }
  bar_sync(BAR_WG + wg, 128);
  float* dst = g_csp + m * (3 * DM + FF) + (qkv ? 384 * n : 3 * DM + 448 * n);
#pragma unroll 1
  for (int c = tid; c < nch * 64; c += 128) {
    const uint32_t a = sb + OFF_EXC + c * 4;
    dst[c] = (lds_f(a) + lds_f(a + 1792)) + (lds_f(a + 3584) + lds_f(a + 5376));
  }
  bar_sync(BAR_WG + wg, 128);
  if (tid == 0) st_release(g_cflag + ((qkv ? 0 : 8) + n) * 32 + m, tag);
}

__device__ __forceinline__ void colsum_gather(const Params& p, const Ctx& cx, bool qkv, uint32_t tag) {
  const int n = cx.n, tid = cx.w * 32 + cx.lane;
  poll_line(g_cflag + ((qkv ? 0 : 8) + n) * 32, tag, 0xffffu, cx.lane);
  if (tid < (qkv ? 96 : 112)) {
    const float4* src = reinterpret_cast<const float4*>(g_csp + (qkv ? 384 * n : 3 * DM + 448 * n)) + tid;
    float4 s = make_float4(0.f, 0.f, 0.f, 0.f);
#pragma unroll 8
    for (int mm = 0; mm < 16; mm++) {
      const float4 v = __ldcg(src + mm * ((3 * DM + FF) / 4));
      s.x += v.x; s.y += v.y; s.z += v.z; s.w += v.w;
    }
    if (qkv) {
      const uint32_t a = cx.sb + OFF_CSQ + ((((tid >> 4) & 1) * 3 + (tid >> 5)) * 16 + (tid & 15)) * 16;
      sts_f2(a, s.x, s.y);
      sts_f2(a + 8, s.z, s.w);
    } else {
      const uint2 bb = __ldg(reinterpret_cast<const uint2*>(p.b1 + 448 * n) + tid);
      const uint32_t a = cx.sb + OFF_CSF + tid * 32;
      sts_f2(a, s.x, s.y);
      sts_f2(a + 8, bf_lo(bb.x), bf_hi(bb.x));
      sts_f2(a + 16, s.z, s.w);
      sts_f2(a + 24, bf_lo(bb.y), bf_hi(bb.y));
    }
  }
}

__device__ __forceinline__ void gelu_epilogue(const Params& p, float (&acc)[2][96], const Ctx& cx, int t, const float (&rs)[4],
                                              const float (&rm)[4]) {
  UNPACK_CTX(cx);
  (void)wg;
  const int col0 = t == 3 ? 0 : t == 4 ? 192 : 320, steps = t == 3 ? 6 : 4;
  const uint32_t stg = sb + OFF_STG + w * 4096;
  uint32_t ctab = sb + OFF_CSF + (col0 / 2 + (lane & 3)) * 16;
  float v[2][16];
#pragma unroll
  for (int r = 0; r < 16; r++) { v[0][r] = acc[0][r]; v[1][r] = acc[1][r]; }
#pragma unroll 1
  for (int it = 0; it < steps; it++) {
    uint32_t hp[4][4];
#pragma unroll
    for (int j = 0; j < 4; j++) {
      const float4 cb = lds_f4(ctab + j * 64);
#pragma unroll
      for (int q = 0; q < 4; q++) {
        float y[2];
#pragma unroll
        for (int e = 0; e < 2; e++) {
          const float x = fmaf(v[q & 1][4 * j + 2 * (q >> 1) + e], rs[q], fmaf(-rm[q], e ? cb.y : cb.x, e ? cb.w : cb.z));
          const float u = x * fmaf(x * x, 0.7978845608028654f * 0.044715f, 0.7978845608028654f);
          const float hx = 0.5f * x;
          y[e] = fmaf(hx, tanh_hw(u), hx);
        }
        hp[j][q] = pack_bf16(y[0], y[1]);
      }
    }
    ctab += 256;
    if (!(it & 1)) {
      if (lane == 0) bulk_wait_read();
      __syncwarp();
    }
#pragma unroll
    for (int j = 0; j < 4; j++)
      stsm4(stg + lane * 128 + (((4 * (it & 1) + j) ^ (lane & 7)) << 4), hp[j][0], hp[j][1], hp[j][2], hp[j][3]);
    if (it & 1) {
      fence_async_smem();
      __syncwarp();
      if (lane == 0) {
        tma_st2(&p.h_st, stg, 448 * n + col0 + 32 * (it - 1), 128 * m + 32 * w);
        bulk_commit();
      }
    }
#define REFILL(k) case k - 1: _Pragma("unroll") for (int r = 0; r < 16; r++) { \
      asm volatile("mov.b32 %0, %1;" : "=f"(v[0][r]) : "f"(acc[0][16 * k + r])); \
      asm volatile("mov.b32 %0, %1;" : "=f"(v[1][r]) : "f"(acc[1][16 * k + r])); } break;
    switch (it) {
      REFILL(1) REFILL(2) REFILL(3) REFILL(4)
      default:
#pragma unroll
        for (int r = 0; r < 16; r++) {
          asm volatile("mov.b32 %0, %1;" : "=f"(v[0][r]) : "f"(acc[0][80 + r]));
          asm volatile("mov.b32 %0, %1;" : "=f"(v[1][r]) : "f"(acc[1][80 + r]));
        }
    }
#undef REFILL
  }
}

__device__ __forceinline__ void attn_epilogue(const Params& p, float (&acc)[2][96], const Ctx& cx, int layer, int t,
                                              const float (&rs)[4], const float (&rm)[4], uint32_t tag) {
  UNPACK_CTX(cx);
  uint32_t Q[4][8], K[4][8], V[4][8];
  const uint32_t ctab = sb + OFF_CSQ + (t * 192 + 2 * (lane & 3)) * 4;
  const int slot = ((layer * 2 + t) * 16 + m) * 8 + n;
  uint4* const exc = reinterpret_cast<uint4*>(__cvta_shared_to_generic(sb + OFF_EXC));
#pragma unroll
  for (int jj = 0; jj < 24; jj++) {
    const int j = (jj + 8) % 24;
    const float2 cs = lds_f2(ctab + j * 32);
#pragma unroll
    for (int q = 0; q < 4; q++) {
      const uint32_t u = pack_bf16(fmaf(ACC(q, j, 0), rs[q], -rm[q] * cs.x), fmaf(ACC(q, j, 1), rs[q], -rm[q] * cs.y));
      if (j < 8) Q[q][j] = u;
      else if (j < 16) K[q][j - 8] = u;
      else V[q][j - 16] = movtrans(u);
    }
    if (jj == 15) {
      uint4* e = (w < 3 ? exc + w * 256 : g_halo + slot * 256) + lane;
#pragma unroll
      for (int h = 0; h < 2; h++) {
        e[(0 + h) * 32] = make_uint4(K[2][4 * h], K[2][4 * h + 1], K[2][4 * h + 2], K[2][4 * h + 3]);
        e[(2 + h) * 32] = make_uint4(K[3][4 * h], K[3][4 * h + 1], K[3][4 * h + 2], K[3][4 * h + 3]);
        e[(4 + h) * 32] = make_uint4(V[2][4 * h], V[2][4 * h + 1], V[2][4 * h + 2], V[2][4 * h + 3]);
        e[(6 + h) * 32] = make_uint4(V[3][4 * h], V[3][4 * h + 1], V[3][4 * h + 2], V[3][4 * h + 3]);
      }
      __syncwarp();
      if (w == 3 && lane == 0) st_release(g_hflag + slot, tag);
      __syncwarp();
    }
  }
  uint32_t O[4][8];
#pragma unroll
  for (int h = 0; h < 2; h++)
    attn_group(&Q[2][4 * h], &Q[3][4 * h], &K[0][4 * h], &K[1][4 * h], &K[2][4 * h], &K[3][4 * h], &V[0][4 * h], &V[1][4 * h],
               &V[2][4 * h], &V[3][4 * h], &O[2][4 * h], &O[3][4 * h], true, lane);
  bar_sync(BAR_WG + wg, 128);
  if (w == 0 && m > 0) poll_line(g_hflag + slot - 8, tag, 1u, 0);
  const uint4* src = (w > 0 ? exc + (w - 1) * 256 : m > 0 ? g_halo + (slot - 8) * 256 : exc) + lane;
  uint32_t P[8][4];
#pragma unroll
  for (int r = 0; r < 8; r++)
    asm volatile("ld.volatile.v4.u32 {%0, %1, %2, %3}, [%4];"
                 : "=r"(P[r][0]), "=r"(P[r][1]), "=r"(P[r][2]), "=r"(P[r][3]) : "l"(src + r * 32) : "memory");
#pragma unroll
  for (int h = 0; h < 2; h++)
    attn_group(&Q[0][4 * h], &Q[1][4 * h], P[0 + h], P[2 + h], &K[0][4 * h], &K[1][4 * h], P[4 + h], P[6 + h],
               &V[0][4 * h], &V[1][4 * h], &O[0][4 * h], &O[1][4 * h], (m | w) != 0, lane);
  const uint32_t stg = sb + OFF_STG + w * 4096;
#pragma unroll
  for (int j = 0; j < 8; j++) stsm4(stg + lane * 128 + ((j ^ (lane & 7)) << 4), O[0][j], O[1][j], O[2][j], O[3][j]);
  fence_async_smem();
  __syncwarp();
  if (lane == 0) {
    tma_st2(&p.att_st, stg, 128 * n + 64 * t, 128 * m + 32 * w);
    bulk_commit();
  }
}

__device__ __forceinline__ void consumer_tile(const Params& p, uint32_t sb0, int i, int mn, uint32_t tag) {
  bool resid = i == -1;
  if (i >= 0) {
    const int t0 = i >= 7 ? i - 7 : i;
    resid = t0 == 2 || t0 == 6;
    float acc[2][96];
    if (resid) {
      const Ctx cx = make_ctx(sb0, mn);
      const uint32_t xrow = cx.sb + OFF_X + cx.w * 4096 + cx.lane * 128;
      const uint32_t* b2 = reinterpret_cast<const uint32_t*>(p.b2 + 128 * cx.n) + (cx.lane & 3);
#pragma unroll
      for (int j = 0; j < 16; j++) {
        uint32_t r[4], bb = 0;
        ldsm4(xrow + (j >> 3) * 16384 + (((j & 7) ^ (cx.lane & 7)) << 4), r[0], r[1], r[2], r[3]);
        if (t0 == 6) bb = __ldg(b2 + 4 * j);
#pragma unroll
        for (int q = 0; q < 4; q++) {
          ACC(q, j, 0) = bf_lo(r[q]) + bf_lo(bb);
          ACC(q, j, 1) = bf_hi(r[q]) + bf_hi(bb);
        }
      }
    } else {
#pragma unroll
      for (int r = 0; r < 64; r++) acc[0][r] = acc[1][r] = 0.f;
    }
#pragma unroll
    for (int r = 64; r < 96; r++) acc[0][r] = acc[1][r] = 0.f;
    if (tile_wide(t0)) mainloop<192>(acc, sb0, i, mn);
    else mainloop<128>(acc, sb0, i, mn);
    asm volatile("" : "+r"(i));
    const int layer = i >= 7, t = i - 7 * layer;
    const Ctx cx = make_ctx(sb0, mn);
    UNPACK_CTX(cx);
    if (t == 2 || t == 6) {
      const uint32_t xrow = sb + OFF_X + w * 4096 + lane * 128;
#pragma unroll
      for (int j = 0; j < 16; j++)
        stsm4(xrow + (j >> 3) * 16384 + (((j & 7) ^ (lane & 7)) << 4), pack_bf16(ACC(0, j, 0), ACC(0, j, 1)),
              pack_bf16(ACC(1, j, 0), ACC(1, j, 1)), pack_bf16(ACC(2, j, 0), ACC(2, j, 1)), pack_bf16(ACC(3, j, 0), ACC(3, j, 1)));
      fence_async_smem();
      __syncwarp();
      if (lane == 0) {
        mbar_arrive(sb + OFF_BAR + 16 * NBAR);
        tma_st2(&p.out_st, sb + OFF_X + w * 4096, 128 * n, 128 * m + 32 * w);
        tma_st2(&p.out_st, sb + OFF_X + 16384 + w * 4096, 128 * n + 64, 128 * m + 32 * w);
        bulk_commit();
      }
    } else {
      bar_sync(BAR_GUARD + wg, 256);
      float rs[4], rm[4];
      row_stats(rs, rm, t == 0 || t == 3, sb, 2 * layer + (t >= 3), 7 * layer + t, m, w, lane, tag);
      if (t < 2) attn_epilogue(p, acc, cx, layer, t, rs, rm, tag);
      else gelu_epilogue(p, acc, cx, t, rs, rm);
    }
  } else {
    mbar_wait(sb0 + OFF_BAR + 16 * NBAR, 0);
  }
  asm volatile("" : "+r"(i));
  const Ctx cx = make_ctx(sb0, mn);
  if (i == 13) {
    if (cx.lane == 0) bulk_wait_read();
    bar_sync(BAR_GUARD + cx.wg, 256);
    return;
  }
  if (resid) write_partial_stats(cx, (i + 3) >> 2);
  __syncwarp();
  if (cx.lane == 0) {
    bulk_wait_all();
    st_release(g_flags + ((1 + i) * 16 + cx.m) * 32 + 4 * cx.n + cx.w, tag);
  }
  __syncwarp();
  if (resid && i >= 0) bar_sync(BAR_GUARD + cx.wg, 256);
  if (i <= 0) colsum_partial(p, cx, i < 0, tag);
  if (i == -1 || i == 2) colsum_gather(p, cx, i < 0, tag);
  bar_arrive(BAR_GUARD + (cx.wg ^ 1), 256);
}

__global__ void __cluster_dims__(2, 1, 1) __launch_bounds__(384, 1) fused_layers_kernel(const __grid_constant__ Params p) {
  extern __shared__ __align__(1024) uint8_t smem_raw[];
  const uint32_t sb = (uint32_t)__cvta_generic_to_shared(smem_raw);
  const int tid = threadIdx.x, lane = tid & 31, wg = tid >> 7, w = (tid >> 5) & 3;

  int mn;
  {
    int id = blockIdx.x;
    if (p.by_smid) asm volatile("mov.u32 %0, %%smid;" : "=r"(id));
    else if (id >= 120) id += 4;
    const int c = id >> 1;
    int g, j;
    if (c < 32) { g = c & 7; j = c >> 3; }
    else if (c < 60) { g = 1 + (c - 32) % 7; j = 4 + (c - 32) / 7; }
    else { g = 0; j = c - 58; }
    mn = ((g >> 2) * 8 + j) * 8 + (g & 3) * 2 + (id & 1);
    if (c == 60 || c == 61) {
      if (tid < 32) {
        const uint32_t tag = __ldcg(g_epoch + NCTA + (id & 3)) + 1;
        for (int nn = 0; nn < 8; nn++) poll_line(g_cflag + nn * 32, tag, 0xffffu, lane);
        if (tid == 0) g_epoch[NCTA + (id & 3)] = tag;
      }
      return;
    }
  }
  const int m = mn >> 3, n = mn & 7;
  const uint32_t full0 = sb + OFF_BAR, empty0 = full0 + 8 * NBAR, xready = full0 + 16 * NBAR;
  if (tid == 0) {
    for (int s = 0; s < NBAR; s++) {
      mbar_init(full0 + 8 * s, 2);
      mbar_init(empty0 + 8 * s, 4);
    }
    mbar_init(xready, 4);
    fence_async_smem();
  }
  __syncthreads();

  if (wg == 2) {
    asm volatile("setmaxnreg.dec.sync.aligned.u32 40;");
    if (w == 0) {
      if (lane == 0) producer<false>(p, sb, m, n, lane, 0);
    } else if (w == 1) {
      if (lane == 0) {
        mbar_expect_tx(xready, 32768);
        tma_ld2(sb + OFF_X, &p.xin_ld, xready, 128 * n, 128 * m);
        tma_ld2(sb + OFF_X + 16384, &p.xin_ld, xready, 128 * n + 64, 128 * m);
        mbar_arrive(xready); mbar_arrive(xready); mbar_arrive(xready);
      }
      producer<true>(p, sb, m, n, lane, __ldcg(g_epoch + mn) + 1);
    }
  } else {
    asm volatile("setmaxnreg.inc.sync.aligned.u32 232;");
    const uint32_t tag = __ldcg(g_epoch + mn) + 1;
#pragma unroll 1
    for (int i = -wg; i < 14; i += 2) {
      consumer_tile(p, sb, i, mn, tag);
      PROF_T(i < 0 ? 3 : 6 + i * 4);
    }
    if (threadIdx.x == 128) {
      g_epoch[mn] = tag;
    }
  }
}

typedef CUresult (*EncodeFn)(CUtensorMap*, CUtensorMapDataType, cuuint32_t, void*, const cuuint64_t*, const cuuint64_t*,
                             const cuuint32_t*, const cuuint32_t*, CUtensorMapInterleave, CUtensorMapSwizzle,
                             CUtensorMapL2promotion, CUtensorMapFloatOOBfill);

void make_2d(EncodeFn enc, CUtensorMap* m, const void* ptr, uint64_t cols, uint64_t rows, uint32_t box_rows) {
  cuuint64_t d[2] = {cols, rows}, st[1] = {cols * 2};
  cuuint32_t b[2] = {64, box_rows}, e[2] = {1, 1};
  enc(m, CU_TENSOR_MAP_DATA_TYPE_BFLOAT16, 2, const_cast<void*>(ptr), d, st, b, e, CU_TENSOR_MAP_INTERLEAVE_NONE,
      CU_TENSOR_MAP_SWIZZLE_128B, CU_TENSOR_MAP_L2_PROMOTION_L2_128B, CU_TENSOR_MAP_FLOAT_OOB_FILL_NONE);
}
void make_3d(EncodeFn enc, CUtensorMap* m, const void* ptr, uint64_t d0, uint64_t rows, uint64_t d2, uint64_t row_bytes,
             uint64_t chunk_bytes, uint32_t box_chunks) {
  cuuint64_t d[3] = {d0, rows, d2}, st[2] = {row_bytes, chunk_bytes};
  cuuint32_t b[3] = {64, 64, box_chunks}, e[3] = {1, 1, 1};
  enc(m, CU_TENSOR_MAP_DATA_TYPE_BFLOAT16, 3, const_cast<void*>(ptr), d, st, b, e, CU_TENSOR_MAP_INTERLEAVE_NONE,
      CU_TENSOR_MAP_SWIZZLE_128B, CU_TENSOR_MAP_L2_PROMOTION_L2_128B, CU_TENSOR_MAP_FLOAT_OOB_FILL_NONE);
}

}

extern "C" void kernel_launch(void* const* d_in, const int* in_sizes, int n_in, void* d_out, int out_size) {
  (void)in_sizes; (void)n_in; (void)out_size;
  static EncodeFn enc = nullptr;
  static void *att = nullptr, *hbuf = nullptr;
  static int by_smid = 0;
  if (!enc) {
    void* fn = nullptr;
    cudaDriverEntryPointQueryResult q;
    cudaGetDriverEntryPoint("cuTensorMapEncodeTiled", &fn, cudaEnableDefault, &q);
    enc = (EncodeFn)fn;
    cudaGetSymbolAddress(&att, g_att);
    cudaGetSymbolAddress(&hbuf, g_h);
    cudaFuncSetAttribute(fused_layers_kernel, cudaFuncAttributeMaxDynamicSharedMemorySize, SMEM_BYTES);
    int sms = 0, clusters = 0, dev = 0;
    cudaGetDevice(&dev);
    cudaDeviceGetAttribute(&sms, cudaDevAttrMultiProcessorCount, dev);
    cudaLaunchConfig_t cfg = {};
    cfg.gridDim = dim3(132);
    cfg.blockDim = dim3(384);
    cfg.dynamicSmemBytes = SMEM_BYTES;
    cudaLaunchAttribute at[1];
    at[0].id = cudaLaunchAttributeClusterDimension;
    at[0].val.clusterDim.x = 2; at[0].val.clusterDim.y = 1; at[0].val.clusterDim.z = 1;
    cfg.attrs = at;
    cfg.numAttrs = 1;
    if (cudaOccupancyMaxActiveClusters(&clusters, fused_layers_kernel, &cfg) != cudaSuccess) (void)cudaGetLastError();
    by_smid = sms == 132 && clusters == 66;
  }
  Params p;
  make_2d(enc, &p.xin_ld, d_in[0], DM, SEQ, 128);
  make_2d(enc, &p.out_ld, d_out, DM, SEQ, 128);
  make_2d(enc, &p.out_st, d_out, DM, SEQ, 32);
  make_2d(enc, &p.att_ld, att, DM, SEQ, 128);
  make_2d(enc, &p.att_st, att, DM, SEQ, 32);
  make_2d(enc, &p.h_ld, hbuf, FF, SEQ, 128);
  make_2d(enc, &p.h_st, hbuf, FF, SEQ, 32);
  make_3d(enc, &p.wqkv, d_in[1], DM, DM, 3, 3 * DM * 2, DM * 2, 3);
  make_3d(enc, &p.wo, d_in[2], 64, DM, DM / 64, DM * 2, 128, 2);
  make_3d(enc, &p.w1a, d_in[4], 64, DM, FF / 64, FF * 2, 128, 3);
  make_3d(enc, &p.w1b, d_in[4], 64, DM, FF / 64, FF * 2, 128, 2);
  make_3d(enc, &p.w2, d_in[6], 64, FF, DM / 64, DM * 2, 128, 2);
  p.wqkv_p = (const __nv_bfloat16*)d_in[1];
  p.w1_p = (const __nv_bfloat16*)d_in[4];
  p.b1 = (const __nv_bfloat16*)d_in[5];
  p.b2 = (const __nv_bfloat16*)d_in[7];
  p.by_smid = by_smid;
  fused_layers_kernel<<<by_smid ? 132 : NCTA, 384, SMEM_BYTES>>>(p);
}
```

```cpp
#include <cuda_runtime.h>
#include <cuda_bf16.h>
#include <cuda.h>
#include <stdint.h>

namespace {

constexpr int SEQ = 2048, DM = 1024, FF = 3584;
constexpr int NCTA = 128;
constexpr int NBAR = 5;

constexpr uint32_t RING_UNITS = 20, UNIT = 8192;
constexpr uint32_t OFF_X   = RING_UNITS * UNIT;
constexpr uint32_t OFF_STG = OFF_X + 32768;
constexpr uint32_t OFF_CSQ = OFF_STG + 18432;
constexpr uint32_t OFF_CSF = OFF_CSQ + 1536;
constexpr uint32_t OFF_ROW = OFF_CSF + 3584;
constexpr uint32_t OFF_BAR = OFF_ROW + 1024;
constexpr uint32_t SMEM_BYTES = OFF_BAR + 128;
constexpr uint32_t BAR_FULL = OFF_BAR, BAR_EMPTY = OFF_BAR + 8 * NBAR, BAR_XREADY = OFF_BAR + 16 * NBAR;
constexpr uint32_t OFF_TAG = OFF_BAR + 96, OFF_ZERO = OFF_BAR + 112;

constexpr uint32_t DESC_A_HI = 0x40000000u | (2048 >> 4), DESC_A_LO = 1u << 16;
constexpr uint32_t DESC_B_HI = 0x40000000u | (1024 >> 4), DESC_B_LO = (8192u >> 4) << 16;

constexpr int BAR_ORDER = 1, BAR_GUARD = 3, BAR_WG = 5, BAR_GO = 7, BAR_DONE = 8;
#define WIN1 8
#define WIN2 4

struct Params {
  CUtensorMap xin_ld, out_ld, out_st, att_ld, att_st, h_ld, h_st, wqkv, wo, w1a, w1b, w2;
  const __nv_bfloat16 *wqkv_p, *w1_p, *b1, *b2;
  int by_smid;
};

__device__ __nv_bfloat16 g_att[SEQ * DM];
__device__ __nv_bfloat16 g_h[SEQ * FF];
__device__ float4 g_stats[4 * SEQ * 4];
__device__ uint4 g_halo[2 * 2 * 16 * 8 * 384];
__device__ float g_csp[16 * (3 * DM + FF)];
__device__ uint32_t g_flags[15 * 16 * 32];
__device__ uint32_t g_sflag[4 * 16 * 32];
__device__ uint32_t g_cflag[2 * 8 * 32];
__device__ uint32_t g_epoch[NCTA + 4];
#define PROF_T(idx)

__device__ __forceinline__ void mbar_init(uint32_t bar, int cnt) {
  asm volatile("mbarrier.init.shared::cta.b64 [%0], %1;" ::"r"(bar), "r"(cnt));
}
__device__ __forceinline__ void mbar_expect_tx(uint32_t bar, uint32_t bytes) {
  asm volatile("mbarrier.arrive.expect_tx.shared::cta.b64 _, [%0], %1;" ::"r"(bar), "r"(bytes) : "memory");
}
__device__ __forceinline__ void mbar_arrive(uint32_t bar) {
  asm volatile("mbarrier.arrive.shared::cta.b64 _, [%0];" ::"r"(bar) : "memory");
}
__device__ __forceinline__ void mbar_wait(uint32_t bar, uint32_t parity) {
  asm volatile(
      "{\n.reg .pred p;\n.reg .u32 it;\nmov.u32 it, 0;\n"
      "WAIT_LOOP:\n"
      "mbarrier.try_wait.parity.shared::cta.b64 p, [%0], %1;\n"
      "@p bra WAIT_DONE;\n"
      "add.u32 it, it, 1;\n"
      "setp.lt.u32 p, it, 0x400000;\n"
      "@p bra WAIT_LOOP;\n"
      "trap;\n"
      "WAIT_DONE:\n}"
      ::"r"(bar), "r"(parity) : "memory");
}
__device__ __forceinline__ void bar_sync(int id, int n) { asm volatile("bar.sync %0, %1;" ::"r"(id), "r"(n) : "memory"); }
__device__ __forceinline__ void bar_arrive(int id, int n) { asm volatile("bar.arrive %0, %1;" ::"r"(id), "r"(n) : "memory"); }
__device__ __forceinline__ void tma_ld2(uint32_t dst, const CUtensorMap* m, uint32_t bar, int c0, int c1) {
  asm volatile("cp.async.bulk.tensor.2d.shared::cluster.global.mbarrier::complete_tx::bytes [%0], [%1, {%3, %4}], [%2];"
               ::"r"(dst), "l"(m), "r"(bar), "r"(c0), "r"(c1) : "memory");
}
__device__ __forceinline__ void tma_ld3(uint32_t dst, const CUtensorMap* m, uint32_t bar, int c0, int c1, int c2) {
  asm volatile("cp.async.bulk.tensor.3d.shared::cluster.global.mbarrier::complete_tx::bytes [%0], [%1, {%3, %4, %5}], [%2];"
               ::"r"(dst), "l"(m), "r"(bar), "r"(c0), "r"(c1), "r"(c2) : "memory");
}
__device__ __forceinline__ void tma_pf3(const CUtensorMap* m, int c0, int c1, int c2) {
  asm volatile("cp.async.bulk.prefetch.tensor.3d.L2.global [%0, {%1, %2, %3}];" ::"l"(m), "r"(c0), "r"(c1), "r"(c2) : "memory");
}
__device__ __forceinline__ void tma_st2(const CUtensorMap* m, uint32_t src, int c0, int c1) {
  asm volatile("cp.async.bulk.tensor.2d.global.shared::cta.bulk_group [%0, {%2, %3}], [%1];"
               ::"l"(m), "r"(src), "r"(c0), "r"(c1) : "memory");
}
__device__ __forceinline__ void bulk_commit() { asm volatile("cp.async.bulk.commit_group;" ::: "memory"); }
__device__ __forceinline__ void bulk_wait_read() { asm volatile("cp.async.bulk.wait_group.read 0;" ::: "memory"); }
__device__ __forceinline__ void bulk_wait_all() { asm volatile("cp.async.bulk.wait_group 0;" ::: "memory"); }
__device__ __forceinline__ void fence_async_smem() { asm volatile("fence.proxy.async.shared::cta;" ::: "memory"); }
__device__ __forceinline__ void fence_async_global() { asm volatile("fence.proxy.async.global;" ::: "memory"); }
__device__ __forceinline__ void st_release(uint32_t* p, uint32_t v) {
  asm volatile("st.release.gpu.global.u32 [%0], %1;" ::"l"(p), "r"(v) : "memory");
}
__device__ __forceinline__ void st_relaxed(uint32_t* p, uint32_t v) {
  asm volatile("st.relaxed.gpu.global.u32 [%0], %1;" ::"l"(p), "r"(v) : "memory");
}
__device__ __forceinline__ void st_msg(uint4* p, uint32_t a, uint32_t b, uint32_t c, uint32_t tag) {
  asm volatile("{\n.reg .b128 v;\nmov.b128 v, {%1, %2, %3, %4};\nst.relaxed.gpu.b128 [%0], v;\n}"
               ::"l"(p), "r"(a), "r"(b), "r"(c), "r"(tag) : "memory");
}
__device__ __forceinline__ void ld_msg(const uint4* p, uint32_t& a, uint32_t& b, uint32_t& c, uint32_t& tag) {
  asm volatile("{\n.reg .b128 v;\nld.relaxed.gpu.b128 v, [%4];\nmov.b128 {%0, %1, %2, %3}, v;\n}"
               : "=r"(a), "=r"(b), "=r"(c), "=r"(tag) : "l"(p) : "memory");
}
__device__ __forceinline__ bool elect_one() {
  uint32_t ok;
  asm volatile("{\n.reg .pred p;\nelect.sync _|p, 0xffffffff;\nselp.u32 %0, 1, 0, p;\n}" : "=r"(ok));
  return ok;
}
__device__ __forceinline__ int uniform(int v) { return __shfl_sync(0xffffffffu, v, 0); }
__device__ __forceinline__ uint32_t pack_bf16(float lo, float hi) {
  uint32_t r;
  asm("cvt.rn.bf16x2.f32 %0, %1, %2;" : "=r"(r) : "f"(hi), "f"(lo));
  return r;
}
__device__ __forceinline__ float bf_lo(uint32_t v) { return __uint_as_float(v << 16); }
__device__ __forceinline__ float bf_hi(uint32_t v) { return __uint_as_float(v & 0xffff0000u); }
__device__ __forceinline__ void stsm4(uint32_t addr, uint32_t r0, uint32_t r1, uint32_t r2, uint32_t r3) {
  asm volatile("stmatrix.sync.aligned.m8n8.x4.shared.b16 [%0], {%1, %2, %3, %4};"
               ::"r"(addr), "r"(r0), "r"(r1), "r"(r2), "r"(r3) : "memory");
}
__device__ __forceinline__ void ldsm4(uint32_t addr, uint32_t& r0, uint32_t& r1, uint32_t& r2, uint32_t& r3) {
  asm volatile("ldmatrix.sync.aligned.m8n8.x4.shared.b16 {%0, %1, %2, %3}, [%4];"
               : "=r"(r0), "=r"(r1), "=r"(r2), "=r"(r3) : "r"(addr) : "memory");
}
__device__ __forceinline__ uint32_t movtrans(uint32_t a) {
  uint32_t d;
  asm volatile("movmatrix.sync.aligned.m8n8.trans.b16 %0, %1;" : "=r"(d) : "r"(a));
  return d;
}
__device__ __forceinline__ void mma16816(float (&c)[4], uint32_t a0, uint32_t a1, uint32_t a2, uint32_t a3, uint32_t b0, uint32_t b1) {
  asm volatile("mma.sync.aligned.m16n8k16.row.col.f32.bf16.bf16.f32 {%0,%1,%2,%3}, {%4,%5,%6,%7}, {%8,%9}, {%0,%1,%2,%3};"
               : "+f"(c[0]), "+f"(c[1]), "+f"(c[2]), "+f"(c[3])
               : "r"(a0), "r"(a1), "r"(a2), "r"(a3), "r"(b0), "r"(b1));
}
__device__ __forceinline__ float2 lds_f2(uint32_t a) {
  float2 v;
  asm volatile("ld.shared.v2.f32 {%0, %1}, [%2];" : "=f"(v.x), "=f"(v.y) : "r"(a) : "memory");
  return v;
}
__device__ __forceinline__ float4 lds_f4(uint32_t a) {
  float4 v;
  asm volatile("ld.shared.v4.f32 {%0, %1, %2, %3}, [%4];" : "=f"(v.x), "=f"(v.y), "=f"(v.z), "=f"(v.w) : "r"(a) : "memory");
  return v;
}
__device__ __forceinline__ float lds_f(uint32_t a) {
  float v;
  asm volatile("ld.shared.f32 %0, [%1];" : "=f"(v) : "r"(a) : "memory");
  return v;
}
__device__ __forceinline__ uint32_t lds_u(uint32_t a) {
  uint32_t v;
  asm volatile("ld.shared.u32 %0, [%1];" : "=r"(v) : "r"(a) : "memory");
  return v;
}
__device__ __forceinline__ void sts_f2(uint32_t a, float x, float y) {
  asm volatile("st.shared.v2.f32 [%0], {%1, %2};" ::"r"(a), "f"(x), "f"(y) : "memory");
}
__device__ __forceinline__ void lds_u4(uint32_t a, uint32_t& x, uint32_t& y, uint32_t& z, uint32_t& w) {
  asm volatile("ld.shared.v4.u32 {%0, %1, %2, %3}, [%4];" : "=r"(x), "=r"(y), "=r"(z), "=r"(w) : "r"(a) : "memory");
}
__device__ __forceinline__ float ex2(float x) {
  float y;
  asm("ex2.approx.ftz.f32 %0, %1;" : "=f"(y) : "f"(x));
  return y;
}
__device__ __forceinline__ float rcp_hw(float x) {
  float y;
  asm("rcp.approx.ftz.f32 %0, %1;" : "=f"(y) : "f"(x));
  return y;
}
__device__ __forceinline__ float tanh_hw(float x) {
  float y;
  asm("tanh.approx.f32 %0, %1;" : "=f"(y) : "f"(x));
  return y;
}
__device__ __forceinline__ float quad_sum(float v) {
  v += __shfl_xor_sync(0xffffffffu, v, 1);
  return v + __shfl_xor_sync(0xffffffffu, v, 2);
}
__device__ __forceinline__ float quad_max(float v) {
  v = fmaxf(v, __shfl_xor_sync(0xffffffffu, v, 1));
  return fmaxf(v, __shfl_xor_sync(0xffffffffu, v, 2));
}

template <int N> __device__ __forceinline__ void wgmma_ss(float (&d)[96], uint32_t alo, uint32_t blo);
template <> __device__ __forceinline__ void wgmma_ss<128>(float (&d)[96], uint32_t alo, uint32_t blo) {
  asm volatile(
      "{\n.reg .b64 da, db;\nmov.b64 da, {%64, %66};\nmov.b64 db, {%65, %67};\n"
      "wgmma.mma_async.sync.aligned.m64n128k16.f32.bf16.bf16 {%0, %1, %2, %3, %4, %5, %6, %7, %8, %9, %10, %11, %12, %13, %14, %15, %16, %17, %18, %19, %20, %21, %22, %23, %24, %25, %26, %27, %28, %29, %30, %31, %32, %33, %34, %35, %36, %37, %38, %39, %40, %41, %42, %43, %44, %45, %46, %47, %48, %49, %50, %51, %52, %53, %54, %55, %56, %57, %58, %59, %60, %61, %62, %63}, da, db, 1, 1, 1, 0, 1;\n}"
      : "+f"(d[0]), "+f"(d[1]), "+f"(d[2]), "+f"(d[3]), "+f"(d[4]), "+f"(d[5]), "+f"(d[6]), "+f"(d[7]), "+f"(d[8]), "+f"(d[9]), "+f"(d[10]), "+f"(d[11]), "+f"(d[12]), "+f"(d[13]), "+f"(d[14]), "+f"(d[15]), "+f"(d[16]), "+f"(d[17]), "+f"(d[18]), "+f"(d[19]), "+f"(d[20]), "+f"(d[21]), "+f"(d[22]), "+f"(d[23]), "+f"(d[24]), "+f"(d[25]), "+f"(d[26]), "+f"(d[27]), "+f"(d[28]), "+f"(d[29]), "+f"(d[30]), "+f"(d[31]), "+f"(d[32]), "+f"(d[33]), "+f"(d[34]), "+f"(d[35]), "+f"(d[36]), "+f"(d[37]), "+f"(d[38]), "+f"(d[39]), "+f"(d[40]), "+f"(d[41]), "+f"(d[42]), "+f"(d[43]), "+f"(d[44]), "+f"(d[45]), "+f"(d[46]), "+f"(d[47]), "+f"(d[48]), "+f"(d[49]), "+f"(d[50]), "+f"(d[51]), "+f"(d[52]), "+f"(d[53]), "+f"(d[54]), "+f"(d[55]), "+f"(d[56]), "+f"(d[57]), "+f"(d[58]), "+f"(d[59]), "+f"(d[60]), "+f"(d[61]), "+f"(d[62]), "+f"(d[63])
      : "r"(alo), "r"(blo), "r"(DESC_A_HI), "r"(DESC_B_HI));
}

template <> __device__ __forceinline__ void wgmma_ss<192>(float (&d)[96], uint32_t alo, uint32_t blo) {
  asm volatile(
      "{\n.reg .b64 da, db;\nmov.b64 da, {%96, %98};\nmov.b64 db, {%97, %99};\n"
      "wgmma.mma_async.sync.aligned.m64n192k16.f32.bf16.bf16 {%0, %1, %2, %3, %4, %5, %6, %7, %8, %9, %10, %11, %12, %13, %14, %15, %16, %17, %18, %19, %20, %21, %22, %23, %24, %25, %26, %27, %28, %29, %30, %31, %32, %33, %34, %35, %36, %37, %38, %39, %40, %41, %42, %43, %44, %45, %46, %47, %48, %49, %50, %51, %52, %53, %54, %55, %56, %57, %58, %59, %60, %61, %62, %63, %64, %65, %66, %67, %68, %69, %70, %71, %72, %73, %74, %75, %76, %77, %78, %79, %80, %81, %82, %83, %84, %85, %86, %87, %88, %89, %90, %91, %92, %93, %94, %95}, da, db, 1, 1, 1, 0, 1;\n}"
      : "+f"(d[0]), "+f"(d[1]), "+f"(d[2]), "+f"(d[3]), "+f"(d[4]), "+f"(d[5]), "+f"(d[6]), "+f"(d[7]), "+f"(d[8]), "+f"(d[9]), "+f"(d[10]), "+f"(d[11]), "+f"(d[12]), "+f"(d[13]), "+f"(d[14]), "+f"(d[15]), "+f"(d[16]), "+f"(d[17]), "+f"(d[18]), "+f"(d[19]), "+f"(d[20]), "+f"(d[21]), "+f"(d[22]), "+f"(d[23]), "+f"(d[24]), "+f"(d[25]), "+f"(d[26]), "+f"(d[27]), "+f"(d[28]), "+f"(d[29]), "+f"(d[30]), "+f"(d[31]), "+f"(d[32]), "+f"(d[33]), "+f"(d[34]), "+f"(d[35]), "+f"(d[36]), "+f"(d[37]), "+f"(d[38]), "+f"(d[39]), "+f"(d[40]), "+f"(d[41]), "+f"(d[42]), "+f"(d[43]), "+f"(d[44]), "+f"(d[45]), "+f"(d[46]), "+f"(d[47]), "+f"(d[48]), "+f"(d[49]), "+f"(d[50]), "+f"(d[51]), "+f"(d[52]), "+f"(d[53]), "+f"(d[54]), "+f"(d[55]), "+f"(d[56]), "+f"(d[57]), "+f"(d[58]), "+f"(d[59]), "+f"(d[60]), "+f"(d[61]), "+f"(d[62]), "+f"(d[63]), "+f"(d[64]), "+f"(d[65]), "+f"(d[66]), "+f"(d[67]), "+f"(d[68]), "+f"(d[69]), "+f"(d[70]), "+f"(d[71]), "+f"(d[72]), "+f"(d[73]), "+f"(d[74]), "+f"(d[75]), "+f"(d[76]), "+f"(d[77]), "+f"(d[78]), "+f"(d[79]), "+f"(d[80]), "+f"(d[81]), "+f"(d[82]), "+f"(d[83]), "+f"(d[84]), "+f"(d[85]), "+f"(d[86]), "+f"(d[87]), "+f"(d[88]), "+f"(d[89]), "+f"(d[90]), "+f"(d[91]), "+f"(d[92]), "+f"(d[93]), "+f"(d[94]), "+f"(d[95])
      : "r"(alo), "r"(blo), "r"(DESC_A_HI), "r"(DESC_B_HI));
}

template <int R>
__device__ __forceinline__ void pin_regs(float (&a)[2][96]) {
#pragma unroll
  for (int m = 0; m < 2; m++)
#pragma unroll
    for (int i = 0; i < R; i++) asm volatile("" : "+f"(a[m][i])::"memory");
}

struct Ctx {
  uint32_t sb;
  int m, n, wg, w, lane;
};
__device__ __forceinline__ Ctx make_ctx(uint32_t sb, int id) {
  int lane;
  asm volatile("mov.u32 %0, %%laneid;" : "=r"(lane));
  asm volatile("" : "+r"(id), "+r"(sb));
  return Ctx{sb, (id >> 3) & 15, id & 7, id >> 9, (id >> 7) & 3, lane};
}
#define UNPACK_CTX(c) const uint32_t sb = c.sb; const int m = c.m, n = c.n, wg = c.wg, w = c.w, lane = c.lane

__device__ __forceinline__ uint32_t poll_line(const uint32_t* line, uint32_t tag, uint32_t need, int lane) {
  uint32_t mask;
  asm volatile(
      "{\n.reg .pred p;\n.reg .u32 it, v;\nmov.u32 it, 0;\n"
      "POLL_LOOP:\n"
      "ld.acquire.gpu.global.u32 v, [%1];\n"
      "setp.eq.u32 p, v, %2;\n"
      "vote.sync.ballot.b32 %0, p, 0xffffffff;\n"
      "and.b32 v, %0, %3;\n"
      "setp.eq.u32 p, v, %3;\n"
      "@p bra.uni POLL_DONE;\n"
      "add.u32 it, it, 1;\n"
      "setp.lt.u32 p, it, 0x400000;\n"
      "@p bra.uni POLL_LOOP;\n"
      "trap;\n"
      "POLL_DONE:\n"
      "bar.warp.sync 0xffffffff;\n}"
      : "=&r"(mask) : "l"(line + lane), "r"(tag), "r"(need) : "memory");
  return mask;
}

constexpr int STAGES_PER_LAYER = 152;
__device__ __forceinline__ int nib(uint64_t v, int i) { return (int)(v >> (4 * i)) & 15; }
__device__ __forceinline__ bool tile_wide(int t) { return (0xB >> t) & 1; }
__device__ __forceinline__ int tile_pos0(int t) { return t < 3 ? 0 : t == 3 ? 5 : 4 * t - 8; }
constexpr uint64_t SEG_TILE = 0x6665432210ull, SEG_PERIOD = 0x2232221122ull, SEG_ADD = 0x5300001000ull;
constexpr uint64_t SEG_LINE = 0x6543332100ull;

__device__ __forceinline__ void weight_coords(const Params& p, int t, int n, const CUtensorMap*& map, int& c0, int& c2) {
  map = &p.wqkv + nib(0x4332100ull, t);
  c0 = t < 2 ? 128 * n + 64 * t : 0;
  c2 = t < 2 ? 0 : (t == 2 || t == 6) ? 2 * n : 7 * n + nib(0x530000ull, t);
}

template <bool IS_A>
__device__ __forceinline__ void producer(const Params& p, uint32_t sb, int m, int n, int lane) {
  int inflight = 0, rph = 0;
  uint32_t b8 = 0, rb8 = 0, pos = 0, tag = 0;
#pragma unroll 1
  for (int sg = 0; sg < 20; sg++) {
    const int layer = sg >= 10, s = sg - 10 * layer;
    const int t = nib(SEG_TILE, s), period = nib(SEG_PERIOD, s), add = nib(SEG_ADD, s);
    const bool wide = tile_wide(t), ownx = t != 2 && t != 6;
    const uint32_t bbytes = wide ? 3 * UNIT : 2 * UNIT;
    const int mul = t == 6 ? 7 : 2;
    int short_left = wide ? 99 : (s == 2 || s == 5) ? 4 : 0;
    if (s == 4 || s == 5) pos = tile_pos0(t) * UNIT;
    const CUtensorMap* map;
    int c0, c2;
    const uint32_t* line = g_flags + ((7 * layer + nib(SEG_LINE, s)) * 16 + m) * 32;
    uint32_t mask = sg < 2 ? 0xffffffffu : 0u;
    if (IS_A) {
      map = t == 2 ? &p.att_ld : t == 6 ? &p.h_ld : sg < 2 ? &p.xin_ld : &p.out_ld;
      if (sg == 1) tag = __ldcg(g_epoch + m * 8 + n) + 1;
    } else {
      if (sg > 0 && sg < 17 && add == 0) {
        weight_coords(p, t == 6 ? 0 : t + 1, n, map, c0, c2);
#pragma unroll 1
        for (int kb = m; kb < (t == 5 ? 56 : 16); kb += 16)
          if (elect_one()) tma_pf3(map, c0, 64 * kb, c2);
      }
      weight_coords(p, t, n, map, c0, c2);
    }
#pragma unroll 1
    for (int q = 0; q < 8; q++) {
      int src = ((n & 6) + q) & 7;
      if (ownx && q < 2) src ^= n & 1;
      const bool own = ownx && q == 0;
      if (IS_A && !own) {
        const uint32_t need = 0xFu << (4 * src);
        if ((mask & need) != need) {
          mask = poll_line(line, tag, need, lane);
          fence_async_global();
        }
      }
      int kc = 64 * (mul * src + add);
#pragma unroll 1
      for (int a = 0; a < period; a++) {
        const int lag = short_left > 0 ? 3 : 4;
        short_left--;
#pragma unroll 1
        for (; inflight > lag; inflight--) {
          mbar_wait(sb + BAR_EMPTY + rb8, rph);
          rb8 += 8;
          if (rb8 == 8 * NBAR) { rb8 = 0; rph ^= 1; }
        }
        const uint32_t fb = sb + BAR_FULL + b8;
        if (elect_one()) {
          if (IS_A) {
            mbar_expect_tx(fb, own ? 0 : 16384);
            if (!own) tma_ld2(sb + pos + bbytes, map, fb, kc, 128 * m);
          } else {
            mbar_expect_tx(fb, bbytes);
            tma_ld3(sb + pos, map, fb, c0, kc, c2);
          }
        }
        kc += 64;
        inflight++;
        b8 += 8;
        if (b8 == 8 * NBAR) b8 = 0;
        pos += bbytes + 2 * UNIT;
        if (pos >= RING_UNITS * UNIT) pos -= RING_UNITS * UNIT;
      }
    }
  }
}

template <int N>
__device__ __forceinline__ void mainloop(float (&acc)[2][96], uint32_t sb, int i, int mn) {
  constexpr uint32_t Z16 = (2 + N / 64) * (UNIT >> 4), RING16 = RING_UNITS * (UNIT >> 4);
  const int wg = i & 1;
  const int layer = i >= 7, t = i - 7 * layer;
  const int nkb = t == 6 ? 56 : 16;
  const int nown = (t == 2 || t == 6) ? 0 : 2;
  const int jwin = t == 1 ? WIN1 : t == 2 ? WIN2 : -2;
  const int g0 = layer * STAGES_PER_LAYER + 16 * t;
  const uint32_t s16 = (sb & 0x3FFFF) >> 4;
  uint32_t b8 = 8 * (g0 % NBAR), ph = (g0 / NBAR) & 1, pos16 = tile_pos0(t) * (UNIT >> 4), prev8 = 0;
  pin_regs<N / 2>(acc);
  if (i > 0) bar_sync(BAR_ORDER + wg, 256);
  if (N == 192 && t != 1) mbar_wait(sb + BAR_XREADY, t == 3);
#pragma unroll 1
  for (int j = 0; j < nkb; j++) {
    mbar_wait(sb + BAR_FULL + b8, ph);
    if (j == 0) PROF_T(4 + i * 4);
    const uint32_t blo = (s16 | DESC_B_LO) + pos16;
    const uint32_t alo = (s16 | DESC_A_LO) + (j < nown ? (OFF_X >> 4) + j * 1024 : pos16 + Z16 - 1024);
    if (j == jwin + 1) bar_sync(BAR_DONE, 256);
    asm volatile("wgmma.fence.sync.aligned;" ::: "memory");
#pragma unroll
    for (int k = 0; k < 4; k++) {
      wgmma_ss<N>(acc[0], alo + 2 * k, blo + 128 * k);
      wgmma_ss<N>(acc[1], alo + 64 + 2 * k, blo + 128 * k);
    }
    asm volatile("wgmma.commit_group.sync.aligned;" ::: "memory");
    if (j == nkb - 1 && i < 13) bar_arrive(BAR_ORDER + (wg ^ 1), 256);
    asm volatile("wgmma.wait_group.sync.aligned 1;" ::: "memory");
    if (j > 0 && elect_one()) mbar_arrive(sb + BAR_EMPTY + prev8);
    if (j == jwin) bar_arrive(BAR_GO, 256);
    prev8 = b8;
    b8 += 8;
    if (b8 == 8 * NBAR) { b8 = 0; ph ^= 1; }
    pos16 += Z16;
    if (pos16 >= RING16) pos16 -= RING16;
  }
  asm volatile("wgmma.wait_group.sync.aligned 0;" ::: "memory");
  pin_regs<N / 2>(acc);
  if (elect_one()) mbar_arrive(sb + BAR_EMPTY + prev8);
  PROF_T(5 + i * 4);
}

#define ACC(q, j, e) acc[(q) & 1][4 * (j) + 2 * ((q) >> 1) + (e)]

__device__ __forceinline__ void write_partial_stats(const Ctx& c, int ln) {
  const uint32_t xrow = c.sb + OFF_X + c.w * 4096 + c.lane * 128;
  uint32_t u[4];
  lds_u4(xrow, u[0], u[1], u[2], u[3]);
  const float x0 = bf_lo(u[0]);
  float s0 = 0.f, s1 = 0.f, q0 = 0.f, q1 = 0.f;
#pragma unroll 2
  for (int j = 0; j < 16; j++) {
    lds_u4(xrow + (j >> 3) * 16384 + (((j & 7) ^ (c.lane & 7)) << 4), u[0], u[1], u[2], u[3]);
#pragma unroll
    for (int e = 0; e < 4; e++) {
      const float a = bf_lo(u[e]) - x0, d = bf_hi(u[e]) - x0;
      s0 += a; s1 += d;
      q0 = fmaf(a, a, q0); q1 = fmaf(d, d, q1);
    }
  }
  const float s = s0 + s1;
  reinterpret_cast<float2*>(g_stats)[(size_t)(ln * SEQ + 128 * c.m + 32 * c.w + c.lane) * 8 + c.n] =
      make_float2(fmaf(128.f, x0, s), fmaxf(q0 + q1 - s * s * (1.f / 128.f), 0.f));
}

__device__ __forceinline__ void finish_row_stats(const Ctx& c, int ln, uint32_t tag) {
  poll_line(g_sflag + (ln * 16 + c.m) * 32, tag, 0x11111111u << c.w, c.lane);
  const float4* src = g_stats + (size_t)(ln * SEQ + 128 * c.m + 32 * c.w + c.lane) * 4;
  float4 v[4];
#pragma unroll
  for (int q = 0; q < 4; q++) v[q] = __ldcg(src + q);
  float s = 0.f, m2 = 0.f;
#pragma unroll
  for (int q = 0; q < 4; q++) s += v[q].x + v[q].z;
  const float mean = s * (1.f / DM);
#pragma unroll
  for (int q = 0; q < 4; q++) {
    const float d0 = v[q].x * (1.f / 128.f) - mean, d1 = v[q].z * (1.f / 128.f) - mean;
    m2 += v[q].y + v[q].w + 128.f * (d0 * d0 + d1 * d1);
  }
  sts_f2(c.sb + OFF_ROW + (32 * c.w + c.lane) * 8, rsqrtf(m2 * (1.f / DM) + 1e-5f), mean);
  __syncwarp();
}

__device__ __forceinline__ void attn_scores(const uint32_t* qa, const uint32_t* qb, const uint32_t* k0, const uint32_t* k1,
                                            const uint32_t* k2, const uint32_t* k3, float (&l)[4], const float4& zero,
                                            bool par, bool early) {
  float s[4][4];
#pragma unroll
  for (int kb = 0; kb < 4; kb++) {
    const uint32_t* kk = kb == 0 ? k0 : kb == 1 ? k1 : kb == 2 ? k2 : k3;
    asm volatile("mma.sync.aligned.m16n8k16.row.col.f32.bf16.bf16.f32 {%0,%1,%2,%3}, {%4,%5,%6,%7}, {%8,%9}, {%10,%11,%12,%13};"
                 : "=f"(s[kb][0]), "=f"(s[kb][1]), "=f"(s[kb][2]), "=f"(s[kb][3])
                 : "r"(qa[0]), "r"(qb[0]), "r"(qa[1]), "r"(qb[1]), "r"(kk[0]), "r"(kk[1]), "f"(zero.x), "f"(zero.y),
                   "f"(zero.z), "f"(zero.w));
  }
#pragma unroll
  for (int kb = 0; kb < 4; kb++) {
    const uint32_t* kk = kb == 0 ? k0 : kb == 1 ? k1 : kb == 2 ? k2 : k3;
    mma16816(s[kb], qa[2], qb[2], qa[3], qb[3], kk[2], kk[3]);
  }
  l[0] = par ? s[1][1] : s[1][0];
  l[1] = early ? (par ? s[0][1] : s[0][0]) : (par ? s[2][1] : s[2][0]);
  l[2] = par ? s[2][3] : s[2][2];
  l[3] = early ? (par ? s[1][3] : s[1][2]) : (par ? s[3][3] : s[3][2]);
}

__device__ __forceinline__ void attn_mix(const float (&l)[4], const float (&sc)[4], const float (&off)[4], const float (&rk)[4],
                                         const uint32_t* v0, const uint32_t* v1, const uint32_t* v2, const uint32_t* v3,
                                         float (&o)[4][4], bool par, bool early) {
  float x[4];
#pragma unroll
  for (int e = 0; e < 4; e++) x[e] = fmaf(l[e], sc[e], off[e]);
  const float ml = quad_max(fmaxf(x[0], x[1])), mh = quad_max(fmaxf(x[2], x[3]));
  x[0] = ex2(x[0] - ml); x[1] = ex2(x[1] - ml);
  x[2] = ex2(x[2] - mh); x[3] = ex2(x[3] - mh);
  const float il = rcp_hw(quad_sum(x[0] + x[1])), ih = rcp_hw(quad_sum(x[2] + x[3]));
  const uint32_t pl = pack_bf16(x[0] * rk[0] * il, x[1] * rk[1] * il), ph = pack_bf16(x[2] * rk[2] * ih, x[3] * rk[3] * ih);
  const uint32_t sel_a = par ? 0x1044u : 0x4410u, sel_b = par ? 0x3244u : 0x4432u;
  const uint32_t sel_e = early ? sel_b : 0x4444u, sel_l = early ? 0x4444u : sel_b;
  const uint32_t pla = __byte_perm(pl, 0, sel_a), pha = __byte_perm(ph, 0, sel_a);
  const uint32_t e_l = __byte_perm(pl, 0, sel_e), e_h = __byte_perm(ph, 0, sel_e);
  const uint32_t l_l = __byte_perm(pl, 0, sel_l), l_h = __byte_perm(ph, 0, sel_l);
#pragma unroll
  for (int jn = 0; jn < 4; jn++) {
    o[jn][0] = o[jn][1] = o[jn][2] = o[jn][3] = 0.f;
    mma16816(o[jn], e_l, 0u, pla, e_h, v0[jn], v1[jn]);
  }
#pragma unroll
  for (int jn = 0; jn < 4; jn++) mma16816(o[jn], l_l, pha, 0u, l_h, v2[jn], v3[jn]);
}

__device__ __forceinline__ void colsum_partial(const Params& p, const Ctx& cx, bool qkv, uint32_t tag) {
  UNPACK_CTX(cx);
  const int tid = w * 32 + lane, cg = tid & 7, rg = tid >> 3;
  const int ld = qkv ? 3 * DM : FF;
  const __nv_bfloat16* W = (qkv ? p.wqkv_p + 128 * n : p.w1_p + 448 * n) + (size_t)(64 * m + 4 * rg) * ld + 8 * cg;
  const int nch = qkv ? 6 : 7;
#pragma unroll 1
  for (int c = 0; c < nch; c++) {
    const int col = qkv ? (c >> 1) * DM + (c & 1) * 64 : 64 * c;
    if ((lane & 7) < 4) asm volatile("prefetch.global.L2 [%0];" ::"l"(W + (size_t)(lane & 3) * ld + col - 8 * cg));
  }
  bar_sync(BAR_WG + wg, 128);
#pragma unroll 1
  for (int c = 0; c < nch; c++) {
    const int col = qkv ? (c >> 1) * DM + (c & 1) * 64 : 64 * c;
    uint4 v[4];
#pragma unroll
    for (int r = 0; r < 4; r++) v[r] = __ldcg(reinterpret_cast<const uint4*>(W + (size_t)r * ld + col));
    float a[8];
#pragma unroll
    for (int e = 0; e < 4; e++) {
      float lo = 0.f, hi = 0.f;
#pragma unroll
      for (int r = 0; r < 4; r++) {
        const uint32_t u = e == 0 ? v[r].x : e == 1 ? v[r].y : e == 2 ? v[r].z : v[r].w;
        lo += bf_lo(u);
        hi += bf_hi(u);
      }
      a[2 * e] = lo;
      a[2 * e + 1] = hi;
    }
    const bool u8 = lane & 8, u16 = lane & 16;
    float h4[4], h2[2];
#pragma unroll
    for (int e = 0; e < 4; e++) h4[e] = (u8 ? a[4 + e] : a[e]) + __shfl_xor_sync(0xffffffffu, u8 ? a[e] : a[4 + e], 8);
#pragma unroll
    for (int e = 0; e < 2; e++) h2[e] = (u16 ? h4[2 + e] : h4[e]) + __shfl_xor_sync(0xffffffffu, u16 ? h4[e] : h4[2 + e], 16);
    sts_f2(sb + OFF_STG + (w * 448 + c * 64 + cg * 8 + (u8 ? 4 : 0) + (u16 ? 2 : 0)) * 4, h2[0], h2[1]);
  }
  bar_sync(BAR_WG + wg, 128);
  float* dst = g_csp + m * (3 * DM + FF) + (qkv ? 384 * n : 3 * DM + 448 * n);
#pragma unroll 1
  for (int c = tid; c < nch * 64; c += 128) {
    const uint32_t a = sb + OFF_STG + c * 4;
    dst[c] = (lds_f(a) + lds_f(a + 1792)) + (lds_f(a + 3584) + lds_f(a + 5376));
  }
  bar_sync(BAR_WG + wg, 128);
  if (tid == 0) st_release(g_cflag + ((qkv ? 0 : 8) + n) * 32 + m, tag);
}

__device__ __forceinline__ void colsum_gather(const Params& p, const Ctx& cx, bool qkv, uint32_t tag) {
  const int n = cx.n, tid = cx.w * 32 + cx.lane;
  poll_line(g_cflag + ((qkv ? 0 : 8) + n) * 32, tag, 0xffffu, cx.lane);
  if (tid < (qkv ? 96 : 112)) {
    const float4* src = reinterpret_cast<const float4*>(g_csp + (qkv ? 384 * n : 3 * DM + 448 * n)) + tid;
    float4 s = make_float4(0.f, 0.f, 0.f, 0.f);
#pragma unroll 8
    for (int mm = 0; mm < 16; mm++) {
      const float4 v = __ldcg(src + mm * ((3 * DM + FF) / 4));
      s.x += v.x; s.y += v.y; s.z += v.z; s.w += v.w;
    }
    if (qkv) {
      const uint32_t a = cx.sb + OFF_CSQ + ((((tid >> 4) & 1) * 3 + (tid >> 5)) * 16 + (tid & 15)) * 16;
      sts_f2(a, s.x, s.y);
      sts_f2(a + 8, s.z, s.w);
    } else {
      const uint2 bb = __ldg(reinterpret_cast<const uint2*>(p.b1 + 448 * n) + tid);
      const uint32_t a = cx.sb + OFF_CSF + tid * 32;
      sts_f2(a, s.x, s.y);
      sts_f2(a + 8, 0.5f * bf_lo(bb.x), 0.5f * bf_hi(bb.x));
      sts_f2(a + 16, s.z, s.w);
      sts_f2(a + 24, 0.5f * bf_lo(bb.y), 0.5f * bf_hi(bb.y));
    }
  }
}

__device__ __forceinline__ void gelu_epilogue(const Params& p, float (&acc)[2][96], const Ctx& cx, int t) {
  UNPACK_CTX(cx);
  (void)wg;
  float rs[4], rm[4];
#pragma unroll
  for (int q = 0; q < 4; q++) {
    const float2 v = lds_f2(sb + OFF_ROW + (32 * w + 8 * q + (lane >> 2)) * 8);
    rs[q] = 0.5f * v.x;
    rm[q] = -rs[q] * v.y;
  }
  const int col0 = t == 3 ? 0 : t == 4 ? 192 : 320, steps = t == 3 ? 6 : 4;
  const uint32_t stg = sb + OFF_STG + w * 4096;
  uint32_t ctab = sb + OFF_CSF + (col0 / 2 + (lane & 3)) * 16;
  float v[2][16];
#pragma unroll
  for (int r = 0; r < 16; r++) { v[0][r] = acc[0][r]; v[1][r] = acc[1][r]; }
#pragma unroll 1
  for (int it = 0; it < steps; it++) {
    uint32_t hp[4][4];
#pragma unroll
    for (int j = 0; j < 4; j++) {
      const float4 cb = lds_f4(ctab + j * 64);
#pragma unroll
      for (int q = 0; q < 4; q++) {
        float y[2];
#pragma unroll
        for (int e = 0; e < 2; e++) {
          const float z = fmaf(v[q & 1][4 * j + 2 * (q >> 1) + e], rs[q], fmaf(rm[q], e ? cb.y : cb.x, e ? cb.w : cb.z));
          const float u = z * fmaf(z * z, 8.f * 0.7978845608028654f * 0.044715f, 2.f * 0.7978845608028654f);
          y[e] = fmaf(z, tanh_hw(u), z);
        }
        hp[j][q] = pack_bf16(y[0], y[1]);
      }
    }
    ctab += 256;
    if (!(it & 1)) {
      if (lane == 0) bulk_wait_read();
      __syncwarp();
    }
#pragma unroll
    for (int j = 0; j < 4; j++)
      stsm4(stg + lane * 128 + (((4 * (it & 1) + j) ^ (lane & 7)) << 4), hp[j][0], hp[j][1], hp[j][2], hp[j][3]);
    if (it & 1) {
      fence_async_smem();
      __syncwarp();
      if (lane == 0) {
        tma_st2(&p.h_st, stg, 448 * n + col0 + 32 * (it - 1), 128 * m + 32 * w);
        bulk_commit();
      }
    }
#define REFILL(k) case k - 1: _Pragma("unroll") for (int r = 0; r < 16; r++) { \
      asm volatile("mov.b32 %0, %1;" : "=f"(v[0][r]) : "f"(acc[0][16 * k + r])); \
      asm volatile("mov.b32 %0, %1;" : "=f"(v[1][r]) : "f"(acc[1][16 * k + r])); } break;
    switch (it) {
      REFILL(1) REFILL(2) REFILL(3) REFILL(4)
      default:
#pragma unroll
        for (int r = 0; r < 16; r++) {
          asm volatile("mov.b32 %0, %1;" : "=f"(v[0][r]) : "f"(acc[0][80 + r]));
          asm volatile("mov.b32 %0, %1;" : "=f"(v[1][r]) : "f"(acc[1][80 + r]));
        }
    }
#undef REFILL
  }
}

__device__ __forceinline__ void attn_epilogue(const Params& p, float (&acc)[2][96], const Ctx& cx, int layer, int t, uint32_t tag) {
  UNPACK_CTX(cx);
  const bool par = (lane >> 2) & 1, early = (lane & 3) > (lane >> 3);
  uint32_t Q[4][8], K[4][8], V[4][8];
  float kr[6], qr[4];
#pragma unroll
  for (int q = 0; q < 4; q++) {
    kr[2 + q] = lds_f(sb + OFF_ROW + (32 * w + 8 * q + 2 * (lane & 3) + par) * 8);
    qr[q] = lds_f(sb + OFF_ROW + (32 * w + 8 * q + (lane >> 2)) * 8) * (0.17677669529663687f * 1.4426950408889634f);
  }
  const int slot = ((layer * 2 + t) * 16 + m) * 8 + n;
  uint4* const exc = reinterpret_cast<uint4*>(__cvta_shared_to_generic(sb + OFF_STG));
#pragma unroll
  for (int qq = 0; qq < 4; qq++) {
    const int q = qq ^ 2;
#pragma unroll
    for (int j = 0; j < 8; j++) {
      K[q][j] = pack_bf16(ACC(q, 8 + j, 0), ACC(q, 8 + j, 1));
      V[q][j] = movtrans(pack_bf16(ACC(q, 16 + j, 0), ACC(q, 16 + j, 1)));
    }
    if (qq == 1) {
      uint4* e = (w < 3 ? exc + w * 384 : g_halo + slot * 384) + lane;
#pragma unroll
      for (int j = 0; j < 8; j++) st_msg(e + j * 32, K[2][j], K[3][j], V[2][j], tag);
      st_msg(e + 8 * 32, V[3][0], V[3][1], V[3][2], tag);
      st_msg(e + 9 * 32, V[3][3], V[3][4], V[3][5], tag);
      st_msg(e + 10 * 32, V[3][6], V[3][7], __float_as_uint(kr[4]), tag);
      st_msg(e + 11 * 32, __float_as_uint(kr[5]), 0u, 0u, tag);
    }
  }
#pragma unroll
  for (int q = 0; q < 4; q++)
#pragma unroll
    for (int j = 0; j < 8; j++) Q[q][j] = pack_bf16(ACC(q, j, 0), ACC(q, j, 1));
  bar_sync(BAR_WG + wg, 128);
  const uint4* src = (w > 0 ? exc + (w - 1) * 384 : m > 0 ? g_halo + (slot - 8) * 384 : exc) + lane;
  uint32_t PK[2][8], PV[2][8], r4, r5;
#pragma unroll 1
  for (int it = 0; it < (1 << 20); it++) {
    uint32_t tg, bad = 0, u0, u1;
#pragma unroll
    for (int j = 0; j < 8; j++) { ld_msg(src + j * 32, PK[0][j], PK[1][j], PV[0][j], tg); bad |= tg ^ tag; }
    ld_msg(src + 8 * 32, PV[1][0], PV[1][1], PV[1][2], tg); bad |= tg ^ tag;
    ld_msg(src + 9 * 32, PV[1][3], PV[1][4], PV[1][5], tg); bad |= tg ^ tag;
    ld_msg(src + 10 * 32, PV[1][6], PV[1][7], r4, tg); bad |= tg ^ tag;
    ld_msg(src + 11 * 32, r5, u0, u1, tg); bad |= tg ^ tag;
    if (__all_sync(0xffffffffu, bad == 0)) break;
  }
  kr[0] = __uint_as_float(r4);
  kr[1] = __uint_as_float(r5);
  float rk[2][4], sc[2][4], off[2][4];
#pragma unroll
  for (int g = 0; g < 2; g++) {
    rk[g][0] = kr[2 * g + 1];
    rk[g][1] = early ? kr[2 * g] : kr[2 * g + 2];
    rk[g][2] = kr[2 * g + 2];
    rk[g][3] = early ? kr[2 * g + 1] : kr[2 * g + 3];
#pragma unroll
    for (int e = 0; e < 4; e++) {
      const bool masked = g == 0 && e != 2 && (m | w) == 0 && (e == 0 || early);
      sc[g][e] = masked ? 0.f : rk[g][e] * qr[2 * g + (e >> 1)];
      off[g][e] = masked ? -1e30f : 0.f;
    }
  }
  bar_sync(BAR_GO, 256);
  const float4 zero = lds_f4(sb + OFF_ZERO);
  float l[2][2][4], o[2][2][4][4];
#pragma unroll
  for (int h = 0; h < 2; h++) {
    attn_scores(&Q[2][4 * h], &Q[3][4 * h], &K[0][4 * h], &K[1][4 * h], &K[2][4 * h], &K[3][4 * h], l[1][h], zero, par, early);
    attn_scores(&Q[0][4 * h], &Q[1][4 * h], &PK[0][4 * h], &PK[1][4 * h], &K[0][4 * h], &K[1][4 * h], l[0][h], zero, par, early);
  }
#pragma unroll
  for (int h = 0; h < 2; h++) {
    attn_mix(l[1][h], sc[1], off[1], rk[1], &V[0][4 * h], &V[1][4 * h], &V[2][4 * h], &V[3][4 * h], o[1][h], par, early);
    attn_mix(l[0][h], sc[0], off[0], rk[0], &PV[0][4 * h], &PV[1][4 * h], &V[0][4 * h], &V[1][4 * h], o[0][h], par, early);
  }
  const uint32_t stg = sb + OFF_STG + w * 4096;
#pragma unroll
  for (int j = 0; j < 8; j++) {
    const float(&a)[4] = o[0][j >> 2][j & 3];
    const float(&c)[4] = o[1][j >> 2][j & 3];
    stsm4(stg + lane * 128 + ((j ^ (lane & 7)) << 4), pack_bf16(a[0], a[1]), pack_bf16(a[2], a[3]), pack_bf16(c[0], c[1]),
          pack_bf16(c[2], c[3]));
  }
  bar_arrive(BAR_DONE, 256);
  fence_async_smem();
  __syncwarp();
  if (lane == 0) {
    tma_st2(&p.att_st, stg, 128 * n + 64 * t, 128 * m + 32 * w);
    bulk_commit();
  }
}

__device__ __forceinline__ void consumer_tile(const Params& p, uint32_t sb0, int i, int mn) {
  const int layer = i >= 7, t = i - 7 * layer;
  const bool resid = i == -1 || t == 2 || t == 6;
  uint32_t tag;
  if (i >= 0) {
    float acc[2][96];
    if (resid) {
      const Ctx cx = make_ctx(sb0, mn);
      const uint32_t xrow = cx.sb + OFF_X + cx.w * 4096 + cx.lane * 128;
      const uint32_t* b2 = reinterpret_cast<const uint32_t*>(p.b2 + 128 * cx.n) + (cx.lane & 3);
#pragma unroll
      for (int j = 0; j < 16; j++) {
        uint32_t r[4], bb = 0;
        ldsm4(xrow + (j >> 3) * 16384 + (((j & 7) ^ (cx.lane & 7)) << 4), r[0], r[1], r[2], r[3]);
        if (t == 6) bb = __ldg(b2 + 4 * j);
#pragma unroll
        for (int q = 0; q < 4; q++) {
          ACC(q, j, 0) = bf_lo(r[q]) + bf_lo(bb);
          ACC(q, j, 1) = bf_hi(r[q]) + bf_hi(bb);
        }
      }
    } else {
#pragma unroll
      for (int r = 0; r < 64; r++) acc[0][r] = acc[1][r] = 0.f;
    }
    if (tile_wide(t)) {
#pragma unroll
      for (int r = 64; r < 96; r++) acc[0][r] = acc[1][r] = 0.f;
#pragma unroll 1
      for (int phase = 0; phase < 2; phase++) {
        if (t + phase == 1) {
          const Ctx cx = make_ctx(sb0, mn);
          float nm[4];
#pragma unroll
          for (int q = 0; q < 4; q++) nm[q] = -lds_f(cx.sb + OFF_ROW + (32 * cx.w + 8 * q + (cx.lane >> 2)) * 8 + 4);
          const uint32_t ctab = cx.sb + OFF_CSQ + (t * 192 + 2 * (cx.lane & 3)) * 4;
#pragma unroll
          for (int j = 0; j < 24; j++) {
            const float2 cs = lds_f2(ctab + j * 32);
#pragma unroll
            for (int q = 0; q < 4; q++) {
              ACC(q, j, 0) = fmaf(nm[q], cs.x, ACC(q, j, 0));
              ACC(q, j, 1) = fmaf(nm[q], cs.y, ACC(q, j, 1));
            }
          }
        }
        if (phase == 0) {
          mainloop<192>(acc, sb0, i, mn);
          bar_sync(BAR_GUARD + (i & 1), 256);
        }
      }
      if (t < 2) {
        attn_epilogue(p, acc, make_ctx(sb0, mn), layer, t, lds_u(sb0 + OFF_TAG));
        goto tile_done;
      }
    } else {
      mainloop<128>(acc, sb0, i, mn);
      if (resid) {
        const Ctx cx = make_ctx(sb0, mn);
        UNPACK_CTX(cx);
        (void)wg;
        const uint32_t xrow = sb + OFF_X + w * 4096 + lane * 128;
#pragma unroll
        for (int j = 0; j < 16; j++)
          stsm4(xrow + (j >> 3) * 16384 + (((j & 7) ^ (lane & 7)) << 4), pack_bf16(ACC(0, j, 0), ACC(0, j, 1)),
                pack_bf16(ACC(1, j, 0), ACC(1, j, 1)), pack_bf16(ACC(2, j, 0), ACC(2, j, 1)), pack_bf16(ACC(3, j, 0), ACC(3, j, 1)));
        fence_async_smem();
        __syncwarp();
        if (lane == 0) {
          mbar_arrive(sb + BAR_XREADY);
          tma_st2(&p.out_st, sb + OFF_X + w * 4096, 128 * n, 128 * m + 32 * w);
          tma_st2(&p.out_st, sb + OFF_X + 16384 + w * 4096, 128 * n + 64, 128 * m + 32 * w);
          bulk_commit();
        }
        goto tile_done;
      }
      bar_sync(BAR_GUARD + (i & 1), 256);
#pragma unroll
      for (int r = 64; r < 96; r++) acc[0][r] = acc[1][r] = acc[0][0];
    }
    gelu_epilogue(p, acc, make_ctx(sb0, mn), t);
  tile_done:
    tag = lds_u(sb0 + OFF_TAG);
  } else {
    tag = __ldcg(g_epoch + (mn & 127)) + 1;
    asm volatile("st.shared.u32 [%0], %1;" ::"r"(sb0 + OFF_TAG), "r"(tag) : "memory");
    mbar_wait(sb0 + BAR_XREADY, 0);
  }
  const Ctx cx = make_ctx(sb0, mn);
  if (i == 13) {
    if (cx.lane == 0) bulk_wait_read();
    bar_sync(BAR_GUARD + 1, 256);
    if (cx.w + cx.lane == 0) g_epoch[mn & 127] = tag;
    return;
  }
  if (cx.lane == 0) {
    bulk_wait_all();
    st_relaxed(g_flags + ((1 + i) * 16 + cx.m) * 32 + 4 * cx.n + cx.w, tag);
  }
  __syncwarp();
  if (resid) {
    const int ln = (i + 3) >> 2;
    write_partial_stats(cx, ln);
    __syncwarp();
    if (cx.lane == 0) st_release(g_sflag + (ln * 16 + cx.m) * 32 + 4 * cx.n + cx.w, tag);
    __syncwarp();
    if (i >= 0) bar_sync(BAR_GUARD + (i & 1), 256);
  }
  if (i <= 0) colsum_partial(p, cx, i < 0, tag);
  if (resid) finish_row_stats(cx, (i + 3) >> 2, tag);
  if (i == -1 || i == 2) {
    colsum_gather(p, cx, i < 0, tag);
    bar_sync(BAR_WG + (i & 1), 128);
  }
  bar_arrive(BAR_GUARD + ((i & 1) ^ 1), 256);
}

__global__ void __cluster_dims__(2, 1, 1) __launch_bounds__(384, 1) fused_layers_kernel(const __grid_constant__ Params p) {
  extern __shared__ __align__(1024) uint8_t smem_raw[];
  const uint32_t sb = (uint32_t)__cvta_generic_to_shared(smem_raw);
  const int tid = threadIdx.x, lane = tid & 31, warp = uniform(tid >> 5), wg = warp >> 2, w = warp & 3;

  int mn;
  {
    int id = blockIdx.x;
    if (p.by_smid) asm volatile("mov.u32 %0, %%smid;" : "=r"(id));
    else if (id >= 120) id += 4;
    const int c = id >> 1;
    int g, j;
    if (c < 32) { g = c & 7; j = c >> 3; }
    else if (c < 60) { g = 1 + (c - 32) % 7; j = 4 + (c - 32) / 7; }
    else { g = 0; j = c - 58; }
    mn = ((g >> 2) * 8 + j) * 8 + (g & 3) * 2 + (id & 1);
    if (c == 60 || c == 61) {
      if (tid < 32) {
        const uint32_t tag = __ldcg(g_epoch + NCTA + (id & 3)) + 1;
#pragma unroll 1
        for (int nn = 0; nn < 8; nn++) poll_line(g_cflag + nn * 32, tag, 0xffffu, lane);
        if (tid == 0) g_epoch[NCTA + (id & 3)] = tag;
      }
      return;
    }
  }
  const int m = mn >> 3, n = mn & 7;
  const uint32_t full0 = sb + OFF_BAR, empty0 = full0 + 8 * NBAR, xready = full0 + 16 * NBAR;
  if (tid == 256) asm volatile("prefetch.tensormap [%0];" ::"l"(&p.wqkv) : "memory");
  if (tid == 288) asm volatile("prefetch.tensormap [%0];" ::"l"(&p.xin_ld) : "memory");
  if (tid == 0) {
    for (int s = 0; s < NBAR; s++) {
      mbar_init(full0 + 8 * s, 2);
      mbar_init(empty0 + 8 * s, 4);
    }
    mbar_init(xready, 4);
    sts_f2(sb + OFF_ZERO, 0.f, 0.f);
    sts_f2(sb + OFF_ZERO + 8, 0.f, 0.f);
    fence_async_smem();
  }
  __syncthreads();

  if (wg == 2) {
    asm volatile("setmaxnreg.dec.sync.aligned.u32 40;");
    if (w == 0) {
      producer<false>(p, sb, m, n, lane);
    } else if (w == 1) {
      if (elect_one()) {
        mbar_expect_tx(xready, 32768);
        tma_ld2(sb + OFF_X, &p.xin_ld, xready, 128 * n, 128 * m);
        tma_ld2(sb + OFF_X + 16384, &p.xin_ld, xready, 128 * n + 64, 128 * m);
        mbar_arrive(xready); mbar_arrive(xready); mbar_arrive(xready);
      }
      producer<true>(p, sb, m, n, lane);
    }
  } else {
    asm volatile("setmaxnreg.inc.sync.aligned.u32 232;");
#pragma unroll 1
    for (int i = -wg; i < 14; i += 2) {
      consumer_tile(p, sb, i, mn | (warp << 7));
      PROF_T(i < 0 ? 3 : 6 + i * 4);
    }
  }
}

typedef CUresult (*EncodeFn)(CUtensorMap*, CUtensorMapDataType, cuuint32_t, void*, const cuuint64_t*, const cuuint64_t*,
                             const cuuint32_t*, const cuuint32_t*, CUtensorMapInterleave, CUtensorMapSwizzle,
                             CUtensorMapL2promotion, CUtensorMapFloatOOBfill);

void make_2d(EncodeFn enc, CUtensorMap* m, const void* ptr, uint64_t cols, uint64_t rows, uint32_t box_rows) {
  cuuint64_t d[2] = {cols, rows}, st[1] = {cols * 2};
  cuuint32_t b[2] = {64, box_rows}, e[2] = {1, 1};
  enc(m, CU_TENSOR_MAP_DATA_TYPE_BFLOAT16, 2, const_cast<void*>(ptr), d, st, b, e, CU_TENSOR_MAP_INTERLEAVE_NONE,
      CU_TENSOR_MAP_SWIZZLE_128B, CU_TENSOR_MAP_L2_PROMOTION_L2_128B, CU_TENSOR_MAP_FLOAT_OOB_FILL_NONE);
}
void make_3d(EncodeFn enc, CUtensorMap* m, const void* ptr, uint64_t d0, uint64_t rows, uint64_t d2, uint64_t row_bytes,
             uint64_t chunk_bytes, uint32_t box_chunks) {
  cuuint64_t d[3] = {d0, rows, d2}, st[2] = {row_bytes, chunk_bytes};
  cuuint32_t b[3] = {64, 64, box_chunks}, e[3] = {1, 1, 1};
  enc(m, CU_TENSOR_MAP_DATA_TYPE_BFLOAT16, 3, const_cast<void*>(ptr), d, st, b, e, CU_TENSOR_MAP_INTERLEAVE_NONE,
      CU_TENSOR_MAP_SWIZZLE_128B, CU_TENSOR_MAP_L2_PROMOTION_L2_128B, CU_TENSOR_MAP_FLOAT_OOB_FILL_NONE);
}

}

extern "C" void kernel_launch(void* const* d_in, const int* in_sizes, int n_in, void* d_out, int out_size) {
  (void)in_sizes; (void)n_in; (void)out_size;
  static EncodeFn enc = nullptr;
  static void *att = nullptr, *hbuf = nullptr;
  static int by_smid = 0;
  if (!enc) {
    void* fn = nullptr;
    cudaDriverEntryPointQueryResult q;
    cudaGetDriverEntryPoint("cuTensorMapEncodeTiled", &fn, cudaEnableDefault, &q);
    enc = (EncodeFn)fn;
    cudaGetSymbolAddress(&att, g_att);
    cudaGetSymbolAddress(&hbuf, g_h);
    cudaFuncSetAttribute(fused_layers_kernel, cudaFuncAttributeMaxDynamicSharedMemorySize, SMEM_BYTES);
    int sms = 0, clusters = 0, dev = 0;
    cudaGetDevice(&dev);
    cudaDeviceGetAttribute(&sms, cudaDevAttrMultiProcessorCount, dev);
    cudaLaunchConfig_t cfg = {};
    cfg.gridDim = dim3(132);
    cfg.blockDim = dim3(384);
    cfg.dynamicSmemBytes = SMEM_BYTES;
    cudaLaunchAttribute at[1];
    at[0].id = cudaLaunchAttributeClusterDimension;
    at[0].val.clusterDim.x = 2; at[0].val.clusterDim.y = 1; at[0].val.clusterDim.z = 1;
    cfg.attrs = at;
    cfg.numAttrs = 1;
    if (cudaOccupancyMaxActiveClusters(&clusters, fused_layers_kernel, &cfg) != cudaSuccess) (void)cudaGetLastError();
    by_smid = sms == 132 && clusters == 66;
  }
  Params p;
  make_2d(enc, &p.xin_ld, d_in[0], DM, SEQ, 128);
  make_2d(enc, &p.out_ld, d_out, DM, SEQ, 128);
  make_2d(enc, &p.out_st, d_out, DM, SEQ, 32);
  make_2d(enc, &p.att_ld, att, DM, SEQ, 128);
  make_2d(enc, &p.att_st, att, DM, SEQ, 32);
  make_2d(enc, &p.h_ld, hbuf, FF, SEQ, 128);
  make_2d(enc, &p.h_st, hbuf, FF, SEQ, 32);
  make_3d(enc, &p.wqkv, d_in[1], DM, DM, 3, 3 * DM * 2, DM * 2, 3);
  make_3d(enc, &p.wo, d_in[2], 64, DM, DM / 64, DM * 2, 128, 2);
  make_3d(enc, &p.w1a, d_in[4], 64, DM, FF / 64, FF * 2, 128, 3);
  make_3d(enc, &p.w1b, d_in[4], 64, DM, FF / 64, FF * 2, 128, 2);
  make_3d(enc, &p.w2, d_in[6], 64, FF, DM / 64, DM * 2, 128, 2);
  p.wqkv_p = (const __nv_bfloat16*)d_in[1];
  p.w1_p = (const __nv_bfloat16*)d_in[4];
  p.b1 = (const __nv_bfloat16*)d_in[5];
  p.b2 = (const __nv_bfloat16*)d_in[7];
  p.by_smid = by_smid;
  fused_layers_kernel<<<by_smid ? 132 : NCTA, 384, SMEM_BYTES>>>(p);
}
```

```cpp
#include <cuda_runtime.h>
#include <cuda_bf16.h>
#include <cuda.h>
#include <stdint.h>

namespace {

constexpr int SEQ = 2048, DM = 1024, FF = 3584;
constexpr int NCTA = 128;
constexpr int NBAR = 5;

constexpr uint32_t RING_UNITS = 20, UNIT = 8192;
constexpr uint32_t OFF_X   = RING_UNITS * UNIT;
constexpr uint32_t OFF_STG = OFF_X + 32768;
constexpr uint32_t OFF_CSQ = OFF_STG + 24576;
constexpr uint32_t OFF_CSF = OFF_CSQ + 1536;
constexpr uint32_t OFF_ROW = OFF_CSF + 3584;
constexpr uint32_t OFF_BAR = OFF_ROW + 1024;
constexpr uint32_t SMEM_BYTES = OFF_BAR + 128;
constexpr uint32_t BAR_FULL = OFF_BAR, BAR_EMPTY = OFF_BAR + 8 * NBAR, BAR_XREADY = OFF_BAR + 16 * NBAR;
constexpr uint32_t BAR_DUMMY = OFF_BAR + 88, OFF_TAG = OFF_BAR + 96, OFF_ZERO = OFF_BAR + 112;

constexpr uint64_t DESC_A = (1ull << 62) | ((uint64_t)(2048 >> 4) << 32) | (1ull << 16);
constexpr uint64_t DESC_B = (1ull << 62) | ((uint64_t)(1024 >> 4) << 32) | ((uint64_t)(8192 >> 4) << 16);

constexpr int BAR_ORDER = 1, BAR_GUARD = 3, BAR_WG = 5, BAR_GO = 7, BAR_DONE = 8;
#define GELU_DEP 3
#define WIN1 8
#define WIN2 4

struct Params {
  CUtensorMap xin_ld, out_ld, out_st, att_ld, att_st, h_ld, h_st, wqkv, wo, w1a, w1b, w2;
  const __nv_bfloat16 *wqkv_p, *w1_p, *b1, *b2;
  int by_smid;
  uint32_t zero;
};

__device__ __nv_bfloat16 g_att[SEQ * DM];
__device__ __nv_bfloat16 g_h[SEQ * FF];
__device__ uint4 g_stats[4 * 8 * SEQ];
__device__ uint4 g_halo[2 * 2 * 16 * 8 * 512];
__device__ uint4 g_csp[2 * 8 * 16 * 160];
__device__ uint32_t g_flags[16 * 32];
__device__ uint32_t g_epoch[NCTA + 4];
#define PROF_T(idx)
#define PROF_S(g)

__device__ __forceinline__ void mbar_init(uint32_t bar, int cnt) {
  asm volatile("mbarrier.init.shared::cta.b64 [%0], %1;" ::"r"(bar), "r"(cnt));
}
__device__ __forceinline__ void mbar_expect_tx(uint32_t bar, uint32_t bytes) {
  asm volatile("mbarrier.arrive.expect_tx.shared::cta.b64 _, [%0], %1;" ::"r"(bar), "r"(bytes) : "memory");
}
__device__ __forceinline__ void mbar_arrive(uint32_t bar) {
  asm volatile("mbarrier.arrive.shared::cta.b64 _, [%0];" ::"r"(bar) : "memory");
}
__device__ __forceinline__ bool mbar_test(uint32_t bar, uint32_t parity) {
  uint32_t ok;
  asm volatile("{\n.reg .pred p;\nmbarrier.test_wait.parity.shared::cta.b64 p, [%1], %2;\nselp.u32 %0, 1, 0, p;\n}"
               : "=r"(ok) : "r"(bar), "r"(parity) : "memory");
  return ok;
}
__device__ __forceinline__ void mbar_wait(uint32_t bar, uint32_t parity) {
  asm volatile(
      "{\n.reg .pred p;\n.reg .u32 it;\nmov.u32 it, 0;\n"
      "WAIT_LOOP:\n"
      "mbarrier.try_wait.parity.shared::cta.b64 p, [%0], %1;\n"
      "@p bra WAIT_DONE;\n"
      "add.u32 it, it, 1;\n"
      "setp.lt.u32 p, it, 0x400000;\n"
      "@p bra WAIT_LOOP;\n"
      "trap;\n"
      "WAIT_DONE:\n}"
      ::"r"(bar), "r"(parity) : "memory");
}
__device__ __forceinline__ void bar_sync(int id, int n) { asm volatile("bar.sync %0, %1;" ::"r"(id), "r"(n) : "memory"); }
__device__ __forceinline__ void bar_arrive(int id, int n) { asm volatile("bar.arrive %0, %1;" ::"r"(id), "r"(n) : "memory"); }
__device__ __forceinline__ void tma_ld2(uint32_t dst, const CUtensorMap* m, uint32_t bar, int c0, int c1) {
  asm volatile("cp.async.bulk.tensor.2d.shared::cluster.global.mbarrier::complete_tx::bytes [%0], [%1, {%3, %4}], [%2];"
               ::"r"(dst), "l"(m), "r"(bar), "r"(c0), "r"(c1) : "memory");
}
__device__ __forceinline__ void tma_ld3(uint32_t dst, const CUtensorMap* m, uint32_t bar, int c0, int c1, int c2) {
  asm volatile("cp.async.bulk.tensor.3d.shared::cluster.global.mbarrier::complete_tx::bytes [%0], [%1, {%3, %4, %5}], [%2];"
               ::"r"(dst), "l"(m), "r"(bar), "r"(c0), "r"(c1), "r"(c2) : "memory");
}
__device__ __forceinline__ void tma_pf3(const CUtensorMap* m, int c0, int c1, int c2) {
  asm volatile("cp.async.bulk.prefetch.tensor.3d.L2.global [%0, {%1, %2, %3}];" ::"l"(m), "r"(c0), "r"(c1), "r"(c2) : "memory");
}
__device__ __forceinline__ void tma_st2(const CUtensorMap* m, uint32_t src, int c0, int c1) {
  asm volatile("cp.async.bulk.tensor.2d.global.shared::cta.bulk_group [%0, {%2, %3}], [%1];"
               ::"l"(m), "r"(src), "r"(c0), "r"(c1) : "memory");
}
__device__ __forceinline__ void bulk_commit() { asm volatile("cp.async.bulk.commit_group;" ::: "memory"); }
__device__ __forceinline__ void bulk_wait_read() { asm volatile("cp.async.bulk.wait_group.read 0;" ::: "memory"); }
__device__ __forceinline__ void bulk_wait_all() { asm volatile("cp.async.bulk.wait_group 0;" ::: "memory"); }
__device__ __forceinline__ void fence_async_smem() { asm volatile("fence.proxy.async.shared::cta;" ::: "memory"); }
__device__ __forceinline__ void fence_async_global() { asm volatile("fence.proxy.async.global;" ::: "memory"); }
__device__ __forceinline__ void st_relaxed(uint32_t* p, uint32_t v) {
  asm volatile("st.relaxed.gpu.global.u32 [%0], %1;" ::"l"(p), "r"(v) : "memory");
}
__device__ __forceinline__ void st_msg(uint4* p, uint32_t a, uint32_t b, uint32_t c, uint32_t tag) {
  asm volatile("{\n.reg .b128 v;\nmov.b128 v, {%1, %2, %3, %4};\nst.relaxed.gpu.b128 [%0], v;\n}"
               ::"l"(p), "r"(a), "r"(b), "r"(c), "r"(tag) : "memory");
}
__device__ __forceinline__ void ld_msg(const uint4* p, uint32_t& a, uint32_t& b, uint32_t& c, uint32_t& tag) {
  asm volatile("{\n.reg .b128 v;\nld.relaxed.gpu.b128 v, [%4];\nmov.b128 {%0, %1, %2, %3}, v;\n}"
               : "=r"(a), "=r"(b), "=r"(c), "=r"(tag) : "l"(p) : "memory");
}
__device__ __forceinline__ bool elect_one() {
  uint32_t ok;
  asm volatile("{\n.reg .pred p;\nelect.sync _|p, 0xffffffff;\nselp.u32 %0, 1, 0, p;\n}" : "=r"(ok));
  return ok;
}
__device__ __forceinline__ int uniform(int v) { return __shfl_sync(0xffffffffu, v, 0); }
__device__ __forceinline__ uint32_t pack_bf16(float lo, float hi) {
  uint32_t r;
  asm("cvt.rn.bf16x2.f32 %0, %1, %2;" : "=r"(r) : "f"(hi), "f"(lo));
  return r;
}
__device__ __forceinline__ float bf_lo(uint32_t v) { return __uint_as_float(v << 16); }
__device__ __forceinline__ float bf_hi(uint32_t v) { return __uint_as_float(v & 0xffff0000u); }
__device__ __forceinline__ void stsm4(uint32_t addr, uint32_t r0, uint32_t r1, uint32_t r2, uint32_t r3) {
  asm volatile("stmatrix.sync.aligned.m8n8.x4.shared.b16 [%0], {%1, %2, %3, %4};"
               ::"r"(addr), "r"(r0), "r"(r1), "r"(r2), "r"(r3) : "memory");
}
__device__ __forceinline__ void ldsm4(uint32_t addr, uint32_t& r0, uint32_t& r1, uint32_t& r2, uint32_t& r3) {
  asm volatile("ldmatrix.sync.aligned.m8n8.x4.shared.b16 {%0, %1, %2, %3}, [%4];"
               : "=r"(r0), "=r"(r1), "=r"(r2), "=r"(r3) : "r"(addr) : "memory");
}
__device__ __forceinline__ uint32_t movtrans(uint32_t a) {
  uint32_t d;
  asm volatile("movmatrix.sync.aligned.m8n8.trans.b16 %0, %1;" : "=r"(d) : "r"(a));
  return d;
}
__device__ __forceinline__ void mma16816(float (&c)[4], uint32_t a0, uint32_t a1, uint32_t a2, uint32_t a3, uint32_t b0, uint32_t b1) {
  asm volatile("mma.sync.aligned.m16n8k16.row.col.f32.bf16.bf16.f32 {%0,%1,%2,%3}, {%4,%5,%6,%7}, {%8,%9}, {%0,%1,%2,%3};"
               : "+f"(c[0]), "+f"(c[1]), "+f"(c[2]), "+f"(c[3])
               : "r"(a0), "r"(a1), "r"(a2), "r"(a3), "r"(b0), "r"(b1));
}
__device__ __forceinline__ float2 lds_f2(uint32_t a) {
  float2 v;
  asm volatile("ld.shared.v2.f32 {%0, %1}, [%2];" : "=f"(v.x), "=f"(v.y) : "r"(a) : "memory");
  return v;
}
__device__ __forceinline__ float4 lds_f4(uint32_t a) {
  float4 v;
  asm volatile("ld.shared.v4.f32 {%0, %1, %2, %3}, [%4];" : "=f"(v.x), "=f"(v.y), "=f"(v.z), "=f"(v.w) : "r"(a) : "memory");
  return v;
}
__device__ __forceinline__ float lds_f(uint32_t a) {
  float v;
  asm volatile("ld.shared.f32 %0, [%1];" : "=f"(v) : "r"(a) : "memory");
  return v;
}
__device__ __forceinline__ void sts_f(uint32_t a, float v) { asm volatile("st.shared.f32 [%0], %1;" ::"r"(a), "f"(v) : "memory"); }
__device__ __forceinline__ uint32_t lds_u(uint32_t a) {
  uint32_t v;
  asm volatile("ld.shared.u32 %0, [%1];" : "=r"(v) : "r"(a) : "memory");
  return v;
}
__device__ __forceinline__ void sts_f2(uint32_t a, float x, float y) {
  asm volatile("st.shared.v2.f32 [%0], {%1, %2};" ::"r"(a), "f"(x), "f"(y) : "memory");
}
__device__ __forceinline__ void lds_u4(uint32_t a, uint32_t& x, uint32_t& y, uint32_t& z, uint32_t& w) {
  asm volatile("ld.shared.v4.u32 {%0, %1, %2, %3}, [%4];" : "=r"(x), "=r"(y), "=r"(z), "=r"(w) : "r"(a) : "memory");
}
__device__ __forceinline__ float ex2(float x) {
  float y;
  asm("ex2.approx.ftz.f32 %0, %1;" : "=f"(y) : "f"(x));
  return y;
}
__device__ __forceinline__ float rcp_hw(float x) {
  float y;
  asm("rcp.approx.ftz.f32 %0, %1;" : "=f"(y) : "f"(x));
  return y;
}
__device__ __forceinline__ float tanh_hw(float x) {
  float y;
  asm("tanh.approx.f32 %0, %1;" : "=f"(y) : "f"(x));
  return y;
}
__device__ __forceinline__ float quad_sum(float v) {
  v += __shfl_xor_sync(0xffffffffu, v, 1);
  return v + __shfl_xor_sync(0xffffffffu, v, 2);
}
__device__ __forceinline__ float quad_max(float v) {
  v = fmaxf(v, __shfl_xor_sync(0xffffffffu, v, 1));
  return fmaxf(v, __shfl_xor_sync(0xffffffffu, v, 2));
}

template <int N> __device__ __forceinline__ void wgmma_ss(float (&d)[96], uint64_t da, uint64_t db);
template <> __device__ __forceinline__ void wgmma_ss<128>(float (&d)[96], uint64_t da, uint64_t db) {
  asm volatile(
      "wgmma.mma_async.sync.aligned.m64n128k16.f32.bf16.bf16 {%0, %1, %2, %3, %4, %5, %6, %7, %8, %9, %10, %11, %12, %13, %14, %15, %16, %17, %18, %19, %20, %21, %22, %23, %24, %25, %26, %27, %28, %29, %30, %31, %32, %33, %34, %35, %36, %37, %38, %39, %40, %41, %42, %43, %44, %45, %46, %47, %48, %49, %50, %51, %52, %53, %54, %55, %56, %57, %58, %59, %60, %61, %62, %63}, %64, %65, 1, 1, 1, 0, 1;"
      : "+f"(d[0]), "+f"(d[1]), "+f"(d[2]), "+f"(d[3]), "+f"(d[4]), "+f"(d[5]), "+f"(d[6]), "+f"(d[7]), "+f"(d[8]), "+f"(d[9]), "+f"(d[10]), "+f"(d[11]), "+f"(d[12]), "+f"(d[13]), "+f"(d[14]), "+f"(d[15]), "+f"(d[16]), "+f"(d[17]), "+f"(d[18]), "+f"(d[19]), "+f"(d[20]), "+f"(d[21]), "+f"(d[22]), "+f"(d[23]), "+f"(d[24]), "+f"(d[25]), "+f"(d[26]), "+f"(d[27]), "+f"(d[28]), "+f"(d[29]), "+f"(d[30]), "+f"(d[31]), "+f"(d[32]), "+f"(d[33]), "+f"(d[34]), "+f"(d[35]), "+f"(d[36]), "+f"(d[37]), "+f"(d[38]), "+f"(d[39]), "+f"(d[40]), "+f"(d[41]), "+f"(d[42]), "+f"(d[43]), "+f"(d[44]), "+f"(d[45]), "+f"(d[46]), "+f"(d[47]), "+f"(d[48]), "+f"(d[49]), "+f"(d[50]), "+f"(d[51]), "+f"(d[52]), "+f"(d[53]), "+f"(d[54]), "+f"(d[55]), "+f"(d[56]), "+f"(d[57]), "+f"(d[58]), "+f"(d[59]), "+f"(d[60]), "+f"(d[61]), "+f"(d[62]), "+f"(d[63])
      : "l"(da), "l"(db));
}

template <> __device__ __forceinline__ void wgmma_ss<192>(float (&d)[96], uint64_t da, uint64_t db) {
  asm volatile(
      "wgmma.mma_async.sync.aligned.m64n192k16.f32.bf16.bf16 {%0, %1, %2, %3, %4, %5, %6, %7, %8, %9, %10, %11, %12, %13, %14, %15, %16, %17, %18, %19, %20, %21, %22, %23, %24, %25, %26, %27, %28, %29, %30, %31, %32, %33, %34, %35, %36, %37, %38, %39, %40, %41, %42, %43, %44, %45, %46, %47, %48, %49, %50, %51, %52, %53, %54, %55, %56, %57, %58, %59, %60, %61, %62, %63, %64, %65, %66, %67, %68, %69, %70, %71, %72, %73, %74, %75, %76, %77, %78, %79, %80, %81, %82, %83, %84, %85, %86, %87, %88, %89, %90, %91, %92, %93, %94, %95}, %96, %97, 1, 1, 1, 0, 1;"
      : "+f"(d[0]), "+f"(d[1]), "+f"(d[2]), "+f"(d[3]), "+f"(d[4]), "+f"(d[5]), "+f"(d[6]), "+f"(d[7]), "+f"(d[8]), "+f"(d[9]), "+f"(d[10]), "+f"(d[11]), "+f"(d[12]), "+f"(d[13]), "+f"(d[14]), "+f"(d[15]), "+f"(d[16]), "+f"(d[17]), "+f"(d[18]), "+f"(d[19]), "+f"(d[20]), "+f"(d[21]), "+f"(d[22]), "+f"(d[23]), "+f"(d[24]), "+f"(d[25]), "+f"(d[26]), "+f"(d[27]), "+f"(d[28]), "+f"(d[29]), "+f"(d[30]), "+f"(d[31]), "+f"(d[32]), "+f"(d[33]), "+f"(d[34]), "+f"(d[35]), "+f"(d[36]), "+f"(d[37]), "+f"(d[38]), "+f"(d[39]), "+f"(d[40]), "+f"(d[41]), "+f"(d[42]), "+f"(d[43]), "+f"(d[44]), "+f"(d[45]), "+f"(d[46]), "+f"(d[47]), "+f"(d[48]), "+f"(d[49]), "+f"(d[50]), "+f"(d[51]), "+f"(d[52]), "+f"(d[53]), "+f"(d[54]), "+f"(d[55]), "+f"(d[56]), "+f"(d[57]), "+f"(d[58]), "+f"(d[59]), "+f"(d[60]), "+f"(d[61]), "+f"(d[62]), "+f"(d[63]), "+f"(d[64]), "+f"(d[65]), "+f"(d[66]), "+f"(d[67]), "+f"(d[68]), "+f"(d[69]), "+f"(d[70]), "+f"(d[71]), "+f"(d[72]), "+f"(d[73]), "+f"(d[74]), "+f"(d[75]), "+f"(d[76]), "+f"(d[77]), "+f"(d[78]), "+f"(d[79]), "+f"(d[80]), "+f"(d[81]), "+f"(d[82]), "+f"(d[83]), "+f"(d[84]), "+f"(d[85]), "+f"(d[86]), "+f"(d[87]), "+f"(d[88]), "+f"(d[89]), "+f"(d[90]), "+f"(d[91]), "+f"(d[92]), "+f"(d[93]), "+f"(d[94]), "+f"(d[95])
      : "l"(da), "l"(db));
}

template <int R>
__device__ __forceinline__ void pin_regs(float (&a)[2][96]) {
#pragma unroll
  for (int m = 0; m < 2; m++)
#pragma unroll
    for (int i = 0; i < R; i++) asm volatile("" : "+f"(a[m][i])::"memory");
}

struct Ctx {
  uint32_t sb;
  int m, n, wg, w, lane;
};
__device__ __forceinline__ Ctx make_ctx(uint32_t sb, int id) {
  int lane;
  asm volatile("mov.u32 %0, %%laneid;" : "=r"(lane));
  asm volatile("" : "+r"(id), "+r"(sb));
  return Ctx{sb, (id >> 3) & 15, id & 7, id >> 9, (id >> 7) & 3, lane};
}
#define UNPACK_CTX(c) const uint32_t sb = c.sb; const int m = c.m, n = c.n, wg = c.wg, w = c.w, lane = c.lane

__device__ __forceinline__ uint32_t poll_line(const uint32_t* word, uint32_t target, uint32_t need) {
  uint32_t v;
  asm volatile(
      "{\n.reg .pred p;\n.reg .u32 it, m;\n.reg .s32 d;\nmov.u32 it, 0;\n"
      "POLL_LOOP:\n"
      "ld.relaxed.gpu.global.u32 %0, [%1];\n"
      "sub.s32 d, %0, %2;\n"
      "setp.ge.s32 p, d, 0;\n"
      "vote.sync.ballot.b32 m, p, 0xffffffff;\n"
      "and.b32 m, m, %3;\n"
      "setp.eq.u32 p, m, %3;\n"
      "@p bra.uni POLL_DONE;\n"
      "add.u32 it, it, 1;\n"
      "setp.lt.u32 p, it, 0x400000;\n"
      "@p bra.uni POLL_LOOP;\n"
      "trap;\n"
      "POLL_DONE:\n}"
      : "=&r"(v) : "l"(word), "r"(target), "r"(need) : "memory");
  return v;
}
__device__ __forceinline__ uint32_t ld_relaxed(const uint32_t* p) {
  uint32_t v;
  asm volatile("ld.relaxed.gpu.global.u32 %0, [%1];" : "=r"(v) : "l"(p) : "memory");
  return v;
}
__device__ __forceinline__ float chain(float x, uint32_t on, uint32_t zero) {
  return __uint_as_float(__float_as_uint(x) | (on & zero));
}
constexpr int MSG_SPINS = 1 << 20;

constexpr int STAGES_PER_LAYER = 152;
__device__ __forceinline__ int nib(uint64_t v, int i) { return (int)(v >> (4 * i)) & 15; }
__device__ __forceinline__ bool tile_wide(int t) { return (0xB >> t) & 1; }
__device__ __forceinline__ int tile_pos0(int t) { return t < 3 ? 0 : t == 3 ? 5 : 4 * t - 8; }
constexpr uint64_t SEG_TILE = 0x6665432210ull, SEG_PERIOD = 0x2232221122ull, SEG_ADD = 0x5300001000ull;
constexpr uint64_t SEG_LINE = 0x6543332100ull;

__device__ __forceinline__ void weight_coords(const Params& p, int t, int n, const CUtensorMap*& map, int& c0, int& c2) {
  map = &p.wqkv + nib(0x4332100ull, t);
  c0 = t < 2 ? 128 * n + 64 * t : 0;
  c2 = t < 2 ? 0 : (t == 2 || t == 6) ? 2 * n : 7 * n + nib(0x530000ull, t);
}

template <bool IS_A>
__device__ __forceinline__ void producer(const Params& p, uint32_t sb, int m, int n, int lane) {
  int inflight = 0, rph = 0;
  uint32_t b8 = 0, rb8 = 0, pos = 0, tag16 = 0, seen = 0;
  const uint32_t* word = g_flags + m * 32 + lane;
#pragma unroll 1
  for (int sg = 0; sg < 20; sg++) {
    const int layer = sg >= 10, s = sg - 10 * layer;
    const int t = nib(SEG_TILE, s), period = nib(SEG_PERIOD, s), add = nib(SEG_ADD, s);
    const bool wide = tile_wide(t), ownx = t != 2 && t != 6;
    const uint32_t bbytes = wide ? 3 * UNIT : 2 * UNIT;
    const int mul = t == 6 ? 7 : 2;
    int short_left = wide ? 99 : (s == 2 || s == 5) ? 4 : 0;
    if (s == 4 || s == 5) pos = tile_pos0(t) * UNIT;
    const CUtensorMap* map;
    int c0, c2;
    if (IS_A) {
      map = t == 2 ? &p.att_ld : t == 6 ? &p.h_ld : sg < 2 ? &p.xin_ld : &p.out_ld;
      if (sg == 1) seen = tag16 = (__ldcg(g_epoch + m * 8 + n) + 1) << 4;
    } else {
      if (sg > 0 && sg < 17 && add == 0) {
        weight_coords(p, t == 6 ? 0 : t + 1, n, map, c0, c2);
#pragma unroll 1
        for (int kb = m; kb < (t == 5 ? 56 : 16); kb += 16)
          if (elect_one()) tma_pf3(map, c0, 64 * kb, c2);
      }
      weight_coords(p, t, n, map, c0, c2);
    }
#pragma unroll 1
    for (int q = 0; q < 8; q++) {
      int src = ((n & 6) + q) & 7;
      if (ownx && q < 2) src ^= n & 1;
      const bool own = ownx && q == 0;
      if (IS_A && sg >= 2) {
        const uint32_t need = own ? 0u : 0xFu << (4 * src), target = tag16 + 7 * layer + nib(SEG_LINE, s);
        if ((__ballot_sync(0xffffffffu, (int)(seen - target) >= 0) & need) != need) poll_line(word, target, need);
        asm volatile("fence.acquire.gpu;" ::: "memory");
        fence_async_global();
        seen = ld_relaxed(word);
      }
      int kc = 64 * (mul * src + add);
#pragma unroll 1
      for (int a = 0; a < period; a++) {
        const int lag = short_left > 0 ? 3 : 4;
        short_left--;
#pragma unroll 1
        for (; inflight > lag; inflight--) {
          mbar_wait(sb + BAR_EMPTY + rb8, rph);
          rb8 += 8;
          if (rb8 == 8 * NBAR) { rb8 = 0; rph ^= 1; }
        }
        const uint32_t fb = sb + BAR_FULL + b8;
        if (elect_one()) {
          if (IS_A) {
            mbar_expect_tx(fb, own ? 0 : 16384);
            if (!own) tma_ld2(sb + pos + bbytes, map, fb, kc, 128 * m);
          } else {
            mbar_expect_tx(fb, bbytes);
            tma_ld3(sb + pos, map, fb, c0, kc, c2);
          }
        }
        kc += 64;
        inflight++;
        b8 += 8;
        if (b8 == 8 * NBAR) b8 = 0;
        pos += bbytes + 2 * UNIT;
        if (pos >= RING_UNITS * UNIT) pos -= RING_UNITS * UNIT;
      }
    }
  }
}

template <int N>
__device__ __forceinline__ void mainloop(float (&acc)[2][96], uint32_t sb, int i, int mn) {
  constexpr uint32_t Z16 = (2 + N / 64) * (UNIT >> 4), RING16 = RING_UNITS * (UNIT >> 4);
  constexpr uint32_t A_OFF = Z16 - 1024 + (uint32_t)DESC_A - (uint32_t)DESC_B;
  const int wg = i & 1;
  const int layer = i >= 7, t = i - 7 * layer;
  const bool own = t != 2 && t != 6;
  const int g0 = layer * STAGES_PER_LAYER + 16 * t;
  const uint32_t s16 = (sb & 0x3FFFF) >> 4;
  const uint32_t blast = uniform((uint32_t)DESC_B + s16 + RING16 - Z16), flast = uniform(sb + BAR_FULL + 8 * (NBAR - 1));
  const int nkb = t == 6 ? 56 : 16;
  int run = uniform(t == 1 ? WIN1 + 1 : t == 2 ? WIN2 + 1 : nkb), rest = nkb - run;
  uint32_t fb = sb + BAR_FULL + 8 * (g0 % NBAR), ph = (g0 / NBAR) & 1;
  uint32_t prev = sb + BAR_DUMMY - 8 * NBAR;
  uint32_t blo = (uint32_t)DESC_B + s16 + tile_pos0(t) * (UNIT >> 4);
  uint32_t alo = own ? (uint32_t)DESC_A + s16 + (OFF_X >> 4) : blo + A_OFF;
  uint32_t aoff = own ? alo + 1024 - (blo + Z16) : A_OFF;
  pin_regs<N / 2>(acc);
  if (i > 0) bar_sync(BAR_ORDER + wg, 256);
  if (N == 192 && t != 1) mbar_wait(sb + BAR_XREADY, t == 3);
  mbar_wait(fb, ph);
  PROF_T(4 + i * 4);
#pragma unroll 1
  while (true) {
    const uint64_t da = (DESC_A & ~0xffffffffull) | alo, db = (DESC_B & ~0xffffffffull) | blo;
    asm volatile("wgmma.fence.sync.aligned;" ::: "memory");
    wgmma_ss<N>(acc[0], da, db);
    wgmma_ss<N>(acc[1], da + 64, db);
    wgmma_ss<N>(acc[0], da + 2, db + 128);
    wgmma_ss<N>(acc[1], da + 66, db + 128);
    asm volatile("wgmma.commit_group.sync.aligned;" ::: "memory");
    asm volatile("wgmma.wait_group.sync.aligned 1;" ::: "memory");
    PROF_S(g0 + nkb - run - rest);
    if (elect_one()) mbar_arrive(prev + 8 * NBAR);
    prev = fb;
    if (fb == flast) { fb -= 8 * NBAR; ph++; }
    fb += 8;
    if (blo == blast) blo -= RING16;
    blo += Z16;
    alo = blo + aoff;
    aoff = A_OFF;
    run--;
    const bool ready = mbar_test(fb, ph) && run != 0;
    asm volatile("wgmma.fence.sync.aligned;" ::: "memory");
    wgmma_ss<N>(acc[0], da + 4, db + 256);
    wgmma_ss<N>(acc[1], da + 68, db + 256);
    wgmma_ss<N>(acc[0], da + 6, db + 384);
    wgmma_ss<N>(acc[1], da + 70, db + 384);
    asm volatile("wgmma.commit_group.sync.aligned;" ::: "memory");
    if (!ready) {
      if (run == 0) {
        if (rest == 0) break;
        run = rest;
        rest = 0;
        bar_arrive(BAR_GO, 256);
        bar_sync(BAR_DONE, 256);
      }
      mbar_wait(fb, ph);
    }
  }
  if (i < 13) bar_arrive(BAR_ORDER + (wg ^ 1), 256);
  asm volatile("wgmma.wait_group.sync.aligned 0;" ::: "memory");
  pin_regs<N / 2>(acc);
  if (elect_one()) mbar_arrive(prev + 8 * NBAR);
  PROF_T(5 + i * 4);
}

#define ACC(q, j, e) acc[(q) & 1][4 * (j) + 2 * ((q) >> 1) + (e)]

__device__ __forceinline__ void write_partial_stats(const Ctx& c, int ln, uint32_t tag) {
  const uint32_t xrow = c.sb + OFF_X + c.w * 4096 + c.lane * 128;
  float s = 0.f, q = 0.f;
#pragma unroll 2
  for (int j = 0; j < 16; j++) {
    uint32_t u[4];
    lds_u4(xrow + (j >> 3) * 16384 + (((j & 7) ^ (c.lane & 7)) << 4), u[0], u[1], u[2], u[3]);
#pragma unroll
    for (int e = 0; e < 4; e++) {
      const float a = bf_lo(u[e]), d = bf_hi(u[e]);
      s += a; q = fmaf(a, a, q);
      s += d; q = fmaf(d, d, q);
    }
  }
  st_msg(g_stats + (ln * 8 + c.n) * SEQ + 128 * c.m + 32 * c.w + c.lane, __float_as_uint(s),
         __float_as_uint(fmaxf(q - s * s * (1.f / 128.f), 0.f)), 0u, tag);
}

__device__ __forceinline__ void finish_row_stats(const Ctx& c, int ln, uint32_t tag) {
  const uint4* src = g_stats + ln * 8 * SEQ + 128 * c.m + 32 * c.w + c.lane;
  uint32_t ps[8], pm[8];
#pragma unroll 1
  for (int it = 0; it < MSG_SPINS; it++) {
    uint32_t bad = 0, u, tg;
#pragma unroll
    for (int k = 0; k < 8; k++) { ld_msg(src + k * SEQ, ps[k], pm[k], u, tg); bad |= tg ^ tag; }
    if (__all_sync(0xffffffffu, bad == 0)) break;
  }
  float s = 0.f, m2 = 0.f;
#pragma unroll
  for (int k = 0; k < 8; k++) s += __uint_as_float(ps[k]);
  const float mean = s * (1.f / DM);
#pragma unroll
  for (int k = 0; k < 8; k++) {
    const float d = __uint_as_float(ps[k]) * (1.f / 128.f) - mean;
    m2 += fmaf(128.f * d, d, __uint_as_float(pm[k]));
  }
  sts_f2(c.sb + OFF_ROW + (32 * c.w + c.lane) * 8, rsqrtf(m2 * (1.f / DM) + 1e-5f), mean);
  __syncwarp();
}

__device__ __forceinline__ void attn_scores(const uint32_t* qa, const uint32_t* qb, const uint32_t* k0, const uint32_t* k1,
                                            const uint32_t* k2, const uint32_t* k3, float (&l)[4], const float4& zero,
                                            bool par, bool early) {
  float s[4][4];
#pragma unroll
  for (int kb = 0; kb < 4; kb++) {
    const uint32_t* kk = kb == 0 ? k0 : kb == 1 ? k1 : kb == 2 ? k2 : k3;
    asm volatile("mma.sync.aligned.m16n8k16.row.col.f32.bf16.bf16.f32 {%0,%1,%2,%3}, {%4,%5,%6,%7}, {%8,%9}, {%10,%11,%12,%13};"
                 : "=f"(s[kb][0]), "=f"(s[kb][1]), "=f"(s[kb][2]), "=f"(s[kb][3])
                 : "r"(qa[0]), "r"(qb[0]), "r"(qa[1]), "r"(qb[1]), "r"(kk[0]), "r"(kk[1]), "f"(zero.x), "f"(zero.y),
                   "f"(zero.z), "f"(zero.w));
  }
#pragma unroll
  for (int kb = 0; kb < 4; kb++) {
    const uint32_t* kk = kb == 0 ? k0 : kb == 1 ? k1 : kb == 2 ? k2 : k3;
    mma16816(s[kb], qa[2], qb[2], qa[3], qb[3], kk[2], kk[3]);
  }
  l[0] = par ? s[1][1] : s[1][0];
  l[1] = early ? (par ? s[0][1] : s[0][0]) : (par ? s[2][1] : s[2][0]);
  l[2] = par ? s[2][3] : s[2][2];
  l[3] = early ? (par ? s[1][3] : s[1][2]) : (par ? s[3][3] : s[3][2]);
}

__device__ __forceinline__ void attn_mix(const float (&l)[4], const float (&sc)[4], const float (&off)[4], const float (&rk)[4],
                                         const uint32_t* v0, const uint32_t* v1, const uint32_t* v2, const uint32_t* v3,
                                         float (&o)[4][4], bool par, bool early) {
  float x[4];
#pragma unroll
  for (int e = 0; e < 4; e++) x[e] = fmaf(l[e], sc[e], off[e]);
  const float ml = quad_max(fmaxf(x[0], x[1])), mh = quad_max(fmaxf(x[2], x[3]));
  x[0] = ex2(x[0] - ml); x[1] = ex2(x[1] - ml);
  x[2] = ex2(x[2] - mh); x[3] = ex2(x[3] - mh);
  const float il = rcp_hw(quad_sum(x[0] + x[1])), ih = rcp_hw(quad_sum(x[2] + x[3]));
  const uint32_t pl = pack_bf16(x[0] * rk[0] * il, x[1] * rk[1] * il), ph = pack_bf16(x[2] * rk[2] * ih, x[3] * rk[3] * ih);
  const uint32_t sel_a = par ? 0x1044u : 0x4410u, sel_b = par ? 0x3244u : 0x4432u;
  const uint32_t sel_e = early ? sel_b : 0x4444u, sel_l = early ? 0x4444u : sel_b;
  const uint32_t pla = __byte_perm(pl, 0, sel_a), pha = __byte_perm(ph, 0, sel_a);
  const uint32_t e_l = __byte_perm(pl, 0, sel_e), e_h = __byte_perm(ph, 0, sel_e);
  const uint32_t l_l = __byte_perm(pl, 0, sel_l), l_h = __byte_perm(ph, 0, sel_l);
#pragma unroll
  for (int jn = 0; jn < 4; jn++) {
    o[jn][0] = o[jn][1] = o[jn][2] = o[jn][3] = 0.f;
    mma16816(o[jn], e_l, 0u, pla, e_h, v0[jn], v1[jn]);
  }
#pragma unroll
  for (int jn = 0; jn < 4; jn++) mma16816(o[jn], l_l, pha, 0u, l_h, v2[jn], v3[jn]);
}

__device__ __forceinline__ void colsum_partial(const Params& p, const Ctx& cx, bool qkv, uint32_t tag) {
  UNPACK_CTX(cx);
  const int groups = qkv ? 48 : 56, cg = (w & 1) * 32 + lane, tid = w * 32 + lane;
  const int ld = qkv ? 3 * DM / 8 : FF / 8;
  float a[8] = {0.f, 0.f, 0.f, 0.f, 0.f, 0.f, 0.f, 0.f};
  if (cg < groups) {
    const uint4* W = reinterpret_cast<const uint4*>(qkv ? p.wqkv_p : p.w1_p) + (64 * m + 32 * (w >> 1)) * ld +
                     (qkv ? (cg >> 4) * (DM / 8) + 16 * n + (cg & 15) : 56 * n + cg);
    uint4 v[4], nx[4], nx2[4];
#pragma unroll 1
    for (int r = 8 + (lane & 7); r < 32; r += 8) asm volatile("prefetch.global.L2 [%0];" ::"l"(W + r * ld));
#pragma unroll
    for (int r = 0; r < 4; r++) { nx[r] = __ldcg(W + r * ld); nx2[r] = __ldcg(W + (4 + r) * ld); }
#pragma unroll 1
    for (int it = 0; it < 8; it++) {
#pragma unroll
      for (int r = 0; r < 4; r++) {
        v[r] = nx[r];
        nx[r] = nx2[r];
        if (it < 6) nx2[r] = __ldcg(W + (4 * it + 8 + r) * ld);
      }
#pragma unroll
      for (int r = 0; r < 4; r++) {
        a[0] += bf_lo(v[r].x); a[1] += bf_hi(v[r].x); a[2] += bf_lo(v[r].y); a[3] += bf_hi(v[r].y);
        a[4] += bf_lo(v[r].z); a[5] += bf_hi(v[r].z); a[6] += bf_lo(v[r].w); a[7] += bf_hi(v[r].w);
      }
    }
  }
  bar_sync(BAR_WG + wg, 128);
  const uint32_t part = sb + OFF_STG + (w >> 1) * 2048 + cg * 32;
#pragma unroll
  for (int e = 0; e < 4; e++) sts_f2(part + 8 * e, a[2 * e], a[2 * e + 1]);
  bar_sync(BAR_WG + wg, 128);
  uint4* dst = g_csp + (((qkv ? 0 : 8) + n) * 16 + m) * 160;
#pragma unroll 1
  for (int c = tid; c < (qkv ? 128 : 160); c += 128) {
    const uint32_t q = sb + OFF_STG + c * 12;
    st_msg(dst + c, __float_as_uint(lds_f(q) + lds_f(q + 2048)), __float_as_uint(lds_f(q + 4) + lds_f(q + 2052)),
           __float_as_uint(lds_f(q + 8) + lds_f(q + 2056)), tag);
  }
}

__device__ __forceinline__ void colsum_gather(const Params& p, const Ctx& cx, bool qkv, uint32_t tag) {
  const int n = cx.n;
#pragma unroll 1
  for (int c0 = cx.w * 32; c0 < (qkv ? 128 : 160); c0 += 128) {
    const int c = c0 + cx.lane;
    const uint4* src = g_csp + ((qkv ? 0 : 8) + n) * 16 * 160 + c;
    float s[3];
#pragma unroll 1
    for (int it = 0; it < MSG_SPINS; it++) {
      uint32_t bad = 0;
      s[0] = s[1] = s[2] = 0.f;
#pragma unroll
      for (int mm = 0; mm < 16; mm++) {
        uint32_t x, y, z, tg;
        ld_msg(src + mm * 160, x, y, z, tg);
        bad |= tg ^ tag;
        s[0] += __uint_as_float(x); s[1] += __uint_as_float(y); s[2] += __uint_as_float(z);
      }
      if (__all_sync(0xffffffffu, bad == 0)) break;
    }
#pragma unroll 1
    for (int e = 0; e < 3; e++) {
      const int col = 3 * c + e;
      const float v = e == 0 ? s[0] : e == 1 ? s[1] : s[2];
      if (qkv) {
        sts_f(cx.sb + OFF_CSQ + ((((col >> 6) & 1) * 3 + (col >> 7)) * 64 + (col & 63)) * 4, v);
      } else if (col < 448) {
        const uint32_t a = cx.sb + OFF_CSF + (col >> 1) * 16 + (col & 1) * 4;
        sts_f(a, v);
        sts_f(a + 8, 0.5f * __bfloat162float(p.b1[448 * n + col]));
      }
    }
  }
}

__device__ __forceinline__ void gelu_epilogue(const Params& p, float (&acc)[2][96], const Ctx& cx, int t) {
  UNPACK_CTX(cx);
  (void)wg;
  float rs[4], rm[4];
#pragma unroll
  for (int q = 0; q < 4; q++) {
    const float2 v = lds_f2(sb + OFF_ROW + (32 * w + 8 * q + (lane >> 2)) * 8);
    rs[q] = 0.5f * v.x;
    rm[q] = -rs[q] * v.y;
  }
  const int col0 = t == 3 ? 0 : t == 4 ? 192 : 320, steps = t == 3 ? 6 : 4;
  const uint32_t stg = sb + OFF_STG + w * 4096;
  uint32_t ctab = sb + OFF_CSF + (col0 / 2 + (lane & 3)) * 16;
  float v[2][16];
#pragma unroll
  for (int r = 0; r < 16; r++) { v[0][r] = acc[0][r]; v[1][r] = acc[1][r]; }
#pragma unroll 1
  for (int it = 0; it < steps; it++) {
    uint32_t hp[4][4];
#pragma unroll
    for (int j = 0; j < 4; j++) {
      const float4 cb = lds_f4(ctab + j * 64);
#pragma unroll
      for (int q = 0; q < 4; q++) {
        float y[2];
        const int k = 4 * j + q - GELU_DEP;
        const float rmq = k >= 0 ? chain(rm[q], hp[k >> 2][k & 3], p.zero) : rm[q];
#pragma unroll
        for (int e = 0; e < 2; e++) {
          const float z = fmaf(v[q & 1][4 * j + 2 * (q >> 1) + e], rs[q], fmaf(rmq, e ? cb.y : cb.x, e ? cb.w : cb.z));
          const float u = z * fmaf(z * z, 8.f * 0.7978845608028654f * 0.044715f, 2.f * 0.7978845608028654f);
          y[e] = fmaf(z, tanh_hw(u), z);
        }
        hp[j][q] = pack_bf16(y[0], y[1]);
      }
    }
    ctab += 256;
    if (!(it & 1)) {
      if (lane == 0) bulk_wait_read();
      __syncwarp();
    }
#pragma unroll
    for (int j = 0; j < 4; j++)
      stsm4(stg + lane * 128 + (((4 * (it & 1) + j) ^ (lane & 7)) << 4), hp[j][0], hp[j][1], hp[j][2], hp[j][3]);
    if (it & 1) {
      fence_async_smem();
      __syncwarp();
      if (lane == 0) {
        tma_st2(&p.h_st, stg, 448 * n + col0 + 32 * (it - 1), 128 * m + 32 * w);
        bulk_commit();
      }
      if (it == steps - 1) break;
    }
    const uint32_t zr = hp[3][3] & p.zero;
#define REFILL(k) _Pragma("unroll") for (int r = 0; r < 32; r++) \
      asm volatile("{\n.reg .b32 t;\nmov.b32 t, %1;\nor.b32 t, t, %2;\nmov.b32 %0, t;\n}" \
                   : "=f"(v[r >> 4][r & 15]) : "f"(acc[r >> 4][16 * k + (r & 15)]), "r"(zr)); break;
    switch (it) {
      case 0: REFILL(1)
      case 1: REFILL(2)
      case 2: REFILL(3)
      case 3: REFILL(4)
      default: REFILL(5)
    }
#undef REFILL
  }
}

__device__ __forceinline__ void attn_epilogue(const Params& p, float (&acc)[2][96], const Ctx& cx, int layer, int t, uint32_t tag) {
  UNPACK_CTX(cx);
  const bool par = (lane >> 2) & 1, early = (lane & 3) > (lane >> 3);
  uint32_t Q[4][8], K[4][8], V[4][8];
  float kr[6], qr[4];
#pragma unroll
  for (int q = 0; q < 4; q++) {
    kr[2 + q] = lds_f(sb + OFF_ROW + (32 * w + 8 * q + 2 * (lane & 3) + par) * 8);
    qr[q] = lds_f(sb + OFF_ROW + (32 * w + 8 * q + (lane >> 2)) * 8) * (0.17677669529663687f * 1.4426950408889634f);
  }
  const int slot = ((layer * 2 + t) * 16 + m) * 8 + n;
  uint4* const exc = reinterpret_cast<uint4*>(__cvta_shared_to_generic(sb + OFF_STG));
#pragma unroll
  for (int qq = 0; qq < 4; qq++) {
    const int q = qq ^ 2;
#pragma unroll
    for (int j = 0; j < 8; j++) {
      K[q][j] = pack_bf16(ACC(q, 8 + j, 0), ACC(q, 8 + j, 1));
      V[q][j] = movtrans(pack_bf16(ACC(q, 16 + j, 0), ACC(q, 16 + j, 1)));
    }
    if (qq == 1) {
      uint4* e = (w < 3 ? exc + w * 512 : g_halo + slot * 512) + lane;
#pragma unroll
      for (int j = 0; j < 8; j++) {
        st_msg(e + j * 32, K[2 + (j >> 2)][2 * (j & 3)], K[2 + (j >> 2)][2 * (j & 3) + 1], __float_as_uint(kr[4]), tag);
        st_msg(e + (8 + j) * 32, V[2][j], V[3][j], __float_as_uint(kr[5]), tag);
      }
    }
  }
#pragma unroll
  for (int q = 0; q < 4; q++)
#pragma unroll
    for (int j = 0; j < 8; j++) Q[q][j] = pack_bf16(ACC(q, j, 0), ACC(q, j, 1));
  bar_sync(BAR_WG + wg, 128);
  const uint4* src = (w > 0 ? exc + (w - 1) * 512 : m > 0 ? g_halo + (slot - 8) * 512 : exc) + lane;
  uint32_t PK[2][8], PV[2][8], r4, r5;
#pragma unroll 1
  for (int it = 0; it < MSG_SPINS; it++) {
    uint32_t tg, bad = 0;
#pragma unroll
    for (int j = 0; j < 8; j++) {
      ld_msg(src + j * 32, PK[j >> 2][2 * (j & 3)], PK[j >> 2][2 * (j & 3) + 1], r4, tg); bad |= tg ^ tag;
      ld_msg(src + (8 + j) * 32, PV[0][j], PV[1][j], r5, tg); bad |= tg ^ tag;
    }
    if (__all_sync(0xffffffffu, bad == 0)) break;
  }
  kr[0] = __uint_as_float(r4);
  kr[1] = __uint_as_float(r5);
  float rk[2][4], sc[2][4], off[2][4];
#pragma unroll
  for (int g = 0; g < 2; g++) {
    rk[g][0] = kr[2 * g + 1];
    rk[g][1] = early ? kr[2 * g] : kr[2 * g + 2];
    rk[g][2] = kr[2 * g + 2];
    rk[g][3] = early ? kr[2 * g + 1] : kr[2 * g + 3];
#pragma unroll
    for (int e = 0; e < 4; e++) {
      const bool masked = g == 0 && e != 2 && (m | w) == 0 && (e == 0 || early);
      sc[g][e] = masked ? 0.f : rk[g][e] * qr[2 * g + (e >> 1)];
      off[g][e] = masked ? -1e30f : 0.f;
    }
  }
  bar_sync(BAR_GO, 256);
  const float4 zero = lds_f4(sb + OFF_ZERO);
  float l[2][2][4], o[2][2][4][4];
#pragma unroll
  for (int h = 0; h < 2; h++) {
    attn_scores(&Q[2][4 * h], &Q[3][4 * h], &K[0][4 * h], &K[1][4 * h], &K[2][4 * h], &K[3][4 * h], l[1][h], zero, par, early);
    attn_scores(&Q[0][4 * h], &Q[1][4 * h], &PK[0][4 * h], &PK[1][4 * h], &K[0][4 * h], &K[1][4 * h], l[0][h], zero, par, early);
  }
#pragma unroll
  for (int h = 0; h < 2; h++) {
    attn_mix(l[1][h], sc[1], off[1], rk[1], &V[0][4 * h], &V[1][4 * h], &V[2][4 * h], &V[3][4 * h], o[1][h], par, early);
    attn_mix(l[0][h], sc[0], off[0], rk[0], &PV[0][4 * h], &PV[1][4 * h], &V[0][4 * h], &V[1][4 * h], o[0][h], par, early);
  }
  const uint32_t stg = sb + OFF_STG + w * 4096;
#pragma unroll
  for (int j = 0; j < 8; j++) {
    const float(&a)[4] = o[0][j >> 2][j & 3];
    const float(&c)[4] = o[1][j >> 2][j & 3];
    stsm4(stg + lane * 128 + ((j ^ (lane & 7)) << 4), pack_bf16(a[0], a[1]), pack_bf16(a[2], a[3]), pack_bf16(c[0], c[1]),
          pack_bf16(c[2], c[3]));
  }
  bar_arrive(BAR_DONE, 256);
  fence_async_smem();
  __syncwarp();
  if (lane == 0) {
    tma_st2(&p.att_st, stg, 128 * n + 64 * t, 128 * m + 32 * w);
    bulk_commit();
  }
}

__device__ __forceinline__ void consumer_tile(const Params& p, uint32_t sb0, int i, int mn) {
  const int layer = i >= 7, t = i - 7 * layer;
  const bool resid = i == -1 || t == 2 || t == 6;
  uint32_t tag;
  if (i >= 0) {
    float acc[2][96];
    if (resid) {
      const Ctx cx = make_ctx(sb0, mn);
      const uint32_t xrow = cx.sb + OFF_X + cx.w * 4096 + cx.lane * 128;
      const uint32_t* b2 = reinterpret_cast<const uint32_t*>(p.b2 + 128 * cx.n) + (cx.lane & 3);
#pragma unroll
      for (int j = 0; j < 16; j++) {
        uint32_t r[4], bb = 0;
        ldsm4(xrow + (j >> 3) * 16384 + (((j & 7) ^ (cx.lane & 7)) << 4), r[0], r[1], r[2], r[3]);
        if (t == 6) bb = __ldg(b2 + 4 * j);
#pragma unroll
        for (int q = 0; q < 4; q++) {
          const int k = 4 * j + q - 1;
          const uint32_t u = k >= 0 ? r[q] | (__float_as_uint(ACC(k & 3, k >> 2, 1)) & p.zero) : r[q];
          ACC(q, j, 0) = bf_lo(u) + bf_lo(bb);
          ACC(q, j, 1) = bf_hi(u) + bf_hi(bb);
        }
      }
    } else {
#pragma unroll
      for (int r = 0; r < 64; r++) acc[0][r] = acc[1][r] = 0.f;
    }
    if (tile_wide(t)) {
#pragma unroll
      for (int r = 64; r < 96; r++) acc[0][r] = acc[1][r] = 0.f;
#pragma unroll 1
      for (int phase = 0; phase < 2; phase++) {
        if (t + phase == 1) {
          const Ctx cx = make_ctx(sb0, mn);
          float nm[4];
#pragma unroll
          for (int q = 0; q < 4; q++) nm[q] = -lds_f(cx.sb + OFF_ROW + (32 * cx.w + 8 * q + (cx.lane >> 2)) * 8 + 4);
          const uint32_t ctab = cx.sb + OFF_CSQ + (t * 192 + 2 * (cx.lane & 3)) * 4;
#pragma unroll
          for (int j = 0; j < 24; j++) {
            const float2 cs = lds_f2(ctab + j * 32);
#pragma unroll
            for (int q = 0; q < 4; q++) {
              const int k = 4 * j + q - 1;
              const float nq = k >= 0 ? chain(nm[q], __float_as_uint(ACC(k & 3, k >> 2, 1)), p.zero) : nm[q];
              ACC(q, j, 0) = fmaf(nq, cs.x, ACC(q, j, 0));
              ACC(q, j, 1) = fmaf(nq, cs.y, ACC(q, j, 1));
            }
          }
        }
        if (phase == 0) {
          mainloop<192>(acc, sb0, i, mn);
          bar_sync(BAR_GUARD + (i & 1), 256);
        }
      }
      if (t < 2) {
        attn_epilogue(p, acc, make_ctx(sb0, mn), layer, t, lds_u(sb0 + OFF_TAG));
        goto tile_done;
      }
    } else {
      mainloop<128>(acc, sb0, i, mn);
      if (resid) {
        const Ctx cx = make_ctx(sb0, mn);
        UNPACK_CTX(cx);
        (void)wg;
        const uint32_t xrow = sb + OFF_X + w * 4096 + lane * 128;
#pragma unroll
        for (int j = 0; j < 16; j++)
          stsm4(xrow + (j >> 3) * 16384 + (((j & 7) ^ (lane & 7)) << 4), pack_bf16(ACC(0, j, 0), ACC(0, j, 1)),
                pack_bf16(ACC(1, j, 0), ACC(1, j, 1)), pack_bf16(ACC(2, j, 0), ACC(2, j, 1)), pack_bf16(ACC(3, j, 0), ACC(3, j, 1)));
        fence_async_smem();
        __syncwarp();
        if (lane == 0) {
          mbar_arrive(sb + BAR_XREADY);
          tma_st2(&p.out_st, sb + OFF_X + w * 4096, 128 * n, 128 * m + 32 * w);
          tma_st2(&p.out_st, sb + OFF_X + 16384 + w * 4096, 128 * n + 64, 128 * m + 32 * w);
          bulk_commit();
        }
        goto tile_done;
      }
      bar_sync(BAR_GUARD + (i & 1), 256);
#pragma unroll
      for (int r = 64; r < 96; r++) acc[0][r] = acc[1][r] = acc[0][0];
    }
    gelu_epilogue(p, acc, make_ctx(sb0, mn), t);
  tile_done:
    tag = lds_u(sb0 + OFF_TAG);
  } else {
    tag = __ldcg(g_epoch + (mn & 127)) + 1;
    asm volatile("st.shared.u32 [%0], %1;" ::"r"(sb0 + OFF_TAG), "r"(tag) : "memory");
  }
  const Ctx cx = make_ctx(sb0, mn);
  if (i == 13) {
    if (cx.lane == 0) bulk_wait_read();
    bar_sync(BAR_GUARD + 1, 256);
    if (cx.w + cx.lane == 0) g_epoch[mn & 127] = tag;
    return;
  }
  if (cx.lane == 0) {
    bulk_wait_all();
    asm volatile("fence.release.gpu;" ::: "memory");
    st_relaxed(g_flags + cx.m * 32 + 4 * cx.n + cx.w, 16 * tag + 1 + i);
  }
  __syncwarp();
  if (i <= 0) colsum_partial(p, cx, i < 0, tag);
  if (resid) {
    const int ln = (i + 3) >> 2;
    if (i < 0) mbar_wait(sb0 + BAR_XREADY, 0);
    write_partial_stats(cx, ln, tag);
    if (i >= 0) bar_sync(BAR_GUARD + (i & 1), 256);
    if (i <= 2) colsum_gather(p, cx, i < 0, tag);
    finish_row_stats(cx, ln, tag);
    bar_sync(BAR_WG + (i & 1), 128);
  }
  bar_arrive(BAR_GUARD + ((i & 1) ^ 1), 256);
}

__global__ void __cluster_dims__(2, 1, 1) __launch_bounds__(384, 1) fused_layers_kernel(const __grid_constant__ Params p) {
  extern __shared__ __align__(1024) uint8_t smem_raw[];
  const uint32_t sb = uniform((uint32_t)__cvta_generic_to_shared(smem_raw));
  const int tid = threadIdx.x, lane = tid & 31, warp = uniform(tid >> 5), wg = warp >> 2, w = warp & 3;

  int mn;
  {
    int id = blockIdx.x;
    if (p.by_smid) asm volatile("mov.u32 %0, %%smid;" : "=r"(id));
    else if (id >= 120) id += 4;
    const int c = id >> 1;
    int g, j;
    if (c < 32) { g = c & 7; j = c >> 3; }
    else if (c < 60) { g = 1 + (c - 32) % 7; j = 4 + (c - 32) / 7; }
    else { g = 0; j = c - 58; }
    mn = ((g >> 2) * 8 + j) * 8 + (g & 3) * 2 + (id & 1);
    if (c == 60 || c == 61) {
      if (tid < 32) {
        const uint32_t tag = __ldcg(g_epoch + NCTA + (id & 3)) + 1;
#pragma unroll 1
        for (int mm = 0; mm < 16; mm++) poll_line(g_flags + mm * 32 + lane, 16 * tag, 0xffffffffu);
        if (tid == 0) g_epoch[NCTA + (id & 3)] = tag;
      }
      return;
    }
  }
  const int m = mn >> 3, n = mn & 7;
  const uint32_t full0 = sb + OFF_BAR, empty0 = full0 + 8 * NBAR, xready = full0 + 16 * NBAR;
  if (tid == 256) asm volatile("prefetch.tensormap [%0];" ::"l"(&p.wqkv) : "memory");
  if (tid == 288) asm volatile("prefetch.tensormap [%0];" ::"l"(&p.xin_ld) : "memory");
  if (tid == 0) {
    for (int s = 0; s < NBAR; s++) {
      mbar_init(full0 + 8 * s, 2);
      mbar_init(empty0 + 8 * s, 4);
    }
    mbar_init(xready, 4);
    mbar_init(sb + BAR_DUMMY, 4);
    sts_f2(sb + OFF_ZERO, 0.f, 0.f);
    sts_f2(sb + OFF_ZERO + 8, 0.f, 0.f);
    fence_async_smem();
  }
  __syncthreads();

  if (wg == 2) {
    asm volatile("setmaxnreg.dec.sync.aligned.u32 40;");
    if (w == 0) {
      producer<false>(p, sb, m, n, lane);
    } else if (w == 1) {
      if (elect_one()) {
        mbar_expect_tx(xready, 32768);
        tma_ld2(sb + OFF_X, &p.xin_ld, xready, 128 * n, 128 * m);
        tma_ld2(sb + OFF_X + 16384, &p.xin_ld, xready, 128 * n + 64, 128 * m);
        mbar_arrive(xready); mbar_arrive(xready); mbar_arrive(xready);
      }
      producer<true>(p, sb, m, n, lane);
    }
  } else {
    asm volatile("setmaxnreg.inc.sync.aligned.u32 232;");
#pragma unroll 1
    for (int i = -wg; i < 14; i += 2) {
      consumer_tile(p, sb, i, mn | (warp << 7));
      PROF_T(i < 0 ? 3 : 6 + i * 4);
    }
  }
}

typedef CUresult (*EncodeFn)(CUtensorMap*, CUtensorMapDataType, cuuint32_t, void*, const cuuint64_t*, const cuuint64_t*,
                             const cuuint32_t*, const cuuint32_t*, CUtensorMapInterleave, CUtensorMapSwizzle,
                             CUtensorMapL2promotion, CUtensorMapFloatOOBfill);

void make_2d(EncodeFn enc, CUtensorMap* m, const void* ptr, uint64_t cols, uint64_t rows, uint32_t box_rows) {
  cuuint64_t d[2] = {cols, rows}, st[1] = {cols * 2};
  cuuint32_t b[2] = {64, box_rows}, e[2] = {1, 1};
  enc(m, CU_TENSOR_MAP_DATA_TYPE_BFLOAT16, 2, const_cast<void*>(ptr), d, st, b, e, CU_TENSOR_MAP_INTERLEAVE_NONE,
      CU_TENSOR_MAP_SWIZZLE_128B, CU_TENSOR_MAP_L2_PROMOTION_L2_128B, CU_TENSOR_MAP_FLOAT_OOB_FILL_NONE);
}
void make_3d(EncodeFn enc, CUtensorMap* m, const void* ptr, uint64_t d0, uint64_t rows, uint64_t d2, uint64_t row_bytes,
             uint64_t chunk_bytes, uint32_t box_chunks) {
  cuuint64_t d[3] = {d0, rows, d2}, st[2] = {row_bytes, chunk_bytes};
  cuuint32_t b[3] = {64, 64, box_chunks}, e[3] = {1, 1, 1};
  enc(m, CU_TENSOR_MAP_DATA_TYPE_BFLOAT16, 3, const_cast<void*>(ptr), d, st, b, e, CU_TENSOR_MAP_INTERLEAVE_NONE,
      CU_TENSOR_MAP_SWIZZLE_128B, CU_TENSOR_MAP_L2_PROMOTION_L2_128B, CU_TENSOR_MAP_FLOAT_OOB_FILL_NONE);
}

}

extern "C" void kernel_launch(void* const* d_in, const int* in_sizes, int n_in, void* d_out, int out_size) {
  (void)in_sizes; (void)n_in; (void)out_size;
  static EncodeFn enc = nullptr;
  static void *att = nullptr, *hbuf = nullptr;
  static int by_smid = 0;
  if (!enc) {
    void* fn = nullptr;
    cudaDriverEntryPointQueryResult q;
    cudaGetDriverEntryPoint("cuTensorMapEncodeTiled", &fn, cudaEnableDefault, &q);
    enc = (EncodeFn)fn;
    cudaGetSymbolAddress(&att, g_att);
    cudaGetSymbolAddress(&hbuf, g_h);
    cudaFuncSetAttribute(fused_layers_kernel, cudaFuncAttributeMaxDynamicSharedMemorySize, SMEM_BYTES);
    int sms = 0, clusters = 0, dev = 0;
    cudaGetDevice(&dev);
    cudaDeviceGetAttribute(&sms, cudaDevAttrMultiProcessorCount, dev);
    cudaLaunchConfig_t cfg = {};
    cfg.gridDim = dim3(132);
    cfg.blockDim = dim3(384);
    cfg.dynamicSmemBytes = SMEM_BYTES;
    cudaLaunchAttribute at[1];
    at[0].id = cudaLaunchAttributeClusterDimension;
    at[0].val.clusterDim.x = 2; at[0].val.clusterDim.y = 1; at[0].val.clusterDim.z = 1;
    cfg.attrs = at;
    cfg.numAttrs = 1;
    if (cudaOccupancyMaxActiveClusters(&clusters, fused_layers_kernel, &cfg) != cudaSuccess) (void)cudaGetLastError();
    by_smid = sms == 132 && clusters == 66;
  }
  Params p;
  make_2d(enc, &p.xin_ld, d_in[0], DM, SEQ, 128);
  make_2d(enc, &p.out_ld, d_out, DM, SEQ, 128);
  make_2d(enc, &p.out_st, d_out, DM, SEQ, 32);
  make_2d(enc, &p.att_ld, att, DM, SEQ, 128);
  make_2d(enc, &p.att_st, att, DM, SEQ, 32);
  make_2d(enc, &p.h_ld, hbuf, FF, SEQ, 128);
  make_2d(enc, &p.h_st, hbuf, FF, SEQ, 32);
  make_3d(enc, &p.wqkv, d_in[1], DM, DM, 3, 3 * DM * 2, DM * 2, 3);
  make_3d(enc, &p.wo, d_in[2], 64, DM, DM / 64, DM * 2, 128, 2);
  make_3d(enc, &p.w1a, d_in[4], 64, DM, FF / 64, FF * 2, 128, 3);
  make_3d(enc, &p.w1b, d_in[4], 64, DM, FF / 64, FF * 2, 128, 2);
  make_3d(enc, &p.w2, d_in[6], 64, FF, DM / 64, DM * 2, 128, 2);
  p.wqkv_p = (const __nv_bfloat16*)d_in[1];
  p.w1_p = (const __nv_bfloat16*)d_in[4];
  p.b1 = (const __nv_bfloat16*)d_in[5];
  p.b2 = (const __nv_bfloat16*)d_in[7];
  p.by_smid = by_smid;
  p.zero = 0;
  fused_layers_kernel<<<by_smid ? 132 : NCTA, 384, SMEM_BYTES>>>(p);
}
```

```cpp
#include <cuda_runtime.h>
#include <cuda_bf16.h>
#include <cuda.h>
#include <stdint.h>

namespace {

constexpr int SEQ = 2048, DM = 1024, FF = 3584;
constexpr int NCTA = 128;
constexpr int NBAR = 5;

constexpr uint32_t RING_UNITS = 20, UNIT = 8192;
constexpr uint32_t OFF_X   = RING_UNITS * UNIT;
constexpr uint32_t OFF_STG = OFF_X + 32768;
constexpr uint32_t OFF_CSQ = OFF_STG + 24576;
constexpr uint32_t OFF_CSF = OFF_CSQ + 1536;
constexpr uint32_t OFF_ROW = OFF_CSF + 3584;
constexpr uint32_t OFF_BAR = OFF_ROW + 1024;
constexpr uint32_t SMEM_BYTES = OFF_BAR + 192;
constexpr uint32_t BAR_FULL = OFF_BAR, BAR_EMPTY = OFF_BAR + 8 * NBAR;
constexpr uint32_t BAR_XRDY = OFF_BAR + 80;
constexpr uint32_t BAR_PUBRDY = OFF_BAR + 96, BAR_PUBFREE = OFF_BAR + 104;
constexpr uint32_t BAR_PUSHOK = OFF_BAR + 112;
constexpr uint32_t BAR_DUMMY = OFF_BAR + 128, OFF_TAG = OFF_BAR + 136, OFF_ZERO = OFF_BAR + 144;

constexpr uint64_t DESC_A = (1ull << 62) | ((uint64_t)(2048 >> 4) << 32) | (1ull << 16);
constexpr uint64_t DESC_B = (1ull << 62) | ((uint64_t)(1024 >> 4) << 32) | ((uint64_t)(8192 >> 4) << 16);

constexpr int BAR_ORDER = 1, BAR_GUARD = 3, BAR_WG = 5, BAR_GO = 7, BAR_DONE = 8;
#define GELU_DEP 3
#define WIN1 6
#define WIN2 4

struct Params {
  CUtensorMap xin, out, att, h, wqkv, wo, w1a, w1b, w2;
  const __nv_bfloat16 *wqkv_p, *w1_p, *b1, *b2;
  int by_smid;
  uint32_t zero;
};

__device__ __nv_bfloat16 g_att[SEQ * DM];
__device__ __nv_bfloat16 g_h[SEQ * FF];
__device__ uint4 g_stats[4 * 8 * SEQ];
__device__ uint4 g_halo[2 * 2 * 16 * 8 * 512];
__device__ uint4 g_csp[2 * 8 * 16 * 160];
__device__ uint32_t g_flags[16 * 32];
__device__ uint32_t g_epoch[NCTA + 4];
#define PROF_T(idx)
#define PROF_S(g)
#define PROF_E(i, k)

__device__ __forceinline__ void mbar_init(uint32_t bar, int cnt) {
  asm volatile("mbarrier.init.shared::cta.b64 [%0], %1;" ::"r"(bar), "r"(cnt));
}
__device__ __forceinline__ void mbar_expect_tx(uint32_t bar, uint32_t bytes) {
  asm volatile("mbarrier.arrive.expect_tx.shared::cta.b64 _, [%0], %1;" ::"r"(bar), "r"(bytes) : "memory");
}
__device__ __forceinline__ void mbar_arrive(uint32_t bar) {
  asm volatile("mbarrier.arrive.shared::cta.b64 _, [%0];" ::"r"(bar) : "memory");
}
__device__ __forceinline__ bool mbar_test(uint32_t bar, uint32_t parity) {
  uint32_t ok;
  asm volatile("{\n.reg .pred p;\nmbarrier.test_wait.parity.shared::cta.b64 p, [%1], %2;\nselp.u32 %0, 1, 0, p;\n}"
               : "=r"(ok) : "r"(bar), "r"(parity) : "memory");
  return ok;
}
__device__ __forceinline__ void mbar_wait(uint32_t bar, uint32_t parity) {
  asm volatile(
      "{\n.reg .pred p;\n.reg .u32 it;\nmov.u32 it, 0;\n"
      "WAIT_LOOP:\n"
      "mbarrier.try_wait.parity.shared::cta.b64 p, [%0], %1;\n"
      "@p bra WAIT_DONE;\n"
      "add.u32 it, it, 1;\n"
      "setp.lt.u32 p, it, 0x400000;\n"
      "@p bra WAIT_LOOP;\n"
      "trap;\n"
      "WAIT_DONE:\n}"
      ::"r"(bar), "r"(parity) : "memory");
}
__device__ __forceinline__ void bar_sync(int id, int n) { asm volatile("bar.sync %0, %1;" ::"r"(id), "r"(n) : "memory"); }
__device__ __forceinline__ void bar_arrive(int id, int n) { asm volatile("bar.arrive %0, %1;" ::"r"(id), "r"(n) : "memory"); }
__device__ __forceinline__ void tma_ld2(uint32_t dst, const CUtensorMap* m, uint32_t bar, int c0, int c1) {
  asm volatile("cp.async.bulk.tensor.2d.shared::cluster.global.mbarrier::complete_tx::bytes [%0], [%1, {%3, %4}], [%2];"
               ::"r"(dst), "l"(m), "r"(bar), "r"(c0), "r"(c1) : "memory");
}
__device__ __forceinline__ void tma_ld3(uint32_t dst, const CUtensorMap* m, uint32_t bar, int c0, int c1, int c2) {
  asm volatile("cp.async.bulk.tensor.3d.shared::cluster.global.mbarrier::complete_tx::bytes [%0], [%1, {%3, %4, %5}], [%2];"
               ::"r"(dst), "l"(m), "r"(bar), "r"(c0), "r"(c1), "r"(c2) : "memory");
}
__device__ __forceinline__ void tma_pf3(const CUtensorMap* m, int c0, int c1, int c2) {
  asm volatile("cp.async.bulk.prefetch.tensor.3d.L2.global [%0, {%1, %2, %3}];" ::"l"(m), "r"(c0), "r"(c1), "r"(c2) : "memory");
}
__device__ __forceinline__ void tma_st2(const CUtensorMap* m, uint32_t src, int c0, int c1) {
  asm volatile("cp.async.bulk.tensor.2d.global.shared::cta.bulk_group [%0, {%2, %3}], [%1];"
               ::"l"(m), "r"(src), "r"(c0), "r"(c1) : "memory");
}
__device__ __forceinline__ uint32_t peer_base(uint32_t sb) {
  uint32_t r;
  asm volatile("{\n.reg .u32 c;\nmov.u32 c, %%cluster_ctarank;\nxor.b32 c, c, 1;\nmapa.shared::cluster.u32 %0, %1, c;\n}" : "=r"(r) : "r"(sb));
  return r;
}
__device__ __forceinline__ void push_to_peer(uint32_t dst, uint32_t src, uint32_t bar) {
  asm volatile("cp.async.bulk.shared::cluster.shared::cta.mbarrier::complete_tx::bytes [%0], [%1], 16384, [%2];"
               ::"r"(dst), "r"(src), "r"(bar) : "memory");
}
__device__ __forceinline__ void mbar_arrive_remote(uint32_t bar) {
  asm volatile("mbarrier.arrive.release.cluster.shared::cluster.b64 _, [%0];" ::"r"(bar) : "memory");
}
__device__ __forceinline__ void bulk_commit() { asm volatile("cp.async.bulk.commit_group;" ::: "memory"); }
__device__ __forceinline__ void bulk_wait_read() { asm volatile("cp.async.bulk.wait_group.read 0;" ::: "memory"); }
__device__ __forceinline__ void bulk_wait_all() { asm volatile("cp.async.bulk.wait_group 0;" ::: "memory"); }
__device__ __forceinline__ void fence_async_smem() { asm volatile("fence.proxy.async.shared::cta;" ::: "memory"); }
__device__ __forceinline__ void fence_async_global() { asm volatile("fence.proxy.async.global;" ::: "memory"); }
__device__ __forceinline__ void st_relaxed(uint32_t* p, uint32_t v) {
  asm volatile("st.relaxed.gpu.global.u32 [%0], %1;" ::"l"(p), "r"(v) : "memory");
}
__device__ __forceinline__ void st_msg(uint4* p, uint32_t a, uint32_t b, uint32_t c, uint32_t tag) {
  asm volatile("{\n.reg .b128 v;\nmov.b128 v, {%1, %2, %3, %4};\nst.relaxed.gpu.b128 [%0], v;\n}"
               ::"l"(p), "r"(a), "r"(b), "r"(c), "r"(tag) : "memory");
}
__device__ __forceinline__ void ld_msg(const uint4* p, uint32_t& a, uint32_t& b, uint32_t& c, uint32_t& tag) {
  asm volatile("{\n.reg .b128 v;\nld.relaxed.gpu.b128 v, [%4];\nmov.b128 {%0, %1, %2, %3}, v;\n}"
               : "=r"(a), "=r"(b), "=r"(c), "=r"(tag) : "l"(p) : "memory");
}
__device__ __forceinline__ bool elect_one() {
  uint32_t ok;
  asm volatile("{\n.reg .pred p;\nelect.sync _|p, 0xffffffff;\nselp.u32 %0, 1, 0, p;\n}" : "=r"(ok));
  return ok;
}
__device__ __forceinline__ int uniform(int v) { return __shfl_sync(0xffffffffu, v, 0); }
__device__ __forceinline__ uint32_t pack_bf16(float lo, float hi) {
  uint32_t r;
  asm("cvt.rn.bf16x2.f32 %0, %1, %2;" : "=r"(r) : "f"(hi), "f"(lo));
  return r;
}
__device__ __forceinline__ float prmt_f(uint32_t a, uint32_t sel) {
  float r;
  asm("{\n.reg .b32 t;\nprmt.b32 t, %1, 0, %2;\nmov.b32 %0, t;\n}" : "=f"(r) : "r"(a), "r"(sel));
  return r;
}
__device__ __forceinline__ float bf_lo(uint32_t v) { return __uint_as_float(v << 16); }
__device__ __forceinline__ float bf_hi(uint32_t v) { return __uint_as_float(v & 0xffff0000u); }
__device__ __forceinline__ void stsm4(uint32_t addr, uint32_t r0, uint32_t r1, uint32_t r2, uint32_t r3) {
  asm volatile("stmatrix.sync.aligned.m8n8.x4.shared.b16 [%0], {%1, %2, %3, %4};"
               ::"r"(addr), "r"(r0), "r"(r1), "r"(r2), "r"(r3) : "memory");
}
__device__ __forceinline__ void ldsm4(uint32_t addr, uint32_t& r0, uint32_t& r1, uint32_t& r2, uint32_t& r3) {
  asm volatile("ldmatrix.sync.aligned.m8n8.x4.shared.b16 {%0, %1, %2, %3}, [%4];"
               : "=r"(r0), "=r"(r1), "=r"(r2), "=r"(r3) : "r"(addr) : "memory");
}
__device__ __forceinline__ uint32_t movtrans(uint32_t a) {
  uint32_t d;
  asm volatile("movmatrix.sync.aligned.m8n8.trans.b16 %0, %1;" : "=r"(d) : "r"(a));
  return d;
}
__device__ __forceinline__ void mma16816(float (&c)[4], uint32_t a0, uint32_t a1, uint32_t a2, uint32_t a3, uint32_t b0, uint32_t b1) {
  asm volatile("mma.sync.aligned.m16n8k16.row.col.f32.bf16.bf16.f32 {%0,%1,%2,%3}, {%4,%5,%6,%7}, {%8,%9}, {%0,%1,%2,%3};"
               : "+f"(c[0]), "+f"(c[1]), "+f"(c[2]), "+f"(c[3])
               : "r"(a0), "r"(a1), "r"(a2), "r"(a3), "r"(b0), "r"(b1));
}
__device__ __forceinline__ float2 lds_f2(uint32_t a) {
  float2 v;
  asm volatile("ld.shared.v2.f32 {%0, %1}, [%2];" : "=f"(v.x), "=f"(v.y) : "r"(a) : "memory");
  return v;
}
__device__ __forceinline__ float4 lds_f4(uint32_t a) {
  float4 v;
  asm volatile("ld.shared.v4.f32 {%0, %1, %2, %3}, [%4];" : "=f"(v.x), "=f"(v.y), "=f"(v.z), "=f"(v.w) : "r"(a) : "memory");
  return v;
}
__device__ __forceinline__ float lds_f(uint32_t a) {
  float v;
  asm volatile("ld.shared.f32 %0, [%1];" : "=f"(v) : "r"(a) : "memory");
  return v;
}
__device__ __forceinline__ void sts_f(uint32_t a, float v) { asm volatile("st.shared.f32 [%0], %1;" ::"r"(a), "f"(v) : "memory"); }
__device__ __forceinline__ uint32_t lds_u(uint32_t a) {
  uint32_t v;
  asm volatile("ld.shared.u32 %0, [%1];" : "=r"(v) : "r"(a) : "memory");
  return v;
}
__device__ __forceinline__ void sts_f2(uint32_t a, float x, float y) {
  asm volatile("st.shared.v2.f32 [%0], {%1, %2};" ::"r"(a), "f"(x), "f"(y) : "memory");
}
__device__ __forceinline__ void lds_u4(uint32_t a, uint32_t& x, uint32_t& y, uint32_t& z, uint32_t& w) {
  asm volatile("ld.shared.v4.u32 {%0, %1, %2, %3}, [%4];" : "=r"(x), "=r"(y), "=r"(z), "=r"(w) : "r"(a) : "memory");
}
__device__ __forceinline__ float ex2(float x) {
  float y;
  asm("ex2.approx.ftz.f32 %0, %1;" : "=f"(y) : "f"(x));
  return y;
}
__device__ __forceinline__ float rcp_hw(float x) {
  float y;
  asm("rcp.approx.ftz.f32 %0, %1;" : "=f"(y) : "f"(x));
  return y;
}
__device__ __forceinline__ float tanh_hw(float x) {
  float y;
  asm("tanh.approx.f32 %0, %1;" : "=f"(y) : "f"(x));
  return y;
}
__device__ __forceinline__ float quad_sum(float v) {
  v += __shfl_xor_sync(0xffffffffu, v, 1);
  return v + __shfl_xor_sync(0xffffffffu, v, 2);
}
__device__ __forceinline__ float quad_max(float v) {
  v = fmaxf(v, __shfl_xor_sync(0xffffffffu, v, 1));
  return fmaxf(v, __shfl_xor_sync(0xffffffffu, v, 2));
}

template <int N> __device__ __forceinline__ void wgmma_ss(float (&d)[96], uint64_t da, uint64_t db);
template <> __device__ __forceinline__ void wgmma_ss<128>(float (&d)[96], uint64_t da, uint64_t db) {
  asm volatile(
      "wgmma.mma_async.sync.aligned.m64n128k16.f32.bf16.bf16 {%0, %1, %2, %3, %4, %5, %6, %7, %8, %9, %10, %11, %12, %13, %14, %15, %16, %17, %18, %19, %20, %21, %22, %23, %24, %25, %26, %27, %28, %29, %30, %31, %32, %33, %34, %35, %36, %37, %38, %39, %40, %41, %42, %43, %44, %45, %46, %47, %48, %49, %50, %51, %52, %53, %54, %55, %56, %57, %58, %59, %60, %61, %62, %63}, %64, %65, 1, 1, 1, 0, 1;"
      : "+f"(d[0]), "+f"(d[1]), "+f"(d[2]), "+f"(d[3]), "+f"(d[4]), "+f"(d[5]), "+f"(d[6]), "+f"(d[7]), "+f"(d[8]), "+f"(d[9]), "+f"(d[10]), "+f"(d[11]), "+f"(d[12]), "+f"(d[13]), "+f"(d[14]), "+f"(d[15]), "+f"(d[16]), "+f"(d[17]), "+f"(d[18]), "+f"(d[19]), "+f"(d[20]), "+f"(d[21]), "+f"(d[22]), "+f"(d[23]), "+f"(d[24]), "+f"(d[25]), "+f"(d[26]), "+f"(d[27]), "+f"(d[28]), "+f"(d[29]), "+f"(d[30]), "+f"(d[31]), "+f"(d[32]), "+f"(d[33]), "+f"(d[34]), "+f"(d[35]), "+f"(d[36]), "+f"(d[37]), "+f"(d[38]), "+f"(d[39]), "+f"(d[40]), "+f"(d[41]), "+f"(d[42]), "+f"(d[43]), "+f"(d[44]), "+f"(d[45]), "+f"(d[46]), "+f"(d[47]), "+f"(d[48]), "+f"(d[49]), "+f"(d[50]), "+f"(d[51]), "+f"(d[52]), "+f"(d[53]), "+f"(d[54]), "+f"(d[55]), "+f"(d[56]), "+f"(d[57]), "+f"(d[58]), "+f"(d[59]), "+f"(d[60]), "+f"(d[61]), "+f"(d[62]), "+f"(d[63])
      : "l"(da), "l"(db));
}

template <> __device__ __forceinline__ void wgmma_ss<192>(float (&d)[96], uint64_t da, uint64_t db) {
  asm volatile(
      "wgmma.mma_async.sync.aligned.m64n192k16.f32.bf16.bf16 {%0, %1, %2, %3, %4, %5, %6, %7, %8, %9, %10, %11, %12, %13, %14, %15, %16, %17, %18, %19, %20, %21, %22, %23, %24, %25, %26, %27, %28, %29, %30, %31, %32, %33, %34, %35, %36, %37, %38, %39, %40, %41, %42, %43, %44, %45, %46, %47, %48, %49, %50, %51, %52, %53, %54, %55, %56, %57, %58, %59, %60, %61, %62, %63, %64, %65, %66, %67, %68, %69, %70, %71, %72, %73, %74, %75, %76, %77, %78, %79, %80, %81, %82, %83, %84, %85, %86, %87, %88, %89, %90, %91, %92, %93, %94, %95}, %96, %97, 1, 1, 1, 0, 1;"
      : "+f"(d[0]), "+f"(d[1]), "+f"(d[2]), "+f"(d[3]), "+f"(d[4]), "+f"(d[5]), "+f"(d[6]), "+f"(d[7]), "+f"(d[8]), "+f"(d[9]), "+f"(d[10]), "+f"(d[11]), "+f"(d[12]), "+f"(d[13]), "+f"(d[14]), "+f"(d[15]), "+f"(d[16]), "+f"(d[17]), "+f"(d[18]), "+f"(d[19]), "+f"(d[20]), "+f"(d[21]), "+f"(d[22]), "+f"(d[23]), "+f"(d[24]), "+f"(d[25]), "+f"(d[26]), "+f"(d[27]), "+f"(d[28]), "+f"(d[29]), "+f"(d[30]), "+f"(d[31]), "+f"(d[32]), "+f"(d[33]), "+f"(d[34]), "+f"(d[35]), "+f"(d[36]), "+f"(d[37]), "+f"(d[38]), "+f"(d[39]), "+f"(d[40]), "+f"(d[41]), "+f"(d[42]), "+f"(d[43]), "+f"(d[44]), "+f"(d[45]), "+f"(d[46]), "+f"(d[47]), "+f"(d[48]), "+f"(d[49]), "+f"(d[50]), "+f"(d[51]), "+f"(d[52]), "+f"(d[53]), "+f"(d[54]), "+f"(d[55]), "+f"(d[56]), "+f"(d[57]), "+f"(d[58]), "+f"(d[59]), "+f"(d[60]), "+f"(d[61]), "+f"(d[62]), "+f"(d[63]), "+f"(d[64]), "+f"(d[65]), "+f"(d[66]), "+f"(d[67]), "+f"(d[68]), "+f"(d[69]), "+f"(d[70]), "+f"(d[71]), "+f"(d[72]), "+f"(d[73]), "+f"(d[74]), "+f"(d[75]), "+f"(d[76]), "+f"(d[77]), "+f"(d[78]), "+f"(d[79]), "+f"(d[80]), "+f"(d[81]), "+f"(d[82]), "+f"(d[83]), "+f"(d[84]), "+f"(d[85]), "+f"(d[86]), "+f"(d[87]), "+f"(d[88]), "+f"(d[89]), "+f"(d[90]), "+f"(d[91]), "+f"(d[92]), "+f"(d[93]), "+f"(d[94]), "+f"(d[95])
      : "l"(da), "l"(db));
}

template <int R>
__device__ __forceinline__ void pin_regs(float (&a)[2][96]) {
#pragma unroll
  for (int m = 0; m < 2; m++)
#pragma unroll
    for (int i = 0; i < R; i++) asm volatile("" : "+f"(a[m][i])::"memory");
}

struct Ctx {
  uint32_t sb;
  int m, n, wg, w, lane;
};
__device__ __forceinline__ Ctx make_ctx(uint32_t sb, int id) {
  int lane;
  asm volatile("mov.u32 %0, %%laneid;" : "=r"(lane));
  asm volatile("" : "+r"(id), "+r"(sb));
  return Ctx{sb, (id >> 3) & 15, id & 7, id >> 9, (id >> 7) & 3, lane};
}
#define UNPACK_CTX(c) const uint32_t sb = c.sb; const int m = c.m, n = c.n, wg = c.wg, w = c.w, lane = c.lane

__device__ __forceinline__ uint32_t poll_line(const uint32_t* word, uint32_t target, uint32_t need) {
  uint32_t v;
  asm volatile(
      "{\n.reg .pred p;\n.reg .u32 it, m;\n.reg .s32 d;\nmov.u32 it, 0;\n"
      "POLL_LOOP:\n"
      "ld.relaxed.gpu.global.u32 %0, [%1];\n"
      "sub.s32 d, %0, %2;\n"
      "setp.ge.s32 p, d, 0;\n"
      "vote.sync.ballot.b32 m, p, 0xffffffff;\n"
      "and.b32 m, m, %3;\n"
      "setp.eq.u32 p, m, %3;\n"
      "@p bra.uni POLL_DONE;\n"
      "add.u32 it, it, 1;\n"
      "setp.lt.u32 p, it, 0x400000;\n"
      "@p bra.uni POLL_LOOP;\n"
      "trap;\n"
      "POLL_DONE:\n}"
      : "=&r"(v) : "l"(word), "r"(target), "r"(need) : "memory");
  return v;
}
__device__ __forceinline__ uint32_t ld_relaxed(const uint32_t* p) {
  uint32_t v;
  asm volatile("ld.relaxed.gpu.global.u32 %0, [%1];" : "=r"(v) : "l"(p) : "memory");
  return v;
}
__device__ __forceinline__ float chain(float x, uint32_t on, uint32_t zero) {
  return __uint_as_float(__float_as_uint(x) | (on & zero));
}
constexpr int MSG_SPINS = 1 << 20;

constexpr int STAGES_PER_LAYER = 152;
__device__ __forceinline__ int nib(uint64_t v, int i) { return (int)(v >> (4 * i)) & 15; }
__device__ __forceinline__ bool tile_wide(int t) { return (0xB >> t) & 1; }
__device__ __forceinline__ int tile_pos0(int t) { return t < 3 ? 0 : t == 3 ? 5 : 4 * t - 8; }
constexpr uint32_t ORDER_PLAIN = 0x76543210u, ORDER_X0 = 0x54329180u, ORDER_X1 = 0xFEDCBA76u;

__device__ __forceinline__ void weight_coords(const Params& p, int t, int n, const CUtensorMap*& map, int& c0, int& c2) {
  map = &p.wqkv + nib(0x4332100ull, t);
  c0 = t < 2 ? 128 * n + 64 * t : 0;
  c2 = t < 2 ? 0 : (t == 2 || t == 6) ? 2 * n : 7 * n + nib(0x530000ull, t);
}

template <bool IS_A>
__device__ __forceinline__ void producer(const Params& p, uint32_t sb, int m, int n, int lane) {
  int inflight = 0, rph = 0, pushes = 0, min_seen = 0;
  uint32_t b8 = 0, rb8 = 0, pos = 0, tag32 = 0, seen = 0;
  const uint32_t* word = g_flags + m * 32 + (lane & 7);
#pragma unroll 1
  for (int rr = 0; rr < 38; rr++) {
    const int layer = rr >= 19, r = rr - 19 * layer;
    const int t = r < 12 ? r >> 1 : 6, sub = r < 12 ? r & 1 : r - 12;
    const bool wide = tile_wide(t), xtype = t != 2 && t != 6;
    const uint32_t bbytes = wide ? 3 * UNIT : 2 * UNIT;
    const int mul = t == 6 ? 7 : 2, add = xtype ? 0 : sub;
    uint32_t order = !xtype ? ORDER_PLAIN : sub ? ORDER_X1 : ORDER_X0;
    int short_left = wide ? 99 : (r == 4 || r == 8) ? 4 : 0;
    if (r == 6 || r == 8) pos = tile_pos0(t) * UNIT;
    const CUtensorMap* map;
    int c0 = 0, c2 = 0, n_own = 0, n_local = 0, ev = 0;
    if (IS_A) {
      map = &p.xin + (t == 2 ? 2 : t == 6 ? 3 : rr >= 4);
      ev = 9 * layer + (t < 2 ? -1 : t == 2 ? 1 + sub : t < 6 ? 3 : nib(0x7766555ull, sub));
      n_local = n_own = xtype ? 2 - 2 * sub : r == 5;
      if (r == 5 || r == 6 || rr == 19) n_local = 2 * n_own;
      if (rr == 3) seen = tag32 = (__ldcg(g_epoch + m * 8 + n) + 1) << 5;
      if (rr >= 4) {
        min_seen = __reduce_min_sync(0xffffffffu, (int)(seen - tag32));
        asm volatile("fence.acquire.gpu;" ::: "memory");
        fence_async_global();
        seen = ld_relaxed(word);
      }
    } else {
      if (rr > 0 && rr < 31 && sub == 0) {
        weight_coords(p, t == 6 ? 0 : t + 1, n, map, c0, c2);
#pragma unroll 1
        for (int kb = m; kb < (t == 5 ? 56 : 16); kb += 16)
          if (elect_one()) tma_pf3(map, c0, 64 * kb, c2);
      }
      weight_coords(p, t, n, map, c0, c2);
    }
#pragma unroll 1
    for (int k = 0; k < 8; k++) {
      const int q = order & 7, hi = (order >> 3) & 1;
      order >>= 4;
      const int src = (((n & 6) + q) & 7) ^ (q < 2 ? n & 1 : 0);
      const int kc = 64 * (mul * src + add + hi);
      const int lag = short_left > 0 ? 3 : 4;
      short_left--;
      if (IS_A && k >= n_local && min_seen < ev + hi) {
        const uint32_t v = poll_line(word, tag32 + ev + hi, 1u << src);
        min_seen = __reduce_min_sync(0xffffffffu, (int)(v - tag32));
        asm volatile("fence.acquire.gpu;" ::: "memory");
        fence_async_global();
      }
#pragma unroll 1
      for (; inflight > lag; inflight--) {
        mbar_wait(sb + BAR_EMPTY + rb8, rph);
        rb8 += 8;
        if (rb8 == 8 * NBAR) { rb8 = 0; rph ^= 1; }
      }
      const uint32_t fb = sb + BAR_FULL + b8;
      if (!IS_A) {
        if (elect_one()) {
          mbar_expect_tx(fb, bbytes);
          tma_ld3(sb + pos, map, fb, c0, kc, c2);
        }
      } else if (k >= n_local) {
        if (elect_one()) {
          mbar_expect_tx(fb, 16384);
          tma_ld2(sb + pos + bbytes, map, fb, kc, 128 * m);
        }
      } else if (k < n_own) {
        if (t == 2) mbar_wait(sb + BAR_PUBRDY, (layer + 1) & 1);
        else if (k == 1 && (r == 0 || r == 6)) mbar_wait(sb + BAR_XRDY + 8, r == 6);
        if (elect_one()) mbar_arrive(fb);
      } else {
        const uint32_t pb = peer_base(sb), ok = BAR_PUSHOK + 8 * (pushes & 1);
        if (elect_one()) {
          mbar_expect_tx(fb, 16384);
          mbar_arrive_remote(pb + ok);
        }
        mbar_wait(sb + ok, (pushes >> 1) & 1);
        if (elect_one()) push_to_peer(pb + pos + bbytes, sb + (t == 2 ? OFF_STG : OFF_X + hi * 16384), pb + BAR_FULL + b8);
        pushes++;
      }
      inflight++;
      b8 += 8;
      if (b8 == 8 * NBAR) b8 = 0;
      pos += bbytes + 2 * UNIT;
      if (pos >= RING_UNITS * UNIT) pos -= RING_UNITS * UNIT;
    }
  }
}

__device__ __forceinline__ void publisher(const Params& p, uint32_t sb, int m, int n) {
  const uint32_t tag = __ldcg(g_epoch + m * 8 + n) + 1;
  uint32_t* word = g_flags + m * 32 + n;
  uint32_t value = 32 * tag, sph = 0;
  st_relaxed(word, value);
#pragma unroll 1
  for (int c = 0; c < 26; c++) {
    const int e = c >= 13 ? c - 13 : c;
    const bool is_x = (0x180C >> e) & 1, is_h = e >= 4 && e <= 10;
    const int half = (e ^ (e >> 3)) & 1;
    if (is_x) {
      mbar_wait(sb + BAR_XRDY + 8 * half, e < 4);
    } else {
      mbar_wait(sb + BAR_PUBRDY, sph);
      sph ^= 1;
    }
    tma_st2(&p.xin + (is_x ? 1 : is_h ? 3 : 2), sb + (is_x ? OFF_X + half * 16384 : OFF_STG),
            is_h ? 448 * n + 64 * (e - 4) : 128 * n + 64 * half, 128 * m);
    bulk_commit();
    if (c >= 24) continue;
    if (!is_x) {
      bulk_wait_read();
      mbar_arrive(sb + BAR_PUBFREE);
    }
    if ((0x1D4F >> e) & 1) {
      bulk_wait_all();
      asm volatile("fence.release.gpu;" ::: "memory");
      st_relaxed(word, ++value);
    }
  }
  g_epoch[m * 8 + n] = tag;
  bulk_wait_read();
}

template <int N>
__device__ __forceinline__ void mainloop(float (&acc)[2][96], uint32_t sb, int i, int mn) {
  constexpr uint32_t Z16 = (2 + N / 64) * (UNIT >> 4), RING16 = RING_UNITS * (UNIT >> 4);
  constexpr uint32_t A_OFF = Z16 - 1024 + (uint32_t)DESC_A - (uint32_t)DESC_B;
  const int wg = i & 1;
  const int layer = i >= 7, t = i - 7 * layer;
  const bool own = t != 2 && t != 6;
  const int g0 = layer * STAGES_PER_LAYER + 16 * t;
  const uint32_t s16 = (sb & 0x3FFFF) >> 4;
  const uint32_t blast = uniform((uint32_t)DESC_B + s16 + RING16 - Z16), flast = uniform(sb + BAR_FULL + 8 * (NBAR - 1));
  const int nkb = t == 6 ? 56 : 16;
  int run = uniform(t == 1 ? WIN1 + 1 : t == 2 ? WIN2 + 1 : nkb);
  int rest = t == 1 ? 64 | (15 - WIN1) : t == 2 ? 64 | (7 - WIN2) | (8 << 7) : 0;
  uint32_t fb = sb + BAR_FULL + 8 * (g0 % NBAR), ph = (g0 / NBAR) & 1;
  uint32_t prev = sb + BAR_DUMMY - 8 * NBAR;
  uint32_t blo = (uint32_t)DESC_B + s16 + tile_pos0(t) * (UNIT >> 4);
  uint32_t alo = own ? (uint32_t)DESC_A + s16 + (OFF_X >> 4) : blo + A_OFF;
  uint32_t aoff = own ? alo + 1024 - (blo + Z16) : A_OFF;
  pin_regs<N / 2>(acc);
  if (i > 0) bar_sync(BAR_ORDER + wg, 256);
  if (N == 192 && t != 1) mbar_wait(sb + BAR_XRDY, t == 3);
  mbar_wait(fb, ph);
  PROF_T(4 + i * 4);
#pragma unroll 1
  while (true) {
    const uint64_t da = (DESC_A & ~0xffffffffull) | alo, db = (DESC_B & ~0xffffffffull) | blo;
    asm volatile("wgmma.fence.sync.aligned;" ::: "memory");
    wgmma_ss<N>(acc[0], da, db);
    wgmma_ss<N>(acc[1], da + 64, db);
    wgmma_ss<N>(acc[0], da + 2, db + 128);
    wgmma_ss<N>(acc[1], da + 66, db + 128);
    asm volatile("wgmma.commit_group.sync.aligned;" ::: "memory");
    asm volatile("wgmma.wait_group.sync.aligned 1;" ::: "memory");
    PROF_S(g0 + jj++);
    if (elect_one()) mbar_arrive(prev + 8 * NBAR);
    prev = fb;
    if (fb == flast) { fb -= 8 * NBAR; ph++; }
    fb += 8;
    if (blo == blast) blo -= RING16;
    blo += Z16;
    alo = blo + aoff;
    aoff = A_OFF;
    run--;
    const bool ready = mbar_test(fb, ph) && run != 0;
    asm volatile("wgmma.fence.sync.aligned;" ::: "memory");
    wgmma_ss<N>(acc[0], da + 4, db + 256);
    wgmma_ss<N>(acc[1], da + 68, db + 256);
    wgmma_ss<N>(acc[0], da + 6, db + 384);
    wgmma_ss<N>(acc[1], da + 70, db + 384);
    asm volatile("wgmma.commit_group.sync.aligned;" ::: "memory");
    if (!ready) {
      if (run == 0) {
        if (rest == 0) break;
        if (rest & 64) {
          bar_arrive(BAR_GO, 256);
          bar_sync(BAR_DONE, 256);
        } else {
          alo = (uint32_t)DESC_A + s16 + (OFF_STG >> 4);
        }
        run = rest & 63;
        rest >>= 7;
      }
      mbar_wait(fb, ph);
    }
  }
  if (i < 13) bar_arrive(BAR_ORDER + (wg ^ 1), 256);
  asm volatile("wgmma.wait_group.sync.aligned 0;" ::: "memory");
  pin_regs<N / 2>(acc);
  if (elect_one()) mbar_arrive(prev + 8 * NBAR);
  PROF_T(5 + i * 4);
  PROF_E(i, 0);
}

#define ACC(q, j, e) acc[(q) & 1][4 * (j) + 2 * ((q) >> 1) + (e)]

__device__ __forceinline__ void write_partial_stats(const Ctx& c, int ln, uint32_t tag) {
  const uint32_t xrow = c.sb + OFF_X + c.w * 4096 + c.lane * 128;
  float s = 0.f, q = 0.f;
#pragma unroll 2
  for (int j = 0; j < 16; j++) {
    uint32_t u[4];
    lds_u4(xrow + (j >> 3) * 16384 + (((j & 7) ^ (c.lane & 7)) << 4), u[0], u[1], u[2], u[3]);
#pragma unroll
    for (int e = 0; e < 4; e++) {
      const float a = bf_lo(u[e]), d = bf_hi(u[e]);
      s += a; q = fmaf(a, a, q);
      s += d; q = fmaf(d, d, q);
    }
  }
  st_msg(g_stats + (ln * 8 + c.n) * SEQ + 128 * c.m + 32 * c.w + c.lane, __float_as_uint(s),
         __float_as_uint(fmaxf(q - s * s * (1.f / 128.f), 0.f)), 0u, tag);
}

__device__ __forceinline__ void finish_row_stats(const Ctx& c, int ln, uint32_t tag) {
  const uint4* src = g_stats + ln * 8 * SEQ + 128 * c.m + 32 * c.w + c.lane;
  uint32_t ps[8], pm[8];
#pragma unroll 1
  for (int it = 0; it < MSG_SPINS; it++) {
    uint32_t bad = 0, u, tg;
#pragma unroll
    for (int k = 0; k < 8; k++) { ld_msg(src + k * SEQ, ps[k], pm[k], u, tg); bad |= tg ^ tag; }
    if (__all_sync(0xffffffffu, bad == 0)) break;
  }
  float s = 0.f, m2 = 0.f;
#pragma unroll
  for (int k = 0; k < 8; k++) s += __uint_as_float(ps[k]);
  const float mean = s * (1.f / DM);
#pragma unroll
  for (int k = 0; k < 8; k++) {
    const float d = __uint_as_float(ps[k]) * (1.f / 128.f) - mean;
    m2 += fmaf(128.f * d, d, __uint_as_float(pm[k]));
  }
  sts_f2(c.sb + OFF_ROW + (32 * c.w + c.lane) * 8, rsqrtf(m2 * (1.f / DM) + 1e-5f), mean);
  __syncwarp();
}

__device__ __forceinline__ void attn_scores(const uint32_t* qa, const uint32_t* qb, const uint32_t* k0, const uint32_t* k1,
                                            const uint32_t* k2, const uint32_t* k3, float (&l)[4], const float4& zero,
                                            bool par, bool early) {
  float s[4][4];
#pragma unroll
  for (int kb = 0; kb < 4; kb++) {
    const uint32_t* kk = kb == 0 ? k0 : kb == 1 ? k1 : kb == 2 ? k2 : k3;
    asm volatile("mma.sync.aligned.m16n8k16.row.col.f32.bf16.bf16.f32 {%0,%1,%2,%3}, {%4,%5,%6,%7}, {%8,%9}, {%10,%11,%12,%13};"
                 : "=f"(s[kb][0]), "=f"(s[kb][1]), "=f"(s[kb][2]), "=f"(s[kb][3])
                 : "r"(qa[0]), "r"(qb[0]), "r"(qa[1]), "r"(qb[1]), "r"(kk[0]), "r"(kk[1]), "f"(zero.x), "f"(zero.y),
                   "f"(zero.z), "f"(zero.w));
  }
#pragma unroll
  for (int kb = 0; kb < 4; kb++) {
    const uint32_t* kk = kb == 0 ? k0 : kb == 1 ? k1 : kb == 2 ? k2 : k3;
    mma16816(s[kb], qa[2], qb[2], qa[3], qb[3], kk[2], kk[3]);
  }
  l[0] = par ? s[1][1] : s[1][0];
  l[1] = early ? (par ? s[0][1] : s[0][0]) : (par ? s[2][1] : s[2][0]);
  l[2] = par ? s[2][3] : s[2][2];
  l[3] = early ? (par ? s[1][3] : s[1][2]) : (par ? s[3][3] : s[3][2]);
}

__device__ __forceinline__ void attn_mix(const float (&l)[4], const float (&sc)[4], const float (&off)[4], const float (&rk)[4],
                                         const uint32_t* v0, const uint32_t* v1, const uint32_t* v2, const uint32_t* v3,
                                         float (&o)[4][4], bool par, bool early) {
  float x[4];
#pragma unroll
  for (int e = 0; e < 4; e++) x[e] = fmaf(l[e], sc[e], off[e]);
  const float ml = quad_max(fmaxf(x[0], x[1])), mh = quad_max(fmaxf(x[2], x[3]));
  x[0] = ex2(x[0] - ml); x[1] = ex2(x[1] - ml);
  x[2] = ex2(x[2] - mh); x[3] = ex2(x[3] - mh);
  const float il = rcp_hw(quad_sum(x[0] + x[1])), ih = rcp_hw(quad_sum(x[2] + x[3]));
  const uint32_t pl = pack_bf16(x[0] * rk[0] * il, x[1] * rk[1] * il), ph = pack_bf16(x[2] * rk[2] * ih, x[3] * rk[3] * ih);
  const uint32_t sel_a = par ? 0x1044u : 0x4410u, sel_b = par ? 0x3244u : 0x4432u;
  const uint32_t sel_e = early ? sel_b : 0x4444u, sel_l = early ? 0x4444u : sel_b;
  const uint32_t pla = __byte_perm(pl, 0, sel_a), pha = __byte_perm(ph, 0, sel_a);
  const uint32_t e_l = __byte_perm(pl, 0, sel_e), e_h = __byte_perm(ph, 0, sel_e);
  const uint32_t l_l = __byte_perm(pl, 0, sel_l), l_h = __byte_perm(ph, 0, sel_l);
#pragma unroll
  for (int jn = 0; jn < 4; jn++) {
    o[jn][0] = o[jn][1] = o[jn][2] = o[jn][3] = 0.f;
    mma16816(o[jn], e_l, 0u, pla, e_h, v0[jn], v1[jn]);
  }
#pragma unroll
  for (int jn = 0; jn < 4; jn++) mma16816(o[jn], l_l, pha, 0u, l_h, v2[jn], v3[jn]);
}

__device__ __forceinline__ void colsum_partial(const Params& p, const Ctx& cx, bool qkv, uint32_t tag) {
  UNPACK_CTX(cx);
  const int groups = qkv ? 48 : 56, cg = (w & 1) * 32 + lane, tid = w * 32 + lane;
  const int ld = qkv ? 3 * DM / 8 : FF / 8;
  float a[8] = {0.f, 0.f, 0.f, 0.f, 0.f, 0.f, 0.f, 0.f};
  if (cg < groups) {
    const uint4* W = reinterpret_cast<const uint4*>(qkv ? p.wqkv_p : p.w1_p) + (64 * m + 32 * (w >> 1)) * ld +
                     (qkv ? (cg >> 4) * (DM / 8) + 16 * n + (cg & 15) : 56 * n + cg);
    asm volatile("prefetch.global.L2 [%0];" ::"l"(W + (16 + (lane & 7)) * ld));
    asm volatile("prefetch.global.L2 [%0];" ::"l"(W + (24 + (lane & 7)) * ld));
#pragma unroll 1
    for (int it = 0; it < 2; it++) {
      uint4 v[16];
#pragma unroll
      for (int r = 0; r < 16; r++) v[r] = __ldcg(W + (16 * it + r) * ld);
#pragma unroll
      for (int r = 0; r < 16; r++) {
        a[0] += bf_lo(v[r].x); a[1] += bf_hi(v[r].x); a[2] += bf_lo(v[r].y); a[3] += bf_hi(v[r].y);
        a[4] += bf_lo(v[r].z); a[5] += bf_hi(v[r].z); a[6] += bf_lo(v[r].w); a[7] += bf_hi(v[r].w);
      }
    }
  }
  const uint32_t part = sb + OFF_STG + 16384 + (w >> 1) * 2048 + cg * 32;
#pragma unroll
  for (int e = 0; e < 4; e++) sts_f2(part + 8 * e, a[2 * e], a[2 * e + 1]);
  bar_sync(BAR_WG + wg, 128);
  uint4* dst = g_csp + (((qkv ? 0 : 8) + n) * 16 + m) * 160;
#pragma unroll 1
  for (int c = tid; c < (qkv ? 128 : 160); c += 128) {
    const uint32_t q = sb + OFF_STG + 16384 + c * 12;
    st_msg(dst + c, __float_as_uint(lds_f(q) + lds_f(q + 2048)), __float_as_uint(lds_f(q + 4) + lds_f(q + 2052)),
           __float_as_uint(lds_f(q + 8) + lds_f(q + 2056)), tag);
  }
}

__device__ __forceinline__ void colsum_gather(const Params& p, const Ctx& cx, bool qkv, uint32_t tag) {
  const int n = cx.n, tid = cx.w * 32 + cx.lane;
  if (!qkv && tid < 112) {
    const uint2 bb = __ldg(reinterpret_cast<const uint2*>(p.b1 + 448 * n) + tid);
    sts_f2(cx.sb + OFF_CSF + tid * 32 + 8, 0.5f * bf_lo(bb.x), 0.5f * bf_hi(bb.x));
    sts_f2(cx.sb + OFF_CSF + tid * 32 + 24, 0.5f * bf_lo(bb.y), 0.5f * bf_hi(bb.y));
  }
#pragma unroll 1
  for (int c0 = cx.w * 32; c0 < (qkv ? 128 : 160); c0 += 128) {
    const int c = c0 + cx.lane;
    const uint4* src = g_csp + ((qkv ? 0 : 8) + n) * 16 * 160 + c;
    float s[3];
#pragma unroll 1
    for (int it = 0; it < MSG_SPINS; it++) {
      uint32_t bad = 0;
      s[0] = s[1] = s[2] = 0.f;
#pragma unroll
      for (int mm = 0; mm < 16; mm++) {
        uint32_t x, y, z, tg;
        ld_msg(src + mm * 160, x, y, z, tg);
        bad |= tg ^ tag;
        s[0] += __uint_as_float(x); s[1] += __uint_as_float(y); s[2] += __uint_as_float(z);
      }
      if (__all_sync(0xffffffffu, bad == 0)) break;
    }
#pragma unroll 1
    for (int e = 0; e < 3; e++) {
      const int col = 3 * c + e;
      const float v = e == 0 ? s[0] : e == 1 ? s[1] : s[2];
      if (col < 448)
        sts_f(cx.sb + (qkv ? OFF_CSQ + ((((col >> 6) & 1) * 3 + (col >> 7)) * 64 + (col & 63)) * 4
                           : OFF_CSF + (col >> 1) * 16 + (col & 1) * 4), v);
    }
  }
}

__device__ __forceinline__ void gelu_epilogue(const Params& p, float (&acc)[2][96], const Ctx& cx, int layer, int t) {
  UNPACK_CTX(cx);
  (void)wg; (void)m; (void)n;
  uint32_t fph = layer + (t == 3);
  float rs[4], rm[4];
#pragma unroll
  for (int q = 0; q < 4; q++) {
    const float2 v = lds_f2(sb + OFF_ROW + (32 * w + 8 * q + (lane >> 2)) * 8);
    rs[q] = 0.5f * v.x;
    rm[q] = -rs[q] * v.y;
  }
  const int col0 = t == 3 ? 0 : t == 4 ? 192 : 320, steps = t == 3 ? 6 : 4;
  const uint32_t stg = sb + OFF_STG + w * 4096;
  uint32_t ctab = sb + OFF_CSF + (col0 / 2 + (lane & 3)) * 16;
  float v[2][16];
#pragma unroll
  for (int r = 0; r < 16; r++) { v[0][r] = acc[0][r]; v[1][r] = acc[1][r]; }
#pragma unroll 1
  for (int it = 0; it < steps; it++) {
    uint32_t hp[4][4];
#pragma unroll
    for (int j = 0; j < 4; j++) {
      const float4 cb = lds_f4(ctab + j * 64);
#pragma unroll
      for (int q = 0; q < 4; q++) {
        float y[2];
        const int k = 4 * j + q - GELU_DEP;
        const float rmq = k >= 0 ? chain(rm[q], hp[k >> 2][k & 3], p.zero) : rm[q];
#pragma unroll
        for (int e = 0; e < 2; e++) {
          const float z = fmaf(v[q & 1][4 * j + 2 * (q >> 1) + e], rs[q], fmaf(rmq, e ? cb.y : cb.x, e ? cb.w : cb.z));
          const float u = z * fmaf(z * z, 8.f * 0.7978845608028654f * 0.044715f, 2.f * 0.7978845608028654f);
          y[e] = fmaf(z, tanh_hw(u), z);
        }
        hp[j][q] = pack_bf16(y[0], y[1]);
      }
    }
    ctab += 256;
    if (!(it & 1)) mbar_wait(sb + BAR_PUBFREE, fph++ & 1);
#pragma unroll
    for (int j = 0; j < 4; j++)
      stsm4(stg + lane * 128 + (((4 * (it & 1) + j) ^ (lane & 7)) << 4), hp[j][0], hp[j][1], hp[j][2], hp[j][3]);
    if (it & 1) {
      fence_async_smem();
      __syncwarp();
      if (elect_one()) mbar_arrive(sb + BAR_PUBRDY);
      if (it == steps - 1) break;
    }
    const uint32_t zr = hp[3][3] & p.zero;
#define REFILL(k) _Pragma("unroll") for (int r = 0; r < 32; r++) \
      asm volatile("{\n.reg .b32 t;\nmov.b32 t, %1;\nor.b32 t, t, %2;\nmov.b32 %0, t;\n}" \
                   : "=f"(v[r >> 4][r & 15]) : "f"(acc[r >> 4][16 * k + (r & 15)]), "r"(zr)); break;
    switch (it) {
      case 0: REFILL(1)
      case 1: REFILL(2)
      case 2: REFILL(3)
      case 3: REFILL(4)
      default: REFILL(5)
    }
#undef REFILL
  }
}

__device__ __forceinline__ void attn_epilogue(const Params& p, float (&acc)[2][96], const Ctx& cx, int layer, int t, uint32_t tag) {
  UNPACK_CTX(cx);
  const bool par = (lane >> 2) & 1, early = (lane & 3) > (lane >> 3);
  uint32_t Q[4][8], K[4][8], V[4][8];
  float kr[6], qr[4];
#pragma unroll
  for (int q = 0; q < 4; q++) {
    kr[2 + q] = lds_f(sb + OFF_ROW + (32 * w + 8 * q + 2 * (lane & 3) + par) * 8);
    qr[q] = lds_f(sb + OFF_ROW + (32 * w + 8 * q + (lane >> 2)) * 8) * (0.17677669529663687f * 1.4426950408889634f);
  }
  mbar_wait(sb + BAR_PUBFREE, (layer + t + 1) & 1);
  const int slot = ((layer * 2 + t) * 16 + m) * 8 + n;
  uint4* const exc = reinterpret_cast<uint4*>(__cvta_shared_to_generic(sb + OFF_STG));
#pragma unroll
  for (int qq = 0; qq < 4; qq++) {
    const int q = qq ^ 2;
#pragma unroll
    for (int j = 0; j < 8; j++) {
      K[q][j] = pack_bf16(ACC(q, 8 + j, 0), ACC(q, 8 + j, 1));
      V[q][j] = movtrans(pack_bf16(ACC(q, 16 + j, 0), ACC(q, 16 + j, 1)));
    }
    if (qq == 1) {
      uint4* e = (w < 3 ? exc + w * 512 : g_halo + slot * 512) + lane;
#pragma unroll
      for (int j = 0; j < 8; j++) {
        st_msg(e + j * 32, K[2 + (j >> 2)][2 * (j & 3)], K[2 + (j >> 2)][2 * (j & 3) + 1], __float_as_uint(kr[4]), tag);
        st_msg(e + (8 + j) * 32, V[2][j], V[3][j], __float_as_uint(kr[5]), tag);
      }
    }
  }
#pragma unroll
  for (int q = 0; q < 4; q++)
#pragma unroll
    for (int j = 0; j < 8; j++) Q[q][j] = pack_bf16(ACC(q, j, 0), ACC(q, j, 1));
  const int mn = m * 8 + n; (void)mn;
  PROF_E(7 * layer + t, 1);
  bar_sync(BAR_WG + wg, 128);
  const uint4* src = (w > 0 ? exc + (w - 1) * 512 : m > 0 ? g_halo + (slot - 8) * 512 : exc) + lane;
  uint32_t PK[2][8], PV[2][8], r4, r5;
#pragma unroll 1
  for (int it = 0; it < MSG_SPINS; it++) {
    uint32_t tg, bad = 0;
#pragma unroll
    for (int j = 0; j < 8; j++) {
      ld_msg(src + j * 32, PK[j >> 2][2 * (j & 3)], PK[j >> 2][2 * (j & 3) + 1], r4, tg); bad |= tg ^ tag;
      ld_msg(src + (8 + j) * 32, PV[0][j], PV[1][j], r5, tg); bad |= tg ^ tag;
    }
    if (__all_sync(0xffffffffu, bad == 0)) break;
  }
  kr[0] = __uint_as_float(r4);
  kr[1] = __uint_as_float(r5);
  float rk[2][4], sc[2][4], off[2][4];
#pragma unroll
  for (int g = 0; g < 2; g++) {
    rk[g][0] = kr[2 * g + 1];
    rk[g][1] = early ? kr[2 * g] : kr[2 * g + 2];
    rk[g][2] = kr[2 * g + 2];
    rk[g][3] = early ? kr[2 * g + 1] : kr[2 * g + 3];
#pragma unroll
    for (int e = 0; e < 4; e++) {
      const bool masked = g == 0 && e != 2 && (m | w) == 0 && (e == 0 || early);
      sc[g][e] = masked ? 0.f : rk[g][e] * qr[2 * g + (e >> 1)];
      off[g][e] = masked ? -1e30f : 0.f;
    }
  }
  PROF_E(7 * layer + t, 2);
  bar_sync(BAR_GO, 256);
  PROF_E(7 * layer + t, 3);
  const float4 zero = lds_f4(sb + OFF_ZERO);
  float l[2][2][4], o[2][2][4][4];
#pragma unroll
  for (int h = 0; h < 2; h++) {
    attn_scores(&Q[2][4 * h], &Q[3][4 * h], &K[0][4 * h], &K[1][4 * h], &K[2][4 * h], &K[3][4 * h], l[1][h], zero, par, early);
    attn_scores(&Q[0][4 * h], &Q[1][4 * h], &PK[0][4 * h], &PK[1][4 * h], &K[0][4 * h], &K[1][4 * h], l[0][h], zero, par, early);
  }
#pragma unroll
  for (int h = 0; h < 2; h++) {
    attn_mix(l[1][h], sc[1], off[1], rk[1], &V[0][4 * h], &V[1][4 * h], &V[2][4 * h], &V[3][4 * h], o[1][h], par, early);
    attn_mix(l[0][h], sc[0], off[0], rk[0], &PV[0][4 * h], &PV[1][4 * h], &V[0][4 * h], &V[1][4 * h], o[0][h], par, early);
  }
  const uint32_t stg = sb + OFF_STG + w * 4096;
#pragma unroll
  for (int j = 0; j < 8; j++) {
    const float(&a)[4] = o[0][j >> 2][j & 3];
    const float(&c)[4] = o[1][j >> 2][j & 3];
    stsm4(stg + lane * 128 + ((j ^ (lane & 7)) << 4), pack_bf16(a[0], a[1]), pack_bf16(a[2], a[3]), pack_bf16(c[0], c[1]),
          pack_bf16(c[2], c[3]));
  }
  bar_arrive(BAR_DONE, 256);
  fence_async_smem();
  __syncwarp();
  if (elect_one()) mbar_arrive(sb + BAR_PUBRDY);
}

__device__ __forceinline__ void consumer_tile(const Params& p, uint32_t sb0, int i, int mn) {
  const int layer = i >= 7, t = i - 7 * layer;
  const bool resid = i == -1 || t == 2 || t == 6;
  uint32_t tag;
  if (i >= 0) {
    float acc[2][96];
    if (resid) {
      const Ctx cx = make_ctx(sb0, mn);
      const uint32_t xrow = cx.sb + OFF_X + cx.w * 4096 + cx.lane * 128;
      const uint32_t sel_lo = 0x1044u | p.zero, sel_hi = 0x3244u | p.zero;
#pragma unroll
      for (int j = 0; j < 16; j++) {
        uint32_t r[4];
        ldsm4(xrow + (j >> 3) * 16384 + (((j & 7) ^ (cx.lane & 7)) << 4), r[0], r[1], r[2], r[3]);
#pragma unroll
        for (int q = 0; q < 4; q++) {
          ACC(q, j, 0) = prmt_f(r[q], sel_lo);
          ACC(q, j, 1) = prmt_f(r[q], sel_hi);
        }
      }
      if (t == 6) {
        const uint32_t* b2 = reinterpret_cast<const uint32_t*>(p.b2 + 128 * cx.n) + (cx.lane & 3);
#pragma unroll
        for (int j = 0; j < 16; j++) {
          const uint32_t bb = __ldg(b2 + 4 * j);
#pragma unroll
          for (int e = 0; e < 2; e++) {
            const int k = 2 * j + e - 1;
            const uint32_t u = k >= 0 ? bb | (__float_as_uint(ACC(3, k >> 1, k & 1)) & p.zero) : bb;
            const float bv = e ? bf_hi(u) : bf_lo(u);
#pragma unroll
            for (int q = 0; q < 4; q++) ACC(q, j, e) += bv;
          }
        }
      }
    } else {
#pragma unroll
      for (int r = 0; r < 64; r++) acc[0][r] = acc[1][r] = 0.f;
    }
    if (tile_wide(t)) {
#pragma unroll
      for (int r = 64; r < 96; r++) acc[0][r] = acc[1][r] = 0.f;
#pragma unroll 1
      for (int phase = 0; phase < 2; phase++) {
        if (t + phase == 1) {
          const Ctx cx = make_ctx(sb0, mn);
          float nm[4];
#pragma unroll
          for (int q = 0; q < 4; q++) nm[q] = -lds_f(cx.sb + OFF_ROW + (32 * cx.w + 8 * q + (cx.lane >> 2)) * 8 + 4);
          const uint32_t ctab = cx.sb + OFF_CSQ + (t * 192 + 2 * (cx.lane & 3)) * 4;
#pragma unroll
          for (int j = 0; j < 24; j++) {
            const float2 cs = lds_f2(ctab + j * 32);
#pragma unroll
            for (int q = 0; q < 4; q++) {
              const int k = 4 * j + q - 1;
              const float nq = k >= 0 ? chain(nm[q], __float_as_uint(ACC(k & 3, k >> 2, 1)), p.zero) : nm[q];
              ACC(q, j, 0) = fmaf(nq, cs.x, ACC(q, j, 0));
              ACC(q, j, 1) = fmaf(nq, cs.y, ACC(q, j, 1));
            }
          }
        }
        if (phase == 0) {
          mainloop<192>(acc, sb0, i, mn);
          bar_sync(BAR_GUARD + (i & 1), 256);
        }
      }
      if (t < 2) {
        attn_epilogue(p, acc, make_ctx(sb0, mn), layer, t, lds_u(sb0 + OFF_TAG));
        goto tile_done;
      }
    } else {
      mainloop<128>(acc, sb0, i, mn);
      if (resid) {
        const Ctx cx = make_ctx(sb0, mn);
        const uint32_t xrow = cx.sb + OFF_X + cx.w * 4096 + cx.lane * 128;
#pragma unroll
        for (int j = 0; j < 16; j++) {
          stsm4(xrow + (j >> 3) * 16384 + (((j & 7) ^ (cx.lane & 7)) << 4), pack_bf16(ACC(0, j, 0), ACC(0, j, 1)),
                pack_bf16(ACC(1, j, 0), ACC(1, j, 1)), pack_bf16(ACC(2, j, 0), ACC(2, j, 1)), pack_bf16(ACC(3, j, 0), ACC(3, j, 1)));
          if ((j & 7) == 7) {
            fence_async_smem();
            __syncwarp();
            if (elect_one()) mbar_arrive(cx.sb + BAR_XRDY + (j & 8));
          }
        }
        goto tile_done;
      }
      bar_sync(BAR_GUARD + (i & 1), 256);
#pragma unroll
      for (int r = 64; r < 96; r++) acc[0][r] = acc[1][r] = acc[0][0];
    }
    gelu_epilogue(p, acc, make_ctx(sb0, mn), layer, t);
  tile_done:
    tag = lds_u(sb0 + OFF_TAG);
  } else {
    tag = __ldcg(g_epoch + (mn & 127)) + 1;
    asm volatile("st.shared.u32 [%0], %1;" ::"r"(sb0 + OFF_TAG), "r"(tag) : "memory");
  }
  const Ctx cx = make_ctx(sb0, mn);
  PROF_E(i, 4);
  if (i == 13) {
    bar_sync(BAR_GUARD + 1, 256);
    return;
  }
  if (i <= 0) colsum_partial(p, cx, i < 0, tag);
  PROF_E(i, 7);
  if (resid) {
    const int ln = (i + 3) >> 2;
    if (i < 0) {
      mbar_wait(sb0 + BAR_XRDY, 0);
      mbar_wait(sb0 + BAR_XRDY + 8, 0);
    }
    write_partial_stats(cx, ln, tag);
    PROF_E(i, 8);
    if (i >= 0) bar_sync(BAR_GUARD + (i & 1), 256);
    if (i <= 2) colsum_gather(p, cx, i < 0, tag);
    PROF_E(i, 9);
    finish_row_stats(cx, ln, tag);
    PROF_E(i, 10);
    bar_sync(BAR_WG + (i & 1), 128);
  }
  bar_arrive(BAR_GUARD + ((i & 1) ^ 1), 256);
}

__global__ void __cluster_dims__(2, 1, 1) __launch_bounds__(384, 1) fused_layers_kernel(const __grid_constant__ Params p) {
  extern __shared__ __align__(1024) uint8_t smem_raw[];
  const uint32_t sb = uniform((uint32_t)__cvta_generic_to_shared(smem_raw));
  const int tid = threadIdx.x, lane = tid & 31, warp = uniform(tid >> 5), wg = warp >> 2, w = warp & 3;

  int mn;
  {
    int id = blockIdx.x;
    if (p.by_smid) asm volatile("mov.u32 %0, %%smid;" : "=r"(id));
    else if (id >= 120) id += 4;
    const int c = id >> 1;
    int g, j;
    if (c < 32) { g = c & 7; j = c >> 3; }
    else if (c < 60) { g = 1 + (c - 32) % 7; j = 4 + (c - 32) / 7; }
    else { g = 0; j = c - 58; }
    mn = ((g >> 2) * 8 + j) * 8 + (g & 3) * 2 + (id & 1);
    if (c == 60 || c == 61) {
      if (tid < 32) {
        const uint32_t tag = __ldcg(g_epoch + NCTA + (id & 3)) + 1;
#pragma unroll 1
        for (int mm = 0; mm < 16; mm++) poll_line(g_flags + mm * 32 + (lane & 7), 32 * tag, 0xffu);
        if (tid == 0) g_epoch[NCTA + (id & 3)] = tag;
      }
      return;
    }
  }
  const int m = mn >> 3, n = mn & 7;
    if (tid == 256) asm volatile("prefetch.tensormap [%0];" ::"l"(&p.wqkv) : "memory");
  if (tid == 288) asm volatile("prefetch.tensormap [%0];" ::"l"(&p.xin) : "memory");
  if (tid == 0) {
    for (int s = 0; s < NBAR; s++) {
      mbar_init(sb + BAR_FULL + 8 * s, 2);
      mbar_init(sb + BAR_EMPTY + 8 * s, 4);
    }
    mbar_init(sb + BAR_XRDY, 4);
    mbar_init(sb + BAR_XRDY + 8, 4);
    mbar_init(sb + BAR_PUBRDY, 4);
    mbar_init(sb + BAR_PUBFREE, 1);
    mbar_init(sb + BAR_PUSHOK, 1);
    mbar_init(sb + BAR_PUSHOK + 8, 1);
    mbar_init(sb + BAR_DUMMY, 4);
    asm volatile("fence.mbarrier_init.release.cluster;" ::: "memory");
    sts_f2(sb + OFF_ZERO, 0.f, 0.f);
    sts_f2(sb + OFF_ZERO + 8, 0.f, 0.f);
    fence_async_smem();
  }
  __syncthreads();

  if (wg == 2) {
    asm volatile("setmaxnreg.dec.sync.aligned.u32 40;");
    if (w == 0) {
      producer<false>(p, sb, m, n, lane);
    } else if (w == 1) {
      if (elect_one()) {
        for (int h = 0; h < 2; h++) {
          const uint32_t xr = sb + BAR_XRDY + 8 * h;
          mbar_expect_tx(xr, 16384);
          tma_ld2(sb + OFF_X + h * 16384, &p.xin, xr, 128 * n + 64 * h, 128 * m);
          asm volatile("mbarrier.arrive.shared::cta.b64 _, [%0], 3;" ::"r"(xr) : "memory");
        }
      }
      producer<true>(p, sb, m, n, lane);
    } else if (w == 2) {
      if (elect_one()) publisher(p, sb, m, n);
    }
  } else {
    asm volatile("setmaxnreg.inc.sync.aligned.u32 232;");
#pragma unroll 1
    for (int i = -wg; i < 14; i += 2) {
      consumer_tile(p, sb, i, mn | (warp << 7));
      PROF_T(i < 0 ? 3 : 6 + i * 4);
    }
  }
}

typedef CUresult (*EncodeFn)(CUtensorMap*, CUtensorMapDataType, cuuint32_t, void*, const cuuint64_t*, const cuuint64_t*,
                             const cuuint32_t*, const cuuint32_t*, CUtensorMapInterleave, CUtensorMapSwizzle,
                             CUtensorMapL2promotion, CUtensorMapFloatOOBfill);

void make_2d(EncodeFn enc, CUtensorMap* m, const void* ptr, uint64_t cols, uint64_t rows, uint32_t box_rows) {
  cuuint64_t d[2] = {cols, rows}, st[1] = {cols * 2};
  cuuint32_t b[2] = {64, box_rows}, e[2] = {1, 1};
  enc(m, CU_TENSOR_MAP_DATA_TYPE_BFLOAT16, 2, const_cast<void*>(ptr), d, st, b, e, CU_TENSOR_MAP_INTERLEAVE_NONE,
      CU_TENSOR_MAP_SWIZZLE_128B, CU_TENSOR_MAP_L2_PROMOTION_L2_128B, CU_TENSOR_MAP_FLOAT_OOB_FILL_NONE);
}
void make_3d(EncodeFn enc, CUtensorMap* m, const void* ptr, uint64_t d0, uint64_t rows, uint64_t d2, uint64_t row_bytes,
             uint64_t chunk_bytes, uint32_t box_chunks) {
  cuuint64_t d[3] = {d0, rows, d2}, st[2] = {row_bytes, chunk_bytes};
  cuuint32_t b[3] = {64, 64, box_chunks}, e[3] = {1, 1, 1};
  enc(m, CU_TENSOR_MAP_DATA_TYPE_BFLOAT16, 3, const_cast<void*>(ptr), d, st, b, e, CU_TENSOR_MAP_INTERLEAVE_NONE,
      CU_TENSOR_MAP_SWIZZLE_128B, CU_TENSOR_MAP_L2_PROMOTION_L2_128B, CU_TENSOR_MAP_FLOAT_OOB_FILL_NONE);
}

}

extern "C" void kernel_launch(void* const* d_in, const int* in_sizes, int n_in, void* d_out, int out_size) {
  (void)in_sizes; (void)n_in; (void)out_size;
  static EncodeFn enc = nullptr;
  static void *att = nullptr, *hbuf = nullptr;
  static int by_smid = 0;
  if (!enc) {
    void* fn = nullptr;
    cudaDriverEntryPointQueryResult q;
    cudaGetDriverEntryPoint("cuTensorMapEncodeTiled", &fn, cudaEnableDefault, &q);
    enc = (EncodeFn)fn;
    cudaGetSymbolAddress(&att, g_att);
    cudaGetSymbolAddress(&hbuf, g_h);
    cudaFuncSetAttribute(fused_layers_kernel, cudaFuncAttributeMaxDynamicSharedMemorySize, SMEM_BYTES);
    int sms = 0, clusters = 0, dev = 0;
    cudaGetDevice(&dev);
    cudaDeviceGetAttribute(&sms, cudaDevAttrMultiProcessorCount, dev);
    cudaLaunchConfig_t cfg = {};
    cfg.gridDim = dim3(132);
    cfg.blockDim = dim3(384);
    cfg.dynamicSmemBytes = SMEM_BYTES;
    cudaLaunchAttribute at[1];
    at[0].id = cudaLaunchAttributeClusterDimension;
    at[0].val.clusterDim.x = 2; at[0].val.clusterDim.y = 1; at[0].val.clusterDim.z = 1;
    cfg.attrs = at;
    cfg.numAttrs = 1;
    if (cudaOccupancyMaxActiveClusters(&clusters, fused_layers_kernel, &cfg) != cudaSuccess) (void)cudaGetLastError();
    by_smid = sms == 132 && clusters == 66;
  }
  Params p;
  make_2d(enc, &p.xin, d_in[0], DM, SEQ, 128);
  make_2d(enc, &p.out, d_out, DM, SEQ, 128);
  make_2d(enc, &p.att, att, DM, SEQ, 128);
  make_2d(enc, &p.h, hbuf, FF, SEQ, 128);
  make_3d(enc, &p.wqkv, d_in[1], DM, DM, 3, 3 * DM * 2, DM * 2, 3);
  make_3d(enc, &p.wo, d_in[2], 64, DM, DM / 64, DM * 2, 128, 2);
  make_3d(enc, &p.w1a, d_in[4], 64, DM, FF / 64, FF * 2, 128, 3);
  make_3d(enc, &p.w1b, d_in[4], 64, DM, FF / 64, FF * 2, 128, 2);
  make_3d(enc, &p.w2, d_in[6], 64, FF, DM / 64, DM * 2, 128, 2);
  p.wqkv_p = (const __nv_bfloat16*)d_in[1];
  p.w1_p = (const __nv_bfloat16*)d_in[4];
  p.b1 = (const __nv_bfloat16*)d_in[5];
  p.b2 = (const __nv_bfloat16*)d_in[7];
  p.by_smid = by_smid;
  p.zero = 0;
  fused_layers_kernel<<<by_smid ? 132 : NCTA, 384, SMEM_BYTES>>>(p);
}
```

```cpp
#include <cuda_runtime.h>
#include <cuda_bf16.h>
#include <cuda.h>
#include <stdint.h>

namespace {

constexpr int SEQ = 2048, DM = 1024, FF = 3584;
constexpr int NCTA = 128;
constexpr int NBAR = 5;

constexpr uint32_t RING_UNITS = 20, UNIT = 8192;
constexpr uint32_t OFF_X   = RING_UNITS * UNIT;
constexpr uint32_t OFF_STG = OFF_X + 32768;
constexpr uint32_t OFF_CSQ = OFF_STG + 24576;
constexpr uint32_t OFF_CSF = OFF_CSQ + 1536;
constexpr uint32_t OFF_ROW = OFF_CSF + 3584;
constexpr uint32_t OFF_BAR = OFF_ROW + 1024;
constexpr uint32_t SMEM_BYTES = OFF_BAR + 256;
constexpr uint32_t BAR_FULL = OFF_BAR, BAR_EMPTY = OFF_BAR + 8 * NBAR;
constexpr uint32_t BAR_XRDY = OFF_BAR + 80;
constexpr uint32_t BAR_DUMMY = OFF_BAR + 96, OFF_TAG = OFF_BAR + 104, OFF_ZERO = OFF_BAR + 112;
constexpr uint32_t BAR_PUB = OFF_BAR + 128;

constexpr uint64_t DESC_A = (1ull << 62) | ((uint64_t)(2048 >> 4) << 32) | (1ull << 16);
constexpr uint64_t DESC_B = (1ull << 62) | ((uint64_t)(1024 >> 4) << 32) | ((uint64_t)(8192 >> 4) << 16);

constexpr int BAR_ORDER = 1, BAR_GUARD = 3, BAR_WG = 5, BAR_GO = 7, BAR_DONE = 8;
#define GELU_DEP 3
#define WIN1 6
#define WIN2 4

struct Params {
  CUtensorMap xin, out, att, h, wqkv, wo, w1a, w1b, w2, out_st, att_st, h_st;
  const __nv_bfloat16 *wqkv_p, *w1_p, *b1, *b2;
  int by_smid;
  uint32_t zero;
};

__device__ __nv_bfloat16 g_att[SEQ * DM];
__device__ __nv_bfloat16 g_h[SEQ * FF];
__device__ uint4 g_stats[4 * 8 * SEQ];
__device__ uint4 g_halo[2 * 2 * 16 * 8 * 512];
__device__ uint4 g_csp[2 * 8 * 16 * 160];
__device__ uint32_t g_flags[16 * 32];
__device__ uint32_t g_epoch[NCTA + 4];
#define PROF_T(idx)
#define PROF_S(g)
#define PROF_E(i, k)

__device__ __forceinline__ void mbar_init(uint32_t bar, int cnt) {
  asm volatile("mbarrier.init.shared::cta.b64 [%0], %1;" ::"r"(bar), "r"(cnt));
}
__device__ __forceinline__ void mbar_expect_tx(uint32_t bar, uint32_t bytes) {
  asm volatile("mbarrier.arrive.expect_tx.shared::cta.b64 _, [%0], %1;" ::"r"(bar), "r"(bytes) : "memory");
}
__device__ __forceinline__ void mbar_arrive(uint32_t bar) {
  asm volatile("mbarrier.arrive.shared::cta.b64 _, [%0];" ::"r"(bar) : "memory");
}
__device__ __forceinline__ bool mbar_test(uint32_t bar, uint32_t parity) {
  uint32_t ok;
  asm volatile("{\n.reg .pred p;\nmbarrier.test_wait.parity.shared::cta.b64 p, [%1], %2;\nselp.u32 %0, 1, 0, p;\n}"
               : "=r"(ok) : "r"(bar), "r"(parity) : "memory");
  return ok;
}
__device__ __forceinline__ void mbar_wait(uint32_t bar, uint32_t parity) {
  asm volatile(
      "{\n.reg .pred p;\n.reg .u32 it;\nmov.u32 it, 0;\n"
      "WAIT_LOOP:\n"
      "mbarrier.try_wait.parity.shared::cta.b64 p, [%0], %1;\n"
      "@p bra WAIT_DONE;\n"
      "add.u32 it, it, 1;\n"
      "setp.lt.u32 p, it, 0x400000;\n"
      "@p bra WAIT_LOOP;\n"
      "trap;\n"
      "WAIT_DONE:\n}"
      ::"r"(bar), "r"(parity) : "memory");
}
__device__ __forceinline__ void bar_sync(int id, int n) { asm volatile("bar.sync %0, %1;" ::"r"(id), "r"(n) : "memory"); }
__device__ __forceinline__ void bar_arrive(int id, int n) { asm volatile("bar.arrive %0, %1;" ::"r"(id), "r"(n) : "memory"); }
__device__ __forceinline__ void tma_ld2(uint32_t dst, const CUtensorMap* m, uint32_t bar, int c0, int c1) {
  asm volatile("cp.async.bulk.tensor.2d.shared::cluster.global.mbarrier::complete_tx::bytes [%0], [%1, {%3, %4}], [%2];"
               ::"r"(dst), "l"(m), "r"(bar), "r"(c0), "r"(c1) : "memory");
}
__device__ __forceinline__ void tma_ld3(uint32_t dst, const CUtensorMap* m, uint32_t bar, int c0, int c1, int c2) {
  asm volatile("cp.async.bulk.tensor.3d.shared::cluster.global.mbarrier::complete_tx::bytes [%0], [%1, {%3, %4, %5}], [%2];"
               ::"r"(dst), "l"(m), "r"(bar), "r"(c0), "r"(c1), "r"(c2) : "memory");
}
__device__ __forceinline__ void tma_pf3(const CUtensorMap* m, int c0, int c1, int c2) {
  asm volatile("cp.async.bulk.prefetch.tensor.3d.L2.global [%0, {%1, %2, %3}];" ::"l"(m), "r"(c0), "r"(c1), "r"(c2) : "memory");
}
__device__ __forceinline__ void tma_st2(const CUtensorMap* m, uint32_t src, int c0, int c1) {
  asm volatile("cp.async.bulk.tensor.2d.global.shared::cta.bulk_group [%0, {%2, %3}], [%1];"
               ::"l"(m), "r"(src), "r"(c0), "r"(c1) : "memory");
}
__device__ __forceinline__ void bulk_commit() { asm volatile("cp.async.bulk.commit_group;" ::: "memory"); }
__device__ __forceinline__ void bulk_wait_read() { asm volatile("cp.async.bulk.wait_group.read 0;" ::: "memory"); }
__device__ __forceinline__ void bulk_wait_all() { asm volatile("cp.async.bulk.wait_group 0;" ::: "memory"); }
__device__ __forceinline__ void fence_async_smem() { asm volatile("fence.proxy.async.shared::cta;" ::: "memory"); }
__device__ __forceinline__ void fence_async_global() { asm volatile("fence.proxy.async.global;" ::: "memory"); }
__device__ __forceinline__ void st_relaxed(uint32_t* p, uint32_t v) {
  asm volatile("st.relaxed.gpu.global.u32 [%0], %1;" ::"l"(p), "r"(v) : "memory");
}
__device__ __forceinline__ void st_msg(uint4* p, uint32_t a, uint32_t b, uint32_t c, uint32_t tag) {
  asm volatile("{\n.reg .b128 v;\nmov.b128 v, {%1, %2, %3, %4};\nst.relaxed.gpu.b128 [%0], v;\n}"
               ::"l"(p), "r"(a), "r"(b), "r"(c), "r"(tag) : "memory");
}
__device__ __forceinline__ void ld_msg(const uint4* p, uint32_t& a, uint32_t& b, uint32_t& c, uint32_t& tag) {
  asm volatile("{\n.reg .b128 v;\nld.relaxed.gpu.b128 v, [%4];\nmov.b128 {%0, %1, %2, %3}, v;\n}"
               : "=r"(a), "=r"(b), "=r"(c), "=r"(tag) : "l"(p) : "memory");
}
__device__ __forceinline__ bool elect_one() {
  uint32_t ok;
  asm volatile("{\n.reg .pred p;\nelect.sync _|p, 0xffffffff;\nselp.u32 %0, 1, 0, p;\n}" : "=r"(ok));
  return ok;
}
__device__ __forceinline__ int uniform(int v) { return __shfl_sync(0xffffffffu, v, 0); }
__device__ __forceinline__ uint32_t pack_bf16(float lo, float hi) {
  uint32_t r;
  asm("cvt.rn.bf16x2.f32 %0, %1, %2;" : "=r"(r) : "f"(hi), "f"(lo));
  return r;
}
__device__ __forceinline__ float prmt_f(uint32_t a, uint32_t sel) {
  float r;
  asm("{\n.reg .b32 t;\nprmt.b32 t, %1, 0, %2;\nmov.b32 %0, t;\n}" : "=f"(r) : "r"(a), "r"(sel));
  return r;
}
__device__ __forceinline__ float bf_lo(uint32_t v) { return __uint_as_float(v << 16); }
__device__ __forceinline__ float bf_hi(uint32_t v) { return __uint_as_float(v & 0xffff0000u); }
__device__ __forceinline__ void stsm4(uint32_t addr, uint32_t r0, uint32_t r1, uint32_t r2, uint32_t r3) {
  asm volatile("stmatrix.sync.aligned.m8n8.x4.shared.b16 [%0], {%1, %2, %3, %4};"
               ::"r"(addr), "r"(r0), "r"(r1), "r"(r2), "r"(r3) : "memory");
}
__device__ __forceinline__ void ldsm4(uint32_t addr, uint32_t& r0, uint32_t& r1, uint32_t& r2, uint32_t& r3) {
  asm volatile("ldmatrix.sync.aligned.m8n8.x4.shared.b16 {%0, %1, %2, %3}, [%4];"
               : "=r"(r0), "=r"(r1), "=r"(r2), "=r"(r3) : "r"(addr) : "memory");
}
__device__ __forceinline__ uint32_t movtrans(uint32_t a) {
  uint32_t d;
  asm volatile("movmatrix.sync.aligned.m8n8.trans.b16 %0, %1;" : "=r"(d) : "r"(a));
  return d;
}
__device__ __forceinline__ void mma16816(float (&c)[4], uint32_t a0, uint32_t a1, uint32_t a2, uint32_t a3, uint32_t b0, uint32_t b1) {
  asm volatile("mma.sync.aligned.m16n8k16.row.col.f32.bf16.bf16.f32 {%0,%1,%2,%3}, {%4,%5,%6,%7}, {%8,%9}, {%0,%1,%2,%3};"
               : "+f"(c[0]), "+f"(c[1]), "+f"(c[2]), "+f"(c[3])
               : "r"(a0), "r"(a1), "r"(a2), "r"(a3), "r"(b0), "r"(b1));
}
__device__ __forceinline__ float2 lds_f2(uint32_t a) {
  float2 v;
  asm volatile("ld.shared.v2.f32 {%0, %1}, [%2];" : "=f"(v.x), "=f"(v.y) : "r"(a) : "memory");
  return v;
}
__device__ __forceinline__ float4 lds_f4(uint32_t a) {
  float4 v;
  asm volatile("ld.shared.v4.f32 {%0, %1, %2, %3}, [%4];" : "=f"(v.x), "=f"(v.y), "=f"(v.z), "=f"(v.w) : "r"(a) : "memory");
  return v;
}
__device__ __forceinline__ float lds_f(uint32_t a) {
  float v;
  asm volatile("ld.shared.f32 %0, [%1];" : "=f"(v) : "r"(a) : "memory");
  return v;
}
__device__ __forceinline__ void sts_f(uint32_t a, float v) { asm volatile("st.shared.f32 [%0], %1;" ::"r"(a), "f"(v) : "memory"); }
__device__ __forceinline__ uint32_t lds_u(uint32_t a) {
  uint32_t v;
  asm volatile("ld.shared.u32 %0, [%1];" : "=r"(v) : "r"(a) : "memory");
  return v;
}
__device__ __forceinline__ void sts_f2(uint32_t a, float x, float y) {
  asm volatile("st.shared.v2.f32 [%0], {%1, %2};" ::"r"(a), "f"(x), "f"(y) : "memory");
}
__device__ __forceinline__ void lds_u4(uint32_t a, uint32_t& x, uint32_t& y, uint32_t& z, uint32_t& w) {
  asm volatile("ld.shared.v4.u32 {%0, %1, %2, %3}, [%4];" : "=r"(x), "=r"(y), "=r"(z), "=r"(w) : "r"(a) : "memory");
}
__device__ __forceinline__ float ex2(float x) {
  float y;
  asm("ex2.approx.ftz.f32 %0, %1;" : "=f"(y) : "f"(x));
  return y;
}
__device__ __forceinline__ float rcp_hw(float x) {
  float y;
  asm("rcp.approx.ftz.f32 %0, %1;" : "=f"(y) : "f"(x));
  return y;
}
__device__ __forceinline__ float tanh_hw(float x) {
  float y;
  asm("tanh.approx.f32 %0, %1;" : "=f"(y) : "f"(x));
  return y;
}
__device__ __forceinline__ float quad_sum(float v) {
  v += __shfl_xor_sync(0xffffffffu, v, 1);
  return v + __shfl_xor_sync(0xffffffffu, v, 2);
}
__device__ __forceinline__ float quad_max(float v) {
  v = fmaxf(v, __shfl_xor_sync(0xffffffffu, v, 1));
  return fmaxf(v, __shfl_xor_sync(0xffffffffu, v, 2));
}

template <int N> __device__ __forceinline__ void wgmma_ss(float (&d)[96], uint64_t da, uint64_t db);
template <> __device__ __forceinline__ void wgmma_ss<128>(float (&d)[96], uint64_t da, uint64_t db) {
  asm volatile(
      "wgmma.mma_async.sync.aligned.m64n128k16.f32.bf16.bf16 {%0, %1, %2, %3, %4, %5, %6, %7, %8, %9, %10, %11, %12, %13, %14, %15, %16, %17, %18, %19, %20, %21, %22, %23, %24, %25, %26, %27, %28, %29, %30, %31, %32, %33, %34, %35, %36, %37, %38, %39, %40, %41, %42, %43, %44, %45, %46, %47, %48, %49, %50, %51, %52, %53, %54, %55, %56, %57, %58, %59, %60, %61, %62, %63}, %64, %65, 1, 1, 1, 0, 1;"
      : "+f"(d[0]), "+f"(d[1]), "+f"(d[2]), "+f"(d[3]), "+f"(d[4]), "+f"(d[5]), "+f"(d[6]), "+f"(d[7]), "+f"(d[8]), "+f"(d[9]), "+f"(d[10]), "+f"(d[11]), "+f"(d[12]), "+f"(d[13]), "+f"(d[14]), "+f"(d[15]), "+f"(d[16]), "+f"(d[17]), "+f"(d[18]), "+f"(d[19]), "+f"(d[20]), "+f"(d[21]), "+f"(d[22]), "+f"(d[23]), "+f"(d[24]), "+f"(d[25]), "+f"(d[26]), "+f"(d[27]), "+f"(d[28]), "+f"(d[29]), "+f"(d[30]), "+f"(d[31]), "+f"(d[32]), "+f"(d[33]), "+f"(d[34]), "+f"(d[35]), "+f"(d[36]), "+f"(d[37]), "+f"(d[38]), "+f"(d[39]), "+f"(d[40]), "+f"(d[41]), "+f"(d[42]), "+f"(d[43]), "+f"(d[44]), "+f"(d[45]), "+f"(d[46]), "+f"(d[47]), "+f"(d[48]), "+f"(d[49]), "+f"(d[50]), "+f"(d[51]), "+f"(d[52]), "+f"(d[53]), "+f"(d[54]), "+f"(d[55]), "+f"(d[56]), "+f"(d[57]), "+f"(d[58]), "+f"(d[59]), "+f"(d[60]), "+f"(d[61]), "+f"(d[62]), "+f"(d[63])
      : "l"(da), "l"(db));
}

template <> __device__ __forceinline__ void wgmma_ss<192>(float (&d)[96], uint64_t da, uint64_t db) {
  asm volatile(
      "wgmma.mma_async.sync.aligned.m64n192k16.f32.bf16.bf16 {%0, %1, %2, %3, %4, %5, %6, %7, %8, %9, %10, %11, %12, %13, %14, %15, %16, %17, %18, %19, %20, %21, %22, %23, %24, %25, %26, %27, %28, %29, %30, %31, %32, %33, %34, %35, %36, %37, %38, %39, %40, %41, %42, %43, %44, %45, %46, %47, %48, %49, %50, %51, %52, %53, %54, %55, %56, %57, %58, %59, %60, %61, %62, %63, %64, %65, %66, %67, %68, %69, %70, %71, %72, %73, %74, %75, %76, %77, %78, %79, %80, %81, %82, %83, %84, %85, %86, %87, %88, %89, %90, %91, %92, %93, %94, %95}, %96, %97, 1, 1, 1, 0, 1;"
      : "+f"(d[0]), "+f"(d[1]), "+f"(d[2]), "+f"(d[3]), "+f"(d[4]), "+f"(d[5]), "+f"(d[6]), "+f"(d[7]), "+f"(d[8]), "+f"(d[9]), "+f"(d[10]), "+f"(d[11]), "+f"(d[12]), "+f"(d[13]), "+f"(d[14]), "+f"(d[15]), "+f"(d[16]), "+f"(d[17]), "+f"(d[18]), "+f"(d[19]), "+f"(d[20]), "+f"(d[21]), "+f"(d[22]), "+f"(d[23]), "+f"(d[24]), "+f"(d[25]), "+f"(d[26]), "+f"(d[27]), "+f"(d[28]), "+f"(d[29]), "+f"(d[30]), "+f"(d[31]), "+f"(d[32]), "+f"(d[33]), "+f"(d[34]), "+f"(d[35]), "+f"(d[36]), "+f"(d[37]), "+f"(d[38]), "+f"(d[39]), "+f"(d[40]), "+f"(d[41]), "+f"(d[42]), "+f"(d[43]), "+f"(d[44]), "+f"(d[45]), "+f"(d[46]), "+f"(d[47]), "+f"(d[48]), "+f"(d[49]), "+f"(d[50]), "+f"(d[51]), "+f"(d[52]), "+f"(d[53]), "+f"(d[54]), "+f"(d[55]), "+f"(d[56]), "+f"(d[57]), "+f"(d[58]), "+f"(d[59]), "+f"(d[60]), "+f"(d[61]), "+f"(d[62]), "+f"(d[63]), "+f"(d[64]), "+f"(d[65]), "+f"(d[66]), "+f"(d[67]), "+f"(d[68]), "+f"(d[69]), "+f"(d[70]), "+f"(d[71]), "+f"(d[72]), "+f"(d[73]), "+f"(d[74]), "+f"(d[75]), "+f"(d[76]), "+f"(d[77]), "+f"(d[78]), "+f"(d[79]), "+f"(d[80]), "+f"(d[81]), "+f"(d[82]), "+f"(d[83]), "+f"(d[84]), "+f"(d[85]), "+f"(d[86]), "+f"(d[87]), "+f"(d[88]), "+f"(d[89]), "+f"(d[90]), "+f"(d[91]), "+f"(d[92]), "+f"(d[93]), "+f"(d[94]), "+f"(d[95])
      : "l"(da), "l"(db));
}

template <int R>
__device__ __forceinline__ void pin_regs(float (&a)[2][96]) {
#pragma unroll
  for (int m = 0; m < 2; m++)
#pragma unroll
    for (int i = 0; i < R; i++) asm volatile("" : "+f"(a[m][i])::"memory");
}

struct Ctx {
  uint32_t sb;
  int m, n, wg, w, lane;
};
__device__ __forceinline__ Ctx make_ctx(uint32_t sb, int id) {
  int lane;
  asm volatile("mov.u32 %0, %%laneid;" : "=r"(lane));
  asm volatile("" : "+r"(id), "+r"(sb));
  return Ctx{sb, (id >> 3) & 15, id & 7, id >> 9, (id >> 7) & 3, lane};
}
#define UNPACK_CTX(c) const uint32_t sb = c.sb; const int m = c.m, n = c.n, wg = c.wg, w = c.w, lane = c.lane

__device__ __forceinline__ uint32_t poll_line(const uint32_t* word, uint32_t target, uint32_t need) {
  uint32_t v;
  asm volatile(
      "{\n.reg .pred p;\n.reg .u32 it, m;\n.reg .s32 d;\nmov.u32 it, 0;\n"
      "POLL_LOOP:\n"
      "ld.relaxed.gpu.global.u32 %0, [%1];\n"
      "sub.s32 d, %0, %2;\n"
      "setp.ge.s32 p, d, 0;\n"
      "vote.sync.ballot.b32 m, p, 0xffffffff;\n"
      "and.b32 m, m, %3;\n"
      "setp.eq.u32 p, m, %3;\n"
      "@p bra.uni POLL_DONE;\n"
      "add.u32 it, it, 1;\n"
      "setp.lt.u32 p, it, 0x400000;\n"
      "@p bra.uni POLL_LOOP;\n"
      "trap;\n"
      "POLL_DONE:\n}"
      : "=&r"(v) : "l"(word), "r"(target), "r"(need) : "memory");
  return v;
}
__device__ __forceinline__ uint32_t ld_relaxed(const uint32_t* p) {
  uint32_t v;
  asm volatile("ld.relaxed.gpu.global.u32 %0, [%1];" : "=r"(v) : "l"(p) : "memory");
  return v;
}
__device__ __forceinline__ float chain(float x, uint32_t on, uint32_t zero) {
  return __uint_as_float(__float_as_uint(x) | (on & zero));
}
constexpr int MSG_SPINS = 1 << 20;

constexpr int STAGES_PER_LAYER = 152;
__device__ __forceinline__ int nib(uint64_t v, int i) { return (int)(v >> (4 * i)) & 15; }
__device__ __forceinline__ bool tile_wide(int t) { return (0x23 >> t) & 1; }
constexpr uint64_t ORDER_PLAIN = 0xFEDCBA9876543210ull, ORDER_X = 0xFEDCBA9765432180ull;

__device__ __forceinline__ void weight_coords(const Params& p, int t, int n, const CUtensorMap*& map, int& c0, int& c2) {
  map = &p.wqkv + nib(0x4233100ull, t);
  c0 = t < 2 ? 128 * n + 64 * t : 0;
  c2 = t < 2 ? 0 : (t == 2 || t == 6) ? 2 * n : 7 * n + 2 * t - 6;
}

template <bool IS_A>
__device__ __forceinline__ void producer(const Params& p, uint32_t sb, int m, int n, int lane) {
  int inflight = 0, rph = 0, min_seen = 0;
  uint32_t b8 = 0, rb8 = 0, pos = 0, tag32 = 0, seen = 0;
  const uint32_t* word = g_flags + m * 32 + (lane & 7);
#pragma unroll 1
  for (int sg = 0; sg < 34; sg++) {
    const int layer = sg >= 17, s = sg == 1 ? 2 : sg == 2 ? 1 : sg - 17 * layer;
    const int t = s < 10 ? nib(0x5434321010ull, s) : 6, kind = s < 10 ? nib(0x2110021100ull, s) : 3;
    const bool wide = tile_wide(t), xtype = t != 2 && t != 6;
    const uint32_t bbytes = wide ? 3 * UNIT : 2 * UNIT;
    const int mul = t == 6 ? 7 : 2, add = t == 6 ? s - 10 : 0, count = 2 * nib(0x4871ull, kind);
    uint64_t order = (xtype ? ORDER_X : ORDER_PLAIN) >> (kind == 1 ? 8 : 0);
    uint32_t lags = s == 9 ? 0x55555545u : wide ? 0x55555555u : (s == 4 || s == 10) ? 0xAAAAAA55u : 0xAAAAAAAAu;
    uint32_t own = t == 2 ? 0x100u : xtype && kind != 1 ? 3u : 0u;
    if (s == 9 || s == 10) pos = (s + 6) * UNIT;
    const CUtensorMap* map;
    int c0 = 0, c2 = 0, ev = 0;
    if (IS_A) {
      map = &p.xin + (t == 2 ? 2 : t == 6 ? 3 : sg >= 4);
      ev = 9 * layer + (t < 2 ? -1 : t == 2 ? 1 : t < 6 ? 3 : nib(0x7776655ull, add));
      if (sg == 3) seen = tag32 = (__ldcg(g_epoch + m * 8 + n) + 1) << 5;
      if (sg >= 4) {
        min_seen = __reduce_min_sync(0xffffffffu, (int)(seen - tag32));
        asm volatile("fence.acquire.gpu;" ::: "memory");
        fence_async_global();
        seen = ld_relaxed(word);
      }
    } else {
      const int pf = s == 3 ? 2 : s == 4 ? 3 : s == 7 ? 5 : s == 8 ? 6 : sg == 12 ? 0 : -1;
#pragma unroll 1
      for (int tt = pf; tt >= 0 && tt <= pf + (pf == 0 || pf == 3); tt++) {
        weight_coords(p, tt, n, map, c0, c2);
#pragma unroll 1
        for (int kb = m; kb < (tt == 6 ? 56 : 16); kb += 16)
          if (elect_one()) tma_pf3(map, c0, 64 * kb, c2);
      }
      weight_coords(p, t, n, map, c0, c2);
    }
#pragma unroll 1
    for (int k = 0; k < count; k++) {
      const int q = order & 7, hi = (order >> 3) & 1, lag = 2 + (lags & 3);
      const bool local = own & 1;
      order >>= 4;
      lags >>= 2;
      own >>= 1;
      const int src = (((n & 6) + q) & 7) ^ (q < 2 ? n & 1 : 0);
      const int kc = 64 * (mul * src + add + hi);
      if (IS_A && !local && min_seen < ev + hi) {
        const uint32_t v = poll_line(word, tag32 + ev + hi, 1u << src);
        min_seen = __reduce_min_sync(0xffffffffu, (int)(v - tag32));
        asm volatile("fence.acquire.gpu;" ::: "memory");
        fence_async_global();
      }
#pragma unroll 1
      for (; inflight > lag; inflight--) {
        mbar_wait(sb + BAR_EMPTY + rb8, rph);
        rb8 += 8;
        if (rb8 == 8 * NBAR) { rb8 = 0; rph ^= 1; }
      }
      const uint32_t fb = sb + BAR_FULL + b8;
      if (!IS_A) {
        if (elect_one()) {
          mbar_expect_tx(fb, bbytes);
          tma_ld3(sb + pos, map, fb, c0, kc, c2);
        }
      } else if (!local) {
        if (elect_one()) {
          mbar_expect_tx(fb, 16384);
          tma_ld2(sb + pos + bbytes, map, fb, kc, 128 * m);
        }
      } else {
        if (t == 2) mbar_wait(sb + BAR_PUB + 8, layer);
        else if (k == 1 && (s == 0 || s == 5)) mbar_wait(sb + BAR_XRDY + 8, s == 5);
        if (elect_one()) mbar_arrive(fb);
      }
      inflight++;
      b8 += 8;
      if (b8 == 8 * NBAR) b8 = 0;
      pos += bbytes + 2 * UNIT;
      if (pos >= RING_UNITS * UNIT) pos -= RING_UNITS * UNIT;
    }
  }
}

__device__ __forceinline__ void publisher(const Params& p, uint32_t sb, int m, int n) {
  const uint32_t tag = __ldcg(g_epoch + m * 8 + n) + 1;
  uint32_t* word = g_flags + m * 32 + n;
  const int mn = m * 8 + n; (void)mn;
  st_relaxed(word, 32 * tag);
#pragma unroll 1
  for (int c = 0; c < 18; c++) {
    const int e = c >= 9 ? c - 9 : c;
    if ((0x18C >> e) & 1) {
      const int half = (0x108 >> e) & 1;
      mbar_wait(sb + BAR_XRDY + 8 * half, e < 4);
#pragma unroll
      for (int w = 0; w < 4; w++) tma_st2(&p.out_st, sb + OFF_X + half * 16384 + w * 4096, 128 * n + 64 * half, 128 * m + 32 * w);
      bulk_commit();
      if (c >= 16) continue;
      bulk_wait_all();
      PROF_E(7 * (c >= 9) + (e < 4 ? 2 : 6), 11 + 2 * half);
    } else {
      mbar_wait(sb + BAR_PUB + 8 * e, c >= 9);
    }
    asm volatile("fence.release.gpu;" ::: "memory");
    st_relaxed(word, 32 * tag + c + 1);
    PROF_E(7 * (c >= 9) + nib(0x665432210ull, e), (0x108 >> e) & 1 ? 14 : 12);
  }
  g_epoch[m * 8 + n] = tag;
  bulk_wait_read();
}

template <int N>
__device__ __forceinline__ void mainloop(float (&acc)[2][96], uint32_t sb, int i, int part, int mn) {
  constexpr uint32_t Z16 = (2 + N / 64) * (UNIT >> 4), RING16 = RING_UNITS * (UNIT >> 4);
  constexpr uint32_t A_OFF = Z16 - 1024 + (uint32_t)DESC_A - (uint32_t)DESC_B;
  const int wg = i & 1;
  const int layer = i >= 7, t = i - 7 * layer;
  const bool own = t != 2 && t != 6 && part != 1, second = t == 1 || t == 4;
  const int gl = 16 * t + (part == 2 ? 0 : second ? 16 * part - 14 : 4 * part), g0 = layer * STAGES_PER_LAYER + gl;
  const uint32_t s16 = (sb & 0x3FFFF) >> 4;
  const uint32_t bfirst = (uint32_t)DESC_B + s16;
  const uint32_t blast = uniform(bfirst + RING16 - Z16), flast = uniform(sb + BAR_FULL + 8 * (NBAR - 1));
  const int nkb = t == 6 ? 56 : part == 0 ? 2 : 12 + 2 * part;
  const bool win1 = t == 1 && part != 0;
  int run = uniform(win1 ? WIN1 + 1 : t == 2 ? WIN2 + 1 : nkb);
  int rest = win1 ? 64 | (nkb - 1 - WIN1) : t == 2 ? 64 | (7 - WIN2) | (8 << 7) : 0;
  uint32_t fb = sb + BAR_FULL + 8 * (g0 % NBAR), ph = (g0 / NBAR) & 1;
  uint32_t prev = sb + BAR_DUMMY - 8 * NBAR;
  uint32_t blo = bfirst + Z16 * (N == 192 ? (gl + (t == 5 ? 3 : 0)) & 3 : (gl + 3) % 5);
  uint32_t alo = own ? (uint32_t)DESC_A + s16 + (OFF_X >> 4) : blo + A_OFF;
  uint32_t aoff = own ? alo + 1024 - (blo == blast ? bfirst : blo + Z16) : A_OFF;
  pin_regs<N / 2>(acc);
  if (i > 0) bar_sync(BAR_ORDER + wg, 256);
  if (t == (N == 192 ? 0 : 3) && part != 1) mbar_wait(sb + BAR_XRDY, N == 128);
  mbar_wait(fb, ph);
  if (part != 1) PROF_T(4 + i * 4);
#pragma unroll 1
  while (true) {
    const uint64_t da = (DESC_A & ~0xffffffffull) | alo, db = (DESC_B & ~0xffffffffull) | blo;
    asm volatile("wgmma.fence.sync.aligned;" ::: "memory");
    wgmma_ss<N>(acc[0], da, db);
    wgmma_ss<N>(acc[1], da + 64, db);
    wgmma_ss<N>(acc[0], da + 2, db + 128);
    wgmma_ss<N>(acc[1], da + 66, db + 128);
    asm volatile("wgmma.commit_group.sync.aligned;" ::: "memory");
    asm volatile("wgmma.wait_group.sync.aligned 1;" ::: "memory");
    PROF_S(g0 + jj++);
    if (elect_one()) mbar_arrive(prev + 8 * NBAR);
    prev = fb;
    if (fb == flast) { fb -= 8 * NBAR; ph++; }
    fb += 8;
    if (blo == blast) blo -= RING16;
    blo += Z16;
    alo = blo + aoff;
    aoff = A_OFF;
    run--;
    const bool ready = mbar_test(fb, ph) && run != 0;
    asm volatile("wgmma.fence.sync.aligned;" ::: "memory");
    wgmma_ss<N>(acc[0], da + 4, db + 256);
    wgmma_ss<N>(acc[1], da + 68, db + 256);
    wgmma_ss<N>(acc[0], da + 6, db + 384);
    wgmma_ss<N>(acc[1], da + 70, db + 384);
    asm volatile("wgmma.commit_group.sync.aligned;" ::: "memory");
    if (!ready) {
      if (run == 0) {
        if (rest == 0) break;
        if (rest & 64) {
          bar_arrive(BAR_GO, 256);
          bar_sync(BAR_DONE, 256);
        } else {
          alo = (uint32_t)DESC_A + s16 + (OFF_STG >> 4);
        }
        run = rest & 63;
        rest >>= 7;
      }
      mbar_wait(fb, ph);
    }
  }
  if (i < 13) bar_arrive(BAR_ORDER + (wg ^ 1), 256);
  asm volatile("wgmma.wait_group.sync.aligned 0;" ::: "memory");
  pin_regs<N / 2>(acc);
  if (elect_one()) mbar_arrive(prev + 8 * NBAR);
  PROF_T(5 + i * 4);
  PROF_E(i, 0);
}

#define ACC(q, j, e) acc[(q) & 1][4 * (j) + 2 * ((q) >> 1) + (e)]

__device__ __forceinline__ void write_partial_stats(const Ctx& c, int ln, uint32_t tag) {
  const uint32_t xrow = c.sb + OFF_X + c.w * 4096 + c.lane * 128;
  float s = 0.f, q = 0.f;
#pragma unroll 2
  for (int j = 0; j < 16; j++) {
    uint32_t u[4];
    lds_u4(xrow + (j >> 3) * 16384 + (((j & 7) ^ (c.lane & 7)) << 4), u[0], u[1], u[2], u[3]);
#pragma unroll
    for (int e = 0; e < 4; e++) {
      const float a = bf_lo(u[e]), d = bf_hi(u[e]);
      s += a; q = fmaf(a, a, q);
      s += d; q = fmaf(d, d, q);
    }
  }
  st_msg(g_stats + (ln * 8 + c.n) * SEQ + 128 * c.m + 32 * c.w + c.lane, __float_as_uint(s),
         __float_as_uint(fmaxf(q - s * s * (1.f / 128.f), 0.f)), 0u, tag);
}

__device__ __forceinline__ void finish_row_stats(const Ctx& c, int ln, uint32_t tag) {
  const uint4* src = g_stats + ln * 8 * SEQ + 128 * c.m + 32 * c.w + c.lane;
  uint32_t ps[8], pm[8];
#pragma unroll 1
  for (int it = 0; it < MSG_SPINS; it++) {
    uint32_t bad = 0, u, tg;
#pragma unroll
    for (int k = 0; k < 8; k++) { ld_msg(src + k * SEQ, ps[k], pm[k], u, tg); bad |= tg ^ tag; }
    if (__all_sync(0xffffffffu, bad == 0)) break;
  }
  float s = 0.f, m2 = 0.f;
#pragma unroll
  for (int k = 0; k < 8; k++) s += __uint_as_float(ps[k]);
  const float mean = s * (1.f / DM);
#pragma unroll
  for (int k = 0; k < 8; k++) {
    const float d = __uint_as_float(ps[k]) * (1.f / 128.f) - mean;
    m2 += fmaf(128.f * d, d, __uint_as_float(pm[k]));
  }
  sts_f2(c.sb + OFF_ROW + (32 * c.w + c.lane) * 8, rsqrtf(m2 * (1.f / DM) + 1e-5f), mean);
  __syncwarp();
}

__device__ __forceinline__ void attn_scores(const uint32_t* qa, const uint32_t* qb, const uint32_t* k0, const uint32_t* k1,
                                            const uint32_t* k2, const uint32_t* k3, float (&l)[4], const float4& zero,
                                            bool par, bool early) {
  float s[4][4];
#pragma unroll
  for (int kb = 0; kb < 4; kb++) {
    const uint32_t* kk = kb == 0 ? k0 : kb == 1 ? k1 : kb == 2 ? k2 : k3;
    asm volatile("mma.sync.aligned.m16n8k16.row.col.f32.bf16.bf16.f32 {%0,%1,%2,%3}, {%4,%5,%6,%7}, {%8,%9}, {%10,%11,%12,%13};"
                 : "=f"(s[kb][0]), "=f"(s[kb][1]), "=f"(s[kb][2]), "=f"(s[kb][3])
                 : "r"(qa[0]), "r"(qb[0]), "r"(qa[1]), "r"(qb[1]), "r"(kk[0]), "r"(kk[1]), "f"(zero.x), "f"(zero.y),
                   "f"(zero.z), "f"(zero.w));
  }
#pragma unroll
  for (int kb = 0; kb < 4; kb++) {
    const uint32_t* kk = kb == 0 ? k0 : kb == 1 ? k1 : kb == 2 ? k2 : k3;
    mma16816(s[kb], qa[2], qb[2], qa[3], qb[3], kk[2], kk[3]);
  }
  l[0] = par ? s[1][1] : s[1][0];
  l[1] = early ? (par ? s[0][1] : s[0][0]) : (par ? s[2][1] : s[2][0]);
  l[2] = par ? s[2][3] : s[2][2];
  l[3] = early ? (par ? s[1][3] : s[1][2]) : (par ? s[3][3] : s[3][2]);
}

__device__ __forceinline__ void attn_mix(const float (&l)[4], const float (&sc)[4], const float (&off)[4], const float (&rk)[4],
                                         const uint32_t* v0, const uint32_t* v1, const uint32_t* v2, const uint32_t* v3,
                                         float (&o)[4][4], bool par, bool early) {
  float x[4];
#pragma unroll
  for (int e = 0; e < 4; e++) x[e] = fmaf(l[e], sc[e], off[e]);
  const float ml = quad_max(fmaxf(x[0], x[1])), mh = quad_max(fmaxf(x[2], x[3]));
  x[0] = ex2(x[0] - ml); x[1] = ex2(x[1] - ml);
  x[2] = ex2(x[2] - mh); x[3] = ex2(x[3] - mh);
  const float il = rcp_hw(quad_sum(x[0] + x[1])), ih = rcp_hw(quad_sum(x[2] + x[3]));
  const uint32_t pl = pack_bf16(x[0] * rk[0] * il, x[1] * rk[1] * il), ph = pack_bf16(x[2] * rk[2] * ih, x[3] * rk[3] * ih);
  const uint32_t sel_a = par ? 0x1044u : 0x4410u, sel_b = par ? 0x3244u : 0x4432u;
  const uint32_t sel_e = early ? sel_b : 0x4444u, sel_l = early ? 0x4444u : sel_b;
  const uint32_t pla = __byte_perm(pl, 0, sel_a), pha = __byte_perm(ph, 0, sel_a);
  const uint32_t e_l = __byte_perm(pl, 0, sel_e), e_h = __byte_perm(ph, 0, sel_e);
  const uint32_t l_l = __byte_perm(pl, 0, sel_l), l_h = __byte_perm(ph, 0, sel_l);
#pragma unroll
  for (int jn = 0; jn < 4; jn++) {
    o[jn][0] = o[jn][1] = o[jn][2] = o[jn][3] = 0.f;
    mma16816(o[jn], e_l, 0u, pla, e_h, v0[jn], v1[jn]);
  }
#pragma unroll
  for (int jn = 0; jn < 4; jn++) mma16816(o[jn], l_l, pha, 0u, l_h, v2[jn], v3[jn]);
}

__device__ __forceinline__ void colsum_partial(const Params& p, const Ctx& cx, bool qkv, uint32_t tag) {
  UNPACK_CTX(cx);
  const int groups = qkv ? 48 : 56, cg = (w & 1) * 32 + lane, tid = w * 32 + lane;
  const int ld = qkv ? 3 * DM / 8 : FF / 8;
  float a[8] = {0.f, 0.f, 0.f, 0.f, 0.f, 0.f, 0.f, 0.f};
  if (cg < groups) {
    const uint4* W = reinterpret_cast<const uint4*>(qkv ? p.wqkv_p : p.w1_p) + (64 * m + 32 * (w >> 1)) * ld +
                     (qkv ? (cg >> 4) * (DM / 8) + 16 * n + (cg & 15) : 56 * n + cg);
    asm volatile("prefetch.global.L2 [%0];" ::"l"(W + (16 + (lane & 7)) * ld));
    asm volatile("prefetch.global.L2 [%0];" ::"l"(W + (24 + (lane & 7)) * ld));
    uint4 nx[8];
#pragma unroll
    for (int r = 0; r < 8; r++) nx[r] = __ldcg(W + r * ld);
#pragma unroll 1
    for (int it = 0; it < 4; it++) {
      uint4 v[8];
      W += it < 3 ? 8 * ld : 0;
#pragma unroll
      for (int r = 0; r < 8; r++) { v[r] = nx[r]; nx[r] = __ldcg(W + r * ld); }
#pragma unroll
      for (int r = 0; r < 8; r++) {
        a[0] += bf_lo(v[r].x); a[1] += bf_hi(v[r].x); a[2] += bf_lo(v[r].y); a[3] += bf_hi(v[r].y);
        a[4] += bf_lo(v[r].z); a[5] += bf_hi(v[r].z); a[6] += bf_lo(v[r].w); a[7] += bf_hi(v[r].w);
      }
    }
  }
  const uint32_t part = sb + OFF_STG + 16384 + (w >> 1) * 2048 + cg * 32;
#pragma unroll
  for (int e = 0; e < 4; e++) sts_f2(part + 8 * e, a[2 * e], a[2 * e + 1]);
  bar_sync(BAR_WG + wg, 128);
  uint4* dst = g_csp + (((qkv ? 0 : 8) + n) * 16 + m) * 160;
#pragma unroll 1
  for (int c = tid; c < (qkv ? 128 : 160); c += 128) {
    const uint32_t q = sb + OFF_STG + 16384 + c * 12;
    st_msg(dst + c, __float_as_uint(lds_f(q) + lds_f(q + 2048)), __float_as_uint(lds_f(q + 4) + lds_f(q + 2052)),
           __float_as_uint(lds_f(q + 8) + lds_f(q + 2056)), tag);
  }
}

__device__ __forceinline__ void colsum_gather(const Params& p, const Ctx& cx, bool qkv, uint32_t tag) {
  const int n = cx.n, tid = cx.w * 32 + cx.lane;
  if (!qkv && tid < 112) {
    const uint2 bb = __ldg(reinterpret_cast<const uint2*>(p.b1 + 448 * n) + tid);
    sts_f2(cx.sb + OFF_CSF + tid * 32 + 8, 0.5f * bf_lo(bb.x), 0.5f * bf_hi(bb.x));
    sts_f2(cx.sb + OFF_CSF + tid * 32 + 24, 0.5f * bf_lo(bb.y), 0.5f * bf_hi(bb.y));
  }
#pragma unroll 1
  for (int c0 = cx.w * 32; c0 < (qkv ? 128 : 160); c0 += 128) {
    const int c = c0 + cx.lane;
    const uint4* src = g_csp + ((qkv ? 0 : 8) + n) * 16 * 160 + c;
    float s[3];
#pragma unroll 1
    for (int it = 0; it < MSG_SPINS; it++) {
      uint32_t bad = 0;
      s[0] = s[1] = s[2] = 0.f;
#pragma unroll
      for (int mm = 0; mm < 16; mm++) {
        uint32_t x, y, z, tg;
        ld_msg(src + mm * 160, x, y, z, tg);
        bad |= tg ^ tag;
        s[0] += __uint_as_float(x); s[1] += __uint_as_float(y); s[2] += __uint_as_float(z);
      }
      if (__all_sync(0xffffffffu, bad == 0)) break;
    }
#pragma unroll 1
    for (int e = 0; e < 3; e++) {
      const int col = 3 * c + e;
      const float v = e == 0 ? s[0] : e == 1 ? s[1] : s[2];
      if (col < 448)
        sts_f(cx.sb + (qkv ? OFF_CSQ + ((((col >> 6) & 1) * 3 + (col >> 7)) * 64 + (col & 63)) * 4
                           : OFF_CSF + (col >> 1) * 16 + (col & 1) * 4), v);
    }
  }
}

__device__ __forceinline__ void gelu_epilogue(const Params& p, float (&acc)[2][96], const Ctx& cx, int t) {
  UNPACK_CTX(cx);
  (void)wg;
  float rs[4], rm[4];
#pragma unroll
  for (int q = 0; q < 4; q++) {
    const float2 v = lds_f2(sb + OFF_ROW + (32 * w + 8 * q + (lane >> 2)) * 8);
    rs[q] = 0.5f * v.x;
    rm[q] = -rs[q] * v.y;
  }
  const int col0 = 128 * (t - 3), steps = t == 5 ? 6 : 4;
  const uint32_t stg = sb + OFF_STG + w * 4096;
  uint32_t ctab = sb + OFF_CSF + (col0 / 2 + (lane & 3)) * 16;
  float v[2][16];
#pragma unroll
  for (int r = 0; r < 16; r++) { v[0][r] = acc[0][r]; v[1][r] = acc[1][r]; }
#pragma unroll 1
  for (int it = 0; it < steps; it++) {
    uint32_t hp[4][4];
#pragma unroll
    for (int j = 0; j < 4; j++) {
      const float4 cb = lds_f4(ctab + j * 64);
#pragma unroll
      for (int q = 0; q < 4; q++) {
        float y[2];
        const int k = 4 * j + q - GELU_DEP;
        const float rmq = k >= 0 ? chain(rm[q], hp[k >> 2][k & 3], p.zero) : rm[q];
#pragma unroll
        for (int e = 0; e < 2; e++) {
          const float z = fmaf(v[q & 1][4 * j + 2 * (q >> 1) + e], rs[q], fmaf(rmq, e ? cb.y : cb.x, e ? cb.w : cb.z));
          const float u = z * fmaf(z * z, 8.f * 0.7978845608028654f * 0.044715f, 2.f * 0.7978845608028654f);
          y[e] = fmaf(z, tanh_hw(u), z);
        }
        hp[j][q] = pack_bf16(y[0], y[1]);
      }
    }
    ctab += 256;
    if (!(it & 1)) {
      if (lane == 0) bulk_wait_read();
      __syncwarp();
    }
#pragma unroll
    for (int j = 0; j < 4; j++)
      stsm4(stg + lane * 128 + (((4 * (it & 1) + j) ^ (lane & 7)) << 4), hp[j][0], hp[j][1], hp[j][2], hp[j][3]);
    if (it & 1) {
      fence_async_smem();
      __syncwarp();
      if (lane == 0) {
        tma_st2(&p.h_st, stg, 448 * n + col0 + 32 * (it - 1), 128 * m + 32 * w);
        bulk_commit();
      }
      if (it == steps - 1) break;
    }
    const uint32_t zr = hp[3][3] & p.zero;
#define REFILL(k) _Pragma("unroll") for (int r = 0; r < 32; r++) \
      asm volatile("{\n.reg .b32 t;\nmov.b32 t, %1;\nor.b32 t, t, %2;\nmov.b32 %0, t;\n}" \
                   : "=f"(v[r >> 4][r & 15]) : "f"(acc[r >> 4][16 * k + (r & 15)]), "r"(zr)); break;
    switch (it) {
      case 0: REFILL(1)
      case 1: REFILL(2)
      case 2: REFILL(3)
      case 3: REFILL(4)
      default: REFILL(5)
    }
#undef REFILL
  }
}

__device__ __forceinline__ void attn_epilogue(const Params& p, float (&acc)[2][96], const Ctx& cx, int layer, int t, uint32_t tag) {
  UNPACK_CTX(cx);
  const bool par = (lane >> 2) & 1, early = (lane & 3) > (lane >> 3);
  uint32_t Q[4][8], K[4][8], V[4][8];
  float kr[6], qr[4];
#pragma unroll
  for (int q = 0; q < 4; q++) {
    kr[2 + q] = lds_f(sb + OFF_ROW + (32 * w + 8 * q + 2 * (lane & 3) + par) * 8);
    qr[q] = lds_f(sb + OFF_ROW + (32 * w + 8 * q + (lane >> 2)) * 8) * (0.17677669529663687f * 1.4426950408889634f);
  }
  const int slot = ((layer * 2 + t) * 16 + m) * 8 + n;
  uint4* const exc = reinterpret_cast<uint4*>(__cvta_shared_to_generic(sb + OFF_STG));
#pragma unroll
  for (int qq = 0; qq < 4; qq++) {
    const int q = qq ^ 2;
#pragma unroll
    for (int j = 0; j < 8; j++) {
      K[q][j] = pack_bf16(ACC(q, 8 + j, 0), ACC(q, 8 + j, 1));
      V[q][j] = movtrans(pack_bf16(ACC(q, 16 + j, 0), ACC(q, 16 + j, 1)));
    }
    if (qq == 1) {
      uint4* e = (w < 3 ? exc + w * 512 : g_halo + slot * 512) + lane;
#pragma unroll
      for (int j = 0; j < 8; j++) {
        st_msg(e + j * 32, K[2 + (j >> 2)][2 * (j & 3)], K[2 + (j >> 2)][2 * (j & 3) + 1], __float_as_uint(kr[4]), tag);
        st_msg(e + (8 + j) * 32, V[2][j], V[3][j], __float_as_uint(kr[5]), tag);
      }
    }
  }
#pragma unroll
  for (int q = 0; q < 4; q++)
#pragma unroll
    for (int j = 0; j < 8; j++) Q[q][j] = pack_bf16(ACC(q, j, 0), ACC(q, j, 1));
  const int mn = m * 8 + n; (void)mn;
  PROF_E(7 * layer + t, 1);
  bar_sync(BAR_WG + wg, 128);
  const uint4* src = (w > 0 ? exc + (w - 1) * 512 : m > 0 ? g_halo + (slot - 8) * 512 : exc) + lane;
  uint32_t PK[2][8], PV[2][8], r4, r5;
#pragma unroll 1
  for (int it = 0; it < MSG_SPINS; it++) {
    uint32_t tg, bad = 0;
#pragma unroll
    for (int j = 0; j < 8; j++) {
      ld_msg(src + j * 32, PK[j >> 2][2 * (j & 3)], PK[j >> 2][2 * (j & 3) + 1], r4, tg); bad |= tg ^ tag;
      ld_msg(src + (8 + j) * 32, PV[0][j], PV[1][j], r5, tg); bad |= tg ^ tag;
    }
    if (__all_sync(0xffffffffu, bad == 0)) break;
  }
  kr[0] = __uint_as_float(r4);
  kr[1] = __uint_as_float(r5);
  float rk[2][4], sc[2][4], off[2][4];
#pragma unroll
  for (int g = 0; g < 2; g++) {
    rk[g][0] = kr[2 * g + 1];
    rk[g][1] = early ? kr[2 * g] : kr[2 * g + 2];
    rk[g][2] = kr[2 * g + 2];
    rk[g][3] = early ? kr[2 * g + 1] : kr[2 * g + 3];
#pragma unroll
    for (int e = 0; e < 4; e++) {
      const bool masked = g == 0 && e != 2 && (m | w) == 0 && (e == 0 || early);
      sc[g][e] = masked ? 0.f : rk[g][e] * qr[2 * g + (e >> 1)];
      off[g][e] = masked ? -1e30f : 0.f;
    }
  }
  PROF_E(7 * layer + t, 2);
  bar_sync(BAR_GO, 256);
  PROF_E(7 * layer + t, 3);
  const float4 zero = lds_f4(sb + OFF_ZERO);
  float l[2][2][4], o[2][2][4][4];
#pragma unroll
  for (int h = 0; h < 2; h++) {
    attn_scores(&Q[2][4 * h], &Q[3][4 * h], &K[0][4 * h], &K[1][4 * h], &K[2][4 * h], &K[3][4 * h], l[1][h], zero, par, early);
    attn_scores(&Q[0][4 * h], &Q[1][4 * h], &PK[0][4 * h], &PK[1][4 * h], &K[0][4 * h], &K[1][4 * h], l[0][h], zero, par, early);
  }
#pragma unroll
  for (int h = 0; h < 2; h++) {
    attn_mix(l[1][h], sc[1], off[1], rk[1], &V[0][4 * h], &V[1][4 * h], &V[2][4 * h], &V[3][4 * h], o[1][h], par, early);
    attn_mix(l[0][h], sc[0], off[0], rk[0], &PV[0][4 * h], &PV[1][4 * h], &V[0][4 * h], &V[1][4 * h], o[0][h], par, early);
  }
  const uint32_t stg = sb + OFF_STG + w * 4096;
#pragma unroll
  for (int j = 0; j < 8; j++) {
    const float(&a)[4] = o[0][j >> 2][j & 3];
    const float(&c)[4] = o[1][j >> 2][j & 3];
    stsm4(stg + lane * 128 + ((j ^ (lane & 7)) << 4), pack_bf16(a[0], a[1]), pack_bf16(a[2], a[3]), pack_bf16(c[0], c[1]),
          pack_bf16(c[2], c[3]));
  }
  bar_arrive(BAR_DONE, 256);
  fence_async_smem();
  __syncwarp();
  if (lane == 0) {
    tma_st2(&p.att_st, stg, 128 * n + 64 * t, 128 * m + 32 * w);
    bulk_commit();
  }
}

__device__ __forceinline__ void consumer_tile(const Params& p, uint32_t sb0, int i, int mn) {
  const int layer = i >= 7, t = i - 7 * layer, wg = i & 1;
  const bool resid = t == 2 || t == 6;
  if (i >= 0) {
    float acc[2][96];
    if (resid) {
      const Ctx cx = make_ctx(sb0, mn);
      const uint32_t xrow = cx.sb + OFF_X + cx.w * 4096 + cx.lane * 128;
      const uint32_t sel_lo = 0x1044u | p.zero, sel_hi = 0x3244u | p.zero;
#pragma unroll
      for (int j = 0; j < 16; j++) {
        uint32_t r[4];
        ldsm4(xrow + (j >> 3) * 16384 + (((j & 7) ^ (cx.lane & 7)) << 4), r[0], r[1], r[2], r[3]);
#pragma unroll
        for (int q = 0; q < 4; q++) {
          ACC(q, j, 0) = prmt_f(r[q], sel_lo);
          ACC(q, j, 1) = prmt_f(r[q], sel_hi);
        }
      }
      if (t == 6) {
        const uint32_t* b2 = reinterpret_cast<const uint32_t*>(p.b2 + 128 * cx.n) + (cx.lane & 3);
#pragma unroll
        for (int j = 0; j < 16; j++) {
          const uint32_t bb = __ldg(b2 + 4 * j);
#pragma unroll
          for (int e = 0; e < 2; e++) {
            const int k = 2 * j + e - 1;
            const uint32_t u = k >= 0 ? bb | (__float_as_uint(ACC(3, k >> 1, k & 1)) & p.zero) : bb;
            const float bv = e ? bf_hi(u) : bf_lo(u);
#pragma unroll
            for (int q = 0; q < 4; q++) ACC(q, j, e) += bv;
          }
        }
      }
    } else {
#pragma unroll
      for (int r = 0; r < 64; r++) acc[0][r] = acc[1][r] = 0.f;
    }
#pragma unroll
    for (int r = 64; r < 96; r++) acc[0][r] = acc[1][r] = 0.f;
    const bool split = t == 3 || t == 4 || i == 7 || i == 8;
#pragma unroll 1
    for (int step = split ? 0 : 1;; step++) {
      if (step == 1 && (t == 1 || t == 4)) {
        const Ctx cx = make_ctx(sb0, mn);
        const uint32_t tag = lds_u(cx.sb + OFF_TAG);
        const int ln = (i + 1) >> 2;
        if (i == 1) {
          mbar_wait(sb0 + BAR_XRDY, 0);
          mbar_wait(sb0 + BAR_XRDY + 8, 0);
        }
        write_partial_stats(cx, ln, tag);
        PROF_E(i - 2, 8);
        if (i != 1) bar_sync(BAR_GUARD + wg, 256);
        finish_row_stats(cx, ln, tag);
        PROF_E(i - 2, 10);
        bar_arrive(BAR_GUARD + (wg ^ 1), 256);
      }
      if (step == 2 && !resid) bar_sync(BAR_GUARD + wg, 256);
      if (t + step == 2) {
        const Ctx cx = make_ctx(sb0, mn);
        float nm[4];
#pragma unroll
        for (int q = 0; q < 4; q++) nm[q] = -lds_f(cx.sb + OFF_ROW + (32 * cx.w + 8 * q + (cx.lane >> 2)) * 8 + 4);
        const uint32_t ctab = cx.sb + OFF_CSQ + (t * 192 + 2 * (cx.lane & 3)) * 4;
#pragma unroll
        for (int j = 0; j < 24; j++) {
          const float2 cs = lds_f2(ctab + j * 32);
#pragma unroll
          for (int q = 0; q < 4; q++) {
            const int k = 4 * j + q - 1;
            const float nq = k >= 0 ? chain(nm[q], __float_as_uint(ACC(k & 3, k >> 2, 1)), p.zero) : nm[q];
            ACC(q, j, 0) = fmaf(nq, cs.x, ACC(q, j, 0));
            ACC(q, j, 1) = fmaf(nq, cs.y, ACC(q, j, 1));
          }
        }
      }
      if (step == 2) break;
      if (tile_wide(t)) {
        mainloop<192>(acc, sb0, i, split ? step : 2, mn);
      } else {
        mainloop<128>(acc, sb0, i, split ? step : 2, mn);
        if (resid) break;
      }
    }
    const Ctx cx = make_ctx(sb0, mn);
    if (resid) {
      const uint32_t xrow = cx.sb + OFF_X + cx.w * 4096 + cx.lane * 128;
#pragma unroll
      for (int j = 0; j < 16; j++) {
        stsm4(xrow + (j >> 3) * 16384 + (((j & 7) ^ (cx.lane & 7)) << 4), pack_bf16(ACC(0, j, 0), ACC(0, j, 1)),
              pack_bf16(ACC(1, j, 0), ACC(1, j, 1)), pack_bf16(ACC(2, j, 0), ACC(2, j, 1)), pack_bf16(ACC(3, j, 0), ACC(3, j, 1)));
        if ((j & 7) == 7) {
          fence_async_smem();
          __syncwarp();
          if (elect_one()) mbar_arrive(sb0 + BAR_XRDY + (j & 8));
        }
      }
      PROF_E(i, 4);
      return;
    }
    if (t < 2) attn_epilogue(p, acc, cx, layer, t, lds_u(sb0 + OFF_TAG));
    else gelu_epilogue(p, acc, cx, t);
    PROF_E(i, 4);
    if (cx.lane == 0) {
      bulk_wait_all();
      mbar_arrive(sb0 + BAR_PUB + 8 * (t < 2 ? t : t + 1));
    }
    __syncwarp();
    PROF_E(i, 5);
  }
  if (i <= 1) {
    const Ctx cx = make_ctx(sb0, mn);
    const uint32_t tag = __ldcg(g_epoch + (mn & 127)) + 1;
    if (i <= 0) colsum_partial(p, cx, i < 0, tag);
    PROF_E(i, 7);
    if (i != 0) {
      asm volatile("st.shared.u32 [%0], %1;" ::"r"(sb0 + OFF_TAG), "r"(tag) : "memory");
      colsum_gather(p, cx, i < 0, tag);
      bar_sync(BAR_WG + wg, 128);
    }
    PROF_E(i, 9);
  }
  if (i >= 0 && i < 12) bar_arrive(BAR_GUARD + (wg ^ 1), 256);
}

__global__ void __cluster_dims__(2, 1, 1) __launch_bounds__(384, 1) fused_layers_kernel(const __grid_constant__ Params p) {
  extern __shared__ __align__(1024) uint8_t smem_raw[];
  const uint32_t sb = uniform((uint32_t)__cvta_generic_to_shared(smem_raw));
  const int tid = threadIdx.x, lane = tid & 31, warp = uniform(tid >> 5), wg = warp >> 2, w = warp & 3;

  int mn;
  {
    int id = blockIdx.x;
    if (p.by_smid) asm volatile("mov.u32 %0, %%smid;" : "=r"(id));
    else if (id >= 120) id += 4;
    const int c = id >> 1;
    int g, j;
    if (c < 32) { g = c & 7; j = c >> 3; }
    else if (c < 60) { g = 1 + (c - 32) % 7; j = 4 + (c - 32) / 7; }
    else { g = 0; j = c - 58; }
    mn = ((g >> 2) * 8 + j) * 8 + (g & 3) * 2 + (id & 1);
    if (c == 60 || c == 61) {
      if (tid < 32) {
        const uint32_t tag = __ldcg(g_epoch + NCTA + (id & 3)) + 1;
#pragma unroll 1
        for (int mm = 0; mm < 16; mm++) poll_line(g_flags + mm * 32 + (lane & 7), 32 * tag, 0xffu);
        if (tid == 0) g_epoch[NCTA + (id & 3)] = tag;
      }
      return;
    }
  }
  const int m = mn >> 3, n = mn & 7;
    if (tid == 256) asm volatile("prefetch.tensormap [%0];" ::"l"(&p.wqkv) : "memory");
  if (tid == 288) asm volatile("prefetch.tensormap [%0];" ::"l"(&p.xin) : "memory");
  if (tid == 0) {
    for (int s = 0; s < NBAR; s++) {
      mbar_init(sb + BAR_FULL + 8 * s, 2);
      mbar_init(sb + BAR_EMPTY + 8 * s, 4);
    }
    mbar_init(sb + BAR_XRDY, 4);
    mbar_init(sb + BAR_XRDY + 8, 4);
    for (int e = 0; e < 9; e++) mbar_init(sb + BAR_PUB + 8 * e, 4);
    mbar_init(sb + BAR_DUMMY, 4);
    sts_f2(sb + OFF_ZERO, 0.f, 0.f);
    sts_f2(sb + OFF_ZERO + 8, 0.f, 0.f);
    fence_async_smem();
  }
  __syncthreads();

  if (wg < 2) {
    asm volatile("setmaxnreg.inc.sync.aligned.u32 232;");
#pragma unroll 1
    for (int i = -wg; i < 14; i += 2) {
      consumer_tile(p, sb, i, mn | (warp << 7));
      PROF_T(i < 0 ? 3 : 6 + i * 4);
    }
  } else {
    asm volatile("setmaxnreg.dec.sync.aligned.u32 40;");
    if (w == 0) {
      producer<false>(p, sb, m, n, lane);
    } else if (w == 1) {
      if (elect_one()) {
        for (int h = 0; h < 2; h++) {
          const uint32_t xr = sb + BAR_XRDY + 8 * h;
          mbar_expect_tx(xr, 16384);
          tma_ld2(sb + OFF_X + h * 16384, &p.xin, xr, 128 * n + 64 * h, 128 * m);
          asm volatile("mbarrier.arrive.shared::cta.b64 _, [%0], 3;" ::"r"(xr) : "memory");
        }
      }
      producer<true>(p, sb, m, n, lane);
    } else if (w == 2) {
      if (elect_one()) publisher(p, sb, m, n);
    }
  }
}

typedef CUresult (*EncodeFn)(CUtensorMap*, CUtensorMapDataType, cuuint32_t, void*, const cuuint64_t*, const cuuint64_t*,
                             const cuuint32_t*, const cuuint32_t*, CUtensorMapInterleave, CUtensorMapSwizzle,
                             CUtensorMapL2promotion, CUtensorMapFloatOOBfill);

void make_2d(EncodeFn enc, CUtensorMap* m, const void* ptr, uint64_t cols, uint64_t rows, uint32_t box_rows) {
  cuuint64_t d[2] = {cols, rows}, st[1] = {cols * 2};
  cuuint32_t b[2] = {64, box_rows}, e[2] = {1, 1};
  enc(m, CU_TENSOR_MAP_DATA_TYPE_BFLOAT16, 2, const_cast<void*>(ptr), d, st, b, e, CU_TENSOR_MAP_INTERLEAVE_NONE,
      CU_TENSOR_MAP_SWIZZLE_128B, CU_TENSOR_MAP_L2_PROMOTION_L2_128B, CU_TENSOR_MAP_FLOAT_OOB_FILL_NONE);
}
void make_3d(EncodeFn enc, CUtensorMap* m, const void* ptr, uint64_t d0, uint64_t rows, uint64_t d2, uint64_t row_bytes,
             uint64_t chunk_bytes, uint32_t box_chunks) {
  cuuint64_t d[3] = {d0, rows, d2}, st[2] = {row_bytes, chunk_bytes};
  cuuint32_t b[3] = {64, 64, box_chunks}, e[3] = {1, 1, 1};
  enc(m, CU_TENSOR_MAP_DATA_TYPE_BFLOAT16, 3, const_cast<void*>(ptr), d, st, b, e, CU_TENSOR_MAP_INTERLEAVE_NONE,
      CU_TENSOR_MAP_SWIZZLE_128B, CU_TENSOR_MAP_L2_PROMOTION_L2_128B, CU_TENSOR_MAP_FLOAT_OOB_FILL_NONE);
}

}

extern "C" void kernel_launch(void* const* d_in, const int* in_sizes, int n_in, void* d_out, int out_size) {
  (void)in_sizes; (void)n_in; (void)out_size;
  static EncodeFn enc = nullptr;
  static void *att = nullptr, *hbuf = nullptr;
  static int by_smid = 0;
  if (!enc) {
    void* fn = nullptr;
    cudaDriverEntryPointQueryResult q;
    cudaGetDriverEntryPoint("cuTensorMapEncodeTiled", &fn, cudaEnableDefault, &q);
    enc = (EncodeFn)fn;
    cudaGetSymbolAddress(&att, g_att);
    cudaGetSymbolAddress(&hbuf, g_h);
    cudaFuncSetAttribute(fused_layers_kernel, cudaFuncAttributeMaxDynamicSharedMemorySize, SMEM_BYTES);
    int sms = 0, clusters = 0, dev = 0;
    cudaGetDevice(&dev);
    cudaDeviceGetAttribute(&sms, cudaDevAttrMultiProcessorCount, dev);
    cudaLaunchConfig_t cfg = {};
    cfg.gridDim = dim3(132);
    cfg.blockDim = dim3(384);
    cfg.dynamicSmemBytes = SMEM_BYTES;
    cudaLaunchAttribute at[1];
    at[0].id = cudaLaunchAttributeClusterDimension;
    at[0].val.clusterDim.x = 2; at[0].val.clusterDim.y = 1; at[0].val.clusterDim.z = 1;
    cfg.attrs = at;
    cfg.numAttrs = 1;
    if (cudaOccupancyMaxActiveClusters(&clusters, fused_layers_kernel, &cfg) != cudaSuccess) (void)cudaGetLastError();
    by_smid = sms == 132 && clusters == 66;
  }
  Params p;
  make_2d(enc, &p.xin, d_in[0], DM, SEQ, 128);
  make_2d(enc, &p.out, d_out, DM, SEQ, 128);
  make_2d(enc, &p.att, att, DM, SEQ, 128);
  make_2d(enc, &p.h, hbuf, FF, SEQ, 128);
  make_2d(enc, &p.out_st, d_out, DM, SEQ, 32);
  make_2d(enc, &p.att_st, att, DM, SEQ, 32);
  make_2d(enc, &p.h_st, hbuf, FF, SEQ, 32);
  make_3d(enc, &p.wqkv, d_in[1], DM, DM, 3, 3 * DM * 2, DM * 2, 3);
  make_3d(enc, &p.wo, d_in[2], 64, DM, DM / 64, DM * 2, 128, 2);
  make_3d(enc, &p.w1a, d_in[4], 64, DM, FF / 64, FF * 2, 128, 3);
  make_3d(enc, &p.w1b, d_in[4], 64, DM, FF / 64, FF * 2, 128, 2);
  make_3d(enc, &p.w2, d_in[6], 64, FF, DM / 64, DM * 2, 128, 2);
  p.wqkv_p = (const __nv_bfloat16*)d_in[1];
  p.w1_p = (const __nv_bfloat16*)d_in[4];
  p.b1 = (const __nv_bfloat16*)d_in[5];
  p.b2 = (const __nv_bfloat16*)d_in[7];
  p.by_smid = by_smid;
  p.zero = 0;
  fused_layers_kernel<<<by_smid ? 132 : NCTA, 384, SMEM_BYTES>>>(p);
}
```

```cpp
#include <cuda_runtime.h>
#include <cuda_bf16.h>
#include <cuda.h>
#include <stdint.h>

namespace {

constexpr int SEQ = 2048, DM = 1024, FF = 3584;
constexpr int NCTA = 128;
constexpr int NBAR = 5;

constexpr uint32_t RING_UNITS = 20, UNIT = 8192;
constexpr uint32_t OFF_X   = RING_UNITS * UNIT;
constexpr uint32_t OFF_STG = OFF_X + 32768;
constexpr uint32_t OFF_HLP = OFF_STG + 24576;
constexpr uint32_t OFF_CSQ = OFF_HLP + 4096;
constexpr uint32_t OFF_CSF = OFF_CSQ + 2048;
constexpr uint32_t OFF_ROW = OFF_CSF + 3584;
constexpr uint32_t OFF_BAR = OFF_ROW + 1024;
constexpr uint32_t SMEM_BYTES = OFF_BAR + 256;
constexpr uint32_t BAR_FULL = OFF_BAR, BAR_EMPTY = OFF_BAR + 8 * NBAR;
constexpr uint32_t BAR_XRDY = OFF_BAR + 80;
constexpr uint32_t BAR_DUMMY = OFF_BAR + 96, OFF_TAG = OFF_BAR + 104, OFF_ZERO = OFF_BAR + 112;
constexpr uint32_t BAR_PUB = OFF_BAR + 128;
constexpr uint32_t BAR_CSLD = OFF_BAR + 200;
constexpr uint32_t BAR_CSOK = OFF_BAR + 216;

constexpr uint64_t DESC_A = (1ull << 62) | ((uint64_t)(2048 >> 4) << 32) | (1ull << 16);
constexpr uint64_t DESC_B = (1ull << 62) | ((uint64_t)(1024 >> 4) << 32) | ((uint64_t)(8192 >> 4) << 16);

constexpr int BAR_ORDER = 1, BAR_GUARD = 3, BAR_WG = 5, BAR_GO = 7, BAR_DONE = 8, BAR_HLP = 9;
#define GELU_DEP 3
#define WIN1 6
#define WIN2 4

struct Params {
  CUtensorMap xin, out, att, h, wqkv, wo, w1a, w1b, w2, out_st, att_st, h_st, w1c;
  const __nv_bfloat16 *x_p, *wqkv_p, *b1, *b2;
  int by_smid;
  uint32_t zero;
};

__device__ __nv_bfloat16 g_att[SEQ * DM];
__device__ __nv_bfloat16 g_h[SEQ * FF];
__device__ uint4 g_stats[4 * 8 * SEQ];
__device__ uint4 g_halo[2 * 2 * 16 * 8 * 512];
__device__ uint4 g_csp[2 * 8 * 17 * 224];
__device__ uint32_t g_flags[16 * 32];
__device__ uint32_t g_epoch[NCTA + 4];
#define PROF_T(idx)
#define PROF_S(g)
#define PROF_E(i, k)

__device__ __forceinline__ void mbar_init(uint32_t bar, int cnt) {
  asm volatile("mbarrier.init.shared::cta.b64 [%0], %1;" ::"r"(bar), "r"(cnt));
}
__device__ __forceinline__ void mbar_expect_tx(uint32_t bar, uint32_t bytes) {
  asm volatile("mbarrier.arrive.expect_tx.shared::cta.b64 _, [%0], %1;" ::"r"(bar), "r"(bytes) : "memory");
}
__device__ __forceinline__ void mbar_arrive(uint32_t bar) {
  asm volatile("mbarrier.arrive.shared::cta.b64 _, [%0];" ::"r"(bar) : "memory");
}
__device__ __forceinline__ bool mbar_test(uint32_t bar, uint32_t parity) {
  uint32_t ok;
  asm volatile("{\n.reg .pred p;\nmbarrier.test_wait.parity.shared::cta.b64 p, [%1], %2;\nselp.u32 %0, 1, 0, p;\n}"
               : "=r"(ok) : "r"(bar), "r"(parity) : "memory");
  return ok;
}
__device__ __forceinline__ void mbar_wait(uint32_t bar, uint32_t parity) {
  asm volatile(
      "{\n.reg .pred p;\n.reg .u32 it;\nmov.u32 it, 0;\n"
      "WAIT_LOOP:\n"
      "mbarrier.try_wait.parity.shared::cta.b64 p, [%0], %1;\n"
      "@p bra WAIT_DONE;\n"
      "add.u32 it, it, 1;\n"
      "setp.lt.u32 p, it, 0x400000;\n"
      "@p bra WAIT_LOOP;\n"
      "trap;\n"
      "WAIT_DONE:\n}"
      ::"r"(bar), "r"(parity) : "memory");
}
__device__ __forceinline__ void bar_sync(int id, int n) { asm volatile("bar.sync %0, %1;" ::"r"(id), "r"(n) : "memory"); }
__device__ __forceinline__ void bar_arrive(int id, int n) { asm volatile("bar.arrive %0, %1;" ::"r"(id), "r"(n) : "memory"); }
__device__ __forceinline__ void tma_ld2(uint32_t dst, const CUtensorMap* m, uint32_t bar, int c0, int c1) {
  asm volatile("cp.async.bulk.tensor.2d.shared::cluster.global.mbarrier::complete_tx::bytes [%0], [%1, {%3, %4}], [%2];"
               ::"r"(dst), "l"(m), "r"(bar), "r"(c0), "r"(c1) : "memory");
}
__device__ __forceinline__ void tma_ld3(uint32_t dst, const CUtensorMap* m, uint32_t bar, int c0, int c1, int c2) {
  asm volatile("cp.async.bulk.tensor.3d.shared::cluster.global.mbarrier::complete_tx::bytes [%0], [%1, {%3, %4, %5}], [%2];"
               ::"r"(dst), "l"(m), "r"(bar), "r"(c0), "r"(c1), "r"(c2) : "memory");
}
__device__ __forceinline__ void tma_pf3(const CUtensorMap* m, int c0, int c1, int c2) {
  asm volatile("cp.async.bulk.prefetch.tensor.3d.L2.global [%0, {%1, %2, %3}];" ::"l"(m), "r"(c0), "r"(c1), "r"(c2) : "memory");
}
__device__ __forceinline__ void tma_st2(const CUtensorMap* m, uint32_t src, int c0, int c1) {
  asm volatile("cp.async.bulk.tensor.2d.global.shared::cta.bulk_group [%0, {%2, %3}], [%1];"
               ::"l"(m), "r"(src), "r"(c0), "r"(c1) : "memory");
}
__device__ __forceinline__ void bulk_commit() { asm volatile("cp.async.bulk.commit_group;" ::: "memory"); }
__device__ __forceinline__ void bulk_wait_read() { asm volatile("cp.async.bulk.wait_group.read 0;" ::: "memory"); }
__device__ __forceinline__ void bulk_wait_all() { asm volatile("cp.async.bulk.wait_group 0;" ::: "memory"); }
__device__ __forceinline__ void fence_async_smem() { asm volatile("fence.proxy.async.shared::cta;" ::: "memory"); }
__device__ __forceinline__ void fence_async_global() { asm volatile("fence.proxy.async.global;" ::: "memory"); }
__device__ __forceinline__ void st_relaxed(uint32_t* p, uint32_t v) {
  asm volatile("st.relaxed.gpu.global.u32 [%0], %1;" ::"l"(p), "r"(v) : "memory");
}
__device__ __forceinline__ void st_msg(uint4* p, uint32_t a, uint32_t b, uint32_t c, uint32_t tag) {
  asm volatile("{\n.reg .b128 v;\nmov.b128 v, {%1, %2, %3, %4};\nst.relaxed.gpu.b128 [%0], v;\n}"
               ::"l"(p), "r"(a), "r"(b), "r"(c), "r"(tag) : "memory");
}
__device__ __forceinline__ void ld_msg(const uint4* p, uint32_t& a, uint32_t& b, uint32_t& c, uint32_t& tag) {
  asm volatile("{\n.reg .b128 v;\nld.relaxed.gpu.b128 v, [%4];\nmov.b128 {%0, %1, %2, %3}, v;\n}"
               : "=r"(a), "=r"(b), "=r"(c), "=r"(tag) : "l"(p) : "memory");
}
__device__ __forceinline__ bool elect_one() {
  uint32_t ok;
  asm volatile("{\n.reg .pred p;\nelect.sync _|p, 0xffffffff;\nselp.u32 %0, 1, 0, p;\n}" : "=r"(ok));
  return ok;
}
__device__ __forceinline__ int uniform(int v) { return __shfl_sync(0xffffffffu, v, 0); }
__device__ __forceinline__ uint32_t pack_bf16(float lo, float hi) {
  uint32_t r;
  asm("cvt.rn.bf16x2.f32 %0, %1, %2;" : "=r"(r) : "f"(hi), "f"(lo));
  return r;
}
__device__ __forceinline__ float prmt_f(uint32_t a, uint32_t sel) {
  float r;
  asm("{\n.reg .b32 t;\nprmt.b32 t, %1, 0, %2;\nmov.b32 %0, t;\n}" : "=f"(r) : "r"(a), "r"(sel));
  return r;
}
__device__ __forceinline__ float bf_lo(uint32_t v) { return __uint_as_float(v << 16); }
__device__ __forceinline__ float bf_hi(uint32_t v) { return __uint_as_float(v & 0xffff0000u); }
__device__ __forceinline__ void stsm4(uint32_t addr, uint32_t r0, uint32_t r1, uint32_t r2, uint32_t r3) {
  asm volatile("stmatrix.sync.aligned.m8n8.x4.shared.b16 [%0], {%1, %2, %3, %4};"
               ::"r"(addr), "r"(r0), "r"(r1), "r"(r2), "r"(r3) : "memory");
}
__device__ __forceinline__ void ldsm4(uint32_t addr, uint32_t& r0, uint32_t& r1, uint32_t& r2, uint32_t& r3) {
  asm volatile("ldmatrix.sync.aligned.m8n8.x4.shared.b16 {%0, %1, %2, %3}, [%4];"
               : "=r"(r0), "=r"(r1), "=r"(r2), "=r"(r3) : "r"(addr) : "memory");
}
__device__ __forceinline__ uint32_t movtrans(uint32_t a) {
  uint32_t d;
  asm volatile("movmatrix.sync.aligned.m8n8.trans.b16 %0, %1;" : "=r"(d) : "r"(a));
  return d;
}
__device__ __forceinline__ void mma16816(float (&c)[4], uint32_t a0, uint32_t a1, uint32_t a2, uint32_t a3, uint32_t b0, uint32_t b1) {
  asm volatile("mma.sync.aligned.m16n8k16.row.col.f32.bf16.bf16.f32 {%0,%1,%2,%3}, {%4,%5,%6,%7}, {%8,%9}, {%0,%1,%2,%3};"
               : "+f"(c[0]), "+f"(c[1]), "+f"(c[2]), "+f"(c[3])
               : "r"(a0), "r"(a1), "r"(a2), "r"(a3), "r"(b0), "r"(b1));
}
__device__ __forceinline__ float2 lds_f2(uint32_t a) {
  float2 v;
  asm volatile("ld.shared.v2.f32 {%0, %1}, [%2];" : "=f"(v.x), "=f"(v.y) : "r"(a) : "memory");
  return v;
}
__device__ __forceinline__ float4 lds_f4(uint32_t a) {
  float4 v;
  asm volatile("ld.shared.v4.f32 {%0, %1, %2, %3}, [%4];" : "=f"(v.x), "=f"(v.y), "=f"(v.z), "=f"(v.w) : "r"(a) : "memory");
  return v;
}
__device__ __forceinline__ float lds_f(uint32_t a) {
  float v;
  asm volatile("ld.shared.f32 %0, [%1];" : "=f"(v) : "r"(a) : "memory");
  return v;
}
__device__ __forceinline__ void sts_f(uint32_t a, float v) { asm volatile("st.shared.f32 [%0], %1;" ::"r"(a), "f"(v) : "memory"); }
__device__ __forceinline__ uint32_t lds_u(uint32_t a) {
  uint32_t v;
  asm volatile("ld.shared.u32 %0, [%1];" : "=r"(v) : "r"(a) : "memory");
  return v;
}
__device__ __forceinline__ void sts_f2(uint32_t a, float x, float y) {
  asm volatile("st.shared.v2.f32 [%0], {%1, %2};" ::"r"(a), "f"(x), "f"(y) : "memory");
}
__device__ __forceinline__ void lds_u4(uint32_t a, uint32_t& x, uint32_t& y, uint32_t& z, uint32_t& w) {
  asm volatile("ld.shared.v4.u32 {%0, %1, %2, %3}, [%4];" : "=r"(x), "=r"(y), "=r"(z), "=r"(w) : "r"(a) : "memory");
}
__device__ __forceinline__ float ex2(float x) {
  float y;
  asm("ex2.approx.ftz.f32 %0, %1;" : "=f"(y) : "f"(x));
  return y;
}
__device__ __forceinline__ float rcp_hw(float x) {
  float y;
  asm("rcp.approx.ftz.f32 %0, %1;" : "=f"(y) : "f"(x));
  return y;
}
__device__ __forceinline__ float tanh_hw(float x) {
  float y;
  asm("tanh.approx.f32 %0, %1;" : "=f"(y) : "f"(x));
  return y;
}
__device__ __forceinline__ float quad_sum(float v) {
  v += __shfl_xor_sync(0xffffffffu, v, 1);
  return v + __shfl_xor_sync(0xffffffffu, v, 2);
}
__device__ __forceinline__ float quad_max(float v) {
  v = fmaxf(v, __shfl_xor_sync(0xffffffffu, v, 1));
  return fmaxf(v, __shfl_xor_sync(0xffffffffu, v, 2));
}

template <int N> __device__ __forceinline__ void wgmma_ss(float (&d)[96], uint64_t da, uint64_t db);
template <> __device__ __forceinline__ void wgmma_ss<128>(float (&d)[96], uint64_t da, uint64_t db) {
  asm volatile(
      "wgmma.mma_async.sync.aligned.m64n128k16.f32.bf16.bf16 {%0, %1, %2, %3, %4, %5, %6, %7, %8, %9, %10, %11, %12, %13, %14, %15, %16, %17, %18, %19, %20, %21, %22, %23, %24, %25, %26, %27, %28, %29, %30, %31, %32, %33, %34, %35, %36, %37, %38, %39, %40, %41, %42, %43, %44, %45, %46, %47, %48, %49, %50, %51, %52, %53, %54, %55, %56, %57, %58, %59, %60, %61, %62, %63}, %64, %65, 1, 1, 1, 0, 1;"
      : "+f"(d[0]), "+f"(d[1]), "+f"(d[2]), "+f"(d[3]), "+f"(d[4]), "+f"(d[5]), "+f"(d[6]), "+f"(d[7]), "+f"(d[8]), "+f"(d[9]), "+f"(d[10]), "+f"(d[11]), "+f"(d[12]), "+f"(d[13]), "+f"(d[14]), "+f"(d[15]), "+f"(d[16]), "+f"(d[17]), "+f"(d[18]), "+f"(d[19]), "+f"(d[20]), "+f"(d[21]), "+f"(d[22]), "+f"(d[23]), "+f"(d[24]), "+f"(d[25]), "+f"(d[26]), "+f"(d[27]), "+f"(d[28]), "+f"(d[29]), "+f"(d[30]), "+f"(d[31]), "+f"(d[32]), "+f"(d[33]), "+f"(d[34]), "+f"(d[35]), "+f"(d[36]), "+f"(d[37]), "+f"(d[38]), "+f"(d[39]), "+f"(d[40]), "+f"(d[41]), "+f"(d[42]), "+f"(d[43]), "+f"(d[44]), "+f"(d[45]), "+f"(d[46]), "+f"(d[47]), "+f"(d[48]), "+f"(d[49]), "+f"(d[50]), "+f"(d[51]), "+f"(d[52]), "+f"(d[53]), "+f"(d[54]), "+f"(d[55]), "+f"(d[56]), "+f"(d[57]), "+f"(d[58]), "+f"(d[59]), "+f"(d[60]), "+f"(d[61]), "+f"(d[62]), "+f"(d[63])
      : "l"(da), "l"(db));
}

template <> __device__ __forceinline__ void wgmma_ss<192>(float (&d)[96], uint64_t da, uint64_t db) {
  asm volatile(
      "wgmma.mma_async.sync.aligned.m64n192k16.f32.bf16.bf16 {%0, %1, %2, %3, %4, %5, %6, %7, %8, %9, %10, %11, %12, %13, %14, %15, %16, %17, %18, %19, %20, %21, %22, %23, %24, %25, %26, %27, %28, %29, %30, %31, %32, %33, %34, %35, %36, %37, %38, %39, %40, %41, %42, %43, %44, %45, %46, %47, %48, %49, %50, %51, %52, %53, %54, %55, %56, %57, %58, %59, %60, %61, %62, %63, %64, %65, %66, %67, %68, %69, %70, %71, %72, %73, %74, %75, %76, %77, %78, %79, %80, %81, %82, %83, %84, %85, %86, %87, %88, %89, %90, %91, %92, %93, %94, %95}, %96, %97, 1, 1, 1, 0, 1;"
      : "+f"(d[0]), "+f"(d[1]), "+f"(d[2]), "+f"(d[3]), "+f"(d[4]), "+f"(d[5]), "+f"(d[6]), "+f"(d[7]), "+f"(d[8]), "+f"(d[9]), "+f"(d[10]), "+f"(d[11]), "+f"(d[12]), "+f"(d[13]), "+f"(d[14]), "+f"(d[15]), "+f"(d[16]), "+f"(d[17]), "+f"(d[18]), "+f"(d[19]), "+f"(d[20]), "+f"(d[21]), "+f"(d[22]), "+f"(d[23]), "+f"(d[24]), "+f"(d[25]), "+f"(d[26]), "+f"(d[27]), "+f"(d[28]), "+f"(d[29]), "+f"(d[30]), "+f"(d[31]), "+f"(d[32]), "+f"(d[33]), "+f"(d[34]), "+f"(d[35]), "+f"(d[36]), "+f"(d[37]), "+f"(d[38]), "+f"(d[39]), "+f"(d[40]), "+f"(d[41]), "+f"(d[42]), "+f"(d[43]), "+f"(d[44]), "+f"(d[45]), "+f"(d[46]), "+f"(d[47]), "+f"(d[48]), "+f"(d[49]), "+f"(d[50]), "+f"(d[51]), "+f"(d[52]), "+f"(d[53]), "+f"(d[54]), "+f"(d[55]), "+f"(d[56]), "+f"(d[57]), "+f"(d[58]), "+f"(d[59]), "+f"(d[60]), "+f"(d[61]), "+f"(d[62]), "+f"(d[63]), "+f"(d[64]), "+f"(d[65]), "+f"(d[66]), "+f"(d[67]), "+f"(d[68]), "+f"(d[69]), "+f"(d[70]), "+f"(d[71]), "+f"(d[72]), "+f"(d[73]), "+f"(d[74]), "+f"(d[75]), "+f"(d[76]), "+f"(d[77]), "+f"(d[78]), "+f"(d[79]), "+f"(d[80]), "+f"(d[81]), "+f"(d[82]), "+f"(d[83]), "+f"(d[84]), "+f"(d[85]), "+f"(d[86]), "+f"(d[87]), "+f"(d[88]), "+f"(d[89]), "+f"(d[90]), "+f"(d[91]), "+f"(d[92]), "+f"(d[93]), "+f"(d[94]), "+f"(d[95])
      : "l"(da), "l"(db));
}

template <int R>
__device__ __forceinline__ void pin_regs(float (&a)[2][96]) {
#pragma unroll
  for (int m = 0; m < 2; m++)
#pragma unroll
    for (int i = 0; i < R; i++) asm volatile("" : "+f"(a[m][i])::"memory");
}

struct Ctx {
  uint32_t sb;
  int m, n, wg, w, lane;
};
__device__ __forceinline__ Ctx make_ctx(uint32_t sb, int id) {
  int lane;
  asm volatile("mov.u32 %0, %%laneid;" : "=r"(lane));
  asm volatile("" : "+r"(id), "+r"(sb));
  return Ctx{sb, (id >> 3) & 15, id & 7, id >> 9, (id >> 7) & 3, lane};
}
#define UNPACK_CTX(c) const uint32_t sb = c.sb; const int m = c.m, n = c.n, wg = c.wg, w = c.w, lane = c.lane

__device__ __forceinline__ uint32_t poll_line(const uint32_t* word, uint32_t target, uint32_t need) {
  uint32_t v;
  asm volatile(
      "{\n.reg .pred p;\n.reg .u32 it, m;\n.reg .s32 d;\nmov.u32 it, 0;\n"
      "POLL_LOOP:\n"
      "ld.relaxed.gpu.global.u32 %0, [%1];\n"
      "sub.s32 d, %0, %2;\n"
      "setp.ge.s32 p, d, 0;\n"
      "vote.sync.ballot.b32 m, p, 0xffffffff;\n"
      "and.b32 m, m, %3;\n"
      "setp.eq.u32 p, m, %3;\n"
      "@p bra.uni POLL_DONE;\n"
      "add.u32 it, it, 1;\n"
      "setp.lt.u32 p, it, 0x400000;\n"
      "@p bra.uni POLL_LOOP;\n"
      "trap;\n"
      "POLL_DONE:\n}"
      : "=&r"(v) : "l"(word), "r"(target), "r"(need) : "memory");
  return v;
}
__device__ __forceinline__ uint32_t ld_relaxed(const uint32_t* p) {
  uint32_t v;
  asm volatile("ld.relaxed.gpu.global.u32 %0, [%1];" : "=r"(v) : "l"(p) : "memory");
  return v;
}
__device__ __forceinline__ float chain(float x, uint32_t on, uint32_t zero) {
  return __uint_as_float(__float_as_uint(x) | (on & zero));
}
constexpr int MSG_SPINS = 1 << 20;

constexpr int STAGES_PER_LAYER = 152;
__device__ __forceinline__ int nib(uint64_t v, int i) { return (int)(v >> (4 * i)) & 15; }
__device__ __forceinline__ bool tile_wide(int t) { return (0x23 >> t) & 1; }
constexpr uint64_t ORDER_PLAIN = 0xFEDCBA9876543210ull, ORDER_X = 0xFEDCBA9765432180ull;

__device__ __forceinline__ void weight_coords(const Params& p, int t, int n, const CUtensorMap*& map, int& c0, int& c2) {
  map = &p.wqkv + nib(0x4233100ull, t);
  c0 = t < 2 ? 128 * n + 64 * t : 0;
  c2 = t < 2 ? 0 : (t == 2 || t == 6) ? 2 * n : 7 * n + 2 * t - 6;
}

template <bool IS_A>
__device__ __forceinline__ void producer(const Params& p, uint32_t sb, int m, int n, int lane) {
  int inflight = 0, rph = 0, min_seen = 0, cur = 0;
  uint32_t b8 = 0, rb8 = 0, pos = 0, tag32 = 0, seen = 0;
  const uint32_t* word = g_flags + m * 32 + (lane & 7);
#pragma unroll 1
  for (int sg = 0; sg < 34; sg++) {
    const int layer = sg >= 17, s = sg == 1 ? 2 : sg == 2 ? 1 : sg - 17 * layer;
    const int t = s < 10 ? nib(0x5434321010ull, s) : 6, kind = s < 10 ? nib(0x2110021100ull, s) : 3;
    const bool wide = tile_wide(t), xtype = t != 2 && t != 6;
    const uint32_t bbytes = wide ? 3 * UNIT : 2 * UNIT;
    const int mul = t == 6 ? 7 : 2, add = t == 6 ? s - 10 : 0, count = 2 * nib(0x4871ull, kind);
    uint64_t order = (xtype ? ORDER_X : ORDER_PLAIN) >> (kind == 1 ? 8 : 0);
    uint32_t lags = s == 9 ? 0x55555545u : wide ? 0x55555555u : (s == 4 || s == 10) ? 0xAAAAAA55u : 0xAAAAAAAAu;
    uint32_t own = t == 2 ? 0x100u : xtype && kind != 1 ? 3u : 0u;
    if (s == 9 || s == 10) pos = (s + 6) * UNIT;
    const CUtensorMap* map;
    int c0 = 0, c2 = 0, ev = 0;
    if (IS_A) {
      map = &p.xin + (t == 2 ? 2 : t == 6 ? 3 : sg >= 4);
      ev = 9 * layer + (t < 2 ? -1 : t == 2 ? 1 : t < 6 ? 3 : nib(0x7776655ull, add));
      if (sg == 3) seen = tag32 = (__ldcg(g_epoch + m * 8 + n) + 1) << 5;
      if (sg >= 4 && (s >= 9 || s == 3 || s == 4)) {
        cur = max(cur, (int)(seen - tag32));
        min_seen = __reduce_min_sync(0xffffffffu, cur);
        asm volatile("fence.acquire.gpu;" ::: "memory");
        fence_async_global();
        seen = ld_relaxed(word);
      }
    } else {
      const int pf = s == 3 ? 2 : s == 4 ? 3 : s == 7 ? 5 : s == 8 ? 6 : sg == 12 ? 0 : -1;
#pragma unroll 1
      for (int tt = pf; tt >= 0 && tt <= pf + (pf == 0 || pf == 3); tt++) {
        weight_coords(p, tt, n, map, c0, c2);
#pragma unroll 1
        for (int kb = m; kb < (tt == 6 ? 56 : 16); kb += 16)
          if (elect_one()) tma_pf3(map, c0, 64 * kb, c2);
      }
      weight_coords(p, t, n, map, c0, c2);
    }
#pragma unroll 1
    for (int k = 0; k < count; k++) {
      const int q = order & 7, hi = (order >> 3) & 1, lag = 2 + (lags & 3);
      const bool local = own & 1;
      order >>= 4;
      lags >>= 2;
      own >>= 1;
      const int src = (((n & 6) + q) & 7) ^ (q < 2 ? n & 1 : 0);
      const int kc = 64 * (mul * src + add + hi);
      if (IS_A && !local && min_seen < ev + hi && __shfl_sync(0xffffffffu, cur, src) < ev + hi) {
        cur = (int)(poll_line(word, tag32 + ev + hi, 1u << src) - tag32);
        min_seen = __reduce_min_sync(0xffffffffu, cur);
        asm volatile("fence.acquire.gpu;" ::: "memory");
        fence_async_global();
      }
#pragma unroll 1
      for (; inflight > lag; inflight--) {
        mbar_wait(sb + BAR_EMPTY + rb8, rph);
        rb8 += 8;
        if (rb8 == 8 * NBAR) { rb8 = 0; rph ^= 1; }
      }
      const uint32_t fb = sb + BAR_FULL + b8;
      if (!IS_A) {
        if (elect_one()) {
          mbar_expect_tx(fb, bbytes);
          tma_ld3(sb + pos, map, fb, c0, kc, c2);
        }
      } else if (!local) {
        if (elect_one()) {
          mbar_expect_tx(fb, 16384);
          tma_ld2(sb + pos + bbytes, map, fb, kc, 128 * m);
        }
      } else {
        if (t == 2) mbar_wait(sb + BAR_PUB + 8, layer);
        else if (k == 1 && (s == 0 || s == 5)) mbar_wait(sb + BAR_XRDY + 8, s == 5);
        if (elect_one()) mbar_arrive(fb);
      }
      inflight++;
      b8 += 8;
      if (b8 == 8 * NBAR) b8 = 0;
      pos += bbytes + 2 * UNIT;
      if (pos >= RING_UNITS * UNIT) pos -= RING_UNITS * UNIT;
    }
  }
}

__device__ __forceinline__ void publisher(const Params& p, uint32_t sb, int m, int n) {
  const uint32_t tag = __ldcg(g_epoch + m * 8 + n) + 1;
  uint32_t* word = g_flags + m * 32 + n;
  const int mn = m * 8 + n; (void)mn;
  st_relaxed(word, 32 * tag);
#pragma unroll 1
  for (int c = 0; c < 18; c++) {
    const int e = c >= 9 ? c - 9 : c;
    if ((0x18C >> e) & 1) {
      const int half = (0x108 >> e) & 1;
      mbar_wait(sb + BAR_XRDY + 8 * half, e < 4);
#pragma unroll
      for (int w = 0; w < 4; w++) tma_st2(&p.out_st, sb + OFF_X + half * 16384 + w * 4096, 128 * n + 64 * half, 128 * m + 32 * w);
      bulk_commit();
      if (c >= 16) continue;
      bulk_wait_all();
      PROF_E(7 * (c >= 9) + (e < 4 ? 2 : 6), 11 + 2 * half);
    } else {
      mbar_wait(sb + BAR_PUB + 8 * e, c >= 9);
    }
    asm volatile("fence.release.gpu;" ::: "memory");
    st_relaxed(word, 32 * tag + c + 1);
    PROF_E(7 * (c >= 9) + nib(0x665432210ull, e), (0x108 >> e) & 1 ? 14 : 12);
  }
  g_epoch[m * 8 + n] = tag;
  bulk_wait_read();
}

__device__ __forceinline__ void sum_rows(uint32_t buf, int iters, float (&a)[8], int lane) {
  uint32_t addr = buf + (lane >> 3) * 128 + (((lane & 7) ^ (lane >> 3)) << 4);
#pragma unroll 1
  for (int it = 0; it < iters; it++) {
    uint32_t u[2][4];
    lds_u4(addr, u[0][0], u[0][1], u[0][2], u[0][3]);
    lds_u4((addr ^ 64) + 512, u[1][0], u[1][1], u[1][2], u[1][3]);
    addr += 1024;
#pragma unroll
    for (int e = 0; e < 8; e++) { a[2 * (e & 3)] += bf_lo(u[e >> 2][e & 3]); a[2 * (e & 3) + 1] += bf_hi(u[e >> 2][e & 3]); }
  }
}
__device__ __forceinline__ void publish_sums(const float (&a)[8], uint4* dst, int lane, uint32_t tag) {
  const bool u8 = lane & 8, u16 = lane & 16;
  float h4[4], h2[2];
#pragma unroll
  for (int e = 0; e < 4; e++) h4[e] = (u8 ? a[4 + e] : a[e]) + __shfl_xor_sync(0xffffffffu, u8 ? a[e] : a[4 + e], 8);
#pragma unroll
  for (int e = 0; e < 2; e++) h2[e] = (u16 ? h4[2 + e] : h4[e]) + __shfl_xor_sync(0xffffffffu, u16 ? h4[e] : h4[2 + e], 16);
  st_msg(dst + (lane & 7) * 4 + (u8 ? 2 : 0) + (u16 ? 1 : 0), __float_as_uint(h2[0]), __float_as_uint(h2[1]), 0u, tag);
}

__device__ __forceinline__ void colsum_helper(const Params& p, uint32_t sb, int m, int n, int lane) {
  const uint32_t tag = __ldcg(g_epoch + m * 8 + n) + 1;
  const int mn = m * 8 + n; (void)mn;
#pragma unroll 1
  for (int mat = 0; mat < 2; mat++) {
    uint4* base = g_csp + (mat * 8 + n) * 17 * 224;
    const int per = 12 + 2 * mat;
    if (mat == 0) {
#pragma unroll 1
      for (int k = lane; k < 288; k += 32) {
        const uint32_t bb = __ldg(reinterpret_cast<const uint32_t*>(k < 224 ? p.b1 + 448 * n : p.b2 + 128 * n - 448) + k);
        const float sc = k < 224 ? 0.5f : 1.f;
        sts_f2(sb + (k < 224 ? OFF_CSF + k * 16 + 8 : OFF_CSQ + 1536 + (k - 224) * 8), sc * bf_lo(bb), sc * bf_hi(bb));
      }
      bar_sync(BAR_HLP, 160);
    } else {
#pragma unroll 1
      for (int c = 0; c < 7; c++) {
        float a[8] = {0.f, 0.f, 0.f, 0.f, 0.f, 0.f, 0.f, 0.f};
#pragma unroll 1
        for (int h = 0; h < 2; h++) {
          if (elect_one()) {
            mbar_expect_tx(sb + BAR_CSLD + 8, 4096);
            tma_ld2(sb + OFF_HLP, &p.w1c, sb + BAR_CSLD + 8, 448 * n + 64 * c, 64 * m + 32 * h);
          }
          mbar_wait(sb + BAR_CSLD + 8, h);
          sum_rows(sb + OFF_HLP, 4, a, lane);
          __syncwarp();
        }
        publish_sums(a, base + m * 224 + c * 32, lane, tag);
      }
    }
    PROF_E(-1, 1 + 4 * mat);
    const int idx = per * m + min(lane & 15, per - 1);
    float s0 = 0.f, s1 = 0.f;
#pragma unroll 1
    for (int g = 0; g < 2; g++) {
      uint32_t x[4], y[4];
#pragma unroll 1
      for (int it = 0; it < MSG_SPINS; it++) {
        uint32_t bad = 0, z, tg;
#pragma unroll
        for (int k = 0; k < 4; k++) { ld_msg(base + ((lane >> 4) * 8 + g * 4 + k) * 224 + idx, x[k], y[k], z, tg); bad |= tg ^ tag; }
        if (__all_sync(0xffffffffu, bad == 0)) break;
      }
#pragma unroll
      for (int k = 0; k < 4; k++) { s0 += __uint_as_float(x[k]); s1 += __uint_as_float(y[k]); }
    }
    s0 += __shfl_xor_sync(0xffffffffu, s0, 16);
    s1 += __shfl_xor_sync(0xffffffffu, s1, 16);
    if (lane < per) st_msg(base + 16 * 224 + idx, __float_as_uint(s0), __float_as_uint(s1), 0u, tag);
    PROF_E(-1, 2);
#pragma unroll 1
    for (int g = 0; g < 2; g++) {
      uint32_t x[4], y[4];
#pragma unroll 1
      for (int it = 0; it < MSG_SPINS; it++) {
        uint32_t bad = 0, z, tg;
#pragma unroll
        for (int k = 0; k < 4; k++) { ld_msg(base + 16 * 224 + min(g * 4 + k, 5 + mat) * 32 + lane, x[k], y[k], z, tg); bad |= tg ^ tag; }
        if (__all_sync(0xffffffffu, bad == 0)) break;
      }
#pragma unroll
      for (int k = 0; k < 4; k++)
        sts_f2(sb + (mat ? OFF_CSF : OFF_CSQ) + ((min(g * 4 + k, 5 + mat) * 32 + lane) << (3 + mat)), __uint_as_float(x[k]), __uint_as_float(y[k]));
    }
    __syncwarp();
    if (elect_one()) mbar_arrive(sb + BAR_CSOK + 8 * mat);
    PROF_E(-1, 3 + 3 * mat);
  }
}

template <int N>
__device__ __forceinline__ void mainloop(float (&acc)[2][96], uint32_t sb, int i, int part, int mn) {
  constexpr uint32_t Z16 = (2 + N / 64) * (UNIT >> 4), RING16 = RING_UNITS * (UNIT >> 4);
  constexpr uint32_t A_OFF = Z16 - 1024 + (uint32_t)DESC_A - (uint32_t)DESC_B;
  const int wg = i & 1;
  const int layer = i >= 7, t = i - 7 * layer;
  const bool own = t != 2 && t != 6 && part != 1, second = t == 1 || t == 4;
  const int gl = 16 * t + (part == 2 ? 0 : second ? 16 * part - 14 : 4 * part), g0 = layer * STAGES_PER_LAYER + gl;
  const uint32_t s16 = (sb & 0x3FFFF) >> 4;
  const uint32_t bfirst = (uint32_t)DESC_B + s16;
  const uint32_t blast = uniform(bfirst + RING16 - Z16), flast = uniform(sb + BAR_FULL + 8 * (NBAR - 1));
  const int nkb = t == 6 ? 56 : part == 0 ? 2 : 12 + 2 * part;
  const bool win1 = t == 1 && part != 0;
  int run = uniform(win1 ? WIN1 + 1 : t == 2 ? WIN2 + 1 : nkb);
  int rest = win1 ? 64 | (nkb - 1 - WIN1) : t == 2 ? 64 | (7 - WIN2) | (8 << 7) : 0;
  uint32_t fb = sb + BAR_FULL + 8 * (g0 % NBAR), ph = (g0 / NBAR) & 1;
  uint32_t prev = sb + BAR_DUMMY - 8 * NBAR;
  uint32_t blo = bfirst + Z16 * (N == 192 ? (gl + (t == 5 ? 3 : 0)) & 3 : (gl + 3) % 5);
  uint32_t alo = own ? (uint32_t)DESC_A + s16 + (OFF_X >> 4) : blo + A_OFF;
  uint32_t aoff = own ? alo + 1024 - (blo == blast ? bfirst : blo + Z16) : A_OFF;
  pin_regs<N / 2>(acc);
  if (i > 0) bar_sync(BAR_ORDER + wg, 256);
  if (t == (N == 192 ? 0 : 3) && part != 1) mbar_wait(sb + BAR_XRDY, N == 128);
  mbar_wait(fb, ph);
  if (part != 1) PROF_T(4 + i * 4);
#pragma unroll 1
  while (true) {
    const uint64_t da = (DESC_A & ~0xffffffffull) | alo, db = (DESC_B & ~0xffffffffull) | blo;
    asm volatile("wgmma.fence.sync.aligned;" ::: "memory");
    wgmma_ss<N>(acc[0], da, db);
    wgmma_ss<N>(acc[1], da + 64, db);
    wgmma_ss<N>(acc[0], da + 2, db + 128);
    wgmma_ss<N>(acc[1], da + 66, db + 128);
    asm volatile("wgmma.commit_group.sync.aligned;" ::: "memory");
    asm volatile("wgmma.wait_group.sync.aligned 1;" ::: "memory");
    PROF_S(g0 + jj++);
    if (elect_one()) mbar_arrive(prev + 8 * NBAR);
    prev = fb;
    if (fb == flast) { fb -= 8 * NBAR; ph++; }
    fb += 8;
    if (blo == blast) blo -= RING16;
    blo += Z16;
    alo = blo + aoff;
    aoff = A_OFF;
    run--;
    const bool ready = mbar_test(fb, ph) && run != 0;
    asm volatile("wgmma.fence.sync.aligned;" ::: "memory");
    wgmma_ss<N>(acc[0], da + 4, db + 256);
    wgmma_ss<N>(acc[1], da + 68, db + 256);
    wgmma_ss<N>(acc[0], da + 6, db + 384);
    wgmma_ss<N>(acc[1], da + 70, db + 384);
    asm volatile("wgmma.commit_group.sync.aligned;" ::: "memory");
    if (!ready) {
      if (run == 0) {
        if (rest == 0) break;
        if (rest & 64) {
          bar_arrive(BAR_GO, 256);
          bar_sync(BAR_DONE, 256);
        } else {
          alo = (uint32_t)DESC_A + s16 + (OFF_STG >> 4);
        }
        run = rest & 63;
        rest >>= 7;
      }
      mbar_wait(fb, ph);
    }
  }
  if (i < 13) bar_arrive(BAR_ORDER + (wg ^ 1), 256);
  asm volatile("wgmma.wait_group.sync.aligned 0;" ::: "memory");
  pin_regs<N / 2>(acc);
  if (elect_one()) mbar_arrive(prev + 8 * NBAR);
  PROF_T(5 + i * 4);
  PROF_E(i, 0);
}

#define ACC(q, j, e) acc[(q) & 1][4 * (j) + 2 * ((q) >> 1) + (e)]

__device__ __forceinline__ void write_partial_stats(const Ctx& c, int ln, uint32_t tag) {
  const uint32_t xrow = c.sb + OFF_X + c.w * 4096 + c.lane * 128;
  float s = 0.f, q = 0.f;
#pragma unroll 2
  for (int j = 0; j < 16; j++) {
    uint32_t u[4];
    lds_u4(xrow + (j >> 3) * 16384 + (((j & 7) ^ (c.lane & 7)) << 4), u[0], u[1], u[2], u[3]);
#pragma unroll
    for (int e = 0; e < 4; e++) {
      const float a = bf_lo(u[e]), d = bf_hi(u[e]);
      s += a; q = fmaf(a, a, q);
      s += d; q = fmaf(d, d, q);
    }
  }
  st_msg(g_stats + (ln * 8 + c.n) * SEQ + 128 * c.m + 32 * c.w + c.lane, __float_as_uint(s),
         __float_as_uint(fmaxf(q - s * s * (1.f / 128.f), 0.f)), 0u, tag);
}

__device__ __forceinline__ void finish_row_stats(const Ctx& c, int ln, uint32_t tag) {
  const uint4* src = g_stats + ln * 8 * SEQ + 128 * c.m + 32 * c.w + c.lane;
  uint32_t ps[8], pm[8];
#pragma unroll 1
  for (int it = 0; it < MSG_SPINS; it++) {
    uint32_t bad = 0, u, tg;
#pragma unroll
    for (int k = 0; k < 8; k++) { ld_msg(src + k * SEQ, ps[k], pm[k], u, tg); bad |= tg ^ tag; }
    if (__all_sync(0xffffffffu, bad == 0)) break;
  }
  float s = 0.f, m2 = 0.f;
#pragma unroll
  for (int k = 0; k < 8; k++) s += __uint_as_float(ps[k]);
  const float mean = s * (1.f / DM);
#pragma unroll
  for (int k = 0; k < 8; k++) {
    const float d = __uint_as_float(ps[k]) * (1.f / 128.f) - mean;
    m2 += fmaf(128.f * d, d, __uint_as_float(pm[k]));
  }
  sts_f2(c.sb + OFF_ROW + (32 * c.w + c.lane) * 8, rsqrtf(m2 * (1.f / DM) + 1e-5f), mean);
  __syncwarp();
}

__device__ __forceinline__ void attn_scores(const uint32_t* qa, const uint32_t* qb, const uint32_t* k0, const uint32_t* k1,
                                            const uint32_t* k2, const uint32_t* k3, float (&l)[4], const float4& zero,
                                            bool par, bool early) {
  float s[4][4];
#pragma unroll
  for (int kb = 0; kb < 4; kb++) {
    const uint32_t* kk = kb == 0 ? k0 : kb == 1 ? k1 : kb == 2 ? k2 : k3;
    asm volatile("mma.sync.aligned.m16n8k16.row.col.f32.bf16.bf16.f32 {%0,%1,%2,%3}, {%4,%5,%6,%7}, {%8,%9}, {%10,%11,%12,%13};"
                 : "=f"(s[kb][0]), "=f"(s[kb][1]), "=f"(s[kb][2]), "=f"(s[kb][3])
                 : "r"(qa[0]), "r"(qb[0]), "r"(qa[1]), "r"(qb[1]), "r"(kk[0]), "r"(kk[1]), "f"(zero.x), "f"(zero.y),
                   "f"(zero.z), "f"(zero.w));
  }
#pragma unroll
  for (int kb = 0; kb < 4; kb++) {
    const uint32_t* kk = kb == 0 ? k0 : kb == 1 ? k1 : kb == 2 ? k2 : k3;
    mma16816(s[kb], qa[2], qb[2], qa[3], qb[3], kk[2], kk[3]);
  }
  l[0] = par ? s[1][1] : s[1][0];
  l[1] = early ? (par ? s[0][1] : s[0][0]) : (par ? s[2][1] : s[2][0]);
  l[2] = par ? s[2][3] : s[2][2];
  l[3] = early ? (par ? s[1][3] : s[1][2]) : (par ? s[3][3] : s[3][2]);
}

__device__ __forceinline__ void attn_mix(const float (&l)[4], const float (&sc)[4], const float (&off)[4], const float (&rk)[4],
                                         const uint32_t* v0, const uint32_t* v1, const uint32_t* v2, const uint32_t* v3,
                                         float (&o)[4][4], bool par, bool early) {
  float x[4];
#pragma unroll
  for (int e = 0; e < 4; e++) x[e] = fmaf(l[e], sc[e], off[e]);
  const float ml = quad_max(fmaxf(x[0], x[1])), mh = quad_max(fmaxf(x[2], x[3]));
  x[0] = ex2(x[0] - ml); x[1] = ex2(x[1] - ml);
  x[2] = ex2(x[2] - mh); x[3] = ex2(x[3] - mh);
  const float il = rcp_hw(quad_sum(x[0] + x[1])), ih = rcp_hw(quad_sum(x[2] + x[3]));
  const uint32_t pl = pack_bf16(x[0] * rk[0] * il, x[1] * rk[1] * il), ph = pack_bf16(x[2] * rk[2] * ih, x[3] * rk[3] * ih);
  const uint32_t sel_a = par ? 0x1044u : 0x4410u, sel_b = par ? 0x3244u : 0x4432u;
  const uint32_t sel_e = early ? sel_b : 0x4444u, sel_l = early ? 0x4444u : sel_b;
  const uint32_t pla = __byte_perm(pl, 0, sel_a), pha = __byte_perm(ph, 0, sel_a);
  const uint32_t e_l = __byte_perm(pl, 0, sel_e), e_h = __byte_perm(ph, 0, sel_e);
  const uint32_t l_l = __byte_perm(pl, 0, sel_l), l_h = __byte_perm(ph, 0, sel_l);
#pragma unroll
  for (int jn = 0; jn < 4; jn++) {
    o[jn][0] = o[jn][1] = o[jn][2] = o[jn][3] = 0.f;
    mma16816(o[jn], e_l, 0u, pla, e_h, v0[jn], v1[jn]);
  }
#pragma unroll
  for (int jn = 0; jn < 4; jn++) mma16816(o[jn], l_l, pha, 0u, l_h, v2[jn], v3[jn]);
}

__device__ __forceinline__ void gelu_epilogue(const Params& p, float (&acc)[2][96], const Ctx& cx, int t) {
  UNPACK_CTX(cx);
  (void)wg;
  float rs[4], rm[4];
#pragma unroll
  for (int q = 0; q < 4; q++) {
    const float2 v = lds_f2(sb + OFF_ROW + (32 * w + 8 * q + (lane >> 2)) * 8);
    rs[q] = 0.5f * v.x;
    rm[q] = -rs[q] * v.y;
  }
  const int col0 = 128 * (t - 3), steps = t == 5 ? 6 : 4;
  const uint32_t stg = sb + OFF_STG + w * 4096;
  uint32_t ctab = sb + OFF_CSF + (col0 / 2 + (lane & 3)) * 16;
  float v[2][16];
#pragma unroll
  for (int r = 0; r < 16; r++) { v[0][r] = acc[0][r]; v[1][r] = acc[1][r]; }
#pragma unroll 1
  for (int it = 0; it < steps; it++) {
    uint32_t hp[4][4];
#pragma unroll
    for (int j = 0; j < 4; j++) {
      const float4 cb = lds_f4(ctab + j * 64);
#pragma unroll
      for (int q = 0; q < 4; q++) {
        float y[2];
        const int k = 4 * j + q - GELU_DEP;
        const float rmq = k >= 0 ? chain(rm[q], hp[k >> 2][k & 3], p.zero) : rm[q];
#pragma unroll
        for (int e = 0; e < 2; e++) {
          const float z = fmaf(v[q & 1][4 * j + 2 * (q >> 1) + e], rs[q], fmaf(rmq, e ? cb.y : cb.x, e ? cb.w : cb.z));
          const float u = z * fmaf(z * z, 8.f * 0.7978845608028654f * 0.044715f, 2.f * 0.7978845608028654f);
          y[e] = fmaf(z, tanh_hw(u), z);
        }
        hp[j][q] = pack_bf16(y[0], y[1]);
      }
    }
    ctab += 256;
    if (!(it & 1)) {
      if (lane == 0) bulk_wait_read();
      __syncwarp();
    }
#pragma unroll
    for (int j = 0; j < 4; j++)
      stsm4(stg + lane * 128 + (((4 * (it & 1) + j) ^ (lane & 7)) << 4), hp[j][0], hp[j][1], hp[j][2], hp[j][3]);
    if (it & 1) {
      fence_async_smem();
      __syncwarp();
      if (lane == 0) {
        tma_st2(&p.h_st, stg, 448 * n + col0 + 32 * (it - 1), 128 * m + 32 * w);
        bulk_commit();
      }
      if (it == steps - 1) break;
    }
    const uint32_t zr = hp[3][3] & p.zero;
#define REFILL(k) _Pragma("unroll") for (int r = 0; r < 32; r++) \
      asm volatile("{\n.reg .b32 t;\nmov.b32 t, %1;\nor.b32 t, t, %2;\nmov.b32 %0, t;\n}" \
                   : "=f"(v[r >> 4][r & 15]) : "f"(acc[r >> 4][16 * k + (r & 15)]), "r"(zr)); break;
    switch (it) {
      case 0: REFILL(1)
      case 1: REFILL(2)
      case 2: REFILL(3)
      case 3: REFILL(4)
      default: REFILL(5)
    }
#undef REFILL
  }
}

__device__ __forceinline__ void attn_epilogue(const Params& p, float (&acc)[2][96], const Ctx& cx, int layer, int t, uint32_t tag) {
  UNPACK_CTX(cx);
  const bool par = (lane >> 2) & 1, early = (lane & 3) > (lane >> 3);
  uint32_t Q[4][8], K[4][8], V[4][8];
  float kr[6], qr[4];
#pragma unroll
  for (int q = 0; q < 4; q++) {
    kr[2 + q] = lds_f(sb + OFF_ROW + (32 * w + 8 * q + 2 * (lane & 3) + par) * 8);
    qr[q] = lds_f(sb + OFF_ROW + (32 * w + 8 * q + (lane >> 2)) * 8) * (0.17677669529663687f * 1.4426950408889634f);
  }
  const int slot = ((layer * 2 + t) * 16 + m) * 8 + n;
  uint4* const exc = reinterpret_cast<uint4*>(__cvta_shared_to_generic(sb + OFF_STG));
#pragma unroll
  for (int qq = 0; qq < 4; qq++) {
    const int q = qq ^ 2;
#pragma unroll
    for (int j = 0; j < 8; j++) {
      K[q][j] = pack_bf16(ACC(q, 8 + j, 0), ACC(q, 8 + j, 1));
      V[q][j] = movtrans(pack_bf16(ACC(q, 16 + j, 0), ACC(q, 16 + j, 1)));
    }
    if (qq == 1) {
      uint4* e = (w < 3 ? exc + w * 512 : g_halo + slot * 512) + lane;
#pragma unroll
      for (int j = 0; j < 8; j++) {
        st_msg(e + j * 32, K[2 + (j >> 2)][2 * (j & 3)], K[2 + (j >> 2)][2 * (j & 3) + 1], __float_as_uint(kr[4]), tag);
        st_msg(e + (8 + j) * 32, V[2][j], V[3][j], __float_as_uint(kr[5]), tag);
      }
    }
  }
#pragma unroll
  for (int q = 0; q < 4; q++)
#pragma unroll
    for (int j = 0; j < 8; j++) Q[q][j] = pack_bf16(ACC(q, j, 0), ACC(q, j, 1));
  const int mn = m * 8 + n; (void)mn;
  PROF_E(7 * layer + t, 1);
  bar_sync(BAR_WG + wg, 128);
  const uint4* src = (w > 0 ? exc + (w - 1) * 512 : m > 0 ? g_halo + (slot - 8) * 512 : exc) + lane;
  uint32_t PK[2][8], PV[2][8], r4, r5;
#pragma unroll 1
  for (int it = 0; it < MSG_SPINS; it++) {
    uint32_t tg, bad = 0;
#pragma unroll
    for (int j = 0; j < 8; j++) {
      ld_msg(src + j * 32, PK[j >> 2][2 * (j & 3)], PK[j >> 2][2 * (j & 3) + 1], r4, tg); bad |= tg ^ tag;
      ld_msg(src + (8 + j) * 32, PV[0][j], PV[1][j], r5, tg); bad |= tg ^ tag;
    }
    if (__all_sync(0xffffffffu, bad == 0)) break;
  }
  kr[0] = __uint_as_float(r4);
  kr[1] = __uint_as_float(r5);
  float rk[2][4], sc[2][4], off[2][4];
#pragma unroll
  for (int g = 0; g < 2; g++) {
    rk[g][0] = kr[2 * g + 1];
    rk[g][1] = early ? kr[2 * g] : kr[2 * g + 2];
    rk[g][2] = kr[2 * g + 2];
    rk[g][3] = early ? kr[2 * g + 1] : kr[2 * g + 3];
#pragma unroll
    for (int e = 0; e < 4; e++) {
      const bool masked = g == 0 && e != 2 && (m | w) == 0 && (e == 0 || early);
      sc[g][e] = masked ? 0.f : rk[g][e] * qr[2 * g + (e >> 1)];
      off[g][e] = masked ? -1e30f : 0.f;
    }
  }
  PROF_E(7 * layer + t, 2);
  bar_sync(BAR_GO, 256);
  PROF_E(7 * layer + t, 3);
  const float4 zero = lds_f4(sb + OFF_ZERO);
  float l[2][2][4], o[2][2][4][4];
#pragma unroll
  for (int h = 0; h < 2; h++) {
    attn_scores(&Q[2][4 * h], &Q[3][4 * h], &K[0][4 * h], &K[1][4 * h], &K[2][4 * h], &K[3][4 * h], l[1][h], zero, par, early);
    attn_scores(&Q[0][4 * h], &Q[1][4 * h], &PK[0][4 * h], &PK[1][4 * h], &K[0][4 * h], &K[1][4 * h], l[0][h], zero, par, early);
  }
#pragma unroll
  for (int h = 0; h < 2; h++) {
    attn_mix(l[1][h], sc[1], off[1], rk[1], &V[0][4 * h], &V[1][4 * h], &V[2][4 * h], &V[3][4 * h], o[1][h], par, early);
    attn_mix(l[0][h], sc[0], off[0], rk[0], &PV[0][4 * h], &PV[1][4 * h], &V[0][4 * h], &V[1][4 * h], o[0][h], par, early);
  }
  const uint32_t stg = sb + OFF_STG + w * 4096;
#pragma unroll
  for (int j = 0; j < 8; j++) {
    const float(&a)[4] = o[0][j >> 2][j & 3];
    const float(&c)[4] = o[1][j >> 2][j & 3];
    stsm4(stg + lane * 128 + ((j ^ (lane & 7)) << 4), pack_bf16(a[0], a[1]), pack_bf16(a[2], a[3]), pack_bf16(c[0], c[1]),
          pack_bf16(c[2], c[3]));
  }
  bar_arrive(BAR_DONE, 256);
  fence_async_smem();
  __syncwarp();
  if (lane == 0) {
    tma_st2(&p.att_st, stg, 128 * n + 64 * t, 128 * m + 32 * w);
    bulk_commit();
  }
}

__device__ __forceinline__ void consumer_tile(const Params& p, uint32_t sb0, int i, int mn) {
  const int layer = i >= 7, t = i - 7 * layer, wg = i & 1;
  const bool resid = t == 2 || t == 6;
  if (i >= 0) {
    float acc[2][96];
    if (resid) {
      const Ctx cx = make_ctx(sb0, mn);
      const uint32_t xrow = cx.sb + OFF_X + cx.w * 4096 + cx.lane * 128;
      const uint32_t sel_lo = 0x1044u | p.zero, sel_hi = 0x3244u | p.zero;
#pragma unroll
      for (int j = 0; j < 16; j++) {
        uint32_t r[4];
        ldsm4(xrow + (j >> 3) * 16384 + (((j & 7) ^ (cx.lane & 7)) << 4), r[0], r[1], r[2], r[3]);
#pragma unroll
        for (int q = 0; q < 4; q++) {
          ACC(q, j, 0) = prmt_f(r[q], sel_lo);
          ACC(q, j, 1) = prmt_f(r[q], sel_hi);
        }
      }
    } else {
#pragma unroll
      for (int r = 0; r < 64; r++) acc[0][r] = acc[1][r] = 0.f;
    }
#pragma unroll
    for (int r = 64; r < 96; r++) acc[0][r] = acc[1][r] = 0.f;
    const bool split = t == 3 || t == 4 || i == 7 || i == 8;
#pragma unroll 1
    for (int step = split ? 0 : 1;; step++) {
      if (step == 1 && (t == 1 || t == 4)) {
        const Ctx cx = make_ctx(sb0, mn);
        const uint32_t tag = lds_u(cx.sb + OFF_TAG);
        const int ln = (i + 1) >> 2;
        if (i == 1) {
          mbar_wait(sb0 + BAR_XRDY, 0);
          mbar_wait(sb0 + BAR_XRDY + 8, 0);
        }
        write_partial_stats(cx, ln, tag);
        PROF_E(i - 2, 8);
        if (i != 1) bar_sync(BAR_GUARD + wg, 256);
        finish_row_stats(cx, ln, tag);
        PROF_E(i - 2, 10);
        if (i <= 4) mbar_wait(sb0 + BAR_CSOK + 2 * (i & 4), 0);
        bar_arrive(BAR_GUARD + (wg ^ 1), 256);
      }
      if (step == 2 && !resid) bar_sync(BAR_GUARD + wg, 256);
      if (t + step == 2 || t == 6) {
        const Ctx cx = make_ctx(sb0, mn);
        float nm[4];
#pragma unroll
        for (int q = 0; q < 4; q++) nm[q] = t == 6 ? 1.f : -lds_f(cx.sb + OFF_ROW + (32 * cx.w + 8 * q + (cx.lane >> 2)) * 8 + 4);
        const uint32_t ctab = cx.sb + OFF_CSQ + ((t & 3) * 192 + 2 * (cx.lane & 3)) * 4;
#pragma unroll
        for (int j = 0; j < 24; j++) {
          const float2 cs = lds_f2(ctab + j * 32);
#pragma unroll
          for (int q = 0; q < 4; q++) {
            const int k = 4 * j + q - 1;
            const float nq = k >= 0 ? chain(nm[q], __float_as_uint(ACC(k & 3, k >> 2, 1)), p.zero) : nm[q];
            ACC(q, j, 0) = fmaf(nq, cs.x, ACC(q, j, 0));
            ACC(q, j, 1) = fmaf(nq, cs.y, ACC(q, j, 1));
          }
        }
      }
      if (step == 2) break;
      if (tile_wide(t)) {
        mainloop<192>(acc, sb0, i, split ? step : 2, mn);
      } else {
        mainloop<128>(acc, sb0, i, split ? step : 2, mn);
        if (resid) break;
      }
    }
    const Ctx cx = make_ctx(sb0, mn);
    if (resid) {
      const uint32_t xrow = cx.sb + OFF_X + cx.w * 4096 + cx.lane * 128;
#pragma unroll
      for (int j = 0; j < 16; j++) {
        stsm4(xrow + (j >> 3) * 16384 + (((j & 7) ^ (cx.lane & 7)) << 4), pack_bf16(ACC(0, j, 0), ACC(0, j, 1)),
              pack_bf16(ACC(1, j, 0), ACC(1, j, 1)), pack_bf16(ACC(2, j, 0), ACC(2, j, 1)), pack_bf16(ACC(3, j, 0), ACC(3, j, 1)));
        if ((j & 7) == 7) {
          fence_async_smem();
          __syncwarp();
          if (elect_one()) mbar_arrive(sb0 + BAR_XRDY + (j & 8));
        }
      }
      PROF_E(i, 4);
      return;
    }
    if (t < 2) attn_epilogue(p, acc, cx, layer, t, lds_u(sb0 + OFF_TAG));
    else gelu_epilogue(p, acc, cx, t);
    PROF_E(i, 4);
    if (cx.lane == 0) {
      bulk_wait_all();
      mbar_arrive(sb0 + BAR_PUB + 8 * (t < 2 ? t : t + 1));
    }
    __syncwarp();
    PROF_E(i, 5);
    if (i < 12) bar_arrive(BAR_GUARD + (wg ^ 1), 256);
  } else {
    const Ctx cx = make_ctx(sb0, mn);
    const uint32_t tag = __ldcg(g_epoch + (mn & 127)) + 1;
#pragma unroll 1
    for (int r = 0; r < 2; r++) {
      if (cx.w == 3) {
        if (elect_one()) {
          mbar_expect_tx(sb0 + BAR_CSLD, 24576);
          tma_ld3(sb0 + OFF_STG, &p.wqkv, sb0 + BAR_CSLD, 128 * cx.n + 64 * r, 64 * cx.m, 0);
          if (r == 0) tma_pf3(&p.wqkv, 128 * cx.n + 64, 64 * cx.m, 0);
        }
      } else {
        float a[8] = {0.f, 0.f, 0.f, 0.f, 0.f, 0.f, 0.f, 0.f};
        mbar_wait(sb0 + BAR_CSLD, r);
        sum_rows(cx.sb + OFF_STG + cx.w * 8192, 8, a, cx.lane);
        publish_sums(a, g_csp + (cx.n * 17 + cx.m) * 224 + (3 * r + cx.w) * 32, cx.lane, tag);
      }
      bar_sync(BAR_WG + 1, 128);
    }
    asm volatile("st.shared.u32 [%0], %1;" ::"r"(sb0 + OFF_TAG), "r"(tag) : "memory");
    bar_arrive(BAR_HLP, 160);
    PROF_E(i, 7);
  }
}

__global__ void __launch_bounds__(384, 1) fused_layers_kernel(const __grid_constant__ Params p) {
  extern __shared__ __align__(1024) uint8_t smem_raw[];
  const uint32_t sb = uniform((uint32_t)__cvta_generic_to_shared(smem_raw));
  const int tid = threadIdx.x, lane = tid & 31, warp = uniform(tid >> 5), wg = warp >> 2, w = warp & 3;

  int mn;
  {
    int id = blockIdx.x;
    if (p.by_smid) asm volatile("mov.u32 %0, %%smid;" : "=r"(id));
    else if (id >= 120) id += 4;
    const int c = id >> 1;
    int g, j;
    if (c < 32) { g = c & 7; j = c >> 3; }
    else if (c < 60) { g = 1 + (c - 32) % 7; j = 4 + (c - 32) / 7; }
    else { g = 0; j = c - 58; }
    mn = ((g >> 2) * 8 + j) * 8 + (g & 3) * 2 + (id & 1);
    if (c == 60 || c == 61) {
      if (tid < 32) {
        const uint32_t tag = __ldcg(g_epoch + NCTA + (id & 3)) + 1;
#pragma unroll 1
        for (int mm = 0; mm < 16; mm++) poll_line(g_flags + mm * 32 + (lane & 7), 32 * tag, 0xffu);
        if (tid == 0) g_epoch[NCTA + (id & 3)] = tag;
      }
      return;
    }
  }
  const int m = mn >> 3, n = mn & 7;
  asm volatile("prefetch.global.L2 [%0];" ::"l"(p.wqkv_p + (128 * n + (tid & 127)) * (3 * DM) + wg * DM + 128 * n));
  if (wg < 2) asm volatile("prefetch.global.L2 [%0];" ::"l"(p.x_p + (128 * m + (tid & 127)) * DM + 128 * n + 64 * wg));
  if (tid == 256) asm volatile("prefetch.tensormap [%0];" ::"l"(&p.wqkv) : "memory");
  if (tid == 288) asm volatile("prefetch.tensormap [%0];" ::"l"(&p.xin) : "memory");
  if (tid == 0) {
    for (int s = 0; s < NBAR; s++) {
      mbar_init(sb + BAR_FULL + 8 * s, 2);
      mbar_init(sb + BAR_EMPTY + 8 * s, 4);
    }
    mbar_init(sb + BAR_XRDY, 4);
    mbar_init(sb + BAR_XRDY + 8, 4);
    for (int e = 0; e < 9; e++) mbar_init(sb + BAR_PUB + 8 * e, 4);
    for (int e = 0; e < 4; e++) mbar_init(sb + BAR_CSLD + 8 * e, 1);
    mbar_init(sb + BAR_DUMMY, 4);
    sts_f2(sb + OFF_ZERO, 0.f, 0.f);
    sts_f2(sb + OFF_ZERO + 8, 0.f, 0.f);
    fence_async_smem();
  }
  __syncthreads();

  if (wg < 2) {
    asm volatile("setmaxnreg.inc.sync.aligned.u32 232;");
#pragma unroll 1
    for (int i = -wg; i < 14; i += 2) {
      consumer_tile(p, sb, i, mn | (warp << 7));
      PROF_T(i < 0 ? 3 : 6 + i * 4);
    }
  } else {
    asm volatile("setmaxnreg.dec.sync.aligned.u32 40;");
    if (w == 0) {
      producer<false>(p, sb, m, n, lane);
    } else if (w == 1) {
      if (elect_one()) {
        for (int h = 0; h < 2; h++) {
          const uint32_t xr = sb + BAR_XRDY + 8 * h;
          mbar_expect_tx(xr, 16384);
          tma_ld2(sb + OFF_X + h * 16384, &p.xin, xr, 128 * n + 64 * h, 128 * m);
          asm volatile("mbarrier.arrive.shared::cta.b64 _, [%0], 3;" ::"r"(xr) : "memory");
        }
      }
      producer<true>(p, sb, m, n, lane);
    } else if (w == 2) {
      if (elect_one()) publisher(p, sb, m, n);
    } else {
      colsum_helper(p, sb, m, n, lane);
    }
  }
}

typedef CUresult (*EncodeFn)(CUtensorMap*, CUtensorMapDataType, cuuint32_t, void*, const cuuint64_t*, const cuuint64_t*,
                             const cuuint32_t*, const cuuint32_t*, CUtensorMapInterleave, CUtensorMapSwizzle,
                             CUtensorMapL2promotion, CUtensorMapFloatOOBfill);

void make_2d(EncodeFn enc, CUtensorMap* m, const void* ptr, uint64_t cols, uint64_t rows, uint32_t box_rows) {
  cuuint64_t d[2] = {cols, rows}, st[1] = {cols * 2};
  cuuint32_t b[2] = {64, box_rows}, e[2] = {1, 1};
  enc(m, CU_TENSOR_MAP_DATA_TYPE_BFLOAT16, 2, const_cast<void*>(ptr), d, st, b, e, CU_TENSOR_MAP_INTERLEAVE_NONE,
      CU_TENSOR_MAP_SWIZZLE_128B, CU_TENSOR_MAP_L2_PROMOTION_L2_128B, CU_TENSOR_MAP_FLOAT_OOB_FILL_NONE);
}
void make_3d(EncodeFn enc, CUtensorMap* m, const void* ptr, uint64_t d0, uint64_t rows, uint64_t d2, uint64_t row_bytes,
             uint64_t chunk_bytes, uint32_t box_chunks) {
  cuuint64_t d[3] = {d0, rows, d2}, st[2] = {row_bytes, chunk_bytes};
  cuuint32_t b[3] = {64, 64, box_chunks}, e[3] = {1, 1, 1};
  enc(m, CU_TENSOR_MAP_DATA_TYPE_BFLOAT16, 3, const_cast<void*>(ptr), d, st, b, e, CU_TENSOR_MAP_INTERLEAVE_NONE,
      CU_TENSOR_MAP_SWIZZLE_128B, CU_TENSOR_MAP_L2_PROMOTION_L2_128B, CU_TENSOR_MAP_FLOAT_OOB_FILL_NONE);
}

}

extern "C" void kernel_launch(void* const* d_in, const int* in_sizes, int n_in, void* d_out, int out_size) {
  (void)in_sizes; (void)n_in; (void)out_size;
  static EncodeFn enc = nullptr;
  static void *att = nullptr, *hbuf = nullptr;
  static int by_smid = 0;
  if (!enc) {
    void* fn = nullptr;
    cudaDriverEntryPointQueryResult q;
    cudaGetDriverEntryPoint("cuTensorMapEncodeTiled", &fn, cudaEnableDefault, &q);
    enc = (EncodeFn)fn;
    cudaGetSymbolAddress(&att, g_att);
    cudaGetSymbolAddress(&hbuf, g_h);
    cudaFuncSetAttribute(fused_layers_kernel, cudaFuncAttributeMaxDynamicSharedMemorySize, SMEM_BYTES);
    int sms = 0, per_sm = 0, dev = 0;
    cudaGetDevice(&dev);
    cudaDeviceGetAttribute(&sms, cudaDevAttrMultiProcessorCount, dev);
    cudaOccupancyMaxActiveBlocksPerMultiprocessor(&per_sm, fused_layers_kernel, 384, SMEM_BYTES);
    by_smid = sms == 132 && per_sm == 1;
  }
  Params p;
  make_2d(enc, &p.xin, d_in[0], DM, SEQ, 128);
  make_2d(enc, &p.out, d_out, DM, SEQ, 128);
  make_2d(enc, &p.att, att, DM, SEQ, 128);
  make_2d(enc, &p.h, hbuf, FF, SEQ, 128);
  make_2d(enc, &p.out_st, d_out, DM, SEQ, 32);
  make_2d(enc, &p.att_st, att, DM, SEQ, 32);
  make_2d(enc, &p.h_st, hbuf, FF, SEQ, 32);
  make_2d(enc, &p.w1c, d_in[4], FF, DM, 32);
  make_3d(enc, &p.wqkv, d_in[1], DM, DM, 3, 3 * DM * 2, DM * 2, 3);
  make_3d(enc, &p.wo, d_in[2], 64, DM, DM / 64, DM * 2, 128, 2);
  make_3d(enc, &p.w1a, d_in[4], 64, DM, FF / 64, FF * 2, 128, 3);
  make_3d(enc, &p.w1b, d_in[4], 64, DM, FF / 64, FF * 2, 128, 2);
  make_3d(enc, &p.w2, d_in[6], 64, FF, DM / 64, DM * 2, 128, 2);
  p.x_p = (const __nv_bfloat16*)d_in[0];
  p.wqkv_p = (const __nv_bfloat16*)d_in[1];
  p.b1 = (const __nv_bfloat16*)d_in[5];
  p.b2 = (const __nv_bfloat16*)d_in[7];
  p.by_smid = by_smid;
  p.zero = 0;
  fused_layers_kernel<<<by_smid ? 132 : NCTA, 384, SMEM_BYTES>>>(p);
}
```

```cpp
#include <cuda_runtime.h>
#include <cuda_bf16.h>
#include <cuda.h>
#include <stdint.h>

namespace {

constexpr int SEQ = 2048, DM = 1024, FF = 3584;
constexpr int NCTA = 128;
constexpr int NBAR = 5;

constexpr uint32_t RING_UNITS = 20, UNIT = 8192;
constexpr uint32_t OFF_X   = RING_UNITS * UNIT;
constexpr uint32_t OFF_STG = OFF_X + 32768;
constexpr uint32_t OFF_HLP = OFF_STG + 24576;
constexpr uint32_t OFF_CSQ = OFF_HLP + 4096;
constexpr uint32_t OFF_CSF = OFF_CSQ + 2048;
constexpr uint32_t OFF_ROW = OFF_CSF + 3584;
constexpr uint32_t OFF_BAR = OFF_ROW + 1024;
constexpr uint32_t SMEM_BYTES = OFF_BAR + 384;
constexpr uint32_t BAR_FULL = OFF_BAR, BAR_EMPTY = OFF_BAR + 8 * NBAR;
constexpr uint32_t BAR_XRDY = OFF_BAR + 80;
constexpr uint32_t BAR_DUMMY = OFF_BAR + 96, OFF_TAG = OFF_BAR + 104, OFF_ZERO = OFF_BAR + 112;
constexpr uint32_t BAR_PUB = OFF_BAR + 128;
constexpr uint32_t BAR_CSLD = OFF_BAR + 200;
constexpr uint32_t BAR_BIAS = OFF_BAR + 216;

constexpr uint64_t DESC_A = (1ull << 62) | ((uint64_t)(2048 >> 4) << 32) | (1ull << 16);
constexpr uint64_t DESC_B = (1ull << 62) | ((uint64_t)(1024 >> 4) << 32) | ((uint64_t)(8192 >> 4) << 16);

constexpr int BAR_INIT = 0, BAR_ORDER = 1, BAR_GUARD = 3, BAR_WG = 5, BAR_GO = 7, BAR_DONE = 8;
#define GELU_DEP 3
#define WIN1 6
#define WIN2 4

struct Params {
  CUtensorMap xin, out, att, h, wqkv, wo, w1a, w1b, w2, out_st, att_st, h_st, w1c;
  const __nv_bfloat16 *b1, *b2;
  uint32_t zero;
};

__device__ __nv_bfloat16 g_att[SEQ * DM];
__device__ __nv_bfloat16 g_h[SEQ * FF];
__device__ uint4 g_stats[4 * 8 * SEQ];
__device__ uint4 g_halo[2 * 2 * 16 * 8 * 512];
__device__ uint4 g_csp[2 * 8 * 17 * 224];
__device__ uint32_t g_flags[16 * 32];
__device__ uint32_t g_epoch[NCTA + 4];
#define PROF_T(idx)
#define PROF_U(k)
#define PROF_S(g)
#define PROF_E(i, k)

__device__ __forceinline__ void mbar_init(uint32_t bar, int cnt) {
  asm volatile("mbarrier.init.shared::cta.b64 [%0], %1;" ::"r"(bar), "r"(cnt));
}
__device__ __forceinline__ void mbar_expect_tx(uint32_t bar, uint32_t bytes) {
  asm volatile("mbarrier.arrive.expect_tx.shared::cta.b64 _, [%0], %1;" ::"r"(bar), "r"(bytes) : "memory");
}
__device__ __forceinline__ void mbar_arrive(uint32_t bar) {
  asm volatile("mbarrier.arrive.shared::cta.b64 _, [%0];" ::"r"(bar) : "memory");
}
__device__ __forceinline__ bool mbar_test(uint32_t bar, uint32_t parity) {
  uint32_t ok;
  asm volatile("{\n.reg .pred p;\nmbarrier.test_wait.parity.shared::cta.b64 p, [%1], %2;\nselp.u32 %0, 1, 0, p;\n}"
               : "=r"(ok) : "r"(bar), "r"(parity) : "memory");
  return ok;
}
__device__ __forceinline__ void mbar_wait(uint32_t bar, uint32_t parity) {
  asm volatile(
      "{\n.reg .pred p;\n.reg .u32 it;\nmov.u32 it, 0;\n"
      "WAIT_LOOP:\n"
      "mbarrier.try_wait.parity.shared::cta.b64 p, [%0], %1;\n"
      "@p bra WAIT_DONE;\n"
      "add.u32 it, it, 1;\n"
      "setp.lt.u32 p, it, 0x400000;\n"
      "@p bra WAIT_LOOP;\n"
      "trap;\n"
      "WAIT_DONE:\n}"
      ::"r"(bar), "r"(parity) : "memory");
}
__device__ __forceinline__ void bar_sync(int id, int n) { asm volatile("bar.sync %0, %1;" ::"r"(id), "r"(n) : "memory"); }
__device__ __forceinline__ void bar_arrive(int id, int n) { asm volatile("bar.arrive %0, %1;" ::"r"(id), "r"(n) : "memory"); }
__device__ __forceinline__ void tma_ld2(uint32_t dst, const CUtensorMap* m, uint32_t bar, int c0, int c1) {
  asm volatile("cp.async.bulk.tensor.2d.shared::cluster.global.mbarrier::complete_tx::bytes [%0], [%1, {%3, %4}], [%2];"
               ::"r"(dst), "l"(m), "r"(bar), "r"(c0), "r"(c1) : "memory");
}
__device__ __forceinline__ void tma_ld3(uint32_t dst, const CUtensorMap* m, uint32_t bar, int c0, int c1, int c2) {
  asm volatile("cp.async.bulk.tensor.3d.shared::cluster.global.mbarrier::complete_tx::bytes [%0], [%1, {%3, %4, %5}], [%2];"
               ::"r"(dst), "l"(m), "r"(bar), "r"(c0), "r"(c1), "r"(c2) : "memory");
}
__device__ __forceinline__ void tma_pf3(const CUtensorMap* m, int c0, int c1, int c2) {
  asm volatile("cp.async.bulk.prefetch.tensor.3d.L2.global [%0, {%1, %2, %3}];" ::"l"(m), "r"(c0), "r"(c1), "r"(c2) : "memory");
}
__device__ __forceinline__ void tma_st2(const CUtensorMap* m, uint32_t src, int c0, int c1) {
  asm volatile("cp.async.bulk.tensor.2d.global.shared::cta.bulk_group [%0, {%2, %3}], [%1];"
               ::"l"(m), "r"(src), "r"(c0), "r"(c1) : "memory");
}
__device__ __forceinline__ void bulk_commit() { asm volatile("cp.async.bulk.commit_group;" ::: "memory"); }
__device__ __forceinline__ void bulk_wait_read() { asm volatile("cp.async.bulk.wait_group.read 0;" ::: "memory"); }
__device__ __forceinline__ void bulk_wait_all() { asm volatile("cp.async.bulk.wait_group 0;" ::: "memory"); }
__device__ __forceinline__ void fence_async_smem() { asm volatile("fence.proxy.async.shared::cta;" ::: "memory"); }
__device__ __forceinline__ void fence_async_global() { asm volatile("fence.proxy.async.global;" ::: "memory"); }
__device__ __forceinline__ void st_relaxed(uint32_t* p, uint32_t v) {
  asm volatile("st.relaxed.gpu.global.u32 [%0], %1;" ::"l"(p), "r"(v) : "memory");
}
__device__ __forceinline__ void st_msg(uint4* p, uint32_t a, uint32_t b, uint32_t c, uint32_t tag) {
  asm volatile("{\n.reg .b128 v;\nmov.b128 v, {%1, %2, %3, %4};\nst.relaxed.gpu.b128 [%0], v;\n}"
               ::"l"(p), "r"(a), "r"(b), "r"(c), "r"(tag) : "memory");
}
__device__ __forceinline__ void ld_msg(const uint4* p, uint32_t& a, uint32_t& b, uint32_t& c, uint32_t& tag) {
  asm volatile("{\n.reg .b128 v;\nld.relaxed.gpu.b128 v, [%4];\nmov.b128 {%0, %1, %2, %3}, v;\n}"
               : "=r"(a), "=r"(b), "=r"(c), "=r"(tag) : "l"(p) : "memory");
}
__device__ __forceinline__ bool elect_one() {
  uint32_t ok;
  asm volatile("{\n.reg .pred p;\nelect.sync _|p, 0xffffffff;\nselp.u32 %0, 1, 0, p;\n}" : "=r"(ok));
  return ok;
}
__device__ __forceinline__ int uniform(int v) { return __shfl_sync(0xffffffffu, v, 0); }
__device__ __forceinline__ uint32_t pack_bf16(float lo, float hi) {
  uint32_t r;
  asm("cvt.rn.bf16x2.f32 %0, %1, %2;" : "=r"(r) : "f"(hi), "f"(lo));
  return r;
}
__device__ __forceinline__ float prmt_f(uint32_t a, uint32_t sel) {
  float r;
  asm("{\n.reg .b32 t;\nprmt.b32 t, %1, 0, %2;\nmov.b32 %0, t;\n}" : "=f"(r) : "r"(a), "r"(sel));
  return r;
}
__device__ __forceinline__ float bf_lo(uint32_t v) { return __uint_as_float(v << 16); }
__device__ __forceinline__ float bf_hi(uint32_t v) { return __uint_as_float(v & 0xffff0000u); }
__device__ __forceinline__ void stsm4(uint32_t addr, uint32_t r0, uint32_t r1, uint32_t r2, uint32_t r3) {
  asm volatile("stmatrix.sync.aligned.m8n8.x4.shared.b16 [%0], {%1, %2, %3, %4};"
               ::"r"(addr), "r"(r0), "r"(r1), "r"(r2), "r"(r3) : "memory");
}
__device__ __forceinline__ void ldsm4(uint32_t addr, uint32_t& r0, uint32_t& r1, uint32_t& r2, uint32_t& r3) {
  asm volatile("ldmatrix.sync.aligned.m8n8.x4.shared.b16 {%0, %1, %2, %3}, [%4];"
               : "=r"(r0), "=r"(r1), "=r"(r2), "=r"(r3) : "r"(addr) : "memory");
}
__device__ __forceinline__ uint32_t movtrans(uint32_t a) {
  uint32_t d;
  asm volatile("movmatrix.sync.aligned.m8n8.trans.b16 %0, %1;" : "=r"(d) : "r"(a));
  return d;
}
__device__ __forceinline__ void mma16816(float (&c)[4], uint32_t a0, uint32_t a1, uint32_t a2, uint32_t a3, uint32_t b0, uint32_t b1) {
  asm volatile("mma.sync.aligned.m16n8k16.row.col.f32.bf16.bf16.f32 {%0,%1,%2,%3}, {%4,%5,%6,%7}, {%8,%9}, {%0,%1,%2,%3};"
               : "+f"(c[0]), "+f"(c[1]), "+f"(c[2]), "+f"(c[3])
               : "r"(a0), "r"(a1), "r"(a2), "r"(a3), "r"(b0), "r"(b1));
}
__device__ __forceinline__ float2 lds_f2(uint32_t a) {
  float2 v;
  asm volatile("ld.shared.v2.f32 {%0, %1}, [%2];" : "=f"(v.x), "=f"(v.y) : "r"(a) : "memory");
  return v;
}
__device__ __forceinline__ float4 lds_f4(uint32_t a) {
  float4 v;
  asm volatile("ld.shared.v4.f32 {%0, %1, %2, %3}, [%4];" : "=f"(v.x), "=f"(v.y), "=f"(v.z), "=f"(v.w) : "r"(a) : "memory");
  return v;
}
__device__ __forceinline__ float lds_f(uint32_t a) {
  float v;
  asm volatile("ld.shared.f32 %0, [%1];" : "=f"(v) : "r"(a) : "memory");
  return v;
}
__device__ __forceinline__ uint32_t lds_u(uint32_t a) {
  uint32_t v;
  asm volatile("ld.shared.u32 %0, [%1];" : "=r"(v) : "r"(a) : "memory");
  return v;
}
__device__ __forceinline__ void sts_f2(uint32_t a, float x, float y) {
  asm volatile("st.shared.v2.f32 [%0], {%1, %2};" ::"r"(a), "f"(x), "f"(y) : "memory");
}
__device__ __forceinline__ void lds_u4(uint32_t a, uint32_t& x, uint32_t& y, uint32_t& z, uint32_t& w) {
  asm volatile("ld.shared.v4.u32 {%0, %1, %2, %3}, [%4];" : "=r"(x), "=r"(y), "=r"(z), "=r"(w) : "r"(a) : "memory");
}
__device__ __forceinline__ float ex2(float x) {
  float y;
  asm("ex2.approx.ftz.f32 %0, %1;" : "=f"(y) : "f"(x));
  return y;
}
__device__ __forceinline__ float rcp_hw(float x) {
  float y;
  asm("rcp.approx.ftz.f32 %0, %1;" : "=f"(y) : "f"(x));
  return y;
}
__device__ __forceinline__ float tanh_hw(float x) {
  float y;
  asm("tanh.approx.f32 %0, %1;" : "=f"(y) : "f"(x));
  return y;
}
__device__ __forceinline__ float quad_sum(float v) {
  v += __shfl_xor_sync(0xffffffffu, v, 1);
  return v + __shfl_xor_sync(0xffffffffu, v, 2);
}
__device__ __forceinline__ float quad_max(float v) {
  v = fmaxf(v, __shfl_xor_sync(0xffffffffu, v, 1));
  return fmaxf(v, __shfl_xor_sync(0xffffffffu, v, 2));
}

template <int N> __device__ __forceinline__ void wgmma_ss(float (&d)[96], uint64_t da, uint64_t db);
template <> __device__ __forceinline__ void wgmma_ss<128>(float (&d)[96], uint64_t da, uint64_t db) {
  asm volatile(
      "wgmma.mma_async.sync.aligned.m64n128k16.f32.bf16.bf16 {%0, %1, %2, %3, %4, %5, %6, %7, %8, %9, %10, %11, %12, %13, %14, %15, %16, %17, %18, %19, %20, %21, %22, %23, %24, %25, %26, %27, %28, %29, %30, %31, %32, %33, %34, %35, %36, %37, %38, %39, %40, %41, %42, %43, %44, %45, %46, %47, %48, %49, %50, %51, %52, %53, %54, %55, %56, %57, %58, %59, %60, %61, %62, %63}, %64, %65, 1, 1, 1, 0, 1;"
      : "+f"(d[0]), "+f"(d[1]), "+f"(d[2]), "+f"(d[3]), "+f"(d[4]), "+f"(d[5]), "+f"(d[6]), "+f"(d[7]), "+f"(d[8]), "+f"(d[9]), "+f"(d[10]), "+f"(d[11]), "+f"(d[12]), "+f"(d[13]), "+f"(d[14]), "+f"(d[15]), "+f"(d[16]), "+f"(d[17]), "+f"(d[18]), "+f"(d[19]), "+f"(d[20]), "+f"(d[21]), "+f"(d[22]), "+f"(d[23]), "+f"(d[24]), "+f"(d[25]), "+f"(d[26]), "+f"(d[27]), "+f"(d[28]), "+f"(d[29]), "+f"(d[30]), "+f"(d[31]), "+f"(d[32]), "+f"(d[33]), "+f"(d[34]), "+f"(d[35]), "+f"(d[36]), "+f"(d[37]), "+f"(d[38]), "+f"(d[39]), "+f"(d[40]), "+f"(d[41]), "+f"(d[42]), "+f"(d[43]), "+f"(d[44]), "+f"(d[45]), "+f"(d[46]), "+f"(d[47]), "+f"(d[48]), "+f"(d[49]), "+f"(d[50]), "+f"(d[51]), "+f"(d[52]), "+f"(d[53]), "+f"(d[54]), "+f"(d[55]), "+f"(d[56]), "+f"(d[57]), "+f"(d[58]), "+f"(d[59]), "+f"(d[60]), "+f"(d[61]), "+f"(d[62]), "+f"(d[63])
      : "l"(da), "l"(db));
}

template <> __device__ __forceinline__ void wgmma_ss<192>(float (&d)[96], uint64_t da, uint64_t db) {
  asm volatile(
      "wgmma.mma_async.sync.aligned.m64n192k16.f32.bf16.bf16 {%0, %1, %2, %3, %4, %5, %6, %7, %8, %9, %10, %11, %12, %13, %14, %15, %16, %17, %18, %19, %20, %21, %22, %23, %24, %25, %26, %27, %28, %29, %30, %31, %32, %33, %34, %35, %36, %37, %38, %39, %40, %41, %42, %43, %44, %45, %46, %47, %48, %49, %50, %51, %52, %53, %54, %55, %56, %57, %58, %59, %60, %61, %62, %63, %64, %65, %66, %67, %68, %69, %70, %71, %72, %73, %74, %75, %76, %77, %78, %79, %80, %81, %82, %83, %84, %85, %86, %87, %88, %89, %90, %91, %92, %93, %94, %95}, %96, %97, 1, 1, 1, 0, 1;"
      : "+f"(d[0]), "+f"(d[1]), "+f"(d[2]), "+f"(d[3]), "+f"(d[4]), "+f"(d[5]), "+f"(d[6]), "+f"(d[7]), "+f"(d[8]), "+f"(d[9]), "+f"(d[10]), "+f"(d[11]), "+f"(d[12]), "+f"(d[13]), "+f"(d[14]), "+f"(d[15]), "+f"(d[16]), "+f"(d[17]), "+f"(d[18]), "+f"(d[19]), "+f"(d[20]), "+f"(d[21]), "+f"(d[22]), "+f"(d[23]), "+f"(d[24]), "+f"(d[25]), "+f"(d[26]), "+f"(d[27]), "+f"(d[28]), "+f"(d[29]), "+f"(d[30]), "+f"(d[31]), "+f"(d[32]), "+f"(d[33]), "+f"(d[34]), "+f"(d[35]), "+f"(d[36]), "+f"(d[37]), "+f"(d[38]), "+f"(d[39]), "+f"(d[40]), "+f"(d[41]), "+f"(d[42]), "+f"(d[43]), "+f"(d[44]), "+f"(d[45]), "+f"(d[46]), "+f"(d[47]), "+f"(d[48]), "+f"(d[49]), "+f"(d[50]), "+f"(d[51]), "+f"(d[52]), "+f"(d[53]), "+f"(d[54]), "+f"(d[55]), "+f"(d[56]), "+f"(d[57]), "+f"(d[58]), "+f"(d[59]), "+f"(d[60]), "+f"(d[61]), "+f"(d[62]), "+f"(d[63]), "+f"(d[64]), "+f"(d[65]), "+f"(d[66]), "+f"(d[67]), "+f"(d[68]), "+f"(d[69]), "+f"(d[70]), "+f"(d[71]), "+f"(d[72]), "+f"(d[73]), "+f"(d[74]), "+f"(d[75]), "+f"(d[76]), "+f"(d[77]), "+f"(d[78]), "+f"(d[79]), "+f"(d[80]), "+f"(d[81]), "+f"(d[82]), "+f"(d[83]), "+f"(d[84]), "+f"(d[85]), "+f"(d[86]), "+f"(d[87]), "+f"(d[88]), "+f"(d[89]), "+f"(d[90]), "+f"(d[91]), "+f"(d[92]), "+f"(d[93]), "+f"(d[94]), "+f"(d[95])
      : "l"(da), "l"(db));
}

template <int R>
__device__ __forceinline__ void pin_regs(float (&a)[2][96]) {
#pragma unroll
  for (int m = 0; m < 2; m++)
#pragma unroll
    for (int i = 0; i < R; i++) asm volatile("" : "+f"(a[m][i])::"memory");
}

struct Ctx {
  uint32_t sb;
  int m, n, wg, w, lane;
};
__device__ __forceinline__ Ctx make_ctx(uint32_t sb, int id) {
  int lane;
  asm volatile("mov.u32 %0, %%laneid;" : "=r"(lane));
  asm volatile("" : "+r"(id), "+r"(sb));
  return Ctx{sb, (id >> 3) & 15, id & 7, id >> 9, (id >> 7) & 3, lane};
}
#define UNPACK_CTX(c) const uint32_t sb = c.sb; const int m = c.m, n = c.n, wg = c.wg, w = c.w, lane = c.lane

__device__ __forceinline__ uint32_t poll_line(const uint32_t* word, uint32_t target, uint32_t need) {
  uint32_t v;
  asm volatile(
      "{\n.reg .pred p;\n.reg .u32 it, m;\n.reg .s32 d;\nmov.u32 it, 0;\n"
      "POLL_LOOP:\n"
      "ld.relaxed.gpu.global.u32 %0, [%1];\n"
      "sub.s32 d, %0, %2;\n"
      "setp.ge.s32 p, d, 0;\n"
      "vote.sync.ballot.b32 m, p, 0xffffffff;\n"
      "and.b32 m, m, %3;\n"
      "setp.eq.u32 p, m, %3;\n"
      "@p bra.uni POLL_DONE;\n"
      "add.u32 it, it, 1;\n"
      "setp.lt.u32 p, it, 0x400000;\n"
      "@p bra.uni POLL_LOOP;\n"
      "trap;\n"
      "POLL_DONE:\n}"
      : "=&r"(v) : "l"(word), "r"(target), "r"(need) : "memory");
  return v;
}
__device__ __forceinline__ uint32_t ld_relaxed(const uint32_t* p) {
  uint32_t v;
  asm volatile("ld.relaxed.gpu.global.u32 %0, [%1];" : "=r"(v) : "l"(p) : "memory");
  return v;
}
__device__ __forceinline__ float chain(float x, uint32_t on, uint32_t zero) {
  return __uint_as_float(__float_as_uint(x) | (on & zero));
}
constexpr int MSG_SPINS = 1 << 20;

constexpr int STAGES_PER_LAYER = 152;
__device__ __forceinline__ int nib(uint64_t v, int i) { return (int)(v >> (4 * i)) & 15; }
__device__ __forceinline__ bool tile_wide(int t) { return (0x23 >> t) & 1; }
constexpr uint64_t ORDER_PLAIN = 0xFEDCBA9876543210ull, ORDER_X = 0xFEDCBA9765432180ull, ORDER_FIRST = 0xF7E6D5C4B3A29180ull;

__device__ __forceinline__ void weight_coords(const Params& p, int t, int n, const CUtensorMap*& map, int& c0, int& c2) {
  map = &p.wqkv + nib(0x4233100ull, t);
  c0 = t < 2 ? 128 * n + 64 * t : 0;
  c2 = t < 2 ? 0 : (t == 2 || t == 6) ? 2 * n : 7 * n + 2 * t - 6;
}

template <bool IS_A>
__device__ __forceinline__ void producer(const Params& p, uint32_t sb, int m, int n, int lane) {
  int inflight = 0, rph = 0, min_seen = 0, cur = 0;
  uint32_t b8 = 0, rb8 = 0, pos = 0, tag32 = 0, seen = 0;
  const uint32_t* word = g_flags + m * 32 + (lane & 7);
#pragma unroll 1
  for (int sg = 0; sg < 34; sg++) {
    const int layer = sg >= 17, s = sg == 1 ? 2 : sg == 2 ? 1 : sg - 17 * layer;
    const int t = s < 10 ? nib(0x5434321010ull, s) : 6, kind = s < 10 ? nib(0x2110021100ull, s) : 3;
    const bool wide = tile_wide(t), xtype = t != 2 && t != 6;
    const uint32_t bbytes = wide ? 3 * UNIT : 2 * UNIT;
    const int mul = t == 6 ? 7 : 2, add = t == 6 ? s - 10 : 0, count = 2 * nib(0x4871ull, kind);
    uint64_t order = (sg < 2 ? ORDER_FIRST : xtype ? ORDER_X : ORDER_PLAIN) >> (kind == 1 ? 8 : 0);
    const int nr = sg < 2 ? 0 : n;
    uint32_t lags = s == 9 ? 0x55555545u : wide ? 0x55555555u : (s == 4 || s == 10) ? 0xAAAAAA55u : 0xAAAAAAAAu;
    uint32_t own = t == 2 ? 0x100u : xtype && kind != 1 ? 3u : 0u;
    if (s == 9 || s == 10) pos = (s + 6) * UNIT;
    const CUtensorMap* map;
    int c0 = 0, c2 = 0, ev = 0;
    if (IS_A) {
      map = &p.xin + (t == 2 ? 2 : t == 6 ? 3 : sg >= 4);
      ev = 9 * layer + (t < 2 ? -1 : t == 2 ? 1 : t < 6 ? 3 : nib(0x7776655ull, add));
      if (sg == 3) seen = tag32 = (__ldcg(g_epoch + m * 8 + n) + 1) << 5;
      if (sg >= 4 && (s >= 9 || s == 3 || s == 4)) {
        cur = max(cur, (int)(seen - tag32));
        min_seen = __reduce_min_sync(0xffffffffu, cur);
        asm volatile("fence.acquire.gpu;" ::: "memory");
        fence_async_global();
        seen = ld_relaxed(word);
      }
    } else {
      const int pf = s == 3 ? 2 : s == 4 ? 3 : s == 7 ? 5 : s == 8 ? 6 : sg == 12 ? 0 : -1;
#pragma unroll 1
      for (int tt = pf; tt >= 0 && tt <= pf + (pf == 0 || pf == 3); tt++) {
        weight_coords(p, tt, n, map, c0, c2);
#pragma unroll 1
        for (int kb = m; kb < (tt == 6 ? 56 : 16); kb += 16)
          if (elect_one()) tma_pf3(map, c0, 64 * kb, c2);
      }
      weight_coords(p, t, n, map, c0, c2);
    }
#pragma unroll 1
    for (int k = 0; k < count; k++) {
      const int q = order & 7, hi = (order >> 3) & 1, lag = 2 + (lags & 3);
      const bool local = own & 1;
      order >>= 4;
      lags >>= 2;
      own >>= 1;
      const int src = (((nr & 6) + q) & 7) ^ (q < 2 ? nr & 1 : 0);
      const int kc = 64 * (mul * src + add + hi);
      if (IS_A && !local && min_seen < ev + hi && __shfl_sync(0xffffffffu, cur, src) < ev + hi) {
        cur = (int)(poll_line(word, tag32 + ev + hi, 1u << src) - tag32);
        min_seen = __reduce_min_sync(0xffffffffu, cur);
        asm volatile("fence.acquire.gpu;" ::: "memory");
        fence_async_global();
      }
#pragma unroll 1
      for (; inflight > lag; inflight--) {
        mbar_wait(sb + BAR_EMPTY + rb8, rph);
        rb8 += 8;
        if (rb8 == 8 * NBAR) { rb8 = 0; rph ^= 1; }
      }
      const uint32_t fb = sb + BAR_FULL + b8;
      if (sg < 2 && k < 2) {
      } else if (!IS_A) {
        if (elect_one()) {
          mbar_expect_tx(fb, bbytes);
          tma_ld3(sb + pos, map, fb, c0, kc, c2);

        }
      } else if (!local) {
        if (elect_one()) {
          mbar_expect_tx(fb, 16384);
          tma_ld2(sb + pos + bbytes, map, fb, kc, 128 * m);
        }
      } else {
        if (t == 2) mbar_wait(sb + BAR_PUB + 8, layer);
        else if (k == 1 && (s == 0 || s == 5)) mbar_wait(sb + BAR_XRDY + 8, s == 5);
        if (elect_one()) mbar_arrive(fb);
      }
      inflight++;
      b8 += 8;
      if (b8 == 8 * NBAR) b8 = 0;
      pos += bbytes + 2 * UNIT;
      if (pos >= RING_UNITS * UNIT) pos -= RING_UNITS * UNIT;
    }
  }
}

__device__ __forceinline__ void publisher(const Params& p, uint32_t sb, int m, int n) {
  const uint32_t tag = __ldcg(g_epoch + m * 8 + n) + 1;
  uint32_t* word = g_flags + m * 32 + n;
  const int mn = m * 8 + n; (void)mn;
  st_relaxed(word, 32 * tag);
#pragma unroll 1
  for (int c = 0; c < 18; c++) {
    const int e = c >= 9 ? c - 9 : c;
    if ((0x18C >> e) & 1) {
      const int half = (0x108 >> e) & 1;
      mbar_wait(sb + BAR_XRDY + 8 * half, e < 4);
#pragma unroll
      for (int w = 0; w < 4; w++) tma_st2(&p.out_st, sb + OFF_X + half * 16384 + w * 4096, 128 * n + 64 * half, 128 * m + 32 * w);
      bulk_commit();
      if (c >= 16) continue;
      bulk_wait_all();
      PROF_E(7 * (c >= 9) + (e < 4 ? 2 : 6), 11 + 2 * half);
    } else {
      mbar_wait(sb + BAR_PUB + 8 * e, c >= 9);
    }
    asm volatile("fence.release.gpu;" ::: "memory");
    st_relaxed(word, 32 * tag + c + 1);
    PROF_E(7 * (c >= 9) + nib(0x665432210ull, e), (0x108 >> e) & 1 ? 14 : 12);
  }
  g_epoch[m * 8 + n] = tag;
  bulk_wait_read();
}

__device__ __forceinline__ void sum_rows(uint32_t buf, int iters, float (&a)[8], int lane) {
  uint32_t addr = buf + (lane >> 3) * 128 + (((lane & 7) ^ (lane >> 3)) << 4);
#pragma unroll 1
  for (int it = 0; it < iters; it++) {
    uint32_t u[2][4];
    lds_u4(addr, u[0][0], u[0][1], u[0][2], u[0][3]);
    lds_u4((addr ^ 64) + 512, u[1][0], u[1][1], u[1][2], u[1][3]);
    addr += 1024;
#pragma unroll
    for (int e = 0; e < 8; e++) { a[2 * (e & 3)] += bf_lo(u[e >> 2][e & 3]); a[2 * (e & 3) + 1] += bf_hi(u[e >> 2][e & 3]); }
  }
}
__device__ __forceinline__ void publish_sums(const float (&a)[8], uint4* dst, int lane, uint32_t tag) {
  const bool u8 = lane & 8, u16 = lane & 16;
  float h4[4], h2[2];
#pragma unroll
  for (int e = 0; e < 4; e++) h4[e] = (u8 ? a[4 + e] : a[e]) + __shfl_xor_sync(0xffffffffu, u8 ? a[e] : a[4 + e], 8);
#pragma unroll
  for (int e = 0; e < 2; e++) h2[e] = (u16 ? h4[2 + e] : h4[e]) + __shfl_xor_sync(0xffffffffu, u16 ? h4[e] : h4[2 + e], 16);
  st_msg(dst + (lane & 7) * 4 + (u8 ? 2 : 0) + (u16 ? 1 : 0), __float_as_uint(h2[0]), __float_as_uint(h2[1]), 0u, tag);
}

__device__ __forceinline__ void colsum_helper(const Params& p, uint32_t sb, int m, int n, int lane) {
  const uint32_t tag = __ldcg(g_epoch + m * 8 + n) + 1;
  const int mn = m * 8 + n; (void)mn;
#pragma unroll 1
  for (int k = lane; k < 288; k += 32) {
    const uint32_t bb = __ldg(reinterpret_cast<const uint32_t*>(k < 224 ? p.b1 + 448 * n : p.b2 + 128 * n - 448) + k);
    const float sc = k < 224 ? 0.5f : 1.f;
    sts_f2(sb + (k < 224 ? OFF_CSF + k * 16 + 8 : OFF_CSQ + 1536 + (k - 224) * 8), sc * bf_lo(bb), sc * bf_hi(bb));
  }
  __syncwarp();
  if (elect_one()) mbar_arrive(sb + BAR_BIAS);
  PROF_E(-1, 1);
#pragma unroll 1
  for (int c = 0; c < 7; c++) {
    float a[8] = {0.f, 0.f, 0.f, 0.f, 0.f, 0.f, 0.f, 0.f};
#pragma unroll 1
    for (int h = 0; h < 2; h++) {
      if (elect_one()) {
        mbar_expect_tx(sb + BAR_CSLD + 8, 4096);
        tma_ld2(sb + OFF_HLP, &p.w1c, sb + BAR_CSLD + 8, 448 * n + 64 * c, 64 * m + 32 * h);
        if (c < 6) asm volatile("cp.async.bulk.prefetch.tensor.2d.L2.global [%0, {%1, %2}];" ::"l"(&p.w1c), "r"(448 * n + 64 * c + 64), "r"(64 * m + 32 * h) : "memory");
      }
      mbar_wait(sb + BAR_CSLD + 8, h);
      sum_rows(sb + OFF_HLP, 4, a, lane);
      __syncwarp();
    }
    publish_sums(a, g_csp + ((8 + n) * 17 + m) * 224 + c * 32, lane, tag);
  }
  PROF_E(-1, 2);
}

__device__ __forceinline__ void poll_msgs2(const uint4* pa, const uint4* pb, float (&v)[4], uint32_t tag) {
#pragma unroll 1
  for (int it = 0; it < MSG_SPINS; it++) {
    uint32_t x[4], z, ta, tb;
    ld_msg(pa, x[0], x[1], z, ta);
    ld_msg(pb, x[2], x[3], z, tb);
#pragma unroll
    for (int e = 0; e < 4; e++) v[e] = __uint_as_float(x[e]);
    if (__all_sync(0xffffffffu, ta == tag && tb == tag)) break;
  }
}
__device__ __forceinline__ void colsum_total(const Ctx& cx, int mat, uint32_t tag) {
  uint4* base = g_csp + (mat * 8 + cx.n) * 17 * 224;
  const int per = 12 + 2 * mat, k = 2 * cx.w + (cx.lane >> 4), ia = per * cx.m + k, ib = per * cx.m + min(k + 8, per - 1);
  float v[4];
  poll_msgs2(base + (cx.lane & 15) * 224 + ia, base + (cx.lane & 15) * 224 + ib, v, tag);
#pragma unroll 1
  for (int d = 1; d < 16; d *= 2)
#pragma unroll
    for (int e = 0; e < 4; e++) v[e] += __shfl_xor_sync(0xffffffffu, v[e], d);
  const bool hi = cx.lane & 1;
  if ((cx.lane & 14) == 0) st_msg(base + 16 * 224 + (hi ? ib : ia), __float_as_uint(hi ? v[2] : v[0]), __float_as_uint(hi ? v[3] : v[1]), 0u, tag);
}
__device__ __forceinline__ void colsum_gather(const Ctx& cx, int mat, uint32_t tag) {
  const uint4* base = g_csp + ((mat * 8 + cx.n) * 17 + 16) * 224;
  const int ia = cx.w * 32 + cx.lane, ib = min(ia + 128, 191 + 32 * mat);
  float v[4];
  poll_msgs2(base + ia, base + ib, v, tag);
  const uint32_t tab = cx.sb + (mat ? OFF_CSF : OFF_CSQ);
  sts_f2(tab + (ia << (3 + mat)), v[0], v[1]);
  sts_f2(tab + (ib << (3 + mat)), v[2], v[3]);
}

template <int N>
__device__ __forceinline__ void mainloop(float (&acc)[2][96], uint32_t sb, int i, int part, int mn) {
  constexpr uint32_t Z16 = (2 + N / 64) * (UNIT >> 4), RING16 = RING_UNITS * (UNIT >> 4);
  constexpr uint32_t A_OFF = Z16 - 1024 + (uint32_t)DESC_A - (uint32_t)DESC_B;
  const int wg = i & 1;
  const int layer = i >= 7, t = i - 7 * layer;
  const bool own = t != 2 && t != 6 && part != 1 && i != 0, second = t == 1 || t == 4;
  const int gl = 16 * t + (part == 2 ? 0 : second ? 16 * part - 14 : 4 * part), g0 = layer * STAGES_PER_LAYER + gl;
  const uint32_t s16 = (sb & 0x3FFFF) >> 4;
  const uint32_t bfirst = (uint32_t)DESC_B + s16;
  const uint32_t blast = uniform(bfirst + RING16 - Z16), flast = uniform(sb + BAR_FULL + 8 * (NBAR - 1));
  const int nkb = t == 6 ? 56 : part == 0 ? 2 : 12 + 2 * part;
  const bool win1 = t == 1 && part != 0;
  int run = uniform(win1 ? WIN1 + 1 : t == 2 ? WIN2 + 1 : nkb);
  int rest = win1 ? 64 | (nkb - 1 - WIN1) : t == 2 ? 64 | (7 - WIN2) | (8 << 7) : 0;
  uint32_t fb = sb + BAR_FULL + 8 * (g0 % NBAR), ph = (g0 / NBAR) & 1;
  uint32_t prev = sb + BAR_DUMMY - 8 * NBAR;
  uint32_t blo = bfirst + Z16 * (N == 192 ? (gl + (t == 5 ? 3 : 0)) & 3 : (gl + 3) % 5);
  uint32_t alo = own ? (uint32_t)DESC_A + s16 + (OFF_X >> 4) : blo + A_OFF;
  uint32_t aoff = own ? alo + 1024 - (blo == blast ? bfirst : blo + Z16) : A_OFF;
  pin_regs<N / 2>(acc);
  if (N == 192 && i == 0 && threadIdx.x == 0) PROF_U(7);
  bar_sync(i > 0 ? BAR_ORDER + wg : BAR_INIT, i > 0 ? 256 : 384);
  if (N == 192 && i == 0 && threadIdx.x == 0) PROF_U(8);
  if (t == (N == 192 ? 0 : 3) && part == 0) mbar_wait(sb + BAR_XRDY, N == 128);
  if (N == 192 && i == 0 && threadIdx.x == 0) PROF_U(9);
  mbar_wait(fb, ph);
  if (part != 1) PROF_T(4 + i * 4);
#pragma unroll 1
  while (true) {
    const uint64_t da = (DESC_A & ~0xffffffffull) | alo, db = (DESC_B & ~0xffffffffull) | blo;
    asm volatile("wgmma.fence.sync.aligned;" ::: "memory");
    wgmma_ss<N>(acc[0], da, db);
    wgmma_ss<N>(acc[1], da + 64, db);
    wgmma_ss<N>(acc[0], da + 2, db + 128);
    wgmma_ss<N>(acc[1], da + 66, db + 128);
    asm volatile("wgmma.commit_group.sync.aligned;" ::: "memory");
    asm volatile("wgmma.wait_group.sync.aligned 1;" ::: "memory");
    PROF_S(g0 + jj++);
    if (elect_one()) mbar_arrive(prev + 8 * NBAR);
    prev = fb;
    if (fb == flast) { fb -= 8 * NBAR; ph++; }
    fb += 8;
    if (blo == blast) blo -= RING16;
    blo += Z16;
    alo = blo + aoff;
    aoff = A_OFF;
    run--;
    const bool ready = mbar_test(fb, ph) && run != 0;
    asm volatile("wgmma.fence.sync.aligned;" ::: "memory");
    wgmma_ss<N>(acc[0], da + 4, db + 256);
    wgmma_ss<N>(acc[1], da + 68, db + 256);
    wgmma_ss<N>(acc[0], da + 6, db + 384);
    wgmma_ss<N>(acc[1], da + 70, db + 384);
    asm volatile("wgmma.commit_group.sync.aligned;" ::: "memory");
    if (!ready) {
      if (run == 0) {
        if (rest == 0) break;
        if (rest & 64) {
          bar_arrive(BAR_GO, 256);
          bar_sync(BAR_DONE, 256);
        } else {
          alo = (uint32_t)DESC_A + s16 + (OFF_STG >> 4);
        }
        run = rest & 63;
        rest >>= 7;
      }
      mbar_wait(fb, ph);
    }
  }
  if (i < 13) bar_arrive(BAR_ORDER + (wg ^ 1), 256);
  asm volatile("wgmma.wait_group.sync.aligned 0;" ::: "memory");
  pin_regs<N / 2>(acc);
  if (elect_one()) mbar_arrive(prev + 8 * NBAR);
  PROF_T(5 + i * 4);
  PROF_E(i, 0);
}

#define ACC(q, j, e) acc[(q) & 1][4 * (j) + 2 * ((q) >> 1) + (e)]

__device__ __forceinline__ void write_partial_stats(const Ctx& c, int ln, uint32_t tag) {
  const uint32_t xrow = c.sb + OFF_X + c.w * 4096 + c.lane * 128;
  float s = 0.f, q = 0.f;
#pragma unroll 2
  for (int j = 0; j < 16; j++) {
    uint32_t u[4];
    lds_u4(xrow + (j >> 3) * 16384 + (((j & 7) ^ (c.lane & 7)) << 4), u[0], u[1], u[2], u[3]);
#pragma unroll
    for (int e = 0; e < 4; e++) {
      const float a = bf_lo(u[e]), d = bf_hi(u[e]);
      s += a; q = fmaf(a, a, q);
      s += d; q = fmaf(d, d, q);
    }
  }
  st_msg(g_stats + (ln * 8 + c.n) * SEQ + 128 * c.m + 32 * c.w + c.lane, __float_as_uint(s),
         __float_as_uint(fmaxf(q - s * s * (1.f / 128.f), 0.f)), 0u, tag);
}

__device__ __forceinline__ void finish_row_stats(const Ctx& c, int ln, uint32_t tag) {
  const uint4* src = g_stats + ln * 8 * SEQ + 128 * c.m + 32 * c.w + c.lane;
  uint32_t ps[8], pm[8];
#pragma unroll 1
  for (int it = 0; it < MSG_SPINS; it++) {
    uint32_t bad = 0, u, tg;
#pragma unroll
    for (int k = 0; k < 8; k++) { ld_msg(src + k * SEQ, ps[k], pm[k], u, tg); bad |= tg ^ tag; }
    if (__all_sync(0xffffffffu, bad == 0)) break;
  }
  float s = 0.f, m2 = 0.f;
#pragma unroll
  for (int k = 0; k < 8; k++) s += __uint_as_float(ps[k]);
  const float mean = s * (1.f / DM);
#pragma unroll
  for (int k = 0; k < 8; k++) {
    const float d = __uint_as_float(ps[k]) * (1.f / 128.f) - mean;
    m2 += fmaf(128.f * d, d, __uint_as_float(pm[k]));
  }
  sts_f2(c.sb + OFF_ROW + (32 * c.w + c.lane) * 8, rsqrtf(m2 * (1.f / DM) + 1e-5f), mean);
  __syncwarp();
}

__device__ __forceinline__ void attn_scores(const uint32_t* qa, const uint32_t* qb, const uint32_t* k0, const uint32_t* k1,
                                            const uint32_t* k2, const uint32_t* k3, float (&l)[4], const float4& zero,
                                            bool par, bool early) {
  float s[4][4];
#pragma unroll
  for (int kb = 0; kb < 4; kb++) {
    const uint32_t* kk = kb == 0 ? k0 : kb == 1 ? k1 : kb == 2 ? k2 : k3;
    asm volatile("mma.sync.aligned.m16n8k16.row.col.f32.bf16.bf16.f32 {%0,%1,%2,%3}, {%4,%5,%6,%7}, {%8,%9}, {%10,%11,%12,%13};"
                 : "=f"(s[kb][0]), "=f"(s[kb][1]), "=f"(s[kb][2]), "=f"(s[kb][3])
                 : "r"(qa[0]), "r"(qb[0]), "r"(qa[1]), "r"(qb[1]), "r"(kk[0]), "r"(kk[1]), "f"(zero.x), "f"(zero.y),
                   "f"(zero.z), "f"(zero.w));
  }
#pragma unroll
  for (int kb = 0; kb < 4; kb++) {
    const uint32_t* kk = kb == 0 ? k0 : kb == 1 ? k1 : kb == 2 ? k2 : k3;
    mma16816(s[kb], qa[2], qb[2], qa[3], qb[3], kk[2], kk[3]);
  }
  l[0] = par ? s[1][1] : s[1][0];
  l[1] = early ? (par ? s[0][1] : s[0][0]) : (par ? s[2][1] : s[2][0]);
  l[2] = par ? s[2][3] : s[2][2];
  l[3] = early ? (par ? s[1][3] : s[1][2]) : (par ? s[3][3] : s[3][2]);
}

__device__ __forceinline__ void attn_mix(const float (&l)[4], const float (&sc)[4], const float (&off)[4], const float (&rk)[4],
                                         const uint32_t* v0, const uint32_t* v1, const uint32_t* v2, const uint32_t* v3,
                                         float (&o)[4][4], bool par, bool early) {
  float x[4];
#pragma unroll
  for (int e = 0; e < 4; e++) x[e] = fmaf(l[e], sc[e], off[e]);
  const float ml = quad_max(fmaxf(x[0], x[1])), mh = quad_max(fmaxf(x[2], x[3]));
  x[0] = ex2(x[0] - ml); x[1] = ex2(x[1] - ml);
  x[2] = ex2(x[2] - mh); x[3] = ex2(x[3] - mh);
  const float il = rcp_hw(quad_sum(x[0] + x[1])), ih = rcp_hw(quad_sum(x[2] + x[3]));
  const uint32_t pl = pack_bf16(x[0] * rk[0] * il, x[1] * rk[1] * il), ph = pack_bf16(x[2] * rk[2] * ih, x[3] * rk[3] * ih);
  const uint32_t sel_a = par ? 0x1044u : 0x4410u, sel_b = par ? 0x3244u : 0x4432u;
  const uint32_t sel_e = early ? sel_b : 0x4444u, sel_l = early ? 0x4444u : sel_b;
  const uint32_t pla = __byte_perm(pl, 0, sel_a), pha = __byte_perm(ph, 0, sel_a);
  const uint32_t e_l = __byte_perm(pl, 0, sel_e), e_h = __byte_perm(ph, 0, sel_e);
  const uint32_t l_l = __byte_perm(pl, 0, sel_l), l_h = __byte_perm(ph, 0, sel_l);
#pragma unroll
  for (int jn = 0; jn < 4; jn++) {
    o[jn][0] = o[jn][1] = o[jn][2] = o[jn][3] = 0.f;
    mma16816(o[jn], e_l, 0u, pla, e_h, v0[jn], v1[jn]);
  }
#pragma unroll
  for (int jn = 0; jn < 4; jn++) mma16816(o[jn], l_l, pha, 0u, l_h, v2[jn], v3[jn]);
}

__device__ __forceinline__ void gelu_epilogue(const Params& p, float (&acc)[2][96], const Ctx& cx, int t) {
  UNPACK_CTX(cx);
  (void)wg;
  float rs[4], rm[4];
#pragma unroll
  for (int q = 0; q < 4; q++) {
    const float2 v = lds_f2(sb + OFF_ROW + (32 * w + 8 * q + (lane >> 2)) * 8);
    rs[q] = 0.5f * v.x;
    rm[q] = -rs[q] * v.y;
  }
  const int col0 = 128 * (t - 3), steps = t == 5 ? 6 : 4;
  const uint32_t stg = sb + OFF_STG + w * 4096;
  uint32_t ctab = sb + OFF_CSF + (col0 / 2 + (lane & 3)) * 16;
  float v[2][16];
#pragma unroll
  for (int r = 0; r < 16; r++) { v[0][r] = acc[0][r]; v[1][r] = acc[1][r]; }
#pragma unroll 1
  for (int it = 0; it < steps; it++) {
    uint32_t hp[4][4];
#pragma unroll
    for (int j = 0; j < 4; j++) {
      const float4 cb = lds_f4(ctab + j * 64);
#pragma unroll
      for (int q = 0; q < 4; q++) {
        float y[2];
        const int k = 4 * j + q - GELU_DEP;
        const float rmq = k >= 0 ? chain(rm[q], hp[k >> 2][k & 3], p.zero) : rm[q];
#pragma unroll
        for (int e = 0; e < 2; e++) {
          const float z = fmaf(v[q & 1][4 * j + 2 * (q >> 1) + e], rs[q], fmaf(rmq, e ? cb.y : cb.x, e ? cb.w : cb.z));
          const float u = z * fmaf(z * z, 8.f * 0.7978845608028654f * 0.044715f, 2.f * 0.7978845608028654f);
          y[e] = fmaf(z, tanh_hw(u), z);
        }
        hp[j][q] = pack_bf16(y[0], y[1]);
      }
    }
    ctab += 256;
    if (!(it & 1)) {
      if (lane == 0) bulk_wait_read();
      __syncwarp();
    }
#pragma unroll
    for (int j = 0; j < 4; j++)
      stsm4(stg + lane * 128 + (((4 * (it & 1) + j) ^ (lane & 7)) << 4), hp[j][0], hp[j][1], hp[j][2], hp[j][3]);
    if (it & 1) {
      fence_async_smem();
      __syncwarp();
      if (lane == 0) {
        tma_st2(&p.h_st, stg, 448 * n + col0 + 32 * (it - 1), 128 * m + 32 * w);
        bulk_commit();
      }
      if (it == steps - 1) break;
    }
    const uint32_t zr = hp[3][3] & p.zero;
#define REFILL(k) _Pragma("unroll") for (int r = 0; r < 32; r++) \
      asm volatile("{\n.reg .b32 t;\nmov.b32 t, %1;\nor.b32 t, t, %2;\nmov.b32 %0, t;\n}" \
                   : "=f"(v[r >> 4][r & 15]) : "f"(acc[r >> 4][16 * k + (r & 15)]), "r"(zr)); break;
    switch (it) {
      case 0: REFILL(1)
      case 1: REFILL(2)
      case 2: REFILL(3)
      case 3: REFILL(4)
      default: REFILL(5)
    }
#undef REFILL
  }
}

__device__ __forceinline__ void attn_epilogue(const Params& p, float (&acc)[2][96], const Ctx& cx, int layer, int t, uint32_t tag) {
  UNPACK_CTX(cx);
  const bool par = (lane >> 2) & 1, early = (lane & 3) > (lane >> 3);
  uint32_t Q[4][8], K[4][8], V[4][8];
  float kr[6], qr[4];
#pragma unroll
  for (int q = 0; q < 4; q++) {
    kr[2 + q] = lds_f(sb + OFF_ROW + (32 * w + 8 * q + 2 * (lane & 3) + par) * 8);
    qr[q] = lds_f(sb + OFF_ROW + (32 * w + 8 * q + (lane >> 2)) * 8) * (0.17677669529663687f * 1.4426950408889634f);
  }
  const int slot = ((layer * 2 + t) * 16 + m) * 8 + n;
  uint4* const exc = reinterpret_cast<uint4*>(__cvta_shared_to_generic(sb + OFF_STG));
#pragma unroll
  for (int qq = 0; qq < 4; qq++) {
    const int q = qq ^ 2;
#pragma unroll
    for (int j = 0; j < 8; j++) {
      K[q][j] = pack_bf16(ACC(q, 8 + j, 0), ACC(q, 8 + j, 1));
      V[q][j] = movtrans(pack_bf16(ACC(q, 16 + j, 0), ACC(q, 16 + j, 1)));
    }
    if (qq == 1) {
      uint4* e = (w < 3 ? exc + w * 512 : g_halo + slot * 512) + lane;
#pragma unroll
      for (int j = 0; j < 8; j++) {
        st_msg(e + j * 32, K[2 + (j >> 2)][2 * (j & 3)], K[2 + (j >> 2)][2 * (j & 3) + 1], __float_as_uint(kr[4]), tag);
        st_msg(e + (8 + j) * 32, V[2][j], V[3][j], __float_as_uint(kr[5]), tag);
      }
    }
  }
#pragma unroll
  for (int q = 0; q < 4; q++)
#pragma unroll
    for (int j = 0; j < 8; j++) Q[q][j] = pack_bf16(ACC(q, j, 0), ACC(q, j, 1));
  const int mn = m * 8 + n; (void)mn;
  PROF_E(7 * layer + t, 1);
  bar_sync(BAR_WG + wg, 128);
  const uint4* src = (w > 0 ? exc + (w - 1) * 512 : m > 0 ? g_halo + (slot - 8) * 512 : exc) + lane;
  uint32_t PK[2][8], PV[2][8], r4, r5;
#pragma unroll 1
  for (int it = 0; it < MSG_SPINS; it++) {
    uint32_t tg, bad = 0;
#pragma unroll
    for (int j = 0; j < 8; j++) {
      ld_msg(src + j * 32, PK[j >> 2][2 * (j & 3)], PK[j >> 2][2 * (j & 3) + 1], r4, tg); bad |= tg ^ tag;
      ld_msg(src + (8 + j) * 32, PV[0][j], PV[1][j], r5, tg); bad |= tg ^ tag;
    }
    if (__all_sync(0xffffffffu, bad == 0)) break;
  }
  kr[0] = __uint_as_float(r4);
  kr[1] = __uint_as_float(r5);
  float rk[2][4], sc[2][4], off[2][4];
#pragma unroll
  for (int g = 0; g < 2; g++) {
    rk[g][0] = kr[2 * g + 1];
    rk[g][1] = early ? kr[2 * g] : kr[2 * g + 2];
    rk[g][2] = kr[2 * g + 2];
    rk[g][3] = early ? kr[2 * g + 1] : kr[2 * g + 3];
#pragma unroll
    for (int e = 0; e < 4; e++) {
      const bool masked = g == 0 && e != 2 && (m | w) == 0 && (e == 0 || early);
      sc[g][e] = masked ? 0.f : rk[g][e] * qr[2 * g + (e >> 1)];
      off[g][e] = masked ? -1e30f : 0.f;
    }
  }
  PROF_E(7 * layer + t, 2);
  bar_sync(BAR_GO, 256);
  PROF_E(7 * layer + t, 3);
  const float4 zero = lds_f4(sb + OFF_ZERO);
  float l[2][2][4], o[2][2][4][4];
#pragma unroll
  for (int h = 0; h < 2; h++) {
    attn_scores(&Q[2][4 * h], &Q[3][4 * h], &K[0][4 * h], &K[1][4 * h], &K[2][4 * h], &K[3][4 * h], l[1][h], zero, par, early);
    attn_scores(&Q[0][4 * h], &Q[1][4 * h], &PK[0][4 * h], &PK[1][4 * h], &K[0][4 * h], &K[1][4 * h], l[0][h], zero, par, early);
  }
#pragma unroll
  for (int h = 0; h < 2; h++) {
    attn_mix(l[1][h], sc[1], off[1], rk[1], &V[0][4 * h], &V[1][4 * h], &V[2][4 * h], &V[3][4 * h], o[1][h], par, early);
    attn_mix(l[0][h], sc[0], off[0], rk[0], &PV[0][4 * h], &PV[1][4 * h], &V[0][4 * h], &V[1][4 * h], o[0][h], par, early);
  }
  const uint32_t stg = sb + OFF_STG + w * 4096;
#pragma unroll
  for (int j = 0; j < 8; j++) {
    const float(&a)[4] = o[0][j >> 2][j & 3];
    const float(&c)[4] = o[1][j >> 2][j & 3];
    stsm4(stg + lane * 128 + ((j ^ (lane & 7)) << 4), pack_bf16(a[0], a[1]), pack_bf16(a[2], a[3]), pack_bf16(c[0], c[1]),
          pack_bf16(c[2], c[3]));
  }
  bar_arrive(BAR_DONE, 256);
  fence_async_smem();
  __syncwarp();
  if (lane == 0) {
    tma_st2(&p.att_st, stg, 128 * n + 64 * t, 128 * m + 32 * w);
    bulk_commit();
  }
}

__device__ __forceinline__ void consumer_tile(const Params& p, uint32_t sb0, int i, int mn) {
  const int layer = i >= 7, t = i - 7 * layer, wg = i & 1;
  const bool resid = t == 2 || t == 6;
  {
    float acc[2][96];
    if (resid) {
      const Ctx cx = make_ctx(sb0, mn);
      const uint32_t xrow = cx.sb + OFF_X + cx.w * 4096 + cx.lane * 128;
      const uint32_t sel_lo = 0x1044u | p.zero, sel_hi = 0x3244u | p.zero;
#pragma unroll
      for (int j = 0; j < 16; j++) {
        uint32_t r[4];
        ldsm4(xrow + (j >> 3) * 16384 + (((j & 7) ^ (cx.lane & 7)) << 4), r[0], r[1], r[2], r[3]);
#pragma unroll
        for (int q = 0; q < 4; q++) {
          ACC(q, j, 0) = prmt_f(r[q], sel_lo);
          ACC(q, j, 1) = prmt_f(r[q], sel_hi);
        }
      }
    } else {
#pragma unroll
      for (int r = 0; r < 64; r++) acc[0][r] = acc[1][r] = 0.f;
    }
#pragma unroll
    for (int r = 64; r < 96; r++) acc[0][r] = acc[1][r] = 0.f;
    const bool split = t == 3 || t == 4 || i == 7 || i == 8;
#pragma unroll 1
    for (int step = split ? 0 : 1;; step++) {
      if (step == 1 && (t == 1 || t == 4)) {
        const Ctx cx = make_ctx(sb0, mn);
        if (i == 1) {
          asm volatile("st.shared.u32 [%0], %1;" ::"r"(sb0 + OFF_TAG), "r"(__ldcg(g_epoch + (mn & 127)) + 1) : "memory");
          bar_sync(BAR_INIT, 384);
        }
        const uint32_t tag = lds_u(cx.sb + OFF_TAG);
        const int ln = (i + 1) >> 2;
#pragma unroll 1
        for (int r = 0; r < 2; r++) {
          if (i == 1) {
            if (cx.w < 3) {
              float a[8] = {0.f, 0.f, 0.f, 0.f, 0.f, 0.f, 0.f, 0.f};
              mbar_wait(sb0 + BAR_CSLD, r);
              sum_rows(cx.sb + OFF_STG + cx.w * 8192, 8, a, cx.lane);
              publish_sums(a, g_csp + (cx.n * 17 + cx.m) * 224 + (3 * r + cx.w) * 32, cx.lane, tag);
            }
            PROF_E(-1, 5 + r);
          }
          if (r == 1) break;
          if (i == 1) {
            bar_sync(BAR_WG + 1, 128);
            if (cx.w == 3 && elect_one()) {
              mbar_expect_tx(sb0 + BAR_CSLD, 24576);
              tma_ld3(sb0 + OFF_STG, &p.wqkv, sb0 + BAR_CSLD, 128 * cx.n + 64, 64 * cx.m, 0);
            }
            mbar_wait(sb0 + BAR_XRDY, 0);
            mbar_wait(sb0 + BAR_XRDY + 8, 0);
          }
          write_partial_stats(cx, ln, tag);
          PROF_E(i - 2, 8);
        }
        if (i <= 4) colsum_total(cx, ln, tag);
        PROF_E(i - 2, 9);
        if (i != 1) bar_sync(BAR_GUARD + wg, 256);
        finish_row_stats(cx, ln, tag);
        PROF_E(i - 2, 10);
        if (i <= 4) {
          colsum_gather(cx, ln, tag);
          if (i == 4) mbar_wait(sb0 + BAR_BIAS, 0);
          bar_sync(BAR_WG + wg, 128);
        }
        PROF_E(i - 2, 15);
        bar_arrive(BAR_GUARD + (wg ^ 1), 256);
      }
      if (step == 2 && !resid) bar_sync(BAR_GUARD + wg, 256);
      if (t + step == 2 || t == 6) {
        const Ctx cx = make_ctx(sb0, mn);
        float nm[4];
#pragma unroll
        for (int q = 0; q < 4; q++) nm[q] = t == 6 ? 1.f : -lds_f(cx.sb + OFF_ROW + (32 * cx.w + 8 * q + (cx.lane >> 2)) * 8 + 4);
        const uint32_t ctab = cx.sb + OFF_CSQ + ((t & 3) * 192 + 2 * (cx.lane & 3)) * 4;
#pragma unroll
        for (int j = 0; j < 24; j++) {
          const float2 cs = lds_f2(ctab + j * 32);
#pragma unroll
          for (int q = 0; q < 4; q++) {
            const int k = 4 * j + q - 1;
            const float nq = k >= 0 ? chain(nm[q], __float_as_uint(ACC(k & 3, k >> 2, 1)), p.zero) : nm[q];
            ACC(q, j, 0) = fmaf(nq, cs.x, ACC(q, j, 0));
            ACC(q, j, 1) = fmaf(nq, cs.y, ACC(q, j, 1));
          }
        }
      }
      if (step == 2) break;
      if (tile_wide(t)) {
        mainloop<192>(acc, sb0, i, split ? step : 2, mn);
      } else {
        mainloop<128>(acc, sb0, i, split ? step : 2, mn);
        if (resid) break;
      }
    }
    const Ctx cx = make_ctx(sb0, mn);
    if (resid) {
      const uint32_t xrow = cx.sb + OFF_X + cx.w * 4096 + cx.lane * 128;
#pragma unroll
      for (int j = 0; j < 16; j++) {
        stsm4(xrow + (j >> 3) * 16384 + (((j & 7) ^ (cx.lane & 7)) << 4), pack_bf16(ACC(0, j, 0), ACC(0, j, 1)),
              pack_bf16(ACC(1, j, 0), ACC(1, j, 1)), pack_bf16(ACC(2, j, 0), ACC(2, j, 1)), pack_bf16(ACC(3, j, 0), ACC(3, j, 1)));
        if ((j & 7) == 7) {
          fence_async_smem();
          __syncwarp();
          if (elect_one()) mbar_arrive(sb0 + BAR_XRDY + (j & 8));
        }
      }
      PROF_E(i, 4);
      return;
    }
    if (t < 2) attn_epilogue(p, acc, cx, layer, t, lds_u(sb0 + OFF_TAG));
    else gelu_epilogue(p, acc, cx, t);
    PROF_E(i, 4);
    if (cx.lane == 0) {
      bulk_wait_all();
      mbar_arrive(sb0 + BAR_PUB + 8 * (t < 2 ? t : t + 1));
    }
    __syncwarp();
    PROF_E(i, 5);
    if (i < 12) bar_arrive(BAR_GUARD + (wg ^ 1), 256);
  }
}

__global__ void __launch_bounds__(384, 1) fused_layers_kernel(const int by_smid, const __nv_bfloat16* x_p, const __nv_bfloat16* wqkv_p,
                                                                  const __grid_constant__ Params p) {
  extern __shared__ __align__(1024) uint8_t smem_raw[];
  const uint32_t sb = uniform((uint32_t)__cvta_generic_to_shared(smem_raw));
  const int tid = threadIdx.x, lane = tid & 31, warp = uniform(tid >> 5), wg = warp >> 2, w = warp & 3;

  int mn;
  {
    int id = blockIdx.x;
    if (by_smid) asm volatile("mov.u32 %0, %%smid;" : "=r"(id));
    else if (id >= 120) id += 4;
    const int c = id >> 1;
    int g, j;
    if (c < 32) { g = c & 7; j = c >> 3; }
    else if (c < 60) { g = 1 + (c - 32) % 7; j = 4 + (c - 32) / 7; }
    else { g = 0; j = c - 58; }
    mn = ((g >> 2) * 8 + j) * 8 + (g & 3) * 2 + (id & 1);
    if (c == 60 || c == 61) {
      if (tid < 32) {
        const uint32_t tag = __ldcg(g_epoch + NCTA + (id & 3)) + 1;
#pragma unroll 1
        for (int mm = 0; mm < 16; mm++) poll_line(g_flags + mm * 32 + (lane & 7), 32 * tag, 0xffu);
        if (tid == 0) g_epoch[NCTA + (id & 3)] = tag;
      }
      return;
    }
  }
  const int m = mn >> 3, n = mn & 7;
  if (tid == 256) PROF_U(1);
  if (tid >= 382) asm volatile("prefetch.global.L2 [%0];" ::"l"(tid & 1 ? wqkv_p + 128 * n : x_p + 128 * m * DM));
  if (wg < 2) {
    asm volatile("setmaxnreg.inc.sync.aligned.u32 232;");
#pragma unroll 1
    for (int i = wg; i < 14; i += 2) {
      consumer_tile(p, sb, i, mn | (warp << 7));
      PROF_T(6 + i * 4);
    }
  } else {
    asm volatile("setmaxnreg.dec.sync.aligned.u32 40;");
    if (w != 0) {
      bar_sync(BAR_INIT, 384);
      if (w == 1) producer<true>(p, sb, m, n, lane);
      else if (w == 3) colsum_helper(p, sb, m, n, lane);
      else if (elect_one()) publisher(p, sb, m, n);
    } else {
      if (elect_one()) {
#pragma unroll
        for (int k = 0; k < 4; k++) mbar_init(sb + BAR_FULL + 8 * k, 2);
        asm volatile("fence.mbarrier_init.release.cluster;" ::: "memory");
        PROF_U(4);
#pragma unroll 1
        for (int k = 0; k < 4; k++) {
          const uint32_t fb = sb + BAR_FULL + 8 * k;
          mbar_expect_tx(fb, 16384);
          tma_ld2(sb + (5 * k + 3) * UNIT, &p.xin, fb, 64 * k, 128 * m);
          mbar_expect_tx(fb, 3 * UNIT);
          tma_ld3(sb + 5 * k * UNIT, &p.wqkv, fb, 128 * n, 64 * k, 0);
        }
        PROF_U(5);
        mbar_init(sb + BAR_XRDY, 4);
        mbar_init(sb + BAR_XRDY + 8, 4);
        mbar_init(sb + BAR_FULL + 32, 2);
#pragma unroll
        for (int k = 0; k < NBAR; k++) mbar_init(sb + BAR_EMPTY + 8 * k, 4);
        mbar_init(sb + BAR_DUMMY, 4);
#pragma unroll
        for (int k = 0; k < 7; k++) mbar_init(sb + BAR_PUB + 8 * k, 4);
#pragma unroll
        for (int k = 0; k < 3; k++) mbar_init(sb + BAR_CSLD + 8 * k, 1);
        sts_f2(sb + OFF_ZERO, 0.f, 0.f);
        sts_f2(sb + OFF_ZERO + 8, 0.f, 0.f);
        asm volatile("fence.mbarrier_init.release.cluster;" ::: "memory");
        mbar_expect_tx(sb + BAR_CSLD, 24576);
        tma_ld3(sb + OFF_STG, &p.wqkv, sb + BAR_CSLD, 128 * n, 64 * m, 0);
#pragma unroll 1
        for (int h = 0; h < 2; h++) {
          const uint32_t xr = sb + BAR_XRDY + 8 * h;
          mbar_expect_tx(xr, 16384);
          tma_ld2(sb + OFF_X + h * 16384, &p.xin, xr, 128 * n + 64 * h, 128 * m);
          asm volatile("mbarrier.arrive.shared::cta.b64 _, [%0], 3;" ::"r"(xr) : "memory");
        }
        PROF_U(6);
      }
      __syncwarp();
      bar_arrive(BAR_INIT, 384);
      producer<false>(p, sb, m, n, lane);
    }
  }
}

typedef CUresult (*EncodeFn)(CUtensorMap*, CUtensorMapDataType, cuuint32_t, void*, const cuuint64_t*, const cuuint64_t*,
                             const cuuint32_t*, const cuuint32_t*, CUtensorMapInterleave, CUtensorMapSwizzle,
                             CUtensorMapL2promotion, CUtensorMapFloatOOBfill);

void make_2d(EncodeFn enc, CUtensorMap* m, const void* ptr, uint64_t cols, uint64_t rows, uint32_t box_rows) {
  cuuint64_t d[2] = {cols, rows}, st[1] = {cols * 2};
  cuuint32_t b[2] = {64, box_rows}, e[2] = {1, 1};
  enc(m, CU_TENSOR_MAP_DATA_TYPE_BFLOAT16, 2, const_cast<void*>(ptr), d, st, b, e, CU_TENSOR_MAP_INTERLEAVE_NONE,
      CU_TENSOR_MAP_SWIZZLE_128B, CU_TENSOR_MAP_L2_PROMOTION_L2_128B, CU_TENSOR_MAP_FLOAT_OOB_FILL_NONE);
}
void make_3d(EncodeFn enc, CUtensorMap* m, const void* ptr, uint64_t d0, uint64_t rows, uint64_t d2, uint64_t row_bytes,
             uint64_t chunk_bytes, uint32_t box_chunks) {
  cuuint64_t d[3] = {d0, rows, d2}, st[2] = {row_bytes, chunk_bytes};
  cuuint32_t b[3] = {64, 64, box_chunks}, e[3] = {1, 1, 1};
  enc(m, CU_TENSOR_MAP_DATA_TYPE_BFLOAT16, 3, const_cast<void*>(ptr), d, st, b, e, CU_TENSOR_MAP_INTERLEAVE_NONE,
      CU_TENSOR_MAP_SWIZZLE_128B, CU_TENSOR_MAP_L2_PROMOTION_L2_128B, CU_TENSOR_MAP_FLOAT_OOB_FILL_NONE);
}

}

extern "C" void kernel_launch(void* const* d_in, const int* in_sizes, int n_in, void* d_out, int out_size) {
  (void)in_sizes; (void)n_in; (void)out_size;
  static EncodeFn enc = nullptr;
  static void *att = nullptr, *hbuf = nullptr;
  static int by_smid = 0;
  if (!enc) {
    void* fn = nullptr;
    cudaDriverEntryPointQueryResult q;
    cudaGetDriverEntryPoint("cuTensorMapEncodeTiled", &fn, cudaEnableDefault, &q);
    enc = (EncodeFn)fn;
    cudaGetSymbolAddress(&att, g_att);
    cudaGetSymbolAddress(&hbuf, g_h);
    cudaFuncSetAttribute(fused_layers_kernel, cudaFuncAttributeMaxDynamicSharedMemorySize, SMEM_BYTES);
    int sms = 0, per_sm = 0, dev = 0;
    cudaGetDevice(&dev);
    cudaDeviceGetAttribute(&sms, cudaDevAttrMultiProcessorCount, dev);
    cudaOccupancyMaxActiveBlocksPerMultiprocessor(&per_sm, fused_layers_kernel, 384, SMEM_BYTES);
    by_smid = sms == 132 && per_sm == 1;
  }
  Params p;
  make_2d(enc, &p.xin, d_in[0], DM, SEQ, 128);
  make_2d(enc, &p.out, d_out, DM, SEQ, 128);
  make_2d(enc, &p.att, att, DM, SEQ, 128);
  make_2d(enc, &p.h, hbuf, FF, SEQ, 128);
  make_2d(enc, &p.out_st, d_out, DM, SEQ, 32);
  make_2d(enc, &p.att_st, att, DM, SEQ, 32);
  make_2d(enc, &p.h_st, hbuf, FF, SEQ, 32);
  make_2d(enc, &p.w1c, d_in[4], FF, DM, 32);
  make_3d(enc, &p.wqkv, d_in[1], DM, DM, 3, 3 * DM * 2, DM * 2, 3);
  make_3d(enc, &p.wo, d_in[2], 64, DM, DM / 64, DM * 2, 128, 2);
  make_3d(enc, &p.w1a, d_in[4], 64, DM, FF / 64, FF * 2, 128, 3);
  make_3d(enc, &p.w1b, d_in[4], 64, DM, FF / 64, FF * 2, 128, 2);
  make_3d(enc, &p.w2, d_in[6], 64, FF, DM / 64, DM * 2, 128, 2);
  p.b1 = (const __nv_bfloat16*)d_in[5];
  p.b2 = (const __nv_bfloat16*)d_in[7];
  p.zero = 0;
  fused_layers_kernel<<<by_smid ? 132 : NCTA, 384, SMEM_BYTES>>>(by_smid, (const __nv_bfloat16*)d_in[0], (const __nv_bfloat16*)d_in[1], p);
}
```

```cpp
#include <cuda_runtime.h>
#include <cuda_bf16.h>
#include <cuda.h>
#include <stdint.h>

namespace {

constexpr int SEQ = 2048, DM = 1024, FF = 3584;
constexpr int NCTA = 128;
constexpr int NBAR = 5;

constexpr uint32_t RING_UNITS = 20, UNIT = 8192;
constexpr uint32_t OFF_X   = RING_UNITS * UNIT;
constexpr uint32_t OFF_STG = OFF_X + 32768;
constexpr uint32_t OFF_HLP = OFF_STG + 24576;
constexpr uint32_t OFF_CSQ = OFF_HLP + 4096;
constexpr uint32_t OFF_CSF = OFF_CSQ + 2048;
constexpr uint32_t OFF_ROW = OFF_CSF + 3584;
constexpr uint32_t OFF_BAR = OFF_ROW + 1024;
constexpr uint32_t SMEM_BYTES = OFF_BAR + 384;
constexpr uint32_t BAR_FULL = OFF_BAR, BAR_EMPTY = OFF_BAR + 8 * NBAR;
constexpr uint32_t BAR_XRDY = OFF_BAR + 80;
constexpr uint32_t BAR_DUMMY = OFF_BAR + 96, OFF_TAG = OFF_BAR + 104, OFF_ZERO = OFF_BAR + 112;
constexpr uint32_t BAR_PUB = OFF_BAR + 128;
constexpr uint32_t BAR_CSLD = OFF_BAR + 200;
constexpr uint32_t BAR_BIAS = OFF_BAR + 216;

constexpr uint64_t DESC_A = (1ull << 62) | ((uint64_t)(2048 >> 4) << 32) | (1ull << 16);
constexpr uint64_t DESC_B = (1ull << 62) | ((uint64_t)(1024 >> 4) << 32) | ((uint64_t)(8192 >> 4) << 16);

constexpr int BAR_INIT = 0, BAR_ORDER = 1, BAR_GUARD = 3, BAR_WG = 5, BAR_GO = 7, BAR_DONE = 8;
#define GELU_DEP 3
#define WIN1 7
#define WIN2 3

struct Params {
  CUtensorMap xin, out, att, h, wqkv, wo, w1a, w1b, w2, out_st, att_st, h_st, w1c;
  const __nv_bfloat16 *b1, *b2;
  uint32_t zero;
};

__device__ __nv_bfloat16 g_att[SEQ * DM];
__device__ __nv_bfloat16 g_h[SEQ * FF];
__device__ uint4 g_stats[4 * 8 * SEQ];
__device__ uint4 g_halo[2 * 2 * 16 * 8 * 384];
__device__ uint4 g_csp[2 * 8 * 17 * 224];
__device__ uint32_t g_flags[16 * 32];
__device__ uint32_t g_epoch[NCTA + 4];
#define PROF_T(idx)
#define PROF_U(k)
#define PROF_S(g)
#define PROF_E(i, k)

__device__ __forceinline__ void mbar_init(uint32_t bar, int cnt) {
  asm volatile("mbarrier.init.shared::cta.b64 [%0], %1;" ::"r"(bar), "r"(cnt));
}
__device__ __forceinline__ void mbar_expect_tx(uint32_t bar, uint32_t bytes) {
  asm volatile("mbarrier.arrive.expect_tx.shared::cta.b64 _, [%0], %1;" ::"r"(bar), "r"(bytes) : "memory");
}
__device__ __forceinline__ void mbar_arrive(uint32_t bar) {
  asm volatile("mbarrier.arrive.shared::cta.b64 _, [%0];" ::"r"(bar) : "memory");
}
__device__ __forceinline__ bool mbar_test(uint32_t bar, uint32_t parity) {
  uint32_t ok;
  asm volatile("{\n.reg .pred p;\nmbarrier.test_wait.parity.shared::cta.b64 p, [%1], %2;\nselp.u32 %0, 1, 0, p;\n}"
               : "=r"(ok) : "r"(bar), "r"(parity) : "memory");
  return ok;
}
__device__ __forceinline__ void mbar_wait(uint32_t bar, uint32_t parity) {
  asm volatile(
      "{\n.reg .pred p;\n.reg .u32 it;\nmov.u32 it, 0;\n"
      "WAIT_LOOP:\n"
      "mbarrier.try_wait.parity.shared::cta.b64 p, [%0], %1;\n"
      "@p bra WAIT_DONE;\n"
      "add.u32 it, it, 1;\n"
      "setp.lt.u32 p, it, 0x400000;\n"
      "@p bra WAIT_LOOP;\n"
      "trap;\n"
      "WAIT_DONE:\n}"
      ::"r"(bar), "r"(parity) : "memory");
}
__device__ __forceinline__ void bar_sync(int id, int n) { asm volatile("bar.sync %0, %1;" ::"r"(id), "r"(n) : "memory"); }
__device__ __forceinline__ void bar_arrive(int id, int n) { asm volatile("bar.arrive %0, %1;" ::"r"(id), "r"(n) : "memory"); }
__device__ __forceinline__ void tma_ld2(uint32_t dst, const CUtensorMap* m, uint32_t bar, int c0, int c1) {
  asm volatile("cp.async.bulk.tensor.2d.shared::cluster.global.mbarrier::complete_tx::bytes [%0], [%1, {%3, %4}], [%2];"
               ::"r"(dst), "l"(m), "r"(bar), "r"(c0), "r"(c1) : "memory");
}
__device__ __forceinline__ void tma_ld3(uint32_t dst, const CUtensorMap* m, uint32_t bar, int c0, int c1, int c2) {
  asm volatile("cp.async.bulk.tensor.3d.shared::cluster.global.mbarrier::complete_tx::bytes [%0], [%1, {%3, %4, %5}], [%2];"
               ::"r"(dst), "l"(m), "r"(bar), "r"(c0), "r"(c1), "r"(c2) : "memory");
}
__device__ __forceinline__ void tma_st2(const CUtensorMap* m, uint32_t src, int c0, int c1) {
  asm volatile("cp.async.bulk.tensor.2d.global.shared::cta.bulk_group [%0, {%2, %3}], [%1];"
               ::"l"(m), "r"(src), "r"(c0), "r"(c1) : "memory");
}
__device__ __forceinline__ void bulk_commit() { asm volatile("cp.async.bulk.commit_group;" ::: "memory"); }
__device__ __forceinline__ void bulk_wait_read() { asm volatile("cp.async.bulk.wait_group.read 0;" ::: "memory"); }
__device__ __forceinline__ void bulk_wait_all() { asm volatile("cp.async.bulk.wait_group 0;" ::: "memory"); }
__device__ __forceinline__ void fence_async_smem() { asm volatile("fence.proxy.async.shared::cta;" ::: "memory"); }
__device__ __forceinline__ void fence_async_global() { asm volatile("fence.proxy.async.global;" ::: "memory"); }
__device__ __forceinline__ void st_relaxed(uint32_t* p, uint32_t v) {
  asm volatile("st.relaxed.gpu.global.u32 [%0], %1;" ::"l"(p), "r"(v) : "memory");
}
__device__ __forceinline__ void st_msg(uint4* p, uint32_t a, uint32_t b, uint32_t c, uint32_t tag) {
  asm volatile("{\n.reg .b128 v;\nmov.b128 v, {%1, %2, %3, %4};\nst.relaxed.gpu.b128 [%0], v;\n}"
               ::"l"(p), "r"(a), "r"(b), "r"(c), "r"(tag) : "memory");
}
__device__ __forceinline__ void ld_msg(const uint4* p, uint32_t& a, uint32_t& b, uint32_t& c, uint32_t& tag) {
  asm volatile("{\n.reg .b128 v;\nld.relaxed.gpu.b128 v, [%4];\nmov.b128 {%0, %1, %2, %3}, v;\n}"
               : "=r"(a), "=r"(b), "=r"(c), "=r"(tag) : "l"(p) : "memory");
}
__device__ __forceinline__ bool elect_one() {
  uint32_t ok;
  asm volatile("{\n.reg .pred p;\nelect.sync _|p, 0xffffffff;\nselp.u32 %0, 1, 0, p;\n}" : "=r"(ok));
  return ok;
}
__device__ __forceinline__ int uniform(int v) { return __shfl_sync(0xffffffffu, v, 0); }
__device__ __forceinline__ uint32_t pack_bf16(float lo, float hi) {
  uint32_t r;
  asm("cvt.rn.bf16x2.f32 %0, %1, %2;" : "=r"(r) : "f"(hi), "f"(lo));
  return r;
}
__device__ __forceinline__ uint32_t prmt_u(uint32_t a, uint32_t sel) {
  uint32_t r;
  asm("prmt.b32 %0, %1, 0, %2;" : "=r"(r) : "r"(a), "r"(sel));
  return r;
}
__device__ __forceinline__ float prmt_f(uint32_t a, uint32_t sel) {
  float r;
  asm("{\n.reg .b32 t;\nprmt.b32 t, %1, 0, %2;\nmov.b32 %0, t;\n}" : "=f"(r) : "r"(a), "r"(sel));
  return r;
}
__device__ __forceinline__ float bf_lo(uint32_t v) { return __uint_as_float(v << 16); }
__device__ __forceinline__ float bf_hi(uint32_t v) { return __uint_as_float(v & 0xffff0000u); }
__device__ __forceinline__ void stsm4(uint32_t addr, uint32_t r0, uint32_t r1, uint32_t r2, uint32_t r3) {
  asm volatile("stmatrix.sync.aligned.m8n8.x4.shared.b16 [%0], {%1, %2, %3, %4};"
               ::"r"(addr), "r"(r0), "r"(r1), "r"(r2), "r"(r3) : "memory");
}
__device__ __forceinline__ void ldsm4(uint32_t addr, uint32_t& r0, uint32_t& r1, uint32_t& r2, uint32_t& r3) {
  asm volatile("ldmatrix.sync.aligned.m8n8.x4.shared.b16 {%0, %1, %2, %3}, [%4];"
               : "=r"(r0), "=r"(r1), "=r"(r2), "=r"(r3) : "r"(addr) : "memory");
}
__device__ __forceinline__ uint32_t movtrans(uint32_t a) {
  uint32_t d;
  asm volatile("movmatrix.sync.aligned.m8n8.trans.b16 %0, %1;" : "=r"(d) : "r"(a));
  return d;
}
__device__ __forceinline__ void mma16816(float (&c)[4], uint32_t a0, uint32_t a1, uint32_t a2, uint32_t a3, uint32_t b0, uint32_t b1) {
  asm volatile("mma.sync.aligned.m16n8k16.row.col.f32.bf16.bf16.f32 {%0,%1,%2,%3}, {%4,%5,%6,%7}, {%8,%9}, {%0,%1,%2,%3};"
               : "+f"(c[0]), "+f"(c[1]), "+f"(c[2]), "+f"(c[3])
               : "r"(a0), "r"(a1), "r"(a2), "r"(a3), "r"(b0), "r"(b1));
}
__device__ __forceinline__ float2 lds_f2(uint32_t a) {
  float2 v;
  asm volatile("ld.shared.v2.f32 {%0, %1}, [%2];" : "=f"(v.x), "=f"(v.y) : "r"(a) : "memory");
  return v;
}
__device__ __forceinline__ float4 lds_f4(uint32_t a) {
  float4 v;
  asm volatile("ld.shared.v4.f32 {%0, %1, %2, %3}, [%4];" : "=f"(v.x), "=f"(v.y), "=f"(v.z), "=f"(v.w) : "r"(a) : "memory");
  return v;
}
__device__ __forceinline__ float lds_f(uint32_t a) {
  float v;
  asm volatile("ld.shared.f32 %0, [%1];" : "=f"(v) : "r"(a) : "memory");
  return v;
}
__device__ __forceinline__ uint32_t lds_u(uint32_t a) {
  uint32_t v;
  asm volatile("ld.shared.u32 %0, [%1];" : "=r"(v) : "r"(a) : "memory");
  return v;
}
__device__ __forceinline__ void sts_f2(uint32_t a, float x, float y) {
  asm volatile("st.shared.v2.f32 [%0], {%1, %2};" ::"r"(a), "f"(x), "f"(y) : "memory");
}
__device__ __forceinline__ void sts_u4(uint32_t a, uint32_t x, uint32_t y, uint32_t z, uint32_t w) {
  asm volatile("st.shared.v4.u32 [%0], {%1, %2, %3, %4};" ::"r"(a), "r"(x), "r"(y), "r"(z), "r"(w) : "memory");
}
__device__ __forceinline__ void lds_u4(uint32_t a, uint32_t& x, uint32_t& y, uint32_t& z, uint32_t& w) {
  asm volatile("ld.shared.v4.u32 {%0, %1, %2, %3}, [%4];" : "=r"(x), "=r"(y), "=r"(z), "=r"(w) : "r"(a) : "memory");
}
__device__ __forceinline__ float ex2(float x) {
  float y;
  asm("ex2.approx.ftz.f32 %0, %1;" : "=f"(y) : "f"(x));
  return y;
}
__device__ __forceinline__ float rcp_hw(float x) {
  float y;
  asm("rcp.approx.ftz.f32 %0, %1;" : "=f"(y) : "f"(x));
  return y;
}
__device__ __forceinline__ float tanh_hw(float x) {
  float y;
  asm("tanh.approx.f32 %0, %1;" : "=f"(y) : "f"(x));
  return y;
}
__device__ __forceinline__ float quad_sum(float v) {
  v += __shfl_xor_sync(0xffffffffu, v, 1);
  return v + __shfl_xor_sync(0xffffffffu, v, 2);
}
__device__ __forceinline__ float quad_max(float v) {
  v = fmaxf(v, __shfl_xor_sync(0xffffffffu, v, 1));
  return fmaxf(v, __shfl_xor_sync(0xffffffffu, v, 2));
}

template <int N> __device__ __forceinline__ void wgmma_ss(float (&d)[96], uint64_t da, uint64_t db);
template <> __device__ __forceinline__ void wgmma_ss<128>(float (&d)[96], uint64_t da, uint64_t db) {
  asm volatile(
      "wgmma.mma_async.sync.aligned.m64n128k16.f32.bf16.bf16 {%0, %1, %2, %3, %4, %5, %6, %7, %8, %9, %10, %11, %12, %13, %14, %15, %16, %17, %18, %19, %20, %21, %22, %23, %24, %25, %26, %27, %28, %29, %30, %31, %32, %33, %34, %35, %36, %37, %38, %39, %40, %41, %42, %43, %44, %45, %46, %47, %48, %49, %50, %51, %52, %53, %54, %55, %56, %57, %58, %59, %60, %61, %62, %63}, %64, %65, 1, 1, 1, 0, 1;"
      : "+f"(d[0]), "+f"(d[1]), "+f"(d[2]), "+f"(d[3]), "+f"(d[4]), "+f"(d[5]), "+f"(d[6]), "+f"(d[7]), "+f"(d[8]), "+f"(d[9]), "+f"(d[10]), "+f"(d[11]), "+f"(d[12]), "+f"(d[13]), "+f"(d[14]), "+f"(d[15]), "+f"(d[16]), "+f"(d[17]), "+f"(d[18]), "+f"(d[19]), "+f"(d[20]), "+f"(d[21]), "+f"(d[22]), "+f"(d[23]), "+f"(d[24]), "+f"(d[25]), "+f"(d[26]), "+f"(d[27]), "+f"(d[28]), "+f"(d[29]), "+f"(d[30]), "+f"(d[31]), "+f"(d[32]), "+f"(d[33]), "+f"(d[34]), "+f"(d[35]), "+f"(d[36]), "+f"(d[37]), "+f"(d[38]), "+f"(d[39]), "+f"(d[40]), "+f"(d[41]), "+f"(d[42]), "+f"(d[43]), "+f"(d[44]), "+f"(d[45]), "+f"(d[46]), "+f"(d[47]), "+f"(d[48]), "+f"(d[49]), "+f"(d[50]), "+f"(d[51]), "+f"(d[52]), "+f"(d[53]), "+f"(d[54]), "+f"(d[55]), "+f"(d[56]), "+f"(d[57]), "+f"(d[58]), "+f"(d[59]), "+f"(d[60]), "+f"(d[61]), "+f"(d[62]), "+f"(d[63])
      : "l"(da), "l"(db));
}

template <> __device__ __forceinline__ void wgmma_ss<192>(float (&d)[96], uint64_t da, uint64_t db) {
  asm volatile(
      "wgmma.mma_async.sync.aligned.m64n192k16.f32.bf16.bf16 {%0, %1, %2, %3, %4, %5, %6, %7, %8, %9, %10, %11, %12, %13, %14, %15, %16, %17, %18, %19, %20, %21, %22, %23, %24, %25, %26, %27, %28, %29, %30, %31, %32, %33, %34, %35, %36, %37, %38, %39, %40, %41, %42, %43, %44, %45, %46, %47, %48, %49, %50, %51, %52, %53, %54, %55, %56, %57, %58, %59, %60, %61, %62, %63, %64, %65, %66, %67, %68, %69, %70, %71, %72, %73, %74, %75, %76, %77, %78, %79, %80, %81, %82, %83, %84, %85, %86, %87, %88, %89, %90, %91, %92, %93, %94, %95}, %96, %97, 1, 1, 1, 0, 1;"
      : "+f"(d[0]), "+f"(d[1]), "+f"(d[2]), "+f"(d[3]), "+f"(d[4]), "+f"(d[5]), "+f"(d[6]), "+f"(d[7]), "+f"(d[8]), "+f"(d[9]), "+f"(d[10]), "+f"(d[11]), "+f"(d[12]), "+f"(d[13]), "+f"(d[14]), "+f"(d[15]), "+f"(d[16]), "+f"(d[17]), "+f"(d[18]), "+f"(d[19]), "+f"(d[20]), "+f"(d[21]), "+f"(d[22]), "+f"(d[23]), "+f"(d[24]), "+f"(d[25]), "+f"(d[26]), "+f"(d[27]), "+f"(d[28]), "+f"(d[29]), "+f"(d[30]), "+f"(d[31]), "+f"(d[32]), "+f"(d[33]), "+f"(d[34]), "+f"(d[35]), "+f"(d[36]), "+f"(d[37]), "+f"(d[38]), "+f"(d[39]), "+f"(d[40]), "+f"(d[41]), "+f"(d[42]), "+f"(d[43]), "+f"(d[44]), "+f"(d[45]), "+f"(d[46]), "+f"(d[47]), "+f"(d[48]), "+f"(d[49]), "+f"(d[50]), "+f"(d[51]), "+f"(d[52]), "+f"(d[53]), "+f"(d[54]), "+f"(d[55]), "+f"(d[56]), "+f"(d[57]), "+f"(d[58]), "+f"(d[59]), "+f"(d[60]), "+f"(d[61]), "+f"(d[62]), "+f"(d[63]), "+f"(d[64]), "+f"(d[65]), "+f"(d[66]), "+f"(d[67]), "+f"(d[68]), "+f"(d[69]), "+f"(d[70]), "+f"(d[71]), "+f"(d[72]), "+f"(d[73]), "+f"(d[74]), "+f"(d[75]), "+f"(d[76]), "+f"(d[77]), "+f"(d[78]), "+f"(d[79]), "+f"(d[80]), "+f"(d[81]), "+f"(d[82]), "+f"(d[83]), "+f"(d[84]), "+f"(d[85]), "+f"(d[86]), "+f"(d[87]), "+f"(d[88]), "+f"(d[89]), "+f"(d[90]), "+f"(d[91]), "+f"(d[92]), "+f"(d[93]), "+f"(d[94]), "+f"(d[95])
      : "l"(da), "l"(db));
}

template <int R>
__device__ __forceinline__ void pin_regs(float (&a)[2][96]) {
#pragma unroll
  for (int m = 0; m < 2; m++)
#pragma unroll
    for (int i = 0; i < R; i++) asm volatile("" : "+f"(a[m][i])::"memory");
}

struct Ctx {
  uint32_t sb;
  int m, n, wg, w, lane;
};
__device__ __forceinline__ Ctx make_ctx(uint32_t sb, int id) {
  int lane;
  asm volatile("mov.u32 %0, %%laneid;" : "=r"(lane));
  asm volatile("" : "+r"(id), "+r"(sb));
  return Ctx{sb, (id >> 3) & 15, id & 7, id >> 9, (id >> 7) & 3, lane};
}
#define UNPACK_CTX(c) const uint32_t sb = c.sb; const int m = c.m, n = c.n, wg = c.wg, w = c.w, lane = c.lane

__device__ __forceinline__ uint32_t poll_line(const uint32_t* word, uint32_t target, uint32_t need) {
  uint32_t v;
  asm volatile(
      "{\n.reg .pred p;\n.reg .u32 it, m;\n.reg .s32 d;\nmov.u32 it, 0;\n"
      "POLL_LOOP:\n"
      "ld.relaxed.gpu.global.u32 %0, [%1];\n"
      "sub.s32 d, %0, %2;\n"
      "setp.ge.s32 p, d, 0;\n"
      "vote.sync.ballot.b32 m, p, 0xffffffff;\n"
      "and.b32 m, m, %3;\n"
      "setp.eq.u32 p, m, %3;\n"
      "@p bra.uni POLL_DONE;\n"
      "add.u32 it, it, 1;\n"
      "setp.lt.u32 p, it, 0x400000;\n"
      "@p bra.uni POLL_LOOP;\n"
      "trap;\n"
      "POLL_DONE:\n}"
      : "=&r"(v) : "l"(word), "r"(target), "r"(need) : "memory");
  return v;
}
__device__ __forceinline__ uint32_t ld_relaxed(const uint32_t* p) {
  uint32_t v;
  asm volatile("ld.relaxed.gpu.global.u32 %0, [%1];" : "=r"(v) : "l"(p) : "memory");
  return v;
}
__device__ __forceinline__ float chain(float x, uint32_t on, uint32_t zero) {
  return __uint_as_float(__float_as_uint(x) | (on & zero));
}
constexpr int MSG_SPINS = 1 << 20;

constexpr int STAGES_PER_LAYER = 152;
__device__ __forceinline__ int nib(uint64_t v, int i) { return (int)(v >> (4 * i)) & 15; }
__device__ __forceinline__ bool tile_wide(int t) { return (0x23 >> t) & 1; }
constexpr uint64_t ORDER_PLAIN = 0xFEDCBA9876543210ull, ORDER_X = 0xFEDCBA9765432180ull, ORDER_FIRST = 0xF7E6D5C4B3A29180ull;

__device__ __forceinline__ void weight_coords(const Params& p, int t, int n, const CUtensorMap*& map, int& c0, int& c2) {
  map = &p.wqkv + nib(0x4233100ull, t);
  c0 = t < 2 ? 128 * n + 64 * t : 0;
  c2 = t < 2 ? 0 : (t == 2 || t == 6) ? 2 * n : 7 * n + 2 * t - 6;
}

template <bool IS_A>
__device__ __forceinline__ void producer(const Params& p, uint32_t sb, int m, int n, int lane) {
  int inflight = 0, rph = 0, min_seen = 0, cur = 0;
  uint32_t b8 = 0, rb8 = 0, pos = 0, tag32 = 0, seen = 0;
  const uint32_t* word = g_flags + m * 32 + (lane & 7);
#pragma unroll 1
  for (int sg = 0; sg < 22; sg++) {
    const int layer = sg >= 11, s = sg == 1 ? 2 : sg == 2 ? 1 : sg - 11 * layer;
    const int t = nib(0x65434321010ull, s), kind = nib(0x32110021100ull, s);
    const bool wide = tile_wide(t), xtype = t != 2 && t != 6;
    const uint32_t bbytes = wide ? 3 * UNIT : 2 * UNIT;
    const int mul = t == 6 ? 7 * 64 : 2 * 64, count = 2 * nib(0x4871ull, kind);
    const uint64_t order0 = (sg < 2 ? ORDER_FIRST : xtype ? ORDER_X : ORDER_PLAIN) >> (kind == 1 ? 8 : 0);
    const int nr = sg < 2 ? 0 : n;
    int lags = s == 9 ? 0x55555545 : wide ? 0x55555555 : (s == 4 || s == 10) ? 0xAAAAAA55 : 0xAAAAAAAA;
    uint32_t own = t == 2 ? 0x100u : xtype && kind != 1 ? 3u : 0u;
    if (s >= 9) pos = (s + 6) * UNIT;
    const CUtensorMap* map;
    int c0 = 0, c2 = 0, ev = 0;
    if (IS_A) {
      map = &p.xin + (t == 2 ? 2 : t == 6 ? 3 : sg >= 4);
      ev = 9 * layer + (t < 2 ? -1 : t == 2 ? 1 : t < 6 ? 3 : 5);
      if (sg == 3) seen = tag32 = (__ldcg(g_epoch + m * 8 + n) + 1) << 5;
    } else {
      weight_coords(p, t, n, map, c0, c2);
    }
#pragma unroll 1
    for (int add = 0; add < (t == 6 ? 7 * 64 : 64); add += 64) {
      uint64_t order = order0;
      if (IS_A && (add == 128 || add == 256)) ev++;
#pragma unroll 1
      for (int k = count; k > 0; k--) {
        const int q = order & 7, hi = (order >> 3) & 1, lag = 2 + (lags & 3);
        const bool local = own & 1;
        order >>= 4;
        lags = (lags >> 2) & 0xBFFFFFFF;
        own >>= 1;
        const int src = (((nr & 6) + q) & 7) ^ (q < 2 ? nr & 1 : 0);
        const int kc = mul * src + add + 64 * hi;
        if (IS_A) {
          if (k == 4 && sg >= 3) seen = ld_relaxed(word);
          if (!local && min_seen < ev + hi) {
            cur = max(cur, (int)(seen - tag32));
            if (__shfl_sync(0xffffffffu, cur, src) < ev + hi) cur = (int)(poll_line(word, tag32 + ev + hi, 1u << src) - tag32);
            min_seen = __reduce_min_sync(0xffffffffu, cur);
            asm volatile("fence.acquire.gpu;" ::: "memory");
            fence_async_global();
          }
        }
#pragma unroll 1
        for (; inflight > lag; inflight--) {
          mbar_wait(sb + BAR_EMPTY + rb8, rph);
          rb8 += 8;
          if (rb8 == 8 * NBAR) { rb8 = 0; rph ^= 1; }
        }
        const uint32_t fb = sb + BAR_FULL + b8;
        if (sg == 0 || (sg == 1 && k > 12)) {
        } else if (!IS_A) {
          if (elect_one()) {
            mbar_expect_tx(fb, bbytes);
            tma_ld3(sb + pos, map, fb, c0, kc, c2);
          }
        } else if (!local) {
          if (elect_one()) {
            mbar_expect_tx(fb, 16384);
            tma_ld2(sb + pos + bbytes, map, fb, kc, 128 * m);
          }
        } else {
          if (t == 2) mbar_wait(sb + BAR_PUB + 8, layer);
          else if (k == 1 && (s == 0 || s == 5)) mbar_wait(sb + BAR_XRDY + 8, s == 5);
          if (elect_one()) mbar_arrive(fb);
        }
        inflight++;
        b8 += 8;
        if (b8 == 8 * NBAR) b8 = 0;
        pos += bbytes + 2 * UNIT;
        if (pos >= RING_UNITS * UNIT) pos -= RING_UNITS * UNIT;
      }
    }
  }
}

__device__ __forceinline__ void publisher(const Params& p, uint32_t sb, int m, int n) {
  const uint32_t tag = __ldcg(g_epoch + m * 8 + n) + 1;
  uint32_t* word = g_flags + m * 32 + n;
  const int mn = m * 8 + n; (void)mn;
  st_relaxed(word, 32 * tag);
#pragma unroll 1
  for (int c = 0; c < 18; c++) {
    const int e = c >= 9 ? c - 9 : c;
    if ((0x18C >> e) & 1) {
      const int half = (0x108 >> e) & 1;
      mbar_wait(sb + BAR_XRDY + 8 * half, e < 4);
#pragma unroll
      for (int w = 0; w < 4; w++) tma_st2(&p.out_st, sb + OFF_X + half * 16384 + w * 4096, 128 * n + 64 * half, 128 * m + 32 * w);
      bulk_commit();
      if (c >= 16) continue;
      bulk_wait_all();
      PROF_E(7 * (c >= 9) + (e < 4 ? 2 : 6), 11 + 2 * half);
    } else {
      mbar_wait(sb + BAR_PUB + 8 * e, c >= 9);
    }
    asm volatile("fence.release.gpu;" ::: "memory");
    st_relaxed(word, 32 * tag + c + 1);
    PROF_E(7 * (c >= 9) + nib(0x665432210ull, e), (0x108 >> e) & 1 ? 14 : 12);
  }
  g_epoch[m * 8 + n] = tag;
  bulk_wait_read();
}

__device__ __forceinline__ void sum_rows(uint32_t buf, int iters, float (&a)[8], int lane) {
  uint32_t addr = buf + (lane >> 3) * 128 + (((lane & 7) ^ (lane >> 3)) << 4);
#pragma unroll 1
  for (int it = 0; it < iters; it++) {
    uint32_t u[2][4];
    lds_u4(addr, u[0][0], u[0][1], u[0][2], u[0][3]);
    lds_u4((addr ^ 64) + 512, u[1][0], u[1][1], u[1][2], u[1][3]);
    addr += 1024;
#pragma unroll
    for (int e = 0; e < 8; e++) { a[2 * (e & 3)] += bf_lo(u[e >> 2][e & 3]); a[2 * (e & 3) + 1] += bf_hi(u[e >> 2][e & 3]); }
  }
}
__device__ __forceinline__ void publish_sums(const float (&a)[8], uint4* dst, int lane, uint32_t tag) {
  const bool u8 = lane & 8, u16 = lane & 16;
  float h4[4], h2[2];
#pragma unroll
  for (int e = 0; e < 4; e++) h4[e] = (u8 ? a[4 + e] : a[e]) + __shfl_xor_sync(0xffffffffu, u8 ? a[e] : a[4 + e], 8);
#pragma unroll
  for (int e = 0; e < 2; e++) h2[e] = (u16 ? h4[2 + e] : h4[e]) + __shfl_xor_sync(0xffffffffu, u16 ? h4[e] : h4[2 + e], 16);
  st_msg(dst + (lane & 7) * 4 + (u8 ? 2 : 0) + (u16 ? 1 : 0), __float_as_uint(h2[0]), __float_as_uint(h2[1]), 0u, tag);
}

__device__ __forceinline__ void colsum_helper(const Params& p, uint32_t sb, int m, int n, int lane) {
  const uint32_t tag = __ldcg(g_epoch + m * 8 + n) + 1;
  const int mn = m * 8 + n; (void)mn;
#pragma unroll 1
  for (int k = lane; k < 288; k += 32) {
    const uint32_t bb = __ldg(reinterpret_cast<const uint32_t*>(k < 224 ? p.b1 + 448 * n : p.b2 + 128 * n - 448) + k);
    const float sc = k < 224 ? 0.5f : 1.f;
    sts_f2(sb + (k < 224 ? OFF_CSF + k * 16 + 8 : OFF_CSQ + 1536 + (k - 224) * 8), sc * bf_lo(bb), sc * bf_hi(bb));
  }
  __syncwarp();
  if (elect_one()) mbar_arrive(sb + BAR_BIAS);
  PROF_E(-1, 1);
#pragma unroll 1
  for (int c = 0; c < 7; c++) {
    float a[8] = {0.f, 0.f, 0.f, 0.f, 0.f, 0.f, 0.f, 0.f};
#pragma unroll 1
    for (int h = 0; h < 2; h++) {
      if (elect_one()) {
        mbar_expect_tx(sb + BAR_CSLD + 8, 4096);
        tma_ld2(sb + OFF_HLP, &p.w1c, sb + BAR_CSLD + 8, 448 * n + 64 * c, 64 * m + 32 * h);
        if (c < 6) asm volatile("cp.async.bulk.prefetch.tensor.2d.L2.global [%0, {%1, %2}];" ::"l"(&p.w1c), "r"(448 * n + 64 * c + 64), "r"(64 * m + 32 * h) : "memory");
      }
      mbar_wait(sb + BAR_CSLD + 8, h);
      sum_rows(sb + OFF_HLP, 4, a, lane);
      __syncwarp();
    }
    publish_sums(a, g_csp + ((8 + n) * 17 + m) * 224 + c * 32, lane, tag);
  }
  PROF_E(-1, 2);
}

__device__ __forceinline__ void poll_msgs2(const uint4* pa, const uint4* pb, float (&v)[4], uint32_t tag) {
#pragma unroll 1
  for (int it = 0; it < MSG_SPINS; it++) {
    uint32_t x[4], z, ta, tb;
    ld_msg(pa, x[0], x[1], z, ta);
    ld_msg(pb, x[2], x[3], z, tb);
#pragma unroll
    for (int e = 0; e < 4; e++) v[e] = __uint_as_float(x[e]);
    if (__all_sync(0xffffffffu, ta == tag && tb == tag)) break;
  }
}
__device__ __forceinline__ void colsum_total(const Ctx& cx, int mat, uint32_t tag) {
  uint4* base = g_csp + (mat * 8 + cx.n) * 17 * 224;
  const int per = 12 + 2 * mat, k = 2 * cx.w + (cx.lane >> 4), ia = per * cx.m + k, ib = per * cx.m + min(k + 8, per - 1);
  float v[4];
  poll_msgs2(base + (cx.lane & 15) * 224 + ia, base + (cx.lane & 15) * 224 + ib, v, tag);
#pragma unroll 1
  for (int d = 1; d < 16; d *= 2)
#pragma unroll
    for (int e = 0; e < 4; e++) v[e] += __shfl_xor_sync(0xffffffffu, v[e], d);
  const bool hi = cx.lane & 1;
  if ((cx.lane & 14) == 0) st_msg(base + 16 * 224 + (hi ? ib : ia), __float_as_uint(hi ? v[2] : v[0]), __float_as_uint(hi ? v[3] : v[1]), 0u, tag);
}
__device__ __forceinline__ void colsum_gather(const Ctx& cx, int mat, uint32_t tag) {
  const uint4* base = g_csp + ((mat * 8 + cx.n) * 17 + 16) * 224;
  const int ia = cx.w * 32 + cx.lane, ib = min(ia + 128, 191 + 32 * mat);
  float v[4];
  poll_msgs2(base + ia, base + ib, v, tag);
  const uint32_t tab = cx.sb + (mat ? OFF_CSF : OFF_CSQ);
  sts_f2(tab + (ia << (3 + mat)), v[0], v[1]);
  sts_f2(tab + (ib << (3 + mat)), v[2], v[3]);
}

template <int N>
__device__ __forceinline__ void mainloop(float (&acc)[2][96], uint32_t sb, int i, int part, int mn) {
  constexpr uint32_t Z16 = (2 + N / 64) * (UNIT >> 4), RING16 = RING_UNITS * (UNIT >> 4);
  constexpr uint32_t A_OFF = Z16 - 1024 + (uint32_t)DESC_A - (uint32_t)DESC_B;
  const int wg = i & 1;
  const int layer = i >= 7, t = i - 7 * layer;
  const bool own = t != 2 && t != 6 && part != 1 && i != 0, second = t == 1 || t == 4;
  const int gl = 16 * t + (part == 2 ? 0 : second ? 16 * part - 14 : 4 * part), g0 = layer * STAGES_PER_LAYER + gl;
  const uint32_t s16 = (sb & 0x3FFFF) >> 4;
  const uint32_t bfirst = (uint32_t)DESC_B + s16;
  const uint32_t blast = uniform(bfirst + RING16 - Z16), flast = uniform(sb + BAR_FULL + 8 * (NBAR - 1));
  const int nkb = t == 6 ? 56 : part == 0 ? 2 : 12 + 2 * part;
  const bool win1 = t == 1 && part != 0;
  int run = uniform(win1 ? WIN1 + 1 : t == 2 ? WIN2 + 1 : nkb);
  int rest = win1 ? 64 | (nkb - 1 - WIN1) : t == 2 ? 64 | (7 - WIN2) | (8 << 7) : 0;
  uint32_t fb = sb + BAR_FULL + 8 * (g0 % NBAR), ph = (g0 / NBAR) & 1;
  uint32_t prev = sb + BAR_DUMMY - 8 * NBAR;
  uint32_t blo = bfirst + Z16 * (N == 192 ? (gl + (t == 5 ? 3 : 0)) & 3 : (gl + 3) % 5);
  uint32_t alo = own ? (uint32_t)DESC_A + s16 + (OFF_X >> 4) : blo + A_OFF;
  uint32_t aoff = own ? alo + 1024 - (blo == blast ? bfirst : blo + Z16) : A_OFF;
  pin_regs<N / 2>(acc);
  if (N == 192 && i == 0 && threadIdx.x == 0) PROF_U(7);
  bar_sync(i > 0 ? BAR_ORDER + wg : BAR_INIT, i > 0 ? 256 : 384);
  if (N == 192 && i == 0 && threadIdx.x == 0) PROF_U(8);
  if (t == (N == 192 ? 0 : 3) && part == 0) mbar_wait(sb + BAR_XRDY, N == 128);
  if (N == 192 && i == 0 && threadIdx.x == 0) PROF_U(9);
  mbar_wait(fb, ph);
  if (part != 1) PROF_T(4 + i * 4);
#pragma unroll 1
  while (true) {
    const uint64_t da = (DESC_A & ~0xffffffffull) | alo, db = (DESC_B & ~0xffffffffull) | blo;
    asm volatile("wgmma.fence.sync.aligned;" ::: "memory");
    wgmma_ss<N>(acc[0], da, db);
    wgmma_ss<N>(acc[1], da + 64, db);
    wgmma_ss<N>(acc[0], da + 2, db + 128);
    wgmma_ss<N>(acc[1], da + 66, db + 128);
    asm volatile("wgmma.commit_group.sync.aligned;" ::: "memory");
    asm volatile("wgmma.wait_group.sync.aligned 1;" ::: "memory");
    PROF_S(g0 + jj++);
    if (elect_one()) mbar_arrive(prev + 8 * NBAR);
    prev = fb;
    if (fb == flast) { fb -= 8 * NBAR; ph++; }
    fb += 8;
    if (blo == blast) blo -= RING16;
    blo += Z16;
    alo = blo + aoff;
    aoff = A_OFF;
    run--;
    const bool ready = mbar_test(fb, ph) && run != 0;
    asm volatile("wgmma.fence.sync.aligned;" ::: "memory");
    wgmma_ss<N>(acc[0], da + 4, db + 256);
    wgmma_ss<N>(acc[1], da + 68, db + 256);
    wgmma_ss<N>(acc[0], da + 6, db + 384);
    wgmma_ss<N>(acc[1], da + 70, db + 384);
    asm volatile("wgmma.commit_group.sync.aligned;" ::: "memory");
    if (!ready) {
      if (run == 0) {
        if (rest == 0) break;
        if (rest & 64) {
          bar_arrive(BAR_GO, 256);
          bar_sync(BAR_DONE, 256);
        } else {
          alo = (uint32_t)DESC_A + s16 + (OFF_STG >> 4);
        }
        run = rest & 63;
        rest >>= 7;
      }
      mbar_wait(fb, ph);
    }
  }
  if (i < 13) bar_arrive(BAR_ORDER + (wg ^ 1), 256);
  asm volatile("wgmma.wait_group.sync.aligned 0;" ::: "memory");
  pin_regs<N / 2>(acc);
  if (elect_one()) mbar_arrive(prev + 8 * NBAR);
  PROF_T(5 + i * 4);
  PROF_E(i, 0);
}

#define ACC(q, j, e) acc[(q) & 1][4 * (j) + 2 * ((q) >> 1) + (e)]

__device__ __forceinline__ void write_partial_stats(const Ctx& c, int ln, uint32_t tag) {
  const uint32_t xrow = c.sb + OFF_X + c.w * 4096 + c.lane * 128;
  float s = 0.f, q = 0.f, s1 = 0.f, q1 = 0.f;
#pragma unroll 2
  for (int j = 0; j < 16; j++) {
    uint32_t u[4];
    lds_u4(xrow + (j >> 3) * 16384 + (((j & 7) ^ (c.lane & 7)) << 4), u[0], u[1], u[2], u[3]);
#pragma unroll
    for (int e = 0; e < 4; e++) {
      const float a = bf_lo(u[e]), d = bf_hi(u[e]);
      s += a; q = fmaf(a, a, q);
      s1 += d; q1 = fmaf(d, d, q1);
    }
  }
  s += s1;
  q += q1;
  st_msg(g_stats + (ln * 8 + c.n) * SEQ + 128 * c.m + 32 * c.w + c.lane, __float_as_uint(s),
         __float_as_uint(fmaxf(q - s * s * (1.f / 128.f), 0.f)), 0u, tag);
}

__device__ __forceinline__ void finish_row_stats(const Ctx& c, int ln, uint32_t tag) {
  const uint4* src = g_stats + ln * 8 * SEQ + 128 * c.m + 32 * c.w + c.lane;
  uint32_t ps[8], pm[8];
#pragma unroll 1
  for (int it = 0; it < MSG_SPINS; it++) {
    uint32_t bad = 0, u, tg;
#pragma unroll
    for (int k = 0; k < 8; k++) { ld_msg(src + k * SEQ, ps[k], pm[k], u, tg); bad |= tg ^ tag; }
    if (__all_sync(0xffffffffu, bad == 0)) break;
  }
  float s = 0.f, m2 = 0.f;
#pragma unroll
  for (int k = 0; k < 8; k++) s += __uint_as_float(ps[k]);
  const float mean = s * (1.f / DM);
#pragma unroll
  for (int k = 0; k < 8; k++) {
    const float d = __uint_as_float(ps[k]) * (1.f / 128.f) - mean;
    m2 += fmaf(128.f * d, d, __uint_as_float(pm[k]));
  }
  sts_f2(c.sb + OFF_ROW + (32 * c.w + c.lane) * 8, rsqrtf(m2 * (1.f / DM) + 1e-5f), mean);
  __syncwarp();
}

__device__ __forceinline__ void attn_scores(const uint32_t* qa, const uint32_t* qb, const uint32_t* k0, const uint32_t* k1,
                                            const uint32_t* k2, const uint32_t* k3, float (&l)[4], const float4& zero,
                                            bool par, bool early) {
  float s[4][4];
#pragma unroll
  for (int kb = 0; kb < 4; kb++) {
    const uint32_t* kk = kb == 0 ? k0 : kb == 1 ? k1 : kb == 2 ? k2 : k3;
    asm volatile("mma.sync.aligned.m16n8k16.row.col.f32.bf16.bf16.f32 {%0,%1,%2,%3}, {%4,%5,%6,%7}, {%8,%9}, {%10,%11,%12,%13};"
                 : "=f"(s[kb][0]), "=f"(s[kb][1]), "=f"(s[kb][2]), "=f"(s[kb][3])
                 : "r"(qa[0]), "r"(qb[0]), "r"(qa[1]), "r"(qb[1]), "r"(kk[0]), "r"(kk[1]), "f"(zero.x), "f"(zero.y),
                   "f"(zero.z), "f"(zero.w));
  }
#pragma unroll
  for (int kb = 0; kb < 4; kb++) {
    const uint32_t* kk = kb == 0 ? k0 : kb == 1 ? k1 : kb == 2 ? k2 : k3;
    mma16816(s[kb], qa[2], qb[2], qa[3], qb[3], kk[2], kk[3]);
  }
  l[0] = par ? s[1][1] : s[1][0];
  l[1] = early ? (par ? s[0][1] : s[0][0]) : (par ? s[2][1] : s[2][0]);
  l[2] = par ? s[2][3] : s[2][2];
  l[3] = early ? (par ? s[1][3] : s[1][2]) : (par ? s[3][3] : s[3][2]);
}

__device__ __forceinline__ void attn_mix(const float (&l)[4], const float (&sc)[4], const float (&off)[4], const float (&rk)[4],
                                         const uint32_t* v0, const uint32_t* v1, const uint32_t* v2, const uint32_t* v3,
                                         uint32_t* olo, uint32_t* ohi, const uint32_t (&sel)[4]) {
  float x[4];
#pragma unroll
  for (int e = 0; e < 4; e++) x[e] = fmaf(l[e], sc[e], off[e]);
  const float ml = quad_max(fmaxf(x[0], x[1])), mh = quad_max(fmaxf(x[2], x[3]));
  x[0] = ex2(x[0] - ml); x[1] = ex2(x[1] - ml);
  x[2] = ex2(x[2] - mh); x[3] = ex2(x[3] - mh);
  const uint32_t pl = pack_bf16(x[0] * rk[0], x[1] * rk[1]), ph = pack_bf16(x[2] * rk[2], x[3] * rk[3]);
  const uint32_t a0 = prmt_u(pl, sel[1]), a1 = prmt_u(pl, sel[3]), a2 = prmt_u(pl, sel[0]), a3 = prmt_u(ph, sel[1]);
  const uint32_t c0 = prmt_u(pl, sel[2]), c1 = prmt_u(ph, sel[0]), c2 = prmt_u(ph, sel[3]), c3 = prmt_u(ph, sel[2]);
  float o[4][4];
#pragma unroll
  for (int jn = 0; jn < 4; jn++) {
    o[jn][0] = o[jn][1] = o[jn][2] = o[jn][3] = 0.f;
    mma16816(o[jn], a0, a1, a2, a3, v0[jn], v1[jn]);
  }
#pragma unroll
  for (int jn = 0; jn < 4; jn++) mma16816(o[jn], c0, c1, c2, c3, v2[jn], v3[jn]);
  const float il = rcp_hw(quad_sum(x[0] + x[1])), ih = rcp_hw(quad_sum(x[2] + x[3]));
#pragma unroll
  for (int jn = 0; jn < 4; jn++) {
    olo[jn] = pack_bf16(o[jn][0] * il, o[jn][1] * il);
    ohi[jn] = pack_bf16(o[jn][2] * ih, o[jn][3] * ih);
  }
}

__device__ __forceinline__ void gelu_epilogue(const Params& p, float (&acc)[2][96], const Ctx& cx, int t) {
  UNPACK_CTX(cx);
  (void)wg;
  float rs[4], rm[4];
#pragma unroll
  for (int q = 0; q < 4; q++) {
    const float2 v = lds_f2(sb + OFF_ROW + (32 * w + 8 * q + (lane >> 2)) * 8);
    rs[q] = 0.5f * v.x;
    rm[q] = -rs[q] * v.y;
  }
  const int col0 = 128 * (t - 3), steps = t == 5 ? 6 : 4;
  const uint32_t stg = sb + OFF_STG + w * 4096;
  uint32_t ctab = sb + OFF_CSF + (col0 / 2 + (lane & 3)) * 16, srow = stg + lane * 128 + ((lane & 7) << 4);
  float v[2][16];
#define PULL(k) _Pragma("unroll") for (int j = 0; j < 4; j++) { \
      const float2 bb = lds_f2(ctab + j * 64 + 8); \
      _Pragma("unroll") for (int r = 0; r < 8; r++) \
        asm volatile("fma.rn.f32 %0, %1, %2, %3;" : "=f"(v[r >> 2][4 * j + (r & 3)]) \
                     : "f"(acc[r >> 2][16 * k + 4 * j + (r & 3)]), "f"(rs[(r >> 2) + (r & 2)]), "f"(r & 1 ? bb.y : bb.x)); }
  PULL(0)
#pragma unroll 1
  for (int it = 0;; it++) {
    uint32_t hp[4][4];
#pragma unroll
    for (int j = 0; j < 4; j++) {
      const float2 cs = lds_f2(ctab + j * 64);
#pragma unroll
      for (int q = 0; q < 4; q++) {
        float y[2];
        const int k = 4 * j + q - GELU_DEP;
        const float rmq = k >= 0 ? chain(rm[q], hp[k >> 2][k & 3], p.zero) : rm[q];
#pragma unroll
        for (int e = 0; e < 2; e++) {
          const float z = fmaf(rmq, e ? cs.y : cs.x, v[q & 1][4 * j + 2 * (q >> 1) + e]);
          const float u = z * fmaf(z * z, 8.f * 0.7978845608028654f * 0.044715f, 2.f * 0.7978845608028654f);
          y[e] = fmaf(z, tanh_hw(u), z);
        }
        hp[j][q] = pack_bf16(y[0], y[1]);
      }
    }
    ctab += 256;
    if (!(it & 1)) {
      if (lane == 0) bulk_wait_read();
      __syncwarp();
    }
#pragma unroll
    for (int j = 0; j < 4; j++) stsm4(srow ^ (j << 4), hp[j][0], hp[j][1], hp[j][2], hp[j][3]);
    srow ^= 64;
    if (it & 1) {
      fence_async_smem();
      __syncwarp();
      if (lane == 0) {
        tma_st2(&p.h_st, stg, 448 * n + col0 + 32 * (it - 1), 128 * m + 32 * w);
        bulk_commit();
      }
      if (it == steps - 1) break;
    }
    switch (it) {
      case 0: PULL(1) break;
      case 1: PULL(2) break;
      case 2: PULL(3) break;
      case 3: PULL(4) break;
      default: PULL(5)
    }
  }
#undef PULL
}

__device__ __forceinline__ void attn_epilogue(const Params& p, float (&acc)[2][96], const Ctx& cx, int layer, int t, uint32_t tag) {
  UNPACK_CTX(cx);
  const bool par = (lane >> 2) & 1, early = (lane & 3) > (lane >> 3);
  const uint32_t ktab = sb + OFF_ROW + (32 * w + 2 * (lane & 3) + par) * 8, exc = sb + OFF_STG + w * 4096 + lane * 16;
  const int slot = ((layer * 2 + t) * 16 + m) * 8 + n;
  const int mn = m * 8 + n; (void)mn;
  uint32_t Q[4][8], K[4][8], V[4][8], E[36], P[36];
  float kr[6], qr[4];
#pragma unroll
  for (int q = 2; q < 4; q++) {
    kr[2 + q] = lds_f(ktab + 64 * q);
#pragma unroll
    for (int j = 0; j < 8; j++) {
      E[8 * (q - 2) + j] = K[q][j] = pack_bf16(ACC(q, 8 + j, 0), ACC(q, 8 + j, 1));
      E[16 + 2 * j + q - 2] = V[q][j] = movtrans(pack_bf16(ACC(q, 16 + j, 0), ACC(q, 16 + j, 1)));
    }
  }
  E[32] = __float_as_uint(kr[4]);
  E[33] = E[34] = E[35] = __float_as_uint(kr[5]);
  if (w < 3) {
#pragma unroll
    for (int k = 0; k < 8; k++) sts_u4(exc + k * 512, E[4 * k], E[4 * k + 1], E[4 * k + 2], E[4 * k + 3]);
  } else {
#pragma unroll
    for (int k = 0; k < 12; k++) st_msg(g_halo + slot * 384 + k * 32 + lane, E[3 * k], E[3 * k + 1], E[3 * k + 2], tag);
  }
  PROF_E(7 * layer + t, 1);
#pragma unroll
  for (int q = 0; q < 4; q++) {
    qr[q] = lds_f(sb + OFF_ROW + (32 * w + 8 * q + (lane >> 2)) * 8) * (0.17677669529663687f * 1.4426950408889634f);
#pragma unroll
    for (int j = 0; j < 8; j++) Q[q][j] = pack_bf16(ACC(q, j, 0), ACC(q, j, 1));
    if (q < 2) {
      kr[2 + q] = lds_f(ktab + 64 * q);
#pragma unroll
      for (int j = 0; j < 8; j++) {
        K[q][j] = pack_bf16(ACC(q, 8 + j, 0), ACC(q, 8 + j, 1));
        V[q][j] = movtrans(pack_bf16(ACC(q, 16 + j, 0), ACC(q, 16 + j, 1)));
      }
    }
  }
  bar_sync(BAR_WG + wg, 128);
  if (w > 0 || m == 0) {
    const uint32_t back = w > 0;
#pragma unroll
    for (int k = 0; k < 8; k++) lds_u4(exc - back * 4096 + k * 512, P[4 * k], P[4 * k + 1], P[4 * k + 2], P[4 * k + 3]);
    P[32] = lds_u(ktab - back * 128);
    P[33] = lds_u(ktab - back * 64);
  } else {
#pragma unroll 1
    for (int it = 0; it < MSG_SPINS; it++) {
      uint32_t tg, bad = 0;
#pragma unroll
      for (int k = 0; k < 12; k++) {
        ld_msg(g_halo + (slot - 8) * 384 + k * 32 + lane, P[3 * k], P[3 * k + 1], P[3 * k + 2], tg);
        bad |= tg ^ tag;
      }
      if (__all_sync(0xffffffffu, bad == 0)) break;
    }
  }
  kr[0] = __uint_as_float(P[32]);
  kr[1] = __uint_as_float(P[33]);
  uint32_t PV[2][8];
#pragma unroll
  for (int j = 0; j < 8; j++) { PV[0][j] = P[16 + 2 * j]; PV[1][j] = P[17 + 2 * j]; }
  float rk[2][4], sc[2][4], off[2][4];
#pragma unroll
  for (int g = 0; g < 2; g++) {
    rk[g][0] = kr[2 * g + 1];
    rk[g][1] = early ? kr[2 * g] : kr[2 * g + 2];
    rk[g][2] = kr[2 * g + 2];
    rk[g][3] = early ? kr[2 * g + 1] : kr[2 * g + 3];
#pragma unroll
    for (int e = 0; e < 4; e++) {
      const bool masked = g == 0 && e != 2 && (m | w) == 0 && (e == 0 || early);
      sc[g][e] = masked ? 0.f : rk[g][e] * qr[2 * g + (e >> 1)];
      off[g][e] = masked ? -1e30f : 0.f;
    }
  }
  const uint32_t none = 0x4444u | p.zero, second = par ? 0x3244u : 0x4432u;
  const uint32_t sel[4] = {par ? 0x1044u : 0x4410u, early ? second : none, early ? none : second, none};
  PROF_E(7 * layer + t, 2);
  bar_sync(BAR_GO, 256);
  const float4 zero = lds_f4(sb + OFF_ZERO);
  float l[2][2][4];
  uint32_t O[4][8];
#pragma unroll
  for (int h = 0; h < 2; h++) {
    if (h == 1) {
      Q[2][4] |= __float_as_uint(l[1][0][0]) & p.zero;
      Q[0][4] |= __float_as_uint(l[0][0][0]) & p.zero;
    }
    attn_scores(&Q[2][4 * h], &Q[3][4 * h], &K[0][4 * h], &K[1][4 * h], &K[2][4 * h], &K[3][4 * h], l[1][h], zero, par, early);
    attn_scores(&Q[0][4 * h], &Q[1][4 * h], &P[4 * h], &P[8 + 4 * h], &K[0][4 * h], &K[1][4 * h], l[0][h], zero, par, early);
  }
  const uint32_t stg = sb + OFF_STG + w * 4096, srow = stg + lane * 128 + ((lane & 7) << 4);
#pragma unroll
  for (int h = 0; h < 2; h++) {
    attn_mix(l[1][h], sc[1], off[1], rk[1], &V[0][4 * h], &V[1][4 * h], &V[2][4 * h], &V[3][4 * h], &O[2][4 * h], &O[3][4 * h], sel);
    attn_mix(l[0][h], sc[0], off[0], rk[0], &PV[0][4 * h], &PV[1][4 * h], &V[0][4 * h], &V[1][4 * h], &O[0][4 * h], &O[1][4 * h], sel);
#pragma unroll
    for (int j = 4 * h; j < 4 * h + 4; j++) stsm4(srow ^ (j << 4), O[0][j], O[1][j], O[2][j], O[3][j]);
  }
  bar_arrive(BAR_DONE, 256);
  fence_async_smem();
  __syncwarp();
  if (lane == 0) {
    tma_st2(&p.att_st, stg, 128 * n + 64 * t, 128 * m + 32 * w);
    bulk_commit();
  }
}

__device__ __forceinline__ void consumer_tile(const Params& p, uint32_t sb0, int i, int mn) {
  const int layer = i >= 7, t = i - 7 * layer, wg = i & 1;
  const bool resid = t == 2 || t == 6;
  {
    float acc[2][96];
    if (resid) {
      const Ctx cx = make_ctx(sb0, mn);
      const uint32_t xrow = cx.sb + OFF_X + cx.w * 4096 + cx.lane * 128;
      const uint32_t sel_lo = 0x1044u | p.zero, sel_hi = 0x3244u | p.zero;
#pragma unroll
      for (int j = 0; j < 16; j++) {
        uint32_t r[4];
        ldsm4(xrow + (j >> 3) * 16384 + (((j & 7) ^ (cx.lane & 7)) << 4), r[0], r[1], r[2], r[3]);
#pragma unroll
        for (int q = 0; q < 4; q++) {
          ACC(q, j, 0) = prmt_f(r[q], sel_lo);
          ACC(q, j, 1) = prmt_f(r[q], sel_hi);
        }
      }
    } else {
#pragma unroll
      for (int r = 0; r < 64; r++) acc[0][r] = acc[1][r] = 0.f;
    }
#pragma unroll
    for (int r = 64; r < 96; r++) acc[0][r] = acc[1][r] = 0.f;
    const bool split = t == 3 || t == 4 || i == 7 || i == 8;
#pragma unroll 1
    for (int step = split ? 0 : 1;; step++) {
      if (step == 1 && (t == 1 || t == 4)) {
        const Ctx cx = make_ctx(sb0, mn);
        if (i == 1) {
          const uint32_t epoch = __ldcg(g_epoch + (mn & 127));
          bar_sync(BAR_INIT, 384);
          asm volatile("st.shared.u32 [%0], %1;" ::"r"(sb0 + OFF_TAG), "r"(epoch + 1) : "memory");
        }
        const uint32_t tag = lds_u(cx.sb + OFF_TAG);
        const int ln = (i + 1) >> 2;
#pragma unroll 1
        for (int r = 0; r < 2; r++) {
          if (i == 1) {
            if (cx.w < 3) {
              float a[8] = {0.f, 0.f, 0.f, 0.f, 0.f, 0.f, 0.f, 0.f};
              mbar_wait(sb0 + BAR_CSLD, r);
              sum_rows(cx.sb + OFF_STG + cx.w * 8192, 8, a, cx.lane);
              publish_sums(a, g_csp + (cx.n * 17 + cx.m) * 224 + (3 * r + cx.w) * 32, cx.lane, tag);
            }
            PROF_E(-1, 5 + r);
          }
          if (r == 1) break;
          if (i == 1) {
            bar_sync(BAR_WG + 1, 128);
            if (cx.w == 3 && elect_one()) {
              mbar_expect_tx(sb0 + BAR_CSLD, 24576);
              tma_ld3(sb0 + OFF_STG, &p.wqkv, sb0 + BAR_CSLD, 128 * cx.n + 64, 64 * cx.m, 0);
            }
            mbar_wait(sb0 + BAR_XRDY, 0);
            mbar_wait(sb0 + BAR_XRDY + 8, 0);
          }
          write_partial_stats(cx, ln, tag);
          PROF_E(i - 2, 8);
        }
        if (i <= 4) colsum_total(cx, ln, tag);
        PROF_E(i - 2, 9);
        if (i != 1) bar_sync(BAR_GUARD + wg, 256);
        finish_row_stats(cx, ln, tag);
        PROF_E(i - 2, 10);
        if (i <= 4) {
          colsum_gather(cx, ln, tag);
          if (i == 4) mbar_wait(sb0 + BAR_BIAS, 0);
          bar_sync(BAR_WG + wg, 128);
        }
        PROF_E(i - 2, 15);
        bar_arrive(BAR_GUARD + (wg ^ 1), 256);
      }
      if (step == 2 && !resid) bar_sync(BAR_GUARD + wg, 256);
      if (t + step == 2 || t == 6) {
        const Ctx cx = make_ctx(sb0, mn);
        float nm[4];
#pragma unroll
        for (int q = 0; q < 4; q++) nm[q] = t == 6 ? 1.f : -lds_f(cx.sb + OFF_ROW + (32 * cx.w + 8 * q + (cx.lane >> 2)) * 8 + 4);
        const uint32_t ctab = cx.sb + OFF_CSQ + ((t & 3) * 192 + 2 * (cx.lane & 3)) * 4;
#pragma unroll
        for (int j = 0; j < 24; j++) {
          const float2 cs = lds_f2(ctab + j * 32);
#pragma unroll
          for (int q = 0; q < 4; q++) {
            const int k = 4 * j + q - 1;
            const float nq = k >= 0 ? chain(nm[q], __float_as_uint(ACC(k & 3, k >> 2, 1)), p.zero) : nm[q];
            ACC(q, j, 0) = fmaf(nq, cs.x, ACC(q, j, 0));
            ACC(q, j, 1) = fmaf(nq, cs.y, ACC(q, j, 1));
          }
        }
      }
      if (step == 2) break;
      if (tile_wide(t)) {
        mainloop<192>(acc, sb0, i, split ? step : 2, mn);
      } else {
        mainloop<128>(acc, sb0, i, split ? step : 2, mn);
        if (resid) break;
      }
    }
    const Ctx cx = make_ctx(sb0, mn);
    if (resid) {
      const uint32_t xrow = cx.sb + OFF_X + cx.w * 4096 + cx.lane * 128;
#pragma unroll
      for (int j = 0; j < 16; j++) {
        stsm4(xrow + (j >> 3) * 16384 + (((j & 7) ^ (cx.lane & 7)) << 4), pack_bf16(ACC(0, j, 0), ACC(0, j, 1)),
              pack_bf16(ACC(1, j, 0), ACC(1, j, 1)), pack_bf16(ACC(2, j, 0), ACC(2, j, 1)), pack_bf16(ACC(3, j, 0), ACC(3, j, 1)));
        if ((j & 7) == 7) {
          fence_async_smem();
          __syncwarp();
          if (elect_one()) mbar_arrive(sb0 + BAR_XRDY + (j & 8));
        }
      }
      PROF_E(i, 4);
      return;
    }
    if (t < 2) attn_epilogue(p, acc, cx, layer, t, lds_u(sb0 + OFF_TAG));
    else gelu_epilogue(p, acc, cx, t);
    PROF_E(i, 4);
    if (cx.lane == 0) {
      bulk_wait_all();
      mbar_arrive(sb0 + BAR_PUB + 8 * (t < 2 ? t : t + 1));
    }
    __syncwarp();
    PROF_E(i, 5);
    if (i < 12) bar_arrive(BAR_GUARD + (wg ^ 1), 256);
  }
}

__global__ void __launch_bounds__(384, 1) fused_layers_kernel(const int by_smid, const __nv_bfloat16* x_p, const __nv_bfloat16* wqkv_p,
                                                                  const __grid_constant__ Params p) {
  extern __shared__ __align__(1024) uint8_t smem_raw[];
  const uint32_t sb = uniform((uint32_t)__cvta_generic_to_shared(smem_raw));
  const int tid = threadIdx.x, lane = tid & 31, warp = uniform(tid >> 5), wg = warp >> 2, w = warp & 3;

  int mn;
  {
    int id = blockIdx.x;
    if (by_smid) asm volatile("mov.u32 %0, %%smid;" : "=r"(id));
    else if (id >= 120) id += 4;
    const int c = id >> 1;
    int g, j;
    if (c < 32) { g = c & 7; j = c >> 3; }
    else if (c < 60) { g = 1 + (c - 32) % 7; j = 4 + (c - 32) / 7; }
    else { g = 0; j = c - 58; }
    mn = ((g >> 2) * 8 + j) * 8 + (g & 3) * 2 + (id & 1);
    if (c == 60 || c == 61) {
      if (tid < 32) {
        const uint32_t tag = __ldcg(g_epoch + NCTA + (id & 3)) + 1;
#pragma unroll 1
        for (int mm = 0; mm < 16; mm++) poll_line(g_flags + mm * 32 + (lane & 7), 32 * tag, 0xffu);
        if (tid == 0) g_epoch[NCTA + (id & 3)] = tag;
      }
      return;
    }
  }
  const int m = mn >> 3, n = mn & 7;
  if (tid == 256) PROF_U(1);
  if (tid >= 382) asm volatile("prefetch.global.L2 [%0];" ::"l"(tid & 1 ? wqkv_p + 128 * n : x_p + 128 * m * DM));
  if (wg < 2) {
    asm volatile("setmaxnreg.inc.sync.aligned.u32 232;");
#pragma unroll 1
    for (int i = wg; i < 14; i += 2) {
      consumer_tile(p, sb, i, mn | (warp << 7));
      PROF_T(6 + i * 4);
    }
  } else {
    asm volatile("setmaxnreg.dec.sync.aligned.u32 40;");
    if (w != 0) {
      bar_sync(BAR_INIT, 384);
      if (w == 1) producer<true>(p, sb, m, n, lane);
      else if (w == 3) colsum_helper(p, sb, m, n, lane);
      else if (elect_one()) publisher(p, sb, m, n);
    } else {
      if (elect_one()) {
#pragma unroll
        for (int k = 0; k < 4; k++) mbar_init(sb + BAR_FULL + 8 * k, 2);
        asm volatile("fence.mbarrier_init.release.cluster;" ::: "memory");
        PROF_U(4);
#pragma unroll 1
        for (int k = 0; k < 4; k++) {
          const uint32_t fb = sb + BAR_FULL + 8 * k;
          mbar_expect_tx(fb, 16384);
          tma_ld2(sb + (5 * k + 3) * UNIT, &p.xin, fb, 64 * k, 128 * m);
          mbar_expect_tx(fb, 3 * UNIT);
          tma_ld3(sb + 5 * k * UNIT, &p.wqkv, fb, 128 * n, 64 * k, 0);
        }
        PROF_U(5);
        mbar_init(sb + BAR_XRDY, 4);
        mbar_init(sb + BAR_XRDY + 8, 4);
        mbar_init(sb + BAR_FULL + 32, 2);
#pragma unroll
        for (int k = 0; k < NBAR; k++) mbar_init(sb + BAR_EMPTY + 8 * k, 4);
        mbar_init(sb + BAR_DUMMY, 4);
#pragma unroll
        for (int k = 0; k < 7; k++) mbar_init(sb + BAR_PUB + 8 * k, 4);
#pragma unroll
        for (int k = 0; k < 3; k++) mbar_init(sb + BAR_CSLD + 8 * k, 1);
        sts_f2(sb + OFF_ZERO, 0.f, 0.f);
        sts_f2(sb + OFF_ZERO + 8, 0.f, 0.f);
        asm volatile("fence.mbarrier_init.release.cluster;" ::: "memory");
        mbar_expect_tx(sb + BAR_CSLD, 24576);
        tma_ld3(sb + OFF_STG, &p.wqkv, sb + BAR_CSLD, 128 * n, 64 * m, 0);
#pragma unroll 1
        for (int h = 0; h < 2; h++) {
          const uint32_t xr = sb + BAR_XRDY + 8 * h;
          mbar_expect_tx(xr, 16384);
          tma_ld2(sb + OFF_X + h * 16384, &p.xin, xr, 128 * n + 64 * h, 128 * m);
          asm volatile("mbarrier.arrive.shared::cta.b64 _, [%0], 3;" ::"r"(xr) : "memory");
        }
        PROF_U(6);
      }
      __syncwarp();
      bar_arrive(BAR_INIT, 384);
      producer<false>(p, sb, m, n, lane);
    }
  }
}

typedef CUresult (*EncodeFn)(CUtensorMap*, CUtensorMapDataType, cuuint32_t, void*, const cuuint64_t*, const cuuint64_t*,
                             const cuuint32_t*, const cuuint32_t*, CUtensorMapInterleave, CUtensorMapSwizzle,
                             CUtensorMapL2promotion, CUtensorMapFloatOOBfill);

void make_2d(EncodeFn enc, CUtensorMap* m, const void* ptr, uint64_t cols, uint64_t rows, uint32_t box_rows) {
  cuuint64_t d[2] = {cols, rows}, st[1] = {cols * 2};
  cuuint32_t b[2] = {64, box_rows}, e[2] = {1, 1};
  enc(m, CU_TENSOR_MAP_DATA_TYPE_BFLOAT16, 2, const_cast<void*>(ptr), d, st, b, e, CU_TENSOR_MAP_INTERLEAVE_NONE,
      CU_TENSOR_MAP_SWIZZLE_128B, CU_TENSOR_MAP_L2_PROMOTION_L2_128B, CU_TENSOR_MAP_FLOAT_OOB_FILL_NONE);
}
void make_3d(EncodeFn enc, CUtensorMap* m, const void* ptr, uint64_t d0, uint64_t rows, uint64_t d2, uint64_t row_bytes,
             uint64_t chunk_bytes, uint32_t box_chunks) {
  cuuint64_t d[3] = {d0, rows, d2}, st[2] = {row_bytes, chunk_bytes};
  cuuint32_t b[3] = {64, 64, box_chunks}, e[3] = {1, 1, 1};
  enc(m, CU_TENSOR_MAP_DATA_TYPE_BFLOAT16, 3, const_cast<void*>(ptr), d, st, b, e, CU_TENSOR_MAP_INTERLEAVE_NONE,
      CU_TENSOR_MAP_SWIZZLE_128B, CU_TENSOR_MAP_L2_PROMOTION_L2_128B, CU_TENSOR_MAP_FLOAT_OOB_FILL_NONE);
}

}

extern "C" void kernel_launch(void* const* d_in, const int* in_sizes, int n_in, void* d_out, int out_size) {
  (void)in_sizes; (void)n_in; (void)out_size;
  static EncodeFn enc = nullptr;
  static void *att = nullptr, *hbuf = nullptr;
  static int by_smid = 0;
  if (!enc) {
    void* fn = nullptr;
    cudaDriverEntryPointQueryResult q;
    cudaGetDriverEntryPoint("cuTensorMapEncodeTiled", &fn, cudaEnableDefault, &q);
    enc = (EncodeFn)fn;
    cudaGetSymbolAddress(&att, g_att);
    cudaGetSymbolAddress(&hbuf, g_h);
    cudaFuncSetAttribute(fused_layers_kernel, cudaFuncAttributeMaxDynamicSharedMemorySize, SMEM_BYTES);
    int sms = 0, per_sm = 0, dev = 0;
    cudaGetDevice(&dev);
    cudaDeviceGetAttribute(&sms, cudaDevAttrMultiProcessorCount, dev);
    cudaOccupancyMaxActiveBlocksPerMultiprocessor(&per_sm, fused_layers_kernel, 384, SMEM_BYTES);
    by_smid = sms == 132 && per_sm == 1;
  }
  Params p;
  make_2d(enc, &p.xin, d_in[0], DM, SEQ, 128);
  make_2d(enc, &p.out, d_out, DM, SEQ, 128);
  make_2d(enc, &p.att, att, DM, SEQ, 128);
  make_2d(enc, &p.h, hbuf, FF, SEQ, 128);
  make_2d(enc, &p.out_st, d_out, DM, SEQ, 32);
  make_2d(enc, &p.att_st, att, DM, SEQ, 32);
  make_2d(enc, &p.h_st, hbuf, FF, SEQ, 32);
  make_2d(enc, &p.w1c, d_in[4], FF, DM, 32);
  make_3d(enc, &p.wqkv, d_in[1], DM, DM, 3, 3 * DM * 2, DM * 2, 3);
  make_3d(enc, &p.wo, d_in[2], 64, DM, DM / 64, DM * 2, 128, 2);
  make_3d(enc, &p.w1a, d_in[4], 64, DM, FF / 64, FF * 2, 128, 3);
  make_3d(enc, &p.w1b, d_in[4], 64, DM, FF / 64, FF * 2, 128, 2);
  make_3d(enc, &p.w2, d_in[6], 64, FF, DM / 64, DM * 2, 128, 2);
  p.b1 = (const __nv_bfloat16*)d_in[5];
  p.b2 = (const __nv_bfloat16*)d_in[7];
  p.zero = 0;
  fused_layers_kernel<<<by_smid ? 132 : NCTA, 384, SMEM_BYTES>>>(by_smid, (const __nv_bfloat16*)d_in[0], (const __nv_bfloat16*)d_in[1], p);
}
```

```cpp
#include <cuda_runtime.h>
#include <cuda_bf16.h>
#include <cuda.h>
#include <stdint.h>

namespace {

constexpr int SEQ = 2048, DM = 1024, FF = 3584;
constexpr int NCTA = 128;
constexpr int NBAR = 5;

constexpr uint32_t RING_UNITS = 20, UNIT = 8192;
constexpr uint32_t OFF_X   = RING_UNITS * UNIT;
constexpr uint32_t OFF_STG = OFF_X + 32768;
constexpr uint32_t OFF_HLP = OFF_STG + 24576;
constexpr uint32_t OFF_CSQ = OFF_HLP + 4096;
constexpr uint32_t OFF_CSF = OFF_CSQ + 2048;
constexpr uint32_t OFF_ROW = OFF_CSF + 3584;
constexpr uint32_t OFF_BAR = OFF_ROW + 1024;
constexpr uint32_t SMEM_BYTES = OFF_BAR + 384;
constexpr uint32_t BAR_FULL = OFF_BAR, BAR_EMPTY = OFF_BAR + 8 * NBAR;
constexpr uint32_t BAR_XRDY = OFF_BAR + 80;
constexpr uint32_t BAR_DUMMY = OFF_BAR + 96, OFF_TAG = OFF_BAR + 104, OFF_ZERO = OFF_BAR + 112;
constexpr uint32_t BAR_PUB = OFF_BAR + 128;
constexpr uint32_t BAR_CSLD = OFF_BAR + 200;
constexpr uint32_t BAR_BIAS = OFF_BAR + 216;

constexpr uint64_t DESC_A = (1ull << 62) | ((uint64_t)(2048 >> 4) << 32) | (1ull << 16);
constexpr uint64_t DESC_B = (1ull << 62) | ((uint64_t)(1024 >> 4) << 32) | ((uint64_t)(8192 >> 4) << 16);

constexpr int BAR_INIT = 0, BAR_ORDER = 1, BAR_GUARD = 3, BAR_WG = 5, BAR_GO = 7, BAR_DONE = 8;
#define GELU_DEP 3
#define LATE_O 0
#define WIN1 7
#define WIN2 3

struct Params {
  CUtensorMap xin, out, att, h, wqkv, wo, w1a, w1b, w2, out_st, att_st, h_st, w1c;
  const __nv_bfloat16 *b1, *b2;
  uint32_t zero;
};

__device__ __nv_bfloat16 g_att[SEQ * DM];
__device__ __nv_bfloat16 g_h[SEQ * FF];
__device__ uint4 g_stats[4 * 8 * SEQ];
__device__ uint4 g_halo[2 * 2 * 16 * 8 * 384];
__device__ uint4 g_csp[2 * 8 * 17 * 224];
__device__ uint32_t g_flags[16 * 32];
__device__ uint32_t g_epoch[NCTA + 4];
#define PROF_T(idx)
#define PROF_U(k)
#define PROF_S(g)
#define PROF_E(i, k)

__device__ __forceinline__ void mbar_init(uint32_t bar, int cnt) {
  asm volatile("mbarrier.init.shared::cta.b64 [%0], %1;" ::"r"(bar), "r"(cnt));
}
__device__ __forceinline__ void mbar_expect_tx(uint32_t bar, uint32_t bytes) {
  asm volatile("mbarrier.arrive.expect_tx.shared::cta.b64 _, [%0], %1;" ::"r"(bar), "r"(bytes) : "memory");
}
__device__ __forceinline__ void mbar_arrive(uint32_t bar) {
  asm volatile("mbarrier.arrive.shared::cta.b64 _, [%0];" ::"r"(bar) : "memory");
}
__device__ __forceinline__ bool mbar_test(uint32_t bar, uint32_t parity) {
  uint32_t ok;
  asm volatile("{\n.reg .pred p;\nmbarrier.test_wait.parity.shared::cta.b64 p, [%1], %2;\nselp.u32 %0, 1, 0, p;\n}"
               : "=r"(ok) : "r"(bar), "r"(parity) : "memory");
  return ok;
}
__device__ __forceinline__ void mbar_wait(uint32_t bar, uint32_t parity) {
  asm volatile(
      "{\n.reg .pred p;\n.reg .u32 it;\nmov.u32 it, 0;\n"
      "WAIT_LOOP:\n"
      "mbarrier.try_wait.parity.shared::cta.b64 p, [%0], %1;\n"
      "@p bra WAIT_DONE;\n"
      "add.u32 it, it, 1;\n"
      "setp.lt.u32 p, it, 0x400000;\n"
      "@p bra WAIT_LOOP;\n"
      "trap;\n"
      "WAIT_DONE:\n}"
      ::"r"(bar), "r"(parity) : "memory");
}
__device__ __forceinline__ void bar_sync(int id, int n) { asm volatile("bar.sync %0, %1;" ::"r"(id), "r"(n) : "memory"); }
__device__ __forceinline__ void bar_arrive(int id, int n) { asm volatile("bar.arrive %0, %1;" ::"r"(id), "r"(n) : "memory"); }
__device__ __forceinline__ void tma_ld2(uint32_t dst, const CUtensorMap* m, uint32_t bar, int c0, int c1) {
  asm volatile("cp.async.bulk.tensor.2d.shared::cluster.global.mbarrier::complete_tx::bytes [%0], [%1, {%3, %4}], [%2];"
               ::"r"(dst), "l"(m), "r"(bar), "r"(c0), "r"(c1) : "memory");
}
__device__ __forceinline__ void tma_ld3(uint32_t dst, const CUtensorMap* m, uint32_t bar, int c0, int c1, int c2) {
  asm volatile("cp.async.bulk.tensor.3d.shared::cluster.global.mbarrier::complete_tx::bytes [%0], [%1, {%3, %4, %5}], [%2];"
               ::"r"(dst), "l"(m), "r"(bar), "r"(c0), "r"(c1), "r"(c2) : "memory");
}
__device__ __forceinline__ void tma_st2(const CUtensorMap* m, uint32_t src, int c0, int c1) {
  asm volatile("cp.async.bulk.tensor.2d.global.shared::cta.bulk_group [%0, {%2, %3}], [%1];"
               ::"l"(m), "r"(src), "r"(c0), "r"(c1) : "memory");
}
__device__ __forceinline__ void bulk_commit() { asm volatile("cp.async.bulk.commit_group;" ::: "memory"); }
__device__ __forceinline__ void bulk_wait_read() { asm volatile("cp.async.bulk.wait_group.read 0;" ::: "memory"); }
__device__ __forceinline__ void bulk_wait_all() { asm volatile("cp.async.bulk.wait_group 0;" ::: "memory"); }
__device__ __forceinline__ void fence_async_smem() { asm volatile("fence.proxy.async.shared::cta;" ::: "memory"); }
__device__ __forceinline__ void fence_async_global() { asm volatile("fence.proxy.async.global;" ::: "memory"); }
__device__ __forceinline__ void st_relaxed(uint32_t* p, uint32_t v) {
  asm volatile("st.relaxed.gpu.global.u32 [%0], %1;" ::"l"(p), "r"(v) : "memory");
}
__device__ __forceinline__ void st_msg(uint4* p, uint32_t a, uint32_t b, uint32_t c, uint32_t tag) {
  asm volatile("{\n.reg .b128 v;\nmov.b128 v, {%1, %2, %3, %4};\nst.relaxed.gpu.b128 [%0], v;\n}"
               ::"l"(p), "r"(a), "r"(b), "r"(c), "r"(tag) : "memory");
}
__device__ __forceinline__ void ld_msg(const uint4* p, uint32_t& a, uint32_t& b, uint32_t& c, uint32_t& tag) {
  asm volatile("{\n.reg .b128 v;\nld.relaxed.gpu.b128 v, [%4];\nmov.b128 {%0, %1, %2, %3}, v;\n}"
               : "=r"(a), "=r"(b), "=r"(c), "=r"(tag) : "l"(p) : "memory");
}
__device__ __forceinline__ bool elect_one() {
  uint32_t ok;
  asm volatile("{\n.reg .pred p;\nelect.sync _|p, 0xffffffff;\nselp.u32 %0, 1, 0, p;\n}" : "=r"(ok));
  return ok;
}
__device__ __forceinline__ int uniform(int v) { return __shfl_sync(0xffffffffu, v, 0); }
__device__ __forceinline__ uint32_t pack_bf16(float lo, float hi) {
  uint32_t r;
  asm("cvt.rn.bf16x2.f32 %0, %1, %2;" : "=r"(r) : "f"(hi), "f"(lo));
  return r;
}
__device__ __forceinline__ uint32_t prmt_u(uint32_t a, uint32_t sel) {
  uint32_t r;
  asm("prmt.b32 %0, %1, 0, %2;" : "=r"(r) : "r"(a), "r"(sel));
  return r;
}
__device__ __forceinline__ float prmt_f(uint32_t a, uint32_t sel) {
  float r;
  asm("{\n.reg .b32 t;\nprmt.b32 t, %1, 0, %2;\nmov.b32 %0, t;\n}" : "=f"(r) : "r"(a), "r"(sel));
  return r;
}
__device__ __forceinline__ float bf_lo(uint32_t v) { return __uint_as_float(v << 16); }
__device__ __forceinline__ float bf_hi(uint32_t v) { return __uint_as_float(v & 0xffff0000u); }
__device__ __forceinline__ void stsm4(uint32_t addr, uint32_t r0, uint32_t r1, uint32_t r2, uint32_t r3) {
  asm volatile("stmatrix.sync.aligned.m8n8.x4.shared.b16 [%0], {%1, %2, %3, %4};"
               ::"r"(addr), "r"(r0), "r"(r1), "r"(r2), "r"(r3) : "memory");
}
__device__ __forceinline__ void ldsm4(uint32_t addr, uint32_t& r0, uint32_t& r1, uint32_t& r2, uint32_t& r3) {
  asm volatile("ldmatrix.sync.aligned.m8n8.x4.shared.b16 {%0, %1, %2, %3}, [%4];"
               : "=r"(r0), "=r"(r1), "=r"(r2), "=r"(r3) : "r"(addr) : "memory");
}
__device__ __forceinline__ uint32_t movtrans(uint32_t a) {
  uint32_t d;
  asm volatile("movmatrix.sync.aligned.m8n8.trans.b16 %0, %1;" : "=r"(d) : "r"(a));
  return d;
}
__device__ __forceinline__ void mma16816(float (&c)[4], uint32_t a0, uint32_t a1, uint32_t a2, uint32_t a3, uint32_t b0, uint32_t b1) {
  asm volatile("mma.sync.aligned.m16n8k16.row.col.f32.bf16.bf16.f32 {%0,%1,%2,%3}, {%4,%5,%6,%7}, {%8,%9}, {%0,%1,%2,%3};"
               : "+f"(c[0]), "+f"(c[1]), "+f"(c[2]), "+f"(c[3])
               : "r"(a0), "r"(a1), "r"(a2), "r"(a3), "r"(b0), "r"(b1));
}
__device__ __forceinline__ float2 lds_f2(uint32_t a) {
  float2 v;
  asm volatile("ld.shared.v2.f32 {%0, %1}, [%2];" : "=f"(v.x), "=f"(v.y) : "r"(a) : "memory");
  return v;
}
__device__ __forceinline__ float4 lds_f4(uint32_t a) {
  float4 v;
  asm volatile("ld.shared.v4.f32 {%0, %1, %2, %3}, [%4];" : "=f"(v.x), "=f"(v.y), "=f"(v.z), "=f"(v.w) : "r"(a) : "memory");
  return v;
}
__device__ __forceinline__ float lds_f(uint32_t a) {
  float v;
  asm volatile("ld.shared.f32 %0, [%1];" : "=f"(v) : "r"(a) : "memory");
  return v;
}
__device__ __forceinline__ uint32_t lds_u(uint32_t a) {
  uint32_t v;
  asm volatile("ld.shared.u32 %0, [%1];" : "=r"(v) : "r"(a) : "memory");
  return v;
}
__device__ __forceinline__ void sts_f2(uint32_t a, float x, float y) {
  asm volatile("st.shared.v2.f32 [%0], {%1, %2};" ::"r"(a), "f"(x), "f"(y) : "memory");
}
__device__ __forceinline__ void sts_u4(uint32_t a, uint32_t x, uint32_t y, uint32_t z, uint32_t w) {
  asm volatile("st.shared.v4.u32 [%0], {%1, %2, %3, %4};" ::"r"(a), "r"(x), "r"(y), "r"(z), "r"(w) : "memory");
}
__device__ __forceinline__ void lds_u4(uint32_t a, uint32_t& x, uint32_t& y, uint32_t& z, uint32_t& w) {
  asm volatile("ld.shared.v4.u32 {%0, %1, %2, %3}, [%4];" : "=r"(x), "=r"(y), "=r"(z), "=r"(w) : "r"(a) : "memory");
}
__device__ __forceinline__ float ex2(float x) {
  float y;
  asm("ex2.approx.ftz.f32 %0, %1;" : "=f"(y) : "f"(x));
  return y;
}
__device__ __forceinline__ float rcp_hw(float x) {
  float y;
  asm("rcp.approx.ftz.f32 %0, %1;" : "=f"(y) : "f"(x));
  return y;
}
__device__ __forceinline__ float tanh_hw(float x) {
  float y;
  asm("tanh.approx.f32 %0, %1;" : "=f"(y) : "f"(x));
  return y;
}
__device__ __forceinline__ float quad_sum(float v) {
  v += __shfl_xor_sync(0xffffffffu, v, 1);
  return v + __shfl_xor_sync(0xffffffffu, v, 2);
}
__device__ __forceinline__ float quad_max(float v) {
  v = fmaxf(v, __shfl_xor_sync(0xffffffffu, v, 1));
  return fmaxf(v, __shfl_xor_sync(0xffffffffu, v, 2));
}

template <int N> __device__ __forceinline__ void wgmma_ss(float (&d)[96], uint64_t da, uint64_t db);
template <> __device__ __forceinline__ void wgmma_ss<128>(float (&d)[96], uint64_t da, uint64_t db) {
  asm volatile(
      "wgmma.mma_async.sync.aligned.m64n128k16.f32.bf16.bf16 {%0, %1, %2, %3, %4, %5, %6, %7, %8, %9, %10, %11, %12, %13, %14, %15, %16, %17, %18, %19, %20, %21, %22, %23, %24, %25, %26, %27, %28, %29, %30, %31, %32, %33, %34, %35, %36, %37, %38, %39, %40, %41, %42, %43, %44, %45, %46, %47, %48, %49, %50, %51, %52, %53, %54, %55, %56, %57, %58, %59, %60, %61, %62, %63}, %64, %65, 1, 1, 1, 0, 1;"
      : "+f"(d[0]), "+f"(d[1]), "+f"(d[2]), "+f"(d[3]), "+f"(d[4]), "+f"(d[5]), "+f"(d[6]), "+f"(d[7]), "+f"(d[8]), "+f"(d[9]), "+f"(d[10]), "+f"(d[11]), "+f"(d[12]), "+f"(d[13]), "+f"(d[14]), "+f"(d[15]), "+f"(d[16]), "+f"(d[17]), "+f"(d[18]), "+f"(d[19]), "+f"(d[20]), "+f"(d[21]), "+f"(d[22]), "+f"(d[23]), "+f"(d[24]), "+f"(d[25]), "+f"(d[26]), "+f"(d[27]), "+f"(d[28]), "+f"(d[29]), "+f"(d[30]), "+f"(d[31]), "+f"(d[32]), "+f"(d[33]), "+f"(d[34]), "+f"(d[35]), "+f"(d[36]), "+f"(d[37]), "+f"(d[38]), "+f"(d[39]), "+f"(d[40]), "+f"(d[41]), "+f"(d[42]), "+f"(d[43]), "+f"(d[44]), "+f"(d[45]), "+f"(d[46]), "+f"(d[47]), "+f"(d[48]), "+f"(d[49]), "+f"(d[50]), "+f"(d[51]), "+f"(d[52]), "+f"(d[53]), "+f"(d[54]), "+f"(d[55]), "+f"(d[56]), "+f"(d[57]), "+f"(d[58]), "+f"(d[59]), "+f"(d[60]), "+f"(d[61]), "+f"(d[62]), "+f"(d[63])
      : "l"(da), "l"(db));
}

template <> __device__ __forceinline__ void wgmma_ss<192>(float (&d)[96], uint64_t da, uint64_t db) {
  asm volatile(
      "wgmma.mma_async.sync.aligned.m64n192k16.f32.bf16.bf16 {%0, %1, %2, %3, %4, %5, %6, %7, %8, %9, %10, %11, %12, %13, %14, %15, %16, %17, %18, %19, %20, %21, %22, %23, %24, %25, %26, %27, %28, %29, %30, %31, %32, %33, %34, %35, %36, %37, %38, %39, %40, %41, %42, %43, %44, %45, %46, %47, %48, %49, %50, %51, %52, %53, %54, %55, %56, %57, %58, %59, %60, %61, %62, %63, %64, %65, %66, %67, %68, %69, %70, %71, %72, %73, %74, %75, %76, %77, %78, %79, %80, %81, %82, %83, %84, %85, %86, %87, %88, %89, %90, %91, %92, %93, %94, %95}, %96, %97, 1, 1, 1, 0, 1;"
      : "+f"(d[0]), "+f"(d[1]), "+f"(d[2]), "+f"(d[3]), "+f"(d[4]), "+f"(d[5]), "+f"(d[6]), "+f"(d[7]), "+f"(d[8]), "+f"(d[9]), "+f"(d[10]), "+f"(d[11]), "+f"(d[12]), "+f"(d[13]), "+f"(d[14]), "+f"(d[15]), "+f"(d[16]), "+f"(d[17]), "+f"(d[18]), "+f"(d[19]), "+f"(d[20]), "+f"(d[21]), "+f"(d[22]), "+f"(d[23]), "+f"(d[24]), "+f"(d[25]), "+f"(d[26]), "+f"(d[27]), "+f"(d[28]), "+f"(d[29]), "+f"(d[30]), "+f"(d[31]), "+f"(d[32]), "+f"(d[33]), "+f"(d[34]), "+f"(d[35]), "+f"(d[36]), "+f"(d[37]), "+f"(d[38]), "+f"(d[39]), "+f"(d[40]), "+f"(d[41]), "+f"(d[42]), "+f"(d[43]), "+f"(d[44]), "+f"(d[45]), "+f"(d[46]), "+f"(d[47]), "+f"(d[48]), "+f"(d[49]), "+f"(d[50]), "+f"(d[51]), "+f"(d[52]), "+f"(d[53]), "+f"(d[54]), "+f"(d[55]), "+f"(d[56]), "+f"(d[57]), "+f"(d[58]), "+f"(d[59]), "+f"(d[60]), "+f"(d[61]), "+f"(d[62]), "+f"(d[63]), "+f"(d[64]), "+f"(d[65]), "+f"(d[66]), "+f"(d[67]), "+f"(d[68]), "+f"(d[69]), "+f"(d[70]), "+f"(d[71]), "+f"(d[72]), "+f"(d[73]), "+f"(d[74]), "+f"(d[75]), "+f"(d[76]), "+f"(d[77]), "+f"(d[78]), "+f"(d[79]), "+f"(d[80]), "+f"(d[81]), "+f"(d[82]), "+f"(d[83]), "+f"(d[84]), "+f"(d[85]), "+f"(d[86]), "+f"(d[87]), "+f"(d[88]), "+f"(d[89]), "+f"(d[90]), "+f"(d[91]), "+f"(d[92]), "+f"(d[93]), "+f"(d[94]), "+f"(d[95])
      : "l"(da), "l"(db));
}

template <int R>
__device__ __forceinline__ void pin_regs(float (&a)[2][96]) {
#pragma unroll
  for (int m = 0; m < 2; m++)
#pragma unroll
    for (int i = 0; i < R; i++) asm volatile("" : "+f"(a[m][i])::"memory");
}

struct Ctx {
  uint32_t sb;
  int m, n, wg, w, lane;
};
__device__ __forceinline__ Ctx make_ctx(uint32_t sb, int id) {
  int lane;
  asm volatile("mov.u32 %0, %%laneid;" : "=r"(lane));
  asm volatile("" : "+r"(id), "+r"(sb));
  return Ctx{sb, (id >> 3) & 15, id & 7, id >> 9, (id >> 7) & 3, lane};
}
#define UNPACK_CTX(c) const uint32_t sb = c.sb; const int m = c.m, n = c.n, wg = c.wg, w = c.w, lane = c.lane

__device__ __forceinline__ uint32_t poll_line(const uint32_t* word, uint32_t target, uint32_t need) {
  uint32_t v;
  asm volatile(
      "{\n.reg .pred p;\n.reg .u32 it, m;\n.reg .s32 d;\nmov.u32 it, 0;\n"
      "POLL_LOOP:\n"
      "ld.relaxed.gpu.global.u32 %0, [%1];\n"
      "sub.s32 d, %0, %2;\n"
      "setp.ge.s32 p, d, 0;\n"
      "vote.sync.ballot.b32 m, p, 0xffffffff;\n"
      "and.b32 m, m, %3;\n"
      "setp.eq.u32 p, m, %3;\n"
      "@p bra.uni POLL_DONE;\n"
      "add.u32 it, it, 1;\n"
      "setp.lt.u32 p, it, 0x400000;\n"
      "@p bra.uni POLL_LOOP;\n"
      "trap;\n"
      "POLL_DONE:\n}"
      : "=&r"(v) : "l"(word), "r"(target), "r"(need) : "memory");
  return v;
}
__device__ __forceinline__ uint32_t ld_relaxed(const uint32_t* p) {
  uint32_t v;
  asm volatile("ld.relaxed.gpu.global.u32 %0, [%1];" : "=r"(v) : "l"(p) : "memory");
  return v;
}
__device__ __forceinline__ float chain(float x, uint32_t on, uint32_t zero) {
  return __uint_as_float(__float_as_uint(x) | (on & zero));
}
constexpr int MSG_SPINS = 1 << 20;

constexpr int STAGES_PER_LAYER = 152;
__device__ __forceinline__ int nib(uint64_t v, int i) { return (int)(v >> (4 * i)) & 15; }
__device__ __forceinline__ bool tile_wide(int t) { return (0x23 >> t) & 1; }
constexpr uint64_t ORDER_PLAIN = 0xFEDCBA9876543210ull, ORDER_X = 0xFEDCBA9765432180ull, ORDER_FIRST = 0xF7E6D5C4B3A29180ull;

__device__ __forceinline__ void weight_coords(const Params& p, int t, int n, const CUtensorMap*& map, int& c0, int& c2) {
  map = &p.wqkv + nib(0x4233100ull, t);
  c0 = t < 2 ? 128 * n + 64 * t : 0;
  c2 = t < 2 ? 0 : (t == 2 || t == 6) ? 2 * n : 7 * n + 2 * t - 6;
}

template <bool IS_A>
__device__ __forceinline__ void producer(const Params& p, uint32_t sb, int m, int n, int lane) {
  int inflight = 0, rph = 0, min_seen = 0, cur = 0;
  uint32_t b8 = 0, rb8 = 0, pos = 0, tag32 = 0, seen = 0;
  const uint32_t* word = g_flags + m * 32 + (lane & 7);
#pragma unroll 1
  for (int sg = 0; sg < 22; sg++) {
    const int layer = sg >= 11, s = sg == 1 ? 2 : sg == 2 ? 1 : sg - 11 * layer;
    const int t = nib(0x65434321010ull, s), kind = nib(0x32110021100ull, s);
    const bool wide = tile_wide(t), xtype = t != 2 && t != 6;
    const uint32_t bbytes = wide ? 3 * UNIT : 2 * UNIT;
    const int mul = t == 6 ? 7 * 64 : 2 * 64, count = 2 * nib(0x4871ull, kind);
    const uint64_t order0 = (sg < 2 ? ORDER_FIRST : xtype ? ORDER_X : ORDER_PLAIN) >> (kind == 1 ? 8 : 0);
    const int nr = sg < 2 ? 0 : n;
    int lags = s == 9 ? 0x55555545 : wide ? 0x55555555 : (s == 4 || s == 10) ? 0xAAAAAA55 : 0xAAAAAAAA;
    uint32_t own = t == 2 ? 0x100u : xtype && kind != 1 ? 3u : 0u;
    if (s >= 9) pos = (s + 6) * UNIT;
    const CUtensorMap* map;
    int c0 = 0, c2 = 0, ev = 0;
    if (IS_A) {
      map = &p.xin + (t == 2 ? 2 : t == 6 ? 3 : sg >= 4);
      ev = 9 * layer + (t < 2 ? -1 : t == 2 ? 1 : t < 6 ? 3 : 5);
      if (sg == 3) seen = tag32 = (__ldcg(g_epoch + m * 8 + n) + 1) << 5;
    } else {
      weight_coords(p, t, n, map, c0, c2);
    }
#pragma unroll 1
    for (int add = 0; add < (t == 6 ? 7 * 64 : 64); add += 64) {
      uint64_t order = order0;
      if (IS_A && (add == 128 || add == 256)) ev++;
#pragma unroll 1
      for (int k = count; k > 0; k--) {
        const int q = order & 7, hi = (order >> 3) & 1, lag = 2 + (lags & 3);
        const bool local = own & 1;
        order >>= 4;
        lags = (lags >> 2) & 0xBFFFFFFF;
        own >>= 1;
        const int src = (((nr & 6) + q) & 7) ^ (q < 2 && (xtype || hi) ? nr & 1 : 0);
        const int kc = mul * src + add + 64 * hi;
#pragma unroll 1
        for (; inflight > lag; inflight--) {
          mbar_wait(sb + BAR_EMPTY + rb8, rph);
          rb8 += 8;
          if (rb8 == 8 * NBAR) { rb8 = 0; rph ^= 1; }
        }
        const uint32_t fb = sb + BAR_FULL + b8;
        if (sg == 0 || (sg == 1 && k > 12)) {
        } else if (!IS_A) {
          if (elect_one()) {
            mbar_expect_tx(fb, bbytes);
            tma_ld3(sb + pos, map, fb, c0, kc, c2);
          }
        } else if (!local) {
          const bool check = min_seen < ev + hi;
          if (elect_one()) mbar_expect_tx(fb, 16384);
          if (check) {
            cur = max(cur, (int)(seen - tag32));
            if (__shfl_sync(0xffffffffu, cur, src) < ev + hi) cur = (int)(poll_line(word, tag32 + ev + hi, 1u << src) - tag32);
            asm volatile("fence.acquire.gpu;" ::: "memory");
            fence_async_global();
          }
          if (elect_one()) tma_ld2(sb + pos + bbytes, map, fb, kc, 128 * m);
          if (check) min_seen = __reduce_min_sync(0xffffffffu, cur);
          if (k == 4 && sg >= 3) seen = ld_relaxed(word);
        } else {
          if (t == 2) mbar_wait(sb + BAR_PUB + 8, layer);
          else if (k == 1 && (s == 0 || s == 5)) mbar_wait(sb + BAR_XRDY + 8, s == 5);
          if (elect_one()) mbar_arrive(fb);
        }
        inflight++;
        b8 += 8;
        if (b8 == 8 * NBAR) b8 = 0;
        pos += bbytes + 2 * UNIT;
        if (pos >= RING_UNITS * UNIT) pos -= RING_UNITS * UNIT;
      }
    }
  }
}

__device__ __forceinline__ void publisher(const Params& p, uint32_t sb, int m, int n) {
  const uint32_t tag = __ldcg(g_epoch + m * 8 + n) + 1;
  uint32_t* word = g_flags + m * 32 + n;
  const int mn = m * 8 + n; (void)mn;
  st_relaxed(word, 32 * tag);
#pragma unroll 1
  for (int c = 0; c < 18; c++) {
    const int e = c >= 9 ? c - 9 : c;
    if ((0x18C >> e) & 1) {
      const int half = (0x108 >> e) & 1;
      mbar_wait(sb + BAR_XRDY + 8 * half, e < 4);
#pragma unroll
      for (int w = 0; w < 4; w++) tma_st2(&p.out_st, sb + OFF_X + half * 16384 + w * 4096, 128 * n + 64 * half, 128 * m + 32 * w);
      bulk_commit();
      if (c >= 16) continue;
      bulk_wait_all();
      PROF_E(7 * (c >= 9) + (e < 4 ? 2 : 6), 11 + 2 * half);
    } else {
      mbar_wait(sb + BAR_PUB + 8 * e, c >= 9);
    }
    asm volatile("fence.release.gpu;" ::: "memory");
    st_relaxed(word, 32 * tag + c + 1);
    PROF_E(7 * (c >= 9) + nib(0x665432210ull, e), (0x108 >> e) & 1 ? 14 : 12);
  }
  g_epoch[m * 8 + n] = tag;
  bulk_wait_read();
}

__device__ __forceinline__ void sum_rows(uint32_t buf, int iters, float (&a)[8], int lane) {
  uint32_t addr = buf + (lane >> 3) * 128 + (((lane & 7) ^ (lane >> 3)) << 4);
#pragma unroll 1
  for (int it = 0; it < iters; it++) {
    uint32_t u[2][4];
    lds_u4(addr, u[0][0], u[0][1], u[0][2], u[0][3]);
    lds_u4((addr ^ 64) + 512, u[1][0], u[1][1], u[1][2], u[1][3]);
    addr += 1024;
#pragma unroll
    for (int e = 0; e < 8; e++) { a[2 * (e & 3)] += bf_lo(u[e >> 2][e & 3]); a[2 * (e & 3) + 1] += bf_hi(u[e >> 2][e & 3]); }
  }
}
__device__ __forceinline__ void publish_sums(const float (&a)[8], uint4* dst, int lane, uint32_t tag) {
  const bool u8 = lane & 8, u16 = lane & 16;
  float h4[4], h2[2];
#pragma unroll
  for (int e = 0; e < 4; e++) h4[e] = (u8 ? a[4 + e] : a[e]) + __shfl_xor_sync(0xffffffffu, u8 ? a[e] : a[4 + e], 8);
#pragma unroll
  for (int e = 0; e < 2; e++) h2[e] = (u16 ? h4[2 + e] : h4[e]) + __shfl_xor_sync(0xffffffffu, u16 ? h4[e] : h4[2 + e], 16);
  st_msg(dst + (lane & 7) * 4 + (u8 ? 2 : 0) + (u16 ? 1 : 0), __float_as_uint(h2[0]), __float_as_uint(h2[1]), 0u, tag);
}

__device__ __forceinline__ void colsum_helper(const Params& p, uint32_t sb, int m, int n, int lane) {
  const uint32_t tag = __ldcg(g_epoch + m * 8 + n) + 1;
  const int mn = m * 8 + n; (void)mn;
#pragma unroll 1
  for (int k = lane; k < 288; k += 32) {
    const uint32_t bb = __ldg(reinterpret_cast<const uint32_t*>(k < 224 ? p.b1 + 448 * n : p.b2 + 128 * n - 448) + k);
    const float sc = k < 224 ? 0.5f : 1.f;
    sts_f2(sb + (k < 224 ? OFF_CSF + k * 16 + 8 : OFF_CSQ + 1536 + (k - 224) * 8), sc * bf_lo(bb), sc * bf_hi(bb));
  }
  __syncwarp();
  if (elect_one()) mbar_arrive(sb + BAR_BIAS);
  PROF_E(-1, 1);
#pragma unroll 1
  for (int c = 0; c < 7; c++) {
    float a[8] = {0.f, 0.f, 0.f, 0.f, 0.f, 0.f, 0.f, 0.f};
#pragma unroll 1
    for (int h = 0; h < 2; h++) {
      if (elect_one()) {
        mbar_expect_tx(sb + BAR_CSLD + 8, 4096);
        tma_ld2(sb + OFF_HLP, &p.w1c, sb + BAR_CSLD + 8, 448 * n + 64 * c, 64 * m + 32 * h);
        if (c < 6) asm volatile("cp.async.bulk.prefetch.tensor.2d.L2.global [%0, {%1, %2}];" ::"l"(&p.w1c), "r"(448 * n + 64 * c + 64), "r"(64 * m + 32 * h) : "memory");
      }
      mbar_wait(sb + BAR_CSLD + 8, h);
      sum_rows(sb + OFF_HLP, 4, a, lane);
      __syncwarp();
    }
    publish_sums(a, g_csp + ((8 + n) * 17 + m) * 224 + c * 32, lane, tag);
  }
  PROF_E(-1, 2);
}

__device__ __forceinline__ void poll_msgs2(const uint4* pa, const uint4* pb, float (&v)[4], uint32_t tag) {
#pragma unroll 1
  for (int it = 0; it < MSG_SPINS; it++) {
    uint32_t x[4], z, ta, tb;
    ld_msg(pa, x[0], x[1], z, ta);
    ld_msg(pb, x[2], x[3], z, tb);
#pragma unroll
    for (int e = 0; e < 4; e++) v[e] = __uint_as_float(x[e]);
    if (__all_sync(0xffffffffu, ta == tag && tb == tag)) break;
  }
}
__device__ __forceinline__ void colsum_total(const Ctx& cx, int mat, uint32_t tag) {
  uint4* base = g_csp + (mat * 8 + cx.n) * 17 * 224;
  const int per = 12 + 2 * mat, k = 2 * cx.w + (cx.lane >> 4), ia = per * cx.m + k, ib = per * cx.m + min(k + 8, per - 1);
  float v[4];
  poll_msgs2(base + (cx.lane & 15) * 224 + ia, base + (cx.lane & 15) * 224 + ib, v, tag);
#pragma unroll 1
  for (int d = 1; d < 16; d *= 2)
#pragma unroll
    for (int e = 0; e < 4; e++) v[e] += __shfl_xor_sync(0xffffffffu, v[e], d);
  const bool hi = cx.lane & 1;
  if ((cx.lane & 14) == 0) st_msg(base + 16 * 224 + (hi ? ib : ia), __float_as_uint(hi ? v[2] : v[0]), __float_as_uint(hi ? v[3] : v[1]), 0u, tag);
}
__device__ __forceinline__ void colsum_gather(const Ctx& cx, int mat, uint32_t tag) {
  const uint4* base = g_csp + ((mat * 8 + cx.n) * 17 + 16) * 224;
  const int ia = cx.w * 32 + cx.lane, ib = min(ia + 128, 191 + 32 * mat);
  float v[4];
  poll_msgs2(base + ia, base + ib, v, tag);
  const uint32_t tab = cx.sb + (mat ? OFF_CSF : OFF_CSQ);
  sts_f2(tab + (ia << (3 + mat)), v[0], v[1]);
  sts_f2(tab + (ib << (3 + mat)), v[2], v[3]);
}

template <int N>
__device__ __forceinline__ void mainloop(float (&acc)[2][96], uint32_t sb, int i, int part, int mn) {
  constexpr uint32_t Z16 = (2 + N / 64) * (UNIT >> 4), RING16 = RING_UNITS * (UNIT >> 4);
  constexpr uint32_t A_OFF = Z16 - 1024 + (uint32_t)DESC_A - (uint32_t)DESC_B;
  const int wg = i & 1;
  const int layer = i >= 7, t = i - 7 * layer;
  const bool own = t != 2 && t != 6 && part != 1 && i != 0, second = t == 1 || t == 4;
  const int gl = 16 * t + (part == 2 ? 0 : second ? 16 * part - 14 : 4 * part), g0 = layer * STAGES_PER_LAYER + gl;
  const uint32_t s16 = (sb & 0x3FFFF) >> 4;
  const uint32_t bfirst = (uint32_t)DESC_B + s16;
  const uint32_t blast = uniform(bfirst + RING16 - Z16), flast = uniform(sb + BAR_FULL + 8 * (NBAR - 1));
  const int nkb = t == 6 ? 56 : part == 0 ? 2 : 12 + 2 * part;
  const bool win1 = t == 1 && part != 0;
  int run = uniform(win1 ? WIN1 + 1 : t == 2 ? WIN2 + 1 : nkb);
  int rest = win1 ? 64 | (nkb - 1 - WIN1) : t == 2 ? 64 | (7 - WIN2) | (8 << 7) : 0;
  uint32_t fb = sb + BAR_FULL + 8 * (g0 % NBAR), ph = (g0 / NBAR) & 1;
  uint32_t prev = sb + BAR_DUMMY - 8 * NBAR;
  uint32_t blo = bfirst + Z16 * (N == 192 ? (gl + (t == 5 ? 3 : 0)) & 3 : (gl + 3) % 5);
  uint32_t alo = own ? (uint32_t)DESC_A + s16 + (OFF_X >> 4) : blo + A_OFF;
  uint32_t aoff = own ? alo + 1024 - (blo == blast ? bfirst : blo + Z16) : A_OFF;
  pin_regs<N / 2>(acc);
  if (N == 192 && i == 0 && threadIdx.x == 0) PROF_U(7);
  bar_sync(i > 0 ? BAR_ORDER + wg : BAR_INIT, i > 0 ? 256 : 384);
  if (N == 192 && i == 0 && threadIdx.x == 0) PROF_U(8);
  if (t == (N == 192 ? 0 : 3) && part == 0) mbar_wait(sb + BAR_XRDY, N == 128);
  if (N == 192 && i == 0 && threadIdx.x == 0) PROF_U(9);
  mbar_wait(fb, ph);
  if (part != 1) PROF_T(4 + i * 4);
#pragma unroll 1
  while (true) {
    const uint64_t da = (DESC_A & ~0xffffffffull) | alo, db = (DESC_B & ~0xffffffffull) | blo;
    asm volatile("wgmma.fence.sync.aligned;" ::: "memory");
    wgmma_ss<N>(acc[0], da, db);
    wgmma_ss<N>(acc[1], da + 64, db);
    wgmma_ss<N>(acc[0], da + 2, db + 128);
    wgmma_ss<N>(acc[1], da + 66, db + 128);
    asm volatile("wgmma.commit_group.sync.aligned;" ::: "memory");
    asm volatile("wgmma.wait_group.sync.aligned 1;" ::: "memory");
    PROF_S(g0 + jj++);
    if (elect_one()) mbar_arrive(prev + 8 * NBAR);
    prev = fb;
    if (fb == flast) { fb -= 8 * NBAR; ph++; }
    fb += 8;
    if (blo == blast) blo -= RING16;
    blo += Z16;
    alo = blo + aoff;
    aoff = A_OFF;
    run--;
    const bool ready = mbar_test(fb, ph) && run != 0;
    asm volatile("wgmma.fence.sync.aligned;" ::: "memory");
    wgmma_ss<N>(acc[0], da + 4, db + 256);
    wgmma_ss<N>(acc[1], da + 68, db + 256);
    wgmma_ss<N>(acc[0], da + 6, db + 384);
    wgmma_ss<N>(acc[1], da + 70, db + 384);
    asm volatile("wgmma.commit_group.sync.aligned;" ::: "memory");
    if (!ready) {
      if (run == 0) {
        if (rest == 0) break;
        if (rest & 64) {
          bar_arrive(BAR_GO, 256);
          bar_sync(BAR_DONE, 256);
        } else {
          alo = (uint32_t)DESC_A + s16 + (OFF_STG >> 4);
        }
        run = rest & 63;
        rest >>= 7;
      }
      mbar_wait(fb, ph);
    }
  }
  if (i < 13 && !(LATE_O && win1)) bar_arrive(BAR_ORDER + (wg ^ 1), 256);
  asm volatile("wgmma.wait_group.sync.aligned 0;" ::: "memory");
  pin_regs<N / 2>(acc);
  if (elect_one()) mbar_arrive(prev + 8 * NBAR);
  PROF_T(5 + i * 4);
  PROF_E(i, 0);
}

#define ACC(q, j, e) acc[(q) & 1][4 * (j) + 2 * ((q) >> 1) + (e)]

__device__ __forceinline__ void write_partial_stats(const Ctx& c, int ln, uint32_t tag) {
  const uint32_t xrow = c.sb + OFF_X + c.w * 4096 + c.lane * 128;
  float s = 0.f, q = 0.f, s1 = 0.f, q1 = 0.f;
#pragma unroll 2
  for (int j = 0; j < 16; j++) {
    uint32_t u[4];
    lds_u4(xrow + (j >> 3) * 16384 + (((j & 7) ^ (c.lane & 7)) << 4), u[0], u[1], u[2], u[3]);
#pragma unroll
    for (int e = 0; e < 4; e++) {
      const float a = bf_lo(u[e]), d = bf_hi(u[e]);
      s += a; q = fmaf(a, a, q);
      s1 += d; q1 = fmaf(d, d, q1);
    }
  }
  s += s1;
  q += q1;
  st_msg(g_stats + (ln * 8 + c.n) * SEQ + 128 * c.m + 32 * c.w + c.lane, __float_as_uint(s),
         __float_as_uint(fmaxf(q - s * s * (1.f / 128.f), 0.f)), 0u, tag);
}

__device__ __forceinline__ void finish_row_stats(const Ctx& c, int ln, uint32_t tag) {
  const uint4* src = g_stats + ln * 8 * SEQ + 128 * c.m + 32 * c.w + c.lane;
  uint32_t ps[8], pm[8];
#pragma unroll 1
  for (int it = 0; it < MSG_SPINS; it++) {
    uint32_t bad = 0, u, tg;
#pragma unroll
    for (int k = 0; k < 8; k++) { ld_msg(src + k * SEQ, ps[k], pm[k], u, tg); bad |= tg ^ tag; }
    if (__all_sync(0xffffffffu, bad == 0)) break;
  }
  float s = 0.f, m2 = 0.f;
#pragma unroll
  for (int k = 0; k < 8; k++) s += __uint_as_float(ps[k]);
  const float mean = s * (1.f / DM);
#pragma unroll
  for (int k = 0; k < 8; k++) {
    const float d = __uint_as_float(ps[k]) * (1.f / 128.f) - mean;
    m2 += fmaf(128.f * d, d, __uint_as_float(pm[k]));
  }
  sts_f2(c.sb + OFF_ROW + (32 * c.w + c.lane) * 8, rsqrtf(m2 * (1.f / DM) + 1e-5f), mean);
  __syncwarp();
}

__device__ __forceinline__ void attn_scores(const uint32_t* qa, const uint32_t* qb, const uint32_t* k0, const uint32_t* k1,
                                            const uint32_t* k2, const uint32_t* k3, float (&l)[4], const float4& zero,
                                            bool par, bool early) {
  float s[4][4];
#pragma unroll
  for (int kb = 0; kb < 4; kb++) {
    const uint32_t* kk = kb == 0 ? k0 : kb == 1 ? k1 : kb == 2 ? k2 : k3;
    asm volatile("mma.sync.aligned.m16n8k16.row.col.f32.bf16.bf16.f32 {%0,%1,%2,%3}, {%4,%5,%6,%7}, {%8,%9}, {%10,%11,%12,%13};"
                 : "=f"(s[kb][0]), "=f"(s[kb][1]), "=f"(s[kb][2]), "=f"(s[kb][3])
                 : "r"(qa[0]), "r"(qb[0]), "r"(qa[1]), "r"(qb[1]), "r"(kk[0]), "r"(kk[1]), "f"(zero.x), "f"(zero.y),
                   "f"(zero.z), "f"(zero.w));
  }
#pragma unroll
  for (int kb = 0; kb < 4; kb++) {
    const uint32_t* kk = kb == 0 ? k0 : kb == 1 ? k1 : kb == 2 ? k2 : k3;
    mma16816(s[kb], qa[2], qb[2], qa[3], qb[3], kk[2], kk[3]);
  }
  l[0] = par ? s[1][1] : s[1][0];
  l[1] = early ? (par ? s[0][1] : s[0][0]) : (par ? s[2][1] : s[2][0]);
  l[2] = par ? s[2][3] : s[2][2];
  l[3] = early ? (par ? s[1][3] : s[1][2]) : (par ? s[3][3] : s[3][2]);
}

__device__ __forceinline__ void attn_mix(const float (&l)[4], const float (&sc)[4], const float (&off)[4], const float (&rk)[4],
                                         const uint32_t* v0, const uint32_t* v1, const uint32_t* v2, const uint32_t* v3,
                                         uint32_t* olo, uint32_t* ohi, const uint32_t (&sel)[4]) {
  float x[4];
#pragma unroll
  for (int e = 0; e < 4; e++) x[e] = fmaf(l[e], sc[e], off[e]);
  const float ml = quad_max(fmaxf(x[0], x[1])), mh = quad_max(fmaxf(x[2], x[3]));
  x[0] = ex2(x[0] - ml); x[1] = ex2(x[1] - ml);
  x[2] = ex2(x[2] - mh); x[3] = ex2(x[3] - mh);
  const uint32_t pl = pack_bf16(x[0] * rk[0], x[1] * rk[1]), ph = pack_bf16(x[2] * rk[2], x[3] * rk[3]);
  const uint32_t a0 = prmt_u(pl, sel[1]), a1 = prmt_u(pl, sel[3]), a2 = prmt_u(pl, sel[0]), a3 = prmt_u(ph, sel[1]);
  const uint32_t c0 = prmt_u(pl, sel[2]), c1 = prmt_u(ph, sel[0]), c2 = prmt_u(ph, sel[3]), c3 = prmt_u(ph, sel[2]);
  float o[4][4];
#pragma unroll
  for (int jn = 0; jn < 4; jn++) {
    o[jn][0] = o[jn][1] = o[jn][2] = o[jn][3] = 0.f;
    mma16816(o[jn], a0, a1, a2, a3, v0[jn], v1[jn]);
  }
#pragma unroll
  for (int jn = 0; jn < 4; jn++) mma16816(o[jn], c0, c1, c2, c3, v2[jn], v3[jn]);
  const float il = rcp_hw(quad_sum(x[0] + x[1])), ih = rcp_hw(quad_sum(x[2] + x[3]));
#pragma unroll
  for (int jn = 0; jn < 4; jn++) {
    olo[jn] = pack_bf16(o[jn][0] * il, o[jn][1] * il);
    ohi[jn] = pack_bf16(o[jn][2] * ih, o[jn][3] * ih);
  }
}

__device__ __forceinline__ void gelu_epilogue(const Params& p, float (&acc)[2][96], const Ctx& cx, int t) {
  UNPACK_CTX(cx);
  (void)wg;
  float rs[4], rm[4];
#pragma unroll
  for (int q = 0; q < 4; q++) {
    const float2 v = lds_f2(sb + OFF_ROW + (32 * w + 8 * q + (lane >> 2)) * 8);
    rs[q] = 0.5f * v.x;
    rm[q] = -rs[q] * v.y;
  }
  const int col0 = 128 * (t - 3), steps = t == 5 ? 6 : 4;
  const uint32_t stg = sb + OFF_STG + w * 4096;
  uint32_t ctab = sb + OFF_CSF + (col0 / 2 + (lane & 3)) * 16, srow = stg + lane * 128 + ((lane & 7) << 4);
  float v[2][16];
#define PULL(k) _Pragma("unroll") for (int j = 0; j < 4; j++) { \
      const float2 bb = lds_f2(ctab + j * 64 + 8); \
      _Pragma("unroll") for (int r = 0; r < 8; r++) \
        asm volatile("fma.rn.f32 %0, %1, %2, %3;" : "=f"(v[r >> 2][4 * j + (r & 3)]) \
                     : "f"(acc[r >> 2][16 * k + 4 * j + (r & 3)]), "f"(rs[(r >> 2) + (r & 2)]), "f"(r & 1 ? bb.y : bb.x)); }
  PULL(0)
#pragma unroll 1
  for (int it = 0;; it++) {
    uint32_t hp[4][4];
#pragma unroll
    for (int j = 0; j < 4; j++) {
      const float2 cs = lds_f2(ctab + j * 64);
#pragma unroll
      for (int q = 0; q < 4; q++) {
        float y[2];
        const int k = 4 * j + q - GELU_DEP;
        const float rmq = k >= 0 ? chain(rm[q], hp[k >> 2][k & 3], p.zero) : rm[q];
#pragma unroll
        for (int e = 0; e < 2; e++) {
          const float z = fmaf(rmq, e ? cs.y : cs.x, v[q & 1][4 * j + 2 * (q >> 1) + e]);
          const float u = z * fmaf(z * z, 8.f * 0.7978845608028654f * 0.044715f, 2.f * 0.7978845608028654f);
          y[e] = fmaf(z, tanh_hw(u), z);
        }
        hp[j][q] = pack_bf16(y[0], y[1]);
      }
    }
    ctab += 256;
    if (!(it & 1)) {
      if (lane == 0) bulk_wait_read();
      __syncwarp();
    }
#pragma unroll
    for (int j = 0; j < 4; j++) stsm4(srow ^ (j << 4), hp[j][0], hp[j][1], hp[j][2], hp[j][3]);
    srow ^= 64;
    if (it & 1) {
      fence_async_smem();
      __syncwarp();
      if (lane == 0) {
        tma_st2(&p.h_st, stg, 448 * n + col0 + 32 * (it - 1), 128 * m + 32 * w);
        bulk_commit();
      }
      if (it == steps - 1) break;
    }
    switch (it) {
      case 0: PULL(1) break;
      case 1: PULL(2) break;
      case 2: PULL(3) break;
      case 3: PULL(4) break;
      default: PULL(5)
    }
  }
#undef PULL
}

__device__ __forceinline__ void attn_epilogue(const Params& p, float (&acc)[2][96], const Ctx& cx, int layer, int t, uint32_t tag) {
  UNPACK_CTX(cx);
  const bool par = (lane >> 2) & 1, early = (lane & 3) > (lane >> 3);
  const uint32_t ktab = sb + OFF_ROW + (32 * w + 2 * (lane & 3) + par) * 8, exc = sb + OFF_STG + w * 4096 + lane * 16;
  const int slot = ((layer * 2 + t) * 16 + m) * 8 + n;
  const int mn = m * 8 + n; (void)mn;
  uint32_t Q[4][8], K[4][8], V[4][8], E[36], P[36];
  float kr[6], qr[4];
#pragma unroll
  for (int q = 2; q < 4; q++) {
    kr[2 + q] = lds_f(ktab + 64 * q);
#pragma unroll
    for (int j = 0; j < 8; j++) {
      E[8 * (q - 2) + j] = K[q][j] = pack_bf16(ACC(q, 8 + j, 0), ACC(q, 8 + j, 1));
      E[16 + 2 * j + q - 2] = V[q][j] = movtrans(pack_bf16(ACC(q, 16 + j, 0), ACC(q, 16 + j, 1)));
    }
  }
  E[32] = __float_as_uint(kr[4]);
  E[33] = E[34] = E[35] = __float_as_uint(kr[5]);
  if (w < 3) {
#pragma unroll
    for (int k = 0; k < 8; k++) sts_u4(exc + k * 512, E[4 * k], E[4 * k + 1], E[4 * k + 2], E[4 * k + 3]);
  } else {
#pragma unroll
    for (int k = 0; k < 12; k++) st_msg(g_halo + slot * 384 + k * 32 + lane, E[3 * k], E[3 * k + 1], E[3 * k + 2], tag);
  }
  if (LATE_O && t == 1) bar_arrive(BAR_ORDER + (wg ^ 1), 256);
  PROF_E(7 * layer + t, 1);
#pragma unroll
  for (int q = 0; q < 4; q++) {
    qr[q] = lds_f(sb + OFF_ROW + (32 * w + 8 * q + (lane >> 2)) * 8) * (0.17677669529663687f * 1.4426950408889634f);
#pragma unroll
    for (int j = 0; j < 8; j++) Q[q][j] = pack_bf16(ACC(q, j, 0), ACC(q, j, 1));
    if (q < 2) {
      kr[2 + q] = lds_f(ktab + 64 * q);
#pragma unroll
      for (int j = 0; j < 8; j++) {
        K[q][j] = pack_bf16(ACC(q, 8 + j, 0), ACC(q, 8 + j, 1));
        V[q][j] = movtrans(pack_bf16(ACC(q, 16 + j, 0), ACC(q, 16 + j, 1)));
      }
    }
  }
  bar_sync(BAR_WG + wg, 128);
  if (w > 0 || m == 0) {
    const uint32_t back = w > 0;
#pragma unroll
    for (int k = 0; k < 8; k++) lds_u4(exc - back * 4096 + k * 512, P[4 * k], P[4 * k + 1], P[4 * k + 2], P[4 * k + 3]);
    P[32] = lds_u(ktab - back * 128);
    P[33] = lds_u(ktab - back * 64);
  } else {
#pragma unroll 1
    for (int it = 0; it < MSG_SPINS; it++) {
      uint32_t tg, bad = 0;
#pragma unroll
      for (int k = 0; k < 12; k++) {
        ld_msg(g_halo + (slot - 8) * 384 + k * 32 + lane, P[3 * k], P[3 * k + 1], P[3 * k + 2], tg);
        bad |= tg ^ tag;
      }
      if (__all_sync(0xffffffffu, bad == 0)) break;
    }
  }
  kr[0] = __uint_as_float(P[32]);
  kr[1] = __uint_as_float(P[33]);
  uint32_t PV[2][8];
#pragma unroll
  for (int j = 0; j < 8; j++) { PV[0][j] = P[16 + 2 * j]; PV[1][j] = P[17 + 2 * j]; }
  float rk[2][4], sc[2][4], off[2][4];
#pragma unroll
  for (int g = 0; g < 2; g++) {
    rk[g][0] = kr[2 * g + 1];
    rk[g][1] = early ? kr[2 * g] : kr[2 * g + 2];
    rk[g][2] = kr[2 * g + 2];
    rk[g][3] = early ? kr[2 * g + 1] : kr[2 * g + 3];
#pragma unroll
    for (int e = 0; e < 4; e++) {
      const bool masked = g == 0 && e != 2 && (m | w) == 0 && (e == 0 || early);
      sc[g][e] = masked ? 0.f : rk[g][e] * qr[2 * g + (e >> 1)];
      off[g][e] = masked ? -1e30f : 0.f;
    }
  }
  const uint32_t none = 0x4444u | p.zero, second = par ? 0x3244u : 0x4432u;
  const uint32_t sel[4] = {par ? 0x1044u : 0x4410u, early ? second : none, early ? none : second, none};
  PROF_E(7 * layer + t, 2);
  bar_sync(BAR_GO, 256);
  const float4 zero = lds_f4(sb + OFF_ZERO);
  float l[2][2][4];
  uint32_t O[4][8];
#pragma unroll
  for (int h = 0; h < 2; h++) {
    if (h == 1) {
      Q[2][4] |= __float_as_uint(l[1][0][0]) & p.zero;
      Q[0][4] |= __float_as_uint(l[0][0][0]) & p.zero;
    }
    attn_scores(&Q[2][4 * h], &Q[3][4 * h], &K[0][4 * h], &K[1][4 * h], &K[2][4 * h], &K[3][4 * h], l[1][h], zero, par, early);
    attn_scores(&Q[0][4 * h], &Q[1][4 * h], &P[4 * h], &P[8 + 4 * h], &K[0][4 * h], &K[1][4 * h], l[0][h], zero, par, early);
  }
  const uint32_t stg = sb + OFF_STG + w * 4096, srow = stg + lane * 128 + ((lane & 7) << 4);
#pragma unroll
  for (int h = 0; h < 2; h++) {
    attn_mix(l[1][h], sc[1], off[1], rk[1], &V[0][4 * h], &V[1][4 * h], &V[2][4 * h], &V[3][4 * h], &O[2][4 * h], &O[3][4 * h], sel);
    attn_mix(l[0][h], sc[0], off[0], rk[0], &PV[0][4 * h], &PV[1][4 * h], &V[0][4 * h], &V[1][4 * h], &O[0][4 * h], &O[1][4 * h], sel);
#pragma unroll
    for (int j = 4 * h; j < 4 * h + 4; j++) stsm4(srow ^ (j << 4), O[0][j], O[1][j], O[2][j], O[3][j]);
  }
  bar_arrive(BAR_DONE, 256);
  fence_async_smem();
  __syncwarp();
  if (lane == 0) {
    tma_st2(&p.att_st, stg, 128 * n + 64 * t, 128 * m + 32 * w);
    bulk_commit();
  }
}

__device__ __forceinline__ void consumer_tile(const Params& p, uint32_t sb0, int i, int mn) {
  const int layer = i >= 7, t = i - 7 * layer, wg = i & 1;
  const bool resid = t == 2 || t == 6;
  {
    float acc[2][96];
    if (resid) {
      const Ctx cx = make_ctx(sb0, mn);
      const uint32_t xrow = cx.sb + OFF_X + cx.w * 4096 + cx.lane * 128;
      const uint32_t sel_lo = 0x1044u | p.zero, sel_hi = 0x3244u | p.zero;
#pragma unroll
      for (int j = 0; j < 16; j++) {
        uint32_t r[4];
        ldsm4(xrow + (j >> 3) * 16384 + (((j & 7) ^ (cx.lane & 7)) << 4), r[0], r[1], r[2], r[3]);
#pragma unroll
        for (int q = 0; q < 4; q++) {
          ACC(q, j, 0) = prmt_f(r[q], sel_lo);
          ACC(q, j, 1) = prmt_f(r[q], sel_hi);
        }
      }
    } else {
#pragma unroll
      for (int r = 0; r < 64; r++) acc[0][r] = acc[1][r] = 0.f;
    }
#pragma unroll
    for (int r = 64; r < 96; r++) acc[0][r] = acc[1][r] = 0.f;
    const bool split = t == 3 || t == 4 || i == 7 || i == 8;
#pragma unroll 1
    for (int step = split ? 0 : 1;; step++) {
      if (step == 1 && (t == 1 || t == 4)) {
        const Ctx cx = make_ctx(sb0, mn);
        if (i == 1) {
          const uint32_t epoch = __ldcg(g_epoch + (mn & 127));
          bar_sync(BAR_INIT, 384);
          asm volatile("st.shared.u32 [%0], %1;" ::"r"(sb0 + OFF_TAG), "r"(epoch + 1) : "memory");
        }
        const uint32_t tag = lds_u(cx.sb + OFF_TAG);
        const int ln = (i + 1) >> 2;
#pragma unroll 1
        for (int r = 0; r < 2; r++) {
          if (i == 1) {
            if (cx.w < 3) {
              float a[8] = {0.f, 0.f, 0.f, 0.f, 0.f, 0.f, 0.f, 0.f};
              mbar_wait(sb0 + BAR_CSLD, r);
              sum_rows(cx.sb + OFF_STG + cx.w * 8192, 8, a, cx.lane);
              publish_sums(a, g_csp + (cx.n * 17 + cx.m) * 224 + (3 * r + cx.w) * 32, cx.lane, tag);
            }
            PROF_E(-1, 5 + r);
          }
          if (r == 1) break;
          if (i == 1) {
            bar_sync(BAR_WG + 1, 128);
            if (cx.w == 3 && elect_one()) {
              mbar_expect_tx(sb0 + BAR_CSLD, 24576);
              tma_ld3(sb0 + OFF_STG, &p.wqkv, sb0 + BAR_CSLD, 128 * cx.n + 64, 64 * cx.m, 0);
            }
            mbar_wait(sb0 + BAR_XRDY, 0);
            mbar_wait(sb0 + BAR_XRDY + 8, 0);
          }
          write_partial_stats(cx, ln, tag);
          PROF_E(i - 2, 8);
        }
        if (i <= 4) colsum_total(cx, ln, tag);
        PROF_E(i - 2, 9);
        if (i != 1) bar_sync(BAR_GUARD + wg, 256);
        finish_row_stats(cx, ln, tag);
        PROF_E(i - 2, 10);
        if (i <= 4) {
          colsum_gather(cx, ln, tag);
          if (i == 4) mbar_wait(sb0 + BAR_BIAS, 0);
          bar_sync(BAR_WG + wg, 128);
        }
        PROF_E(i - 2, 15);
        bar_arrive(BAR_GUARD + (wg ^ 1), 256);
      }
      if (step == 2 && !resid) bar_sync(BAR_GUARD + wg, 256);
      if (t + step == 2 || t == 6) {
        const Ctx cx = make_ctx(sb0, mn);
        float nm[4];
#pragma unroll
        for (int q = 0; q < 4; q++) nm[q] = t == 6 ? 1.f : -lds_f(cx.sb + OFF_ROW + (32 * cx.w + 8 * q + (cx.lane >> 2)) * 8 + 4);
        const uint32_t ctab = cx.sb + OFF_CSQ + ((t & 3) * 192 + 2 * (cx.lane & 3)) * 4;
#pragma unroll
        for (int j = 0; j < 24; j++) {
          const float2 cs = lds_f2(ctab + j * 32);
#pragma unroll
          for (int q = 0; q < 4; q++) {
            const int k = 4 * j + q - 1;
            const float nq = k >= 0 ? chain(nm[q], __float_as_uint(ACC(k & 3, k >> 2, 1)), p.zero) : nm[q];
            ACC(q, j, 0) = fmaf(nq, cs.x, ACC(q, j, 0));
            ACC(q, j, 1) = fmaf(nq, cs.y, ACC(q, j, 1));
          }
        }
      }
      if (step == 2) break;
      if (tile_wide(t)) {
        mainloop<192>(acc, sb0, i, split ? step : 2, mn);
      } else {
        mainloop<128>(acc, sb0, i, split ? step : 2, mn);
        if (resid) break;
      }
    }
    const Ctx cx = make_ctx(sb0, mn);
    if (resid) {
      const uint32_t xrow = cx.sb + OFF_X + cx.w * 4096 + cx.lane * 128;
#pragma unroll
      for (int j = 0; j < 16; j++) {
        stsm4(xrow + (j >> 3) * 16384 + (((j & 7) ^ (cx.lane & 7)) << 4), pack_bf16(ACC(0, j, 0), ACC(0, j, 1)),
              pack_bf16(ACC(1, j, 0), ACC(1, j, 1)), pack_bf16(ACC(2, j, 0), ACC(2, j, 1)), pack_bf16(ACC(3, j, 0), ACC(3, j, 1)));
        if ((j & 7) == 7) {
          fence_async_smem();
          __syncwarp();
          if (elect_one()) mbar_arrive(sb0 + BAR_XRDY + (j & 8));
        }
      }
      PROF_E(i, 4);
      return;
    }
    if (t < 2) attn_epilogue(p, acc, cx, layer, t, lds_u(sb0 + OFF_TAG));
    else gelu_epilogue(p, acc, cx, t);
    PROF_E(i, 4);
    if (cx.lane == 0) {
      bulk_wait_all();
      mbar_arrive(sb0 + BAR_PUB + 8 * (t < 2 ? t : t + 1));
    }
    __syncwarp();
    PROF_E(i, 5);
    if (i < 12) bar_arrive(BAR_GUARD + (wg ^ 1), 256);
  }
}

__global__ void __launch_bounds__(384, 1) fused_layers_kernel(const int by_smid, const __nv_bfloat16* x_p, const __nv_bfloat16* wqkv_p,
                                                                  const __grid_constant__ Params p) {
  extern __shared__ __align__(1024) uint8_t smem_raw[];
  const uint32_t sb = uniform((uint32_t)__cvta_generic_to_shared(smem_raw));
  const int tid = threadIdx.x, lane = tid & 31, warp = uniform(tid >> 5), wg = warp >> 2, w = warp & 3;

  int mn;
  {
    int id = blockIdx.x;
    if (by_smid) asm volatile("mov.u32 %0, %%smid;" : "=r"(id));
    else if (id >= 120) id += 4;
    const int c = id >> 1;
    int g, j;
    if (c < 32) { g = c & 7; j = c >> 3; }
    else if (c < 60) { g = 1 + (c - 32) % 7; j = 4 + (c - 32) / 7; }
    else { g = 0; j = c - 58; }
    mn = ((g >> 2) * 8 + j) * 8 + (g & 3) * 2 + (id & 1);
    if (c == 60 || c == 61) {
      if (tid < 32) {
        const uint32_t tag = __ldcg(g_epoch + NCTA + (id & 3)) + 1;
#pragma unroll 1
        for (int mm = 0; mm < 16; mm++) poll_line(g_flags + mm * 32 + (lane & 7), 32 * tag, 0xffu);
        if (tid == 0) g_epoch[NCTA + (id & 3)] = tag;
      }
      return;
    }
  }
  const int m = mn >> 3, n = mn & 7;
  if (tid == 256) PROF_U(1);
  if (tid >= 382) asm volatile("prefetch.global.L2 [%0];" ::"l"(tid & 1 ? wqkv_p + 128 * n : x_p + 128 * m * DM));
  if (wg < 2) {
    asm volatile("setmaxnreg.inc.sync.aligned.u32 232;");
#pragma unroll 1
    for (int i = wg; i < 14; i += 2) {
      consumer_tile(p, sb, i, mn | (warp << 7));
      PROF_T(6 + i * 4);
    }
  } else {
    asm volatile("setmaxnreg.dec.sync.aligned.u32 40;");
    if (w != 0) {
      bar_sync(BAR_INIT, 384);
      if (w == 1) producer<true>(p, sb, m, n, lane);
      else if (w == 3) colsum_helper(p, sb, m, n, lane);
      else if (elect_one()) publisher(p, sb, m, n);
    } else {
      if (elect_one()) {
#pragma unroll
        for (int k = 0; k < 4; k++) mbar_init(sb + BAR_FULL + 8 * k, 2);
        asm volatile("fence.mbarrier_init.release.cluster;" ::: "memory");
        PROF_U(4);
#pragma unroll 1
        for (int k = 0; k < 4; k++) {
          const uint32_t fb = sb + BAR_FULL + 8 * k;
          mbar_expect_tx(fb, 16384);
          tma_ld2(sb + (5 * k + 3) * UNIT, &p.xin, fb, 64 * k, 128 * m);
          mbar_expect_tx(fb, 3 * UNIT);
          tma_ld3(sb + 5 * k * UNIT, &p.wqkv, fb, 128 * n, 64 * k, 0);
        }
        PROF_U(5);
        mbar_init(sb + BAR_XRDY, 4);
        mbar_init(sb + BAR_XRDY + 8, 4);
        mbar_init(sb + BAR_FULL + 32, 2);
#pragma unroll
        for (int k = 0; k < NBAR; k++) mbar_init(sb + BAR_EMPTY + 8 * k, 4);
        mbar_init(sb + BAR_DUMMY, 4);
#pragma unroll
        for (int k = 0; k < 7; k++) mbar_init(sb + BAR_PUB + 8 * k, 4);
#pragma unroll
        for (int k = 0; k < 3; k++) mbar_init(sb + BAR_CSLD + 8 * k, 1);
        sts_f2(sb + OFF_ZERO, 0.f, 0.f);
        sts_f2(sb + OFF_ZERO + 8, 0.f, 0.f);
        asm volatile("fence.mbarrier_init.release.cluster;" ::: "memory");
        mbar_expect_tx(sb + BAR_CSLD, 24576);
        tma_ld3(sb + OFF_STG, &p.wqkv, sb + BAR_CSLD, 128 * n, 64 * m, 0);
#pragma unroll 1
        for (int h = 0; h < 2; h++) {
          const uint32_t xr = sb + BAR_XRDY + 8 * h;
          mbar_expect_tx(xr, 16384);
          tma_ld2(sb + OFF_X + h * 16384, &p.xin, xr, 128 * n + 64 * h, 128 * m);
          asm volatile("mbarrier.arrive.shared::cta.b64 _, [%0], 3;" ::"r"(xr) : "memory");
        }
        PROF_U(6);
      }
      __syncwarp();
      bar_arrive(BAR_INIT, 384);
      producer<false>(p, sb, m, n, lane);
    }
  }
}

typedef CUresult (*EncodeFn)(CUtensorMap*, CUtensorMapDataType, cuuint32_t, void*, const cuuint64_t*, const cuuint64_t*,
                             const cuuint32_t*, const cuuint32_t*, CUtensorMapInterleave, CUtensorMapSwizzle,
                             CUtensorMapL2promotion, CUtensorMapFloatOOBfill);

void make_2d(EncodeFn enc, CUtensorMap* m, const void* ptr, uint64_t cols, uint64_t rows, uint32_t box_rows) {
  cuuint64_t d[2] = {cols, rows}, st[1] = {cols * 2};
  cuuint32_t b[2] = {64, box_rows}, e[2] = {1, 1};
  enc(m, CU_TENSOR_MAP_DATA_TYPE_BFLOAT16, 2, const_cast<void*>(ptr), d, st, b, e, CU_TENSOR_MAP_INTERLEAVE_NONE,
      CU_TENSOR_MAP_SWIZZLE_128B, CU_TENSOR_MAP_L2_PROMOTION_L2_128B, CU_TENSOR_MAP_FLOAT_OOB_FILL_NONE);
}
void make_3d(EncodeFn enc, CUtensorMap* m, const void* ptr, uint64_t d0, uint64_t rows, uint64_t d2, uint64_t row_bytes,
             uint64_t chunk_bytes, uint32_t box_chunks) {
  cuuint64_t d[3] = {d0, rows, d2}, st[2] = {row_bytes, chunk_bytes};
  cuuint32_t b[3] = {64, 64, box_chunks}, e[3] = {1, 1, 1};
  enc(m, CU_TENSOR_MAP_DATA_TYPE_BFLOAT16, 3, const_cast<void*>(ptr), d, st, b, e, CU_TENSOR_MAP_INTERLEAVE_NONE,
      CU_TENSOR_MAP_SWIZZLE_128B, CU_TENSOR_MAP_L2_PROMOTION_L2_128B, CU_TENSOR_MAP_FLOAT_OOB_FILL_NONE);
}

}

extern "C" void kernel_launch(void* const* d_in, const int* in_sizes, int n_in, void* d_out, int out_size) {
  (void)in_sizes; (void)n_in; (void)out_size;
  static EncodeFn enc = nullptr;
  static void *att = nullptr, *hbuf = nullptr;
  static int by_smid = 0;
  if (!enc) {
    void* fn = nullptr;
    cudaDriverEntryPointQueryResult q;
    cudaGetDriverEntryPoint("cuTensorMapEncodeTiled", &fn, cudaEnableDefault, &q);
    enc = (EncodeFn)fn;
    cudaGetSymbolAddress(&att, g_att);
    cudaGetSymbolAddress(&hbuf, g_h);
    cudaFuncSetAttribute(fused_layers_kernel, cudaFuncAttributeMaxDynamicSharedMemorySize, SMEM_BYTES);
    int sms = 0, per_sm = 0, dev = 0;
    cudaGetDevice(&dev);
    cudaDeviceGetAttribute(&sms, cudaDevAttrMultiProcessorCount, dev);
    cudaOccupancyMaxActiveBlocksPerMultiprocessor(&per_sm, fused_layers_kernel, 384, SMEM_BYTES);
    by_smid = sms == 132 && per_sm == 1;
  }
  Params p;
  make_2d(enc, &p.xin, d_in[0], DM, SEQ, 128);
  make_2d(enc, &p.out, d_out, DM, SEQ, 128);
  make_2d(enc, &p.att, att, DM, SEQ, 128);
  make_2d(enc, &p.h, hbuf, FF, SEQ, 128);
  make_2d(enc, &p.out_st, d_out, DM, SEQ, 32);
  make_2d(enc, &p.att_st, att, DM, SEQ, 32);
  make_2d(enc, &p.h_st, hbuf, FF, SEQ, 32);
  make_2d(enc, &p.w1c, d_in[4], FF, DM, 32);
  make_3d(enc, &p.wqkv, d_in[1], DM, DM, 3, 3 * DM * 2, DM * 2, 3);
  make_3d(enc, &p.wo, d_in[2], 64, DM, DM / 64, DM * 2, 128, 2);
  make_3d(enc, &p.w1a, d_in[4], 64, DM, FF / 64, FF * 2, 128, 3);
  make_3d(enc, &p.w1b, d_in[4], 64, DM, FF / 64, FF * 2, 128, 2);
  make_3d(enc, &p.w2, d_in[6], 64, FF, DM / 64, DM * 2, 128, 2);
  p.b1 = (const __nv_bfloat16*)d_in[5];
  p.b2 = (const __nv_bfloat16*)d_in[7];
  p.zero = 0;
  fused_layers_kernel<<<by_smid ? 132 : NCTA, 384, SMEM_BYTES>>>(by_smid, (const __nv_bfloat16*)d_in[0], (const __nv_bfloat16*)d_in[1], p);
}
```

```cpp
#include <cuda_runtime.h>
#include <cuda_bf16.h>
#include <cuda.h>
#include <stdint.h>

namespace {

constexpr int SEQ = 2048, DM = 1024, FF = 3584;
constexpr int NCTA = 128;
constexpr int NBAR = 5;

constexpr uint32_t RING_UNITS = 20, UNIT = 8192;
constexpr uint32_t OFF_X   = RING_UNITS * UNIT;
constexpr uint32_t OFF_STG = OFF_X + 32768;
constexpr uint32_t OFF_HLP = OFF_STG + 16384;
constexpr uint32_t OFF_RUN = OFF_STG + 24576;
constexpr uint32_t OFF_CSQ = OFF_RUN + 512;
constexpr uint32_t OFF_CSF = OFF_CSQ + 2048;
constexpr uint32_t OFF_ROW = OFF_CSF + 3584;
constexpr uint32_t OFF_BAR = OFF_ROW + 1024;
constexpr uint32_t SMEM_BYTES = OFF_BAR + 384;
constexpr uint32_t BAR_FULL = OFF_BAR, BAR_EMPTY = OFF_BAR + 8 * NBAR;
constexpr uint32_t BAR_XRDY = OFF_BAR + 80;
constexpr uint32_t BAR_DUMMY = OFF_BAR + 96, OFF_TAG = OFF_BAR + 104, OFF_ZERO = OFF_BAR + 112;
constexpr uint32_t BAR_PUB = OFF_BAR + 128;
constexpr uint32_t BAR_CSLD = OFF_BAR + 200;
constexpr uint32_t BAR_BIAS = OFF_BAR + 216;

constexpr uint64_t DESC_A = (1ull << 62) | ((uint64_t)(2048 >> 4) << 32) | (1ull << 16);
constexpr uint64_t DESC_B = (1ull << 62) | ((uint64_t)(1024 >> 4) << 32) | ((uint64_t)(8192 >> 4) << 16);

constexpr int BAR_INIT = 0, BAR_ORDER = 1, BAR_GUARD = 3, BAR_WG = 5, BAR_GO = 7, BAR_DONE = 8, BAR_HLP = 9;
#define GELU_DEP 3
#define WIN1 7
#define WIN2 4

struct Params {
  CUtensorMap xin, out, att, h, wqkv, wo, w1a, w1b, w2, out_st, att_st, h_st, w1c;
  const __nv_bfloat16 *b1, *b2;
  uint32_t zero;
};

__device__ __nv_bfloat16 g_att[SEQ * DM];
__device__ __nv_bfloat16 g_h[SEQ * FF];
__device__ uint4 g_stats[4 * 8 * SEQ];
__device__ uint4 g_halo[2 * 2 * 16 * 8 * 384];
__device__ uint4 g_csp[2 * 8 * 17 * 224];
__device__ uint32_t g_flags[16 * 32];
__device__ uint32_t g_epoch[NCTA + 4];
#define PROF_T(idx)
#define PROF_U(k)
#define PROF_S(g)
#define PROF_E(i, k)

__device__ __forceinline__ void mbar_init(uint32_t bar, int cnt) {
  asm volatile("mbarrier.init.shared::cta.b64 [%0], %1;" ::"r"(bar), "r"(cnt));
}
__device__ __forceinline__ void mbar_expect_tx(uint32_t bar, uint32_t bytes) {
  asm volatile("mbarrier.arrive.expect_tx.shared::cta.b64 _, [%0], %1;" ::"r"(bar), "r"(bytes) : "memory");
}
__device__ __forceinline__ void mbar_arrive(uint32_t bar) {
  asm volatile("mbarrier.arrive.shared::cta.b64 _, [%0];" ::"r"(bar) : "memory");
}
__device__ __forceinline__ bool mbar_test(uint32_t bar, uint32_t parity) {
  uint32_t ok;
  asm volatile("{\n.reg .pred p;\nmbarrier.test_wait.parity.shared::cta.b64 p, [%1], %2;\nselp.u32 %0, 1, 0, p;\n}"
               : "=r"(ok) : "r"(bar), "r"(parity) : "memory");
  return ok;
}
__device__ __forceinline__ void mbar_wait(uint32_t bar, uint32_t parity) {
  asm volatile(
      "{\n.reg .pred p;\n.reg .u32 it;\nmov.u32 it, 0;\n"
      "WAIT_LOOP:\n"
      "mbarrier.try_wait.parity.shared::cta.b64 p, [%0], %1;\n"
      "@p bra WAIT_DONE;\n"
      "add.u32 it, it, 1;\n"
      "setp.lt.u32 p, it, 0x400000;\n"
      "@p bra WAIT_LOOP;\n"
      "trap;\n"
      "WAIT_DONE:\n}"
      ::"r"(bar), "r"(parity) : "memory");
}
__device__ __forceinline__ void bar_sync(int id, int n) { asm volatile("bar.sync %0, %1;" ::"r"(id), "r"(n) : "memory"); }
__device__ __forceinline__ void bar_arrive(int id, int n) { asm volatile("bar.arrive %0, %1;" ::"r"(id), "r"(n) : "memory"); }
__device__ __forceinline__ void tma_ld2(uint32_t dst, const CUtensorMap* m, uint32_t bar, int c0, int c1) {
  asm volatile("cp.async.bulk.tensor.2d.shared::cluster.global.mbarrier::complete_tx::bytes [%0], [%1, {%3, %4}], [%2];"
               ::"r"(dst), "l"(m), "r"(bar), "r"(c0), "r"(c1) : "memory");
}
__device__ __forceinline__ void tma_ld3(uint32_t dst, const CUtensorMap* m, uint32_t bar, int c0, int c1, int c2) {
  asm volatile("cp.async.bulk.tensor.3d.shared::cluster.global.mbarrier::complete_tx::bytes [%0], [%1, {%3, %4, %5}], [%2];"
               ::"r"(dst), "l"(m), "r"(bar), "r"(c0), "r"(c1), "r"(c2) : "memory");
}
__device__ __forceinline__ void tma_st2(const CUtensorMap* m, uint32_t src, int c0, int c1) {
  asm volatile("cp.async.bulk.tensor.2d.global.shared::cta.bulk_group [%0, {%2, %3}], [%1];"
               ::"l"(m), "r"(src), "r"(c0), "r"(c1) : "memory");
}
__device__ __forceinline__ void bulk_commit() { asm volatile("cp.async.bulk.commit_group;" ::: "memory"); }
__device__ __forceinline__ void bulk_wait_read() { asm volatile("cp.async.bulk.wait_group.read 0;" ::: "memory"); }
__device__ __forceinline__ void bulk_wait_all() { asm volatile("cp.async.bulk.wait_group 0;" ::: "memory"); }
__device__ __forceinline__ void fence_async_smem() { asm volatile("fence.proxy.async.shared::cta;" ::: "memory"); }
__device__ __forceinline__ void fence_async_global() { asm volatile("fence.proxy.async.global;" ::: "memory"); }
__device__ __forceinline__ void st_relaxed(uint32_t* p, uint32_t v) {
  asm volatile("st.relaxed.gpu.global.u32 [%0], %1;" ::"l"(p), "r"(v) : "memory");
}
__device__ __forceinline__ void st_msg(uint4* p, uint32_t a, uint32_t b, uint32_t c, uint32_t tag) {
  asm volatile("{\n.reg .b128 v;\nmov.b128 v, {%1, %2, %3, %4};\nst.relaxed.gpu.b128 [%0], v;\n}"
               ::"l"(p), "r"(a), "r"(b), "r"(c), "r"(tag) : "memory");
}
__device__ __forceinline__ void ld_msg(const uint4* p, uint32_t& a, uint32_t& b, uint32_t& c, uint32_t& tag) {
  asm volatile("{\n.reg .b128 v;\nld.relaxed.gpu.b128 v, [%4];\nmov.b128 {%0, %1, %2, %3}, v;\n}"
               : "=r"(a), "=r"(b), "=r"(c), "=r"(tag) : "l"(p) : "memory");
}
__device__ __forceinline__ bool elect_one() {
  uint32_t ok;
  asm volatile("{\n.reg .pred p;\nelect.sync _|p, 0xffffffff;\nselp.u32 %0, 1, 0, p;\n}" : "=r"(ok));
  return ok;
}
__device__ __forceinline__ int uniform(int v) { return __shfl_sync(0xffffffffu, v, 0); }
__device__ __forceinline__ uint32_t pack_bf16(float lo, float hi) {
  uint32_t r;
  asm("cvt.rn.bf16x2.f32 %0, %1, %2;" : "=r"(r) : "f"(hi), "f"(lo));
  return r;
}
__device__ __forceinline__ uint32_t prmt_u(uint32_t a, uint32_t sel) {
  uint32_t r;
  asm("prmt.b32 %0, %1, 0, %2;" : "=r"(r) : "r"(a), "r"(sel));
  return r;
}
__device__ __forceinline__ float prmt_f(uint32_t a, uint32_t sel) {
  float r;
  asm("{\n.reg .b32 t;\nprmt.b32 t, %1, 0, %2;\nmov.b32 %0, t;\n}" : "=f"(r) : "r"(a), "r"(sel));
  return r;
}
__device__ __forceinline__ float bf_lo(uint32_t v) { return __uint_as_float(v << 16); }
__device__ __forceinline__ float bf_hi(uint32_t v) { return __uint_as_float(v & 0xffff0000u); }
__device__ __forceinline__ void stsm4(uint32_t addr, uint32_t r0, uint32_t r1, uint32_t r2, uint32_t r3) {
  asm volatile("stmatrix.sync.aligned.m8n8.x4.shared.b16 [%0], {%1, %2, %3, %4};"
               ::"r"(addr), "r"(r0), "r"(r1), "r"(r2), "r"(r3) : "memory");
}
__device__ __forceinline__ void ldsm4(uint32_t addr, uint32_t& r0, uint32_t& r1, uint32_t& r2, uint32_t& r3) {
  asm volatile("ldmatrix.sync.aligned.m8n8.x4.shared.b16 {%0, %1, %2, %3}, [%4];"
               : "=r"(r0), "=r"(r1), "=r"(r2), "=r"(r3) : "r"(addr) : "memory");
}
__device__ __forceinline__ uint32_t movtrans(uint32_t a) {
  uint32_t d;
  asm volatile("movmatrix.sync.aligned.m8n8.trans.b16 %0, %1;" : "=r"(d) : "r"(a));
  return d;
}
__device__ __forceinline__ void mma16816(float (&c)[4], uint32_t a0, uint32_t a1, uint32_t a2, uint32_t a3, uint32_t b0, uint32_t b1) {
  asm volatile("mma.sync.aligned.m16n8k16.row.col.f32.bf16.bf16.f32 {%0,%1,%2,%3}, {%4,%5,%6,%7}, {%8,%9}, {%0,%1,%2,%3};"
               : "+f"(c[0]), "+f"(c[1]), "+f"(c[2]), "+f"(c[3])
               : "r"(a0), "r"(a1), "r"(a2), "r"(a3), "r"(b0), "r"(b1));
}
__device__ __forceinline__ float2 lds_f2(uint32_t a) {
  float2 v;
  asm volatile("ld.shared.v2.f32 {%0, %1}, [%2];" : "=f"(v.x), "=f"(v.y) : "r"(a) : "memory");
  return v;
}
__device__ __forceinline__ float4 lds_f4(uint32_t a) {
  float4 v;
  asm volatile("ld.shared.v4.f32 {%0, %1, %2, %3}, [%4];" : "=f"(v.x), "=f"(v.y), "=f"(v.z), "=f"(v.w) : "r"(a) : "memory");
  return v;
}
__device__ __forceinline__ float lds_f(uint32_t a) {
  float v;
  asm volatile("ld.shared.f32 %0, [%1];" : "=f"(v) : "r"(a) : "memory");
  return v;
}
__device__ __forceinline__ uint32_t lds_u(uint32_t a) {
  uint32_t v;
  asm volatile("ld.shared.u32 %0, [%1];" : "=r"(v) : "r"(a) : "memory");
  return v;
}
__device__ __forceinline__ void sts_f2(uint32_t a, float x, float y) {
  asm volatile("st.shared.v2.f32 [%0], {%1, %2};" ::"r"(a), "f"(x), "f"(y) : "memory");
}
__device__ __forceinline__ void sts_u4(uint32_t a, uint32_t x, uint32_t y, uint32_t z, uint32_t w) {
  asm volatile("st.shared.v4.u32 [%0], {%1, %2, %3, %4};" ::"r"(a), "r"(x), "r"(y), "r"(z), "r"(w) : "memory");
}
__device__ __forceinline__ void lds_u4(uint32_t a, uint32_t& x, uint32_t& y, uint32_t& z, uint32_t& w) {
  asm volatile("ld.shared.v4.u32 {%0, %1, %2, %3}, [%4];" : "=r"(x), "=r"(y), "=r"(z), "=r"(w) : "r"(a) : "memory");
}
__device__ __forceinline__ float ex2(float x) {
  float y;
  asm("ex2.approx.ftz.f32 %0, %1;" : "=f"(y) : "f"(x));
  return y;
}
__device__ __forceinline__ float rcp_hw(float x) {
  float y;
  asm("rcp.approx.ftz.f32 %0, %1;" : "=f"(y) : "f"(x));
  return y;
}
__device__ __forceinline__ float tanh_hw(float x) {
  float y;
  asm("tanh.approx.f32 %0, %1;" : "=f"(y) : "f"(x));
  return y;
}
__device__ __forceinline__ float quad_sum(float v) {
  v += __shfl_xor_sync(0xffffffffu, v, 1);
  return v + __shfl_xor_sync(0xffffffffu, v, 2);
}
__device__ __forceinline__ float quad_max(float v) {
  v = fmaxf(v, __shfl_xor_sync(0xffffffffu, v, 1));
  return fmaxf(v, __shfl_xor_sync(0xffffffffu, v, 2));
}

template <int N> __device__ __forceinline__ void wgmma_ss(float (&d)[96], uint64_t da, uint64_t db);
template <> __device__ __forceinline__ void wgmma_ss<128>(float (&d)[96], uint64_t da, uint64_t db) {
  asm volatile(
      "wgmma.mma_async.sync.aligned.m64n128k16.f32.bf16.bf16 {%0, %1, %2, %3, %4, %5, %6, %7, %8, %9, %10, %11, %12, %13, %14, %15, %16, %17, %18, %19, %20, %21, %22, %23, %24, %25, %26, %27, %28, %29, %30, %31, %32, %33, %34, %35, %36, %37, %38, %39, %40, %41, %42, %43, %44, %45, %46, %47, %48, %49, %50, %51, %52, %53, %54, %55, %56, %57, %58, %59, %60, %61, %62, %63}, %64, %65, 1, 1, 1, 0, 1;"
      : "+f"(d[0]), "+f"(d[1]), "+f"(d[2]), "+f"(d[3]), "+f"(d[4]), "+f"(d[5]), "+f"(d[6]), "+f"(d[7]), "+f"(d[8]), "+f"(d[9]), "+f"(d[10]), "+f"(d[11]), "+f"(d[12]), "+f"(d[13]), "+f"(d[14]), "+f"(d[15]), "+f"(d[16]), "+f"(d[17]), "+f"(d[18]), "+f"(d[19]), "+f"(d[20]), "+f"(d[21]), "+f"(d[22]), "+f"(d[23]), "+f"(d[24]), "+f"(d[25]), "+f"(d[26]), "+f"(d[27]), "+f"(d[28]), "+f"(d[29]), "+f"(d[30]), "+f"(d[31]), "+f"(d[32]), "+f"(d[33]), "+f"(d[34]), "+f"(d[35]), "+f"(d[36]), "+f"(d[37]), "+f"(d[38]), "+f"(d[39]), "+f"(d[40]), "+f"(d[41]), "+f"(d[42]), "+f"(d[43]), "+f"(d[44]), "+f"(d[45]), "+f"(d[46]), "+f"(d[47]), "+f"(d[48]), "+f"(d[49]), "+f"(d[50]), "+f"(d[51]), "+f"(d[52]), "+f"(d[53]), "+f"(d[54]), "+f"(d[55]), "+f"(d[56]), "+f"(d[57]), "+f"(d[58]), "+f"(d[59]), "+f"(d[60]), "+f"(d[61]), "+f"(d[62]), "+f"(d[63])
      : "l"(da), "l"(db));
}

template <> __device__ __forceinline__ void wgmma_ss<192>(float (&d)[96], uint64_t da, uint64_t db) {
  asm volatile(
      "wgmma.mma_async.sync.aligned.m64n192k16.f32.bf16.bf16 {%0, %1, %2, %3, %4, %5, %6, %7, %8, %9, %10, %11, %12, %13, %14, %15, %16, %17, %18, %19, %20, %21, %22, %23, %24, %25, %26, %27, %28, %29, %30, %31, %32, %33, %34, %35, %36, %37, %38, %39, %40, %41, %42, %43, %44, %45, %46, %47, %48, %49, %50, %51, %52, %53, %54, %55, %56, %57, %58, %59, %60, %61, %62, %63, %64, %65, %66, %67, %68, %69, %70, %71, %72, %73, %74, %75, %76, %77, %78, %79, %80, %81, %82, %83, %84, %85, %86, %87, %88, %89, %90, %91, %92, %93, %94, %95}, %96, %97, 1, 1, 1, 0, 1;"
      : "+f"(d[0]), "+f"(d[1]), "+f"(d[2]), "+f"(d[3]), "+f"(d[4]), "+f"(d[5]), "+f"(d[6]), "+f"(d[7]), "+f"(d[8]), "+f"(d[9]), "+f"(d[10]), "+f"(d[11]), "+f"(d[12]), "+f"(d[13]), "+f"(d[14]), "+f"(d[15]), "+f"(d[16]), "+f"(d[17]), "+f"(d[18]), "+f"(d[19]), "+f"(d[20]), "+f"(d[21]), "+f"(d[22]), "+f"(d[23]), "+f"(d[24]), "+f"(d[25]), "+f"(d[26]), "+f"(d[27]), "+f"(d[28]), "+f"(d[29]), "+f"(d[30]), "+f"(d[31]), "+f"(d[32]), "+f"(d[33]), "+f"(d[34]), "+f"(d[35]), "+f"(d[36]), "+f"(d[37]), "+f"(d[38]), "+f"(d[39]), "+f"(d[40]), "+f"(d[41]), "+f"(d[42]), "+f"(d[43]), "+f"(d[44]), "+f"(d[45]), "+f"(d[46]), "+f"(d[47]), "+f"(d[48]), "+f"(d[49]), "+f"(d[50]), "+f"(d[51]), "+f"(d[52]), "+f"(d[53]), "+f"(d[54]), "+f"(d[55]), "+f"(d[56]), "+f"(d[57]), "+f"(d[58]), "+f"(d[59]), "+f"(d[60]), "+f"(d[61]), "+f"(d[62]), "+f"(d[63]), "+f"(d[64]), "+f"(d[65]), "+f"(d[66]), "+f"(d[67]), "+f"(d[68]), "+f"(d[69]), "+f"(d[70]), "+f"(d[71]), "+f"(d[72]), "+f"(d[73]), "+f"(d[74]), "+f"(d[75]), "+f"(d[76]), "+f"(d[77]), "+f"(d[78]), "+f"(d[79]), "+f"(d[80]), "+f"(d[81]), "+f"(d[82]), "+f"(d[83]), "+f"(d[84]), "+f"(d[85]), "+f"(d[86]), "+f"(d[87]), "+f"(d[88]), "+f"(d[89]), "+f"(d[90]), "+f"(d[91]), "+f"(d[92]), "+f"(d[93]), "+f"(d[94]), "+f"(d[95])
      : "l"(da), "l"(db));
}

template <int R>
__device__ __forceinline__ void pin_regs(float (&a)[2][96]) {
#pragma unroll
  for (int m = 0; m < 2; m++)
#pragma unroll
    for (int i = 0; i < R; i++) asm volatile("" : "+f"(a[m][i])::"memory");
}

struct Ctx {
  uint32_t sb;
  int m, n, wg, w, lane;
};
__device__ __forceinline__ Ctx make_ctx(uint32_t sb, int id) {
  int lane;
  asm volatile("mov.u32 %0, %%laneid;" : "=r"(lane));
  asm volatile("" : "+r"(id), "+r"(sb));
  return Ctx{sb, (id >> 3) & 15, id & 7, id >> 9, (id >> 7) & 3, lane};
}
#define UNPACK_CTX(c) const uint32_t sb = c.sb; const int m = c.m, n = c.n, wg = c.wg, w = c.w, lane = c.lane

__device__ __forceinline__ uint32_t poll_line(const uint32_t* word, uint32_t target, uint32_t need) {
  uint32_t v;
  asm volatile(
      "{\n.reg .pred p;\n.reg .u32 it, m;\n.reg .s32 d;\nmov.u32 it, 0;\n"
      "POLL_LOOP:\n"
      "ld.relaxed.gpu.global.u32 %0, [%1];\n"
      "sub.s32 d, %0, %2;\n"
      "setp.ge.s32 p, d, 0;\n"
      "vote.sync.ballot.b32 m, p, 0xffffffff;\n"
      "and.b32 m, m, %3;\n"
      "setp.eq.u32 p, m, %3;\n"
      "@p bra.uni POLL_DONE;\n"
      "add.u32 it, it, 1;\n"
      "setp.lt.u32 p, it, 0x400000;\n"
      "@p bra.uni POLL_LOOP;\n"
      "trap;\n"
      "POLL_DONE:\n}"
      : "=&r"(v) : "l"(word), "r"(target), "r"(need) : "memory");
  return v;
}
__device__ __forceinline__ uint32_t ld_relaxed(const uint32_t* p) {
  uint32_t v;
  asm volatile("ld.relaxed.gpu.global.u32 %0, [%1];" : "=r"(v) : "l"(p) : "memory");
  return v;
}
__device__ __forceinline__ float chain(float x, uint32_t on, uint32_t zero) {
  return __uint_as_float(__float_as_uint(x) | (on & zero));
}
constexpr int MSG_SPINS = 1 << 20;

constexpr int STAGES_PER_LAYER = 152;
__device__ __forceinline__ int nib(uint64_t v, int i) { return (int)(v >> (4 * i)) & 15; }
__device__ __forceinline__ bool tile_wide(int t) { return (0x23 >> t) & 1; }
__device__ __forceinline__ void weight_coords(const Params& p, int t, int n, const CUtensorMap*& map, int& c0, int& c2) {
  map = &p.wqkv + nib(0x4233100ull, t);
  c0 = t < 2 ? 128 * n + 64 * t : 0;
  c2 = t < 2 ? 0 : (t == 2 || t == 6) ? 2 * n : 7 * n + 2 * t - 6;
}

template <bool IS_A>
__device__ __forceinline__ void producer(const Params& p, uint32_t sb, int m, int n, int lane) {
  uint32_t owners = 0;
#pragma unroll 1
  for (int q = 7; q >= 0; q--) owners = owners << 4 | ((((n & 6) + q) & 7) ^ (q < 2 ? n & 1 : 0));
  const uint64_t order_x = (uint64_t)((owners >> 4) * 2 + 0x1111111u) << 36 | (uint64_t)(owners >> 4) * 2 << 8 | (n * 0x22 + 0x10);
  int inflight = 4, cur = 0;
  uint32_t fb = sb + BAR_FULL + 32, rb = sb + BAR_EMPTY, rph = 0, pos = 0, tag32 = 0, seen = 0;
  const uint32_t fend = sb + BAR_FULL + 8 * NBAR, rend = sb + BAR_EMPTY + 8 * NBAR;
  const uint32_t* word = g_flags + m * 32 + (lane < 16 ? lane >> 1 : lane & 7);
#pragma unroll 1
  for (int sg = 1; sg < 22; sg++) {
    const int layer = sg >= 11, s = sg == 1 ? 2 : sg == 2 ? 1 : sg - 11 * layer;
    const int t = nib(0x65434321010ull, s), kind = nib(0x32110031100ull, s);
    const bool wide = tile_wide(t);
    const uint32_t bbytes = wide ? 3 * UNIT : 2 * UNIT, base = sb + (IS_A ? bbytes : 0);
    const int mul = t == 6 ? 448 : t == 2 ? 128 : 64, count = sg == 1 ? 12 : 2 * nib(0x4871ull, kind);
    const uint64_t order0 = sg == 1 ? 0xFEDCBA987654ull : kind == 3 ? owners : order_x >> (8 * (kind & 1));
    uint32_t special = (s == 4 || s == 10) ? 0x10 : s == 9 ? 0xF : 1;
    if (IS_A) special |= (kind & 1 ? 0 : 3) | (count >= 4 ? 1u << (count - 4) : 0);
    if (s >= 9) pos = (s + 6) * UNIT;
    const CUtensorMap* map;
    int c0 = 0, c2 = 0, ev = 0;
    if (IS_A) {
      map = &p.xin + (t == 2 ? 2 : t == 6 ? 3 : sg >= 4);
      ev = 9 * layer + (t < 2 ? 0 : t == 2 ? 1 : t < 6 ? 4 : 5);
      if (sg == 2) seen = tag32 = (__ldcg(g_epoch + m * 8 + n) + 1) << 5;
    } else {
      weight_coords(p, t, n, map, c0, c2);
    }
#pragma unroll 1
    for (int add = 0; add < mul; add += 64) {
      uint64_t order = order0;
      const int need = kind == 3 ? ev : ev - 1 + (lane & 1), sh = kind == 3 ? 16 : 0;
      uint32_t ready = IS_A ? __ballot_sync(0xffffffffu, cur >= need) >> sh : 0;
#pragma unroll 1
      for (int k = 0; k < count; k++) {
        const int code = order & 15, kc = code * mul + add;
        order >>= 4;
        if ((special >> k) & 1) {
          const int lag = wide ? (s == 9 && k == 2 ? 2 : 3) : ((s == 4 || s == 10) && add == 0 && k < 4) ? 3 : 4;
#pragma unroll 1
          for (; inflight > lag; inflight--) {
            mbar_wait(rb, rph);
            rb += 8;
            if (rb == rend) { rb -= 8 * NBAR; rph ^= 1; }
          }
          inflight++;
          if (IS_A) {
            if (kind == 3 ? t == 2 && add + k == 64 : !(kind & 1) && k < 2) {
              if (t == 2) mbar_wait(sb + BAR_PUB + 8, layer);
              else if (k == 1 && (s == 0 || s == 5)) mbar_wait(sb + BAR_XRDY + 8, s == 5);
              if (elect_one()) mbar_arrive(fb);
              goto next_stage;
            }
            if (k == count - 4 && sg >= 3) seen = ld_relaxed(word);
          }
        } else {
          mbar_wait(rb, rph);
          rb += 8;
          if (rb == rend) { rb -= 8 * NBAR; rph ^= 1; }
        }
        if (IS_A && !((ready >> code) & 1)) {
          cur = max(cur, (int)(seen - tag32));
          ready = __ballot_sync(0xffffffffu, cur >= need) >> sh;
          if (!((ready >> code) & 1)) {
            cur = (int)(poll_line(word, tag32 + need, 1u << (code + sh)) - tag32);
            ready = __ballot_sync(0xffffffffu, cur >= need) >> sh;
          }
          asm volatile("fence.acquire.gpu;" ::: "memory");
          fence_async_global();
        }
        if (elect_one()) {
          if (!IS_A) tma_ld3(base + pos, map, fb, c0, kc, c2);
          else tma_ld2(base + pos, map, fb, kc, 128 * m);
          mbar_expect_tx(fb, IS_A ? 16384 : bbytes);
        }
      next_stage:
        fb += 8;
        if (fb == fend) fb -= 8 * NBAR;
        pos += bbytes + 2 * UNIT;
        if (pos >= RING_UNITS * UNIT) pos -= RING_UNITS * UNIT;
      }
      special = !IS_A ? 0 : t == 2 ? 1 : add == 128 ? 0x10 : 0;
      if (IS_A && (t == 2 || add == 64 || add == 192)) ev++;
    }
  }
}

__device__ __forceinline__ void publisher(const Params& p, uint32_t sb, int m, int n) {
  const uint32_t tag = __ldcg(g_epoch + m * 8 + n) + 1;
  uint32_t* word = g_flags + m * 32 + n;
  const int mn = m * 8 + n; (void)mn;
  st_relaxed(word, 32 * tag);
#pragma unroll 1
  for (int c = 0; c < 18; c++) {
    const int e = c >= 9 ? c - 9 : c;
    if ((0x18C >> e) & 1) {
      const int half = (0x108 >> e) & 1;
      mbar_wait(sb + BAR_XRDY + 8 * half, e < 4);
#pragma unroll
      for (int w = 0; w < 4; w++) tma_st2(&p.out_st, sb + OFF_X + half * 16384 + w * 4096, 128 * n + 64 * half, 128 * m + 32 * w);
      bulk_commit();
      if (c >= 16) continue;
      bulk_wait_all();
      PROF_E(7 * (c >= 9) + (e < 4 ? 2 : 6), 11 + 2 * half);
    } else {
      mbar_wait(sb + BAR_PUB + 8 * e, c >= 9);
    }
    asm volatile("fence.release.gpu;" ::: "memory");
    st_relaxed(word, 32 * tag + c + 1);
    PROF_E(7 * (c >= 9) + nib(0x665432210ull, e), (0x108 >> e) & 1 ? 14 : 12);
  }
  g_epoch[m * 8 + n] = tag;
  bulk_wait_read();
}

__device__ __forceinline__ void sum_rows(uint32_t buf, int iters, float (&a)[8], int lane) {
  uint32_t addr = buf + (lane >> 3) * 128 + (((lane & 7) ^ (lane >> 3)) << 4);
#pragma unroll 1
  for (int it = 0; it < iters; it++) {
    uint32_t u[2][4];
    lds_u4(addr, u[0][0], u[0][1], u[0][2], u[0][3]);
    lds_u4((addr ^ 64) + 512, u[1][0], u[1][1], u[1][2], u[1][3]);
    addr += 1024;
#pragma unroll
    for (int e = 0; e < 8; e++) { a[2 * (e & 3)] += bf_lo(u[e >> 2][e & 3]); a[2 * (e & 3) + 1] += bf_hi(u[e >> 2][e & 3]); }
  }
}
__device__ __forceinline__ void publish_sums(const float (&a)[8], uint4* dst, int lane, uint32_t tag) {
  const bool u8 = lane & 8, u16 = lane & 16;
  float h4[4], h2[2];
#pragma unroll
  for (int e = 0; e < 4; e++) h4[e] = (u8 ? a[4 + e] : a[e]) + __shfl_xor_sync(0xffffffffu, u8 ? a[e] : a[4 + e], 8);
#pragma unroll
  for (int e = 0; e < 2; e++) h2[e] = (u16 ? h4[2 + e] : h4[e]) + __shfl_xor_sync(0xffffffffu, u16 ? h4[e] : h4[2 + e], 16);
  st_msg(dst + (lane & 7) * 4 + (u8 ? 2 : 0) + (u16 ? 1 : 0), __float_as_uint(h2[0]), __float_as_uint(h2[1]), 0u, tag);
}

__device__ __forceinline__ void colsum_helper(const Params& p, uint32_t sb, int m, int n, int lane) {
  const uint32_t tag = __ldcg(g_epoch + m * 8 + n) + 1;
  const int mn = m * 8 + n; (void)mn;
#pragma unroll 1
  for (int k = lane; k < 288; k += 32) {
    const uint32_t bb = __ldg(reinterpret_cast<const uint32_t*>(k < 224 ? p.b1 + 448 * n : p.b2 + 128 * n - 448) + k);
    const float sc = k < 224 ? 0.5f : 1.f;
    sts_f2(sb + (k < 224 ? OFF_CSF + k * 16 + 8 : OFF_CSQ + 1536 + (k - 224) * 8), sc * bf_lo(bb), sc * bf_hi(bb));
  }
  __syncwarp();
  if (elect_one()) mbar_arrive(sb + BAR_BIAS);
  bar_sync(BAR_HLP, 160);
  PROF_E(-1, 1);
#pragma unroll 1
  for (int c = 0; c < 7; c++) {
    float a[8] = {0.f, 0.f, 0.f, 0.f, 0.f, 0.f, 0.f, 0.f};
#pragma unroll 1
    for (int h = 0; h < 2; h++) {
      if (elect_one()) {
        mbar_expect_tx(sb + BAR_CSLD + 8, 4096);
        tma_ld2(sb + OFF_HLP, &p.w1c, sb + BAR_CSLD + 8, 448 * n + 64 * c, 64 * m + 32 * h);
        if (c < 6) asm volatile("cp.async.bulk.prefetch.tensor.2d.L2.global [%0, {%1, %2}];" ::"l"(&p.w1c), "r"(448 * n + 64 * c + 64), "r"(64 * m + 32 * h) : "memory");
      }
      mbar_wait(sb + BAR_CSLD + 8, h);
      sum_rows(sb + OFF_HLP, 4, a, lane);
      __syncwarp();
    }
    publish_sums(a, g_csp + ((8 + n) * 17 + m) * 224 + c * 32, lane, tag);
  }
  PROF_E(-1, 2);
}

__device__ __forceinline__ void poll_msgs2(const uint4* pa, const uint4* pb, float (&v)[4], uint32_t tag) {
#pragma unroll 1
  for (int it = 0; it < MSG_SPINS; it++) {
    uint32_t x[4], z, ta, tb;
    ld_msg(pa, x[0], x[1], z, ta);
    ld_msg(pb, x[2], x[3], z, tb);
#pragma unroll
    for (int e = 0; e < 4; e++) v[e] = __uint_as_float(x[e]);
    if (__all_sync(0xffffffffu, ta == tag && tb == tag)) break;
  }
}
__device__ __forceinline__ void colsum_total(const Ctx& cx, int mat, uint32_t tag) {
  uint4* base = g_csp + (mat * 8 + cx.n) * 17 * 224;
  const int per = 12 + 2 * mat, k = 2 * cx.w + (cx.lane >> 4), ia = per * cx.m + k, ib = per * cx.m + min(k + 8, per - 1);
  float v[4];
  poll_msgs2(base + (cx.lane & 15) * 224 + ia, base + (cx.lane & 15) * 224 + ib, v, tag);
#pragma unroll 1
  for (int d = 1; d < 16; d *= 2)
#pragma unroll
    for (int e = 0; e < 4; e++) v[e] += __shfl_xor_sync(0xffffffffu, v[e], d);
  const bool hi = cx.lane & 1;
  if ((cx.lane & 14) == 0) st_msg(base + 16 * 224 + (hi ? ib : ia), __float_as_uint(hi ? v[2] : v[0]), __float_as_uint(hi ? v[3] : v[1]), 0u, tag);
}
__device__ __forceinline__ void colsum_gather(const Ctx& cx, int mat, uint32_t tag) {
  const uint4* base = g_csp + ((mat * 8 + cx.n) * 17 + 16) * 224;
  const int ia = cx.w * 32 + cx.lane, ib = min(ia + 128, 191 + 32 * mat);
  float v[4];
  poll_msgs2(base + ia, base + ib, v, tag);
  const uint32_t tab = cx.sb + (mat ? OFF_CSF : OFF_CSQ);
  sts_f2(tab + (ia << (3 + mat)), v[0], v[1]);
  sts_f2(tab + (ib << (3 + mat)), v[2], v[3]);
}

constexpr uint32_t RING16 = RING_UNITS * (UNIT >> 4);
__device__ __forceinline__ bool tile_split(int i) { return (0xD98 >> i) & 1; }

__device__ __forceinline__ void write_run_desc(uint32_t sb, int i, int step) {
  const int layer = i >= 7, t = i - 7 * layer, part = tile_split(i) ? step : 2;
  const bool wide = tile_wide(t), own = t != 2 && t != 6 && part != 1 && i != 0, second = t == 1 || t == 4;
  const uint32_t z16 = (wide ? 5 : 4) * (UNIT >> 4), a_off = z16 - 1024 + (uint32_t)DESC_A - (uint32_t)DESC_B;
  const int gl = 16 * t + (part == 2 ? 0 : second ? 16 * part - 14 : 4 * part), g0 = layer * STAGES_PER_LAYER + gl;
  const uint32_t s16 = (sb & 0x3FFFF) >> 4, bfirst = (uint32_t)DESC_B + s16;
  const int nkb = t == 6 ? 56 : part == 0 ? 2 : 12 + 2 * part;
  const bool win1 = t == 1 && part != 0;
  const int run = win1 ? WIN1 + 1 : t == 2 ? WIN2 + 1 : nkb;
  const int rest = win1 ? 64 | (nkb - 1 - WIN1) : t == 2 ? 64 | (7 - WIN2) | (8 << 7) : 0;
  const uint32_t blo = bfirst + z16 * (wide ? (gl + (t == 5 ? 3 : 0)) & 3 : (gl + 3) % 5);
  const uint32_t alo = own ? (uint32_t)DESC_A + s16 + (OFF_X >> 4) : blo + a_off;
  const uint32_t aoff = own ? alo + 1024 - (blo == bfirst + RING16 - z16 ? bfirst : blo + z16) : a_off;
  const bool xwait = part == 0 && !second;
  sts_u4(sb + OFF_RUN + (2 * i + step) * 16, blo, alo, aoff,
         ((g0 / NBAR) & 1) | xwait << 1 | 8 * (g0 % NBAR) | run << 6 | rest << 12);
}

template <int N>
__device__ __forceinline__ void mainloop(float (&acc)[2][96], uint32_t sb, int i, int step, int mn) {
  constexpr uint32_t Z16 = (2 + N / 64) * (UNIT >> 4);
  constexpr uint32_t A_OFF = Z16 - 1024 + (uint32_t)DESC_A - (uint32_t)DESC_B;
  const int wg = i & 1;
  const uint32_t s16 = (sb & 0x3FFFF) >> 4;
  const uint32_t blast = (uint32_t)DESC_B + s16 + RING16 - Z16, flast = sb + BAR_FULL + 8 * (NBAR - 1);
  uint32_t blo, alo, aoff, misc;
  lds_u4(sb + OFF_RUN + (2 * i + step) * 16, blo, alo, aoff, misc);
  int run = (misc >> 6) & 63, rest = misc >> 12;
  uint32_t fb = sb + BAR_FULL + (misc & 0x38), ph = misc & 1;
  uint32_t prev = sb + BAR_DUMMY - 8 * NBAR;
  pin_regs<N / 2>(acc);
  if (i > 0) bar_sync(BAR_ORDER + wg, 256);
  mbar_wait(fb, ph);
  if (misc & 2) mbar_wait(sb + BAR_XRDY, N == 128);
  if (step == 0 || !tile_split(i)) PROF_T(4 + i * 4);
#pragma unroll 1
  while (true) {
    const uint64_t da = (DESC_A & ~0xffffffffull) | alo, db = (DESC_B & ~0xffffffffull) | blo;
    asm volatile("wgmma.fence.sync.aligned;" ::: "memory");
    wgmma_ss<N>(acc[0], da, db);
    wgmma_ss<N>(acc[1], da + 64, db);
    wgmma_ss<N>(acc[0], da + 2, db + 128);
    wgmma_ss<N>(acc[1], da + 66, db + 128);
    asm volatile("wgmma.commit_group.sync.aligned;" ::: "memory");
    asm volatile("wgmma.wait_group.sync.aligned 1;" ::: "memory");
    PROF_S(jj++);
    if (elect_one()) mbar_arrive(prev + 8 * NBAR);
    prev = fb;
    if (fb == flast) { fb -= 8 * NBAR; ph++; }
    fb += 8;
    if (blo == blast) blo -= RING16;
    blo += Z16;
    alo = blo + aoff;
    aoff = A_OFF;
    run--;
    const bool ready = mbar_test(fb, ph) && run != 0;
    asm volatile("wgmma.fence.sync.aligned;" ::: "memory");
    wgmma_ss<N>(acc[0], da + 4, db + 256);
    wgmma_ss<N>(acc[1], da + 68, db + 256);
    wgmma_ss<N>(acc[0], da + 6, db + 384);
    wgmma_ss<N>(acc[1], da + 70, db + 384);
    asm volatile("wgmma.commit_group.sync.aligned;" ::: "memory");
    if (!ready) {
      if (run == 0) {
        if (rest == 0) break;
        if (rest & 64) {
          bar_arrive(BAR_GO, 256);
          bar_sync(BAR_DONE, 256);
        } else {
          alo = (uint32_t)DESC_A + s16 + (OFF_STG >> 4);
        }
        run = rest & 63;
        rest >>= 7;
      }
      mbar_wait(fb, ph);
    }
  }
  if (i < 13) bar_arrive(BAR_ORDER + (wg ^ 1), 256);
  asm volatile("wgmma.wait_group.sync.aligned 0;" ::: "memory");
  pin_regs<N / 2>(acc);
  if (elect_one()) mbar_arrive(prev + 8 * NBAR);
  PROF_T(5 + i * 4);
  PROF_E(i, 0);
}

#define ACC(q, j, e) acc[(q) & 1][4 * (j) + 2 * ((q) >> 1) + (e)]

__device__ __forceinline__ void write_partial_stats(const Ctx& c, int ln, uint32_t tag) {
  const uint32_t xrow = c.sb + OFF_X + c.w * 4096 + c.lane * 128;
  float s = 0.f, q = 0.f, s1 = 0.f, q1 = 0.f;
#pragma unroll 2
  for (int j = 0; j < 16; j++) {
    uint32_t u[4];
    lds_u4(xrow + (j >> 3) * 16384 + (((j & 7) ^ (c.lane & 7)) << 4), u[0], u[1], u[2], u[3]);
#pragma unroll
    for (int e = 0; e < 4; e++) {
      const float a = bf_lo(u[e]), d = bf_hi(u[e]);
      s += a; q = fmaf(a, a, q);
      s1 += d; q1 = fmaf(d, d, q1);
    }
  }
  s += s1;
  q += q1;
  st_msg(g_stats + (ln * 8 + c.n) * SEQ + 128 * c.m + 32 * c.w + c.lane, __float_as_uint(s),
         __float_as_uint(fmaxf(q - s * s * (1.f / 128.f), 0.f)), 0u, tag);
}

__device__ __forceinline__ void finish_row_stats(const Ctx& c, int ln, uint32_t tag) {
  const uint4* src = g_stats + ln * 8 * SEQ + 128 * c.m + 32 * c.w + c.lane;
  uint32_t ps[8], pm[8];
#pragma unroll 1
  for (int it = 0; it < MSG_SPINS; it++) {
    uint32_t bad = 0, u, tg;
#pragma unroll
    for (int k = 0; k < 8; k++) { ld_msg(src + k * SEQ, ps[k], pm[k], u, tg); bad |= tg ^ tag; }
    if (__all_sync(0xffffffffu, bad == 0)) break;
  }
  float s = 0.f, m2 = 0.f;
#pragma unroll
  for (int k = 0; k < 8; k++) s += __uint_as_float(ps[k]);
  const float mean = s * (1.f / DM);
#pragma unroll
  for (int k = 0; k < 8; k++) {
    const float d = __uint_as_float(ps[k]) * (1.f / 128.f) - mean;
    m2 += fmaf(128.f * d, d, __uint_as_float(pm[k]));
  }
  sts_f2(c.sb + OFF_ROW + (32 * c.w + c.lane) * 8, rsqrtf(m2 * (1.f / DM) + 1e-5f), mean);
  __syncwarp();
}

__device__ __forceinline__ void attn_scores(const uint32_t* qa, const uint32_t* qb, const uint32_t* k0, const uint32_t* k1,
                                            const uint32_t* k2, const uint32_t* k3, float (&l)[4], const float4& zero,
                                            bool par, bool early) {
  float s[4][4];
#pragma unroll
  for (int kb = 0; kb < 4; kb++) {
    const uint32_t* kk = kb == 0 ? k0 : kb == 1 ? k1 : kb == 2 ? k2 : k3;
    asm volatile("mma.sync.aligned.m16n8k16.row.col.f32.bf16.bf16.f32 {%0,%1,%2,%3}, {%4,%5,%6,%7}, {%8,%9}, {%10,%11,%12,%13};"
                 : "=f"(s[kb][0]), "=f"(s[kb][1]), "=f"(s[kb][2]), "=f"(s[kb][3])
                 : "r"(qa[0]), "r"(qb[0]), "r"(qa[1]), "r"(qb[1]), "r"(kk[0]), "r"(kk[1]), "f"(zero.x), "f"(zero.y),
                   "f"(zero.z), "f"(zero.w));
  }
#pragma unroll
  for (int kb = 0; kb < 4; kb++) {
    const uint32_t* kk = kb == 0 ? k0 : kb == 1 ? k1 : kb == 2 ? k2 : k3;
    mma16816(s[kb], qa[2], qb[2], qa[3], qb[3], kk[2], kk[3]);
  }
  l[0] = par ? s[1][1] : s[1][0];
  l[1] = early ? (par ? s[0][1] : s[0][0]) : (par ? s[2][1] : s[2][0]);
  l[2] = par ? s[2][3] : s[2][2];
  l[3] = early ? (par ? s[1][3] : s[1][2]) : (par ? s[3][3] : s[3][2]);
}

__device__ __forceinline__ void attn_mix(const float (&l)[4], const float (&sc)[4], const float (&off)[4], const float (&rk)[4],
                                         const uint32_t* v0, const uint32_t* v1, const uint32_t* v2, const uint32_t* v3,
                                         uint32_t* olo, uint32_t* ohi, const uint32_t (&sel)[4]) {
  float x[4];
#pragma unroll
  for (int e = 0; e < 4; e++) x[e] = fmaf(l[e], sc[e], off[e]);
  const float ml = quad_max(fmaxf(x[0], x[1])), mh = quad_max(fmaxf(x[2], x[3]));
  x[0] = ex2(x[0] - ml); x[1] = ex2(x[1] - ml);
  x[2] = ex2(x[2] - mh); x[3] = ex2(x[3] - mh);
  const uint32_t pl = pack_bf16(x[0] * rk[0], x[1] * rk[1]), ph = pack_bf16(x[2] * rk[2], x[3] * rk[3]);
  const uint32_t a0 = prmt_u(pl, sel[1]), a1 = prmt_u(pl, sel[3]), a2 = prmt_u(pl, sel[0]), a3 = prmt_u(ph, sel[1]);
  const uint32_t c0 = prmt_u(pl, sel[2]), c1 = prmt_u(ph, sel[0]), c2 = prmt_u(ph, sel[3]), c3 = prmt_u(ph, sel[2]);
  float o[4][4];
#pragma unroll
  for (int jn = 0; jn < 4; jn++) {
    o[jn][0] = o[jn][1] = o[jn][2] = o[jn][3] = 0.f;
    mma16816(o[jn], a0, a1, a2, a3, v0[jn], v1[jn]);
  }
#pragma unroll
  for (int jn = 0; jn < 4; jn++) mma16816(o[jn], c0, c1, c2, c3, v2[jn], v3[jn]);
  const float il = rcp_hw(quad_sum(x[0] + x[1])), ih = rcp_hw(quad_sum(x[2] + x[3]));
#pragma unroll
  for (int jn = 0; jn < 4; jn++) {
    olo[jn] = pack_bf16(o[jn][0] * il, o[jn][1] * il);
    ohi[jn] = pack_bf16(o[jn][2] * ih, o[jn][3] * ih);
  }
}

__device__ __forceinline__ void gelu_epilogue(const Params& p, float (&acc)[2][96], const Ctx& cx, int t) {
  UNPACK_CTX(cx);
  (void)wg;
  float rs[4], rm[4];
#pragma unroll
  for (int q = 0; q < 4; q++) {
    const float2 v = lds_f2(sb + OFF_ROW + (32 * w + 8 * q + (lane >> 2)) * 8);
    rs[q] = 0.5f * v.x;
    rm[q] = -rs[q] * v.y;
  }
  const int col0 = 128 * (t - 3), steps = t == 5 ? 6 : 4;
  const uint32_t stg = sb + OFF_STG + w * 4096;
  uint32_t ctab = sb + OFF_CSF + (col0 / 2 + (lane & 3)) * 16, srow = stg + lane * 128 + ((lane & 7) << 4);
  float v[2][16];
#define PULL(k) _Pragma("unroll") for (int j = 0; j < 4; j++) { \
      const float2 bb = lds_f2(ctab + j * 64 + 8); \
      _Pragma("unroll") for (int r = 0; r < 8; r++) \
        asm volatile("fma.rn.f32 %0, %1, %2, %3;" : "=f"(v[r >> 2][4 * j + (r & 3)]) \
                     : "f"(acc[r >> 2][16 * k + 4 * j + (r & 3)]), "f"(rs[(r >> 2) + (r & 2)]), "f"(r & 1 ? bb.y : bb.x)); }
  PULL(0)
#pragma unroll 1
  for (int it = 0;; it++) {
    uint32_t hp[4][4];
#pragma unroll
    for (int j = 0; j < 4; j++) {
      const float2 cs = lds_f2(ctab + j * 64);
#pragma unroll
      for (int q = 0; q < 4; q++) {
        float y[2];
        const int k = 4 * j + q - GELU_DEP;
        const float rmq = k >= 0 ? chain(rm[q], hp[k >> 2][k & 3], p.zero) : rm[q];
#pragma unroll
        for (int e = 0; e < 2; e++) {
          const float z = fmaf(rmq, e ? cs.y : cs.x, v[q & 1][4 * j + 2 * (q >> 1) + e]);
          const float u = z * fmaf(z * z, 8.f * 0.7978845608028654f * 0.044715f, 2.f * 0.7978845608028654f);
          y[e] = fmaf(z, tanh_hw(u), z);
        }
        hp[j][q] = pack_bf16(y[0], y[1]);
      }
    }
    ctab += 256;
    if (!(it & 1)) {
      if (lane == 0) bulk_wait_read();
      __syncwarp();
    }
#pragma unroll
    for (int j = 0; j < 4; j++) stsm4(srow ^ (j << 4), hp[j][0], hp[j][1], hp[j][2], hp[j][3]);
    srow ^= 64;
    if (it & 1) {
      fence_async_smem();
      __syncwarp();
      if (lane == 0) {
        tma_st2(&p.h_st, stg, 448 * n + col0 + 32 * (it - 1), 128 * m + 32 * w);
        bulk_commit();
      }
      if (it == steps - 1) break;
    }
    switch (it) {
      case 0: PULL(1) break;
      case 1: PULL(2) break;
      case 2: PULL(3) break;
      case 3: PULL(4) break;
      default: PULL(5)
    }
  }
#undef PULL
}

__device__ __forceinline__ void attn_epilogue(const Params& p, float (&acc)[2][96], const Ctx& cx, int layer, int t, uint32_t tag) {
  UNPACK_CTX(cx);
  const bool par = (lane >> 2) & 1, early = (lane & 3) > (lane >> 3);
  const uint32_t ktab = sb + OFF_ROW + (32 * w + 2 * (lane & 3) + par) * 8, exc = sb + OFF_STG + w * 4096 + lane * 16;
  const int slot = ((layer * 2 + t) * 16 + m) * 8 + n;
  const int mn = m * 8 + n; (void)mn;
  uint32_t Q[4][8], K[4][8], V[4][8], E[36], P[36];
  float kr[6], qr[4];
#pragma unroll
  for (int q = 2; q < 4; q++) {
    kr[2 + q] = lds_f(ktab + 64 * q);
#pragma unroll
    for (int j = 0; j < 8; j++) {
      E[8 * (q - 2) + j] = K[q][j] = pack_bf16(ACC(q, 8 + j, 0), ACC(q, 8 + j, 1));
      E[16 + 2 * j + q - 2] = V[q][j] = movtrans(pack_bf16(ACC(q, 16 + j, 0), ACC(q, 16 + j, 1)));
    }
  }
  E[32] = __float_as_uint(kr[4]);
  E[33] = E[34] = E[35] = __float_as_uint(kr[5]);
  if (w < 3) {
#pragma unroll
    for (int k = 0; k < 8; k++) sts_u4(exc + k * 512, E[4 * k], E[4 * k + 1], E[4 * k + 2], E[4 * k + 3]);
  } else {
#pragma unroll
    for (int k = 0; k < 12; k++) st_msg(g_halo + slot * 384 + k * 32 + lane, E[3 * k], E[3 * k + 1], E[3 * k + 2], tag);
  }
  PROF_E(7 * layer + t, 1);
#pragma unroll
  for (int q = 0; q < 4; q++) {
    qr[q] = lds_f(sb + OFF_ROW + (32 * w + 8 * q + (lane >> 2)) * 8) * (0.17677669529663687f * 1.4426950408889634f);
#pragma unroll
    for (int j = 0; j < 8; j++) Q[q][j] = pack_bf16(ACC(q, j, 0), ACC(q, j, 1));
    if (q < 2) {
      kr[2 + q] = lds_f(ktab + 64 * q);
#pragma unroll
      for (int j = 0; j < 8; j++) {
        K[q][j] = pack_bf16(ACC(q, 8 + j, 0), ACC(q, 8 + j, 1));
        V[q][j] = movtrans(pack_bf16(ACC(q, 16 + j, 0), ACC(q, 16 + j, 1)));
      }
    }
  }
  bar_sync(BAR_WG + wg, 128);
  if (w > 0 || m == 0) {
    const uint32_t back = w > 0;
#pragma unroll
    for (int k = 0; k < 8; k++) lds_u4(exc - back * 4096 + k * 512, P[4 * k], P[4 * k + 1], P[4 * k + 2], P[4 * k + 3]);
    P[32] = lds_u(ktab - back * 128);
    P[33] = lds_u(ktab - back * 64);
  } else {
#pragma unroll 1
    for (int it = 0; it < MSG_SPINS; it++) {
      uint32_t tg, bad = 0;
#pragma unroll
      for (int k = 0; k < 12; k++) {
        ld_msg(g_halo + (slot - 8) * 384 + k * 32 + lane, P[3 * k], P[3 * k + 1], P[3 * k + 2], tg);
        bad |= tg ^ tag;
      }
      if (__all_sync(0xffffffffu, bad == 0)) break;
    }
  }
  kr[0] = __uint_as_float(P[32]);
  kr[1] = __uint_as_float(P[33]);
  uint32_t PV[2][8];
#pragma unroll
  for (int j = 0; j < 8; j++) { PV[0][j] = P[16 + 2 * j]; PV[1][j] = P[17 + 2 * j]; }
  float rk[2][4], sc[2][4], off[2][4];
#pragma unroll
  for (int g = 0; g < 2; g++) {
    rk[g][0] = kr[2 * g + 1];
    rk[g][1] = early ? kr[2 * g] : kr[2 * g + 2];
    rk[g][2] = kr[2 * g + 2];
    rk[g][3] = early ? kr[2 * g + 1] : kr[2 * g + 3];
#pragma unroll
    for (int e = 0; e < 4; e++) {
      const bool masked = g == 0 && e != 2 && (m | w) == 0 && (e == 0 || early);
      sc[g][e] = masked ? 0.f : rk[g][e] * qr[2 * g + (e >> 1)];
      off[g][e] = masked ? -1e30f : 0.f;
    }
  }
  const uint32_t none = 0x4444u | p.zero, second = par ? 0x3244u : 0x4432u;
  const uint32_t sel[4] = {par ? 0x1044u : 0x4410u, early ? second : none, early ? none : second, none};
  PROF_E(7 * layer + t, 2);
  bar_sync(BAR_GO, 256);
  const float4 zero = lds_f4(sb + OFF_ZERO);
  float l[2][2][4];
  uint32_t O[4][8];
#pragma unroll
  for (int h = 0; h < 2; h++) {
    if (h == 1) {
      Q[2][4] |= __float_as_uint(l[1][0][0]) & p.zero;
      Q[0][4] |= __float_as_uint(l[0][0][0]) & p.zero;
    }
    attn_scores(&Q[2][4 * h], &Q[3][4 * h], &K[0][4 * h], &K[1][4 * h], &K[2][4 * h], &K[3][4 * h], l[1][h], zero, par, early);
    attn_scores(&Q[0][4 * h], &Q[1][4 * h], &P[4 * h], &P[8 + 4 * h], &K[0][4 * h], &K[1][4 * h], l[0][h], zero, par, early);
  }
  const uint32_t stg = sb + OFF_STG + w * 4096, srow = stg + lane * 128 + ((lane & 7) << 4);
#pragma unroll
  for (int h = 0; h < 2; h++) {
    attn_mix(l[1][h], sc[1], off[1], rk[1], &V[0][4 * h], &V[1][4 * h], &V[2][4 * h], &V[3][4 * h], &O[2][4 * h], &O[3][4 * h], sel);
    attn_mix(l[0][h], sc[0], off[0], rk[0], &PV[0][4 * h], &PV[1][4 * h], &V[0][4 * h], &V[1][4 * h], &O[0][4 * h], &O[1][4 * h], sel);
#pragma unroll
    for (int j = 4 * h; j < 4 * h + 4; j++) stsm4(srow ^ (j << 4), O[0][j], O[1][j], O[2][j], O[3][j]);
  }
  bar_arrive(BAR_DONE, 256);
  fence_async_smem();
  __syncwarp();
  if (lane == 0) {
    tma_st2(&p.att_st, stg, 128 * n + 64 * t, 128 * m + 32 * w);
    bulk_commit();
  }
}

__device__ __forceinline__ void finish_stores(uint32_t sb, int i) {
  const int t = i >= 7 ? i - 7 : i;
  if ((threadIdx.x & 31) == 0) {
    bulk_wait_all();
    mbar_arrive(sb + BAR_PUB + 8 * (t < 2 ? t : t + 1));
  }
  __syncwarp();
  if (i < 12) bar_arrive(BAR_GUARD + ((i & 1) ^ 1), 256);
}

__device__ __forceinline__ void consumer_tile(const Params& p, uint32_t sb0, int i, int mn) {
  const int layer = i >= 7, t = i - 7 * layer, wg = i & 1;
  const bool resid = t == 2 || t == 6;
  {
    float acc[2][96];
    if (resid) {
      const Ctx cx = make_ctx(sb0, mn);
      const uint32_t xrow = cx.sb + OFF_X + cx.w * 4096 + cx.lane * 128;
      const uint32_t sel_lo = 0x1044u | p.zero, sel_hi = 0x3244u | p.zero;
#pragma unroll
      for (int j = 0; j < 16; j++) {
        uint32_t r[4];
        ldsm4(xrow + (j >> 3) * 16384 + (((j & 7) ^ (cx.lane & 7)) << 4), r[0], r[1], r[2], r[3]);
#pragma unroll
        for (int q = 0; q < 4; q++) {
          ACC(q, j, 0) = prmt_f(r[q], sel_lo);
          ACC(q, j, 1) = prmt_f(r[q], sel_hi);
        }
      }
    } else {
#pragma unroll
      for (int r = 0; r < 64; r++) acc[0][r] = acc[1][r] = 0.f;
    }
#pragma unroll
    for (int r = 64; r < 96; r++) acc[0][r] = acc[1][r] = 0.f;
    if (i == 0) bar_sync(BAR_INIT, 384);
    if (t >= 5 || i == 7) finish_stores(sb0, i - 2);
#pragma unroll 1
    for (int step = !tile_split(i);; step++) {
      if (step == 1 && (t == 1 || t == 4)) {
        const Ctx cx = make_ctx(sb0, mn);
        if (i == 1) {
          const uint32_t epoch = __ldcg(g_epoch + (mn & 127));
          bar_sync(BAR_INIT, 384);
          asm volatile("st.shared.u32 [%0], %1;" ::"r"(sb0 + OFF_TAG), "r"(epoch + 1) : "memory");
        }
        const uint32_t tag = lds_u(cx.sb + OFF_TAG);
        const int ln = (i + 1) >> 2;
#pragma unroll 1
        for (int r = 0; r < 2; r++) {
          if (i == 1) {
            if (cx.w < 3) {
              float a[8] = {0.f, 0.f, 0.f, 0.f, 0.f, 0.f, 0.f, 0.f};
              mbar_wait(sb0 + BAR_CSLD, r);
              sum_rows(cx.sb + OFF_STG + cx.w * 8192, 8, a, cx.lane);
              publish_sums(a, g_csp + (cx.n * 17 + cx.m) * 224 + (3 * r + cx.w) * 32, cx.lane, tag);
            }
            PROF_E(-1, 5 + r);
          }
          if (r == 1) break;
          if (i == 1) {
            bar_sync(BAR_WG + 1, 128);
            if (cx.w == 3 && elect_one()) {
              mbar_expect_tx(sb0 + BAR_CSLD, 24576);
              tma_ld3(sb0 + OFF_STG, &p.wqkv, sb0 + BAR_CSLD, 128 * cx.n + 64, 64 * cx.m, 0);
            }
            mbar_wait(sb0 + BAR_XRDY, 0);
            mbar_wait(sb0 + BAR_XRDY + 8, 0);
          }
          write_partial_stats(cx, ln, tag);
          PROF_E(i - 2, 8);
        }
        if (i == 1) bar_arrive(BAR_HLP, 160);
        if (i <= 4) colsum_total(cx, ln, tag);
        PROF_E(i - 2, 9);
        if (i != 1) bar_sync(BAR_GUARD + wg, 256);
        finish_row_stats(cx, ln, tag);
        PROF_E(i - 2, 10);
        if (i <= 4) {
          colsum_gather(cx, ln, tag);
          if (i == 4) mbar_wait(sb0 + BAR_BIAS, 0);
          bar_sync(BAR_WG + wg, 128);
        }
        PROF_E(i - 2, 15);
        bar_arrive(BAR_GUARD + (wg ^ 1), 256);
      }
      if (step == 2 && !resid) bar_sync(BAR_GUARD + wg, 256);
      if (t + step == 2 || t == 6) {
        const Ctx cx = make_ctx(sb0, mn);
        float nm[4];
#pragma unroll
        for (int q = 0; q < 4; q++) nm[q] = t == 6 ? 1.f : -lds_f(cx.sb + OFF_ROW + (32 * cx.w + 8 * q + (cx.lane >> 2)) * 8 + 4);
        const uint32_t ctab = cx.sb + OFF_CSQ + ((t & 3) * 192 + 2 * (cx.lane & 3)) * 4;
#pragma unroll
        for (int j = 0; j < 24; j++) {
          const float2 cs = lds_f2(ctab + j * 32);
#pragma unroll
          for (int q = 0; q < 4; q++) {
            const int k = 4 * j + q - 1;
            const float nq = k >= 0 ? chain(nm[q], __float_as_uint(ACC(k & 3, k >> 2, 1)), p.zero) : nm[q];
            ACC(q, j, 0) = fmaf(nq, cs.x, ACC(q, j, 0));
            ACC(q, j, 1) = fmaf(nq, cs.y, ACC(q, j, 1));
          }
        }
      }
      if (step == 2) break;
      if (tile_wide(t)) {
        mainloop<192>(acc, sb0, i, step, mn);
      } else {
        mainloop<128>(acc, sb0, i, step, mn);
        if (resid) break;
      }
    }
    const Ctx cx = make_ctx(sb0, mn);
    if (resid) {
      const uint32_t xrow = cx.sb + OFF_X + cx.w * 4096 + cx.lane * 128;
#pragma unroll
      for (int j = 0; j < 16; j++) {
        stsm4(xrow + (j >> 3) * 16384 + (((j & 7) ^ (cx.lane & 7)) << 4), pack_bf16(ACC(0, j, 0), ACC(0, j, 1)),
              pack_bf16(ACC(1, j, 0), ACC(1, j, 1)), pack_bf16(ACC(2, j, 0), ACC(2, j, 1)), pack_bf16(ACC(3, j, 0), ACC(3, j, 1)));
        if ((j & 7) == 7) {
          fence_async_smem();
          __syncwarp();
          if (elect_one()) mbar_arrive(sb0 + BAR_XRDY + (j & 8));
        }
      }
      PROF_E(i, 4);
      return;
    }
    if (t < 2) attn_epilogue(p, acc, cx, layer, t, lds_u(sb0 + OFF_TAG));
    else gelu_epilogue(p, acc, cx, t);
    PROF_E(i, 4);
    if (t < 2 || i == 12) finish_stores(sb0, i);
    PROF_E(i, 5);
  }
}

__global__ void __launch_bounds__(384, 1) fused_layers_kernel(const int by_smid, const __nv_bfloat16* x_p, const __nv_bfloat16* wqkv_p,
                                                                  const __grid_constant__ Params p) {
  extern __shared__ __align__(1024) uint8_t smem_raw[];
  const uint32_t sb = uniform((uint32_t)__cvta_generic_to_shared(smem_raw));
  const int tid = threadIdx.x, lane = tid & 31, warp = uniform(tid >> 5), wg = warp >> 2, w = warp & 3;

  int mn;
  {
    int id = blockIdx.x;
    if (by_smid) asm volatile("mov.u32 %0, %%smid;" : "=r"(id));
    else if (id >= 120) id += 4;
    const int c = id >> 1;
    int g, j;
    if (c < 32) { g = c & 7; j = c >> 3; }
    else if (c < 60) { g = 1 + (c - 32) % 7; j = 4 + (c - 32) / 7; }
    else { g = 0; j = c - 58; }
    mn = ((g >> 2) * 8 + j) * 8 + (g & 3) * 2 + (id & 1);
    if (c == 60 || c == 61) {
      if (tid < 32) {
        const uint32_t tag = __ldcg(g_epoch + NCTA + (id & 3)) + 1;
#pragma unroll 1
        for (int mm = 0; mm < 16; mm++) poll_line(g_flags + mm * 32 + (lane & 7), 32 * tag, 0xffu);
        if (tid == 0) g_epoch[NCTA + (id & 3)] = tag;
      }
      return;
    }
  }
  const int m = mn >> 3, n = mn & 7;
  if (tid == 256) PROF_U(1);
  if (tid >= 382) asm volatile("prefetch.global.L2 [%0];" ::"l"(tid & 1 ? wqkv_p + 128 * n : x_p + 128 * m * DM));
  if (wg < 2) {
    asm volatile("setmaxnreg.inc.sync.aligned.u32 232;");
#pragma unroll 1
    for (int i = wg; i < 14; i += 2) {
      consumer_tile(p, sb, i, mn | (warp << 7));
      PROF_T(6 + i * 4);
    }
  } else {
    asm volatile("setmaxnreg.dec.sync.aligned.u32 40;");
    if (w != 0) {
      if (w == 2 && lane < 28) write_run_desc(sb, lane >> 1, lane & 1);
      bar_sync(BAR_INIT, 384);
      if (w == 1) producer<true>(p, sb, m, n, lane);
      else if (w == 3) colsum_helper(p, sb, m, n, lane);
      else if (elect_one()) publisher(p, sb, m, n);
    } else {
      if (elect_one()) {
#pragma unroll
        for (int k = 0; k < 4; k++) mbar_init(sb + BAR_FULL + 8 * k, 2);
        asm volatile("fence.mbarrier_init.release.cluster;" ::: "memory");
        PROF_U(4);
#pragma unroll 1
        for (int k = 0; k < 4; k++) {
          const uint32_t fb = sb + BAR_FULL + 8 * k;
          mbar_expect_tx(fb, 16384);
          tma_ld2(sb + (5 * k + 3) * UNIT, &p.xin, fb, 64 * k, 128 * m);
          mbar_expect_tx(fb, 3 * UNIT);
          tma_ld3(sb + 5 * k * UNIT, &p.wqkv, fb, 128 * n, 64 * k, 0);
        }
        PROF_U(5);
        mbar_init(sb + BAR_XRDY, 4);
        mbar_init(sb + BAR_XRDY + 8, 4);
        mbar_init(sb + BAR_FULL + 32, 2);
#pragma unroll
        for (int k = 0; k < NBAR; k++) mbar_init(sb + BAR_EMPTY + 8 * k, 4);
        mbar_init(sb + BAR_DUMMY, 4);
#pragma unroll
        for (int k = 0; k < 7; k++) mbar_init(sb + BAR_PUB + 8 * k, 4);
#pragma unroll
        for (int k = 0; k < 3; k++) mbar_init(sb + BAR_CSLD + 8 * k, 1);
        sts_f2(sb + OFF_ZERO, 0.f, 0.f);
        sts_f2(sb + OFF_ZERO + 8, 0.f, 0.f);
        asm volatile("fence.mbarrier_init.release.cluster;" ::: "memory");
        mbar_expect_tx(sb + BAR_CSLD, 24576);
        tma_ld3(sb + OFF_STG, &p.wqkv, sb + BAR_CSLD, 128 * n, 64 * m, 0);
#pragma unroll 1
        for (int h = 0; h < 2; h++) {
          const uint32_t xr = sb + BAR_XRDY + 8 * h;
          mbar_expect_tx(xr, 16384);
          tma_ld2(sb + OFF_X + h * 16384, &p.xin, xr, 128 * n + 64 * h, 128 * m);
          asm volatile("mbarrier.arrive.shared::cta.b64 _, [%0], 3;" ::"r"(xr) : "memory");
        }
        PROF_U(6);
      }
      __syncwarp();
      bar_arrive(BAR_INIT, 384);
      producer<false>(p, sb, m, n, lane);
    }
  }
}

typedef CUresult (*EncodeFn)(CUtensorMap*, CUtensorMapDataType, cuuint32_t, void*, const cuuint64_t*, const cuuint64_t*,
                             const cuuint32_t*, const cuuint32_t*, CUtensorMapInterleave, CUtensorMapSwizzle,
                             CUtensorMapL2promotion, CUtensorMapFloatOOBfill);

void make_2d(EncodeFn enc, CUtensorMap* m, const void* ptr, uint64_t cols, uint64_t rows, uint32_t box_rows) {
  cuuint64_t d[2] = {cols, rows}, st[1] = {cols * 2};
  cuuint32_t b[2] = {64, box_rows}, e[2] = {1, 1};
  enc(m, CU_TENSOR_MAP_DATA_TYPE_BFLOAT16, 2, const_cast<void*>(ptr), d, st, b, e, CU_TENSOR_MAP_INTERLEAVE_NONE,
      CU_TENSOR_MAP_SWIZZLE_128B, CU_TENSOR_MAP_L2_PROMOTION_L2_128B, CU_TENSOR_MAP_FLOAT_OOB_FILL_NONE);
}
void make_3d(EncodeFn enc, CUtensorMap* m, const void* ptr, uint64_t d0, uint64_t rows, uint64_t d2, uint64_t row_bytes,
             uint64_t chunk_bytes, uint32_t box_chunks) {
  cuuint64_t d[3] = {d0, rows, d2}, st[2] = {row_bytes, chunk_bytes};
  cuuint32_t b[3] = {64, 64, box_chunks}, e[3] = {1, 1, 1};
  enc(m, CU_TENSOR_MAP_DATA_TYPE_BFLOAT16, 3, const_cast<void*>(ptr), d, st, b, e, CU_TENSOR_MAP_INTERLEAVE_NONE,
      CU_TENSOR_MAP_SWIZZLE_128B, CU_TENSOR_MAP_L2_PROMOTION_L2_128B, CU_TENSOR_MAP_FLOAT_OOB_FILL_NONE);
}

}

extern "C" void kernel_launch(void* const* d_in, const int* in_sizes, int n_in, void* d_out, int out_size) {
  (void)in_sizes; (void)n_in; (void)out_size;
  static EncodeFn enc = nullptr;
  static void *att = nullptr, *hbuf = nullptr;
  static int by_smid = 0;
  if (!enc) {
    void* fn = nullptr;
    cudaDriverEntryPointQueryResult q;
    cudaGetDriverEntryPoint("cuTensorMapEncodeTiled", &fn, cudaEnableDefault, &q);
    enc = (EncodeFn)fn;
    cudaGetSymbolAddress(&att, g_att);
    cudaGetSymbolAddress(&hbuf, g_h);
    cudaFuncSetAttribute(fused_layers_kernel, cudaFuncAttributeMaxDynamicSharedMemorySize, SMEM_BYTES);
    int sms = 0, per_sm = 0, dev = 0;
    cudaGetDevice(&dev);
    cudaDeviceGetAttribute(&sms, cudaDevAttrMultiProcessorCount, dev);
    cudaOccupancyMaxActiveBlocksPerMultiprocessor(&per_sm, fused_layers_kernel, 384, SMEM_BYTES);
    by_smid = sms == 132 && per_sm == 1;
  }
  Params p;
  make_2d(enc, &p.xin, d_in[0], DM, SEQ, 128);
  make_2d(enc, &p.out, d_out, DM, SEQ, 128);
  make_2d(enc, &p.att, att, DM, SEQ, 128);
  make_2d(enc, &p.h, hbuf, FF, SEQ, 128);
  make_2d(enc, &p.out_st, d_out, DM, SEQ, 32);
  make_2d(enc, &p.att_st, att, DM, SEQ, 32);
  make_2d(enc, &p.h_st, hbuf, FF, SEQ, 32);
  make_2d(enc, &p.w1c, d_in[4], FF, DM, 32);
  make_3d(enc, &p.wqkv, d_in[1], DM, DM, 3, 3 * DM * 2, DM * 2, 3);
  make_3d(enc, &p.wo, d_in[2], 64, DM, DM / 64, DM * 2, 128, 2);
  make_3d(enc, &p.w1a, d_in[4], 64, DM, FF / 64, FF * 2, 128, 3);
  make_3d(enc, &p.w1b, d_in[4], 64, DM, FF / 64, FF * 2, 128, 2);
  make_3d(enc, &p.w2, d_in[6], 64, FF, DM / 64, DM * 2, 128, 2);
  p.b1 = (const __nv_bfloat16*)d_in[5];
  p.b2 = (const __nv_bfloat16*)d_in[7];
  p.zero = 0;
  fused_layers_kernel<<<by_smid ? 132 : NCTA, 384, SMEM_BYTES>>>(by_smid, (const __nv_bfloat16*)d_in[0], (const __nv_bfloat16*)d_in[1], p);
}
```

```cpp
#include <cuda_runtime.h>
#include <cuda_bf16.h>
#include <cuda.h>
#include <stdint.h>

namespace {

constexpr int SEQ = 2048, DM = 1024, FF = 3584;
constexpr int NCTA = 128;
constexpr int NBAR = 5;

constexpr uint32_t RING_UNITS = 20, UNIT = 8192;
constexpr uint32_t OFF_X   = RING_UNITS * UNIT;
constexpr uint32_t OFF_STG = OFF_X + 32768;
constexpr uint32_t OFF_HLP = OFF_STG + 16384;
constexpr uint32_t OFF_RUN = OFF_STG + 24576;
constexpr uint32_t OFF_CSQ = OFF_RUN + 512;
constexpr uint32_t OFF_CSF = OFF_CSQ + 2048;
constexpr uint32_t OFF_ROW = OFF_CSF + 3584;
constexpr uint32_t OFF_BAR = OFF_ROW + 1024;
constexpr uint32_t SMEM_BYTES = OFF_BAR + 384;
constexpr uint32_t BAR_FULL = OFF_BAR, BAR_EMPTY = OFF_BAR + 8 * NBAR;
constexpr uint32_t BAR_XRDY = OFF_BAR + 80;
constexpr uint32_t BAR_DUMMY = OFF_BAR + 96, OFF_TAG = OFF_BAR + 104, OFF_ZERO = OFF_BAR + 112;
constexpr uint32_t BAR_PUB = OFF_BAR + 128;
constexpr uint32_t BAR_CSLD = OFF_BAR + 200;
constexpr uint32_t BAR_BIAS = OFF_BAR + 216;

constexpr uint64_t DESC_A = (1ull << 62) | ((uint64_t)(2048 >> 4) << 32) | (1ull << 16);
constexpr uint64_t DESC_B = (1ull << 62) | ((uint64_t)(1024 >> 4) << 32) | ((uint64_t)(8192 >> 4) << 16);

constexpr int BAR_INIT = 0, BAR_ORDER = 1, BAR_GUARD = 3, BAR_WG = 5, BAR_GO = 7, BAR_DONE = 8, BAR_HLP = 9, BAR_INIT0 = 10;
#define GELU_DEP 2
#define WIN1 7
#define WIN2 4

struct Params {
  CUtensorMap xin, out, att, h, wqkv, wo, w1a, w1b, w2, out_st, att_st, h_st, w1c;
  const __nv_bfloat16 *b1, *b2;
  uint32_t zero;
};

__device__ __nv_bfloat16 g_att[SEQ * DM];
__device__ __nv_bfloat16 g_h[SEQ * FF];
__device__ uint4 g_stats[4 * 8 * SEQ];
__device__ uint4 g_halo[2 * 2 * 16 * 8 * 384];
__device__ uint4 g_csp[2 * 8 * 17 * 224];
__device__ uint32_t g_flags[16 * 32];
__device__ uint32_t g_epoch[NCTA + 4];
#define PROF_T(idx)
#define PROF_U(k)
#define PROF_S(g)
#define PROF_E(i, k)

__device__ __forceinline__ void mbar_init(uint32_t bar, int cnt) {
  asm volatile("mbarrier.init.shared::cta.b64 [%0], %1;" ::"r"(bar), "r"(cnt));
}
__device__ __forceinline__ void mbar_expect_tx(uint32_t bar, uint32_t bytes) {
  asm volatile("mbarrier.arrive.expect_tx.shared::cta.b64 _, [%0], %1;" ::"r"(bar), "r"(bytes) : "memory");
}
__device__ __forceinline__ void mbar_arrive(uint32_t bar) {
  asm volatile("mbarrier.arrive.shared::cta.b64 _, [%0];" ::"r"(bar) : "memory");
}
__device__ __forceinline__ bool mbar_test(uint32_t bar, uint32_t parity) {
  uint32_t ok;
  asm volatile("{\n.reg .pred p;\nmbarrier.test_wait.parity.shared::cta.b64 p, [%1], %2;\nselp.u32 %0, 1, 0, p;\n}"
               : "=r"(ok) : "r"(bar), "r"(parity) : "memory");
  return ok;
}
__device__ __forceinline__ void mbar_wait(uint32_t bar, uint32_t parity) {
  asm volatile(
      "{\n.reg .pred p;\n.reg .u32 it;\nmov.u32 it, 0;\n"
      "WAIT_LOOP:\n"
      "mbarrier.try_wait.parity.shared::cta.b64 p, [%0], %1;\n"
      "@p bra WAIT_DONE;\n"
      "add.u32 it, it, 1;\n"
      "setp.lt.u32 p, it, 0x400000;\n"
      "@p bra WAIT_LOOP;\n"
      "trap;\n"
      "WAIT_DONE:\n}"
      ::"r"(bar), "r"(parity) : "memory");
}
__device__ __forceinline__ void bar_sync(int id, int n) { asm volatile("bar.sync %0, %1;" ::"r"(id), "r"(n) : "memory"); }
__device__ __forceinline__ void bar_arrive(int id, int n) { asm volatile("bar.arrive %0, %1;" ::"r"(id), "r"(n) : "memory"); }
__device__ __forceinline__ void tma_ld2(uint32_t dst, const CUtensorMap* m, uint32_t bar, int c0, int c1) {
  asm volatile("cp.async.bulk.tensor.2d.shared::cluster.global.mbarrier::complete_tx::bytes [%0], [%1, {%3, %4}], [%2];"
               ::"r"(dst), "l"(m), "r"(bar), "r"(c0), "r"(c1) : "memory");
}
__device__ __forceinline__ void tma_ld3(uint32_t dst, const CUtensorMap* m, uint32_t bar, int c0, int c1, int c2) {
  asm volatile("cp.async.bulk.tensor.3d.shared::cluster.global.mbarrier::complete_tx::bytes [%0], [%1, {%3, %4, %5}], [%2];"
               ::"r"(dst), "l"(m), "r"(bar), "r"(c0), "r"(c1), "r"(c2) : "memory");
}
__device__ __forceinline__ void tma_st2(const CUtensorMap* m, uint32_t src, int c0, int c1) {
  asm volatile("cp.async.bulk.tensor.2d.global.shared::cta.bulk_group [%0, {%2, %3}], [%1];"
               ::"l"(m), "r"(src), "r"(c0), "r"(c1) : "memory");
}
__device__ __forceinline__ void bulk_commit() { asm volatile("cp.async.bulk.commit_group;" ::: "memory"); }
__device__ __forceinline__ void bulk_wait_read() { asm volatile("cp.async.bulk.wait_group.read 0;" ::: "memory"); }
__device__ __forceinline__ void bulk_wait_all() { asm volatile("cp.async.bulk.wait_group 0;" ::: "memory"); }
__device__ __forceinline__ void fence_async_smem() { asm volatile("fence.proxy.async.shared::cta;" ::: "memory"); }
__device__ __forceinline__ void fence_async_global() { asm volatile("fence.proxy.async.global;" ::: "memory"); }
__device__ __forceinline__ void st_relaxed(uint32_t* p, uint32_t v) {
  asm volatile("st.relaxed.gpu.global.u32 [%0], %1;" ::"l"(p), "r"(v) : "memory");
}
__device__ __forceinline__ void st_msg(uint4* p, uint32_t a, uint32_t b, uint32_t c, uint32_t tag) {
  asm volatile("{\n.reg .b128 v;\nmov.b128 v, {%1, %2, %3, %4};\nst.relaxed.gpu.b128 [%0], v;\n}"
               ::"l"(p), "r"(a), "r"(b), "r"(c), "r"(tag) : "memory");
}
__device__ __forceinline__ void ld_msg(const uint4* p, uint32_t& a, uint32_t& b, uint32_t& c, uint32_t& tag) {
  asm volatile("{\n.reg .b128 v;\nld.relaxed.gpu.b128 v, [%4];\nmov.b128 {%0, %1, %2, %3}, v;\n}"
               : "=r"(a), "=r"(b), "=r"(c), "=r"(tag) : "l"(p) : "memory");
}
__device__ __forceinline__ bool elect_one() {
  uint32_t ok;
  asm volatile("{\n.reg .pred p;\nelect.sync _|p, 0xffffffff;\nselp.u32 %0, 1, 0, p;\n}" : "=r"(ok));
  return ok;
}
__device__ __forceinline__ int uniform(int v) { return __shfl_sync(0xffffffffu, v, 0); }
__device__ __forceinline__ uint32_t pack_bf16(float lo, float hi) {
  uint32_t r;
  asm("cvt.rn.bf16x2.f32 %0, %1, %2;" : "=r"(r) : "f"(hi), "f"(lo));
  return r;
}
__device__ __forceinline__ uint32_t prmt_u(uint32_t a, uint32_t sel) {
  uint32_t r;
  asm("prmt.b32 %0, %1, 0, %2;" : "=r"(r) : "r"(a), "r"(sel));
  return r;
}
__device__ __forceinline__ float prmt_f(uint32_t a, uint32_t sel) {
  float r;
  asm("{\n.reg .b32 t;\nprmt.b32 t, %1, 0, %2;\nmov.b32 %0, t;\n}" : "=f"(r) : "r"(a), "r"(sel));
  return r;
}
__device__ __forceinline__ float bf_lo(uint32_t v) { return __uint_as_float(v << 16); }
__device__ __forceinline__ float bf_hi(uint32_t v) { return __uint_as_float(v & 0xffff0000u); }
__device__ __forceinline__ void stsm4(uint32_t addr, uint32_t r0, uint32_t r1, uint32_t r2, uint32_t r3) {
  asm volatile("stmatrix.sync.aligned.m8n8.x4.shared.b16 [%0], {%1, %2, %3, %4};"
               ::"r"(addr), "r"(r0), "r"(r1), "r"(r2), "r"(r3) : "memory");
}
__device__ __forceinline__ void ldsm4(uint32_t addr, uint32_t& r0, uint32_t& r1, uint32_t& r2, uint32_t& r3) {
  asm volatile("ldmatrix.sync.aligned.m8n8.x4.shared.b16 {%0, %1, %2, %3}, [%4];"
               : "=r"(r0), "=r"(r1), "=r"(r2), "=r"(r3) : "r"(addr) : "memory");
}
__device__ __forceinline__ uint32_t movtrans(uint32_t a) {
  uint32_t d;
  asm volatile("movmatrix.sync.aligned.m8n8.trans.b16 %0, %1;" : "=r"(d) : "r"(a));
  return d;
}
__device__ __forceinline__ void mma16816(float (&c)[4], uint32_t a0, uint32_t a1, uint32_t a2, uint32_t a3, uint32_t b0, uint32_t b1) {
  asm volatile("mma.sync.aligned.m16n8k16.row.col.f32.bf16.bf16.f32 {%0,%1,%2,%3}, {%4,%5,%6,%7}, {%8,%9}, {%0,%1,%2,%3};"
               : "+f"(c[0]), "+f"(c[1]), "+f"(c[2]), "+f"(c[3])
               : "r"(a0), "r"(a1), "r"(a2), "r"(a3), "r"(b0), "r"(b1));
}
__device__ __forceinline__ float2 lds_f2(uint32_t a) {
  float2 v;
  asm volatile("ld.shared.v2.f32 {%0, %1}, [%2];" : "=f"(v.x), "=f"(v.y) : "r"(a) : "memory");
  return v;
}
__device__ __forceinline__ float4 lds_f4(uint32_t a) {
  float4 v;
  asm volatile("ld.shared.v4.f32 {%0, %1, %2, %3}, [%4];" : "=f"(v.x), "=f"(v.y), "=f"(v.z), "=f"(v.w) : "r"(a) : "memory");
  return v;
}
__device__ __forceinline__ float lds_f(uint32_t a) {
  float v;
  asm volatile("ld.shared.f32 %0, [%1];" : "=f"(v) : "r"(a) : "memory");
  return v;
}
__device__ __forceinline__ uint32_t lds_u(uint32_t a) {
  uint32_t v;
  asm volatile("ld.shared.u32 %0, [%1];" : "=r"(v) : "r"(a) : "memory");
  return v;
}
__device__ __forceinline__ void sts_f2(uint32_t a, float x, float y) {
  asm volatile("st.shared.v2.f32 [%0], {%1, %2};" ::"r"(a), "f"(x), "f"(y) : "memory");
}
__device__ __forceinline__ void sts_u4(uint32_t a, uint32_t x, uint32_t y, uint32_t z, uint32_t w) {
  asm volatile("st.shared.v4.u32 [%0], {%1, %2, %3, %4};" ::"r"(a), "r"(x), "r"(y), "r"(z), "r"(w) : "memory");
}
__device__ __forceinline__ void lds_u4(uint32_t a, uint32_t& x, uint32_t& y, uint32_t& z, uint32_t& w) {
  asm volatile("ld.shared.v4.u32 {%0, %1, %2, %3}, [%4];" : "=r"(x), "=r"(y), "=r"(z), "=r"(w) : "r"(a) : "memory");
}
__device__ __forceinline__ float ex2(float x) {
  float y;
  asm("ex2.approx.ftz.f32 %0, %1;" : "=f"(y) : "f"(x));
  return y;
}
__device__ __forceinline__ float rcp_hw(float x) {
  float y;
  asm("rcp.approx.ftz.f32 %0, %1;" : "=f"(y) : "f"(x));
  return y;
}
__device__ __forceinline__ float tanh_hw(float x) {
  float y;
  asm("tanh.approx.f32 %0, %1;" : "=f"(y) : "f"(x));
  return y;
}
__device__ __forceinline__ float quad_sum(float v) {
  v += __shfl_xor_sync(0xffffffffu, v, 1);
  return v + __shfl_xor_sync(0xffffffffu, v, 2);
}
__device__ __forceinline__ float quad_max(float v) {
  v = fmaxf(v, __shfl_xor_sync(0xffffffffu, v, 1));
  return fmaxf(v, __shfl_xor_sync(0xffffffffu, v, 2));
}

template <int N> __device__ __forceinline__ void wgmma_ss(float (&d)[96], uint64_t da, uint64_t db);
template <> __device__ __forceinline__ void wgmma_ss<128>(float (&d)[96], uint64_t da, uint64_t db) {
  asm volatile(
      "wgmma.mma_async.sync.aligned.m64n128k16.f32.bf16.bf16 {%0, %1, %2, %3, %4, %5, %6, %7, %8, %9, %10, %11, %12, %13, %14, %15, %16, %17, %18, %19, %20, %21, %22, %23, %24, %25, %26, %27, %28, %29, %30, %31, %32, %33, %34, %35, %36, %37, %38, %39, %40, %41, %42, %43, %44, %45, %46, %47, %48, %49, %50, %51, %52, %53, %54, %55, %56, %57, %58, %59, %60, %61, %62, %63}, %64, %65, 1, 1, 1, 0, 1;"
      : "+f"(d[0]), "+f"(d[1]), "+f"(d[2]), "+f"(d[3]), "+f"(d[4]), "+f"(d[5]), "+f"(d[6]), "+f"(d[7]), "+f"(d[8]), "+f"(d[9]), "+f"(d[10]), "+f"(d[11]), "+f"(d[12]), "+f"(d[13]), "+f"(d[14]), "+f"(d[15]), "+f"(d[16]), "+f"(d[17]), "+f"(d[18]), "+f"(d[19]), "+f"(d[20]), "+f"(d[21]), "+f"(d[22]), "+f"(d[23]), "+f"(d[24]), "+f"(d[25]), "+f"(d[26]), "+f"(d[27]), "+f"(d[28]), "+f"(d[29]), "+f"(d[30]), "+f"(d[31]), "+f"(d[32]), "+f"(d[33]), "+f"(d[34]), "+f"(d[35]), "+f"(d[36]), "+f"(d[37]), "+f"(d[38]), "+f"(d[39]), "+f"(d[40]), "+f"(d[41]), "+f"(d[42]), "+f"(d[43]), "+f"(d[44]), "+f"(d[45]), "+f"(d[46]), "+f"(d[47]), "+f"(d[48]), "+f"(d[49]), "+f"(d[50]), "+f"(d[51]), "+f"(d[52]), "+f"(d[53]), "+f"(d[54]), "+f"(d[55]), "+f"(d[56]), "+f"(d[57]), "+f"(d[58]), "+f"(d[59]), "+f"(d[60]), "+f"(d[61]), "+f"(d[62]), "+f"(d[63])
      : "l"(da), "l"(db));
}

template <> __device__ __forceinline__ void wgmma_ss<192>(float (&d)[96], uint64_t da, uint64_t db) {
  asm volatile(
      "wgmma.mma_async.sync.aligned.m64n192k16.f32.bf16.bf16 {%0, %1, %2, %3, %4, %5, %6, %7, %8, %9, %10, %11, %12, %13, %14, %15, %16, %17, %18, %19, %20, %21, %22, %23, %24, %25, %26, %27, %28, %29, %30, %31, %32, %33, %34, %35, %36, %37, %38, %39, %40, %41, %42, %43, %44, %45, %46, %47, %48, %49, %50, %51, %52, %53, %54, %55, %56, %57, %58, %59, %60, %61, %62, %63, %64, %65, %66, %67, %68, %69, %70, %71, %72, %73, %74, %75, %76, %77, %78, %79, %80, %81, %82, %83, %84, %85, %86, %87, %88, %89, %90, %91, %92, %93, %94, %95}, %96, %97, 1, 1, 1, 0, 1;"
      : "+f"(d[0]), "+f"(d[1]), "+f"(d[2]), "+f"(d[3]), "+f"(d[4]), "+f"(d[5]), "+f"(d[6]), "+f"(d[7]), "+f"(d[8]), "+f"(d[9]), "+f"(d[10]), "+f"(d[11]), "+f"(d[12]), "+f"(d[13]), "+f"(d[14]), "+f"(d[15]), "+f"(d[16]), "+f"(d[17]), "+f"(d[18]), "+f"(d[19]), "+f"(d[20]), "+f"(d[21]), "+f"(d[22]), "+f"(d[23]), "+f"(d[24]), "+f"(d[25]), "+f"(d[26]), "+f"(d[27]), "+f"(d[28]), "+f"(d[29]), "+f"(d[30]), "+f"(d[31]), "+f"(d[32]), "+f"(d[33]), "+f"(d[34]), "+f"(d[35]), "+f"(d[36]), "+f"(d[37]), "+f"(d[38]), "+f"(d[39]), "+f"(d[40]), "+f"(d[41]), "+f"(d[42]), "+f"(d[43]), "+f"(d[44]), "+f"(d[45]), "+f"(d[46]), "+f"(d[47]), "+f"(d[48]), "+f"(d[49]), "+f"(d[50]), "+f"(d[51]), "+f"(d[52]), "+f"(d[53]), "+f"(d[54]), "+f"(d[55]), "+f"(d[56]), "+f"(d[57]), "+f"(d[58]), "+f"(d[59]), "+f"(d[60]), "+f"(d[61]), "+f"(d[62]), "+f"(d[63]), "+f"(d[64]), "+f"(d[65]), "+f"(d[66]), "+f"(d[67]), "+f"(d[68]), "+f"(d[69]), "+f"(d[70]), "+f"(d[71]), "+f"(d[72]), "+f"(d[73]), "+f"(d[74]), "+f"(d[75]), "+f"(d[76]), "+f"(d[77]), "+f"(d[78]), "+f"(d[79]), "+f"(d[80]), "+f"(d[81]), "+f"(d[82]), "+f"(d[83]), "+f"(d[84]), "+f"(d[85]), "+f"(d[86]), "+f"(d[87]), "+f"(d[88]), "+f"(d[89]), "+f"(d[90]), "+f"(d[91]), "+f"(d[92]), "+f"(d[93]), "+f"(d[94]), "+f"(d[95])
      : "l"(da), "l"(db));
}

template <int R>
__device__ __forceinline__ void pin_regs(float (&a)[2][96]) {
#pragma unroll
  for (int m = 0; m < 2; m++)
#pragma unroll
    for (int i = 0; i < R; i++) asm volatile("" : "+f"(a[m][i])::"memory");
}

struct Ctx {
  uint32_t sb;
  int m, n, wg, w, lane;
};
__device__ __forceinline__ Ctx make_ctx(uint32_t sb, int id) {
  int lane;
  asm volatile("mov.u32 %0, %%laneid;" : "=r"(lane));
  asm volatile("" : "+r"(id), "+r"(sb));
  return Ctx{sb, (id >> 3) & 15, id & 7, id >> 9, (id >> 7) & 3, lane};
}
#define UNPACK_CTX(c) const uint32_t sb = c.sb; const int m = c.m, n = c.n, wg = c.wg, w = c.w, lane = c.lane

__device__ __forceinline__ uint32_t poll_line(const uint32_t* word, uint32_t target, uint32_t need) {
  uint32_t v;
  asm volatile(
      "{\n.reg .pred p;\n.reg .u32 it, m;\n.reg .s32 d;\nmov.u32 it, 0;\n"
      "POLL_LOOP:\n"
      "ld.relaxed.gpu.global.u32 %0, [%1];\n"
      "sub.s32 d, %0, %2;\n"
      "setp.ge.s32 p, d, 0;\n"
      "vote.sync.ballot.b32 m, p, 0xffffffff;\n"
      "and.b32 m, m, %3;\n"
      "setp.eq.u32 p, m, %3;\n"
      "@p bra.uni POLL_DONE;\n"
      "add.u32 it, it, 1;\n"
      "setp.lt.u32 p, it, 0x400000;\n"
      "@p bra.uni POLL_LOOP;\n"
      "trap;\n"
      "POLL_DONE:\n}"
      : "=&r"(v) : "l"(word), "r"(target), "r"(need) : "memory");
  return v;
}
__device__ __forceinline__ uint32_t ld_relaxed(const uint32_t* p) {
  uint32_t v;
  asm volatile("ld.relaxed.gpu.global.u32 %0, [%1];" : "=r"(v) : "l"(p) : "memory");
  return v;
}
__device__ __forceinline__ float chain(float x, uint32_t on, uint32_t zero) {
  return __uint_as_float(__float_as_uint(x) | (on & zero));
}
constexpr int MSG_SPINS = 1 << 20;

constexpr int STAGES_PER_LAYER = 152;
__device__ __forceinline__ int nib(uint64_t v, int i) { return (int)(v >> (4 * i)) & 15; }
__device__ __forceinline__ bool tile_wide(int t) { return (0x23 >> t) & 1; }
__device__ __forceinline__ void weight_coords(const Params& p, int t, int n, const CUtensorMap*& map, int& c0, int& c2) {
  map = &p.wqkv + nib(0x4233100ull, t);
  c0 = t < 2 ? 128 * n + 64 * t : 0;
  c2 = t < 2 ? 0 : (t == 2 || t == 6) ? 2 * n : 7 * n + 2 * t - 6;
}

template <bool IS_A>
__device__ __forceinline__ void producer(const Params& p, uint32_t sb, int m, int n, int lane) {
  uint32_t owners = 0;
#pragma unroll 1
  for (int q = 7; q >= 0; q--) owners = owners << 4 | ((((n & 6) + q) & 7) ^ (q < 2 ? n & 1 : 0));
  const uint64_t order_x = (uint64_t)((owners >> 4) * 2 + 0x1111111u) << 36 | (uint64_t)(owners >> 4) * 2 << 8 | (n * 0x22 + 0x10);
  int inflight = 4, cur = 0;
  uint32_t fb = sb + BAR_FULL + 32, rb = sb + BAR_EMPTY, rph = 0, pos = 0, tag32 = 0, seen = 0;
  const uint32_t fend = sb + BAR_FULL + 8 * NBAR, rend = sb + BAR_EMPTY + 8 * NBAR;
  const uint32_t* word = g_flags + m * 32 + (lane < 16 ? lane >> 1 : lane & 7);
#pragma unroll 1
  for (int sg = 1; sg < 22; sg++) {
    const int layer = sg >= 11, s = sg == 1 ? 2 : sg == 2 ? 1 : sg - 11 * layer;
    const int t = nib(0x65434321010ull, s), kind = nib(0x32110031100ull, s);
    const bool wide = tile_wide(t);
    const uint32_t bbytes = wide ? 3 * UNIT : 2 * UNIT, base = sb + (IS_A ? bbytes : 0);
    const int mul = t == 6 ? 448 : t == 2 ? 128 : 64, count = sg == 1 ? 12 : 2 * nib(0x4871ull, kind);
    const uint64_t order0 = sg == 1 ? 0xFEDCBA987654ull : kind == 3 ? owners : order_x >> (8 * (kind & 1));
    uint32_t special = (s == 4 || s == 10) ? 0x10 : s == 9 ? 0xF : 1;
    if (IS_A) special |= (kind & 1 ? 0 : 3) | (count >= 4 ? 1u << (count - 4) : 0);
    if (s >= 9) pos = (s + 6) * UNIT;
    const CUtensorMap* map;
    int c0 = 0, c2 = 0, ev = 0;
    if (IS_A) {
      map = &p.xin + (t == 2 ? 2 : t == 6 ? 3 : sg >= 4);
      ev = 9 * layer + (t < 2 ? 0 : t == 2 ? 1 : t < 6 ? 4 : 5);
      if (sg == 2) seen = tag32 = (__ldcg(g_epoch + m * 8 + n) + 1) << 5;
    } else {
      weight_coords(p, t, n, map, c0, c2);
    }
#pragma unroll 1
    for (int add = 0; add < mul; add += 64) {
      uint64_t order = order0;
      const int need = kind == 3 ? ev : ev - 1 + (lane & 1), sh = kind == 3 ? 16 : 0;
      uint32_t ready = IS_A ? __ballot_sync(0xffffffffu, cur >= need) >> sh : 0;
#pragma unroll 1
      for (int k = 0; k < count; k++) {
        const int code = order & 15, kc = code * mul + add;
        order >>= 4;
        if ((special >> k) & 1) {
          const int lag = wide ? (s == 9 && k == 2 ? 2 : 3) : ((s == 4 || s == 10) && add == 0 && k < 4) ? 3 : 4;
#pragma unroll 1
          for (; inflight > lag; inflight--) {
            mbar_wait(rb, rph);
            rb += 8;
            if (rb == rend) { rb -= 8 * NBAR; rph ^= 1; }
          }
          inflight++;
          if (IS_A) {
            if (kind == 3 ? t == 2 && add + k == 64 : !(kind & 1) && k < 2) {
              if (t == 2) mbar_wait(sb + BAR_PUB + 8, layer);
              else if (k == 1 && (s == 0 || s == 5)) mbar_wait(sb + BAR_XRDY + 8, s == 5);
              if (elect_one()) mbar_arrive(fb);
              goto next_stage;
            }
            if (k == count - 4 && sg >= 3) seen = ld_relaxed(word);
          }
        } else {
          mbar_wait(rb, rph);
          rb += 8;
          if (rb == rend) { rb -= 8 * NBAR; rph ^= 1; }
        }
        if (IS_A && !((ready >> code) & 1)) {
          cur = max(cur, (int)(seen - tag32));
          ready = __ballot_sync(0xffffffffu, cur >= need) >> sh;
          if (!((ready >> code) & 1)) {
            cur = (int)(poll_line(word, tag32 + need, 1u << (code + sh)) - tag32);
            ready = __ballot_sync(0xffffffffu, cur >= need) >> sh;
          }
          asm volatile("fence.acquire.gpu;" ::: "memory");
          fence_async_global();
        }
        if (elect_one()) {
          if (!IS_A) tma_ld3(base + pos, map, fb, c0, kc, c2);
          else tma_ld2(base + pos, map, fb, kc, 128 * m);
          mbar_expect_tx(fb, IS_A ? 16384 : bbytes);
        }
      next_stage:
        fb += 8;
        if (fb == fend) fb -= 8 * NBAR;
        pos += bbytes + 2 * UNIT;
        if (pos >= RING_UNITS * UNIT) pos -= RING_UNITS * UNIT;
      }
      special = !IS_A ? 0 : t == 2 ? 1 : add == 128 ? 0x10 : 0;
      if (IS_A && (t == 2 || add == 64 || add == 192)) ev++;
    }
  }
}

__device__ __forceinline__ void publisher(const Params& p, uint32_t sb, int m, int n) {
  const uint32_t tag = __ldcg(g_epoch + m * 8 + n) + 1;
  uint32_t* word = g_flags + m * 32 + n;
  const int mn = m * 8 + n; (void)mn;
  st_relaxed(word, 32 * tag);
#pragma unroll 1
  for (int c = 0; c < 18; c++) {
    const int e = c >= 9 ? c - 9 : c;
    if ((0x18C >> e) & 1) {
      const int half = (0x108 >> e) & 1;
      mbar_wait(sb + BAR_XRDY + 8 * half, e < 4);
#pragma unroll
      for (int w = 0; w < 4; w++) tma_st2(&p.out_st, sb + OFF_X + half * 16384 + w * 4096, 128 * n + 64 * half, 128 * m + 32 * w);
      bulk_commit();
      if (c >= 16) continue;
      bulk_wait_all();
      PROF_E(7 * (c >= 9) + (e < 4 ? 2 : 6), 11 + 2 * half);
    } else {
      mbar_wait(sb + BAR_PUB + 8 * e, c >= 9);
    }
    asm volatile("fence.release.gpu;" ::: "memory");
    st_relaxed(word, 32 * tag + c + 1);
    PROF_E(7 * (c >= 9) + nib(0x665432210ull, e), (0x108 >> e) & 1 ? 14 : 12);
  }
  g_epoch[m * 8 + n] = tag;
  bulk_wait_read();
}

__device__ __forceinline__ void sum_rows(uint32_t buf, int iters, float (&a)[8], int lane) {
  uint32_t addr = buf + (lane >> 3) * 128 + (((lane & 7) ^ (lane >> 3)) << 4);
#pragma unroll 1
  for (int it = 0; it < iters; it++) {
    uint32_t u[2][4];
    lds_u4(addr, u[0][0], u[0][1], u[0][2], u[0][3]);
    lds_u4((addr ^ 64) + 512, u[1][0], u[1][1], u[1][2], u[1][3]);
    addr += 1024;
#pragma unroll
    for (int e = 0; e < 8; e++) { a[2 * (e & 3)] += bf_lo(u[e >> 2][e & 3]); a[2 * (e & 3) + 1] += bf_hi(u[e >> 2][e & 3]); }
  }
}
__device__ __forceinline__ void publish_sums(const float (&a)[8], uint4* dst, int lane, uint32_t tag) {
  const bool u8 = lane & 8, u16 = lane & 16;
  float h4[4], h2[2];
#pragma unroll
  for (int e = 0; e < 4; e++) h4[e] = (u8 ? a[4 + e] : a[e]) + __shfl_xor_sync(0xffffffffu, u8 ? a[e] : a[4 + e], 8);
#pragma unroll
  for (int e = 0; e < 2; e++) h2[e] = (u16 ? h4[2 + e] : h4[e]) + __shfl_xor_sync(0xffffffffu, u16 ? h4[e] : h4[2 + e], 16);
  st_msg(dst + (lane & 7) * 4 + (u8 ? 2 : 0) + (u16 ? 1 : 0), __float_as_uint(h2[0]), __float_as_uint(h2[1]), 0u, tag);
}

__device__ __forceinline__ void colsum_helper(const Params& p, uint32_t sb, int m, int n, int lane) {
  const uint32_t tag = __ldcg(g_epoch + m * 8 + n) + 1;
  const int mn = m * 8 + n; (void)mn;
#pragma unroll 1
  for (int k = lane; k < 288; k += 32) {
    const uint32_t bb = __ldg(reinterpret_cast<const uint32_t*>(k < 224 ? p.b1 + 448 * n : p.b2 + 128 * n - 448) + k);
    const float sc = k < 224 ? 0.5f : 1.f;
    sts_f2(sb + (k < 224 ? OFF_CSF + k * 16 + 8 : OFF_CSQ + 1536 + (k - 224) * 8), sc * bf_lo(bb), sc * bf_hi(bb));
  }
  __syncwarp();
  if (elect_one()) mbar_arrive(sb + BAR_BIAS);
  bar_sync(BAR_HLP, 160);
  PROF_E(-1, 1);
#pragma unroll 1
  for (int c = 0; c < 7; c++) {
    float a[8] = {0.f, 0.f, 0.f, 0.f, 0.f, 0.f, 0.f, 0.f};
#pragma unroll 1
    for (int h = 0; h < 2; h++) {
      if (elect_one()) {
        mbar_expect_tx(sb + BAR_CSLD + 8, 4096);
        tma_ld2(sb + OFF_HLP, &p.w1c, sb + BAR_CSLD + 8, 448 * n + 64 * c, 64 * m + 32 * h);
        if (c < 6) asm volatile("cp.async.bulk.prefetch.tensor.2d.L2.global [%0, {%1, %2}];" ::"l"(&p.w1c), "r"(448 * n + 64 * c + 64), "r"(64 * m + 32 * h) : "memory");
      }
      mbar_wait(sb + BAR_CSLD + 8, h);
      sum_rows(sb + OFF_HLP, 4, a, lane);
      __syncwarp();
    }
    publish_sums(a, g_csp + ((8 + n) * 17 + m) * 224 + c * 32, lane, tag);
  }
  PROF_E(-1, 2);
}

__device__ __forceinline__ void poll_msgs2(const uint4* pa, const uint4* pb, float (&v)[4], uint32_t tag) {
#pragma unroll 1
  for (int it = 0; it < MSG_SPINS; it++) {
    uint32_t x[4], z, ta, tb;
    ld_msg(pa, x[0], x[1], z, ta);
    ld_msg(pb, x[2], x[3], z, tb);
#pragma unroll
    for (int e = 0; e < 4; e++) v[e] = __uint_as_float(x[e]);
    if (__all_sync(0xffffffffu, ta == tag && tb == tag)) break;
  }
}
__device__ __forceinline__ void colsum_total(const Ctx& cx, int mat, uint32_t tag) {
  uint4* base = g_csp + (mat * 8 + cx.n) * 17 * 224;
  const int per = 12 + 2 * mat, k = 2 * cx.w + (cx.lane >> 4), ia = per * cx.m + k, ib = per * cx.m + min(k + 8, per - 1);
  float v[4];
  poll_msgs2(base + (cx.lane & 15) * 224 + ia, base + (cx.lane & 15) * 224 + ib, v, tag);
#pragma unroll 1
  for (int d = 1; d < 16; d *= 2)
#pragma unroll
    for (int e = 0; e < 4; e++) v[e] += __shfl_xor_sync(0xffffffffu, v[e], d);
  const bool hi = cx.lane & 1;
  if ((cx.lane & 14) == 0) st_msg(base + 16 * 224 + (hi ? ib : ia), __float_as_uint(hi ? v[2] : v[0]), __float_as_uint(hi ? v[3] : v[1]), 0u, tag);
}
__device__ __forceinline__ void colsum_gather(const Ctx& cx, int mat, uint32_t tag) {
  const uint4* base = g_csp + ((mat * 8 + cx.n) * 17 + 16) * 224;
  const int ia = cx.w * 32 + cx.lane, ib = min(ia + 128, 191 + 32 * mat);
  float v[4];
  poll_msgs2(base + ia, base + ib, v, tag);
  const uint32_t tab = cx.sb + (mat ? OFF_CSF : OFF_CSQ);
  sts_f2(tab + (ia << (3 + mat)), v[0], v[1]);
  sts_f2(tab + (ib << (3 + mat)), v[2], v[3]);
}

constexpr uint32_t RING16 = RING_UNITS * (UNIT >> 4);
__device__ __forceinline__ bool tile_split(int i) { return (0xD98 >> i) & 1; }

__device__ __forceinline__ void write_run_desc(uint32_t sb, int i, int step) {
  const int layer = i >= 7, t = i - 7 * layer, part = tile_split(i) ? step : 2;
  const bool wide = tile_wide(t), own = t != 2 && t != 6 && part != 1 && i != 0, second = t == 1 || t == 4;
  const uint32_t z16 = (wide ? 5 : 4) * (UNIT >> 4), a_off = z16 - 1024 + (uint32_t)DESC_A - (uint32_t)DESC_B;
  const int gl = 16 * t + (part == 2 ? 0 : second ? 16 * part - 14 : 4 * part), g0 = layer * STAGES_PER_LAYER + gl;
  const uint32_t s16 = (sb & 0x3FFFF) >> 4, bfirst = (uint32_t)DESC_B + s16;
  const int nkb = t == 6 ? 56 : part == 0 ? 2 : 12 + 2 * part;
  const bool win1 = t == 1 && part != 0;
  const int run = win1 ? WIN1 + 1 : t == 2 ? WIN2 + 1 : nkb;
  const int rest = win1 ? 64 | (nkb - 1 - WIN1) : t == 2 ? 64 | (7 - WIN2) | (8 << 7) : 0;
  const uint32_t blo = bfirst + z16 * (wide ? (gl + (t == 5 ? 3 : 0)) & 3 : (gl + 3) % 5);
  const uint32_t alo = own ? (uint32_t)DESC_A + s16 + (OFF_X >> 4) : blo + a_off;
  const uint32_t aoff = own ? alo + 1024 - (blo == bfirst + RING16 - z16 ? bfirst : blo + z16) : a_off;
  const bool xwait = part == 0 && !second;
  sts_u4(sb + OFF_RUN + (2 * i + step) * 16, blo, alo, aoff,
         ((g0 / NBAR) & 1) | xwait << 1 | 8 * (g0 % NBAR) | run << 6 | rest << 12);
}

template <int N>
__device__ __forceinline__ void mainloop(float (&acc)[2][96], uint32_t sb, int i, int step, int mn) {
  constexpr uint32_t Z16 = (2 + N / 64) * (UNIT >> 4);
  constexpr uint32_t A_OFF = Z16 - 1024 + (uint32_t)DESC_A - (uint32_t)DESC_B;
  const int wg = i & 1;
  const uint32_t s16 = (sb & 0x3FFFF) >> 4;
  const uint32_t blast = (uint32_t)DESC_B + s16 + RING16 - Z16, flast = sb + BAR_FULL + 8 * (NBAR - 1);
  uint32_t blo, alo, aoff, misc;
  if (N == 192 && i == 0) bar_sync(BAR_INIT0, 192);
  lds_u4(sb + OFF_RUN + (2 * i + step) * 16, blo, alo, aoff, misc);
  int run = (misc >> 6) & 63, rest = misc >> 12;
  uint32_t fb = sb + BAR_FULL + (misc & 0x38), ph = misc & 1;
  uint32_t prev = sb + BAR_DUMMY - 8 * NBAR;
  pin_regs<N / 2>(acc);
  if (i > 0) bar_sync(BAR_ORDER + wg, 256);
  if (N == 192 && i == 0 && threadIdx.x == 0) PROF_U(8);
  mbar_wait(fb, ph);
  if (misc & 2) mbar_wait(sb + BAR_XRDY, N == 128);
  if (step == 0 || !tile_split(i)) PROF_T(4 + i * 4);
#pragma unroll 1
  while (true) {
    const uint64_t da = (DESC_A & ~0xffffffffull) | alo, db = (DESC_B & ~0xffffffffull) | blo;
    asm volatile("wgmma.fence.sync.aligned;" ::: "memory");
    wgmma_ss<N>(acc[0], da, db);
    wgmma_ss<N>(acc[1], da + 64, db);
    wgmma_ss<N>(acc[0], da + 2, db + 128);
    wgmma_ss<N>(acc[1], da + 66, db + 128);
    asm volatile("wgmma.commit_group.sync.aligned;" ::: "memory");
    asm volatile("wgmma.wait_group.sync.aligned 1;" ::: "memory");
    PROF_S(jj++);
    if (elect_one()) mbar_arrive(prev + 8 * NBAR);
    prev = fb;
    if (fb == flast) { fb -= 8 * NBAR; ph++; }
    fb += 8;
    if (blo == blast) blo -= RING16;
    blo += Z16;
    alo = blo + aoff;
    aoff = A_OFF;
    run--;
    const bool ready = mbar_test(fb, ph) && run != 0;
    asm volatile("wgmma.fence.sync.aligned;" ::: "memory");
    wgmma_ss<N>(acc[0], da + 4, db + 256);
    wgmma_ss<N>(acc[1], da + 68, db + 256);
    wgmma_ss<N>(acc[0], da + 6, db + 384);
    wgmma_ss<N>(acc[1], da + 70, db + 384);
    asm volatile("wgmma.commit_group.sync.aligned;" ::: "memory");
    if (!ready) {
      if (run == 0) {
        if (rest == 0) break;
        if (rest & 64) {
          bar_arrive(BAR_GO, 256);
          bar_sync(BAR_DONE, 256);
        } else {
          alo = (uint32_t)DESC_A + s16 + (OFF_STG >> 4);
        }
        run = rest & 63;
        rest >>= 7;
      }
      mbar_wait(fb, ph);
    }
  }
  if (i < 13) bar_arrive(BAR_ORDER + (wg ^ 1), 256);
  asm volatile("wgmma.wait_group.sync.aligned 0;" ::: "memory");
  pin_regs<N / 2>(acc);
  if (elect_one()) mbar_arrive(prev + 8 * NBAR);
  PROF_T(5 + i * 4);
  PROF_E(i, 0);
}

#define ACC(q, j, e) acc[(q) & 1][4 * (j) + 2 * ((q) >> 1) + (e)]

__device__ __forceinline__ void write_partial_stats(const Ctx& c, int ln, uint32_t tag) {
  const uint32_t xrow = c.sb + OFF_X + c.w * 4096 + c.lane * 128;
  float s = 0.f, q = 0.f, s1 = 0.f, q1 = 0.f;
#pragma unroll 2
  for (int j = 0; j < 16; j++) {
    uint32_t u[4];
    lds_u4(xrow + (j >> 3) * 16384 + (((j & 7) ^ (c.lane & 7)) << 4), u[0], u[1], u[2], u[3]);
#pragma unroll
    for (int e = 0; e < 4; e++) {
      const float a = bf_lo(u[e]), d = bf_hi(u[e]);
      s += a; q = fmaf(a, a, q);
      s1 += d; q1 = fmaf(d, d, q1);
    }
  }
  s += s1;
  q += q1;
  st_msg(g_stats + (ln * 8 + c.n) * SEQ + 128 * c.m + 32 * c.w + c.lane, __float_as_uint(s),
         __float_as_uint(fmaxf(q - s * s * (1.f / 128.f), 0.f)), 0u, tag);
}

__device__ __forceinline__ void finish_row_stats(const Ctx& c, int ln, uint32_t tag) {
  const uint4* src = g_stats + ln * 8 * SEQ + 128 * c.m + 32 * c.w + c.lane;
  uint32_t ps[8], pm[8];
#pragma unroll 1
  for (int it = 0; it < MSG_SPINS; it++) {
    uint32_t bad = 0, u, tg;
#pragma unroll
    for (int k = 0; k < 8; k++) { ld_msg(src + k * SEQ, ps[k], pm[k], u, tg); bad |= tg ^ tag; }
    if (__all_sync(0xffffffffu, bad == 0)) break;
  }
  float s = 0.f, m2 = 0.f;
#pragma unroll
  for (int k = 0; k < 8; k++) s += __uint_as_float(ps[k]);
  const float mean = s * (1.f / DM);
#pragma unroll
  for (int k = 0; k < 8; k++) {
    const float d = __uint_as_float(ps[k]) * (1.f / 128.f) - mean;
    m2 += fmaf(128.f * d, d, __uint_as_float(pm[k]));
  }
  sts_f2(c.sb + OFF_ROW + (32 * c.w + c.lane) * 8, rsqrtf(m2 * (1.f / DM) + 1e-5f), mean);
  __syncwarp();
}

__device__ __forceinline__ void attn_scores(const uint32_t* qa, const uint32_t* qb, const uint32_t* k0, const uint32_t* k1,
                                            const uint32_t* k2, const uint32_t* k3, float (&l)[4], const float4& zero,
                                            bool par, bool early) {
  float s[4][4];
#pragma unroll
  for (int kb = 0; kb < 4; kb++) {
    const uint32_t* kk = kb == 0 ? k0 : kb == 1 ? k1 : kb == 2 ? k2 : k3;
    asm volatile("mma.sync.aligned.m16n8k16.row.col.f32.bf16.bf16.f32 {%0,%1,%2,%3}, {%4,%5,%6,%7}, {%8,%9}, {%10,%11,%12,%13};"
                 : "=f"(s[kb][0]), "=f"(s[kb][1]), "=f"(s[kb][2]), "=f"(s[kb][3])
                 : "r"(qa[0]), "r"(qb[0]), "r"(qa[1]), "r"(qb[1]), "r"(kk[0]), "r"(kk[1]), "f"(zero.x), "f"(zero.y),
                   "f"(zero.z), "f"(zero.w));
  }
#pragma unroll
  for (int kb = 0; kb < 4; kb++) {
    const uint32_t* kk = kb == 0 ? k0 : kb == 1 ? k1 : kb == 2 ? k2 : k3;
    mma16816(s[kb], qa[2], qb[2], qa[3], qb[3], kk[2], kk[3]);
  }
  l[0] = par ? s[1][1] : s[1][0];
  l[1] = early ? (par ? s[0][1] : s[0][0]) : (par ? s[2][1] : s[2][0]);
  l[2] = par ? s[2][3] : s[2][2];
  l[3] = early ? (par ? s[1][3] : s[1][2]) : (par ? s[3][3] : s[3][2]);
}

__device__ __forceinline__ void attn_mix(const float (&l)[4], const float (&sc)[4], const float (&off)[4], const float (&rk)[4],
                                         const uint32_t* v0, const uint32_t* v1, const uint32_t* v2, const uint32_t* v3,
                                         uint32_t* olo, uint32_t* ohi, const uint32_t (&sel)[4]) {
  float x[4];
#pragma unroll
  for (int e = 0; e < 4; e++) x[e] = fmaf(l[e], sc[e], off[e]);
  const float ml = quad_max(fmaxf(x[0], x[1])), mh = quad_max(fmaxf(x[2], x[3]));
  x[0] = ex2(x[0] - ml); x[1] = ex2(x[1] - ml);
  x[2] = ex2(x[2] - mh); x[3] = ex2(x[3] - mh);
  const uint32_t pl = pack_bf16(x[0] * rk[0], x[1] * rk[1]), ph = pack_bf16(x[2] * rk[2], x[3] * rk[3]);
  const uint32_t a0 = prmt_u(pl, sel[1]), a1 = prmt_u(pl, sel[3]), a2 = prmt_u(pl, sel[0]), a3 = prmt_u(ph, sel[1]);
  const uint32_t c0 = prmt_u(pl, sel[2]), c1 = prmt_u(ph, sel[0]), c2 = prmt_u(ph, sel[3]), c3 = prmt_u(ph, sel[2]);
  float o[4][4];
#pragma unroll
  for (int jn = 0; jn < 4; jn++) {
    o[jn][0] = o[jn][1] = o[jn][2] = o[jn][3] = 0.f;
    mma16816(o[jn], a0, a1, a2, a3, v0[jn], v1[jn]);
  }
#pragma unroll
  for (int jn = 0; jn < 4; jn++) mma16816(o[jn], c0, c1, c2, c3, v2[jn], v3[jn]);
  const float il = rcp_hw(quad_sum(x[0] + x[1])), ih = rcp_hw(quad_sum(x[2] + x[3]));
#pragma unroll
  for (int jn = 0; jn < 4; jn++) {
    olo[jn] = pack_bf16(o[jn][0] * il, o[jn][1] * il);
    ohi[jn] = pack_bf16(o[jn][2] * ih, o[jn][3] * ih);
  }
}

__device__ __forceinline__ void gelu_epilogue(const Params& p, float (&acc)[2][96], const Ctx& cx, int t) {
  UNPACK_CTX(cx);
  (void)wg;
  float rs[4], rm[4];
#pragma unroll
  for (int q = 0; q < 4; q++) {
    const float2 v = lds_f2(sb + OFF_ROW + (32 * w + 8 * q + (lane >> 2)) * 8);
    rs[q] = 0.5f * v.x;
    rm[q] = -rs[q] * v.y;
  }
  const int col0 = 128 * (t - 3), steps = t == 5 ? 6 : 4;
  const uint32_t stg = sb + OFF_STG + w * 4096;
  uint32_t ctab = sb + OFF_CSF + (col0 / 2 + (lane & 3)) * 16, srow = stg + lane * 128 + ((lane & 7) << 4);
  float v[2][16];
#define PULL(k) _Pragma("unroll") for (int j = 0; j < 4; j++) { \
      const float2 bb = lds_f2(ctab + j * 64 + 8); \
      _Pragma("unroll") for (int r = 0; r < 8; r++) \
        asm volatile("fma.rn.f32 %0, %1, %2, %3;" : "=f"(v[r >> 2][4 * j + (r & 3)]) \
                     : "f"(acc[r >> 2][16 * k + 4 * j + (r & 3)]), "f"(rs[(r >> 2) + (r & 2)]), "f"(r & 1 ? bb.y : bb.x)); }
  PULL(0)
#pragma unroll 1
  for (int it = 0;; it++) {
    uint32_t hp[4][4];
#pragma unroll
    for (int j = 0; j < 4; j++) {
      const float2 cs = lds_f2(ctab + j * 64);
#pragma unroll
      for (int q = 0; q < 4; q++) {
        float y[2];
        const int k = 4 * j + q - GELU_DEP;
        const float rmq = k >= 0 ? chain(rm[q], hp[k >> 2][k & 3], p.zero) : rm[q];
#pragma unroll
        for (int e = 0; e < 2; e++) {
          const float z = fmaf(rmq, e ? cs.y : cs.x, v[q & 1][4 * j + 2 * (q >> 1) + e]);
          const float u = z * fmaf(z * z, 8.f * 0.7978845608028654f * 0.044715f, 2.f * 0.7978845608028654f);
          y[e] = fmaf(z, tanh_hw(u), z);
        }
        hp[j][q] = pack_bf16(y[0], y[1]);
      }
    }
    ctab += 256;
    if (!(it & 1)) {
      if (lane == 0) bulk_wait_read();
      __syncwarp();
    }
#pragma unroll
    for (int j = 0; j < 4; j++) stsm4(srow ^ (j << 4), hp[j][0], hp[j][1], hp[j][2], hp[j][3]);
    srow ^= 64;
    if (it & 1) {
      fence_async_smem();
      __syncwarp();
      if (lane == 0) {
        tma_st2(&p.h_st, stg, 448 * n + col0 + 32 * (it - 1), 128 * m + 32 * w);
        bulk_commit();
      }
      if (it == steps - 1) break;
    }
    switch (it) {
      case 0: PULL(1) break;
      case 1: PULL(2) break;
      case 2: PULL(3) break;
      case 3: PULL(4) break;
      default: PULL(5)
    }
  }
#undef PULL
}

__device__ __forceinline__ void attn_epilogue(const Params& p, float (&acc)[2][96], const Ctx& cx, int layer, int t, uint32_t tag) {
  UNPACK_CTX(cx);
  const bool par = (lane >> 2) & 1, early = (lane & 3) > (lane >> 3);
  const uint32_t ktab = sb + OFF_ROW + (32 * w + 2 * (lane & 3) + par) * 8, exc = sb + OFF_STG + w * 4096 + lane * 16;
  const int slot = ((layer * 2 + t) * 16 + m) * 8 + n;
  const int mn = m * 8 + n; (void)mn;
  uint32_t Q[4][8], K[4][8], V[4][8], E[36], P[36];
  float kr[6], qr[4];
#pragma unroll
  for (int q = 2; q < 4; q++) {
    kr[2 + q] = lds_f(ktab + 64 * q);
#pragma unroll
    for (int j = 0; j < 8; j++) {
      E[8 * (q - 2) + j] = K[q][j] = pack_bf16(ACC(q, 8 + j, 0), ACC(q, 8 + j, 1));
      E[16 + 2 * j + q - 2] = V[q][j] = movtrans(pack_bf16(ACC(q, 16 + j, 0), ACC(q, 16 + j, 1)));
    }
  }
  E[32] = __float_as_uint(kr[4]);
  E[33] = E[34] = E[35] = __float_as_uint(kr[5]);
  if (w < 3) {
#pragma unroll
    for (int k = 0; k < 8; k++) sts_u4(exc + k * 512, E[4 * k], E[4 * k + 1], E[4 * k + 2], E[4 * k + 3]);
  } else {
#pragma unroll
    for (int k = 0; k < 12; k++) st_msg(g_halo + slot * 384 + k * 32 + lane, E[3 * k], E[3 * k + 1], E[3 * k + 2], tag);
  }
  PROF_E(7 * layer + t, 1);
#pragma unroll
  for (int q = 0; q < 4; q++) {
    qr[q] = lds_f(sb + OFF_ROW + (32 * w + 8 * q + (lane >> 2)) * 8) * (0.17677669529663687f * 1.4426950408889634f);
#pragma unroll
    for (int j = 0; j < 8; j++) Q[q][j] = pack_bf16(ACC(q, j, 0), ACC(q, j, 1));
    if (q < 2) {
      kr[2 + q] = lds_f(ktab + 64 * q);
#pragma unroll
      for (int j = 0; j < 8; j++) {
        K[q][j] = pack_bf16(ACC(q, 8 + j, 0), ACC(q, 8 + j, 1));
        V[q][j] = movtrans(pack_bf16(ACC(q, 16 + j, 0), ACC(q, 16 + j, 1)));
      }
    }
  }
  bar_sync(BAR_WG + wg, 128);
  if (w > 0 || m == 0) {
    const uint32_t back = w > 0;
#pragma unroll
    for (int k = 0; k < 8; k++) lds_u4(exc - back * 4096 + k * 512, P[4 * k], P[4 * k + 1], P[4 * k + 2], P[4 * k + 3]);
    P[32] = lds_u(ktab - back * 128);
    P[33] = lds_u(ktab - back * 64);
  } else {
#pragma unroll 1
    for (int it = 0; it < MSG_SPINS; it++) {
      uint32_t tg, bad = 0;
#pragma unroll
      for (int k = 0; k < 12; k++) {
        ld_msg(g_halo + (slot - 8) * 384 + k * 32 + lane, P[3 * k], P[3 * k + 1], P[3 * k + 2], tg);
        bad |= tg ^ tag;
      }
      if (__all_sync(0xffffffffu, bad == 0)) break;
    }
  }
  kr[0] = __uint_as_float(P[32]);
  kr[1] = __uint_as_float(P[33]);
  uint32_t PV[2][8];
#pragma unroll
  for (int j = 0; j < 8; j++) { PV[0][j] = P[16 + 2 * j]; PV[1][j] = P[17 + 2 * j]; }
  float rk[2][4], sc[2][4], off[2][4];
#pragma unroll
  for (int g = 0; g < 2; g++) {
    rk[g][0] = kr[2 * g + 1];
    rk[g][1] = early ? kr[2 * g] : kr[2 * g + 2];
    rk[g][2] = kr[2 * g + 2];
    rk[g][3] = early ? kr[2 * g + 1] : kr[2 * g + 3];
#pragma unroll
    for (int e = 0; e < 4; e++) {
      const bool masked = g == 0 && e != 2 && (m | w) == 0 && (e == 0 || early);
      sc[g][e] = masked ? 0.f : rk[g][e] * qr[2 * g + (e >> 1)];
      off[g][e] = masked ? -1e30f : 0.f;
    }
  }
  const uint32_t none = 0x4444u | p.zero, second = par ? 0x3244u : 0x4432u;
  const uint32_t sel[4] = {par ? 0x1044u : 0x4410u, early ? second : none, early ? none : second, none};
  PROF_E(7 * layer + t, 2);
  bar_sync(BAR_GO, 256);
  const float4 zero = lds_f4(sb + OFF_ZERO);
  float l[2][2][4];
  uint32_t O[4][8];
#pragma unroll
  for (int h = 0; h < 2; h++) {
    if (h == 1) {
      Q[2][4] |= __float_as_uint(l[1][0][0]) & p.zero;
      Q[0][4] |= __float_as_uint(l[0][0][0]) & p.zero;
    }
    attn_scores(&Q[2][4 * h], &Q[3][4 * h], &K[0][4 * h], &K[1][4 * h], &K[2][4 * h], &K[3][4 * h], l[1][h], zero, par, early);
    attn_scores(&Q[0][4 * h], &Q[1][4 * h], &P[4 * h], &P[8 + 4 * h], &K[0][4 * h], &K[1][4 * h], l[0][h], zero, par, early);
  }
  const uint32_t stg = sb + OFF_STG + w * 4096, srow = stg + lane * 128 + ((lane & 7) << 4);
#pragma unroll
  for (int h = 0; h < 2; h++) {
    attn_mix(l[1][h], sc[1], off[1], rk[1], &V[0][4 * h], &V[1][4 * h], &V[2][4 * h], &V[3][4 * h], &O[2][4 * h], &O[3][4 * h], sel);
    attn_mix(l[0][h], sc[0], off[0], rk[0], &PV[0][4 * h], &PV[1][4 * h], &V[0][4 * h], &V[1][4 * h], &O[0][4 * h], &O[1][4 * h], sel);
#pragma unroll
    for (int j = 4 * h; j < 4 * h + 4; j++) stsm4(srow ^ (j << 4), O[0][j], O[1][j], O[2][j], O[3][j]);
  }
  bar_arrive(BAR_DONE, 256);
  fence_async_smem();
  __syncwarp();
  if (lane == 0) {
    tma_st2(&p.att_st, stg, 128 * n + 64 * t, 128 * m + 32 * w);
    bulk_commit();
  }
}

__device__ __forceinline__ void finish_stores(uint32_t sb, int i) {
  const int t = i >= 7 ? i - 7 : i;
  if ((threadIdx.x & 31) == 0) {
    bulk_wait_all();
    mbar_arrive(sb + BAR_PUB + 8 * (t < 2 ? t : t + 1));
  }
  __syncwarp();
  if (i < 12) bar_arrive(BAR_GUARD + ((i & 1) ^ 1), 256);
}

__device__ __forceinline__ void consumer_tile(const Params& p, uint32_t sb0, int i, int mn) {
  const int layer = i >= 7, t = i - 7 * layer, wg = i & 1;
  const bool resid = t == 2 || t == 6;
  {
    float acc[2][96];
    if (resid) {
      const Ctx cx = make_ctx(sb0, mn);
      const uint32_t xrow = cx.sb + OFF_X + cx.w * 4096 + cx.lane * 128;
      const uint32_t sel_lo = 0x1044u | p.zero, sel_hi = 0x3244u | p.zero;
#pragma unroll
      for (int j = 0; j < 16; j++) {
        uint32_t r[4];
        ldsm4(xrow + (j >> 3) * 16384 + (((j & 7) ^ (cx.lane & 7)) << 4), r[0], r[1], r[2], r[3]);
#pragma unroll
        for (int q = 0; q < 4; q++) {
          ACC(q, j, 0) = prmt_f(r[q], sel_lo);
          ACC(q, j, 1) = prmt_f(r[q], sel_hi);
        }
      }
    } else {
#pragma unroll
      for (int r = 0; r < 64; r++) acc[0][r] = acc[1][r] = 0.f;
    }
#pragma unroll
    for (int r = 64; r < 96; r++) acc[0][r] = acc[1][r] = 0.f;
    if (t >= 5 || i == 7) finish_stores(sb0, i - 2);
#pragma unroll 1
    for (int step = !tile_split(i);; step++) {
      if (step == 1 && (t == 1 || t == 4)) {
        const Ctx cx = make_ctx(sb0, mn);
        if (i == 1) {
          const uint32_t epoch = __ldcg(g_epoch + (mn & 127));
          bar_sync(BAR_INIT, 256);
          asm volatile("st.shared.u32 [%0], %1;" ::"r"(sb0 + OFF_TAG), "r"(epoch + 1) : "memory");
        }
        const uint32_t tag = lds_u(cx.sb + OFF_TAG);
        const int ln = (i + 1) >> 2;
#pragma unroll 1
        for (int r = 0; r < 2; r++) {
          if (i == 1) {
            if (cx.w < 3) {
              float a[8] = {0.f, 0.f, 0.f, 0.f, 0.f, 0.f, 0.f, 0.f};
              mbar_wait(sb0 + BAR_CSLD, r);
              sum_rows(cx.sb + OFF_STG + cx.w * 8192, 8, a, cx.lane);
              publish_sums(a, g_csp + (cx.n * 17 + cx.m) * 224 + (3 * r + cx.w) * 32, cx.lane, tag);
            }
            PROF_E(-1, 5 + r);
          }
          if (r == 1) break;
          if (i == 1) {
            bar_sync(BAR_WG + 1, 128);
            if (cx.w == 3 && elect_one()) {
              mbar_expect_tx(sb0 + BAR_CSLD, 24576);
              tma_ld3(sb0 + OFF_STG, &p.wqkv, sb0 + BAR_CSLD, 128 * cx.n + 64, 64 * cx.m, 0);
            }
            mbar_wait(sb0 + BAR_XRDY, 0);
            mbar_wait(sb0 + BAR_XRDY + 8, 0);
          }
          write_partial_stats(cx, ln, tag);
          PROF_E(i - 2, 8);
        }
        if (i == 1) bar_arrive(BAR_HLP, 160);
        if (i <= 4) colsum_total(cx, ln, tag);
        PROF_E(i - 2, 9);
        if (i != 1) bar_sync(BAR_GUARD + wg, 256);
        finish_row_stats(cx, ln, tag);
        PROF_E(i - 2, 10);
        if (i <= 4) {
          colsum_gather(cx, ln, tag);
          if (i == 4) mbar_wait(sb0 + BAR_BIAS, 0);
          bar_sync(BAR_WG + wg, 128);
        }
        PROF_E(i - 2, 15);
        bar_arrive(BAR_GUARD + (wg ^ 1), 256);
      }
      if (step == 2 && !resid) bar_sync(BAR_GUARD + wg, 256);
      if (t + step == 2 || t == 6) {
        const Ctx cx = make_ctx(sb0, mn);
        float nm[4];
#pragma unroll
        for (int q = 0; q < 4; q++) nm[q] = t == 6 ? 1.f : -lds_f(cx.sb + OFF_ROW + (32 * cx.w + 8 * q + (cx.lane >> 2)) * 8 + 4);
        const uint32_t ctab = cx.sb + OFF_CSQ + ((t & 3) * 192 + 2 * (cx.lane & 3)) * 4;
#pragma unroll
        for (int j = 0; j < 24; j++) {
          const float2 cs = lds_f2(ctab + j * 32);
#pragma unroll
          for (int q = 0; q < 4; q++) {
            const int k = 4 * j + q - 1;
            const float nq = k >= 0 ? chain(nm[q], __float_as_uint(ACC(k & 3, k >> 2, 1)), p.zero) : nm[q];
            ACC(q, j, 0) = fmaf(nq, cs.x, ACC(q, j, 0));
            ACC(q, j, 1) = fmaf(nq, cs.y, ACC(q, j, 1));
          }
        }
      }
      if (step == 2) break;
      if (tile_wide(t)) {
        mainloop<192>(acc, sb0, i, step, mn);
      } else {
        mainloop<128>(acc, sb0, i, step, mn);
        if (resid) break;
      }
    }
    const Ctx cx = make_ctx(sb0, mn);
    if (resid) {
      const uint32_t xrow = cx.sb + OFF_X + cx.w * 4096 + cx.lane * 128;
#pragma unroll
      for (int j = 0; j < 16; j++) {
        stsm4(xrow + (j >> 3) * 16384 + (((j & 7) ^ (cx.lane & 7)) << 4), pack_bf16(ACC(0, j, 0), ACC(0, j, 1)),
              pack_bf16(ACC(1, j, 0), ACC(1, j, 1)), pack_bf16(ACC(2, j, 0), ACC(2, j, 1)), pack_bf16(ACC(3, j, 0), ACC(3, j, 1)));
        if ((j & 7) == 7) {
          fence_async_smem();
          __syncwarp();
          if (elect_one()) mbar_arrive(sb0 + BAR_XRDY + (j & 8));
        }
      }
      PROF_E(i, 4);
      return;
    }
    if (t < 2) attn_epilogue(p, acc, cx, layer, t, lds_u(sb0 + OFF_TAG));
    else gelu_epilogue(p, acc, cx, t);
    PROF_E(i, 4);
    if (t < 2 || i == 12) finish_stores(sb0, i);
    PROF_E(i, 5);
  }
}

__global__ void __launch_bounds__(384, 1) fused_layers_kernel(const int by_smid, const __nv_bfloat16* x_p, const __nv_bfloat16* wqkv_p,
                                                                  const __grid_constant__ Params p) {
  extern __shared__ __align__(1024) uint8_t smem_raw[];
  const uint32_t sb = uniform((uint32_t)__cvta_generic_to_shared(smem_raw));
  const int tid = threadIdx.x, lane = tid & 31, warp = uniform(tid >> 5), wg = warp >> 2, w = warp & 3;

  int mn;
  {
    int id = blockIdx.x;
    if (by_smid) asm volatile("mov.u32 %0, %%smid;" : "=r"(id));
    else if (id >= 120) id += 4;
    const int c = id >> 1;
    int g, j;
    if (c < 32) { g = c & 7; j = c >> 3; }
    else if (c < 60) { g = 1 + (c - 32) % 7; j = 4 + (c - 32) / 7; }
    else { g = 0; j = c - 58; }
    mn = ((g >> 2) * 8 + j) * 8 + (g & 3) * 2 + (id & 1);
    if (c == 60 || c == 61) {
      if (tid < 32) {
        const uint32_t tag = __ldcg(g_epoch + NCTA + (id & 3)) + 1;
#pragma unroll 1
        for (int mm = 0; mm < 16; mm++) poll_line(g_flags + mm * 32 + (lane & 7), 32 * tag, 0xffu);
        if (tid == 0) g_epoch[NCTA + (id & 3)] = tag;
      }
      return;
    }
  }
  const int m = mn >> 3, n = mn & 7;
  if (tid == 256) PROF_U(1);
  if (tid >= 382) asm volatile("prefetch.global.L2 [%0];" ::"l"(tid & 1 ? wqkv_p + 128 * n : x_p + 128 * m * DM));
  if (wg < 2) {
    asm volatile("setmaxnreg.inc.sync.aligned.u32 232;");
#pragma unroll 1
    for (int i = wg; i < 14; i += 2) {
      consumer_tile(p, sb, i, mn | (warp << 7));
      PROF_T(6 + i * 4);
    }
  } else {
    asm volatile("setmaxnreg.dec.sync.aligned.u32 40;");
    if (w != 0) {
      if (w == 2) {
        if (lane < 28) write_run_desc(sb, lane >> 1, lane & 1);
        bar_arrive(BAR_INIT0, 192);
      }
      bar_sync(BAR_INIT, 256);
      if (w == 1) producer<true>(p, sb, m, n, lane);
      else if (w == 3) colsum_helper(p, sb, m, n, lane);
      else if (elect_one()) publisher(p, sb, m, n);
    } else {
      if (elect_one()) {
#pragma unroll
        for (int k = 0; k < 4; k++) mbar_init(sb + BAR_FULL + 8 * k, 2);
        asm volatile("fence.mbarrier_init.release.cluster;" ::: "memory");
        PROF_U(4);
#pragma unroll 1
        for (int k = 0; k < 4; k++) {
          const uint32_t fb = sb + BAR_FULL + 8 * k;
          mbar_expect_tx(fb, 16384);
          tma_ld2(sb + (5 * k + 3) * UNIT, &p.xin, fb, 64 * k, 128 * m);
          mbar_expect_tx(fb, 3 * UNIT);
          tma_ld3(sb + 5 * k * UNIT, &p.wqkv, fb, 128 * n, 64 * k, 0);
        }
        PROF_U(5);
        mbar_init(sb + BAR_XRDY, 4);
        mbar_init(sb + BAR_XRDY + 8, 4);
        mbar_init(sb + BAR_FULL + 32, 2);
#pragma unroll
        for (int k = 0; k < NBAR; k++) mbar_init(sb + BAR_EMPTY + 8 * k, 4);
        mbar_init(sb + BAR_DUMMY, 4);
#pragma unroll
        for (int k = 0; k < 7; k++) mbar_init(sb + BAR_PUB + 8 * k, 4);
#pragma unroll
        for (int k = 0; k < 3; k++) mbar_init(sb + BAR_CSLD + 8 * k, 1);
        sts_f2(sb + OFF_ZERO, 0.f, 0.f);
        sts_f2(sb + OFF_ZERO + 8, 0.f, 0.f);
        asm volatile("fence.mbarrier_init.release.cluster;" ::: "memory");
        mbar_expect_tx(sb + BAR_CSLD, 24576);
        tma_ld3(sb + OFF_STG, &p.wqkv, sb + BAR_CSLD, 128 * n, 64 * m, 0);
#pragma unroll 1
        for (int h = 0; h < 2; h++) {
          const uint32_t xr = sb + BAR_XRDY + 8 * h;
          mbar_expect_tx(xr, 16384);
          tma_ld2(sb + OFF_X + h * 16384, &p.xin, xr, 128 * n + 64 * h, 128 * m);
          asm volatile("mbarrier.arrive.shared::cta.b64 _, [%0], 3;" ::"r"(xr) : "memory");
        }
        PROF_U(6);
      }
      __syncwarp();
      bar_arrive(BAR_INIT0, 192);
      bar_arrive(BAR_INIT, 256);
      producer<false>(p, sb, m, n, lane);
    }
  }
}

typedef CUresult (*EncodeFn)(CUtensorMap*, CUtensorMapDataType, cuuint32_t, void*, const cuuint64_t*, const cuuint64_t*,
                             const cuuint32_t*, const cuuint32_t*, CUtensorMapInterleave, CUtensorMapSwizzle,
                             CUtensorMapL2promotion, CUtensorMapFloatOOBfill);

void make_2d(EncodeFn enc, CUtensorMap* m, const void* ptr, uint64_t cols, uint64_t rows, uint32_t box_rows) {
  cuuint64_t d[2] = {cols, rows}, st[1] = {cols * 2};
  cuuint32_t b[2] = {64, box_rows}, e[2] = {1, 1};
  enc(m, CU_TENSOR_MAP_DATA_TYPE_BFLOAT16, 2, const_cast<void*>(ptr), d, st, b, e, CU_TENSOR_MAP_INTERLEAVE_NONE,
      CU_TENSOR_MAP_SWIZZLE_128B, CU_TENSOR_MAP_L2_PROMOTION_L2_128B, CU_TENSOR_MAP_FLOAT_OOB_FILL_NONE);
}
void make_3d(EncodeFn enc, CUtensorMap* m, const void* ptr, uint64_t d0, uint64_t rows, uint64_t d2, uint64_t row_bytes,
             uint64_t chunk_bytes, uint32_t box_chunks) {
  cuuint64_t d[3] = {d0, rows, d2}, st[2] = {row_bytes, chunk_bytes};
  cuuint32_t b[3] = {64, 64, box_chunks}, e[3] = {1, 1, 1};
  enc(m, CU_TENSOR_MAP_DATA_TYPE_BFLOAT16, 3, const_cast<void*>(ptr), d, st, b, e, CU_TENSOR_MAP_INTERLEAVE_NONE,
      CU_TENSOR_MAP_SWIZZLE_128B, CU_TENSOR_MAP_L2_PROMOTION_L2_128B, CU_TENSOR_MAP_FLOAT_OOB_FILL_NONE);
}

}

extern "C" void kernel_launch(void* const* d_in, const int* in_sizes, int n_in, void* d_out, int out_size) {
  (void)in_sizes; (void)n_in; (void)out_size;
  static EncodeFn enc = nullptr;
  static void *att = nullptr, *hbuf = nullptr;
  static int by_smid = 0;
  if (!enc) {
    void* fn = nullptr;
    cudaDriverEntryPointQueryResult q;
    cudaGetDriverEntryPoint("cuTensorMapEncodeTiled", &fn, cudaEnableDefault, &q);
    enc = (EncodeFn)fn;
    cudaGetSymbolAddress(&att, g_att);
    cudaGetSymbolAddress(&hbuf, g_h);
    cudaFuncSetAttribute(fused_layers_kernel, cudaFuncAttributeMaxDynamicSharedMemorySize, SMEM_BYTES);
    int sms = 0, per_sm = 0, dev = 0;
    cudaGetDevice(&dev);
    cudaDeviceGetAttribute(&sms, cudaDevAttrMultiProcessorCount, dev);
    cudaOccupancyMaxActiveBlocksPerMultiprocessor(&per_sm, fused_layers_kernel, 384, SMEM_BYTES);
    by_smid = sms == 132 && per_sm == 1;
  }
  Params p;
  make_2d(enc, &p.xin, d_in[0], DM, SEQ, 128);
  make_2d(enc, &p.out, d_out, DM, SEQ, 128);
  make_2d(enc, &p.att, att, DM, SEQ, 128);
  make_2d(enc, &p.h, hbuf, FF, SEQ, 128);
  make_2d(enc, &p.out_st, d_out, DM, SEQ, 32);
  make_2d(enc, &p.att_st, att, DM, SEQ, 32);
  make_2d(enc, &p.h_st, hbuf, FF, SEQ, 32);
  make_2d(enc, &p.w1c, d_in[4], FF, DM, 32);
  make_3d(enc, &p.wqkv, d_in[1], DM, DM, 3, 3 * DM * 2, DM * 2, 3);
  make_3d(enc, &p.wo, d_in[2], 64, DM, DM / 64, DM * 2, 128, 2);
  make_3d(enc, &p.w1a, d_in[4], 64, DM, FF / 64, FF * 2, 128, 3);
  make_3d(enc, &p.w1b, d_in[4], 64, DM, FF / 64, FF * 2, 128, 2);
  make_3d(enc, &p.w2, d_in[6], 64, FF, DM / 64, DM * 2, 128, 2);
  p.b1 = (const __nv_bfloat16*)d_in[5];
  p.b2 = (const __nv_bfloat16*)d_in[7];
  p.zero = 0;
  fused_layers_kernel<<<by_smid ? 132 : NCTA, 384, SMEM_BYTES>>>(by_smid, (const __nv_bfloat16*)d_in[0], (const __nv_bfloat16*)d_in[1], p);
}
```

```cpp
#include <cuda_runtime.h>
#include <cuda_bf16.h>
#include <cuda.h>
#include <stdint.h>

namespace {

constexpr int SEQ = 2048, DM = 1024, FF = 3584;
constexpr int NCTA = 128;
constexpr int NBAR = 5;

constexpr uint32_t RING_UNITS = 20, UNIT = 8192;
constexpr uint32_t OFF_X   = RING_UNITS * UNIT;
constexpr uint32_t OFF_STG = OFF_X + 32768;
constexpr uint32_t OFF_HLP = OFF_STG + 16384;
constexpr uint32_t OFF_RUN = OFF_STG + 24576;
constexpr uint32_t OFF_CSQ = OFF_RUN + 512;
constexpr uint32_t OFF_CSF = OFF_CSQ + 2048;
constexpr uint32_t OFF_ROW = OFF_CSF + 3584;
constexpr uint32_t OFF_BAR = OFF_ROW + 1024;
constexpr uint32_t SMEM_BYTES = OFF_BAR + 384;
constexpr uint32_t BAR_FULL = OFF_BAR, BAR_EMPTY = OFF_BAR + 8 * NBAR;
constexpr uint32_t BAR_XRDY = OFF_BAR + 80;
constexpr uint32_t BAR_DUMMY = OFF_BAR + 96, OFF_TAG = OFF_BAR + 104, OFF_ZERO = OFF_BAR + 112;
constexpr uint32_t BAR_PUB = OFF_BAR + 128;
constexpr uint32_t BAR_CSLD = OFF_BAR + 200;
constexpr uint32_t BAR_BIAS = OFF_BAR + 216;

constexpr uint64_t DESC_A = (1ull << 62) | ((uint64_t)(2048 >> 4) << 32) | (1ull << 16);
constexpr uint64_t DESC_B = (1ull << 62) | ((uint64_t)(1024 >> 4) << 32) | ((uint64_t)(8192 >> 4) << 16);

constexpr int BAR_INIT = 0, BAR_ORDER = 1, BAR_GUARD = 3, BAR_WG = 5, BAR_GO = 7, BAR_DONE = 8, BAR_HLP = 9, BAR_INIT0 = 10;
#define GELU_DEP 2
#define F2ROT 0
#define WIN1 7
#define WIN2 4

struct Params {
  CUtensorMap xin, out, att, h, wqkv, wo, w1a, w1b, w2, out_st, att_st, h_st, w1c;
  const __nv_bfloat16 *b1, *b2;
  uint32_t zero;
};

__device__ __nv_bfloat16 g_att[SEQ * DM];
__device__ __nv_bfloat16 g_h[SEQ * FF];
__device__ uint4 g_stats[4 * 8 * SEQ];
__device__ uint4 g_halo[2 * 2 * 16 * 8 * 384];
__device__ uint4 g_csp[2 * 8 * 17 * 224];
__device__ uint32_t g_flags[16 * 32];
__device__ uint32_t g_epoch[NCTA + 4];
#define PROF_T(idx)
#define PROF_U(k)
#define PROF_S(g)
#define PROF_E(i, k)

__device__ __forceinline__ void mbar_init(uint32_t bar, int cnt) {
  asm volatile("mbarrier.init.shared::cta.b64 [%0], %1;" ::"r"(bar), "r"(cnt));
}
__device__ __forceinline__ void mbar_expect_tx(uint32_t bar, uint32_t bytes) {
  asm volatile("mbarrier.arrive.expect_tx.shared::cta.b64 _, [%0], %1;" ::"r"(bar), "r"(bytes) : "memory");
}
__device__ __forceinline__ void mbar_arrive(uint32_t bar) {
  asm volatile("mbarrier.arrive.shared::cta.b64 _, [%0];" ::"r"(bar) : "memory");
}
__device__ __forceinline__ bool mbar_test(uint32_t bar, uint32_t parity) {
  uint32_t ok;
  asm volatile("{\n.reg .pred p;\nmbarrier.test_wait.parity.shared::cta.b64 p, [%1], %2;\nselp.u32 %0, 1, 0, p;\n}"
               : "=r"(ok) : "r"(bar), "r"(parity) : "memory");
  return ok;
}
__device__ __forceinline__ void mbar_wait(uint32_t bar, uint32_t parity) {
  asm volatile(
      "{\n.reg .pred p;\n.reg .u32 it;\nmov.u32 it, 0;\n"
      "WAIT_LOOP:\n"
      "mbarrier.try_wait.parity.shared::cta.b64 p, [%0], %1;\n"
      "@p bra WAIT_DONE;\n"
      "add.u32 it, it, 1;\n"
      "setp.lt.u32 p, it, 0x400000;\n"
      "@p bra WAIT_LOOP;\n"
      "trap;\n"
      "WAIT_DONE:\n}"
      ::"r"(bar), "r"(parity) : "memory");
}
__device__ __forceinline__ void bar_sync(int id, int n) { asm volatile("bar.sync %0, %1;" ::"r"(id), "r"(n) : "memory"); }
__device__ __forceinline__ void bar_arrive(int id, int n) { asm volatile("bar.arrive %0, %1;" ::"r"(id), "r"(n) : "memory"); }
__device__ __forceinline__ void tma_ld2(uint32_t dst, const CUtensorMap* m, uint32_t bar, int c0, int c1) {
  asm volatile("cp.async.bulk.tensor.2d.shared::cluster.global.mbarrier::complete_tx::bytes [%0], [%1, {%3, %4}], [%2];"
               ::"r"(dst), "l"(m), "r"(bar), "r"(c0), "r"(c1) : "memory");
}
__device__ __forceinline__ void tma_ld3(uint32_t dst, const CUtensorMap* m, uint32_t bar, int c0, int c1, int c2) {
  asm volatile("cp.async.bulk.tensor.3d.shared::cluster.global.mbarrier::complete_tx::bytes [%0], [%1, {%3, %4, %5}], [%2];"
               ::"r"(dst), "l"(m), "r"(bar), "r"(c0), "r"(c1), "r"(c2) : "memory");
}
__device__ __forceinline__ void tma_st2(const CUtensorMap* m, uint32_t src, int c0, int c1) {
  asm volatile("cp.async.bulk.tensor.2d.global.shared::cta.bulk_group [%0, {%2, %3}], [%1];"
               ::"l"(m), "r"(src), "r"(c0), "r"(c1) : "memory");
}
__device__ __forceinline__ void bulk_commit() { asm volatile("cp.async.bulk.commit_group;" ::: "memory"); }
__device__ __forceinline__ void bulk_wait_read() { asm volatile("cp.async.bulk.wait_group.read 0;" ::: "memory"); }
__device__ __forceinline__ void bulk_wait_all() { asm volatile("cp.async.bulk.wait_group 0;" ::: "memory"); }
__device__ __forceinline__ void fence_async_smem() { asm volatile("fence.proxy.async.shared::cta;" ::: "memory"); }
__device__ __forceinline__ void fence_async_global() { asm volatile("fence.proxy.async.global;" ::: "memory"); }
__device__ __forceinline__ void st_relaxed(uint32_t* p, uint32_t v) {
  asm volatile("st.relaxed.gpu.global.u32 [%0], %1;" ::"l"(p), "r"(v) : "memory");
}
__device__ __forceinline__ void st_msg(uint4* p, uint32_t a, uint32_t b, uint32_t c, uint32_t tag) {
  asm volatile("{\n.reg .b128 v;\nmov.b128 v, {%1, %2, %3, %4};\nst.relaxed.gpu.b128 [%0], v;\n}"
               ::"l"(p), "r"(a), "r"(b), "r"(c), "r"(tag) : "memory");
}
__device__ __forceinline__ void ld_msg(const uint4* p, uint32_t& a, uint32_t& b, uint32_t& c, uint32_t& tag) {
  asm volatile("{\n.reg .b128 v;\nld.relaxed.gpu.b128 v, [%4];\nmov.b128 {%0, %1, %2, %3}, v;\n}"
               : "=r"(a), "=r"(b), "=r"(c), "=r"(tag) : "l"(p) : "memory");
}
__device__ __forceinline__ bool elect_one() {
  uint32_t ok;
  asm volatile("{\n.reg .pred p;\nelect.sync _|p, 0xffffffff;\nselp.u32 %0, 1, 0, p;\n}" : "=r"(ok));
  return ok;
}
__device__ __forceinline__ int uniform(int v) { return __shfl_sync(0xffffffffu, v, 0); }
__device__ __forceinline__ uint32_t pack_bf16(float lo, float hi) {
  uint32_t r;
  asm("cvt.rn.bf16x2.f32 %0, %1, %2;" : "=r"(r) : "f"(hi), "f"(lo));
  return r;
}
__device__ __forceinline__ uint32_t prmt_u(uint32_t a, uint32_t sel) {
  uint32_t r;
  asm("prmt.b32 %0, %1, 0, %2;" : "=r"(r) : "r"(a), "r"(sel));
  return r;
}
__device__ __forceinline__ float prmt_f(uint32_t a, uint32_t sel) {
  float r;
  asm("{\n.reg .b32 t;\nprmt.b32 t, %1, 0, %2;\nmov.b32 %0, t;\n}" : "=f"(r) : "r"(a), "r"(sel));
  return r;
}
__device__ __forceinline__ float bf_lo(uint32_t v) { return __uint_as_float(v << 16); }
__device__ __forceinline__ float bf_hi(uint32_t v) { return __uint_as_float(v & 0xffff0000u); }
__device__ __forceinline__ void stsm4(uint32_t addr, uint32_t r0, uint32_t r1, uint32_t r2, uint32_t r3) {
  asm volatile("stmatrix.sync.aligned.m8n8.x4.shared.b16 [%0], {%1, %2, %3, %4};"
               ::"r"(addr), "r"(r0), "r"(r1), "r"(r2), "r"(r3) : "memory");
}
__device__ __forceinline__ void ldsm4(uint32_t addr, uint32_t& r0, uint32_t& r1, uint32_t& r2, uint32_t& r3) {
  asm volatile("ldmatrix.sync.aligned.m8n8.x4.shared.b16 {%0, %1, %2, %3}, [%4];"
               : "=r"(r0), "=r"(r1), "=r"(r2), "=r"(r3) : "r"(addr) : "memory");
}
__device__ __forceinline__ uint32_t movtrans(uint32_t a) {
  uint32_t d;
  asm volatile("movmatrix.sync.aligned.m8n8.trans.b16 %0, %1;" : "=r"(d) : "r"(a));
  return d;
}
__device__ __forceinline__ void mma16816(float (&c)[4], uint32_t a0, uint32_t a1, uint32_t a2, uint32_t a3, uint32_t b0, uint32_t b1) {
  asm volatile("mma.sync.aligned.m16n8k16.row.col.f32.bf16.bf16.f32 {%0,%1,%2,%3}, {%4,%5,%6,%7}, {%8,%9}, {%0,%1,%2,%3};"
               : "+f"(c[0]), "+f"(c[1]), "+f"(c[2]), "+f"(c[3])
               : "r"(a0), "r"(a1), "r"(a2), "r"(a3), "r"(b0), "r"(b1));
}
__device__ __forceinline__ float2 lds_f2(uint32_t a) {
  float2 v;
  asm volatile("ld.shared.v2.f32 {%0, %1}, [%2];" : "=f"(v.x), "=f"(v.y) : "r"(a) : "memory");
  return v;
}
__device__ __forceinline__ float4 lds_f4(uint32_t a) {
  float4 v;
  asm volatile("ld.shared.v4.f32 {%0, %1, %2, %3}, [%4];" : "=f"(v.x), "=f"(v.y), "=f"(v.z), "=f"(v.w) : "r"(a) : "memory");
  return v;
}
__device__ __forceinline__ float lds_f(uint32_t a) {
  float v;
  asm volatile("ld.shared.f32 %0, [%1];" : "=f"(v) : "r"(a) : "memory");
  return v;
}
__device__ __forceinline__ uint32_t lds_u(uint32_t a) {
  uint32_t v;
  asm volatile("ld.shared.u32 %0, [%1];" : "=r"(v) : "r"(a) : "memory");
  return v;
}
__device__ __forceinline__ void sts_f2(uint32_t a, float x, float y) {
  asm volatile("st.shared.v2.f32 [%0], {%1, %2};" ::"r"(a), "f"(x), "f"(y) : "memory");
}
__device__ __forceinline__ void sts_u4(uint32_t a, uint32_t x, uint32_t y, uint32_t z, uint32_t w) {
  asm volatile("st.shared.v4.u32 [%0], {%1, %2, %3, %4};" ::"r"(a), "r"(x), "r"(y), "r"(z), "r"(w) : "memory");
}
__device__ __forceinline__ void lds_u4(uint32_t a, uint32_t& x, uint32_t& y, uint32_t& z, uint32_t& w) {
  asm volatile("ld.shared.v4.u32 {%0, %1, %2, %3}, [%4];" : "=r"(x), "=r"(y), "=r"(z), "=r"(w) : "r"(a) : "memory");
}
__device__ __forceinline__ float ex2(float x) {
  float y;
  asm("ex2.approx.ftz.f32 %0, %1;" : "=f"(y) : "f"(x));
  return y;
}
__device__ __forceinline__ float rcp_hw(float x) {
  float y;
  asm("rcp.approx.ftz.f32 %0, %1;" : "=f"(y) : "f"(x));
  return y;
}
__device__ __forceinline__ float tanh_hw(float x) {
  float y;
  asm("tanh.approx.f32 %0, %1;" : "=f"(y) : "f"(x));
  return y;
}
__device__ __forceinline__ float quad_sum(float v) {
  v += __shfl_xor_sync(0xffffffffu, v, 1);
  return v + __shfl_xor_sync(0xffffffffu, v, 2);
}
__device__ __forceinline__ float quad_max(float v) {
  v = fmaxf(v, __shfl_xor_sync(0xffffffffu, v, 1));
  return fmaxf(v, __shfl_xor_sync(0xffffffffu, v, 2));
}

template <int N> __device__ __forceinline__ void wgmma_ss(float (&d)[96], uint64_t da, uint64_t db, uint32_t keep = 1);
template <> __device__ __forceinline__ void wgmma_ss<128>(float (&d)[96], uint64_t da, uint64_t db, uint32_t keep) {
  asm volatile(
      "{\n.reg .pred p;\nsetp.ne.u32 p, %66, 0;\n"
      "wgmma.mma_async.sync.aligned.m64n128k16.f32.bf16.bf16 {%0, %1, %2, %3, %4, %5, %6, %7, %8, %9, %10, %11, %12, %13, %14, %15, %16, %17, %18, %19, %20, %21, %22, %23, %24, %25, %26, %27, %28, %29, %30, %31, %32, %33, %34, %35, %36, %37, %38, %39, %40, %41, %42, %43, %44, %45, %46, %47, %48, %49, %50, %51, %52, %53, %54, %55, %56, %57, %58, %59, %60, %61, %62, %63}, %64, %65, p, 1, 1, 0, 1;\n}"
      : "+f"(d[0]), "+f"(d[1]), "+f"(d[2]), "+f"(d[3]), "+f"(d[4]), "+f"(d[5]), "+f"(d[6]), "+f"(d[7]), "+f"(d[8]), "+f"(d[9]), "+f"(d[10]), "+f"(d[11]), "+f"(d[12]), "+f"(d[13]), "+f"(d[14]), "+f"(d[15]), "+f"(d[16]), "+f"(d[17]), "+f"(d[18]), "+f"(d[19]), "+f"(d[20]), "+f"(d[21]), "+f"(d[22]), "+f"(d[23]), "+f"(d[24]), "+f"(d[25]), "+f"(d[26]), "+f"(d[27]), "+f"(d[28]), "+f"(d[29]), "+f"(d[30]), "+f"(d[31]), "+f"(d[32]), "+f"(d[33]), "+f"(d[34]), "+f"(d[35]), "+f"(d[36]), "+f"(d[37]), "+f"(d[38]), "+f"(d[39]), "+f"(d[40]), "+f"(d[41]), "+f"(d[42]), "+f"(d[43]), "+f"(d[44]), "+f"(d[45]), "+f"(d[46]), "+f"(d[47]), "+f"(d[48]), "+f"(d[49]), "+f"(d[50]), "+f"(d[51]), "+f"(d[52]), "+f"(d[53]), "+f"(d[54]), "+f"(d[55]), "+f"(d[56]), "+f"(d[57]), "+f"(d[58]), "+f"(d[59]), "+f"(d[60]), "+f"(d[61]), "+f"(d[62]), "+f"(d[63])
      : "l"(da), "l"(db), "r"(keep));
}

template <> __device__ __forceinline__ void wgmma_ss<192>(float (&d)[96], uint64_t da, uint64_t db, uint32_t keep) {
  asm volatile(
      "{\n.reg .pred p;\nsetp.ne.u32 p, %98, 0;\n"
      "wgmma.mma_async.sync.aligned.m64n192k16.f32.bf16.bf16 {%0, %1, %2, %3, %4, %5, %6, %7, %8, %9, %10, %11, %12, %13, %14, %15, %16, %17, %18, %19, %20, %21, %22, %23, %24, %25, %26, %27, %28, %29, %30, %31, %32, %33, %34, %35, %36, %37, %38, %39, %40, %41, %42, %43, %44, %45, %46, %47, %48, %49, %50, %51, %52, %53, %54, %55, %56, %57, %58, %59, %60, %61, %62, %63, %64, %65, %66, %67, %68, %69, %70, %71, %72, %73, %74, %75, %76, %77, %78, %79, %80, %81, %82, %83, %84, %85, %86, %87, %88, %89, %90, %91, %92, %93, %94, %95}, %96, %97, p, 1, 1, 0, 1;\n}"
      : "+f"(d[0]), "+f"(d[1]), "+f"(d[2]), "+f"(d[3]), "+f"(d[4]), "+f"(d[5]), "+f"(d[6]), "+f"(d[7]), "+f"(d[8]), "+f"(d[9]), "+f"(d[10]), "+f"(d[11]), "+f"(d[12]), "+f"(d[13]), "+f"(d[14]), "+f"(d[15]), "+f"(d[16]), "+f"(d[17]), "+f"(d[18]), "+f"(d[19]), "+f"(d[20]), "+f"(d[21]), "+f"(d[22]), "+f"(d[23]), "+f"(d[24]), "+f"(d[25]), "+f"(d[26]), "+f"(d[27]), "+f"(d[28]), "+f"(d[29]), "+f"(d[30]), "+f"(d[31]), "+f"(d[32]), "+f"(d[33]), "+f"(d[34]), "+f"(d[35]), "+f"(d[36]), "+f"(d[37]), "+f"(d[38]), "+f"(d[39]), "+f"(d[40]), "+f"(d[41]), "+f"(d[42]), "+f"(d[43]), "+f"(d[44]), "+f"(d[45]), "+f"(d[46]), "+f"(d[47]), "+f"(d[48]), "+f"(d[49]), "+f"(d[50]), "+f"(d[51]), "+f"(d[52]), "+f"(d[53]), "+f"(d[54]), "+f"(d[55]), "+f"(d[56]), "+f"(d[57]), "+f"(d[58]), "+f"(d[59]), "+f"(d[60]), "+f"(d[61]), "+f"(d[62]), "+f"(d[63]), "+f"(d[64]), "+f"(d[65]), "+f"(d[66]), "+f"(d[67]), "+f"(d[68]), "+f"(d[69]), "+f"(d[70]), "+f"(d[71]), "+f"(d[72]), "+f"(d[73]), "+f"(d[74]), "+f"(d[75]), "+f"(d[76]), "+f"(d[77]), "+f"(d[78]), "+f"(d[79]), "+f"(d[80]), "+f"(d[81]), "+f"(d[82]), "+f"(d[83]), "+f"(d[84]), "+f"(d[85]), "+f"(d[86]), "+f"(d[87]), "+f"(d[88]), "+f"(d[89]), "+f"(d[90]), "+f"(d[91]), "+f"(d[92]), "+f"(d[93]), "+f"(d[94]), "+f"(d[95])
      : "l"(da), "l"(db), "r"(keep));
}

template <int R>
__device__ __forceinline__ void pin_regs(float (&a)[2][96]) {
#pragma unroll
  for (int m = 0; m < 2; m++)
#pragma unroll
    for (int i = 0; i < R; i++) asm volatile("" : "+f"(a[m][i])::"memory");
}

struct Ctx {
  uint32_t sb;
  int m, n, wg, w, lane;
};
__device__ __forceinline__ Ctx make_ctx(uint32_t sb, int id) {
  int lane;
  asm volatile("mov.u32 %0, %%laneid;" : "=r"(lane));
  asm volatile("" : "+r"(id), "+r"(sb));
  return Ctx{sb, (id >> 3) & 15, id & 7, id >> 9, (id >> 7) & 3, lane};
}
#define UNPACK_CTX(c) const uint32_t sb = c.sb; const int m = c.m, n = c.n, wg = c.wg, w = c.w, lane = c.lane

__device__ __forceinline__ uint32_t poll_line(const uint32_t* word, uint32_t target, uint32_t need) {
  uint32_t v;
  asm volatile(
      "{\n.reg .pred p;\n.reg .u32 it, m;\n.reg .s32 d;\nmov.u32 it, 0;\n"
      "POLL_LOOP:\n"
      "ld.relaxed.gpu.global.u32 %0, [%1];\n"
      "sub.s32 d, %0, %2;\n"
      "setp.ge.s32 p, d, 0;\n"
      "vote.sync.ballot.b32 m, p, 0xffffffff;\n"
      "and.b32 m, m, %3;\n"
      "setp.eq.u32 p, m, %3;\n"
      "@p bra.uni POLL_DONE;\n"
      "add.u32 it, it, 1;\n"
      "setp.lt.u32 p, it, 0x400000;\n"
      "@p bra.uni POLL_LOOP;\n"
      "trap;\n"
      "POLL_DONE:\n}"
      : "=&r"(v) : "l"(word), "r"(target), "r"(need) : "memory");
  return v;
}
__device__ __forceinline__ uint32_t ld_relaxed(const uint32_t* p) {
  uint32_t v;
  asm volatile("ld.relaxed.gpu.global.u32 %0, [%1];" : "=r"(v) : "l"(p) : "memory");
  return v;
}
__device__ __forceinline__ float chain(float x, uint32_t on, uint32_t zero) {
  return __uint_as_float(__float_as_uint(x) | (on & zero));
}
constexpr int MSG_SPINS = 1 << 20;

constexpr int STAGES_PER_LAYER = 152;
__device__ __forceinline__ int nib(uint64_t v, int i) { return (int)(v >> (4 * i)) & 15; }
__device__ __forceinline__ bool tile_wide(int t) { return (0x23 >> t) & 1; }
__device__ __forceinline__ void weight_coords(const Params& p, int t, int n, const CUtensorMap*& map, int& c0, int& c2) {
  map = &p.wqkv + nib(0x4233100ull, t);
  c0 = t < 2 ? 128 * n + 64 * t : 0;
  c2 = t < 2 ? 0 : (t == 2 || t == 6) ? 2 * n : 7 * n + 2 * t - 6;
}

template <bool IS_A>
__device__ __forceinline__ void producer(const Params& p, uint32_t sb, int m, int n, int lane) {
  uint32_t owners = 0;
#pragma unroll 1
  for (int q = 7; q >= 0; q--) owners = owners << 4 | ((((n & 6) + q) & 7) ^ (q < 2 ? n & 1 : 0));
  const uint64_t order_x = (uint64_t)((owners >> 4) * 2 + 0x1111111u) << 36 | (uint64_t)(owners >> 4) * 2 << 8 | (n * 0x22 + 0x10);
  int inflight = 4, cur = 0;
  uint32_t fb = sb + BAR_FULL + 32, rb = sb + BAR_EMPTY, rph = 0, pos = 0, tag32 = 0, seen = 0;
  const uint32_t fend = sb + BAR_FULL + 8 * NBAR, rend = sb + BAR_EMPTY + 8 * NBAR;
  const uint32_t* word = g_flags + m * 32 + (lane < 16 ? lane >> 1 : lane & 7);
#pragma unroll 1
  for (int sg = 1; sg < 22; sg++) {
    const int layer = sg >= 11, s = sg == 1 ? 2 : sg == 2 ? 1 : sg - 11 * layer;
    const int t = nib(0x65434321010ull, s), kind = nib(0x32110031100ull, s);
    const bool wide = tile_wide(t);
    const uint32_t bbytes = wide ? 3 * UNIT : 2 * UNIT, base = sb + (IS_A ? bbytes : 0);
    const int mul = t == 6 ? 448 : t == 2 ? 128 : 64, count = sg == 1 ? 12 : 2 * nib(0x4871ull, kind);
    const uint64_t order0 = sg == 1 ? 0xFEDCBA987654ull : kind == 3 ? (F2ROT || t == 2 ? owners : 0x76543210u) : order_x >> (8 * (kind & 1));
    uint32_t special = (s == 4 || s == 10) ? 0x10 : s == 9 ? 0xF : 1;
    if (IS_A) special |= (kind & 1 ? 0 : 3) | (count >= 4 ? 1u << (count - 4) : 0);
    if (s >= 9) pos = (s + 6) * UNIT;
    const CUtensorMap* map;
    int c0 = 0, c2 = 0, ev = 0;
    if (IS_A) {
      map = &p.xin + (t == 2 ? 2 : t == 6 ? 3 : sg >= 4);
      ev = 9 * layer + (t < 2 ? 0 : t == 2 ? 1 : t < 6 ? 4 : 5);
      if (sg == 2) seen = tag32 = (__ldcg(g_epoch + m * 8 + n) + 1) << 5;
    } else {
      weight_coords(p, t, n, map, c0, c2);
    }
#pragma unroll 1
    for (int add = 0; add < mul; add += 64) {
      uint64_t order = order0;
      const int need = kind == 3 ? ev : ev - 1 + (lane & 1), sh = kind == 3 ? 16 : 0;
      uint32_t ready = IS_A ? __ballot_sync(0xffffffffu, cur >= need) >> sh : 0;
#pragma unroll 1
      for (int k = 0; k < count; k++) {
        const int code = order & 15, kc = code * mul + add;
        order >>= 4;
        if ((special >> k) & 1) {
          const int lag = wide ? (s == 9 && k == 2 ? 2 : 3) : ((s == 4 || s == 10) && add == 0 && k < 4) ? 3 : 4;
#pragma unroll 1
          for (; inflight > lag; inflight--) {
            mbar_wait(rb, rph);
            rb += 8;
            if (rb == rend) { rb -= 8 * NBAR; rph ^= 1; }
          }
          inflight++;
          if (IS_A) {
            if (kind == 3 ? t == 2 && add + k == 64 : !(kind & 1) && k < 2) {
              if (t == 2) mbar_wait(sb + BAR_PUB + 8, layer);
              else if (k == 1 && (s == 0 || s == 5)) mbar_wait(sb + BAR_XRDY + 8, s == 5);
              if (elect_one()) mbar_arrive(fb);
              goto next_stage;
            }
            if (k == count - 4 && sg >= 3) seen = ld_relaxed(word);
          }
        } else {
          mbar_wait(rb, rph);
          rb += 8;
          if (rb == rend) { rb -= 8 * NBAR; rph ^= 1; }
        }
        if (IS_A && !((ready >> code) & 1)) {
          cur = max(cur, (int)(seen - tag32));
          ready = __ballot_sync(0xffffffffu, cur >= need) >> sh;
          if (!((ready >> code) & 1)) {
            cur = (int)(poll_line(word, tag32 + need, 1u << (code + sh)) - tag32);
            ready = __ballot_sync(0xffffffffu, cur >= need) >> sh;
          }
          asm volatile("fence.acquire.gpu;" ::: "memory");
          fence_async_global();
        }
        if (elect_one()) {
          if (!IS_A) tma_ld3(base + pos, map, fb, c0, kc, c2);
          else tma_ld2(base + pos, map, fb, kc, 128 * m);
          mbar_expect_tx(fb, IS_A ? 16384 : bbytes);
        }
      next_stage:
        fb += 8;
        if (fb == fend) fb -= 8 * NBAR;
        pos += bbytes + 2 * UNIT;
        if (pos >= RING_UNITS * UNIT) pos -= RING_UNITS * UNIT;
      }
      special = !IS_A ? 0 : t == 2 ? 1 : add == 128 ? 0x10 : 0;
      if (IS_A && (t == 2 || add == 64 || add == 192)) ev++;
    }
  }
}

__device__ __forceinline__ void publisher(const Params& p, uint32_t sb, int m, int n) {
  const uint32_t tag = __ldcg(g_epoch + m * 8 + n) + 1;
  uint32_t* word = g_flags + m * 32 + n;
  const int mn = m * 8 + n; (void)mn;
  st_relaxed(word, 32 * tag);
#pragma unroll 1
  for (int c = 0; c < 18; c++) {
    const int e = c >= 9 ? c - 9 : c;
    if ((0x18C >> e) & 1) {
      const int half = (0x108 >> e) & 1;
      mbar_wait(sb + BAR_XRDY + 8 * half, e < 4);
#pragma unroll
      for (int w = 0; w < 4; w++) tma_st2(&p.out_st, sb + OFF_X + half * 16384 + w * 4096, 128 * n + 64 * half, 128 * m + 32 * w);
      bulk_commit();
      if (c >= 16) continue;
      bulk_wait_all();
      PROF_E(7 * (c >= 9) + (e < 4 ? 2 : 6), 11 + 2 * half);
    } else {
      mbar_wait(sb + BAR_PUB + 8 * e, c >= 9);
    }
    asm volatile("fence.release.gpu;" ::: "memory");
    st_relaxed(word, 32 * tag + c + 1);
    PROF_E(7 * (c >= 9) + nib(0x665432210ull, e), (0x108 >> e) & 1 ? 14 : 12);
  }
  g_epoch[m * 8 + n] = tag;
  bulk_wait_read();
}

__device__ __forceinline__ void sum_rows(uint32_t buf, int iters, float (&a)[8], int lane) {
  uint32_t addr = buf + (lane >> 3) * 128 + (((lane & 7) ^ (lane >> 3)) << 4);
#pragma unroll 1
  for (int it = 0; it < iters; it++) {
    uint32_t u[2][4];
    lds_u4(addr, u[0][0], u[0][1], u[0][2], u[0][3]);
    lds_u4((addr ^ 64) + 512, u[1][0], u[1][1], u[1][2], u[1][3]);
    addr += 1024;
#pragma unroll
    for (int e = 0; e < 8; e++) { a[2 * (e & 3)] += bf_lo(u[e >> 2][e & 3]); a[2 * (e & 3) + 1] += bf_hi(u[e >> 2][e & 3]); }
  }
}
__device__ __forceinline__ void publish_sums(const float (&a)[8], uint4* dst, int lane, uint32_t tag) {
  const bool u8 = lane & 8, u16 = lane & 16;
  float h4[4], h2[2];
#pragma unroll
  for (int e = 0; e < 4; e++) h4[e] = (u8 ? a[4 + e] : a[e]) + __shfl_xor_sync(0xffffffffu, u8 ? a[e] : a[4 + e], 8);
#pragma unroll
  for (int e = 0; e < 2; e++) h2[e] = (u16 ? h4[2 + e] : h4[e]) + __shfl_xor_sync(0xffffffffu, u16 ? h4[e] : h4[2 + e], 16);
  st_msg(dst + (lane & 7) * 4 + (u8 ? 2 : 0) + (u16 ? 1 : 0), __float_as_uint(h2[0]), __float_as_uint(h2[1]), 0u, tag);
}

__device__ __forceinline__ void colsum_helper(const Params& p, uint32_t sb, int m, int n, int lane) {
  const uint32_t tag = __ldcg(g_epoch + m * 8 + n) + 1;
  const int mn = m * 8 + n; (void)mn;
#pragma unroll 1
  for (int k = lane; k < 288; k += 32) {
    const uint32_t bb = __ldg(reinterpret_cast<const uint32_t*>(k < 224 ? p.b1 + 448 * n : p.b2 + 128 * n - 448) + k);
    const float sc = k < 224 ? 0.5f : 1.f;
    sts_f2(sb + (k < 224 ? OFF_CSF + k * 16 + 8 : OFF_CSQ + 1536 + (k - 224) * 8), sc * bf_lo(bb), sc * bf_hi(bb));
  }
  __syncwarp();
  if (elect_one()) mbar_arrive(sb + BAR_BIAS);
  bar_sync(BAR_HLP, 160);
  PROF_E(-1, 1);
#pragma unroll 1
  for (int c = 0; c < 7; c++) {
    float a[8] = {0.f, 0.f, 0.f, 0.f, 0.f, 0.f, 0.f, 0.f};
#pragma unroll 1
    for (int h = 0; h < 2; h++) {
      if (elect_one()) {
        mbar_expect_tx(sb + BAR_CSLD + 8, 4096);
        tma_ld2(sb + OFF_HLP, &p.w1c, sb + BAR_CSLD + 8, 448 * n + 64 * c, 64 * m + 32 * h);
        if (c < 6) asm volatile("cp.async.bulk.prefetch.tensor.2d.L2.global [%0, {%1, %2}];" ::"l"(&p.w1c), "r"(448 * n + 64 * c + 64), "r"(64 * m + 32 * h) : "memory");
      }
      mbar_wait(sb + BAR_CSLD + 8, h);
      sum_rows(sb + OFF_HLP, 4, a, lane);
      __syncwarp();
    }
    publish_sums(a, g_csp + ((8 + n) * 17 + m) * 224 + c * 32, lane, tag);
  }
  PROF_E(-1, 2);
}

__device__ __forceinline__ void poll_msgs2(const uint4* pa, const uint4* pb, float (&v)[4], uint32_t tag) {
#pragma unroll 1
  for (int it = 0; it < MSG_SPINS; it++) {
    uint32_t x[4], z, ta, tb;
    ld_msg(pa, x[0], x[1], z, ta);
    ld_msg(pb, x[2], x[3], z, tb);
#pragma unroll
    for (int e = 0; e < 4; e++) v[e] = __uint_as_float(x[e]);
    if (__all_sync(0xffffffffu, ta == tag && tb == tag)) break;
  }
}
__device__ __forceinline__ void colsum_total(const Ctx& cx, int mat, uint32_t tag) {
  uint4* base = g_csp + (mat * 8 + cx.n) * 17 * 224;
  const int per = 12 + 2 * mat, k = 2 * cx.w + (cx.lane >> 4), ia = per * cx.m + k, ib = per * cx.m + min(k + 8, per - 1);
  float v[4];
  poll_msgs2(base + (cx.lane & 15) * 224 + ia, base + (cx.lane & 15) * 224 + ib, v, tag);
#pragma unroll 1
  for (int d = 1; d < 16; d *= 2)
#pragma unroll
    for (int e = 0; e < 4; e++) v[e] += __shfl_xor_sync(0xffffffffu, v[e], d);
  const bool hi = cx.lane & 1;
  if ((cx.lane & 14) == 0) st_msg(base + 16 * 224 + (hi ? ib : ia), __float_as_uint(hi ? v[2] : v[0]), __float_as_uint(hi ? v[3] : v[1]), 0u, tag);
}
__device__ __forceinline__ void colsum_gather(const Ctx& cx, int mat, uint32_t tag) {
  const uint4* base = g_csp + ((mat * 8 + cx.n) * 17 + 16) * 224;
  const int ia = cx.w * 32 + cx.lane, ib = min(ia + 128, 191 + 32 * mat);
  float v[4];
  poll_msgs2(base + ia, base + ib, v, tag);
  const uint32_t tab = cx.sb + (mat ? OFF_CSF : OFF_CSQ);
  sts_f2(tab + (ia << (3 + mat)), v[0], v[1]);
  sts_f2(tab + (ib << (3 + mat)), v[2], v[3]);
}

constexpr uint32_t RING16 = RING_UNITS * (UNIT >> 4);
__device__ __forceinline__ bool tile_split(int i) { return (0xD98 >> i) & 1; }

__device__ __forceinline__ void write_run_desc(uint32_t sb, int i, int step) {
  const int layer = i >= 7, t = i - 7 * layer, part = tile_split(i) ? step : 2;
  const bool wide = tile_wide(t), own = t != 2 && t != 6 && part != 1 && i != 0, second = t == 1 || t == 4;
  const uint32_t z16 = (wide ? 5 : 4) * (UNIT >> 4), a_off = z16 - 1024 + (uint32_t)DESC_A - (uint32_t)DESC_B;
  const int gl = 16 * t + (part == 2 ? 0 : second ? 16 * part - 14 : 4 * part), g0 = layer * STAGES_PER_LAYER + gl;
  const uint32_t s16 = (sb & 0x3FFFF) >> 4, bfirst = (uint32_t)DESC_B + s16;
  const int nkb = t == 6 ? 56 : part == 0 ? 2 : 12 + 2 * part;
  const bool win1 = t == 1 && part != 0;
  const int run = win1 ? WIN1 + 1 : t == 2 ? WIN2 + 1 : nkb;
  const int rest = win1 ? 64 | (nkb - 1 - WIN1) : t == 2 ? 64 | (7 - WIN2) | (8 << 7) : 0;
  const uint32_t blo = bfirst + z16 * (wide ? (gl + (t == 5 ? 3 : 0)) & 3 : (gl + 3) % 5);
  const uint32_t alo = own ? (uint32_t)DESC_A + s16 + (OFF_X >> 4) : blo + a_off;
  const uint32_t aoff = own ? alo + 1024 - (blo == bfirst + RING16 - z16 ? bfirst : blo + z16) : a_off;
  const bool xwait = part == 0 && !second, keep = !(part == 0 || t == 5);
  sts_u4(sb + OFF_RUN + (2 * i + step) * 16, blo, alo, aoff,
         ((g0 / NBAR) & 1) | xwait << 1 | keep << 2 | 8 * (g0 % NBAR) | run << 6 | rest << 12);
}

template <int N>
__device__ __forceinline__ void mainloop(float (&acc)[2][96], uint32_t sb, int i, int step, int mn) {
  constexpr uint32_t Z16 = (2 + N / 64) * (UNIT >> 4);
  constexpr uint32_t A_OFF = Z16 - 1024 + (uint32_t)DESC_A - (uint32_t)DESC_B;
  const int wg = i & 1;
  const uint32_t s16 = (sb & 0x3FFFF) >> 4;
  const uint32_t blast = (uint32_t)DESC_B + s16 + RING16 - Z16, flast = sb + BAR_FULL + 8 * (NBAR - 1);
  uint32_t blo = (uint32_t)DESC_B + s16, alo = blo + A_OFF, aoff = A_OFF, misc = 16 << 6;
  if (N == 128 || i > 0) lds_u4(sb + OFF_RUN + (2 * i + step) * 16, blo, alo, aoff, misc);
  uint32_t keep = misc & 4;
  int run = (misc >> 6) & 63, rest = misc >> 12;
  uint32_t fb = sb + BAR_FULL + (misc & 0x38), ph = misc & 1;
  uint32_t prev = sb + BAR_DUMMY - 8 * NBAR;
  pin_regs<N / 2>(acc);
  if (N == 128 || i > 0) bar_sync(BAR_ORDER + wg, 256);
  else bar_sync(BAR_INIT0, 160);
  if (N == 192 && i == 0 && threadIdx.x == 0) PROF_U(8);
  mbar_wait(fb, ph);
  if (misc & 2) mbar_wait(sb + BAR_XRDY, N == 128);
  if (step == 0 || !tile_split(i)) PROF_T(4 + i * 4);
#pragma unroll 1
  while (true) {
    const uint64_t da = (DESC_A & ~0xffffffffull) | alo, db = (DESC_B & ~0xffffffffull) | blo;
    asm volatile("wgmma.fence.sync.aligned;" ::: "memory");
    wgmma_ss<N>(acc[0], da, db, keep);
    wgmma_ss<N>(acc[1], da + 64, db, keep);
    keep = 4;
    wgmma_ss<N>(acc[0], da + 2, db + 128);
    wgmma_ss<N>(acc[1], da + 66, db + 128);
    asm volatile("wgmma.commit_group.sync.aligned;" ::: "memory");
    asm volatile("wgmma.wait_group.sync.aligned 1;" ::: "memory");
    PROF_S(jj++);
    if (elect_one()) mbar_arrive(prev + 8 * NBAR);
    prev = fb;
    if (fb == flast) { fb -= 8 * NBAR; ph++; }
    fb += 8;
    if (blo == blast) blo -= RING16;
    blo += Z16;
    alo = blo + aoff;
    aoff = A_OFF;
    run--;
    const bool ready = mbar_test(fb, ph) && run != 0;
    asm volatile("wgmma.fence.sync.aligned;" ::: "memory");
    wgmma_ss<N>(acc[0], da + 4, db + 256);
    wgmma_ss<N>(acc[1], da + 68, db + 256);
    wgmma_ss<N>(acc[0], da + 6, db + 384);
    wgmma_ss<N>(acc[1], da + 70, db + 384);
    asm volatile("wgmma.commit_group.sync.aligned;" ::: "memory");
    if (!ready) {
      if (run == 0) {
        if (rest == 0) break;
        if (rest & 64) {
          bar_arrive(BAR_GO, 256);
          bar_sync(BAR_DONE, 256);
        } else {
          alo = (uint32_t)DESC_A + s16 + (OFF_STG >> 4);
        }
        run = rest & 63;
        rest >>= 7;
      }
      mbar_wait(fb, ph);
    }
  }
  if (i < 13) bar_arrive(BAR_ORDER + (wg ^ 1), 256);
  asm volatile("wgmma.wait_group.sync.aligned 0;" ::: "memory");
  pin_regs<N / 2>(acc);
  if (elect_one()) mbar_arrive(prev + 8 * NBAR);
  PROF_T(5 + i * 4);
  PROF_E(i, 0);
}

#define ACC(q, j, e) acc[(q) & 1][4 * (j) + 2 * ((q) >> 1) + (e)]

__device__ __forceinline__ void write_partial_stats(const Ctx& c, int ln, uint32_t tag) {
  const uint32_t xrow = c.sb + OFF_X + c.w * 4096 + c.lane * 128;
  float s = 0.f, q = 0.f, s1 = 0.f, q1 = 0.f;
#pragma unroll 2
  for (int j = 0; j < 16; j++) {
    uint32_t u[4];
    lds_u4(xrow + (j >> 3) * 16384 + (((j & 7) ^ (c.lane & 7)) << 4), u[0], u[1], u[2], u[3]);
#pragma unroll
    for (int e = 0; e < 4; e++) {
      const float a = bf_lo(u[e]), d = bf_hi(u[e]);
      s += a; q = fmaf(a, a, q);
      s1 += d; q1 = fmaf(d, d, q1);
    }
  }
  s += s1;
  q += q1;
  st_msg(g_stats + (ln * 8 + c.n) * SEQ + 128 * c.m + 32 * c.w + c.lane, __float_as_uint(s),
         __float_as_uint(fmaxf(q - s * s * (1.f / 128.f), 0.f)), 0u, tag);
}

__device__ __forceinline__ void finish_row_stats(const Ctx& c, int ln, uint32_t tag) {
  const uint4* src = g_stats + ln * 8 * SEQ + 128 * c.m + 32 * c.w + c.lane;
  uint32_t ps[8], pm[8];
#pragma unroll 1
  for (int it = 0; it < MSG_SPINS; it++) {
    uint32_t bad = 0, u, tg;
#pragma unroll
    for (int k = 0; k < 8; k++) { ld_msg(src + k * SEQ, ps[k], pm[k], u, tg); bad |= tg ^ tag; }
    if (__all_sync(0xffffffffu, bad == 0)) break;
  }
  float s = 0.f, m2 = 0.f;
#pragma unroll
  for (int k = 0; k < 8; k++) s += __uint_as_float(ps[k]);
  const float mean = s * (1.f / DM);
#pragma unroll
  for (int k = 0; k < 8; k++) {
    const float d = __uint_as_float(ps[k]) * (1.f / 128.f) - mean;
    m2 += fmaf(128.f * d, d, __uint_as_float(pm[k]));
  }
  sts_f2(c.sb + OFF_ROW + (32 * c.w + c.lane) * 8, rsqrtf(m2 * (1.f / DM) + 1e-5f), mean);
  __syncwarp();
}

__device__ __forceinline__ void attn_scores(const uint32_t* qa, const uint32_t* qb, const uint32_t* k0, const uint32_t* k1,
                                            const uint32_t* k2, const uint32_t* k3, float (&l)[4], const float4& zero,
                                            bool par, bool early) {
  float s[4][4];
#pragma unroll
  for (int kb = 0; kb < 4; kb++) {
    const uint32_t* kk = kb == 0 ? k0 : kb == 1 ? k1 : kb == 2 ? k2 : k3;
    asm volatile("mma.sync.aligned.m16n8k16.row.col.f32.bf16.bf16.f32 {%0,%1,%2,%3}, {%4,%5,%6,%7}, {%8,%9}, {%10,%11,%12,%13};"
                 : "=f"(s[kb][0]), "=f"(s[kb][1]), "=f"(s[kb][2]), "=f"(s[kb][3])
                 : "r"(qa[0]), "r"(qb[0]), "r"(qa[1]), "r"(qb[1]), "r"(kk[0]), "r"(kk[1]), "f"(zero.x), "f"(zero.y),
                   "f"(zero.z), "f"(zero.w));
  }
#pragma unroll
  for (int kb = 0; kb < 4; kb++) {
    const uint32_t* kk = kb == 0 ? k0 : kb == 1 ? k1 : kb == 2 ? k2 : k3;
    mma16816(s[kb], qa[2], qb[2], qa[3], qb[3], kk[2], kk[3]);
  }
  l[0] = par ? s[1][1] : s[1][0];
  l[1] = early ? (par ? s[0][1] : s[0][0]) : (par ? s[2][1] : s[2][0]);
  l[2] = par ? s[2][3] : s[2][2];
  l[3] = early ? (par ? s[1][3] : s[1][2]) : (par ? s[3][3] : s[3][2]);
}

__device__ __forceinline__ void attn_mix(const float (&l)[4], const float (&sc)[4], const float (&off)[4], const float (&rk)[4],
                                         const uint32_t* v0, const uint32_t* v1, const uint32_t* v2, const uint32_t* v3,
                                         uint32_t* olo, uint32_t* ohi, const uint32_t (&sel)[4]) {
  float x[4];
#pragma unroll
  for (int e = 0; e < 4; e++) x[e] = fmaf(l[e], sc[e], off[e]);
  const float ml = quad_max(fmaxf(x[0], x[1])), mh = quad_max(fmaxf(x[2], x[3]));
  x[0] = ex2(x[0] - ml); x[1] = ex2(x[1] - ml);
  x[2] = ex2(x[2] - mh); x[3] = ex2(x[3] - mh);
  const uint32_t pl = pack_bf16(x[0] * rk[0], x[1] * rk[1]), ph = pack_bf16(x[2] * rk[2], x[3] * rk[3]);
  const uint32_t a0 = prmt_u(pl, sel[1]), a1 = prmt_u(pl, sel[3]), a2 = prmt_u(pl, sel[0]), a3 = prmt_u(ph, sel[1]);
  const uint32_t c0 = prmt_u(pl, sel[2]), c1 = prmt_u(ph, sel[0]), c2 = prmt_u(ph, sel[3]), c3 = prmt_u(ph, sel[2]);
  float o[4][4];
#pragma unroll
  for (int jn = 0; jn < 4; jn++) {
    o[jn][0] = o[jn][1] = o[jn][2] = o[jn][3] = 0.f;
    mma16816(o[jn], a0, a1, a2, a3, v0[jn], v1[jn]);
  }
#pragma unroll
  for (int jn = 0; jn < 4; jn++) mma16816(o[jn], c0, c1, c2, c3, v2[jn], v3[jn]);
  const float il = rcp_hw(quad_sum(x[0] + x[1])), ih = rcp_hw(quad_sum(x[2] + x[3]));
#pragma unroll
  for (int jn = 0; jn < 4; jn++) {
    olo[jn] = pack_bf16(o[jn][0] * il, o[jn][1] * il);
    ohi[jn] = pack_bf16(o[jn][2] * ih, o[jn][3] * ih);
  }
}

__device__ __forceinline__ void gelu_epilogue(const Params& p, float (&acc)[2][96], const Ctx& cx, int t) {
  UNPACK_CTX(cx);
  (void)wg;
  float rs[4], rm[4];
#pragma unroll
  for (int q = 0; q < 4; q++) {
    const float2 v = lds_f2(sb + OFF_ROW + (32 * w + 8 * q + (lane >> 2)) * 8);
    rs[q] = 0.5f * v.x;
    rm[q] = -rs[q] * v.y;
  }
  const int col0 = 128 * (t - 3), steps = t == 5 ? 6 : 4;
  const uint32_t stg = sb + OFF_STG + w * 4096;
  uint32_t ctab = sb + OFF_CSF + (col0 / 2 + (lane & 3)) * 16, srow = stg + lane * 128 + ((lane & 7) << 4);
  float v[2][16];
#define PULL(k) _Pragma("unroll") for (int j = 0; j < 4; j++) { \
      const float2 bb = lds_f2(ctab + j * 64 + 8); \
      _Pragma("unroll") for (int r = 0; r < 8; r++) \
        asm volatile("fma.rn.f32 %0, %1, %2, %3;" : "=f"(v[r >> 2][4 * j + (r & 3)]) \
                     : "f"(acc[r >> 2][16 * k + 4 * j + (r & 3)]), "f"(rs[(r >> 2) + (r & 2)]), "f"(r & 1 ? bb.y : bb.x)); }
  PULL(0)
#pragma unroll 1
  for (int it = 0;; it++) {
    uint32_t hp[4][4];
#pragma unroll
    for (int j = 0; j < 4; j++) {
      const float2 cs = lds_f2(ctab + j * 64);
#pragma unroll
      for (int q = 0; q < 4; q++) {
        float y[2];
        const int k = 4 * j + q - GELU_DEP;
        const float rmq = k >= 0 ? chain(rm[q], hp[k >> 2][k & 3], p.zero) : rm[q];
#pragma unroll
        for (int e = 0; e < 2; e++) {
          const float z = fmaf(rmq, e ? cs.y : cs.x, v[q & 1][4 * j + 2 * (q >> 1) + e]);
          const float u = z * fmaf(z * z, 8.f * 0.7978845608028654f * 0.044715f, 2.f * 0.7978845608028654f);
          y[e] = fmaf(z, tanh_hw(u), z);
        }
        hp[j][q] = pack_bf16(y[0], y[1]);
      }
    }
    ctab += 256;
    if (!(it & 1)) {
      if (lane == 0) bulk_wait_read();
      __syncwarp();
    }
#pragma unroll
    for (int j = 0; j < 4; j++) stsm4(srow ^ (j << 4), hp[j][0], hp[j][1], hp[j][2], hp[j][3]);
    srow ^= 64;
    if (it & 1) {
      fence_async_smem();
      __syncwarp();
      if (lane == 0) {
        tma_st2(&p.h_st, stg, 448 * n + col0 + 32 * (it - 1), 128 * m + 32 * w);
        bulk_commit();
      }
      if (it == steps - 1) break;
    }
    switch (it) {
      case 0: PULL(1) break;
      case 1: PULL(2) break;
      case 2: PULL(3) break;
      case 3: PULL(4) break;
      default: PULL(5)
    }
  }
#undef PULL
#pragma unroll
  for (int r = 0; r < 16; r++) acc[0][r] = acc[1][r] = 0.f;
}

__device__ __forceinline__ void attn_epilogue(const Params& p, float (&acc)[2][96], const Ctx& cx, int layer, int t, uint32_t tag) {
  UNPACK_CTX(cx);
  const bool par = (lane >> 2) & 1, early = (lane & 3) > (lane >> 3);
  const uint32_t ktab = sb + OFF_ROW + (32 * w + 2 * (lane & 3) + par) * 8, exc = sb + OFF_STG + w * 4096 + lane * 16;
  const int slot = ((layer * 2 + t) * 16 + m) * 8 + n;
  const int mn = m * 8 + n; (void)mn;
  uint32_t Q[4][8], K[4][8], V[4][8], E[36], P[36];
  float kr[6], qr[4];
#pragma unroll
  for (int q = 2; q < 4; q++) {
    kr[2 + q] = lds_f(ktab + 64 * q);
#pragma unroll
    for (int j = 0; j < 8; j++) {
      E[8 * (q - 2) + j] = K[q][j] = pack_bf16(ACC(q, 8 + j, 0), ACC(q, 8 + j, 1));
      E[16 + 2 * j + q - 2] = V[q][j] = movtrans(pack_bf16(ACC(q, 16 + j, 0), ACC(q, 16 + j, 1)));
    }
  }
  E[32] = __float_as_uint(kr[4]);
  E[33] = E[34] = E[35] = __float_as_uint(kr[5]);
  if (w < 3) {
#pragma unroll
    for (int k = 0; k < 8; k++) sts_u4(exc + k * 512, E[4 * k], E[4 * k + 1], E[4 * k + 2], E[4 * k + 3]);
  } else {
#pragma unroll
    for (int k = 0; k < 12; k++) st_msg(g_halo + slot * 384 + k * 32 + lane, E[3 * k], E[3 * k + 1], E[3 * k + 2], tag);
  }
  PROF_E(7 * layer + t, 1);
#pragma unroll
  for (int q = 0; q < 4; q++) {
    qr[q] = lds_f(sb + OFF_ROW + (32 * w + 8 * q + (lane >> 2)) * 8) * (0.17677669529663687f * 1.4426950408889634f);
#pragma unroll
    for (int j = 0; j < 8; j++) Q[q][j] = pack_bf16(ACC(q, j, 0), ACC(q, j, 1));
    if (q < 2) {
      kr[2 + q] = lds_f(ktab + 64 * q);
#pragma unroll
      for (int j = 0; j < 8; j++) {
        K[q][j] = pack_bf16(ACC(q, 8 + j, 0), ACC(q, 8 + j, 1));
        V[q][j] = movtrans(pack_bf16(ACC(q, 16 + j, 0), ACC(q, 16 + j, 1)));
      }
    }
  }
  bar_sync(BAR_WG + wg, 128);
  if (w > 0 || m == 0) {
    const uint32_t back = w > 0;
#pragma unroll
    for (int k = 0; k < 8; k++) lds_u4(exc - back * 4096 + k * 512, P[4 * k], P[4 * k + 1], P[4 * k + 2], P[4 * k + 3]);
    P[32] = lds_u(ktab - back * 128);
    P[33] = lds_u(ktab - back * 64);
  } else {
#pragma unroll 1
    for (int it = 0; it < MSG_SPINS; it++) {
      uint32_t tg, bad = 0;
#pragma unroll
      for (int k = 0; k < 12; k++) {
        ld_msg(g_halo + (slot - 8) * 384 + k * 32 + lane, P[3 * k], P[3 * k + 1], P[3 * k + 2], tg);
        bad |= tg ^ tag;
      }
      if (__all_sync(0xffffffffu, bad == 0)) break;
    }
  }
  kr[0] = __uint_as_float(P[32]);
  kr[1] = __uint_as_float(P[33]);
  uint32_t PV[2][8];
#pragma unroll
  for (int j = 0; j < 8; j++) { PV[0][j] = P[16 + 2 * j]; PV[1][j] = P[17 + 2 * j]; }
  float rk[2][4], sc[2][4], off[2][4];
#pragma unroll
  for (int g = 0; g < 2; g++) {
    rk[g][0] = kr[2 * g + 1];
    rk[g][1] = early ? kr[2 * g] : kr[2 * g + 2];
    rk[g][2] = kr[2 * g + 2];
    rk[g][3] = early ? kr[2 * g + 1] : kr[2 * g + 3];
#pragma unroll
    for (int e = 0; e < 4; e++) {
      const bool masked = g == 0 && e != 2 && (m | w) == 0 && (e == 0 || early);
      sc[g][e] = masked ? 0.f : rk[g][e] * qr[2 * g + (e >> 1)];
      off[g][e] = masked ? -1e30f : 0.f;
    }
  }
  const uint32_t none = 0x4444u | p.zero, second = par ? 0x3244u : 0x4432u;
  const uint32_t sel[4] = {par ? 0x1044u : 0x4410u, early ? second : none, early ? none : second, none};
  PROF_E(7 * layer + t, 2);
  bar_sync(BAR_GO, 256);
  const float4 zero = lds_f4(sb + OFF_ZERO);
  float l[2][2][4];
  uint32_t O[4][8];
#pragma unroll
  for (int h = 0; h < 2; h++) {
    if (h == 1) {
      Q[2][4] |= __float_as_uint(l[1][0][0]) & p.zero;
      Q[0][4] |= __float_as_uint(l[0][0][0]) & p.zero;
    }
    attn_scores(&Q[2][4 * h], &Q[3][4 * h], &K[0][4 * h], &K[1][4 * h], &K[2][4 * h], &K[3][4 * h], l[1][h], zero, par, early);
    attn_scores(&Q[0][4 * h], &Q[1][4 * h], &P[4 * h], &P[8 + 4 * h], &K[0][4 * h], &K[1][4 * h], l[0][h], zero, par, early);
  }
  const uint32_t stg = sb + OFF_STG + w * 4096, srow = stg + lane * 128 + ((lane & 7) << 4);
#pragma unroll
  for (int h = 0; h < 2; h++) {
    attn_mix(l[1][h], sc[1], off[1], rk[1], &V[0][4 * h], &V[1][4 * h], &V[2][4 * h], &V[3][4 * h], &O[2][4 * h], &O[3][4 * h], sel);
    attn_mix(l[0][h], sc[0], off[0], rk[0], &PV[0][4 * h], &PV[1][4 * h], &V[0][4 * h], &V[1][4 * h], &O[0][4 * h], &O[1][4 * h], sel);
#pragma unroll
    for (int j = 4 * h; j < 4 * h + 4; j++) stsm4(srow ^ (j << 4), O[0][j], O[1][j], O[2][j], O[3][j]);
  }
  bar_arrive(BAR_DONE, 256);
  fence_async_smem();
  __syncwarp();
  if (lane == 0) {
    tma_st2(&p.att_st, stg, 128 * n + 64 * t, 128 * m + 32 * w);
    bulk_commit();
  }
}

__device__ __forceinline__ void finish_stores(uint32_t sb, int i) {
  const int t = i >= 7 ? i - 7 : i;
  if ((threadIdx.x & 31) == 0) {
    bulk_wait_all();
    mbar_arrive(sb + BAR_PUB + 8 * (t < 2 ? t : t + 1));
  }
  __syncwarp();
  if (i < 12) bar_arrive(BAR_GUARD + ((i & 1) ^ 1), 256);
}

__device__ __forceinline__ bool consumer_tile(const Params& p, float (&acc)[2][96], uint32_t sb0, int i, int mn) {
  const int layer = i >= 7, t = i - 7 * layer, wg = i & 1;
  const bool resid = t == 2 || t == 6;
  {
    if (resid) {
      const Ctx cx = make_ctx(sb0, mn);
      const uint32_t xrow = cx.sb + OFF_X + cx.w * 4096 + cx.lane * 128;
      const uint32_t sel_lo = 0x1044u | p.zero, sel_hi = 0x3244u | p.zero;
#pragma unroll
      for (int j = 0; j < 16; j++) {
        uint32_t r[4];
        ldsm4(xrow + (j >> 3) * 16384 + (((j & 7) ^ (cx.lane & 7)) << 4), r[0], r[1], r[2], r[3]);
#pragma unroll
        for (int q = 0; q < 4; q++) {
          ACC(q, j, 0) = prmt_f(r[q], sel_lo);
          ACC(q, j, 1) = prmt_f(r[q], sel_hi);
        }
      }
    }
    if (t >= 5 || i == 7) finish_stores(sb0, i - 2);
#pragma unroll 1
    for (int step = !tile_split(i);; step++) {
      if (step == 1 && (t == 1 || t == 4)) {
        const Ctx cx = make_ctx(sb0, mn);
        if (i == 1) {
          const uint32_t epoch = __ldcg(g_epoch + (mn & 127));
          bar_sync(BAR_INIT, 256);
          asm volatile("st.shared.u32 [%0], %1;" ::"r"(sb0 + OFF_TAG), "r"(epoch + 1) : "memory");
        }
        const uint32_t tag = lds_u(cx.sb + OFF_TAG);
        const int ln = (i + 1) >> 2;
#pragma unroll 1
        for (int r = 0; r < 2; r++) {
          if (i == 1) {
            if (cx.w < 3) {
              float a[8] = {0.f, 0.f, 0.f, 0.f, 0.f, 0.f, 0.f, 0.f};
              mbar_wait(sb0 + BAR_CSLD, r);
              sum_rows(cx.sb + OFF_STG + cx.w * 8192, 8, a, cx.lane);
              publish_sums(a, g_csp + (cx.n * 17 + cx.m) * 224 + (3 * r + cx.w) * 32, cx.lane, tag);
            }
            PROF_E(-1, 5 + r);
          }
          if (r == 1) break;
          if (i == 1) {
            bar_sync(BAR_WG + 1, 128);
            if (cx.w == 3 && elect_one()) {
              mbar_expect_tx(sb0 + BAR_CSLD, 24576);
              tma_ld3(sb0 + OFF_STG, &p.wqkv, sb0 + BAR_CSLD, 128 * cx.n + 64, 64 * cx.m, 0);
            }
            mbar_wait(sb0 + BAR_XRDY, 0);
            mbar_wait(sb0 + BAR_XRDY + 8, 0);
          }
          write_partial_stats(cx, ln, tag);
          PROF_E(i - 2, 8);
        }
        if (i == 1) bar_arrive(BAR_HLP, 160);
        if (i <= 4) colsum_total(cx, ln, tag);
        PROF_E(i - 2, 9);
        if (i != 1) bar_sync(BAR_GUARD + wg, 256);
        finish_row_stats(cx, ln, tag);
        PROF_E(i - 2, 10);
        if (i <= 4) {
          colsum_gather(cx, ln, tag);
          if (i == 4) mbar_wait(sb0 + BAR_BIAS, 0);
          bar_sync(BAR_WG + wg, 128);
        }
        PROF_E(i - 2, 15);
        bar_arrive(BAR_GUARD + (wg ^ 1), 256);
      }
      if (step == 2 && !resid) bar_sync(BAR_GUARD + wg, 256);
      if (t + step == 2 || t == 6) {
        const Ctx cx = make_ctx(sb0, mn);
        float nm[4];
#pragma unroll
        for (int q = 0; q < 4; q++) nm[q] = t == 6 ? 1.f : -lds_f(cx.sb + OFF_ROW + (32 * cx.w + 8 * q + (cx.lane >> 2)) * 8 + 4);
        const uint32_t ctab = cx.sb + OFF_CSQ + ((t & 3) * 192 + 2 * (cx.lane & 3)) * 4;
#pragma unroll
        for (int j = 0; j < 24; j++) {
          const float2 cs = lds_f2(ctab + j * 32);
#pragma unroll
          for (int q = 0; q < 4; q++) {
            const int k = 4 * j + q - 1;
            const float nq = k >= 0 ? chain(nm[q], __float_as_uint(ACC(k & 3, k >> 2, 1)), p.zero) : nm[q];
            ACC(q, j, 0) = fmaf(nq, cs.x, ACC(q, j, 0));
            ACC(q, j, 1) = fmaf(nq, cs.y, ACC(q, j, 1));
          }
        }
      }
      if (step == 2) break;
      if (tile_wide(t)) {
        mainloop<192>(acc, sb0, i, step, mn);
      } else {
        mainloop<128>(acc, sb0, i, step, mn);
        if (resid) break;
      }
    }
    if (t < 2) return true;
    const Ctx cx = make_ctx(sb0, mn);
    if (resid) {
      const uint32_t xrow = cx.sb + OFF_X + cx.w * 4096 + cx.lane * 128;
#pragma unroll
      for (int j = 0; j < 16; j++) {
        stsm4(xrow + (j >> 3) * 16384 + (((j & 7) ^ (cx.lane & 7)) << 4), pack_bf16(ACC(0, j, 0), ACC(0, j, 1)),
              pack_bf16(ACC(1, j, 0), ACC(1, j, 1)), pack_bf16(ACC(2, j, 0), ACC(2, j, 1)), pack_bf16(ACC(3, j, 0), ACC(3, j, 1)));
        if ((j & 7) == 7) {
          fence_async_smem();
          __syncwarp();
          if (elect_one()) mbar_arrive(sb0 + BAR_XRDY + (j & 8));
        }
      }
      PROF_E(i, 4);
      return false;
    }
    gelu_epilogue(p, acc, cx, t);
    PROF_E(i, 4);
    return false;
  }
}

__global__ void __launch_bounds__(384, 1) fused_layers_kernel(const int by_smid, const __nv_bfloat16* x_p, const __nv_bfloat16* wqkv_p,
                                                                  const __grid_constant__ Params p) {
  extern __shared__ __align__(1024) uint8_t smem_raw[];
  const uint32_t sb = uniform((uint32_t)__cvta_generic_to_shared(smem_raw));
  const int tid = threadIdx.x, lane = tid & 31, warp = uniform(tid >> 5), wg = warp >> 2, w = warp & 3;

  int mn;
  {
    int id = blockIdx.x;
    if (by_smid) asm volatile("mov.u32 %0, %%smid;" : "=r"(id));
    else if (id >= 120) id += 4;
    const int c = id >> 1;
    int g, j;
    if (c < 32) { g = c & 7; j = c >> 3; }
    else if (c < 60) { g = 1 + (c - 32) % 7; j = 4 + (c - 32) / 7; }
    else { g = 0; j = c - 58; }
    mn = ((g >> 2) * 8 + j) * 8 + (g & 3) * 2 + (id & 1);
    if (c == 60 || c == 61) {
      if (tid < 32) {
        const uint32_t tag = __ldcg(g_epoch + NCTA + (id & 3)) + 1;
#pragma unroll 1
        for (int mm = 0; mm < 16; mm++) poll_line(g_flags + mm * 32 + (lane & 7), 32 * tag, 0xffu);
        if (tid == 0) g_epoch[NCTA + (id & 3)] = tag;
      }
      return;
    }
  }
  const int m = mn >> 3, n = mn & 7;
  if (tid == 256) PROF_U(1);
  if (tid >= 382) asm volatile("prefetch.global.L2 [%0];" ::"l"(tid & 1 ? wqkv_p + 128 * n : x_p + 128 * m * DM));
  if (wg < 2) {
    asm volatile("setmaxnreg.inc.sync.aligned.u32 232;");
    const int id = mn | (warp << 7);
#pragma unroll 1
    for (int i = wg;; i += 2) {
      float acc[2][96];
#pragma unroll
      for (int r = 0; r < 96; r++) acc[0][r] = acc[1][r] = 0.f;
      pin_regs<96>(acc);
#pragma unroll 1
      while (!consumer_tile(p, acc, sb, i, id)) {
        PROF_T(6 + i * 4);
        i += 2;
        if (i >= 14) goto all_done;
      }
      attn_epilogue(p, acc, make_ctx(sb, id), i >= 7, i >= 7 ? i - 7 : i, lds_u(sb + OFF_TAG));
      PROF_E(i, 4);
      finish_stores(sb, i);
      PROF_E(i, 5);
      PROF_T(6 + i * 4);
    }
  all_done:
    if (wg == 0) finish_stores(sb, 12);
  } else {
    asm volatile("setmaxnreg.dec.sync.aligned.u32 40;");
    if (w != 0) {
      if (w == 2 && lane < 28) write_run_desc(sb, lane >> 1, lane & 1);
      bar_sync(BAR_INIT, 256);
      if (w == 1) producer<true>(p, sb, m, n, lane);
      else if (w == 3) colsum_helper(p, sb, m, n, lane);
      else if (elect_one()) publisher(p, sb, m, n);
    } else {
      if (elect_one()) {
#pragma unroll
        for (int k = 0; k < 4; k++) mbar_init(sb + BAR_FULL + 8 * k, 2);
        asm volatile("fence.mbarrier_init.release.cluster;" ::: "memory");
        PROF_U(4);
#pragma unroll 1
        for (int k = 0; k < 4; k++) {
          const uint32_t fb = sb + BAR_FULL + 8 * k;
          mbar_expect_tx(fb, 16384);
          tma_ld2(sb + (5 * k + 3) * UNIT, &p.xin, fb, 64 * k, 128 * m);
          mbar_expect_tx(fb, 3 * UNIT);
          tma_ld3(sb + 5 * k * UNIT, &p.wqkv, fb, 128 * n, 64 * k, 0);
        }
        PROF_U(5);
        mbar_init(sb + BAR_XRDY, 4);
        mbar_init(sb + BAR_XRDY + 8, 4);
        mbar_init(sb + BAR_FULL + 32, 2);
#pragma unroll
        for (int k = 0; k < NBAR; k++) mbar_init(sb + BAR_EMPTY + 8 * k, 4);
        mbar_init(sb + BAR_DUMMY, 4);
#pragma unroll
        for (int k = 0; k < 7; k++) mbar_init(sb + BAR_PUB + 8 * k, 4);
#pragma unroll
        for (int k = 0; k < 3; k++) mbar_init(sb + BAR_CSLD + 8 * k, 1);
        sts_f2(sb + OFF_ZERO, 0.f, 0.f);
        sts_f2(sb + OFF_ZERO + 8, 0.f, 0.f);
        asm volatile("fence.mbarrier_init.release.cluster;" ::: "memory");
        mbar_expect_tx(sb + BAR_CSLD, 24576);
        tma_ld3(sb + OFF_STG, &p.wqkv, sb + BAR_CSLD, 128 * n, 64 * m, 0);
#pragma unroll 1
        for (int h = 0; h < 2; h++) {
          const uint32_t xr = sb + BAR_XRDY + 8 * h;
          mbar_expect_tx(xr, 16384);
          tma_ld2(sb + OFF_X + h * 16384, &p.xin, xr, 128 * n + 64 * h, 128 * m);
          asm volatile("mbarrier.arrive.shared::cta.b64 _, [%0], 3;" ::"r"(xr) : "memory");
        }
        PROF_U(6);
      }
      __syncwarp();
      bar_arrive(BAR_INIT0, 160);
      bar_arrive(BAR_INIT, 256);
      producer<false>(p, sb, m, n, lane);
    }
  }
}

typedef CUresult (*EncodeFn)(CUtensorMap*, CUtensorMapDataType, cuuint32_t, void*, const cuuint64_t*, const cuuint64_t*,
                             const cuuint32_t*, const cuuint32_t*, CUtensorMapInterleave, CUtensorMapSwizzle,
                             CUtensorMapL2promotion, CUtensorMapFloatOOBfill);

void make_2d(EncodeFn enc, CUtensorMap* m, const void* ptr, uint64_t cols, uint64_t rows, uint32_t box_rows) {
  cuuint64_t d[2] = {cols, rows}, st[1] = {cols * 2};
  cuuint32_t b[2] = {64, box_rows}, e[2] = {1, 1};
  enc(m, CU_TENSOR_MAP_DATA_TYPE_BFLOAT16, 2, const_cast<void*>(ptr), d, st, b, e, CU_TENSOR_MAP_INTERLEAVE_NONE,
      CU_TENSOR_MAP_SWIZZLE_128B, CU_TENSOR_MAP_L2_PROMOTION_L2_128B, CU_TENSOR_MAP_FLOAT_OOB_FILL_NONE);
}
void make_3d(EncodeFn enc, CUtensorMap* m, const void* ptr, uint64_t d0, uint64_t rows, uint64_t d2, uint64_t row_bytes,
             uint64_t chunk_bytes, uint32_t box_chunks) {
  cuuint64_t d[3] = {d0, rows, d2}, st[2] = {row_bytes, chunk_bytes};
  cuuint32_t b[3] = {64, 64, box_chunks}, e[3] = {1, 1, 1};
  enc(m, CU_TENSOR_MAP_DATA_TYPE_BFLOAT16, 3, const_cast<void*>(ptr), d, st, b, e, CU_TENSOR_MAP_INTERLEAVE_NONE,
      CU_TENSOR_MAP_SWIZZLE_128B, CU_TENSOR_MAP_L2_PROMOTION_L2_128B, CU_TENSOR_MAP_FLOAT_OOB_FILL_NONE);
}

}

extern "C" void kernel_launch(void* const* d_in, const int* in_sizes, int n_in, void* d_out, int out_size) {
  (void)in_sizes; (void)n_in; (void)out_size;
  static EncodeFn enc = nullptr;
  static void *att = nullptr, *hbuf = nullptr;
  static int by_smid = 0;
  if (!enc) {
    void* fn = nullptr;
    cudaDriverEntryPointQueryResult q;
    cudaGetDriverEntryPoint("cuTensorMapEncodeTiled", &fn, cudaEnableDefault, &q);
    enc = (EncodeFn)fn;
    cudaGetSymbolAddress(&att, g_att);
    cudaGetSymbolAddress(&hbuf, g_h);
    cudaFuncSetAttribute(fused_layers_kernel, cudaFuncAttributeMaxDynamicSharedMemorySize, SMEM_BYTES);
    int sms = 0, per_sm = 0, dev = 0;
    cudaGetDevice(&dev);
    cudaDeviceGetAttribute(&sms, cudaDevAttrMultiProcessorCount, dev);
    cudaOccupancyMaxActiveBlocksPerMultiprocessor(&per_sm, fused_layers_kernel, 384, SMEM_BYTES);
    by_smid = sms == 132 && per_sm == 1;
  }
  Params p;
  make_2d(enc, &p.xin, d_in[0], DM, SEQ, 128);
  make_2d(enc, &p.out, d_out, DM, SEQ, 128);
  make_2d(enc, &p.att, att, DM, SEQ, 128);
  make_2d(enc, &p.h, hbuf, FF, SEQ, 128);
  make_2d(enc, &p.out_st, d_out, DM, SEQ, 32);
  make_2d(enc, &p.att_st, att, DM, SEQ, 32);
  make_2d(enc, &p.h_st, hbuf, FF, SEQ, 32);
  make_2d(enc, &p.w1c, d_in[4], FF, DM, 32);
  make_3d(enc, &p.wqkv, d_in[1], DM, DM, 3, 3 * DM * 2, DM * 2, 3);
  make_3d(enc, &p.wo, d_in[2], 64, DM, DM / 64, DM * 2, 128, 2);
  make_3d(enc, &p.w1a, d_in[4], 64, DM, FF / 64, FF * 2, 128, 3);
  make_3d(enc, &p.w1b, d_in[4], 64, DM, FF / 64, FF * 2, 128, 2);
  make_3d(enc, &p.w2, d_in[6], 64, FF, DM / 64, DM * 2, 128, 2);
  p.b1 = (const __nv_bfloat16*)d_in[5];
  p.b2 = (const __nv_bfloat16*)d_in[7];
  p.zero = 0;
  fused_layers_kernel<<<by_smid ? 132 : NCTA, 384, SMEM_BYTES>>>(by_smid, (const __nv_bfloat16*)d_in[0], (const __nv_bfloat16*)d_in[1], p);
}
```

```cpp
#include <cuda_runtime.h>
#include <cuda_bf16.h>
#include <cuda.h>
#include <stdint.h>

namespace {

constexpr int SEQ = 2048, DM = 1024, FF = 3584;
constexpr int NCTA = 128;
constexpr int NBAR = 5;

constexpr uint32_t RING_UNITS = 20, UNIT = 8192;
constexpr uint32_t OFF_X   = RING_UNITS * UNIT;
constexpr uint32_t OFF_STG = OFF_X + 32768;
constexpr uint32_t OFF_HLP = OFF_STG + 16384;
constexpr uint32_t OFF_RUN = OFF_STG + 24576;
constexpr uint32_t OFF_CSQ = OFF_RUN + 512;
constexpr uint32_t OFF_CSF = OFF_CSQ + 2048;
constexpr uint32_t OFF_ROW = OFF_CSF + 3584;
constexpr uint32_t OFF_BAR = OFF_ROW + 1024;
constexpr uint32_t SMEM_BYTES = OFF_BAR + 384;
constexpr uint32_t BAR_FULL = OFF_BAR, BAR_EMPTY = OFF_BAR + 8 * NBAR;
constexpr uint32_t BAR_XRDY = OFF_BAR + 80;
constexpr uint32_t BAR_DUMMY = OFF_BAR + 96, OFF_TAG = OFF_BAR + 104, OFF_ZERO = OFF_BAR + 112;
constexpr uint32_t BAR_PUB = OFF_BAR + 128;
constexpr uint32_t BAR_CSLD = OFF_BAR + 200;
constexpr uint32_t BAR_BIAS = OFF_BAR + 216;

constexpr uint64_t DESC_A = (1ull << 62) | ((uint64_t)(2048 >> 4) << 32) | (1ull << 16);
constexpr uint64_t DESC_B = (1ull << 62) | ((uint64_t)(1024 >> 4) << 32) | ((uint64_t)(8192 >> 4) << 16);

constexpr int BAR_INIT = 0, BAR_ORDER = 1, BAR_GUARD = 3, BAR_WG = 5, BAR_GO = 7, BAR_DONE = 8, BAR_HLP = 9, BAR_INIT0 = 10;
#define GELU_DEP 2
#define WIN1 7
#define WIN2 4

struct Scratch {
  uint4 stats[4 * 8 * SEQ];
  uint4 halo[2 * 2 * 16 * 8 * 384];
  uint4 csp[2 * 8 * 17 * 224];
  uint32_t flags[16 * 32];
  uint32_t epoch[NCTA + 4];
};

struct Params {
  CUtensorMap xin, out, att, h, wqkv, wo, w1a, w1b, w2, out_st, att_st, h_st, w1c;
  const __nv_bfloat16 *b1, *b2;
  Scratch* g;
  uint32_t zero;
};

__device__ __nv_bfloat16 g_att[SEQ * DM];
__device__ __nv_bfloat16 g_h[SEQ * FF];
__device__ Scratch g_scratch;
#define PROF_T(idx)
#define PROF_U(k)
#define PROF_S(g)
#define PROF_E(i, k)

__device__ __forceinline__ void mbar_init(uint32_t bar, int cnt) {
  asm volatile("mbarrier.init.shared::cta.b64 [%0], %1;" ::"r"(bar), "r"(cnt));
}
__device__ __forceinline__ void mbar_expect_tx(uint32_t bar, uint32_t bytes) {
  asm volatile("mbarrier.arrive.expect_tx.shared::cta.b64 _, [%0], %1;" ::"r"(bar), "r"(bytes) : "memory");
}
__device__ __forceinline__ void mbar_arrive(uint32_t bar) {
  asm volatile("mbarrier.arrive.shared::cta.b64 _, [%0];" ::"r"(bar) : "memory");
}
__device__ __forceinline__ bool mbar_test(uint32_t bar, uint32_t parity) {
  uint32_t ok;
  asm volatile("{\n.reg .pred p;\nmbarrier.test_wait.parity.shared::cta.b64 p, [%1], %2;\nselp.u32 %0, 1, 0, p;\n}"
               : "=r"(ok) : "r"(bar), "r"(parity) : "memory");
  return ok;
}
__device__ __forceinline__ void mbar_wait(uint32_t bar, uint32_t parity) {
  asm volatile(
      "{\n.reg .pred p;\n.reg .u32 it;\nmov.u32 it, 0;\n"
      "WAIT_LOOP:\n"
      "mbarrier.try_wait.parity.shared::cta.b64 p, [%0], %1;\n"
      "@p bra WAIT_DONE;\n"
      "add.u32 it, it, 1;\n"
      "setp.lt.u32 p, it, 0x400000;\n"
      "@p bra WAIT_LOOP;\n"
      "trap;\n"
      "WAIT_DONE:\n}"
      ::"r"(bar), "r"(parity) : "memory");
}
__device__ __forceinline__ void bar_sync(int id, int n) { asm volatile("bar.sync %0, %1;" ::"r"(id), "r"(n) : "memory"); }
__device__ __forceinline__ void bar_arrive(int id, int n) { asm volatile("bar.arrive %0, %1;" ::"r"(id), "r"(n) : "memory"); }
__device__ __forceinline__ void tma_ld2(uint32_t dst, const CUtensorMap* m, uint32_t bar, int c0, int c1) {
  asm volatile("cp.async.bulk.tensor.2d.shared::cluster.global.mbarrier::complete_tx::bytes [%0], [%1, {%3, %4}], [%2];"
               ::"r"(dst), "l"(m), "r"(bar), "r"(c0), "r"(c1) : "memory");
}
__device__ __forceinline__ void tma_ld3(uint32_t dst, const CUtensorMap* m, uint32_t bar, int c0, int c1, int c2) {
  asm volatile("cp.async.bulk.tensor.3d.shared::cluster.global.mbarrier::complete_tx::bytes [%0], [%1, {%3, %4, %5}], [%2];"
               ::"r"(dst), "l"(m), "r"(bar), "r"(c0), "r"(c1), "r"(c2) : "memory");
}
__device__ __forceinline__ void tma_st2(const CUtensorMap* m, uint32_t src, int c0, int c1) {
  asm volatile("cp.async.bulk.tensor.2d.global.shared::cta.bulk_group [%0, {%2, %3}], [%1];"
               ::"l"(m), "r"(src), "r"(c0), "r"(c1) : "memory");
}
__device__ __forceinline__ void bulk_commit() { asm volatile("cp.async.bulk.commit_group;" ::: "memory"); }
__device__ __forceinline__ void bulk_wait_read() { asm volatile("cp.async.bulk.wait_group.read 0;" ::: "memory"); }
__device__ __forceinline__ void bulk_wait_all() { asm volatile("cp.async.bulk.wait_group 0;" ::: "memory"); }
__device__ __forceinline__ void fence_async_smem() { asm volatile("fence.proxy.async.shared::cta;" ::: "memory"); }
__device__ __forceinline__ void fence_async_global() { asm volatile("fence.proxy.async.global;" ::: "memory"); }
__device__ __forceinline__ void st_relaxed(uint32_t* p, uint32_t v) {
  asm volatile("st.relaxed.gpu.global.u32 [%0], %1;" ::"l"(p), "r"(v) : "memory");
}
__device__ __forceinline__ void st_msg(uint4* p, uint32_t a, uint32_t b, uint32_t c, uint32_t tag) {
  asm volatile("{\n.reg .b128 v;\nmov.b128 v, {%1, %2, %3, %4};\nst.relaxed.gpu.b128 [%0], v;\n}"
               ::"l"(p), "r"(a), "r"(b), "r"(c), "r"(tag) : "memory");
}
__device__ __forceinline__ void ld_msg(const uint4* p, uint32_t& a, uint32_t& b, uint32_t& c, uint32_t& tag) {
  asm volatile("{\n.reg .b128 v;\nld.relaxed.gpu.b128 v, [%4];\nmov.b128 {%0, %1, %2, %3}, v;\n}"
               : "=r"(a), "=r"(b), "=r"(c), "=r"(tag) : "l"(p) : "memory");
}
__device__ __forceinline__ bool elect_one() {
  uint32_t ok;
  asm volatile("{\n.reg .pred p;\nelect.sync _|p, 0xffffffff;\nselp.u32 %0, 1, 0, p;\n}" : "=r"(ok));
  return ok;
}
__device__ __forceinline__ int uniform(int v) { return __shfl_sync(0xffffffffu, v, 0); }
__device__ __forceinline__ uint32_t pack_bf16(float lo, float hi) {
  uint32_t r;
  asm("cvt.rn.bf16x2.f32 %0, %1, %2;" : "=r"(r) : "f"(hi), "f"(lo));
  return r;
}
__device__ __forceinline__ uint32_t prmt_u(uint32_t a, uint32_t sel) {
  uint32_t r;
  asm("prmt.b32 %0, %1, 0, %2;" : "=r"(r) : "r"(a), "r"(sel));
  return r;
}
__device__ __forceinline__ float prmt_f(uint32_t a, uint32_t sel) {
  float r;
  asm("{\n.reg .b32 t;\nprmt.b32 t, %1, 0, %2;\nmov.b32 %0, t;\n}" : "=f"(r) : "r"(a), "r"(sel));
  return r;
}
__device__ __forceinline__ float bf_lo(uint32_t v) { return __uint_as_float(v << 16); }
__device__ __forceinline__ float bf_hi(uint32_t v) { return __uint_as_float(v & 0xffff0000u); }
__device__ __forceinline__ void stsm4(uint32_t addr, uint32_t r0, uint32_t r1, uint32_t r2, uint32_t r3) {
  asm volatile("stmatrix.sync.aligned.m8n8.x4.shared.b16 [%0], {%1, %2, %3, %4};"
               ::"r"(addr), "r"(r0), "r"(r1), "r"(r2), "r"(r3) : "memory");
}
__device__ __forceinline__ void ldsm4(uint32_t addr, uint32_t& r0, uint32_t& r1, uint32_t& r2, uint32_t& r3) {
  asm volatile("ldmatrix.sync.aligned.m8n8.x4.shared.b16 {%0, %1, %2, %3}, [%4];"
               : "=r"(r0), "=r"(r1), "=r"(r2), "=r"(r3) : "r"(addr) : "memory");
}
__device__ __forceinline__ uint32_t movtrans(uint32_t a) {
  uint32_t d;
  asm volatile("movmatrix.sync.aligned.m8n8.trans.b16 %0, %1;" : "=r"(d) : "r"(a));
  return d;
}
__device__ __forceinline__ void mma16816(float (&c)[4], uint32_t a0, uint32_t a1, uint32_t a2, uint32_t a3, uint32_t b0, uint32_t b1) {
  asm volatile("mma.sync.aligned.m16n8k16.row.col.f32.bf16.bf16.f32 {%0,%1,%2,%3}, {%4,%5,%6,%7}, {%8,%9}, {%0,%1,%2,%3};"
               : "+f"(c[0]), "+f"(c[1]), "+f"(c[2]), "+f"(c[3])
               : "r"(a0), "r"(a1), "r"(a2), "r"(a3), "r"(b0), "r"(b1));
}
__device__ __forceinline__ float2 lds_f2(uint32_t a) {
  float2 v;
  asm volatile("ld.shared.v2.f32 {%0, %1}, [%2];" : "=f"(v.x), "=f"(v.y) : "r"(a) : "memory");
  return v;
}
__device__ __forceinline__ float4 lds_f4(uint32_t a) {
  float4 v;
  asm volatile("ld.shared.v4.f32 {%0, %1, %2, %3}, [%4];" : "=f"(v.x), "=f"(v.y), "=f"(v.z), "=f"(v.w) : "r"(a) : "memory");
  return v;
}
__device__ __forceinline__ float lds_f(uint32_t a) {
  float v;
  asm volatile("ld.shared.f32 %0, [%1];" : "=f"(v) : "r"(a) : "memory");
  return v;
}
__device__ __forceinline__ uint32_t lds_u(uint32_t a) {
  uint32_t v;
  asm volatile("ld.shared.u32 %0, [%1];" : "=r"(v) : "r"(a) : "memory");
  return v;
}
__device__ __forceinline__ void sts_f2(uint32_t a, float x, float y) {
  asm volatile("st.shared.v2.f32 [%0], {%1, %2};" ::"r"(a), "f"(x), "f"(y) : "memory");
}
__device__ __forceinline__ void sts_u4(uint32_t a, uint32_t x, uint32_t y, uint32_t z, uint32_t w) {
  asm volatile("st.shared.v4.u32 [%0], {%1, %2, %3, %4};" ::"r"(a), "r"(x), "r"(y), "r"(z), "r"(w) : "memory");
}
__device__ __forceinline__ void lds_u4(uint32_t a, uint32_t& x, uint32_t& y, uint32_t& z, uint32_t& w) {
  asm volatile("ld.shared.v4.u32 {%0, %1, %2, %3}, [%4];" : "=r"(x), "=r"(y), "=r"(z), "=r"(w) : "r"(a) : "memory");
}
__device__ __forceinline__ float ex2(float x) {
  float y;
  asm("ex2.approx.ftz.f32 %0, %1;" : "=f"(y) : "f"(x));
  return y;
}
__device__ __forceinline__ float rcp_hw(float x) {
  float y;
  asm("rcp.approx.ftz.f32 %0, %1;" : "=f"(y) : "f"(x));
  return y;
}
__device__ __forceinline__ float tanh_hw(float x) {
  float y;
  asm("tanh.approx.f32 %0, %1;" : "=f"(y) : "f"(x));
  return y;
}
__device__ __forceinline__ float quad_sum(float v) {
  v += __shfl_xor_sync(0xffffffffu, v, 1);
  return v + __shfl_xor_sync(0xffffffffu, v, 2);
}
__device__ __forceinline__ float quad_max(float v) {
  v = fmaxf(v, __shfl_xor_sync(0xffffffffu, v, 1));
  return fmaxf(v, __shfl_xor_sync(0xffffffffu, v, 2));
}

template <int N> __device__ __forceinline__ void wgmma_ss(float (&d)[96], uint64_t da, uint64_t db, uint32_t keep = 1);
template <> __device__ __forceinline__ void wgmma_ss<128>(float (&d)[96], uint64_t da, uint64_t db, uint32_t keep) {
  asm volatile(
      "{\n.reg .pred p;\nsetp.ne.u32 p, %66, 0;\n"
      "wgmma.mma_async.sync.aligned.m64n128k16.f32.bf16.bf16 {%0, %1, %2, %3, %4, %5, %6, %7, %8, %9, %10, %11, %12, %13, %14, %15, %16, %17, %18, %19, %20, %21, %22, %23, %24, %25, %26, %27, %28, %29, %30, %31, %32, %33, %34, %35, %36, %37, %38, %39, %40, %41, %42, %43, %44, %45, %46, %47, %48, %49, %50, %51, %52, %53, %54, %55, %56, %57, %58, %59, %60, %61, %62, %63}, %64, %65, p, 1, 1, 0, 1;\n}"
      : "+f"(d[0]), "+f"(d[1]), "+f"(d[2]), "+f"(d[3]), "+f"(d[4]), "+f"(d[5]), "+f"(d[6]), "+f"(d[7]), "+f"(d[8]), "+f"(d[9]), "+f"(d[10]), "+f"(d[11]), "+f"(d[12]), "+f"(d[13]), "+f"(d[14]), "+f"(d[15]), "+f"(d[16]), "+f"(d[17]), "+f"(d[18]), "+f"(d[19]), "+f"(d[20]), "+f"(d[21]), "+f"(d[22]), "+f"(d[23]), "+f"(d[24]), "+f"(d[25]), "+f"(d[26]), "+f"(d[27]), "+f"(d[28]), "+f"(d[29]), "+f"(d[30]), "+f"(d[31]), "+f"(d[32]), "+f"(d[33]), "+f"(d[34]), "+f"(d[35]), "+f"(d[36]), "+f"(d[37]), "+f"(d[38]), "+f"(d[39]), "+f"(d[40]), "+f"(d[41]), "+f"(d[42]), "+f"(d[43]), "+f"(d[44]), "+f"(d[45]), "+f"(d[46]), "+f"(d[47]), "+f"(d[48]), "+f"(d[49]), "+f"(d[50]), "+f"(d[51]), "+f"(d[52]), "+f"(d[53]), "+f"(d[54]), "+f"(d[55]), "+f"(d[56]), "+f"(d[57]), "+f"(d[58]), "+f"(d[59]), "+f"(d[60]), "+f"(d[61]), "+f"(d[62]), "+f"(d[63])
      : "l"(da), "l"(db), "r"(keep));
}

template <> __device__ __forceinline__ void wgmma_ss<192>(float (&d)[96], uint64_t da, uint64_t db, uint32_t keep) {
  asm volatile(
      "{\n.reg .pred p;\nsetp.ne.u32 p, %98, 0;\n"
      "wgmma.mma_async.sync.aligned.m64n192k16.f32.bf16.bf16 {%0, %1, %2, %3, %4, %5, %6, %7, %8, %9, %10, %11, %12, %13, %14, %15, %16, %17, %18, %19, %20, %21, %22, %23, %24, %25, %26, %27, %28, %29, %30, %31, %32, %33, %34, %35, %36, %37, %38, %39, %40, %41, %42, %43, %44, %45, %46, %47, %48, %49, %50, %51, %52, %53, %54, %55, %56, %57, %58, %59, %60, %61, %62, %63, %64, %65, %66, %67, %68, %69, %70, %71, %72, %73, %74, %75, %76, %77, %78, %79, %80, %81, %82, %83, %84, %85, %86, %87, %88, %89, %90, %91, %92, %93, %94, %95}, %96, %97, p, 1, 1, 0, 1;\n}"
      : "+f"(d[0]), "+f"(d[1]), "+f"(d[2]), "+f"(d[3]), "+f"(d[4]), "+f"(d[5]), "+f"(d[6]), "+f"(d[7]), "+f"(d[8]), "+f"(d[9]), "+f"(d[10]), "+f"(d[11]), "+f"(d[12]), "+f"(d[13]), "+f"(d[14]), "+f"(d[15]), "+f"(d[16]), "+f"(d[17]), "+f"(d[18]), "+f"(d[19]), "+f"(d[20]), "+f"(d[21]), "+f"(d[22]), "+f"(d[23]), "+f"(d[24]), "+f"(d[25]), "+f"(d[26]), "+f"(d[27]), "+f"(d[28]), "+f"(d[29]), "+f"(d[30]), "+f"(d[31]), "+f"(d[32]), "+f"(d[33]), "+f"(d[34]), "+f"(d[35]), "+f"(d[36]), "+f"(d[37]), "+f"(d[38]), "+f"(d[39]), "+f"(d[40]), "+f"(d[41]), "+f"(d[42]), "+f"(d[43]), "+f"(d[44]), "+f"(d[45]), "+f"(d[46]), "+f"(d[47]), "+f"(d[48]), "+f"(d[49]), "+f"(d[50]), "+f"(d[51]), "+f"(d[52]), "+f"(d[53]), "+f"(d[54]), "+f"(d[55]), "+f"(d[56]), "+f"(d[57]), "+f"(d[58]), "+f"(d[59]), "+f"(d[60]), "+f"(d[61]), "+f"(d[62]), "+f"(d[63]), "+f"(d[64]), "+f"(d[65]), "+f"(d[66]), "+f"(d[67]), "+f"(d[68]), "+f"(d[69]), "+f"(d[70]), "+f"(d[71]), "+f"(d[72]), "+f"(d[73]), "+f"(d[74]), "+f"(d[75]), "+f"(d[76]), "+f"(d[77]), "+f"(d[78]), "+f"(d[79]), "+f"(d[80]), "+f"(d[81]), "+f"(d[82]), "+f"(d[83]), "+f"(d[84]), "+f"(d[85]), "+f"(d[86]), "+f"(d[87]), "+f"(d[88]), "+f"(d[89]), "+f"(d[90]), "+f"(d[91]), "+f"(d[92]), "+f"(d[93]), "+f"(d[94]), "+f"(d[95])
      : "l"(da), "l"(db), "r"(keep));
}

template <int R>
__device__ __forceinline__ void pin_regs(float (&a)[2][96]) {
#pragma unroll
  for (int m = 0; m < 2; m++)
#pragma unroll
    for (int i = 0; i < R; i++) asm volatile("" : "+f"(a[m][i])::"memory");
}

struct Ctx {
  uint32_t sb;
  int m, n, wg, w, lane;
};
__device__ __forceinline__ Ctx make_ctx(uint32_t sb, int id) {
  int lane;
  asm volatile("mov.u32 %0, %%laneid;" : "=r"(lane));
  asm volatile("" : "+r"(id), "+r"(sb));
  return Ctx{sb, (id >> 3) & 15, id & 7, id >> 9, (id >> 7) & 3, lane};
}
#define UNPACK_CTX(c) const uint32_t sb = c.sb; const int m = c.m, n = c.n, wg = c.wg, w = c.w, lane = c.lane

__device__ __forceinline__ uint32_t poll_line(const uint32_t* word, uint32_t target, uint32_t need) {
  uint32_t v;
  asm volatile(
      "{\n.reg .pred p;\n.reg .u32 it, m;\n.reg .s32 d;\nmov.u32 it, 0;\n"
      "POLL_LOOP:\n"
      "ld.relaxed.gpu.global.u32 %0, [%1];\n"
      "sub.s32 d, %0, %2;\n"
      "setp.ge.s32 p, d, 0;\n"
      "vote.sync.ballot.b32 m, p, 0xffffffff;\n"
      "and.b32 m, m, %3;\n"
      "setp.eq.u32 p, m, %3;\n"
      "@p bra.uni POLL_DONE;\n"
      "add.u32 it, it, 1;\n"
      "setp.lt.u32 p, it, 0x400000;\n"
      "@p bra.uni POLL_LOOP;\n"
      "trap;\n"
      "POLL_DONE:\n}"
      : "=&r"(v) : "l"(word), "r"(target), "r"(need) : "memory");
  return v;
}
__device__ __forceinline__ uint32_t ld_relaxed(const uint32_t* p) {
  uint32_t v;
  asm volatile("ld.relaxed.gpu.global.u32 %0, [%1];" : "=r"(v) : "l"(p) : "memory");
  return v;
}
__device__ __forceinline__ float chain(float x, uint32_t on, uint32_t zero) {
  return __uint_as_float(__float_as_uint(x) | (on & zero));
}
constexpr int MSG_SPINS = 1 << 20;

constexpr int STAGES_PER_LAYER = 152;
__device__ __forceinline__ int nib(uint64_t v, int i) { return (int)(v >> (4 * i)) & 15; }
__device__ __forceinline__ bool tile_wide(int t) { return (0x23 >> t) & 1; }
__device__ __forceinline__ void weight_coords(const Params& p, int t, int n, const CUtensorMap*& map, int& c0, int& c2) {
  map = &p.wqkv + nib(0x4233100ull, t);
  c0 = t < 2 ? 128 * n + 64 * t : 0;
  c2 = t < 2 ? 0 : (t == 2 || t == 6) ? 2 * n : 7 * n + 2 * t - 6;
}

template <bool IS_A>
__device__ __forceinline__ void producer(const Params& p, uint32_t sb, int m, int n, int lane) {
  const uint32_t low = (1u << (4 * n)) - 1, others = (0x6543210u & low) | (0x7654321u & ~low);
  const uint64_t order_x = (uint64_t)(others * 2 + 0x1111111u) << 36 | (uint64_t)others * 2 << 8 | (n * 0x22 + 0x10);
  int inflight = 4, cur = 0;
  uint32_t fb = sb + BAR_FULL + 32, rb = sb + BAR_EMPTY, rph = 0, pos = 0, tag32 = 0, seen = 0;
  const uint32_t fend = sb + BAR_FULL + 8 * NBAR, rend = sb + BAR_EMPTY + 8 * NBAR;
  const uint32_t* word = p.g->flags + m * 32 + (lane < 16 ? lane >> 1 : lane & 7);
#pragma unroll 1
  for (int sg = 1; sg < 22; sg++) {
    const int layer = sg >= 11, s = sg == 1 ? 2 : sg == 2 ? 1 : sg - 11 * layer;
    const int t = nib(0x65434321010ull, s), kind = nib(0x32110031100ull, s);
    const bool wide = tile_wide(t);
    const uint32_t bbytes = wide ? 3 * UNIT : 2 * UNIT, base = sb + (IS_A ? bbytes : 0);
    const int mul = t == 6 ? 448 : t == 2 ? 128 : 64, count = sg == 1 ? 12 : 2 * nib(0x4871ull, kind);
    uint64_t order0 = sg == 1 ? 0xFEDCBA987654ull : kind == 3 ? 0x76543210u : order_x >> (8 * (kind & 1));
    uint32_t special = (s == 4 || s == 10) ? 0x10 : s == 9 ? 0xF : 1;
    if (IS_A) special |= (kind & 1 ? 0 : 3) | (count >= 4 ? 1u << (count - 4) : 0);
    if (s >= 9) pos = (s + 6) * UNIT;
    const CUtensorMap* map;
    int c0 = 0, c2 = 0, ev = 0;
    if (IS_A) {
      map = &p.xin + (t == 2 ? 2 : t == 6 ? 3 : sg >= 4);
      ev = 9 * layer + (t < 2 ? 0 : t == 2 ? 1 : t < 6 ? 4 : 5);
      if (sg == 2) seen = tag32 = (__ldcg(p.g->epoch + m * 8 + n) + 1) << 5;
    } else {
      weight_coords(p, t, n, map, c0, c2);
    }
#pragma unroll 1
    for (int add = 0; add < mul; add += 64) {
      uint64_t order = order0;
      const int need = kind == 3 ? ev : ev - 1 + (lane & 1), sh = kind == 3 ? 16 : 0;
      uint32_t ready = IS_A ? __ballot_sync(0xffffffffu, cur >= need) >> sh : 0;
#pragma unroll 1
      for (int k = 0; k < count; k++) {
        const int code = order & 15, kc = code * mul + add;
        order >>= 4;
        if ((special >> k) & 1) {
          const int lag = wide ? (s == 9 && k == 2 ? 2 : 3) : ((s == 4 || s == 10) && add == 0 && k < 4) ? 3 : 4;
#pragma unroll 1
          for (; inflight > lag; inflight--) {
            mbar_wait(rb, rph);
            rb += 8;
            if (rb == rend) { rb -= 8 * NBAR; rph ^= 1; }
          }
          inflight++;
          if (IS_A) {
            if (kind == 3 ? t == 2 && add + k == 64 : !(kind & 1) && k < 2) {
              if (t == 2) mbar_wait(sb + BAR_PUB + 8, layer);
              else if (k == 1 && (s == 0 || s == 5)) mbar_wait(sb + BAR_XRDY + 8, s == 5);
              if (elect_one()) mbar_arrive(fb);
              goto next_stage;
            }
            if (k == count - 4 && sg >= 3) seen = ld_relaxed(word);
          }
        } else {
          mbar_wait(rb, rph);
          rb += 8;
          if (rb == rend) { rb -= 8 * NBAR; rph ^= 1; }
        }
        if (IS_A && !((ready >> code) & 1)) {
          cur = max(cur, (int)(seen - tag32));
          ready = __ballot_sync(0xffffffffu, cur >= need) >> sh;
          if (!((ready >> code) & 1)) {
            cur = (int)(poll_line(word, tag32 + need, 1u << (code + sh)) - tag32);
            ready = __ballot_sync(0xffffffffu, cur >= need) >> sh;
          }
          asm volatile("fence.acquire.gpu;" ::: "memory");
          fence_async_global();
        }
        if (elect_one()) {
          if (!IS_A) tma_ld3(base + pos, map, fb, c0, kc, c2);
          else tma_ld2(base + pos, map, fb, kc, 128 * m);
          mbar_expect_tx(fb, IS_A ? 16384 : bbytes);
        }
      next_stage:
        fb += 8;
        if (fb == fend) fb -= 8 * NBAR;
        pos += bbytes + 2 * UNIT;
        if (pos >= RING_UNITS * UNIT) pos -= RING_UNITS * UNIT;
      }
      special = !IS_A ? 0 : t == 2 ? 1 : add == 128 ? 0x10 : 0;
      if (t == 2) order0 = others << 4 | n;
      if (IS_A && (t == 2 || add == 64 || add == 192)) ev++;
    }
  }
}

__device__ __forceinline__ void publisher(const Params& p, uint32_t sb, int m, int n) {
  const uint32_t tag = __ldcg(p.g->epoch + m * 8 + n) + 1;
  uint32_t* word = p.g->flags + m * 32 + n;
  const int mn = m * 8 + n; (void)mn;
  st_relaxed(word, 32 * tag);
#pragma unroll 1
  for (int c = 0; c < 18; c++) {
    const int e = c >= 9 ? c - 9 : c;
    if ((0x18C >> e) & 1) {
      const int half = (0x108 >> e) & 1;
      mbar_wait(sb + BAR_XRDY + 8 * half, e < 4);
#pragma unroll
      for (int w = 0; w < 4; w++) tma_st2(&p.out_st, sb + OFF_X + half * 16384 + w * 4096, 128 * n + 64 * half, 128 * m + 32 * w);
      bulk_commit();
      if (c >= 16) continue;
      bulk_wait_all();
      PROF_E(7 * (c >= 9) + (e < 4 ? 2 : 6), 11 + 2 * half);
    } else {
      mbar_wait(sb + BAR_PUB + 8 * e, c >= 9);
    }
    asm volatile("fence.release.gpu;" ::: "memory");
    st_relaxed(word, 32 * tag + c + 1);
    PROF_E(7 * (c >= 9) + nib(0x665432210ull, e), (0x108 >> e) & 1 ? 14 : 12);
  }
  p.g->epoch[m * 8 + n] = tag;
  bulk_wait_read();
}

__device__ __forceinline__ void sum_rows(uint32_t buf, int iters, float (&a)[8], int lane) {
  uint32_t addr = buf + (lane >> 3) * 128 + (((lane & 7) ^ (lane >> 3)) << 4);
#pragma unroll 1
  for (int it = 0; it < iters; it++) {
    uint32_t u[2][4];
    lds_u4(addr, u[0][0], u[0][1], u[0][2], u[0][3]);
    lds_u4((addr ^ 64) + 512, u[1][0], u[1][1], u[1][2], u[1][3]);
    addr += 1024;
#pragma unroll
    for (int e = 0; e < 8; e++) { a[2 * (e & 3)] += bf_lo(u[e >> 2][e & 3]); a[2 * (e & 3) + 1] += bf_hi(u[e >> 2][e & 3]); }
  }
}
__device__ __forceinline__ void publish_sums(const float (&a)[8], uint4* dst, int lane, uint32_t tag) {
  const bool u8 = lane & 8, u16 = lane & 16;
  float h4[4], h2[2];
#pragma unroll
  for (int e = 0; e < 4; e++) h4[e] = (u8 ? a[4 + e] : a[e]) + __shfl_xor_sync(0xffffffffu, u8 ? a[e] : a[4 + e], 8);
#pragma unroll
  for (int e = 0; e < 2; e++) h2[e] = (u16 ? h4[2 + e] : h4[e]) + __shfl_xor_sync(0xffffffffu, u16 ? h4[e] : h4[2 + e], 16);
  st_msg(dst + (lane & 7) * 4 + (u8 ? 2 : 0) + (u16 ? 1 : 0), __float_as_uint(h2[0]), __float_as_uint(h2[1]), 0u, tag);
}

__device__ __forceinline__ void colsum_helper(const Params& p, uint32_t sb, int m, int n, int lane) {
  const uint32_t tag = __ldcg(p.g->epoch + m * 8 + n) + 1;
  const int mn = m * 8 + n; (void)mn;
#pragma unroll 1
  for (int k = lane; k < 288; k += 32) {
    const uint32_t bb = __ldg(reinterpret_cast<const uint32_t*>(k < 224 ? p.b1 + 448 * n : p.b2 + 128 * n - 448) + k);
    const float sc = k < 224 ? 0.5f : 1.f;
    sts_f2(sb + (k < 224 ? OFF_CSF + k * 16 + 8 : OFF_CSQ + 1536 + (k - 224) * 8), sc * bf_lo(bb), sc * bf_hi(bb));
  }
  __syncwarp();
  if (elect_one()) mbar_arrive(sb + BAR_BIAS);
  bar_sync(BAR_HLP, 160);
  PROF_E(-1, 1);
#pragma unroll 1
  for (int c = 0; c < 7; c++) {
    float a[8] = {0.f, 0.f, 0.f, 0.f, 0.f, 0.f, 0.f, 0.f};
#pragma unroll 1
    for (int h = 0; h < 2; h++) {
      if (elect_one()) {
        mbar_expect_tx(sb + BAR_CSLD + 8, 4096);
        tma_ld2(sb + OFF_HLP, &p.w1c, sb + BAR_CSLD + 8, 448 * n + 64 * c, 64 * m + 32 * h);
        if (c < 6) asm volatile("cp.async.bulk.prefetch.tensor.2d.L2.global [%0, {%1, %2}];" ::"l"(&p.w1c), "r"(448 * n + 64 * c + 64), "r"(64 * m + 32 * h) : "memory");
      }
      mbar_wait(sb + BAR_CSLD + 8, h);
      sum_rows(sb + OFF_HLP, 4, a, lane);
      __syncwarp();
    }
    publish_sums(a, p.g->csp + ((8 + n) * 17 + m) * 224 + c * 32, lane, tag);
  }
  PROF_E(-1, 2);
}

__device__ __forceinline__ void poll_msgs2(const uint4* pa, const uint4* pb, float (&v)[4], uint32_t tag) {
#pragma unroll 1
  for (int it = 0; it < MSG_SPINS; it++) {
    uint32_t x[4], z, ta, tb;
    ld_msg(pa, x[0], x[1], z, ta);
    ld_msg(pb, x[2], x[3], z, tb);
#pragma unroll
    for (int e = 0; e < 4; e++) v[e] = __uint_as_float(x[e]);
    if (__all_sync(0xffffffffu, ta == tag && tb == tag)) break;
  }
}
__device__ __forceinline__ void colsum_total(const Params& p, const Ctx& cx, int mat, uint32_t tag) {
  uint4* base = p.g->csp + (mat * 8 + cx.n) * 17 * 224;
  const int per = 12 + 2 * mat, k = 2 * cx.w + (cx.lane >> 4), ia = per * cx.m + k, ib = per * cx.m + min(k + 8, per - 1);
  float v[4];
  poll_msgs2(base + (cx.lane & 15) * 224 + ia, base + (cx.lane & 15) * 224 + ib, v, tag);
#pragma unroll 1
  for (int d = 1; d < 16; d *= 2)
#pragma unroll
    for (int e = 0; e < 4; e++) v[e] += __shfl_xor_sync(0xffffffffu, v[e], d);
  const bool hi = cx.lane & 1;
  if ((cx.lane & 14) == 0) st_msg(base + 16 * 224 + (hi ? ib : ia), __float_as_uint(hi ? v[2] : v[0]), __float_as_uint(hi ? v[3] : v[1]), 0u, tag);
}
__device__ __forceinline__ void colsum_gather(const Params& p, const Ctx& cx, int mat, uint32_t tag) {
  const uint4* base = p.g->csp + ((mat * 8 + cx.n) * 17 + 16) * 224;
  const int ia = cx.w * 32 + cx.lane, ib = min(ia + 128, 191 + 32 * mat);
  float v[4];
  poll_msgs2(base + ia, base + ib, v, tag);
  const uint32_t tab = cx.sb + (mat ? OFF_CSF : OFF_CSQ);
  sts_f2(tab + (ia << (3 + mat)), v[0], v[1]);
  sts_f2(tab + (ib << (3 + mat)), v[2], v[3]);
}

constexpr uint32_t RING16 = RING_UNITS * (UNIT >> 4);
__device__ __forceinline__ bool tile_split(int i) { return (0xD98 >> i) & 1; }

__device__ __forceinline__ void write_run_desc(uint32_t sb, int i, int step) {
  const int layer = i >= 7, t = i - 7 * layer, part = tile_split(i) ? step : 2;
  const bool wide = tile_wide(t), own = t != 2 && t != 6 && part != 1 && i != 0, second = t == 1 || t == 4;
  const uint32_t z16 = (wide ? 5 : 4) * (UNIT >> 4), a_off = z16 - 1024 + (uint32_t)DESC_A - (uint32_t)DESC_B;
  const int gl = 16 * t + (part == 2 ? 0 : second ? 16 * part - 14 : 4 * part), g0 = layer * STAGES_PER_LAYER + gl;
  const uint32_t s16 = (sb & 0x3FFFF) >> 4, bfirst = (uint32_t)DESC_B + s16;
  const int nkb = t == 6 ? 56 : part == 0 ? 2 : 12 + 2 * part;
  const bool win1 = t == 1 && part != 0;
  const int run = win1 ? WIN1 + 1 : t == 2 ? WIN2 + 1 : nkb;
  const int rest = win1 ? 64 | (nkb - 1 - WIN1) : t == 2 ? 64 | (7 - WIN2) | (8 << 7) : 0;
  const uint32_t blo = bfirst + z16 * (wide ? (gl + (t == 5 ? 3 : 0)) & 3 : (gl + 3) % 5);
  const uint32_t alo = own ? (uint32_t)DESC_A + s16 + (OFF_X >> 4) : blo + a_off;
  const uint32_t aoff = own ? alo + 1024 - (blo == bfirst + RING16 - z16 ? bfirst : blo + z16) : a_off;
  const bool xwait = part == 0 && !second, keep = !(part == 0 || t == 5);
  sts_u4(sb + OFF_RUN + (2 * i + step) * 16, blo, alo, aoff,
         ((g0 / NBAR) & 1) | xwait << 1 | keep << 2 | 8 * (g0 % NBAR) | run << 6 | rest << 12);
}

template <int N>
__device__ __forceinline__ void mainloop(float (&acc)[2][96], uint32_t sb, int i, int step, int mn) {
  constexpr uint32_t Z16 = (2 + N / 64) * (UNIT >> 4);
  constexpr uint32_t A_OFF = Z16 - 1024 + (uint32_t)DESC_A - (uint32_t)DESC_B;
  const int wg = i & 1;
  const uint32_t s16 = (sb & 0x3FFFF) >> 4;
  const uint32_t blast = (uint32_t)DESC_B + s16 + RING16 - Z16, flast = sb + BAR_FULL + 8 * (NBAR - 1);
  uint32_t blo = (uint32_t)DESC_B + s16, alo = blo + A_OFF, aoff = A_OFF, misc = 16 << 6;
  if (N == 128 || i > 0) lds_u4(sb + OFF_RUN + (2 * i + step) * 16, blo, alo, aoff, misc);
  uint32_t keep = misc & 4;
  int run = (misc >> 6) & 63, rest = misc >> 12;
  uint32_t fb = sb + BAR_FULL + (misc & 0x38), ph = misc & 1;
  uint32_t prev = sb + BAR_DUMMY - 8 * NBAR;
  pin_regs<N / 2>(acc);
  if (N == 128 || i > 0) bar_sync(BAR_ORDER + wg, 256);
  else bar_sync(BAR_INIT0, 160);
  if (N == 192 && i == 0 && threadIdx.x == 0) PROF_U(8);
  mbar_wait(fb, ph);
  if (misc & 2) mbar_wait(sb + BAR_XRDY, N == 128);
  if (step == 0 || !tile_split(i)) PROF_T(4 + i * 4);
#pragma unroll 1
  while (true) {
    const uint64_t da = (DESC_A & ~0xffffffffull) | alo, db = (DESC_B & ~0xffffffffull) | blo;
    asm volatile("wgmma.fence.sync.aligned;" ::: "memory");
    wgmma_ss<N>(acc[0], da, db, keep);
    wgmma_ss<N>(acc[1], da + 64, db, keep);
    keep = 4;
    wgmma_ss<N>(acc[0], da + 2, db + 128);
    wgmma_ss<N>(acc[1], da + 66, db + 128);
    asm volatile("wgmma.commit_group.sync.aligned;" ::: "memory");
    asm volatile("wgmma.wait_group.sync.aligned 1;" ::: "memory");
    PROF_S(jj++);
    if (elect_one()) mbar_arrive(prev + 8 * NBAR);
    prev = fb;
    if (fb == flast) { fb -= 8 * NBAR; ph++; }
    fb += 8;
    if (blo == blast) blo -= RING16;
    blo += Z16;
    alo = blo + aoff;
    aoff = A_OFF;
    run--;
    const bool ready = mbar_test(fb, ph) && run != 0;
    asm volatile("wgmma.fence.sync.aligned;" ::: "memory");
    wgmma_ss<N>(acc[0], da + 4, db + 256);
    wgmma_ss<N>(acc[1], da + 68, db + 256);
    wgmma_ss<N>(acc[0], da + 6, db + 384);
    wgmma_ss<N>(acc[1], da + 70, db + 384);
    asm volatile("wgmma.commit_group.sync.aligned;" ::: "memory");
    if (!ready) {
      if (run == 0) {
        if (rest == 0) break;
        if (rest & 64) {
          bar_arrive(BAR_GO, 256);
          bar_sync(BAR_DONE, 256);
        } else {
          alo = (uint32_t)DESC_A + s16 + (OFF_STG >> 4);
        }
        run = rest & 63;
        rest >>= 7;
      }
      mbar_wait(fb, ph);
    }
  }
  if (i < 13) bar_arrive(BAR_ORDER + (wg ^ 1), 256);
  asm volatile("wgmma.wait_group.sync.aligned 0;" ::: "memory");
  pin_regs<N / 2>(acc);
  if (elect_one()) mbar_arrive(prev + 8 * NBAR);
  PROF_T(5 + i * 4);
  PROF_E(i, 0);
}

#define ACC(q, j, e) acc[(q) & 1][4 * (j) + 2 * ((q) >> 1) + (e)]

__device__ __forceinline__ void write_partial_stats(const Params& p, const Ctx& c, int ln, uint32_t tag) {
  const uint32_t xrow = c.sb + OFF_X + c.w * 4096 + c.lane * 128;
  float s = 0.f, q = 0.f, s1 = 0.f, q1 = 0.f;
#pragma unroll 2
  for (int j = 0; j < 16; j++) {
    uint32_t u[4];
    lds_u4(xrow + (j >> 3) * 16384 + (((j & 7) ^ (c.lane & 7)) << 4), u[0], u[1], u[2], u[3]);
#pragma unroll
    for (int e = 0; e < 4; e++) {
      const float a = bf_lo(u[e]), d = bf_hi(u[e]);
      s += a; q = fmaf(a, a, q);
      s1 += d; q1 = fmaf(d, d, q1);
    }
  }
  s += s1;
  q += q1;
  st_msg(p.g->stats + (ln * 8 + c.n) * SEQ + 128 * c.m + 32 * c.w + c.lane, __float_as_uint(s),
         __float_as_uint(fmaxf(q - s * s * (1.f / 128.f), 0.f)), 0u, tag);
}

__device__ __forceinline__ void finish_row_stats(const Params& p, const Ctx& c, int ln, uint32_t tag) {
  const uint4* src = p.g->stats + ln * 8 * SEQ + 128 * c.m + 32 * c.w + c.lane;
  uint32_t ps[8], pm[8];
#pragma unroll 1
  for (int it = 0; it < MSG_SPINS; it++) {
    uint32_t bad = 0, u, tg;
#pragma unroll
    for (int k = 0; k < 8; k++) { ld_msg(src + k * SEQ, ps[k], pm[k], u, tg); bad |= tg ^ tag; }
    if (__all_sync(0xffffffffu, bad == 0)) break;
  }
  float s = 0.f, m2 = 0.f;
#pragma unroll
  for (int k = 0; k < 8; k++) s += __uint_as_float(ps[k]);
  const float mean = s * (1.f / DM);
#pragma unroll
  for (int k = 0; k < 8; k++) {
    const float d = __uint_as_float(ps[k]) * (1.f / 128.f) - mean;
    m2 += fmaf(128.f * d, d, __uint_as_float(pm[k]));
  }
  sts_f2(c.sb + OFF_ROW + (32 * c.w + c.lane) * 8, rsqrtf(m2 * (1.f / DM) + 1e-5f), mean);
  __syncwarp();
}

__device__ __forceinline__ void attn_scores(const uint32_t* qa, const uint32_t* qb, const uint32_t* k0, const uint32_t* k1,
                                            const uint32_t* k2, const uint32_t* k3, float (&l)[4], const float4& zero,
                                            bool par, bool early) {
  float s[4][4];
#pragma unroll
  for (int kb = 0; kb < 4; kb++) {
    const uint32_t* kk = kb == 0 ? k0 : kb == 1 ? k1 : kb == 2 ? k2 : k3;
    asm volatile("mma.sync.aligned.m16n8k16.row.col.f32.bf16.bf16.f32 {%0,%1,%2,%3}, {%4,%5,%6,%7}, {%8,%9}, {%10,%11,%12,%13};"
                 : "=f"(s[kb][0]), "=f"(s[kb][1]), "=f"(s[kb][2]), "=f"(s[kb][3])
                 : "r"(qa[0]), "r"(qb[0]), "r"(qa[1]), "r"(qb[1]), "r"(kk[0]), "r"(kk[1]), "f"(zero.x), "f"(zero.y),
                   "f"(zero.z), "f"(zero.w));
  }
#pragma unroll
  for (int kb = 0; kb < 4; kb++) {
    const uint32_t* kk = kb == 0 ? k0 : kb == 1 ? k1 : kb == 2 ? k2 : k3;
    mma16816(s[kb], qa[2], qb[2], qa[3], qb[3], kk[2], kk[3]);
  }
  l[0] = par ? s[1][1] : s[1][0];
  l[1] = early ? (par ? s[0][1] : s[0][0]) : (par ? s[2][1] : s[2][0]);
  l[2] = par ? s[2][3] : s[2][2];
  l[3] = early ? (par ? s[1][3] : s[1][2]) : (par ? s[3][3] : s[3][2]);
}

__device__ __forceinline__ void attn_mix(const float (&l)[4], const float (&sc)[4], const float (&off)[4], const float (&rk)[4],
                                         const uint32_t* v0, const uint32_t* v1, const uint32_t* v2, const uint32_t* v3,
                                         uint32_t* olo, uint32_t* ohi, const uint32_t (&sel)[4]) {
  float x[4];
#pragma unroll
  for (int e = 0; e < 4; e++) x[e] = fmaf(l[e], sc[e], off[e]);
  const float ml = quad_max(fmaxf(x[0], x[1])), mh = quad_max(fmaxf(x[2], x[3]));
  x[0] = ex2(x[0] - ml); x[1] = ex2(x[1] - ml);
  x[2] = ex2(x[2] - mh); x[3] = ex2(x[3] - mh);
  const uint32_t pl = pack_bf16(x[0] * rk[0], x[1] * rk[1]), ph = pack_bf16(x[2] * rk[2], x[3] * rk[3]);
  const uint32_t a0 = prmt_u(pl, sel[1]), a1 = prmt_u(pl, sel[3]), a2 = prmt_u(pl, sel[0]), a3 = prmt_u(ph, sel[1]);
  const uint32_t c0 = prmt_u(pl, sel[2]), c1 = prmt_u(ph, sel[0]), c2 = prmt_u(ph, sel[3]), c3 = prmt_u(ph, sel[2]);
  float o[4][4];
#pragma unroll
  for (int jn = 0; jn < 4; jn++) {
    o[jn][0] = o[jn][1] = o[jn][2] = o[jn][3] = 0.f;
    mma16816(o[jn], a0, a1, a2, a3, v0[jn], v1[jn]);
  }
#pragma unroll
  for (int jn = 0; jn < 4; jn++) mma16816(o[jn], c0, c1, c2, c3, v2[jn], v3[jn]);
  const float il = rcp_hw(quad_sum(x[0] + x[1])), ih = rcp_hw(quad_sum(x[2] + x[3]));
#pragma unroll
  for (int jn = 0; jn < 4; jn++) {
    olo[jn] = pack_bf16(o[jn][0] * il, o[jn][1] * il);
    ohi[jn] = pack_bf16(o[jn][2] * ih, o[jn][3] * ih);
  }
}

__device__ __forceinline__ void gelu_epilogue(const Params& p, float (&acc)[2][96], const Ctx& cx, int t) {
  UNPACK_CTX(cx);
  (void)wg;
  float rs[4], rm[4];
#pragma unroll
  for (int q = 0; q < 4; q++) {
    const float2 v = lds_f2(sb + OFF_ROW + (32 * w + 8 * q + (lane >> 2)) * 8);
    rs[q] = 0.5f * v.x;
    rm[q] = -rs[q] * v.y;
  }
  const int col0 = 128 * (t - 3), steps = t == 5 ? 6 : 4;
  const uint32_t stg = sb + OFF_STG + w * 4096;
  uint32_t ctab = sb + OFF_CSF + (col0 / 2 + (lane & 3)) * 16, srow = stg + lane * 128 + ((lane & 7) << 4);
  float v[2][16];
#define PULL(k) _Pragma("unroll") for (int j = 0; j < 4; j++) { \
      const float2 bb = lds_f2(ctab + j * 64 + 8); \
      _Pragma("unroll") for (int r = 0; r < 8; r++) \
        asm volatile("fma.rn.f32 %0, %1, %2, %3;" : "=f"(v[r >> 2][4 * j + (r & 3)]) \
                     : "f"(acc[r >> 2][16 * k + 4 * j + (r & 3)]), "f"(rs[(r >> 2) + (r & 2)]), "f"(r & 1 ? bb.y : bb.x)); }
  PULL(0)
#pragma unroll 1
  for (int it = 0;; it++) {
    uint32_t hp[4][4];
#pragma unroll
    for (int j = 0; j < 4; j++) {
      const float2 cs = lds_f2(ctab + j * 64);
#pragma unroll
      for (int q = 0; q < 4; q++) {
        float y[2];
        const int k = 4 * j + q - GELU_DEP;
        const float rmq = k >= 0 ? chain(rm[q], hp[k >> 2][k & 3], p.zero) : rm[q];
#pragma unroll
        for (int e = 0; e < 2; e++) {
          const float z = fmaf(rmq, e ? cs.y : cs.x, v[q & 1][4 * j + 2 * (q >> 1) + e]);
          const float u = z * fmaf(z * z, 8.f * 0.7978845608028654f * 0.044715f, 2.f * 0.7978845608028654f);
          y[e] = fmaf(z, tanh_hw(u), z);
        }
        hp[j][q] = pack_bf16(y[0], y[1]);
      }
    }
    ctab += 256;
    if (!(it & 1)) {
      if (lane == 0) bulk_wait_read();
      __syncwarp();
    }
#pragma unroll
    for (int j = 0; j < 4; j++) stsm4(srow ^ (j << 4), hp[j][0], hp[j][1], hp[j][2], hp[j][3]);
    srow ^= 64;
    if (it & 1) {
      fence_async_smem();
      __syncwarp();
      if (lane == 0) {
        tma_st2(&p.h_st, stg, 448 * n + col0 + 32 * (it - 1), 128 * m + 32 * w);
        bulk_commit();
      }
      if (it == steps - 1) break;
    }
    if (it & 1) {
      if (it & 2) { PULL(4) } else { PULL(2) }
    } else if (it & 2) {
      PULL(3)
    } else {
      if (it & 4) { PULL(5) } else { PULL(1) }
    }
  }
#undef PULL
#pragma unroll
  for (int r = 0; r < 16; r++) acc[0][r] = acc[1][r] = 0.f;
}

__device__ __forceinline__ void attn_epilogue(const Params& p, float (&acc)[2][96], const Ctx& cx, int layer, int t, uint32_t tag) {
  UNPACK_CTX(cx);
  const bool par = (lane >> 2) & 1, early = (lane & 3) > (lane >> 3);
  const uint32_t ktab = sb + OFF_ROW + (32 * w + 2 * (lane & 3) + par) * 8, exc = sb + OFF_STG + w * 4096 + lane * 16;
  const int slot = ((layer * 2 + t) * 16 + m) * 8 + n;
  const int mn = m * 8 + n; (void)mn;
  uint32_t Q[4][8], K[4][8], V[4][8], E[36], P[36];
  float kr[6], qr[4];
#pragma unroll
  for (int q = 2; q < 4; q++) {
    kr[2 + q] = lds_f(ktab + 64 * q);
#pragma unroll
    for (int j = 0; j < 8; j++) {
      E[8 * (q - 2) + j] = K[q][j] = pack_bf16(ACC(q, 8 + j, 0), ACC(q, 8 + j, 1));
      E[16 + 2 * j + q - 2] = V[q][j] = movtrans(pack_bf16(ACC(q, 16 + j, 0), ACC(q, 16 + j, 1)));
    }
  }
  E[32] = __float_as_uint(kr[4]);
  E[33] = E[34] = E[35] = __float_as_uint(kr[5]);
  if (w < 3) {
#pragma unroll
    for (int k = 0; k < 8; k++) sts_u4(exc + k * 512, E[4 * k], E[4 * k + 1], E[4 * k + 2], E[4 * k + 3]);
  } else {
#pragma unroll
    for (int k = 0; k < 12; k++) st_msg(p.g->halo + slot * 384 + k * 32 + lane, E[3 * k], E[3 * k + 1], E[3 * k + 2], tag);
  }
  PROF_E(7 * layer + t, 1);
#pragma unroll
  for (int q = 0; q < 4; q++) {
    qr[q] = lds_f(sb + OFF_ROW + (32 * w + 8 * q + (lane >> 2)) * 8) * (0.17677669529663687f * 1.4426950408889634f);
#pragma unroll
    for (int j = 0; j < 8; j++) Q[q][j] = pack_bf16(ACC(q, j, 0), ACC(q, j, 1));
    if (q < 2) {
      kr[2 + q] = lds_f(ktab + 64 * q);
#pragma unroll
      for (int j = 0; j < 8; j++) {
        K[q][j] = pack_bf16(ACC(q, 8 + j, 0), ACC(q, 8 + j, 1));
        V[q][j] = movtrans(pack_bf16(ACC(q, 16 + j, 0), ACC(q, 16 + j, 1)));
      }
    }
  }
  bar_sync(BAR_WG + wg, 128);
  if (w > 0 || m == 0) {
    const uint32_t back = w > 0;
#pragma unroll
    for (int k = 0; k < 8; k++) lds_u4(exc - back * 4096 + k * 512, P[4 * k], P[4 * k + 1], P[4 * k + 2], P[4 * k + 3]);
    P[32] = lds_u(ktab - back * 128);
    P[33] = lds_u(ktab - back * 64);
  } else {
#pragma unroll 1
    for (int it = 0; it < MSG_SPINS; it++) {
      uint32_t tg, bad = 0;
#pragma unroll
      for (int k = 0; k < 12; k++) {
        ld_msg(p.g->halo + (slot - 8) * 384 + k * 32 + lane, P[3 * k], P[3 * k + 1], P[3 * k + 2], tg);
        bad |= tg ^ tag;
      }
      if (__all_sync(0xffffffffu, bad == 0)) break;
    }
  }
  kr[0] = __uint_as_float(P[32]);
  kr[1] = __uint_as_float(P[33]);
  uint32_t PV[2][8];
#pragma unroll
  for (int j = 0; j < 8; j++) { PV[0][j] = P[16 + 2 * j]; PV[1][j] = P[17 + 2 * j]; }
  float rk[2][4], sc[2][4], off[2][4];
#pragma unroll
  for (int g = 0; g < 2; g++) {
    rk[g][0] = kr[2 * g + 1];
    rk[g][1] = early ? kr[2 * g] : kr[2 * g + 2];
    rk[g][2] = kr[2 * g + 2];
    rk[g][3] = early ? kr[2 * g + 1] : kr[2 * g + 3];
#pragma unroll
    for (int e = 0; e < 4; e++) {
      const bool masked = g == 0 && e != 2 && (m | w) == 0 && (e == 0 || early);
      sc[g][e] = masked ? 0.f : rk[g][e] * qr[2 * g + (e >> 1)];
      off[g][e] = masked ? -1e30f : 0.f;
    }
  }
  const uint32_t none = 0x4444u | p.zero, second = par ? 0x3244u : 0x4432u;
  const uint32_t sel[4] = {par ? 0x1044u : 0x4410u, early ? second : none, early ? none : second, none};
  PROF_E(7 * layer + t, 2);
  bar_sync(BAR_GO, 256);
  const float4 zero = lds_f4(sb + OFF_ZERO);
  float l[2][2][4];
  uint32_t O[4][8];
#pragma unroll
  for (int h = 0; h < 2; h++) {
    if (h == 1) {
      Q[2][4] |= __float_as_uint(l[1][0][0]) & p.zero;
      Q[0][4] |= __float_as_uint(l[0][0][0]) & p.zero;
    }
    attn_scores(&Q[2][4 * h], &Q[3][4 * h], &K[0][4 * h], &K[1][4 * h], &K[2][4 * h], &K[3][4 * h], l[1][h], zero, par, early);
    attn_scores(&Q[0][4 * h], &Q[1][4 * h], &P[4 * h], &P[8 + 4 * h], &K[0][4 * h], &K[1][4 * h], l[0][h], zero, par, early);
  }
  const uint32_t stg = sb + OFF_STG + w * 4096, srow = stg + lane * 128 + ((lane & 7) << 4);
#pragma unroll
  for (int h = 0; h < 2; h++) {
    attn_mix(l[1][h], sc[1], off[1], rk[1], &V[0][4 * h], &V[1][4 * h], &V[2][4 * h], &V[3][4 * h], &O[2][4 * h], &O[3][4 * h], sel);
    attn_mix(l[0][h], sc[0], off[0], rk[0], &PV[0][4 * h], &PV[1][4 * h], &V[0][4 * h], &V[1][4 * h], &O[0][4 * h], &O[1][4 * h], sel);
#pragma unroll
    for (int j = 4 * h; j < 4 * h + 4; j++) stsm4(srow ^ (j << 4), O[0][j], O[1][j], O[2][j], O[3][j]);
  }
  bar_arrive(BAR_DONE, 256);
  fence_async_smem();
  __syncwarp();
  if (lane == 0) {
    tma_st2(&p.att_st, stg, 128 * n + 64 * t, 128 * m + 32 * w);
    bulk_commit();
  }
}

__device__ __forceinline__ void finish_stores(uint32_t sb, int i) {
  const int t = i >= 7 ? i - 7 : i;
  if ((threadIdx.x & 31) == 0) {
    bulk_wait_all();
    mbar_arrive(sb + BAR_PUB + 8 * (t < 2 ? t : t + 1));
  }
  __syncwarp();
  if (i < 12) bar_arrive(BAR_GUARD + ((i & 1) ^ 1), 256);
}

__device__ __forceinline__ bool consumer_tile(const Params& p, float (&acc)[2][96], uint32_t sb0, int i, int mn) {
  const int layer = i >= 7, t = i - 7 * layer, wg = i & 1;
  const bool resid = t == 2 || t == 6;
  {
    if (resid) {
      const Ctx cx = make_ctx(sb0, mn);
      const uint32_t xrow = cx.sb + OFF_X + cx.w * 4096 + cx.lane * 128;
      const uint32_t sel_lo = 0x1044u | p.zero, sel_hi = 0x3244u | p.zero;
#pragma unroll
      for (int j = 0; j < 16; j++) {
        uint32_t r[4];
        ldsm4(xrow + (j >> 3) * 16384 + (((j & 7) ^ (cx.lane & 7)) << 4), r[0], r[1], r[2], r[3]);
#pragma unroll
        for (int q = 0; q < 4; q++) {
          ACC(q, j, 0) = prmt_f(r[q], sel_lo);
          ACC(q, j, 1) = prmt_f(r[q], sel_hi);
        }
      }
    }
    if (t >= 5 || i == 7) finish_stores(sb0, i - 2);
#pragma unroll 1
    for (int step = !tile_split(i);; step++) {
      if (step == 1 && (t == 1 || t == 4)) {
        const Ctx cx = make_ctx(sb0, mn);
        if (i == 1) {
          const uint32_t epoch = __ldcg(p.g->epoch + (mn & 127));
          bar_sync(BAR_INIT, 256);
          asm volatile("st.shared.u32 [%0], %1;" ::"r"(sb0 + OFF_TAG), "r"(epoch + 1) : "memory");
        }
        const uint32_t tag = lds_u(cx.sb + OFF_TAG);
        const int ln = (i + 1) >> 2;
#pragma unroll 1
        for (int r = 0; r < 2; r++) {
          if (i == 1) {
            if (cx.w < 3) {
              float a[8] = {0.f, 0.f, 0.f, 0.f, 0.f, 0.f, 0.f, 0.f};
              mbar_wait(sb0 + BAR_CSLD, r);
              sum_rows(cx.sb + OFF_STG + cx.w * 8192, 8, a, cx.lane);
              publish_sums(a, p.g->csp + (cx.n * 17 + cx.m) * 224 + (3 * r + cx.w) * 32, cx.lane, tag);
            }
            PROF_E(-1, 5 + r);
          }
          if (r == 1) break;
          if (i == 1) {
            bar_sync(BAR_WG + 1, 128);
            if (cx.w == 3 && elect_one()) {
              mbar_expect_tx(sb0 + BAR_CSLD, 24576);
              tma_ld3(sb0 + OFF_STG, &p.wqkv, sb0 + BAR_CSLD, 128 * cx.n + 64, 64 * cx.m, 0);
            }
            mbar_wait(sb0 + BAR_XRDY, 0);
            mbar_wait(sb0 + BAR_XRDY + 8, 0);
          }
          write_partial_stats(p, cx, ln, tag);
          PROF_E(i - 2, 8);
        }
        if (i == 1) bar_arrive(BAR_HLP, 160);
        if (i <= 4) colsum_total(p, cx, ln, tag);
        PROF_E(i - 2, 9);
        if (i != 1) bar_sync(BAR_GUARD + wg, 256);
        finish_row_stats(p, cx, ln, tag);
        PROF_E(i - 2, 10);
        if (i <= 4) {
          colsum_gather(p, cx, ln, tag);
          if (i == 4) mbar_wait(sb0 + BAR_BIAS, 0);
          bar_sync(BAR_WG + wg, 128);
        }
        PROF_E(i - 2, 15);
        bar_arrive(BAR_GUARD + (wg ^ 1), 256);
      }
      if (step == 2 && !resid) bar_sync(BAR_GUARD + wg, 256);
      if (t + step == 2 || t == 6) {
        const Ctx cx = make_ctx(sb0, mn);
        float nm[4];
#pragma unroll
        for (int q = 0; q < 4; q++) nm[q] = t == 6 ? 1.f : -lds_f(cx.sb + OFF_ROW + (32 * cx.w + 8 * q + (cx.lane >> 2)) * 8 + 4);
        const uint32_t ctab = cx.sb + OFF_CSQ + ((t & 3) * 192 + 2 * (cx.lane & 3)) * 4;
#pragma unroll
        for (int j = 0; j < 24; j++) {
          const float2 cs = lds_f2(ctab + j * 32);
#pragma unroll
          for (int q = 0; q < 4; q++) {
            const int k = 4 * j + q - 1;
            const float nq = k >= 0 ? chain(nm[q], __float_as_uint(ACC(k & 3, k >> 2, 1)), p.zero) : nm[q];
            ACC(q, j, 0) = fmaf(nq, cs.x, ACC(q, j, 0));
            ACC(q, j, 1) = fmaf(nq, cs.y, ACC(q, j, 1));
          }
        }
      }
      if (step == 2) break;
      if (tile_wide(t)) {
        mainloop<192>(acc, sb0, i, step, mn);
      } else {
        mainloop<128>(acc, sb0, i, step, mn);
        if (resid) break;
      }
    }
    if (t < 2) return true;
    const Ctx cx = make_ctx(sb0, mn);
    if (resid) {
      const uint32_t xrow = cx.sb + OFF_X + cx.w * 4096 + cx.lane * 128;
#pragma unroll
      for (int j = 0; j < 16; j++) {
        stsm4(xrow + (j >> 3) * 16384 + (((j & 7) ^ (cx.lane & 7)) << 4), pack_bf16(ACC(0, j, 0), ACC(0, j, 1)),
              pack_bf16(ACC(1, j, 0), ACC(1, j, 1)), pack_bf16(ACC(2, j, 0), ACC(2, j, 1)), pack_bf16(ACC(3, j, 0), ACC(3, j, 1)));
        if ((j & 7) == 7) {
          fence_async_smem();
          __syncwarp();
          if (elect_one()) mbar_arrive(sb0 + BAR_XRDY + (j & 8));
        }
      }
      PROF_E(i, 4);
      return false;
    }
    gelu_epilogue(p, acc, cx, t);
    PROF_E(i, 4);
    return false;
  }
}

__global__ void __launch_bounds__(384, 1) fused_layers_kernel(const int by_smid, const __nv_bfloat16* x_p, const __nv_bfloat16* wqkv_p,
                                                                  const __grid_constant__ Params p) {
  extern __shared__ __align__(1024) uint8_t smem_raw[];
  const uint32_t sb = uniform((uint32_t)__cvta_generic_to_shared(smem_raw));
  const int tid = threadIdx.x, lane = tid & 31, warp = uniform(tid >> 5), wg = warp >> 2, w = warp & 3;

  int mn;
  {
    int id = blockIdx.x;
    if (by_smid) asm volatile("mov.u32 %0, %%smid;" : "=r"(id));
    else if (id >= 120) id += 4;
    const int c = id >> 1;
    int g, j;
    if (c < 32) { g = c & 7; j = c >> 3; }
    else if (c < 60) { g = 1 + (c - 32) % 7; j = 4 + (c - 32) / 7; }
    else { g = 0; j = c - 58; }
    mn = ((g >> 2) * 8 + j) * 8 + (g & 3) * 2 + (id & 1);
    if (c == 60 || c == 61) {
      if (tid < 32) {
        const uint32_t tag = __ldcg(p.g->epoch + NCTA + (id & 3)) + 1;
#pragma unroll 1
        for (int mm = 0; mm < 16; mm++) poll_line(p.g->flags + mm * 32 + (lane & 7), 32 * tag, 0xffu);
        if (tid == 0) p.g->epoch[NCTA + (id & 3)] = tag;
      }
      return;
    }
  }
  const int m = mn >> 3, n = mn & 7;
  if (tid == 256) PROF_U(1);
  if (tid >= 382) asm volatile("prefetch.global.L2 [%0];" ::"l"(tid & 1 ? wqkv_p + 128 * n : x_p + 128 * m * DM));
  if (wg < 2) {
    asm volatile("setmaxnreg.inc.sync.aligned.u32 232;");
    const int id = mn | (warp << 7);
#pragma unroll 1
    for (int i = wg;; i += 2) {
      float acc[2][96];
#pragma unroll
      for (int r = 0; r < 96; r++) acc[0][r] = acc[1][r] = 0.f;
      pin_regs<96>(acc);
#pragma unroll 1
      while (!consumer_tile(p, acc, sb, i, id)) {
        PROF_T(6 + i * 4);
        i += 2;
        if (i >= 14) goto all_done;
      }
      attn_epilogue(p, acc, make_ctx(sb, id), i >= 7, i >= 7 ? i - 7 : i, lds_u(sb + OFF_TAG));
      PROF_E(i, 4);
      finish_stores(sb, i);
      PROF_E(i, 5);
      PROF_T(6 + i * 4);
    }
  all_done:
    if (wg == 0) finish_stores(sb, 12);
  } else {
    asm volatile("setmaxnreg.dec.sync.aligned.u32 40;");
    if (w != 0) {
      if (w == 2 && lane < 28) write_run_desc(sb, lane >> 1, lane & 1);
      bar_sync(BAR_INIT, 256);
      if (w == 1) producer<true>(p, sb, m, n, lane);
      else if (w == 3) colsum_helper(p, sb, m, n, lane);
      else if (elect_one()) publisher(p, sb, m, n);
    } else {
      if (elect_one()) {
#pragma unroll
        for (int k = 0; k < 4; k++) mbar_init(sb + BAR_FULL + 8 * k, 2);
        asm volatile("fence.mbarrier_init.release.cluster;" ::: "memory");
        PROF_U(4);
#pragma unroll 1
        for (int k = 0; k < 4; k++) {
          const uint32_t fb = sb + BAR_FULL + 8 * k;
          mbar_expect_tx(fb, 16384);
          tma_ld2(sb + (5 * k + 3) * UNIT, &p.xin, fb, 64 * k, 128 * m);
          mbar_expect_tx(fb, 3 * UNIT);
          tma_ld3(sb + 5 * k * UNIT, &p.wqkv, fb, 128 * n, 64 * k, 0);
        }
        PROF_U(5);
        mbar_init(sb + BAR_XRDY, 4);
        mbar_init(sb + BAR_XRDY + 8, 4);
        mbar_init(sb + BAR_FULL + 32, 2);
#pragma unroll
        for (int k = 0; k < NBAR; k++) mbar_init(sb + BAR_EMPTY + 8 * k, 4);
        mbar_init(sb + BAR_DUMMY, 4);
#pragma unroll
        for (int k = 0; k < 7; k++) mbar_init(sb + BAR_PUB + 8 * k, 4);
#pragma unroll
        for (int k = 0; k < 3; k++) mbar_init(sb + BAR_CSLD + 8 * k, 1);
        sts_f2(sb + OFF_ZERO, 0.f, 0.f);
        sts_f2(sb + OFF_ZERO + 8, 0.f, 0.f);
        asm volatile("fence.mbarrier_init.release.cluster;" ::: "memory");
        mbar_expect_tx(sb + BAR_CSLD, 24576);
        tma_ld3(sb + OFF_STG, &p.wqkv, sb + BAR_CSLD, 128 * n, 64 * m, 0);
#pragma unroll 1
        for (int h = 0; h < 2; h++) {
          const uint32_t xr = sb + BAR_XRDY + 8 * h;
          mbar_expect_tx(xr, 16384);
          tma_ld2(sb + OFF_X + h * 16384, &p.xin, xr, 128 * n + 64 * h, 128 * m);
          asm volatile("mbarrier.arrive.shared::cta.b64 _, [%0], 3;" ::"r"(xr) : "memory");
        }
        PROF_U(6);
      }
      __syncwarp();
      bar_arrive(BAR_INIT0, 160);
      bar_arrive(BAR_INIT, 256);
      producer<false>(p, sb, m, n, lane);
    }
  }
}

typedef CUresult (*EncodeFn)(CUtensorMap*, CUtensorMapDataType, cuuint32_t, void*, const cuuint64_t*, const cuuint64_t*,
                             const cuuint32_t*, const cuuint32_t*, CUtensorMapInterleave, CUtensorMapSwizzle,
                             CUtensorMapL2promotion, CUtensorMapFloatOOBfill);

void make_2d(EncodeFn enc, CUtensorMap* m, const void* ptr, uint64_t cols, uint64_t rows, uint32_t box_rows) {
  cuuint64_t d[2] = {cols, rows}, st[1] = {cols * 2};
  cuuint32_t b[2] = {64, box_rows}, e[2] = {1, 1};
  enc(m, CU_TENSOR_MAP_DATA_TYPE_BFLOAT16, 2, const_cast<void*>(ptr), d, st, b, e, CU_TENSOR_MAP_INTERLEAVE_NONE,
      CU_TENSOR_MAP_SWIZZLE_128B, CU_TENSOR_MAP_L2_PROMOTION_L2_128B, CU_TENSOR_MAP_FLOAT_OOB_FILL_NONE);
}
void make_3d(EncodeFn enc, CUtensorMap* m, const void* ptr, uint64_t d0, uint64_t rows, uint64_t d2, uint64_t row_bytes,
             uint64_t chunk_bytes, uint32_t box_chunks) {
  cuuint64_t d[3] = {d0, rows, d2}, st[2] = {row_bytes, chunk_bytes};
  cuuint32_t b[3] = {64, 64, box_chunks}, e[3] = {1, 1, 1};
  enc(m, CU_TENSOR_MAP_DATA_TYPE_BFLOAT16, 3, const_cast<void*>(ptr), d, st, b, e, CU_TENSOR_MAP_INTERLEAVE_NONE,
      CU_TENSOR_MAP_SWIZZLE_128B, CU_TENSOR_MAP_L2_PROMOTION_L2_128B, CU_TENSOR_MAP_FLOAT_OOB_FILL_NONE);
}

}

extern "C" void kernel_launch(void* const* d_in, const int* in_sizes, int n_in, void* d_out, int out_size) {
  (void)in_sizes; (void)n_in; (void)out_size;
  static EncodeFn enc = nullptr;
  static void *att = nullptr, *hbuf = nullptr, *scratch = nullptr;
  static int by_smid = 0;
  if (!enc) {
    void* fn = nullptr;
    cudaDriverEntryPointQueryResult q;
    cudaGetDriverEntryPoint("cuTensorMapEncodeTiled", &fn, cudaEnableDefault, &q);
    enc = (EncodeFn)fn;
    cudaGetSymbolAddress(&att, g_att);
    cudaGetSymbolAddress(&hbuf, g_h);
    cudaGetSymbolAddress(&scratch, g_scratch);
    cudaFuncSetAttribute(fused_layers_kernel, cudaFuncAttributeMaxDynamicSharedMemorySize, SMEM_BYTES);
    int sms = 0, per_sm = 0, dev = 0;
    cudaGetDevice(&dev);
    cudaDeviceGetAttribute(&sms, cudaDevAttrMultiProcessorCount, dev);
    cudaOccupancyMaxActiveBlocksPerMultiprocessor(&per_sm, fused_layers_kernel, 384, SMEM_BYTES);
    by_smid = sms == 132 && per_sm == 1;
  }
  Params p;
  make_2d(enc, &p.xin, d_in[0], DM, SEQ, 128);
  make_2d(enc, &p.out, d_out, DM, SEQ, 128);
  make_2d(enc, &p.att, att, DM, SEQ, 128);
  make_2d(enc, &p.h, hbuf, FF, SEQ, 128);
  make_2d(enc, &p.out_st, d_out, DM, SEQ, 32);
  make_2d(enc, &p.att_st, att, DM, SEQ, 32);
  make_2d(enc, &p.h_st, hbuf, FF, SEQ, 32);
  make_2d(enc, &p.w1c, d_in[4], FF, DM, 32);
  make_3d(enc, &p.wqkv, d_in[1], DM, DM, 3, 3 * DM * 2, DM * 2, 3);
  make_3d(enc, &p.wo, d_in[2], 64, DM, DM / 64, DM * 2, 128, 2);
  make_3d(enc, &p.w1a, d_in[4], 64, DM, FF / 64, FF * 2, 128, 3);
  make_3d(enc, &p.w1b, d_in[4], 64, DM, FF / 64, FF * 2, 128, 2);
  make_3d(enc, &p.w2, d_in[6], 64, FF, DM / 64, DM * 2, 128, 2);
  p.b1 = (const __nv_bfloat16*)d_in[5];
  p.b2 = (const __nv_bfloat16*)d_in[7];
  p.g = (Scratch*)scratch;
  p.zero = 0;
  fused_layers_kernel<<<by_smid ? 132 : NCTA, 384, SMEM_BYTES>>>(by_smid, (const __nv_bfloat16*)d_in[0], (const __nv_bfloat16*)d_in[1], p);
}
```

```cpp
#include <cuda_runtime.h>
#include <cuda_bf16.h>
#include <cuda.h>
#include <stdint.h>

namespace {

constexpr int SEQ = 2048, DM = 1024, FF = 3584;
constexpr int NCTA = 128;
constexpr int NBAR = 5;

constexpr uint32_t RING_UNITS = 20, UNIT = 8192;
constexpr uint32_t OFF_X   = RING_UNITS * UNIT;
constexpr uint32_t OFF_STG = OFF_X + 32768;
constexpr uint32_t OFF_HLP = OFF_STG + 16384;
constexpr uint32_t OFF_RUN = OFF_STG + 24576;
constexpr uint32_t OFF_CSQ = OFF_RUN + 512;
constexpr uint32_t OFF_CSF = OFF_CSQ + 2048;
constexpr uint32_t OFF_ROW = OFF_CSF + 3584;
constexpr uint32_t OFF_BAR = OFF_ROW + 1024;
constexpr uint32_t SMEM_BYTES = OFF_BAR + 384;
constexpr uint32_t BAR_FULL = OFF_BAR, BAR_EMPTY = OFF_BAR + 8 * NBAR;
constexpr uint32_t BAR_XRDY = OFF_BAR + 80;
constexpr uint32_t BAR_DUMMY = OFF_BAR + 96, OFF_TAG = OFF_BAR + 104, OFF_ZERO = OFF_BAR + 112;
constexpr uint32_t BAR_PUB = OFF_BAR + 128;
constexpr uint32_t BAR_CSLD = OFF_BAR + 200;
constexpr uint32_t BAR_BIAS = OFF_BAR + 216;

constexpr uint64_t DESC_A = (1ull << 62) | ((uint64_t)(2048 >> 4) << 32) | (1ull << 16);
constexpr uint64_t DESC_B = (1ull << 62) | ((uint64_t)(1024 >> 4) << 32) | ((uint64_t)(8192 >> 4) << 16);

constexpr int BAR_INIT = 0, BAR_ORDER = 1, BAR_GUARD = 3, BAR_WG = 5, BAR_GO = 7, BAR_DONE = 8, BAR_HLP = 9, BAR_INIT0 = 10;
#define GELU_DEP 3
#define MAP 1
#define WIN1 7
#define WIN2 4

struct Scratch {
  uint4 stats[4 * 8 * SEQ];
  uint4 halo[2 * 2 * 16 * 8 * 384];
  uint4 csp[2 * 8 * 17 * 224];
  uint32_t flags[16 * 32];
  uint32_t epoch[NCTA + 4];
};

struct Params {
  CUtensorMap xin, out, att, h, wqkv, wo, w1a, w1b, w2, out_st, att_st, h_st, w1c;
  const __nv_bfloat16 *b1, *b2;
  Scratch* g;
  uint32_t zero;
};

__device__ __nv_bfloat16 g_att[SEQ * DM];
__device__ __nv_bfloat16 g_h[SEQ * FF];
__device__ Scratch g_scratch;
#define PROF_T(idx)
#define PROF_U(k)
#define PROF_S(g)
#define PROF_E(i, k)

__device__ __forceinline__ void mbar_init(uint32_t bar, int cnt) {
  asm volatile("mbarrier.init.shared::cta.b64 [%0], %1;" ::"r"(bar), "r"(cnt));
}
__device__ __forceinline__ void mbar_expect_tx(uint32_t bar, uint32_t bytes) {
  asm volatile("mbarrier.arrive.expect_tx.shared::cta.b64 _, [%0], %1;" ::"r"(bar), "r"(bytes) : "memory");
}
__device__ __forceinline__ void mbar_arrive(uint32_t bar) {
  asm volatile("mbarrier.arrive.shared::cta.b64 _, [%0];" ::"r"(bar) : "memory");
}
__device__ __forceinline__ bool mbar_test(uint32_t bar, uint32_t parity) {
  uint32_t ok;
  asm volatile("{\n.reg .pred p;\nmbarrier.test_wait.parity.shared::cta.b64 p, [%1], %2;\nselp.u32 %0, 1, 0, p;\n}"
               : "=r"(ok) : "r"(bar), "r"(parity) : "memory");
  return ok;
}
__device__ __forceinline__ void mbar_wait(uint32_t bar, uint32_t parity) {
  asm volatile(
      "{\n.reg .pred p;\n.reg .u32 it;\nmov.u32 it, 0;\n"
      "WAIT_LOOP:\n"
      "mbarrier.try_wait.parity.shared::cta.b64 p, [%0], %1;\n"
      "@p bra WAIT_DONE;\n"
      "add.u32 it, it, 1;\n"
      "setp.lt.u32 p, it, 0x400000;\n"
      "@p bra WAIT_LOOP;\n"
      "trap;\n"
      "WAIT_DONE:\n}"
      ::"r"(bar), "r"(parity) : "memory");
}
__device__ __forceinline__ void bar_sync(int id, int n) { asm volatile("bar.sync %0, %1;" ::"r"(id), "r"(n) : "memory"); }
__device__ __forceinline__ void bar_arrive(int id, int n) { asm volatile("bar.arrive %0, %1;" ::"r"(id), "r"(n) : "memory"); }
__device__ __forceinline__ void tma_ld2(uint32_t dst, const CUtensorMap* m, uint32_t bar, int c0, int c1) {
  asm volatile("cp.async.bulk.tensor.2d.shared::cluster.global.mbarrier::complete_tx::bytes [%0], [%1, {%3, %4}], [%2];"
               ::"r"(dst), "l"(m), "r"(bar), "r"(c0), "r"(c1) : "memory");
}
__device__ __forceinline__ void tma_ld3(uint32_t dst, const CUtensorMap* m, uint32_t bar, int c0, int c1, int c2) {
  asm volatile("cp.async.bulk.tensor.3d.shared::cluster.global.mbarrier::complete_tx::bytes [%0], [%1, {%3, %4, %5}], [%2];"
               ::"r"(dst), "l"(m), "r"(bar), "r"(c0), "r"(c1), "r"(c2) : "memory");
}
__device__ __forceinline__ void tma_st2(const CUtensorMap* m, uint32_t src, int c0, int c1) {
  asm volatile("cp.async.bulk.tensor.2d.global.shared::cta.bulk_group [%0, {%2, %3}], [%1];"
               ::"l"(m), "r"(src), "r"(c0), "r"(c1) : "memory");
}
__device__ __forceinline__ void bulk_commit() { asm volatile("cp.async.bulk.commit_group;" ::: "memory"); }
__device__ __forceinline__ void bulk_wait_read() { asm volatile("cp.async.bulk.wait_group.read 0;" ::: "memory"); }
__device__ __forceinline__ void bulk_wait_all() { asm volatile("cp.async.bulk.wait_group 0;" ::: "memory"); }
__device__ __forceinline__ void fence_async_smem() { asm volatile("fence.proxy.async.shared::cta;" ::: "memory"); }
__device__ __forceinline__ void fence_async_global() { asm volatile("fence.proxy.async.global;" ::: "memory"); }
__device__ __forceinline__ void st_relaxed(uint32_t* p, uint32_t v) {
  asm volatile("st.relaxed.gpu.global.u32 [%0], %1;" ::"l"(p), "r"(v) : "memory");
}
__device__ __forceinline__ void st_msg(uint4* p, uint32_t a, uint32_t b, uint32_t c, uint32_t tag) {
  asm volatile("{\n.reg .b128 v;\nmov.b128 v, {%1, %2, %3, %4};\nst.relaxed.gpu.b128 [%0], v;\n}"
               ::"l"(p), "r"(a), "r"(b), "r"(c), "r"(tag) : "memory");
}
__device__ __forceinline__ void ld_msg(const uint4* p, uint32_t& a, uint32_t& b, uint32_t& c, uint32_t& tag) {
  asm volatile("{\n.reg .b128 v;\nld.relaxed.gpu.b128 v, [%4];\nmov.b128 {%0, %1, %2, %3}, v;\n}"
               : "=r"(a), "=r"(b), "=r"(c), "=r"(tag) : "l"(p) : "memory");
}
__device__ __forceinline__ bool elect_one() {
  uint32_t ok;
  asm volatile("{\n.reg .pred p;\nelect.sync _|p, 0xffffffff;\nselp.u32 %0, 1, 0, p;\n}" : "=r"(ok));
  return ok;
}
__device__ __forceinline__ int uniform(int v) { return __shfl_sync(0xffffffffu, v, 0); }
__device__ __forceinline__ uint32_t pack_bf16(float lo, float hi) {
  uint32_t r;
  asm("cvt.rn.bf16x2.f32 %0, %1, %2;" : "=r"(r) : "f"(hi), "f"(lo));
  return r;
}
__device__ __forceinline__ uint32_t prmt_u(uint32_t a, uint32_t sel) {
  uint32_t r;
  asm("prmt.b32 %0, %1, 0, %2;" : "=r"(r) : "r"(a), "r"(sel));
  return r;
}
__device__ __forceinline__ float prmt_f(uint32_t a, uint32_t sel) {
  float r;
  asm("{\n.reg .b32 t;\nprmt.b32 t, %1, 0, %2;\nmov.b32 %0, t;\n}" : "=f"(r) : "r"(a), "r"(sel));
  return r;
}
__device__ __forceinline__ float bf_lo(uint32_t v) { return __uint_as_float(v << 16); }
__device__ __forceinline__ float bf_hi(uint32_t v) { return __uint_as_float(v & 0xffff0000u); }
__device__ __forceinline__ void stsm4(uint32_t addr, uint32_t r0, uint32_t r1, uint32_t r2, uint32_t r3) {
  asm volatile("stmatrix.sync.aligned.m8n8.x4.shared.b16 [%0], {%1, %2, %3, %4};"
               ::"r"(addr), "r"(r0), "r"(r1), "r"(r2), "r"(r3) : "memory");
}
__device__ __forceinline__ void ldsm4(uint32_t addr, uint32_t& r0, uint32_t& r1, uint32_t& r2, uint32_t& r3) {
  asm volatile("ldmatrix.sync.aligned.m8n8.x4.shared.b16 {%0, %1, %2, %3}, [%4];"
               : "=r"(r0), "=r"(r1), "=r"(r2), "=r"(r3) : "r"(addr) : "memory");
}
__device__ __forceinline__ uint32_t movtrans(uint32_t a) {
  uint32_t d;
  asm volatile("movmatrix.sync.aligned.m8n8.trans.b16 %0, %1;" : "=r"(d) : "r"(a));
  return d;
}
__device__ __forceinline__ void mma16816(float (&c)[4], uint32_t a0, uint32_t a1, uint32_t a2, uint32_t a3, uint32_t b0, uint32_t b1) {
  asm volatile("mma.sync.aligned.m16n8k16.row.col.f32.bf16.bf16.f32 {%0,%1,%2,%3}, {%4,%5,%6,%7}, {%8,%9}, {%0,%1,%2,%3};"
               : "+f"(c[0]), "+f"(c[1]), "+f"(c[2]), "+f"(c[3])
               : "r"(a0), "r"(a1), "r"(a2), "r"(a3), "r"(b0), "r"(b1));
}
__device__ __forceinline__ float2 lds_f2(uint32_t a) {
  float2 v;
  asm volatile("ld.shared.v2.f32 {%0, %1}, [%2];" : "=f"(v.x), "=f"(v.y) : "r"(a) : "memory");
  return v;
}
__device__ __forceinline__ float4 lds_f4(uint32_t a) {
  float4 v;
  asm volatile("ld.shared.v4.f32 {%0, %1, %2, %3}, [%4];" : "=f"(v.x), "=f"(v.y), "=f"(v.z), "=f"(v.w) : "r"(a) : "memory");
  return v;
}
__device__ __forceinline__ float lds_f(uint32_t a) {
  float v;
  asm volatile("ld.shared.f32 %0, [%1];" : "=f"(v) : "r"(a) : "memory");
  return v;
}
__device__ __forceinline__ uint32_t lds_u(uint32_t a) {
  uint32_t v;
  asm volatile("ld.shared.u32 %0, [%1];" : "=r"(v) : "r"(a) : "memory");
  return v;
}
__device__ __forceinline__ void sts_f2(uint32_t a, float x, float y) {
  asm volatile("st.shared.v2.f32 [%0], {%1, %2};" ::"r"(a), "f"(x), "f"(y) : "memory");
}
__device__ __forceinline__ void sts_u4(uint32_t a, uint32_t x, uint32_t y, uint32_t z, uint32_t w) {
  asm volatile("st.shared.v4.u32 [%0], {%1, %2, %3, %4};" ::"r"(a), "r"(x), "r"(y), "r"(z), "r"(w) : "memory");
}
__device__ __forceinline__ void lds_u4(uint32_t a, uint32_t& x, uint32_t& y, uint32_t& z, uint32_t& w) {
  asm volatile("ld.shared.v4.u32 {%0, %1, %2, %3}, [%4];" : "=r"(x), "=r"(y), "=r"(z), "=r"(w) : "r"(a) : "memory");
}
__device__ __forceinline__ float ex2(float x) {
  float y;
  asm("ex2.approx.ftz.f32 %0, %1;" : "=f"(y) : "f"(x));
  return y;
}
__device__ __forceinline__ float rcp_hw(float x) {
  float y;
  asm("rcp.approx.ftz.f32 %0, %1;" : "=f"(y) : "f"(x));
  return y;
}
__device__ __forceinline__ float tanh_hw(float x) {
  float y;
  asm("tanh.approx.f32 %0, %1;" : "=f"(y) : "f"(x));
  return y;
}
__device__ __forceinline__ float quad_sum(float v) {
  v += __shfl_xor_sync(0xffffffffu, v, 1);
  return v + __shfl_xor_sync(0xffffffffu, v, 2);
}
__device__ __forceinline__ float quad_max(float v) {
  v = fmaxf(v, __shfl_xor_sync(0xffffffffu, v, 1));
  return fmaxf(v, __shfl_xor_sync(0xffffffffu, v, 2));
}

template <int N> __device__ __forceinline__ void wgmma_ss(float (&d)[96], uint64_t da, uint64_t db, uint32_t keep = 1);
template <> __device__ __forceinline__ void wgmma_ss<128>(float (&d)[96], uint64_t da, uint64_t db, uint32_t keep) {
  asm volatile(
      "{\n.reg .pred p;\nsetp.ne.u32 p, %66, 0;\n"
      "wgmma.mma_async.sync.aligned.m64n128k16.f32.bf16.bf16 {%0, %1, %2, %3, %4, %5, %6, %7, %8, %9, %10, %11, %12, %13, %14, %15, %16, %17, %18, %19, %20, %21, %22, %23, %24, %25, %26, %27, %28, %29, %30, %31, %32, %33, %34, %35, %36, %37, %38, %39, %40, %41, %42, %43, %44, %45, %46, %47, %48, %49, %50, %51, %52, %53, %54, %55, %56, %57, %58, %59, %60, %61, %62, %63}, %64, %65, p, 1, 1, 0, 1;\n}"
      : "+f"(d[0]), "+f"(d[1]), "+f"(d[2]), "+f"(d[3]), "+f"(d[4]), "+f"(d[5]), "+f"(d[6]), "+f"(d[7]), "+f"(d[8]), "+f"(d[9]), "+f"(d[10]), "+f"(d[11]), "+f"(d[12]), "+f"(d[13]), "+f"(d[14]), "+f"(d[15]), "+f"(d[16]), "+f"(d[17]), "+f"(d[18]), "+f"(d[19]), "+f"(d[20]), "+f"(d[21]), "+f"(d[22]), "+f"(d[23]), "+f"(d[24]), "+f"(d[25]), "+f"(d[26]), "+f"(d[27]), "+f"(d[28]), "+f"(d[29]), "+f"(d[30]), "+f"(d[31]), "+f"(d[32]), "+f"(d[33]), "+f"(d[34]), "+f"(d[35]), "+f"(d[36]), "+f"(d[37]), "+f"(d[38]), "+f"(d[39]), "+f"(d[40]), "+f"(d[41]), "+f"(d[42]), "+f"(d[43]), "+f"(d[44]), "+f"(d[45]), "+f"(d[46]), "+f"(d[47]), "+f"(d[48]), "+f"(d[49]), "+f"(d[50]), "+f"(d[51]), "+f"(d[52]), "+f"(d[53]), "+f"(d[54]), "+f"(d[55]), "+f"(d[56]), "+f"(d[57]), "+f"(d[58]), "+f"(d[59]), "+f"(d[60]), "+f"(d[61]), "+f"(d[62]), "+f"(d[63])
      : "l"(da), "l"(db), "r"(keep));
}

template <> __device__ __forceinline__ void wgmma_ss<192>(float (&d)[96], uint64_t da, uint64_t db, uint32_t keep) {
  asm volatile(
      "{\n.reg .pred p;\nsetp.ne.u32 p, %98, 0;\n"
      "wgmma.mma_async.sync.aligned.m64n192k16.f32.bf16.bf16 {%0, %1, %2, %3, %4, %5, %6, %7, %8, %9, %10, %11, %12, %13, %14, %15, %16, %17, %18, %19, %20, %21, %22, %23, %24, %25, %26, %27, %28, %29, %30, %31, %32, %33, %34, %35, %36, %37, %38, %39, %40, %41, %42, %43, %44, %45, %46, %47, %48, %49, %50, %51, %52, %53, %54, %55, %56, %57, %58, %59, %60, %61, %62, %63, %64, %65, %66, %67, %68, %69, %70, %71, %72, %73, %74, %75, %76, %77, %78, %79, %80, %81, %82, %83, %84, %85, %86, %87, %88, %89, %90, %91, %92, %93, %94, %95}, %96, %97, p, 1, 1, 0, 1;\n}"
      : "+f"(d[0]), "+f"(d[1]), "+f"(d[2]), "+f"(d[3]), "+f"(d[4]), "+f"(d[5]), "+f"(d[6]), "+f"(d[7]), "+f"(d[8]), "+f"(d[9]), "+f"(d[10]), "+f"(d[11]), "+f"(d[12]), "+f"(d[13]), "+f"(d[14]), "+f"(d[15]), "+f"(d[16]), "+f"(d[17]), "+f"(d[18]), "+f"(d[19]), "+f"(d[20]), "+f"(d[21]), "+f"(d[22]), "+f"(d[23]), "+f"(d[24]), "+f"(d[25]), "+f"(d[26]), "+f"(d[27]), "+f"(d[28]), "+f"(d[29]), "+f"(d[30]), "+f"(d[31]), "+f"(d[32]), "+f"(d[33]), "+f"(d[34]), "+f"(d[35]), "+f"(d[36]), "+f"(d[37]), "+f"(d[38]), "+f"(d[39]), "+f"(d[40]), "+f"(d[41]), "+f"(d[42]), "+f"(d[43]), "+f"(d[44]), "+f"(d[45]), "+f"(d[46]), "+f"(d[47]), "+f"(d[48]), "+f"(d[49]), "+f"(d[50]), "+f"(d[51]), "+f"(d[52]), "+f"(d[53]), "+f"(d[54]), "+f"(d[55]), "+f"(d[56]), "+f"(d[57]), "+f"(d[58]), "+f"(d[59]), "+f"(d[60]), "+f"(d[61]), "+f"(d[62]), "+f"(d[63]), "+f"(d[64]), "+f"(d[65]), "+f"(d[66]), "+f"(d[67]), "+f"(d[68]), "+f"(d[69]), "+f"(d[70]), "+f"(d[71]), "+f"(d[72]), "+f"(d[73]), "+f"(d[74]), "+f"(d[75]), "+f"(d[76]), "+f"(d[77]), "+f"(d[78]), "+f"(d[79]), "+f"(d[80]), "+f"(d[81]), "+f"(d[82]), "+f"(d[83]), "+f"(d[84]), "+f"(d[85]), "+f"(d[86]), "+f"(d[87]), "+f"(d[88]), "+f"(d[89]), "+f"(d[90]), "+f"(d[91]), "+f"(d[92]), "+f"(d[93]), "+f"(d[94]), "+f"(d[95])
      : "l"(da), "l"(db), "r"(keep));
}

template <int R>
__device__ __forceinline__ void pin_regs(float (&a)[2][96]) {
#pragma unroll
  for (int m = 0; m < 2; m++)
#pragma unroll
    for (int i = 0; i < R; i++) asm volatile("" : "+f"(a[m][i])::"memory");
}

struct Ctx {
  uint32_t sb;
  int m, n, wg, w, lane;
};
__device__ __forceinline__ Ctx make_ctx(uint32_t sb, int id) {
  int lane;
  asm volatile("mov.u32 %0, %%laneid;" : "=r"(lane));
  asm volatile("" : "+r"(id), "+r"(sb));
  return Ctx{sb, (id >> 3) & 15, id & 7, id >> 9, (id >> 7) & 3, lane};
}
#define UNPACK_CTX(c) const uint32_t sb = c.sb; const int m = c.m, n = c.n, wg = c.wg, w = c.w, lane = c.lane

__device__ __forceinline__ uint32_t poll_line(const uint32_t* word, uint32_t target, uint32_t need) {
  uint32_t v;
  asm volatile(
      "{\n.reg .pred p;\n.reg .u32 it, m;\n.reg .s32 d;\nmov.u32 it, 0;\n"
      "POLL_LOOP:\n"
      "ld.relaxed.gpu.global.u32 %0, [%1];\n"
      "sub.s32 d, %0, %2;\n"
      "setp.ge.s32 p, d, 0;\n"
      "vote.sync.ballot.b32 m, p, 0xffffffff;\n"
      "and.b32 m, m, %3;\n"
      "setp.eq.u32 p, m, %3;\n"
      "@p bra.uni POLL_DONE;\n"
      "add.u32 it, it, 1;\n"
      "setp.lt.u32 p, it, 0x400000;\n"
      "@p bra.uni POLL_LOOP;\n"
      "trap;\n"
      "POLL_DONE:\n}"
      : "=&r"(v) : "l"(word), "r"(target), "r"(need) : "memory");
  return v;
}
__device__ __forceinline__ uint32_t ld_relaxed(const uint32_t* p) {
  uint32_t v;
  asm volatile("ld.relaxed.gpu.global.u32 %0, [%1];" : "=r"(v) : "l"(p) : "memory");
  return v;
}
__device__ __forceinline__ float chain(float x, uint32_t on, uint32_t zero) {
  return __uint_as_float(__float_as_uint(x) | (on & zero));
}
constexpr int MSG_SPINS = 1 << 20;

constexpr int STAGES_PER_LAYER = 152;
__device__ __forceinline__ int nib(uint64_t v, int i) { return (int)(v >> (4 * i)) & 15; }
__device__ __forceinline__ bool tile_wide(int t) { return (0x23 >> t) & 1; }
__device__ __forceinline__ void weight_coords(const Params& p, int t, int n, const CUtensorMap*& map, int& c0, int& c2) {
  map = &p.wqkv + nib(0x4233100ull, t);
  c0 = t < 2 ? 128 * n + 64 * t : 0;
  c2 = t < 2 ? 0 : (t == 2 || t == 6) ? 2 * n : 7 * n + 2 * t - 6;
}

template <bool IS_A>
__device__ __forceinline__ void producer(const Params& p, uint32_t sb, int m, int n, int lane) {
  const uint32_t low = (1u << (4 * n)) - 1, others = (0x6543210u & low) | (0x7654321u & ~low);
  const uint64_t order_x = (uint64_t)(others * 2 + 0x1111111u) << 36 | (uint64_t)others * 2 << 8 | (n * 0x22 + 0x10);
  int inflight = 4, cur = 0;
  uint32_t fb = sb + BAR_FULL + 32, rb = sb + BAR_EMPTY, rph = 0, pos = 0, tag32 = 0, seen = 0;
  const uint32_t fend = sb + BAR_FULL + 8 * NBAR, rend = sb + BAR_EMPTY + 8 * NBAR;
  const uint32_t* word = p.g->flags + m * 32 + (lane < 16 ? lane >> 1 : lane & 7);
#pragma unroll 1
  for (int sg = 1; sg < 22; sg++) {
    const int layer = sg >= 11, s = sg == 1 ? 2 : sg == 2 ? 1 : sg - 11 * layer;
    const int t = nib(0x65434321010ull, s), kind = nib(0x32110031100ull, s);
    const bool wide = tile_wide(t);
    const uint32_t bbytes = wide ? 3 * UNIT : 2 * UNIT, base = sb + (IS_A ? bbytes : 0);
    const int mul = t == 6 ? 448 : t == 2 ? 128 : 64, count = sg == 1 ? 12 : 2 * nib(0x4871ull, kind);
    uint64_t order0 = sg == 1 ? 0xFEDCBA987654ull : kind == 3 ? 0x76543210u : order_x >> (8 * (kind & 1));
    uint32_t special = (s == 4 || s == 10) ? 0x10 : s == 9 ? 0xF : 1;
    if (IS_A) special |= (kind & 1 ? 0 : 3) | (count >= 4 ? 1u << (count - 4) : 0);
    if (s >= 9) pos = (s + 6) * UNIT;
    const CUtensorMap* map;
    int c0 = 0, c2 = 0, ev = 0;
    if (IS_A) {
      map = &p.xin + (t == 2 ? 2 : t == 6 ? 3 : sg >= 4);
      ev = 9 * layer + (t < 2 ? 0 : t == 2 ? 1 : t < 6 ? 4 : 5);
      if (sg == 2) seen = tag32 = (__ldcg(p.g->epoch + m * 8 + n) + 1) << 5;
    } else {
      weight_coords(p, t, n, map, c0, c2);
    }
#pragma unroll 1
    for (int add = 0; add < mul; add += 64) {
      uint64_t order = order0;
      const int need = kind == 3 ? ev : ev - 1 + (lane & 1), sh = kind == 3 ? 16 : 0;
      uint32_t ready = IS_A ? __ballot_sync(0xffffffffu, cur >= need) >> sh : 0;
#pragma unroll 1
      for (int k = 0; k < count; k++) {
        const int code = order & 15, kc = code * mul + add;
        order >>= 4;
        if ((special >> k) & 1) {
          const int lag = wide ? (s == 9 && k == 2 ? 2 : 3) : ((s == 4 || s == 10) && add == 0 && k < 4) ? 3 : 4;
#pragma unroll 1
          for (; inflight > lag; inflight--) {
            mbar_wait(rb, rph);
            rb += 8;
            if (rb == rend) { rb -= 8 * NBAR; rph ^= 1; }
          }
          inflight++;
          if (IS_A) {
            if (kind == 3 ? t == 2 && add + k == 64 : !(kind & 1) && k < 2) {
              if (t == 2) mbar_wait(sb + BAR_PUB + 8, layer);
              else if (k == 1 && (s == 0 || s == 5)) mbar_wait(sb + BAR_XRDY + 8, s == 5);
              if (elect_one()) mbar_arrive(fb);
              goto next_stage;
            }
            if (k == count - 4 && sg >= 3) seen = ld_relaxed(word);
          }
        } else {
          mbar_wait(rb, rph);
          rb += 8;
          if (rb == rend) { rb -= 8 * NBAR; rph ^= 1; }
        }
        if (IS_A && !((ready >> code) & 1)) {
          cur = max(cur, (int)(seen - tag32));
          ready = __ballot_sync(0xffffffffu, cur >= need) >> sh;
          if (!((ready >> code) & 1)) {
            cur = (int)(poll_line(word, tag32 + need, 1u << (code + sh)) - tag32);
            ready = __ballot_sync(0xffffffffu, cur >= need) >> sh;
          }
          asm volatile("fence.acquire.gpu;" ::: "memory");
          fence_async_global();
        }
        if (elect_one()) {
          if (!IS_A) tma_ld3(base + pos, map, fb, c0, kc, c2);
          else tma_ld2(base + pos, map, fb, kc, 128 * m);
          mbar_expect_tx(fb, IS_A ? 16384 : bbytes);
        }
      next_stage:
        fb += 8;
        if (fb == fend) fb -= 8 * NBAR;
        pos += bbytes + 2 * UNIT;
        if (pos >= RING_UNITS * UNIT) pos -= RING_UNITS * UNIT;
      }
      special = !IS_A ? 0 : t == 2 ? 1 : add == 128 ? 0x10 : 0;
      if (t == 2) order0 = others << 4 | n;
      if (IS_A && (t == 2 || add == 64 || add == 192)) ev++;
    }
  }
}

__device__ __forceinline__ void publisher(const Params& p, uint32_t sb, int m, int n) {
  const uint32_t tag = __ldcg(p.g->epoch + m * 8 + n) + 1;
  uint32_t* word = p.g->flags + m * 32 + n;
  const int mn = m * 8 + n; (void)mn;
  st_relaxed(word, 32 * tag);
#pragma unroll 1
  for (int c = 0; c < 18; c++) {
    const int e = c >= 9 ? c - 9 : c;
    if ((0x18C >> e) & 1) {
      const int half = (0x108 >> e) & 1;
      mbar_wait(sb + BAR_XRDY + 8 * half, e < 4);
#pragma unroll
      for (int w = 0; w < 4; w++) tma_st2(&p.out_st, sb + OFF_X + half * 16384 + w * 4096, 128 * n + 64 * half, 128 * m + 32 * w);
      bulk_commit();
      if (c >= 16) continue;
      bulk_wait_all();
      PROF_E(7 * (c >= 9) + (e < 4 ? 2 : 6), 11 + 2 * half);
    } else {
      mbar_wait(sb + BAR_PUB + 8 * e, c >= 9);
    }
    asm volatile("fence.release.gpu;" ::: "memory");
    st_relaxed(word, 32 * tag + c + 1);
    PROF_E(7 * (c >= 9) + nib(0x665432210ull, e), (0x108 >> e) & 1 ? 14 : 12);
  }
  p.g->epoch[m * 8 + n] = tag;
  bulk_wait_read();
}

__device__ __forceinline__ void sum_rows(uint32_t buf, int iters, float (&a)[8], int lane) {
  uint32_t addr = buf + (lane >> 3) * 128 + (((lane & 7) ^ (lane >> 3)) << 4);
#pragma unroll 1
  for (int it = 0; it < iters; it++) {
    uint32_t u[2][4];
    lds_u4(addr, u[0][0], u[0][1], u[0][2], u[0][3]);
    lds_u4((addr ^ 64) + 512, u[1][0], u[1][1], u[1][2], u[1][3]);
    addr += 1024;
#pragma unroll
    for (int e = 0; e < 8; e++) { a[2 * (e & 3)] += bf_lo(u[e >> 2][e & 3]); a[2 * (e & 3) + 1] += bf_hi(u[e >> 2][e & 3]); }
  }
}
__device__ __forceinline__ void publish_sums(const float (&a)[8], uint4* dst, int lane, uint32_t tag) {
  const bool u8 = lane & 8, u16 = lane & 16;
  float h4[4], h2[2];
#pragma unroll
  for (int e = 0; e < 4; e++) h4[e] = (u8 ? a[4 + e] : a[e]) + __shfl_xor_sync(0xffffffffu, u8 ? a[e] : a[4 + e], 8);
#pragma unroll
  for (int e = 0; e < 2; e++) h2[e] = (u16 ? h4[2 + e] : h4[e]) + __shfl_xor_sync(0xffffffffu, u16 ? h4[e] : h4[2 + e], 16);
  st_msg(dst + (lane & 7) * 4 + (u8 ? 2 : 0) + (u16 ? 1 : 0), __float_as_uint(h2[0]), __float_as_uint(h2[1]), 0u, tag);
}

__device__ __forceinline__ void colsum_helper(const Params& p, uint32_t sb, int m, int n, int lane) {
  const uint32_t tag = __ldcg(p.g->epoch + m * 8 + n) + 1;
  const int mn = m * 8 + n; (void)mn;
#pragma unroll 1
  for (int k = lane; k < 288; k += 32) {
    const uint32_t bb = __ldg(reinterpret_cast<const uint32_t*>(k < 224 ? p.b1 + 448 * n : p.b2 + 128 * n - 448) + k);
    const float sc = k < 224 ? 0.5f : 1.f;
    sts_f2(sb + (k < 224 ? OFF_CSF + k * 16 + 8 : OFF_CSQ + 1536 + (k - 224) * 8), sc * bf_lo(bb), sc * bf_hi(bb));
  }
  __syncwarp();
  if (elect_one()) mbar_arrive(sb + BAR_BIAS);
  bar_sync(BAR_HLP, 160);
  PROF_E(-1, 1);
#pragma unroll 1
  for (int c = 0; c < 7; c++) {
    float a[8] = {0.f, 0.f, 0.f, 0.f, 0.f, 0.f, 0.f, 0.f};
#pragma unroll 1
    for (int h = 0; h < 2; h++) {
      if (elect_one()) {
        mbar_expect_tx(sb + BAR_CSLD + 8, 4096);
        tma_ld2(sb + OFF_HLP, &p.w1c, sb + BAR_CSLD + 8, 448 * n + 64 * c, 64 * m + 32 * h);
        if (c < 6) asm volatile("cp.async.bulk.prefetch.tensor.2d.L2.global [%0, {%1, %2}];" ::"l"(&p.w1c), "r"(448 * n + 64 * c + 64), "r"(64 * m + 32 * h) : "memory");
      }
      mbar_wait(sb + BAR_CSLD + 8, h);
      sum_rows(sb + OFF_HLP, 4, a, lane);
      __syncwarp();
    }
    publish_sums(a, p.g->csp + ((8 + n) * 17 + m) * 224 + c * 32, lane, tag);
  }
  PROF_E(-1, 2);
}

__device__ __forceinline__ void poll_msgs2(const uint4* pa, const uint4* pb, float (&v)[4], uint32_t tag) {
#pragma unroll 1
  for (int it = 0; it < MSG_SPINS; it++) {
    uint32_t x[4], z, ta, tb;
    ld_msg(pa, x[0], x[1], z, ta);
    ld_msg(pb, x[2], x[3], z, tb);
#pragma unroll
    for (int e = 0; e < 4; e++) v[e] = __uint_as_float(x[e]);
    if (__all_sync(0xffffffffu, ta == tag && tb == tag)) break;
  }
}
__device__ __forceinline__ void colsum_total(const Params& p, const Ctx& cx, int mat, uint32_t tag) {
  uint4* base = p.g->csp + (mat * 8 + cx.n) * 17 * 224;
  const int per = 12 + 2 * mat, k = 2 * cx.w + (cx.lane >> 4), ia = per * cx.m + k, ib = per * cx.m + min(k + 8, per - 1);
  float v[4];
  poll_msgs2(base + (cx.lane & 15) * 224 + ia, base + (cx.lane & 15) * 224 + ib, v, tag);
#pragma unroll 1
  for (int d = 1; d < 16; d *= 2)
#pragma unroll
    for (int e = 0; e < 4; e++) v[e] += __shfl_xor_sync(0xffffffffu, v[e], d);
  const bool hi = cx.lane & 1;
  if ((cx.lane & 14) == 0) st_msg(base + 16 * 224 + (hi ? ib : ia), __float_as_uint(hi ? v[2] : v[0]), __float_as_uint(hi ? v[3] : v[1]), 0u, tag);
}
__device__ __forceinline__ void colsum_gather(const Params& p, const Ctx& cx, int mat, uint32_t tag) {
  const uint4* base = p.g->csp + ((mat * 8 + cx.n) * 17 + 16) * 224;
  const int ia = cx.w * 32 + cx.lane, ib = min(ia + 128, 191 + 32 * mat);
  float v[4];
  poll_msgs2(base + ia, base + ib, v, tag);
  const uint32_t tab = cx.sb + (mat ? OFF_CSF : OFF_CSQ);
  sts_f2(tab + (ia << (3 + mat)), v[0], v[1]);
  sts_f2(tab + (ib << (3 + mat)), v[2], v[3]);
}

constexpr uint32_t RING16 = RING_UNITS * (UNIT >> 4);
__device__ __forceinline__ bool tile_split(int i) { return (0xD98 >> i) & 1; }

__device__ __forceinline__ void write_run_desc(uint32_t sb, int i, int step) {
  const int layer = i >= 7, t = i - 7 * layer, part = tile_split(i) ? step : 2;
  const bool wide = tile_wide(t), own = t != 2 && t != 6 && part != 1 && i != 0, second = t == 1 || t == 4;
  const uint32_t z16 = (wide ? 5 : 4) * (UNIT >> 4), a_off = z16 - 1024 + (uint32_t)DESC_A - (uint32_t)DESC_B;
  const int gl = 16 * t + (part == 2 ? 0 : second ? 16 * part - 14 : 4 * part), g0 = layer * STAGES_PER_LAYER + gl;
  const uint32_t s16 = (sb & 0x3FFFF) >> 4, bfirst = (uint32_t)DESC_B + s16;
  const int nkb = t == 6 ? 56 : part == 0 ? 2 : 12 + 2 * part;
  const bool win1 = t == 1 && part != 0;
  const int run = win1 ? WIN1 + 1 : t == 2 ? WIN2 + 1 : nkb;
  const int rest = win1 ? 64 | (nkb - 1 - WIN1) : t == 2 ? 64 | (7 - WIN2) | (8 << 7) : 0;
  const uint32_t blo = bfirst + z16 * (wide ? (gl + (t == 5 ? 3 : 0)) & 3 : (gl + 3) % 5);
  const uint32_t alo = own ? (uint32_t)DESC_A + s16 + (OFF_X >> 4) : blo + a_off;
  const uint32_t aoff = own ? alo + 1024 - (blo == bfirst + RING16 - z16 ? bfirst : blo + z16) : a_off;
  const bool xwait = part == 0 && !second, keep = !(part == 0 || t == 5);
  sts_u4(sb + OFF_RUN + (2 * i + step) * 16, blo, alo, aoff,
         ((g0 / NBAR) & 1) | xwait << 1 | keep << 2 | 8 * (g0 % NBAR) | run << 6 | rest << 12);
}

template <int N>
__device__ __forceinline__ void mainloop(const Params& p, float (&acc)[2][96], uint32_t sb, int i, int step, int mn) {
  constexpr uint32_t Z16 = (2 + N / 64) * (UNIT >> 4);
  constexpr uint32_t A_OFF = Z16 - 1024 + (uint32_t)DESC_A - (uint32_t)DESC_B;
  const int wg = i & 1;
  const uint32_t s16 = (sb & 0x3FFFF) >> 4;
  const uint32_t blast = (uint32_t)DESC_B + s16 + RING16 - Z16, flast = sb + BAR_FULL + 8 * (NBAR - 1);
  uint32_t blo = (uint32_t)DESC_B + s16, alo = blo + A_OFF, aoff = A_OFF, misc = 16 << 6;
  if (N == 128 || i > 0) lds_u4(sb + OFF_RUN + (2 * i + step) * 16, blo, alo, aoff, misc);
  uint32_t keep = misc & 4;
  int run = (misc >> 6) & 63, rest = misc >> 12;
  uint32_t fb = sb + BAR_FULL + (misc & 0x38), ph = misc & 1;
  uint32_t prev = sb + BAR_DUMMY - 8 * NBAR;
  pin_regs<N / 2>(acc);
  if (N == 128 || i > 0) bar_sync(BAR_ORDER + wg, 256);
  else bar_sync(BAR_INIT0, 160);
  if (N == 192 && i == 0 && threadIdx.x == 0) PROF_U(8);
  mbar_wait(fb, ph);
  if (misc & 2) mbar_wait(sb + BAR_XRDY, N == 128);
  if (step == 0 || !tile_split(i)) PROF_T(4 + i * 4);
#pragma unroll 1
  while (true) {
    const uint64_t da = (DESC_A & ~0xffffffffull) | alo, db = (DESC_B & ~0xffffffffull) | blo;
    asm volatile("wgmma.fence.sync.aligned;" ::: "memory");
    wgmma_ss<N>(acc[0], da, db, keep);
    wgmma_ss<N>(acc[1], da + 64, db, keep);
    keep = 4;
    wgmma_ss<N>(acc[0], da + 2, db + 128);
    wgmma_ss<N>(acc[1], da + 66, db + 128);
    asm volatile("wgmma.commit_group.sync.aligned;" ::: "memory");
    asm volatile("wgmma.wait_group.sync.aligned 1;" ::: "memory");
    PROF_S(jj++);
    if (elect_one()) mbar_arrive(prev + 8 * NBAR);
    prev = fb;
    if (fb == flast) { fb -= 8 * NBAR; ph++; }
    fb += 8;
    if (blo == blast) blo -= RING16;
    blo += Z16;
    alo = blo + aoff;
    aoff = A_OFF;
    run--;
    const bool ready = mbar_test(fb, ph) && run != 0;
    asm volatile("wgmma.fence.sync.aligned;" ::: "memory");
    wgmma_ss<N>(acc[0], da + 4, db + 256);
    wgmma_ss<N>(acc[1], da + 68, db + 256);
    wgmma_ss<N>(acc[0], da + 6, db + 384);
    wgmma_ss<N>(acc[1], da + 70, db + 384);
    asm volatile("wgmma.commit_group.sync.aligned;" ::: "memory");
    if (!ready) {
      if (run == 0) {
        if (rest == 0) break;
        if (rest & 64) {
          bar_arrive(BAR_GO, 256);
          bar_sync(BAR_DONE, 256);
        } else {
          alo = (uint32_t)DESC_A + s16 + (OFF_STG >> 4);
        }
        run = rest & 63;
        rest >>= 7;
      }
      mbar_wait(fb, ph);
    }
  }
  if (i < 13) bar_arrive(BAR_ORDER + (wg ^ 1), 256);
  asm volatile("wgmma.wait_group.sync.aligned 0;" ::: "memory");
  pin_regs<N / 2>(acc);
  if (elect_one()) mbar_arrive(prev + 8 * NBAR);
  PROF_T(5 + i * 4);
  PROF_E(i, 0);
}

#define ACC(q, j, e) acc[(q) & 1][4 * (j) + 2 * ((q) >> 1) + (e)]

__device__ __forceinline__ void write_partial_stats(const Params& p, const Ctx& c, int ln, uint32_t tag) {
  const uint32_t xrow = c.sb + OFF_X + c.w * 4096 + c.lane * 128;
  float s = 0.f, q = 0.f, s1 = 0.f, q1 = 0.f;
#pragma unroll 2
  for (int j = 0; j < 16; j++) {
    uint32_t u[4];
    lds_u4(xrow + (j >> 3) * 16384 + (((j & 7) ^ (c.lane & 7)) << 4), u[0], u[1], u[2], u[3]);
#pragma unroll
    for (int e = 0; e < 4; e++) {
      const float a = bf_lo(u[e]), d = bf_hi(u[e]);
      s += a; q = fmaf(a, a, q);
      s1 += d; q1 = fmaf(d, d, q1);
    }
  }
  s += s1;
  q += q1;
  st_msg(p.g->stats + (ln * 8 + c.n) * SEQ + 128 * c.m + 32 * c.w + c.lane, __float_as_uint(s),
         __float_as_uint(fmaxf(q - s * s * (1.f / 128.f), 0.f)), 0u, tag);
}

__device__ __forceinline__ void finish_row_stats(const Params& p, const Ctx& c, int ln, uint32_t tag) {
  const uint4* src = p.g->stats + ln * 8 * SEQ + 128 * c.m + 32 * c.w + c.lane;
  uint32_t ps[8], pm[8];
#pragma unroll 1
  for (int it = 0; it < MSG_SPINS; it++) {
    uint32_t bad = 0, u, tg;
#pragma unroll
    for (int k = 0; k < 8; k++) { ld_msg(src + k * SEQ, ps[k], pm[k], u, tg); bad |= tg ^ tag; }
    if (__all_sync(0xffffffffu, bad == 0)) break;
  }
  float s = 0.f, m2 = 0.f;
#pragma unroll
  for (int k = 0; k < 8; k++) s += __uint_as_float(ps[k]);
  const float mean = s * (1.f / DM);
#pragma unroll
  for (int k = 0; k < 8; k++) {
    const float d = __uint_as_float(ps[k]) * (1.f / 128.f) - mean;
    m2 += fmaf(128.f * d, d, __uint_as_float(pm[k]));
  }
  sts_f2(c.sb + OFF_ROW + (32 * c.w + c.lane) * 8, rsqrtf(m2 * (1.f / DM) + 1e-5f), mean);
  __syncwarp();
}

__device__ __forceinline__ void attn_scores(const uint32_t* qa, const uint32_t* qb, const uint32_t* k0, const uint32_t* k1,
                                            const uint32_t* k2, const uint32_t* k3, float (&l)[4], const float4& zero,
                                            bool par, bool early) {
  float s[4][4];
#pragma unroll
  for (int kb = 0; kb < 4; kb++) {
    const uint32_t* kk = kb == 0 ? k0 : kb == 1 ? k1 : kb == 2 ? k2 : k3;
    asm volatile("mma.sync.aligned.m16n8k16.row.col.f32.bf16.bf16.f32 {%0,%1,%2,%3}, {%4,%5,%6,%7}, {%8,%9}, {%10,%11,%12,%13};"
                 : "=f"(s[kb][0]), "=f"(s[kb][1]), "=f"(s[kb][2]), "=f"(s[kb][3])
                 : "r"(qa[0]), "r"(qb[0]), "r"(qa[1]), "r"(qb[1]), "r"(kk[0]), "r"(kk[1]), "f"(zero.x), "f"(zero.y),
                   "f"(zero.z), "f"(zero.w));
  }
#pragma unroll
  for (int kb = 0; kb < 4; kb++) {
    const uint32_t* kk = kb == 0 ? k0 : kb == 1 ? k1 : kb == 2 ? k2 : k3;
    mma16816(s[kb], qa[2], qb[2], qa[3], qb[3], kk[2], kk[3]);
  }
  l[0] = par ? s[1][1] : s[1][0];
  l[1] = early ? (par ? s[0][1] : s[0][0]) : (par ? s[2][1] : s[2][0]);
  l[2] = par ? s[2][3] : s[2][2];
  l[3] = early ? (par ? s[1][3] : s[1][2]) : (par ? s[3][3] : s[3][2]);
}

__device__ __forceinline__ void attn_mix(const float (&l)[4], const float (&sc)[4], const float (&off)[4], const float (&rk)[4],
                                         const uint32_t* v0, const uint32_t* v1, const uint32_t* v2, const uint32_t* v3,
                                         uint32_t* olo, uint32_t* ohi, const uint32_t (&sel)[4]) {
  float x[4];
#pragma unroll
  for (int e = 0; e < 4; e++) x[e] = fmaf(l[e], sc[e], off[e]);
  const float ml = quad_max(fmaxf(x[0], x[1])), mh = quad_max(fmaxf(x[2], x[3]));
  x[0] = ex2(x[0] - ml); x[1] = ex2(x[1] - ml);
  x[2] = ex2(x[2] - mh); x[3] = ex2(x[3] - mh);
  const uint32_t pl = pack_bf16(x[0] * rk[0], x[1] * rk[1]), ph = pack_bf16(x[2] * rk[2], x[3] * rk[3]);
  const uint32_t a0 = prmt_u(pl, sel[1]), a1 = prmt_u(pl, sel[3]), a2 = prmt_u(pl, sel[0]), a3 = prmt_u(ph, sel[1]);
  const uint32_t c0 = prmt_u(pl, sel[2]), c1 = prmt_u(ph, sel[0]), c2 = prmt_u(ph, sel[3]), c3 = prmt_u(ph, sel[2]);
  float o[4][4];
#pragma unroll
  for (int jn = 0; jn < 4; jn++) {
    o[jn][0] = o[jn][1] = o[jn][2] = o[jn][3] = 0.f;
    mma16816(o[jn], a0, a1, a2, a3, v0[jn], v1[jn]);
  }
#pragma unroll
  for (int jn = 0; jn < 4; jn++) mma16816(o[jn], c0, c1, c2, c3, v2[jn], v3[jn]);
  const float il = rcp_hw(quad_sum(x[0] + x[1])), ih = rcp_hw(quad_sum(x[2] + x[3]));
#pragma unroll
  for (int jn = 0; jn < 4; jn++) {
    olo[jn] = pack_bf16(o[jn][0] * il, o[jn][1] * il);
    ohi[jn] = pack_bf16(o[jn][2] * ih, o[jn][3] * ih);
  }
}

__device__ __forceinline__ void gelu_epilogue(const Params& p, float (&acc)[2][96], const Ctx& cx, int t) {
  UNPACK_CTX(cx);
  (void)wg;
  float rs[4], rm[4];
#pragma unroll
  for (int q = 0; q < 4; q++) {
    const float2 v = lds_f2(sb + OFF_ROW + (32 * w + 8 * q + (lane >> 2)) * 8);
    rs[q] = 0.5f * v.x;
    rm[q] = -rs[q] * v.y;
  }
  const int col0 = 128 * (t - 3);
  const uint32_t stg = sb + OFF_STG + w * 4096;
  const uint32_t ctab = sb + OFF_CSF + (col0 / 2 + (lane & 3)) * 16, srow = stg + lane * 128 + ((lane & 7) << 4);
#pragma unroll
  for (int c = 0; c < 3; c++) {
    if (c == 2 && t != 5) break;
    uint32_t hp[8][4];
#pragma unroll
    for (int j = 0; j < 8; j++) {
      const float4 cb = lds_f4(ctab + (8 * c + j) * 64);
#pragma unroll
      for (int q = 0; q < 4; q++) {
        float y[2];
        const int k = 4 * j + q - GELU_DEP;
        const float rmq = k >= 0 ? chain(rm[q], hp[k >> 2][k & 3], p.zero) : rm[q];
#pragma unroll
        for (int e = 0; e < 2; e++) {
          const float z = fmaf(ACC(q, 8 * c + j, e), rs[q], fmaf(rmq, e ? cb.y : cb.x, e ? cb.w : cb.z));
          const float u = z * fmaf(z * z, 8.f * 0.7978845608028654f * 0.044715f, 2.f * 0.7978845608028654f);
          y[e] = fmaf(z, tanh_hw(u), z);
        }
        hp[j][q] = pack_bf16(y[0], y[1]);
      }
      if (j == 3 && c > 0) {
        if (lane == 0) bulk_wait_read();
        __syncwarp();
      }
      if (c == 0 || j > 3) {
        stsm4(srow ^ (j << 4), hp[j][0], hp[j][1], hp[j][2], hp[j][3]);
      } else if (j == 3) {
#pragma unroll
        for (int jj = 0; jj < 4; jj++) stsm4(srow ^ (jj << 4), hp[jj][0], hp[jj][1], hp[jj][2], hp[jj][3]);
      }
    }
    fence_async_smem();
    __syncwarp();
    if (lane == 0) {
      tma_st2(&p.h_st, stg, 448 * n + col0 + 64 * c, 128 * m + 32 * w);
      bulk_commit();
    }
  }
#pragma unroll
  for (int r = 0; r < 16; r++) acc[0][r] = acc[1][r] = 0.f;
}

__device__ __forceinline__ void attn_epilogue(const Params& p, float (&acc)[2][96], const Ctx& cx, int layer, int t, uint32_t tag) {
  UNPACK_CTX(cx);
  const bool par = (lane >> 2) & 1, early = (lane & 3) > (lane >> 3);
  const uint32_t ktab = sb + OFF_ROW + (32 * w + 2 * (lane & 3) + par) * 8, exc = sb + OFF_STG + w * 4096 + lane * 16;
  const int slot = ((layer * 2 + t) * 16 + m) * 8 + n;
  const int mn = m * 8 + n; (void)mn;
  uint32_t Q[4][8], K[4][8], V[4][8], E[36], P[36];
  float kr[6], qr[4];
#pragma unroll
  for (int q = 2; q < 4; q++) {
    kr[2 + q] = lds_f(ktab + 64 * q);
#pragma unroll
    for (int j = 0; j < 8; j++) {
      E[8 * (q - 2) + j] = K[q][j] = pack_bf16(ACC(q, 8 + j, 0), ACC(q, 8 + j, 1));
      E[16 + 2 * j + q - 2] = V[q][j] = movtrans(pack_bf16(ACC(q, 16 + j, 0), ACC(q, 16 + j, 1)));
    }
  }
  E[32] = __float_as_uint(kr[4]);
  E[33] = E[34] = E[35] = __float_as_uint(kr[5]);
  if (w < 3) {
#pragma unroll
    for (int k = 0; k < 8; k++) sts_u4(exc + k * 512, E[4 * k], E[4 * k + 1], E[4 * k + 2], E[4 * k + 3]);
  } else {
#pragma unroll
    for (int k = 0; k < 12; k++) st_msg(p.g->halo + slot * 384 + k * 32 + lane, E[3 * k], E[3 * k + 1], E[3 * k + 2], tag);
  }
  PROF_E(7 * layer + t, 1);
#pragma unroll
  for (int q = 0; q < 4; q++) {
    qr[q] = lds_f(sb + OFF_ROW + (32 * w + 8 * q + (lane >> 2)) * 8) * (0.17677669529663687f * 1.4426950408889634f);
#pragma unroll
    for (int j = 0; j < 8; j++) Q[q][j] = pack_bf16(ACC(q, j, 0), ACC(q, j, 1));
    if (q < 2) {
      kr[2 + q] = lds_f(ktab + 64 * q);
#pragma unroll
      for (int j = 0; j < 8; j++) {
        K[q][j] = pack_bf16(ACC(q, 8 + j, 0), ACC(q, 8 + j, 1));
        V[q][j] = movtrans(pack_bf16(ACC(q, 16 + j, 0), ACC(q, 16 + j, 1)));
      }
    }
  }
  bar_sync(BAR_WG + wg, 128);
  if (w > 0 || m == 0) {
    const uint32_t back = w > 0;
#pragma unroll
    for (int k = 0; k < 8; k++) lds_u4(exc - back * 4096 + k * 512, P[4 * k], P[4 * k + 1], P[4 * k + 2], P[4 * k + 3]);
    P[32] = lds_u(ktab - back * 128);
    P[33] = lds_u(ktab - back * 64);
  } else {
#pragma unroll 1
    for (int it = 0; it < MSG_SPINS; it++) {
      uint32_t tg, bad = 0;
#pragma unroll
      for (int k = 0; k < 12; k++) {
        ld_msg(p.g->halo + (slot - 8) * 384 + k * 32 + lane, P[3 * k], P[3 * k + 1], P[3 * k + 2], tg);
        bad |= tg ^ tag;
      }
      if (__all_sync(0xffffffffu, bad == 0)) break;
    }
  }
  kr[0] = __uint_as_float(P[32]);
  kr[1] = __uint_as_float(P[33]);
  uint32_t PV[2][8];
#pragma unroll
  for (int j = 0; j < 8; j++) { PV[0][j] = P[16 + 2 * j]; PV[1][j] = P[17 + 2 * j]; }
  float rk[2][4], sc[2][4], off[2][4];
#pragma unroll
  for (int g = 0; g < 2; g++) {
    rk[g][0] = kr[2 * g + 1];
    rk[g][1] = early ? kr[2 * g] : kr[2 * g + 2];
    rk[g][2] = kr[2 * g + 2];
    rk[g][3] = early ? kr[2 * g + 1] : kr[2 * g + 3];
#pragma unroll
    for (int e = 0; e < 4; e++) {
      const bool masked = g == 0 && e != 2 && (m | w) == 0 && (e == 0 || early);
      sc[g][e] = masked ? 0.f : rk[g][e] * qr[2 * g + (e >> 1)];
      off[g][e] = masked ? -1e30f : 0.f;
    }
  }
  const uint32_t none = 0x4444u | p.zero, second = par ? 0x3244u : 0x4432u;
  const uint32_t sel[4] = {par ? 0x1044u : 0x4410u, early ? second : none, early ? none : second, none};
  PROF_E(7 * layer + t, 2);
  bar_sync(BAR_GO, 256);
  const float4 zero = lds_f4(sb + OFF_ZERO);
  float l[2][2][4];
  uint32_t O[4][8];
#pragma unroll
  for (int h = 0; h < 2; h++) {
    if (h == 1) {
      Q[2][4] |= __float_as_uint(l[1][0][0]) & p.zero;
      Q[0][4] |= __float_as_uint(l[0][0][0]) & p.zero;
    }
    attn_scores(&Q[2][4 * h], &Q[3][4 * h], &K[0][4 * h], &K[1][4 * h], &K[2][4 * h], &K[3][4 * h], l[1][h], zero, par, early);
    attn_scores(&Q[0][4 * h], &Q[1][4 * h], &P[4 * h], &P[8 + 4 * h], &K[0][4 * h], &K[1][4 * h], l[0][h], zero, par, early);
  }
  const uint32_t stg = sb + OFF_STG + w * 4096, srow = stg + lane * 128 + ((lane & 7) << 4);
#pragma unroll
  for (int h = 0; h < 2; h++) {
    attn_mix(l[1][h], sc[1], off[1], rk[1], &V[0][4 * h], &V[1][4 * h], &V[2][4 * h], &V[3][4 * h], &O[2][4 * h], &O[3][4 * h], sel);
    attn_mix(l[0][h], sc[0], off[0], rk[0], &PV[0][4 * h], &PV[1][4 * h], &V[0][4 * h], &V[1][4 * h], &O[0][4 * h], &O[1][4 * h], sel);
#pragma unroll
    for (int j = 4 * h; j < 4 * h + 4; j++) stsm4(srow ^ (j << 4), O[0][j], O[1][j], O[2][j], O[3][j]);
  }
  bar_arrive(BAR_DONE, 256);
  fence_async_smem();
  __syncwarp();
  if (lane == 0) {
    tma_st2(&p.att_st, stg, 128 * n + 64 * t, 128 * m + 32 * w);
    bulk_commit();
  }
}

__device__ __forceinline__ void finish_stores(uint32_t sb, int i) {
  const int t = i >= 7 ? i - 7 : i;
  if ((threadIdx.x & 31) == 0) {
    bulk_wait_all();
    mbar_arrive(sb + BAR_PUB + 8 * (t < 2 ? t : t + 1));
  }
  __syncwarp();
  if (i < 12) bar_arrive(BAR_GUARD + ((i & 1) ^ 1), 256);
}

__device__ __forceinline__ bool consumer_tile(const Params& p, float (&acc)[2][96], uint32_t sb0, int i, int mn) {
  const int layer = i >= 7, t = i - 7 * layer, wg = i & 1;
  const bool resid = t == 2 || t == 6;
  {
    if (resid) {
      const Ctx cx = make_ctx(sb0, mn);
      const uint32_t xrow = cx.sb + OFF_X + cx.w * 4096 + cx.lane * 128;
      const uint32_t sel_lo = 0x1044u | p.zero, sel_hi = 0x3244u | p.zero;
#pragma unroll
      for (int j = 0; j < 16; j++) {
        uint32_t r[4];
        ldsm4(xrow + (j >> 3) * 16384 + (((j & 7) ^ (cx.lane & 7)) << 4), r[0], r[1], r[2], r[3]);
#pragma unroll
        for (int q = 0; q < 4; q++) {
          ACC(q, j, 0) = prmt_f(r[q], sel_lo);
          ACC(q, j, 1) = prmt_f(r[q], sel_hi);
        }
      }
    }
    if (t >= 5 || i == 7) finish_stores(sb0, i - 2);
#pragma unroll 1
    for (int step = !tile_split(i);; step++) {
      if (step == 1 && (t == 1 || t == 4)) {
        const Ctx cx = make_ctx(sb0, mn);
        if (i == 1) {
          const uint32_t epoch = __ldcg(p.g->epoch + (mn & 127));
          bar_sync(BAR_INIT, 256);
          asm volatile("st.shared.u32 [%0], %1;" ::"r"(sb0 + OFF_TAG), "r"(epoch + 1) : "memory");
        }
        const uint32_t tag = lds_u(cx.sb + OFF_TAG);
        const int ln = (i + 1) >> 2;
#pragma unroll 1
        for (int r = 0; r < 2; r++) {
          if (i == 1) {
            if (cx.w < 3) {
              float a[8] = {0.f, 0.f, 0.f, 0.f, 0.f, 0.f, 0.f, 0.f};
              mbar_wait(sb0 + BAR_CSLD, r);
              sum_rows(cx.sb + OFF_STG + cx.w * 8192, 8, a, cx.lane);
              publish_sums(a, p.g->csp + (cx.n * 17 + cx.m) * 224 + (3 * r + cx.w) * 32, cx.lane, tag);
            }
            PROF_E(-1, 5 + r);
          }
          if (r == 1) break;
          if (i == 1) {
            bar_sync(BAR_WG + 1, 128);
            if (cx.w == 3 && elect_one()) {
              mbar_expect_tx(sb0 + BAR_CSLD, 24576);
              tma_ld3(sb0 + OFF_STG, &p.wqkv, sb0 + BAR_CSLD, 128 * cx.n + 64, 64 * cx.m, 0);
            }
            mbar_wait(sb0 + BAR_XRDY, 0);
            mbar_wait(sb0 + BAR_XRDY + 8, 0);
          }
          write_partial_stats(p, cx, ln, tag);
          PROF_E(i - 2, 8);
        }
        if (i == 1) bar_arrive(BAR_HLP, 160);
        if (i <= 4) colsum_total(p, cx, ln, tag);
        PROF_E(i - 2, 9);
        if (i != 1) bar_sync(BAR_GUARD + wg, 256);
        finish_row_stats(p, cx, ln, tag);
        PROF_E(i - 2, 10);
        if (i <= 4) {
          colsum_gather(p, cx, ln, tag);
          if (i == 4) mbar_wait(sb0 + BAR_BIAS, 0);
          bar_sync(BAR_WG + wg, 128);
        }
        PROF_E(i - 2, 15);
        bar_arrive(BAR_GUARD + (wg ^ 1), 256);
      }
      if (step == 2 && !resid) bar_sync(BAR_GUARD + wg, 256);
      if (t + step == 2 || t == 6) {
        const Ctx cx = make_ctx(sb0, mn);
        float nm[4];
#pragma unroll
        for (int q = 0; q < 4; q++) nm[q] = t == 6 ? 1.f : -lds_f(cx.sb + OFF_ROW + (32 * cx.w + 8 * q + (cx.lane >> 2)) * 8 + 4);
        const uint32_t ctab = cx.sb + OFF_CSQ + ((t & 3) * 192 + 2 * (cx.lane & 3)) * 4;
#pragma unroll
        for (int j = 0; j < 24; j++) {
          const float2 cs = lds_f2(ctab + j * 32);
#pragma unroll
          for (int q = 0; q < 4; q++) {
            const int k = 4 * j + q - 1;
            const float nq = k >= 0 ? chain(nm[q], __float_as_uint(ACC(k & 3, k >> 2, 1)), p.zero) : nm[q];
            ACC(q, j, 0) = fmaf(nq, cs.x, ACC(q, j, 0));
            ACC(q, j, 1) = fmaf(nq, cs.y, ACC(q, j, 1));
          }
        }
      }
      if (step == 2) break;
      if (tile_wide(t)) {
        mainloop<192>(p, acc, sb0, i, step, mn);
      } else {
        mainloop<128>(p, acc, sb0, i, step, mn);
        if (resid) break;
      }
    }
    if (t < 2) return true;
    const Ctx cx = make_ctx(sb0, mn);
    if (resid) {
      const uint32_t xrow = cx.sb + OFF_X + cx.w * 4096 + cx.lane * 128;
#pragma unroll
      for (int j = 0; j < 16; j++) {
        stsm4(xrow + (j >> 3) * 16384 + (((j & 7) ^ (cx.lane & 7)) << 4), pack_bf16(ACC(0, j, 0), ACC(0, j, 1)),
              pack_bf16(ACC(1, j, 0), ACC(1, j, 1)), pack_bf16(ACC(2, j, 0), ACC(2, j, 1)), pack_bf16(ACC(3, j, 0), ACC(3, j, 1)));
        if ((j & 7) == 7) {
          fence_async_smem();
          __syncwarp();
          if (elect_one()) mbar_arrive(sb0 + BAR_XRDY + (j & 8));
        }
      }
      PROF_E(i, 4);
      return false;
    }
    gelu_epilogue(p, acc, cx, t);
    PROF_E(i, 4);
    return false;
  }
}

__global__ void __launch_bounds__(384, 1) fused_layers_kernel(const int by_smid, const __nv_bfloat16* x_p, const __nv_bfloat16* wqkv_p,
                                                                  const __grid_constant__ Params p) {
  extern __shared__ __align__(1024) uint8_t smem_raw[];
  const uint32_t sb = uniform((uint32_t)__cvta_generic_to_shared(smem_raw));
  const int tid = threadIdx.x, lane = tid & 31, warp = uniform(tid >> 5), wg = warp >> 2, w = warp & 3;

  int mn;
  {
    int id = blockIdx.x;
    if (by_smid) asm volatile("mov.u32 %0, %%smid;" : "=r"(id));
    else if (id >= 120) id += 4;
    const int c = id >> 1;
    int g, j;
    if (c < 32) { g = c & 7; j = c >> 3; }
    else if (c < 60) { g = 1 + (c - 32) % 7; j = 4 + (c - 32) / 7; }
    else { g = 0; j = c - 58; }
    mn = ((g >> 2) * 8 + j) * 8 + (g & 3) * 2 + (id & 1);
    if (c == 60 || c == 61) {
      if (tid < 32) {
        const uint32_t tag = __ldcg(p.g->epoch + NCTA + (id & 3)) + 1;
#pragma unroll 1
        for (int mm = 0; mm < 16; mm++) poll_line(p.g->flags + mm * 32 + (lane & 7), 32 * tag, 0xffu);
        if (tid == 0) p.g->epoch[NCTA + (id & 3)] = tag;
      }
      return;
    }
  }
  const int m = mn >> 3, n = mn & 7;
  if (tid == 256) PROF_U(1);
  if (tid >= 382) asm volatile("prefetch.global.L2 [%0];" ::"l"(tid & 1 ? wqkv_p + 128 * n : x_p + 128 * m * DM));
  if (wg < 2) {
    asm volatile("setmaxnreg.inc.sync.aligned.u32 232;");
    const int id = mn | (warp << 7);
#pragma unroll 1
    for (int i = wg;; i += 2) {
      float acc[2][96];
#pragma unroll
      for (int r = 0; r < 96; r++) acc[0][r] = acc[1][r] = 0.f;
      pin_regs<96>(acc);
#pragma unroll 1
      while (!consumer_tile(p, acc, sb, i, id)) {
        PROF_T(6 + i * 4);
        i += 2;
        if (i >= 14) goto all_done;
      }
      attn_epilogue(p, acc, make_ctx(sb, id), i >= 7, i >= 7 ? i - 7 : i, lds_u(sb + OFF_TAG));
      PROF_E(i, 4);
      finish_stores(sb, i);
      PROF_E(i, 5);
      PROF_T(6 + i * 4);
    }
  all_done:
    if (wg == 0) finish_stores(sb, 12);
  } else {
    asm volatile("setmaxnreg.dec.sync.aligned.u32 40;");
    if (w != 0) {
      if (w == 2 && lane < 28) write_run_desc(sb, lane >> 1, lane & 1);
      bar_sync(BAR_INIT, 256);
      if (w == 1) producer<true>(p, sb, m, n, lane);
      else if (w == 3) colsum_helper(p, sb, m, n, lane);
      else if (elect_one()) publisher(p, sb, m, n);
    } else {
      if (elect_one()) {
#pragma unroll
        for (int k = 0; k < 4; k++) mbar_init(sb + BAR_FULL + 8 * k, 2);
        asm volatile("fence.mbarrier_init.release.cluster;" ::: "memory");
        PROF_U(4);
#pragma unroll 1
        for (int k = 0; k < 4; k++) {
          const uint32_t fb = sb + BAR_FULL + 8 * k;
          mbar_expect_tx(fb, 16384);
          tma_ld2(sb + (5 * k + 3) * UNIT, &p.xin, fb, 64 * k, 128 * m);
          mbar_expect_tx(fb, 3 * UNIT);
          tma_ld3(sb + 5 * k * UNIT, &p.wqkv, fb, 128 * n, 64 * k, 0);
        }
        PROF_U(5);
        mbar_init(sb + BAR_XRDY, 4);
        mbar_init(sb + BAR_XRDY + 8, 4);
        mbar_init(sb + BAR_FULL + 32, 2);
#pragma unroll
        for (int k = 0; k < NBAR; k++) mbar_init(sb + BAR_EMPTY + 8 * k, 4);
        mbar_init(sb + BAR_DUMMY, 4);
#pragma unroll
        for (int k = 0; k < 7; k++) mbar_init(sb + BAR_PUB + 8 * k, 4);
#pragma unroll
        for (int k = 0; k < 3; k++) mbar_init(sb + BAR_CSLD + 8 * k, 1);
        sts_f2(sb + OFF_ZERO, 0.f, 0.f);
        sts_f2(sb + OFF_ZERO + 8, 0.f, 0.f);
        asm volatile("fence.mbarrier_init.release.cluster;" ::: "memory");
        mbar_expect_tx(sb + BAR_CSLD, 24576);
        tma_ld3(sb + OFF_STG, &p.wqkv, sb + BAR_CSLD, 128 * n, 64 * m, 0);
#pragma unroll 1
        for (int h = 0; h < 2; h++) {
          const uint32_t xr = sb + BAR_XRDY + 8 * h;
          mbar_expect_tx(xr, 16384);
          tma_ld2(sb + OFF_X + h * 16384, &p.xin, xr, 128 * n + 64 * h, 128 * m);
          asm volatile("mbarrier.arrive.shared::cta.b64 _, [%0], 3;" ::"r"(xr) : "memory");
        }
        PROF_U(6);
      }
      __syncwarp();
      bar_arrive(BAR_INIT0, 160);
      bar_arrive(BAR_INIT, 256);
      producer<false>(p, sb, m, n, lane);
    }
  }
}

typedef CUresult (*EncodeFn)(CUtensorMap*, CUtensorMapDataType, cuuint32_t, void*, const cuuint64_t*, const cuuint64_t*,
                             const cuuint32_t*, const cuuint32_t*, CUtensorMapInterleave, CUtensorMapSwizzle,
                             CUtensorMapL2promotion, CUtensorMapFloatOOBfill);

void make_2d(EncodeFn enc, CUtensorMap* m, const void* ptr, uint64_t cols, uint64_t rows, uint32_t box_rows) {
  cuuint64_t d[2] = {cols, rows}, st[1] = {cols * 2};
  cuuint32_t b[2] = {64, box_rows}, e[2] = {1, 1};
  enc(m, CU_TENSOR_MAP_DATA_TYPE_BFLOAT16, 2, const_cast<void*>(ptr), d, st, b, e, CU_TENSOR_MAP_INTERLEAVE_NONE,
      CU_TENSOR_MAP_SWIZZLE_128B, CU_TENSOR_MAP_L2_PROMOTION_L2_128B, CU_TENSOR_MAP_FLOAT_OOB_FILL_NONE);
}
void make_3d(EncodeFn enc, CUtensorMap* m, const void* ptr, uint64_t d0, uint64_t rows, uint64_t d2, uint64_t row_bytes,
             uint64_t chunk_bytes, uint32_t box_chunks) {
  cuuint64_t d[3] = {d0, rows, d2}, st[2] = {row_bytes, chunk_bytes};
  cuuint32_t b[3] = {64, 64, box_chunks}, e[3] = {1, 1, 1};
  enc(m, CU_TENSOR_MAP_DATA_TYPE_BFLOAT16, 3, const_cast<void*>(ptr), d, st, b, e, CU_TENSOR_MAP_INTERLEAVE_NONE,
      CU_TENSOR_MAP_SWIZZLE_128B, CU_TENSOR_MAP_L2_PROMOTION_L2_128B, CU_TENSOR_MAP_FLOAT_OOB_FILL_NONE);
}

}

extern "C" void kernel_launch(void* const* d_in, const int* in_sizes, int n_in, void* d_out, int out_size) {
  (void)in_sizes; (void)n_in; (void)out_size;
  static EncodeFn enc = nullptr;
  static void *att = nullptr, *hbuf = nullptr, *scratch = nullptr;
  static int by_smid = 0;
  if (!enc) {
    void* fn = nullptr;
    cudaDriverEntryPointQueryResult q;
    cudaGetDriverEntryPoint("cuTensorMapEncodeTiled", &fn, cudaEnableDefault, &q);
    enc = (EncodeFn)fn;
    cudaGetSymbolAddress(&att, g_att);
    cudaGetSymbolAddress(&hbuf, g_h);
    cudaGetSymbolAddress(&scratch, g_scratch);
    cudaFuncSetAttribute(fused_layers_kernel, cudaFuncAttributeMaxDynamicSharedMemorySize, SMEM_BYTES);
    int sms = 0, per_sm = 0, dev = 0;
    cudaGetDevice(&dev);
    cudaDeviceGetAttribute(&sms, cudaDevAttrMultiProcessorCount, dev);
    cudaOccupancyMaxActiveBlocksPerMultiprocessor(&per_sm, fused_layers_kernel, 384, SMEM_BYTES);
    by_smid = sms == 132 && per_sm == 1;
  }
  Params p;
  make_2d(enc, &p.xin, d_in[0], DM, SEQ, 128);
  make_2d(enc, &p.out, d_out, DM, SEQ, 128);
  make_2d(enc, &p.att, att, DM, SEQ, 128);
  make_2d(enc, &p.h, hbuf, FF, SEQ, 128);
  make_2d(enc, &p.out_st, d_out, DM, SEQ, 32);
  make_2d(enc, &p.att_st, att, DM, SEQ, 32);
  make_2d(enc, &p.h_st, hbuf, FF, SEQ, 32);
  make_2d(enc, &p.w1c, d_in[4], FF, DM, 32);
  make_3d(enc, &p.wqkv, d_in[1], DM, DM, 3, 3 * DM * 2, DM * 2, 3);
  make_3d(enc, &p.wo, d_in[2], 64, DM, DM / 64, DM * 2, 128, 2);
  make_3d(enc, &p.w1a, d_in[4], 64, DM, FF / 64, FF * 2, 128, 3);
  make_3d(enc, &p.w1b, d_in[4], 64, DM, FF / 64, FF * 2, 128, 2);
  make_3d(enc, &p.w2, d_in[6], 64, FF, DM / 64, DM * 2, 128, 2);
  p.b1 = (const __nv_bfloat16*)d_in[5];
  p.b2 = (const __nv_bfloat16*)d_in[7];
  p.g = (Scratch*)scratch;
  p.zero = 0;
  fused_layers_kernel<<<by_smid ? 132 : NCTA, 384, SMEM_BYTES>>>(by_smid, (const __nv_bfloat16*)d_in[0], (const __nv_bfloat16*)d_in[1], p);
}
```

```cpp
#include <cuda_runtime.h>
#include <cuda_bf16.h>
#include <cuda.h>
#include <stdint.h>

namespace {

constexpr int SEQ = 2048, DM = 1024, FF = 3584;
constexpr int NCTA = 128;
constexpr int NBAR = 5;

constexpr uint32_t RING_UNITS = 20, UNIT = 8192;
constexpr uint32_t OFF_X   = RING_UNITS * UNIT;
constexpr uint32_t OFF_STG = OFF_X + 32768;
constexpr uint32_t OFF_HLP = OFF_STG + 16384;
constexpr uint32_t OFF_RUN = OFF_STG + 24576;
constexpr uint32_t OFF_CSQ = OFF_RUN + 512;
constexpr uint32_t OFF_CSF = OFF_CSQ + 2048;
constexpr uint32_t OFF_ROW = OFF_CSF + 3584;
constexpr uint32_t OFF_BAR = OFF_ROW + 1024;
constexpr uint32_t SMEM_BYTES = OFF_BAR + 384;
constexpr uint32_t BAR_FULL = OFF_BAR, BAR_EMPTY = OFF_BAR + 8 * NBAR;
constexpr uint32_t BAR_XRDY = OFF_BAR + 80;
constexpr uint32_t BAR_DUMMY = OFF_BAR + 96, OFF_TAG = OFF_BAR + 104, OFF_ZERO = OFF_BAR + 112;
constexpr uint32_t BAR_PUB = OFF_BAR + 128;
constexpr uint32_t BAR_CSLD = OFF_BAR + 200;
constexpr uint32_t BAR_BIAS = OFF_BAR + 216;

constexpr uint64_t DESC_A = (1ull << 62) | ((uint64_t)(2048 >> 4) << 32) | (1ull << 16);
constexpr uint64_t DESC_B = (1ull << 62) | ((uint64_t)(1024 >> 4) << 32) | ((uint64_t)(8192 >> 4) << 16);

constexpr int BAR_INIT = 0, BAR_ORDER = 1, BAR_GUARD = 3, BAR_WG = 5, BAR_GO = 7, BAR_DONE = 8, BAR_HLP = 9, BAR_INIT0 = 10, BAR_PAIR = 11;
#define GELU_DEP 3
#define MAP 3
#define LATE_O 0
#define HALO_NS 400
#define WIN1 7
#define WIN2 4

struct Scratch {
  uint4 stats[4 * 8 * SEQ];
  uint4 halo[2 * 2 * 16 * 8 * 384];
  uint4 csp[2 * 8 * 17 * 224];
  uint32_t flags[16 * 32];
  uint32_t epoch[NCTA + 4];
};

struct Params {
  CUtensorMap xin, out, att, h, wqkv, wo, w1a, w1b, w2, out_st, att_st, h_st, w1c;
  const __nv_bfloat16 *b1, *b2;
  Scratch* g;
  uint32_t zero;
};

__device__ __nv_bfloat16 g_att[SEQ * DM];
__device__ __nv_bfloat16 g_h[SEQ * FF];
__device__ Scratch g_scratch;
#define PROF_T(idx)
#define PROF_U(k)
#define PROF_S(g)
#define PROF_E(i, k)

__device__ __forceinline__ void mbar_init(uint32_t bar, int cnt) {
  asm volatile("mbarrier.init.shared::cta.b64 [%0], %1;" ::"r"(bar), "r"(cnt));
}
__device__ __forceinline__ void mbar_expect_tx(uint32_t bar, uint32_t bytes) {
  asm volatile("mbarrier.arrive.expect_tx.shared::cta.b64 _, [%0], %1;" ::"r"(bar), "r"(bytes) : "memory");
}
__device__ __forceinline__ void mbar_arrive(uint32_t bar) {
  asm volatile("mbarrier.arrive.shared::cta.b64 _, [%0];" ::"r"(bar) : "memory");
}
__device__ __forceinline__ bool mbar_test(uint32_t bar, uint32_t parity) {
  uint32_t ok;
  asm volatile("{\n.reg .pred p;\nmbarrier.test_wait.parity.shared::cta.b64 p, [%1], %2;\nselp.u32 %0, 1, 0, p;\n}"
               : "=r"(ok) : "r"(bar), "r"(parity) : "memory");
  return ok;
}
__device__ __forceinline__ void mbar_wait(uint32_t bar, uint32_t parity) {
  asm volatile(
      "{\n.reg .pred p;\n.reg .u32 it;\nmov.u32 it, 0;\n"
      "WAIT_LOOP:\n"
      "mbarrier.try_wait.parity.shared::cta.b64 p, [%0], %1;\n"
      "@p bra WAIT_DONE;\n"
      "add.u32 it, it, 1;\n"
      "setp.lt.u32 p, it, 0x400000;\n"
      "@p bra WAIT_LOOP;\n"
      "trap;\n"
      "WAIT_DONE:\n}"
      ::"r"(bar), "r"(parity) : "memory");
}
__device__ __forceinline__ void bar_sync(int id, int n) { asm volatile("bar.sync %0, %1;" ::"r"(id), "r"(n) : "memory"); }
__device__ __forceinline__ void bar_arrive(int id, int n) { asm volatile("bar.arrive %0, %1;" ::"r"(id), "r"(n) : "memory"); }
__device__ __forceinline__ void tma_ld2(uint32_t dst, const CUtensorMap* m, uint32_t bar, int c0, int c1) {
  asm volatile("cp.async.bulk.tensor.2d.shared::cluster.global.mbarrier::complete_tx::bytes [%0], [%1, {%3, %4}], [%2];"
               ::"r"(dst), "l"(m), "r"(bar), "r"(c0), "r"(c1) : "memory");
}
__device__ __forceinline__ void tma_ld3(uint32_t dst, const CUtensorMap* m, uint32_t bar, int c0, int c1, int c2) {
  asm volatile("cp.async.bulk.tensor.3d.shared::cluster.global.mbarrier::complete_tx::bytes [%0], [%1, {%3, %4, %5}], [%2];"
               ::"r"(dst), "l"(m), "r"(bar), "r"(c0), "r"(c1), "r"(c2) : "memory");
}
__device__ __forceinline__ void tma_st2(const CUtensorMap* m, uint32_t src, int c0, int c1) {
  asm volatile("cp.async.bulk.tensor.2d.global.shared::cta.bulk_group [%0, {%2, %3}], [%1];"
               ::"l"(m), "r"(src), "r"(c0), "r"(c1) : "memory");
}
__device__ __forceinline__ void bulk_commit() { asm volatile("cp.async.bulk.commit_group;" ::: "memory"); }
__device__ __forceinline__ void bulk_wait_read() { asm volatile("cp.async.bulk.wait_group.read 0;" ::: "memory"); }
__device__ __forceinline__ void bulk_wait_all() { asm volatile("cp.async.bulk.wait_group 0;" ::: "memory"); }
__device__ __forceinline__ void fence_async_smem() { asm volatile("fence.proxy.async.shared::cta;" ::: "memory"); }
__device__ __forceinline__ void fence_async_global() { asm volatile("fence.proxy.async.global;" ::: "memory"); }
__device__ __forceinline__ void st_relaxed(uint32_t* p, uint32_t v) {
  asm volatile("st.relaxed.gpu.global.u32 [%0], %1;" ::"l"(p), "r"(v) : "memory");
}
__device__ __forceinline__ void st_msg(uint4* p, uint32_t a, uint32_t b, uint32_t c, uint32_t tag) {
  asm volatile("{\n.reg .b128 v;\nmov.b128 v, {%1, %2, %3, %4};\nst.relaxed.gpu.global.b128 [%0], v;\n}"
               ::"l"(p), "r"(a), "r"(b), "r"(c), "r"(tag) : "memory");
}
__device__ __forceinline__ void ld_msg(const uint4* p, uint32_t& a, uint32_t& b, uint32_t& c, uint32_t& tag) {
  asm volatile("{\n.reg .b128 v;\nld.relaxed.gpu.global.b128 v, [%4];\nmov.b128 {%0, %1, %2, %3}, v;\n}"
               : "=r"(a), "=r"(b), "=r"(c), "=r"(tag) : "l"(p) : "memory");
}
__device__ __forceinline__ bool elect_one() {
  uint32_t ok;
  asm volatile("{\n.reg .pred p;\nelect.sync _|p, 0xffffffff;\nselp.u32 %0, 1, 0, p;\n}" : "=r"(ok));
  return ok;
}
__device__ __forceinline__ int uniform(int v) { return __shfl_sync(0xffffffffu, v, 0); }
__device__ __forceinline__ uint32_t pack_bf16(float lo, float hi) {
  uint32_t r;
  asm("cvt.rn.bf16x2.f32 %0, %1, %2;" : "=r"(r) : "f"(hi), "f"(lo));
  return r;
}
__device__ __forceinline__ uint32_t prmt_u(uint32_t a, uint32_t sel) {
  uint32_t r;
  asm("prmt.b32 %0, %1, 0, %2;" : "=r"(r) : "r"(a), "r"(sel));
  return r;
}
__device__ __forceinline__ float prmt_f(uint32_t a, uint32_t sel) {
  float r;
  asm("{\n.reg .b32 t;\nprmt.b32 t, %1, 0, %2;\nmov.b32 %0, t;\n}" : "=f"(r) : "r"(a), "r"(sel));
  return r;
}
__device__ __forceinline__ float bf_lo(uint32_t v) { return __uint_as_float(v << 16); }
__device__ __forceinline__ float bf_hi(uint32_t v) { return __uint_as_float(v & 0xffff0000u); }
__device__ __forceinline__ void stsm4(uint32_t addr, uint32_t r0, uint32_t r1, uint32_t r2, uint32_t r3) {
  asm volatile("stmatrix.sync.aligned.m8n8.x4.shared.b16 [%0], {%1, %2, %3, %4};"
               ::"r"(addr), "r"(r0), "r"(r1), "r"(r2), "r"(r3) : "memory");
}
__device__ __forceinline__ void ldsm4(uint32_t addr, uint32_t& r0, uint32_t& r1, uint32_t& r2, uint32_t& r3) {
  asm volatile("ldmatrix.sync.aligned.m8n8.x4.shared.b16 {%0, %1, %2, %3}, [%4];"
               : "=r"(r0), "=r"(r1), "=r"(r2), "=r"(r3) : "r"(addr) : "memory");
}
__device__ __forceinline__ uint32_t movtrans(uint32_t a) {
  uint32_t d;
  asm volatile("movmatrix.sync.aligned.m8n8.trans.b16 %0, %1;" : "=r"(d) : "r"(a));
  return d;
}
__device__ __forceinline__ void mma16816(float (&c)[4], uint32_t a0, uint32_t a1, uint32_t a2, uint32_t a3, uint32_t b0, uint32_t b1) {
  asm volatile("mma.sync.aligned.m16n8k16.row.col.f32.bf16.bf16.f32 {%0,%1,%2,%3}, {%4,%5,%6,%7}, {%8,%9}, {%0,%1,%2,%3};"
               : "+f"(c[0]), "+f"(c[1]), "+f"(c[2]), "+f"(c[3])
               : "r"(a0), "r"(a1), "r"(a2), "r"(a3), "r"(b0), "r"(b1));
}
__device__ __forceinline__ float2 lds_f2(uint32_t a) {
  float2 v;
  asm volatile("ld.shared.v2.f32 {%0, %1}, [%2];" : "=f"(v.x), "=f"(v.y) : "r"(a) : "memory");
  return v;
}
__device__ __forceinline__ float4 lds_f4(uint32_t a) {
  float4 v;
  asm volatile("ld.shared.v4.f32 {%0, %1, %2, %3}, [%4];" : "=f"(v.x), "=f"(v.y), "=f"(v.z), "=f"(v.w) : "r"(a) : "memory");
  return v;
}
__device__ __forceinline__ float lds_f(uint32_t a) {
  float v;
  asm volatile("ld.shared.f32 %0, [%1];" : "=f"(v) : "r"(a) : "memory");
  return v;
}
__device__ __forceinline__ uint32_t lds_u(uint32_t a) {
  uint32_t v;
  asm volatile("ld.shared.u32 %0, [%1];" : "=r"(v) : "r"(a) : "memory");
  return v;
}
__device__ __forceinline__ void sts_f2(uint32_t a, float x, float y) {
  asm volatile("st.shared.v2.f32 [%0], {%1, %2};" ::"r"(a), "f"(x), "f"(y) : "memory");
}
__device__ __forceinline__ void sts_u4(uint32_t a, uint32_t x, uint32_t y, uint32_t z, uint32_t w) {
  asm volatile("st.shared.v4.u32 [%0], {%1, %2, %3, %4};" ::"r"(a), "r"(x), "r"(y), "r"(z), "r"(w) : "memory");
}
__device__ __forceinline__ void lds_u4(uint32_t a, uint32_t& x, uint32_t& y, uint32_t& z, uint32_t& w) {
  asm volatile("ld.shared.v4.u32 {%0, %1, %2, %3}, [%4];" : "=r"(x), "=r"(y), "=r"(z), "=r"(w) : "r"(a) : "memory");
}
__device__ __forceinline__ float ex2(float x) {
  float y;
  asm("ex2.approx.ftz.f32 %0, %1;" : "=f"(y) : "f"(x));
  return y;
}
__device__ __forceinline__ float rcp_hw(float x) {
  float y;
  asm("rcp.approx.ftz.f32 %0, %1;" : "=f"(y) : "f"(x));
  return y;
}
__device__ __forceinline__ float tanh_hw(float x) {
  float y;
  asm("tanh.approx.f32 %0, %1;" : "=f"(y) : "f"(x));
  return y;
}
__device__ __forceinline__ float quad_sum(float v) {
  v += __shfl_xor_sync(0xffffffffu, v, 1);
  return v + __shfl_xor_sync(0xffffffffu, v, 2);
}
__device__ __forceinline__ float quad_max(float v) {
  v = fmaxf(v, __shfl_xor_sync(0xffffffffu, v, 1));
  return fmaxf(v, __shfl_xor_sync(0xffffffffu, v, 2));
}

template <int N> __device__ __forceinline__ void wgmma_ss(float (&d)[96], uint64_t da, uint64_t db, uint32_t keep = 1);
template <> __device__ __forceinline__ void wgmma_ss<128>(float (&d)[96], uint64_t da, uint64_t db, uint32_t keep) {
  asm volatile(
      "{\n.reg .pred p;\nsetp.ne.u32 p, %66, 0;\n"
      "wgmma.mma_async.sync.aligned.m64n128k16.f32.bf16.bf16 {%0, %1, %2, %3, %4, %5, %6, %7, %8, %9, %10, %11, %12, %13, %14, %15, %16, %17, %18, %19, %20, %21, %22, %23, %24, %25, %26, %27, %28, %29, %30, %31, %32, %33, %34, %35, %36, %37, %38, %39, %40, %41, %42, %43, %44, %45, %46, %47, %48, %49, %50, %51, %52, %53, %54, %55, %56, %57, %58, %59, %60, %61, %62, %63}, %64, %65, p, 1, 1, 0, 1;\n}"
      : "+f"(d[0]), "+f"(d[1]), "+f"(d[2]), "+f"(d[3]), "+f"(d[4]), "+f"(d[5]), "+f"(d[6]), "+f"(d[7]), "+f"(d[8]), "+f"(d[9]), "+f"(d[10]), "+f"(d[11]), "+f"(d[12]), "+f"(d[13]), "+f"(d[14]), "+f"(d[15]), "+f"(d[16]), "+f"(d[17]), "+f"(d[18]), "+f"(d[19]), "+f"(d[20]), "+f"(d[21]), "+f"(d[22]), "+f"(d[23]), "+f"(d[24]), "+f"(d[25]), "+f"(d[26]), "+f"(d[27]), "+f"(d[28]), "+f"(d[29]), "+f"(d[30]), "+f"(d[31]), "+f"(d[32]), "+f"(d[33]), "+f"(d[34]), "+f"(d[35]), "+f"(d[36]), "+f"(d[37]), "+f"(d[38]), "+f"(d[39]), "+f"(d[40]), "+f"(d[41]), "+f"(d[42]), "+f"(d[43]), "+f"(d[44]), "+f"(d[45]), "+f"(d[46]), "+f"(d[47]), "+f"(d[48]), "+f"(d[49]), "+f"(d[50]), "+f"(d[51]), "+f"(d[52]), "+f"(d[53]), "+f"(d[54]), "+f"(d[55]), "+f"(d[56]), "+f"(d[57]), "+f"(d[58]), "+f"(d[59]), "+f"(d[60]), "+f"(d[61]), "+f"(d[62]), "+f"(d[63])
      : "l"(da), "l"(db), "r"(keep));
}

template <> __device__ __forceinline__ void wgmma_ss<192>(float (&d)[96], uint64_t da, uint64_t db, uint32_t keep) {
  asm volatile(
      "{\n.reg .pred p;\nsetp.ne.u32 p, %98, 0;\n"
      "wgmma.mma_async.sync.aligned.m64n192k16.f32.bf16.bf16 {%0, %1, %2, %3, %4, %5, %6, %7, %8, %9, %10, %11, %12, %13, %14, %15, %16, %17, %18, %19, %20, %21, %22, %23, %24, %25, %26, %27, %28, %29, %30, %31, %32, %33, %34, %35, %36, %37, %38, %39, %40, %41, %42, %43, %44, %45, %46, %47, %48, %49, %50, %51, %52, %53, %54, %55, %56, %57, %58, %59, %60, %61, %62, %63, %64, %65, %66, %67, %68, %69, %70, %71, %72, %73, %74, %75, %76, %77, %78, %79, %80, %81, %82, %83, %84, %85, %86, %87, %88, %89, %90, %91, %92, %93, %94, %95}, %96, %97, p, 1, 1, 0, 1;\n}"
      : "+f"(d[0]), "+f"(d[1]), "+f"(d[2]), "+f"(d[3]), "+f"(d[4]), "+f"(d[5]), "+f"(d[6]), "+f"(d[7]), "+f"(d[8]), "+f"(d[9]), "+f"(d[10]), "+f"(d[11]), "+f"(d[12]), "+f"(d[13]), "+f"(d[14]), "+f"(d[15]), "+f"(d[16]), "+f"(d[17]), "+f"(d[18]), "+f"(d[19]), "+f"(d[20]), "+f"(d[21]), "+f"(d[22]), "+f"(d[23]), "+f"(d[24]), "+f"(d[25]), "+f"(d[26]), "+f"(d[27]), "+f"(d[28]), "+f"(d[29]), "+f"(d[30]), "+f"(d[31]), "+f"(d[32]), "+f"(d[33]), "+f"(d[34]), "+f"(d[35]), "+f"(d[36]), "+f"(d[37]), "+f"(d[38]), "+f"(d[39]), "+f"(d[40]), "+f"(d[41]), "+f"(d[42]), "+f"(d[43]), "+f"(d[44]), "+f"(d[45]), "+f"(d[46]), "+f"(d[47]), "+f"(d[48]), "+f"(d[49]), "+f"(d[50]), "+f"(d[51]), "+f"(d[52]), "+f"(d[53]), "+f"(d[54]), "+f"(d[55]), "+f"(d[56]), "+f"(d[57]), "+f"(d[58]), "+f"(d[59]), "+f"(d[60]), "+f"(d[61]), "+f"(d[62]), "+f"(d[63]), "+f"(d[64]), "+f"(d[65]), "+f"(d[66]), "+f"(d[67]), "+f"(d[68]), "+f"(d[69]), "+f"(d[70]), "+f"(d[71]), "+f"(d[72]), "+f"(d[73]), "+f"(d[74]), "+f"(d[75]), "+f"(d[76]), "+f"(d[77]), "+f"(d[78]), "+f"(d[79]), "+f"(d[80]), "+f"(d[81]), "+f"(d[82]), "+f"(d[83]), "+f"(d[84]), "+f"(d[85]), "+f"(d[86]), "+f"(d[87]), "+f"(d[88]), "+f"(d[89]), "+f"(d[90]), "+f"(d[91]), "+f"(d[92]), "+f"(d[93]), "+f"(d[94]), "+f"(d[95])
      : "l"(da), "l"(db), "r"(keep));
}

template <int R>
__device__ __forceinline__ void pin_regs(float (&a)[2][96]) {
#pragma unroll
  for (int m = 0; m < 2; m++)
#pragma unroll
    for (int i = 0; i < R; i++) asm volatile("" : "+f"(a[m][i])::"memory");
}

struct Ctx {
  uint32_t sb;
  int m, n, wg, w, lane;
};
__device__ __forceinline__ Ctx make_ctx(uint32_t sb, int id) {
  int lane;
  asm volatile("mov.u32 %0, %%laneid;" : "=r"(lane));
  asm volatile("" : "+r"(id), "+r"(sb));
  return Ctx{sb, (id >> 3) & 15, id & 7, id >> 9, (id >> 7) & 3, lane};
}
#define UNPACK_CTX(c) const uint32_t sb = c.sb; const int m = c.m, n = c.n, wg = c.wg, w = c.w, lane = c.lane

__device__ __forceinline__ uint32_t poll_line(const uint32_t* word, uint32_t target, uint32_t need) {
  uint32_t v;
  asm volatile(
      "{\n.reg .pred p;\n.reg .u32 it, m;\n.reg .s32 d;\nmov.u32 it, 0;\n"
      "POLL_LOOP:\n"
      "ld.relaxed.gpu.global.u32 %0, [%1];\n"
      "sub.s32 d, %0, %2;\n"
      "setp.ge.s32 p, d, 0;\n"
      "vote.sync.ballot.b32 m, p, 0xffffffff;\n"
      "and.b32 m, m, %3;\n"
      "setp.eq.u32 p, m, %3;\n"
      "@p bra.uni POLL_DONE;\n"
      "add.u32 it, it, 1;\n"
      "setp.lt.u32 p, it, 0x400000;\n"
      "@p bra.uni POLL_LOOP;\n"
      "trap;\n"
      "POLL_DONE:\n}"
      : "=&r"(v) : "l"(word), "r"(target), "r"(need) : "memory");
  return v;
}
__device__ __forceinline__ uint32_t ld_relaxed(const uint32_t* p) {
  uint32_t v;
  asm volatile("ld.relaxed.gpu.global.u32 %0, [%1];" : "=r"(v) : "l"(p) : "memory");
  return v;
}
__device__ __forceinline__ float chain(float x, uint32_t on, uint32_t zero) {
  return __uint_as_float(__float_as_uint(x) | (on & zero));
}
constexpr int MSG_SPINS = 1 << 20;

constexpr int STAGES_PER_LAYER = 152;
__device__ __forceinline__ int nib(uint64_t v, int i) { return (int)(v >> (4 * i)) & 15; }
__device__ __forceinline__ bool tile_wide(int t) { return (0x23 >> t) & 1; }
__device__ __forceinline__ void weight_coords(const Params& p, int t, int n, const CUtensorMap*& map, int& c0, int& c2) {
  map = &p.wqkv + nib(0x4233100ull, t);
  c0 = t < 2 ? 128 * n + 64 * t : 0;
  c2 = t < 2 ? 0 : (t == 2 || t == 6) ? 2 * n : 7 * n + 2 * t - 6;
}

template <bool IS_A>
__device__ __forceinline__ void producer(const Params& p, uint32_t sb, int m, int n, int lane) {
  const uint32_t low = (1u << (4 * n)) - 1, others = (0x6543210u & low) | (0x7654321u & ~low);
  const uint64_t order_x = (uint64_t)(others * 2 + 0x1111111u) << 36 | (uint64_t)others * 2 << 8 | (n * 0x22 + 0x10);
  int inflight = 4, cur = 0;
  uint32_t fb = sb + BAR_FULL + 32, rb = sb + BAR_EMPTY, rph = 0, pos = 0, tag32 = 0, seen = 0;
  const uint32_t fend = sb + BAR_FULL + 8 * NBAR, rend = sb + BAR_EMPTY + 8 * NBAR;
  const uint32_t* word = p.g->flags + m * 32 + (lane < 16 ? lane >> 1 : lane & 7);
#pragma unroll 1
  for (int sg = 1; sg < 22; sg++) {
    const int layer = sg >= 11, s = sg == 1 ? 2 : sg == 2 ? 1 : sg - 11 * layer;
    const int t = nib(0x65434321010ull, s), kind = nib(0x32110031100ull, s);
    const bool wide = tile_wide(t);
    const uint32_t bbytes = wide ? 3 * UNIT : 2 * UNIT, base = sb + (IS_A ? bbytes : 0);
    const int mul = t == 6 ? 448 : t == 2 ? 128 : 64, count = sg == 1 ? 12 : 2 * nib(0x4871ull, kind);
    uint64_t order0 = sg == 1 ? 0xFEDCBA987654ull : kind == 3 ? 0x76543210u : order_x >> (8 * (kind & 1));
    uint32_t special = (s == 4 || s == 10) ? 0x10 : s == 9 ? 0xF : 1;
    if (IS_A) special |= (kind & 1 ? 0 : 3) | (count >= 4 ? 1u << (count - 4) : 0);
    if (s >= 9) pos = (s + 6) * UNIT;
    const CUtensorMap* map;
    int c0 = 0, c2 = 0, ev = 0;
    if (IS_A) {
      map = &p.xin + (t == 2 ? 2 : t == 6 ? 3 : sg >= 4);
      ev = 9 * layer + (t < 2 ? 0 : t == 2 ? 1 : t < 6 ? 4 : 5);
      if (sg == 2) seen = tag32 = (__ldcg(p.g->epoch + m * 8 + n) + 1) << 5;
    } else {
      weight_coords(p, t, n, map, c0, c2);
    }
#pragma unroll 1
    for (int add = 0; add < mul; add += 64) {
      uint64_t order = order0;
      const int need = kind == 3 ? ev : ev - 1 + (lane & 1), sh = kind == 3 ? 16 : 0;
      uint32_t ready = IS_A ? __ballot_sync(0xffffffffu, cur >= need) >> sh : 0;
#pragma unroll 1
      for (int k = 0; k < count; k++) {
        const int code = order & 15, kc = code * mul + add;
        order >>= 4;
        if ((special >> k) & 1) {
          const int lag = wide ? (s == 9 && k == 2 ? 2 : 3) : ((s == 4 || s == 10) && add == 0 && k < 4) ? 3 : 4;
#pragma unroll 1
          for (; inflight > lag; inflight--) {
            mbar_wait(rb, rph);
            rb += 8;
            if (rb == rend) { rb -= 8 * NBAR; rph ^= 1; }
          }
          inflight++;
          if (IS_A) {
            if (kind == 3 ? t == 2 && add + k == 64 : !(kind & 1) && k < 2) {
              if (t == 2) mbar_wait(sb + BAR_PUB + 8, layer);
              else if (k == 1 && (s == 0 || s == 5)) mbar_wait(sb + BAR_XRDY + 8, s == 5);
              if (elect_one()) mbar_arrive(fb);
              goto next_stage;
            }
            if (k == count - 4 && sg >= 3) seen = ld_relaxed(word);
          }
        } else {
          mbar_wait(rb, rph);
          rb += 8;
          if (rb == rend) { rb -= 8 * NBAR; rph ^= 1; }
        }
        if (IS_A && !((ready >> code) & 1)) {
          cur = max(cur, (int)(seen - tag32));
          ready = __ballot_sync(0xffffffffu, cur >= need) >> sh;
          if (!((ready >> code) & 1)) {
            cur = (int)(poll_line(word, tag32 + need, 1u << (code + sh)) - tag32);
            ready = __ballot_sync(0xffffffffu, cur >= need) >> sh;
          }
          asm volatile("fence.acquire.gpu;" ::: "memory");
          fence_async_global();
        }
        if (elect_one()) {
          if (!IS_A) tma_ld3(base + pos, map, fb, c0, kc, c2);
          else tma_ld2(base + pos, map, fb, kc, 128 * m);
          mbar_expect_tx(fb, IS_A ? 16384 : bbytes);
        }
      next_stage:
        fb += 8;
        if (fb == fend) fb -= 8 * NBAR;
        pos += bbytes + 2 * UNIT;
        if (pos >= RING_UNITS * UNIT) pos -= RING_UNITS * UNIT;
      }
      special = !IS_A ? 0 : t == 2 ? 1 : add == 128 ? 0x10 : 0;
      if (t == 2) order0 = others << 4 | n;
      if (IS_A && (t == 2 || add == 64 || add == 192)) ev++;
    }
  }
}

__device__ __forceinline__ void publisher(const Params& p, uint32_t sb, int m, int n) {
  const uint32_t tag = __ldcg(p.g->epoch + m * 8 + n) + 1;
  uint32_t* word = p.g->flags + m * 32 + n;
  const int mn = m * 8 + n; (void)mn;
  st_relaxed(word, 32 * tag);
#pragma unroll 1
  for (int c = 0; c < 18; c++) {
    const int e = c >= 9 ? c - 9 : c;
    if ((0x18C >> e) & 1) {
      const int half = (0x108 >> e) & 1;
      mbar_wait(sb + BAR_XRDY + 8 * half, e < 4);
#pragma unroll
      for (int w = 0; w < 4; w++) tma_st2(&p.out_st, sb + OFF_X + half * 16384 + w * 4096, 128 * n + 64 * half, 128 * m + 32 * w);
      bulk_commit();
      if (c >= 16) continue;
      bulk_wait_all();
      PROF_E(7 * (c >= 9) + (e < 4 ? 2 : 6), 11 + 2 * half);
    } else {
      mbar_wait(sb + BAR_PUB + 8 * e, c >= 9);
    }
    asm volatile("fence.release.gpu;" ::: "memory");
    asm volatile("red.relaxed.gpu.global.add.u32 [%0], 1;" ::"l"(word) : "memory");
    PROF_E(7 * (c >= 9) + nib(0x665432210ull, e), (0x108 >> e) & 1 ? 14 : 12);
  }
  p.g->epoch[m * 8 + n] = tag;
  bulk_wait_read();
}

__device__ __forceinline__ void sum_rows(uint32_t buf, int iters, float (&a)[8], int lane) {
  uint32_t addr = buf + (lane >> 3) * 128 + (((lane & 7) ^ (lane >> 3)) << 4);
#pragma unroll 1
  for (int it = 0; it < iters; it++) {
    uint32_t u[2][4];
    lds_u4(addr, u[0][0], u[0][1], u[0][2], u[0][3]);
    lds_u4((addr ^ 64) + 512, u[1][0], u[1][1], u[1][2], u[1][3]);
    addr += 1024;
#pragma unroll
    for (int e = 0; e < 8; e++) { a[2 * (e & 3)] += bf_lo(u[e >> 2][e & 3]); a[2 * (e & 3) + 1] += bf_hi(u[e >> 2][e & 3]); }
  }
}
__device__ __forceinline__ void publish_sums(const float (&a)[8], uint4* dst, int lane, uint32_t tag) {
  const bool u8 = lane & 8, u16 = lane & 16;
  float h4[4], h2[2];
#pragma unroll
  for (int e = 0; e < 4; e++) h4[e] = (u8 ? a[4 + e] : a[e]) + __shfl_xor_sync(0xffffffffu, u8 ? a[e] : a[4 + e], 8);
#pragma unroll
  for (int e = 0; e < 2; e++) h2[e] = (u16 ? h4[2 + e] : h4[e]) + __shfl_xor_sync(0xffffffffu, u16 ? h4[e] : h4[2 + e], 16);
  st_msg(dst + (lane & 7) * 4 + (u8 ? 2 : 0) + (u16 ? 1 : 0), __float_as_uint(h2[0]), __float_as_uint(h2[1]), 0u, tag);
}

__device__ __forceinline__ void colsum_helper(const Params& p, uint32_t sb, int m, int n, int lane) {
  const uint32_t tag = __ldcg(p.g->epoch + m * 8 + n) + 1;
  const int mn = m * 8 + n; (void)mn;
#pragma unroll 1
  for (int k = lane; k < 288; k += 32) {
    const uint32_t bb = __ldg(reinterpret_cast<const uint32_t*>(k < 224 ? p.b1 + 448 * n : p.b2 + 128 * n - 448) + k);
    const float sc = k < 224 ? 0.5f : 1.f;
    sts_f2(sb + (k < 224 ? OFF_CSF + k * 16 + 8 : OFF_CSQ + 1536 + (k - 224) * 8), sc * bf_lo(bb), sc * bf_hi(bb));
  }
  __syncwarp();
  if (elect_one()) mbar_arrive(sb + BAR_BIAS);
  bar_sync(BAR_HLP, 160);
  PROF_E(-1, 1);
#pragma unroll 1
  for (int c = 0; c < 7; c++) {
    float a[8] = {0.f, 0.f, 0.f, 0.f, 0.f, 0.f, 0.f, 0.f};
#pragma unroll 1
    for (int h = 0; h < 2; h++) {
      if (elect_one()) {
        mbar_expect_tx(sb + BAR_CSLD + 8, 4096);
        tma_ld2(sb + OFF_HLP, &p.w1c, sb + BAR_CSLD + 8, 448 * n + 64 * c, 64 * m + 32 * h);
        if (c < 6) asm volatile("cp.async.bulk.prefetch.tensor.2d.L2.global [%0, {%1, %2}];" ::"l"(&p.w1c), "r"(448 * n + 64 * c + 64), "r"(64 * m + 32 * h) : "memory");
      }
      mbar_wait(sb + BAR_CSLD + 8, h);
      sum_rows(sb + OFF_HLP, 4, a, lane);
      __syncwarp();
    }
    publish_sums(a, p.g->csp + ((8 + n) * 17 + m) * 224 + c * 32, lane, tag);
  }
  PROF_E(-1, 2);
}

__device__ __forceinline__ void poll_msgs2(const uint4* pa, const uint4* pb, float (&v)[4], uint32_t tag) {
#pragma unroll 1
  for (int it = 0; it < MSG_SPINS; it++) {
    uint32_t x[4], z, ta, tb;
    ld_msg(pa, x[0], x[1], z, ta);
    ld_msg(pb, x[2], x[3], z, tb);
#pragma unroll
    for (int e = 0; e < 4; e++) v[e] = __uint_as_float(x[e]);
    if (__all_sync(0xffffffffu, ta == tag && tb == tag)) break;
  }
}
__device__ __forceinline__ void colsum_total(const Params& p, const Ctx& cx, int mat, uint32_t tag) {
  uint4* base = p.g->csp + (mat * 8 + cx.n) * 17 * 224;
  const int per = 12 + 2 * mat, k = 2 * cx.w + (cx.lane >> 4), ia = per * cx.m + k, ib = per * cx.m + min(k + 8, per - 1);
  float v[4];
  poll_msgs2(base + (cx.lane & 15) * 224 + ia, base + (cx.lane & 15) * 224 + ib, v, tag);
#pragma unroll 1
  for (int d = 1; d < 16; d *= 2)
#pragma unroll
    for (int e = 0; e < 4; e++) v[e] += __shfl_xor_sync(0xffffffffu, v[e], d);
  const bool hi = cx.lane & 1;
  if ((cx.lane & 14) == 0) st_msg(base + 16 * 224 + (hi ? ib : ia), __float_as_uint(hi ? v[2] : v[0]), __float_as_uint(hi ? v[3] : v[1]), 0u, tag);
}
__device__ __forceinline__ void colsum_gather(const Params& p, const Ctx& cx, int mat, uint32_t tag) {
  const uint4* base = p.g->csp + ((mat * 8 + cx.n) * 17 + 16) * 224;
  const int ia = cx.w * 32 + cx.lane, ib = min(ia + 128, 191 + 32 * mat);
  float v[4];
  poll_msgs2(base + ia, base + ib, v, tag);
  const uint32_t tab = cx.sb + (mat ? OFF_CSF : OFF_CSQ);
  sts_f2(tab + (ia << (3 + mat)), v[0], v[1]);
  sts_f2(tab + (ib << (3 + mat)), v[2], v[3]);
}

constexpr uint32_t RING16 = RING_UNITS * (UNIT >> 4);
__device__ __forceinline__ bool tile_split(int i) { return (0xD98 >> i) & 1; }

__device__ __forceinline__ void write_run_desc(uint32_t sb, int i, int step) {
  const int layer = i >= 7, t = i - 7 * layer, part = tile_split(i) ? step : 2;
  const bool wide = tile_wide(t), own = t != 2 && t != 6 && part != 1 && i != 0, second = t == 1 || t == 4;
  const uint32_t z16 = (wide ? 5 : 4) * (UNIT >> 4), a_off = z16 - 1024 + (uint32_t)DESC_A - (uint32_t)DESC_B;
  const int gl = 16 * t + (part == 2 ? 0 : second ? 16 * part - 14 : 4 * part), g0 = layer * STAGES_PER_LAYER + gl;
  const uint32_t s16 = (sb & 0x3FFFF) >> 4, bfirst = (uint32_t)DESC_B + s16;
  const int nkb = t == 6 ? 56 : part == 0 ? 2 : 12 + 2 * part;
  const bool win1 = t == 1 && part != 0;
  const int run = win1 ? WIN1 + 1 : t == 2 ? WIN2 + 1 : nkb;
  const int rest = win1 ? 64 | (nkb - 1 - WIN1) : t == 2 ? 64 | (7 - WIN2) | (8 << 7) : 0;
  const uint32_t blo = bfirst + z16 * (wide ? (gl + (t == 5 ? 3 : 0)) & 3 : (gl + 3) % 5);
  const uint32_t alo = own ? (uint32_t)DESC_A + s16 + (OFF_X >> 4) : blo + a_off;
  const uint32_t aoff = own ? alo + 1024 - (blo == bfirst + RING16 - z16 ? bfirst : blo + z16) : a_off;
  const bool xwait = part == 0 && !second, keep = !(part == 0 || t == 5);
  sts_u4(sb + OFF_RUN + (2 * i + step) * 16, blo, alo, aoff,
         ((g0 / NBAR) & 1) | xwait << 1 | keep << 2 | 8 * (g0 % NBAR) | run << 6 | rest << 12);
}

template <int N>
__device__ __forceinline__ void mainloop(const Params& p, float (&acc)[2][96], uint32_t sb, int i, int step, int mn) {
  constexpr uint32_t Z16 = (2 + N / 64) * (UNIT >> 4);
  constexpr uint32_t A_OFF = Z16 - 1024 + (uint32_t)DESC_A - (uint32_t)DESC_B;
  const int wg = i & 1;
  const uint32_t s16 = (sb & 0x3FFFF) >> 4;
  const uint32_t blast = (uint32_t)DESC_B + s16 + RING16 - Z16, flast = sb + BAR_FULL + 8 * (NBAR - 1);
  uint32_t blo = (uint32_t)DESC_B + s16, alo = blo + A_OFF, aoff = A_OFF, misc = 16 << 6;
  if (N == 128 || i > 0) lds_u4(sb + OFF_RUN + (2 * i + step) * 16, blo, alo, aoff, misc);
  uint32_t keep = misc & 4;
  int run = (misc >> 6) & 63, rest = misc >> 12;
  uint32_t fb = sb + BAR_FULL + (misc & 0x38), ph = misc & 1;
  uint32_t prev = sb + BAR_DUMMY - 8 * NBAR;
  pin_regs<N / 2>(acc);
  if (N == 128 || i > 0) bar_sync(BAR_ORDER + wg, 256);
  else bar_sync(BAR_INIT0, 160);
  if (N == 192 && i == 0 && threadIdx.x == 0) PROF_U(8);
  mbar_wait(fb, ph);
  if (misc & 2) mbar_wait(sb + BAR_XRDY, N == 128);
  if (step == 0 || !tile_split(i)) PROF_T(4 + i * 4);
#pragma unroll 1
  while (true) {
    const uint64_t da = (DESC_A & ~0xffffffffull) | alo, db = (DESC_B & ~0xffffffffull) | blo;
    asm volatile("wgmma.fence.sync.aligned;" ::: "memory");
    wgmma_ss<N>(acc[0], da, db, keep);
    wgmma_ss<N>(acc[1], da + 64, db, keep);
    keep = 4;
    wgmma_ss<N>(acc[0], da + 2, db + 128);
    wgmma_ss<N>(acc[1], da + 66, db + 128);
    asm volatile("wgmma.commit_group.sync.aligned;" ::: "memory");
    asm volatile("wgmma.wait_group.sync.aligned 1;" ::: "memory");
    PROF_S(jj++);
    if (elect_one()) mbar_arrive(prev + 8 * NBAR);
    prev = fb;
    if (fb == flast) { fb -= 8 * NBAR; ph++; }
    fb += 8;
    if (blo == blast) blo -= RING16;
    blo += Z16;
    alo = blo + aoff;
    aoff = A_OFF;
    run--;
    const bool ready = mbar_test(fb, ph) && run != 0;
    asm volatile("wgmma.fence.sync.aligned;" ::: "memory");
    wgmma_ss<N>(acc[0], da + 4, db + 256);
    wgmma_ss<N>(acc[1], da + 68, db + 256);
    wgmma_ss<N>(acc[0], da + 6, db + 384);
    wgmma_ss<N>(acc[1], da + 70, db + 384);
    asm volatile("wgmma.commit_group.sync.aligned;" ::: "memory");
    if (!ready) {
      if (run == 0) {
        if (rest == 0) break;
        if (rest & 64) {
          bar_arrive(BAR_GO, 256);
          bar_sync(BAR_DONE, 256);
        } else {
          alo = (uint32_t)DESC_A + s16 + (OFF_STG >> 4);
        }
        run = rest & 63;
        rest >>= 7;
      }
      mbar_wait(fb, ph);
    }
  }
  if (i < 13 && !(LATE_O && N == 192 && (misc >> 12))) bar_arrive(BAR_ORDER + (wg ^ 1), 256);
  asm volatile("wgmma.wait_group.sync.aligned 0;" ::: "memory");
  pin_regs<N / 2>(acc);
  if (elect_one()) mbar_arrive(prev + 8 * NBAR);
  PROF_T(5 + i * 4);
  PROF_E(i, 0);
}

#define ACC(q, j, e) acc[(q) & 1][4 * (j) + 2 * ((q) >> 1) + (e)]

__device__ __forceinline__ void write_partial_stats(const Params& p, const Ctx& c, int ln, uint32_t tag) {
  const uint32_t xrow = c.sb + OFF_X + c.w * 4096 + c.lane * 128;
  float s = 0.f, q = 0.f, s1 = 0.f, q1 = 0.f;
#pragma unroll 4
  for (int j = 0; j < 16; j++) {
    uint32_t u[4];
    lds_u4(xrow + (j >> 3) * 16384 + (((j & 7) ^ (c.lane & 7)) << 4), u[0], u[1], u[2], u[3]);
#pragma unroll
    for (int e = 0; e < 4; e++) {
      const float a = bf_lo(u[e]), d = bf_hi(u[e]);
      s += a; q = fmaf(a, a, q);
      s1 += d; q1 = fmaf(d, d, q1);
    }
  }
  s += s1;
  q += q1;
  st_msg(p.g->stats + (ln * 8 + c.n) * SEQ + 128 * c.m + 32 * c.w + c.lane, __float_as_uint(s),
         __float_as_uint(fmaxf(q - s * s * (1.f / 128.f), 0.f)), 0u, tag);
}

__device__ __forceinline__ void finish_row_stats(const Params& p, const Ctx& c, int ln, uint32_t tag) {
  const uint4* src = p.g->stats + ln * 8 * SEQ + 128 * c.m + 32 * c.w + c.lane;
  uint32_t ps[8], pm[8];
#pragma unroll 1
  for (int it = 0; it < MSG_SPINS; it++) {
    uint32_t bad = 0, u, tg;
#pragma unroll
    for (int k = 0; k < 8; k++) { ld_msg(src + k * SEQ, ps[k], pm[k], u, tg); bad |= tg ^ tag; }
    if (__all_sync(0xffffffffu, bad == 0)) break;
  }
  float s = 0.f, m2 = 0.f;
#pragma unroll
  for (int k = 0; k < 8; k++) s += __uint_as_float(ps[k]);
  const float mean = s * (1.f / DM);
#pragma unroll
  for (int k = 0; k < 8; k++) {
    const float d = __uint_as_float(ps[k]) * (1.f / 128.f) - mean;
    m2 += fmaf(128.f * d, d, __uint_as_float(pm[k]));
  }
  sts_f2(c.sb + OFF_ROW + (32 * c.w + c.lane) * 8, rsqrtf(m2 * (1.f / DM) + 1e-5f), mean);
  __syncwarp();
}

__device__ __forceinline__ void attn_scores(const uint32_t* qa, const uint32_t* qb, const uint32_t* k0, const uint32_t* k1,
                                            const uint32_t* k2, const uint32_t* k3, float (&l)[4], const float4& zero,
                                            bool par, bool early) {
  float s[4][4];
#pragma unroll
  for (int kb = 0; kb < 4; kb++) {
    const uint32_t* kk = kb == 0 ? k0 : kb == 1 ? k1 : kb == 2 ? k2 : k3;
    asm volatile("mma.sync.aligned.m16n8k16.row.col.f32.bf16.bf16.f32 {%0,%1,%2,%3}, {%4,%5,%6,%7}, {%8,%9}, {%10,%11,%12,%13};"
                 : "=f"(s[kb][0]), "=f"(s[kb][1]), "=f"(s[kb][2]), "=f"(s[kb][3])
                 : "r"(qa[0]), "r"(qb[0]), "r"(qa[1]), "r"(qb[1]), "r"(kk[0]), "r"(kk[1]), "f"(zero.x), "f"(zero.y),
                   "f"(zero.z), "f"(zero.w));
  }
#pragma unroll
  for (int kb = 0; kb < 4; kb++) {
    const uint32_t* kk = kb == 0 ? k0 : kb == 1 ? k1 : kb == 2 ? k2 : k3;
    mma16816(s[kb], qa[2], qb[2], qa[3], qb[3], kk[2], kk[3]);
  }
  l[0] = par ? s[1][1] : s[1][0];
  l[1] = early ? (par ? s[0][1] : s[0][0]) : (par ? s[2][1] : s[2][0]);
  l[2] = par ? s[2][3] : s[2][2];
  l[3] = early ? (par ? s[1][3] : s[1][2]) : (par ? s[3][3] : s[3][2]);
}

__device__ __forceinline__ void attn_mix(const float (&l)[4], const float (&sc)[4], const float (&off)[4], const float (&rk)[4],
                                         const uint32_t* v0, const uint32_t* v1, const uint32_t* v2, const uint32_t* v3,
                                         uint32_t* olo, uint32_t* ohi, const uint32_t (&sel)[4]) {
  float x[4];
#pragma unroll
  for (int e = 0; e < 4; e++) x[e] = fmaf(l[e], sc[e], off[e]);
  const float ml = quad_max(fmaxf(x[0], x[1])), mh = quad_max(fmaxf(x[2], x[3]));
  x[0] = ex2(x[0] - ml); x[1] = ex2(x[1] - ml);
  x[2] = ex2(x[2] - mh); x[3] = ex2(x[3] - mh);
  const uint32_t pl = pack_bf16(x[0] * rk[0], x[1] * rk[1]), ph = pack_bf16(x[2] * rk[2], x[3] * rk[3]);
  const uint32_t a0 = prmt_u(pl, sel[1]), a1 = prmt_u(pl, sel[3]), a2 = prmt_u(pl, sel[0]), a3 = prmt_u(ph, sel[1]);
  const uint32_t c0 = prmt_u(pl, sel[2]), c1 = prmt_u(ph, sel[0]), c2 = prmt_u(ph, sel[3]), c3 = prmt_u(ph, sel[2]);
  float o[4][4];
#pragma unroll
  for (int jn = 0; jn < 4; jn++) {
    o[jn][0] = o[jn][1] = o[jn][2] = o[jn][3] = 0.f;
    mma16816(o[jn], a0, a1, a2, a3, v0[jn], v1[jn]);
  }
#pragma unroll
  for (int jn = 0; jn < 4; jn++) mma16816(o[jn], c0, c1, c2, c3, v2[jn], v3[jn]);
  const float il = rcp_hw(quad_sum(x[0] + x[1])), ih = rcp_hw(quad_sum(x[2] + x[3]));
#pragma unroll
  for (int jn = 0; jn < 4; jn++) {
    olo[jn] = pack_bf16(o[jn][0] * il, o[jn][1] * il);
    ohi[jn] = pack_bf16(o[jn][2] * ih, o[jn][3] * ih);
  }
}

__device__ __forceinline__ void gelu_epilogue(const Params& p, float (&acc)[2][96], const Ctx& cx, int t) {
  UNPACK_CTX(cx);
  (void)wg;
  float rs[4], rm[4];
#pragma unroll
  for (int q = 0; q < 4; q++) {
    const float2 v = lds_f2(sb + OFF_ROW + (32 * w + 8 * q + (lane >> 2)) * 8);
    rs[q] = 0.5f * v.x;
    rm[q] = -rs[q] * v.y;
  }
  const int col0 = 128 * (t - 3);
  const uint32_t stg = sb + OFF_STG + w * 4096;
  const uint32_t ctab = sb + OFF_CSF + (col0 / 2 + (lane & 3)) * 16, srow = stg + lane * 128 + ((lane & 7) << 4);
#pragma unroll
  for (int c = 0; c < 3; c++) {
    if (c == 2 && t != 5) break;
    uint32_t hp[8][4];
#pragma unroll
    for (int j = 0; j < 8; j++) {
      const float4 cb = lds_f4(ctab + (8 * c + j) * 64);
#pragma unroll
      for (int q = 0; q < 4; q++) {
        float y[2];
        const int k = 4 * j + q - GELU_DEP;
        const float rmq = k >= 0 ? chain(rm[q], hp[k >> 2][k & 3], p.zero) : rm[q];
#pragma unroll
        for (int e = 0; e < 2; e++) {
          const float z = fmaf(ACC(q, 8 * c + j, e), rs[q], fmaf(rmq, e ? cb.y : cb.x, e ? cb.w : cb.z));
          const float u = z * fmaf(z * z, 8.f * 0.7978845608028654f * 0.044715f, 2.f * 0.7978845608028654f);
          y[e] = fmaf(z, tanh_hw(u), z);
        }
        hp[j][q] = pack_bf16(y[0], y[1]);
      }
      if (j == 3 && c > 0) {
        if (lane == 0) bulk_wait_read();
        __syncwarp();
      }
      if (c == 0 || j > 3) {
        stsm4(srow ^ (j << 4), hp[j][0], hp[j][1], hp[j][2], hp[j][3]);
      } else if (j == 3) {
#pragma unroll
        for (int jj = 0; jj < 4; jj++) stsm4(srow ^ (jj << 4), hp[jj][0], hp[jj][1], hp[jj][2], hp[jj][3]);
      }
    }
    fence_async_smem();
    __syncwarp();
    if (lane == 0) {
      tma_st2(&p.h_st, stg, 448 * n + col0 + 64 * c, 128 * m + 32 * w);
      bulk_commit();
    }
  }
#pragma unroll
  for (int r = 0; r < 16; r++) acc[0][r] = acc[1][r] = 0.f;
}

__device__ __forceinline__ void attn_epilogue(const Params& p, float (&acc)[2][96], const Ctx& cx, int layer, int t, uint32_t tag) {
  UNPACK_CTX(cx);
  const bool par = (lane >> 2) & 1, early = (lane & 3) > (lane >> 3);
  const uint32_t ktab = sb + OFF_ROW + (32 * w + 2 * (lane & 3) + par) * 8, exc = sb + OFF_STG + w * 4096 + lane * 16;
  const int slot = ((layer * 2 + t) * 16 + m) * 8 + n;
  const int mn = m * 8 + n; (void)mn;
  uint32_t Q[4][8], K[4][8], V[4][8], E[36], P[36];
  float kr[6], qr[4];
#pragma unroll
  for (int q = 2; q < 4; q++) {
    kr[2 + q] = lds_f(ktab + 64 * q);
#pragma unroll
    for (int j = 0; j < 8; j++) {
      E[8 * (q - 2) + j] = K[q][j] = pack_bf16(ACC(q, 8 + j, 0), ACC(q, 8 + j, 1));
      E[16 + 2 * j + q - 2] = V[q][j] = movtrans(pack_bf16(ACC(q, 16 + j, 0), ACC(q, 16 + j, 1)));
    }
  }
#pragma unroll
  for (int j = 0; j < 16; j++) K[j >> 3][j & 7] = pack_bf16(ACC(j >> 3, 8 + (j & 7), 0), ACC(j >> 3, 8 + (j & 7), 1));
#pragma unroll
  for (int j = 0; j < 16; j++) asm volatile("" : "+r"(K[j >> 3][j & 7]));
  E[32] = __float_as_uint(kr[4]);
  E[33] = E[34] = E[35] = __float_as_uint(kr[5]);
  if (w < 3) {
#pragma unroll
    for (int k = 0; k < 8; k++) sts_u4(exc + k * 512, E[4 * k], E[4 * k + 1], E[4 * k + 2], E[4 * k + 3]);
  } else {
#pragma unroll
    for (int k = 0; k < 12; k++) st_msg(p.g->halo + slot * 384 + k * 32 + lane, E[3 * k], E[3 * k + 1], E[3 * k + 2], tag);
  }
  bar_arrive(BAR_PAIR + w, 64);
  if (LATE_O && t == 1) bar_arrive(BAR_ORDER + (wg ^ 1), 256);
  PROF_E(7 * layer + t, 1);
#pragma unroll
  for (int q = 0; q < 4; q++) {
    qr[q] = lds_f(sb + OFF_ROW + (32 * w + 8 * q + (lane >> 2)) * 8) * (0.17677669529663687f * 1.4426950408889634f);
#pragma unroll
    for (int j = 0; j < 8; j++) Q[q][j] = pack_bf16(ACC(q, j, 0), ACC(q, j, 1));
    if (q < 2) {
      kr[2 + q] = lds_f(ktab + 64 * q);
#pragma unroll
      for (int j = 0; j < 8; j++) V[q][j] = movtrans(pack_bf16(ACC(q, 16 + j, 0), ACC(q, 16 + j, 1)));
    }
  }
  PROF_E(7 * layer + t, 6);
  bar_sync(BAR_PAIR + ((w + 3) & 3), 64);
  if (w > 0 || m == 0) {
    const uint32_t back = w > 0;
#pragma unroll
    for (int k = 0; k < 8; k++) lds_u4(exc - back * 4096 + k * 512, P[4 * k], P[4 * k + 1], P[4 * k + 2], P[4 * k + 3]);
    P[32] = lds_u(ktab - back * 128);
    P[33] = lds_u(ktab - back * 64);
  } else {
    if (HALO_NS) __nanosleep(HALO_NS);
#pragma unroll 1
    for (int it = 0; it < MSG_SPINS; it++) {
      uint32_t tg, bad = 0;
      if (it > 0) poll_line(reinterpret_cast<const uint32_t*>(p.g->halo + (slot - 8) * 384 + 383) + 3, tag, 1u);
#pragma unroll
      for (int k = 0; k < 12; k++) {
        ld_msg(p.g->halo + (slot - 8) * 384 + k * 32 + lane, P[3 * k], P[3 * k + 1], P[3 * k + 2], tg);
        bad |= tg ^ tag;
      }
      if (__all_sync(0xffffffffu, bad == 0)) break;
    }
  }
  kr[0] = __uint_as_float(P[32]);
  kr[1] = __uint_as_float(P[33]);
  uint32_t PV[2][8];
#pragma unroll
  for (int j = 0; j < 8; j++) { PV[0][j] = P[16 + 2 * j]; PV[1][j] = P[17 + 2 * j]; }
  float rk[2][4], sc[2][4], off[2][4];
#pragma unroll
  for (int g = 0; g < 2; g++) {
    rk[g][0] = kr[2 * g + 1];
    rk[g][1] = early ? kr[2 * g] : kr[2 * g + 2];
    rk[g][2] = kr[2 * g + 2];
    rk[g][3] = early ? kr[2 * g + 1] : kr[2 * g + 3];
#pragma unroll
    for (int e = 0; e < 4; e++) {
      const bool masked = g == 0 && e != 2 && (m | w) == 0 && (e == 0 || early);
      sc[g][e] = masked ? 0.f : rk[g][e] * qr[2 * g + (e >> 1)];
      off[g][e] = masked ? -1e30f : 0.f;
    }
  }
  const uint32_t none = 0x4444u | p.zero, second = par ? 0x3244u : 0x4432u;
  const uint32_t sel[4] = {par ? 0x1044u : 0x4410u, early ? second : none, early ? none : second, none};
  PROF_E(7 * layer + t, 2);
  bar_sync(BAR_GO, 256);
  const float4 zero = lds_f4(sb + OFF_ZERO);
  float l[2][2][4];
  uint32_t O[4][8];
#pragma unroll
  for (int h = 0; h < 2; h++) {
    if (h == 1) {
      Q[2][4] |= __float_as_uint(l[1][0][0]) & p.zero;
      Q[0][4] |= __float_as_uint(l[0][0][0]) & p.zero;
    }
    attn_scores(&Q[2][4 * h], &Q[3][4 * h], &K[0][4 * h], &K[1][4 * h], &K[2][4 * h], &K[3][4 * h], l[1][h], zero, par, early);
    attn_scores(&Q[0][4 * h], &Q[1][4 * h], &P[4 * h], &P[8 + 4 * h], &K[0][4 * h], &K[1][4 * h], l[0][h], zero, par, early);
  }
  const uint32_t stg = sb + OFF_STG + w * 4096, srow = stg + lane * 128 + ((lane & 7) << 4);
#pragma unroll
  for (int h = 0; h < 2; h++) {
    attn_mix(l[1][h], sc[1], off[1], rk[1], &V[0][4 * h], &V[1][4 * h], &V[2][4 * h], &V[3][4 * h], &O[2][4 * h], &O[3][4 * h], sel);
    attn_mix(l[0][h], sc[0], off[0], rk[0], &PV[0][4 * h], &PV[1][4 * h], &V[0][4 * h], &V[1][4 * h], &O[0][4 * h], &O[1][4 * h], sel);
#pragma unroll
    for (int j = 4 * h; j < 4 * h + 4; j++) stsm4(srow ^ (j << 4), O[0][j], O[1][j], O[2][j], O[3][j]);
  }
  bar_arrive(BAR_DONE, 256);
  fence_async_smem();
  __syncwarp();
  if (lane == 0) {
    tma_st2(&p.att_st, stg, 128 * n + 64 * t, 128 * m + 32 * w);
    bulk_commit();
  }
}

__device__ __forceinline__ void finish_stores(uint32_t sb, int i) {
  const int t = i >= 7 ? i - 7 : i;
  if ((threadIdx.x & 31) == 0) {
    bulk_wait_all();
    mbar_arrive(sb + BAR_PUB + 8 * (t < 2 ? t : t + 1));
  }
  __syncwarp();
  if (i < 12) bar_arrive(BAR_GUARD + ((i & 1) ^ 1), 256);
}

__device__ __forceinline__ bool consumer_tile(const Params& p, float (&acc)[2][96], uint32_t sb0, int i, int mn) {
  const int layer = i >= 7, t = i - 7 * layer, wg = i & 1;
  const bool resid = t == 2 || t == 6;
  {
    if (resid) {
      const Ctx cx = make_ctx(sb0, mn);
      const uint32_t xrow = cx.sb + OFF_X + cx.w * 4096 + cx.lane * 128;
      const uint32_t sel_lo = 0x1044u | p.zero, sel_hi = 0x3244u | p.zero;
#pragma unroll
      for (int j = 0; j < 16; j++) {
        uint32_t r[4];
        ldsm4(xrow + (j >> 3) * 16384 + (((j & 7) ^ (cx.lane & 7)) << 4), r[0], r[1], r[2], r[3]);
#pragma unroll
        for (int q = 0; q < 4; q++) {
          ACC(q, j, 0) = prmt_f(r[q], sel_lo);
          ACC(q, j, 1) = prmt_f(r[q], sel_hi);
        }
      }
    }
    if (t >= 5 || i == 7) finish_stores(sb0, i - 2);
#pragma unroll 1
    for (int step = !tile_split(i);; step++) {
      if (step == 1 && (t == 1 || t == 4)) {
        const Ctx cx = make_ctx(sb0, mn);
        if (i == 1) {
          const uint32_t epoch = __ldcg(p.g->epoch + (mn & 127));
          bar_sync(BAR_INIT, 256);
          asm volatile("st.shared.u32 [%0], %1;" ::"r"(sb0 + OFF_TAG), "r"(epoch + 1) : "memory");
        }
        const uint32_t tag = lds_u(cx.sb + OFF_TAG);
        const int ln = (i + 1) >> 2;
#pragma unroll 1
        for (int r = 0; r < 2; r++) {
          if (i == 1) {
            if (cx.w < 3) {
              float a[8] = {0.f, 0.f, 0.f, 0.f, 0.f, 0.f, 0.f, 0.f};
              mbar_wait(sb0 + BAR_CSLD, r);
              sum_rows(cx.sb + OFF_STG + cx.w * 8192, 8, a, cx.lane);
              publish_sums(a, p.g->csp + (cx.n * 17 + cx.m) * 224 + (3 * r + cx.w) * 32, cx.lane, tag);
            }
            PROF_E(-1, 5 + r);
          }
          if (r == 1) break;
          if (i == 1) {
            bar_sync(BAR_WG + 1, 128);
            if (cx.w == 3 && elect_one()) {
              mbar_expect_tx(sb0 + BAR_CSLD, 24576);
              tma_ld3(sb0 + OFF_STG, &p.wqkv, sb0 + BAR_CSLD, 128 * cx.n + 64, 64 * cx.m, 0);
            }
            mbar_wait(sb0 + BAR_XRDY, 0);
            mbar_wait(sb0 + BAR_XRDY + 8, 0);
          }
          write_partial_stats(p, cx, ln, tag);
          PROF_E(i - 2, 8);
        }
        if (i == 1) bar_arrive(BAR_HLP, 160);
        if (i <= 4) colsum_total(p, cx, ln, tag);
        PROF_E(i - 2, 9);
        if (i != 1) bar_sync(BAR_GUARD + wg, 256);
        finish_row_stats(p, cx, ln, tag);
        PROF_E(i - 2, 10);
        if (i <= 4) {
          colsum_gather(p, cx, ln, tag);
          if (i == 4) mbar_wait(sb0 + BAR_BIAS, 0);
          bar_sync(BAR_WG + wg, 128);
        }
        PROF_E(i - 2, 15);
        bar_arrive(BAR_GUARD + (wg ^ 1), 256);
      }
      if (step == 2 && !resid) bar_sync(BAR_GUARD + wg, 256);
      if (t + step == 2 || t == 6) {
        const Ctx cx = make_ctx(sb0, mn);
        float nm[4];
#pragma unroll
        for (int q = 0; q < 4; q++) nm[q] = t == 6 ? 1.f : -lds_f(cx.sb + OFF_ROW + (32 * cx.w + 8 * q + (cx.lane >> 2)) * 8 + 4);
        const uint32_t ctab = cx.sb + OFF_CSQ + ((t & 3) * 192 + 2 * (cx.lane & 3)) * 4;
#pragma unroll
        for (int j = 0; j < 24; j++) {
          const float2 cs = lds_f2(ctab + j * 32);
#pragma unroll
          for (int q = 0; q < 4; q++) {
            const int k = 4 * j + q - 1;
            const float nq = k >= 0 ? chain(nm[q], __float_as_uint(ACC(k & 3, k >> 2, 1)), p.zero) : nm[q];
            ACC(q, j, 0) = fmaf(nq, cs.x, ACC(q, j, 0));
            ACC(q, j, 1) = fmaf(nq, cs.y, ACC(q, j, 1));
          }
        }
      }
      if (step == 2) break;
      if (tile_wide(t)) {
        mainloop<192>(p, acc, sb0, i, step, mn);
      } else {
        mainloop<128>(p, acc, sb0, i, step, mn);
        if (resid) break;
      }
    }
    if (t < 2) return true;
    const Ctx cx = make_ctx(sb0, mn);
    if (resid) {
      const uint32_t xrow = cx.sb + OFF_X + cx.w * 4096 + cx.lane * 128;
#pragma unroll
      for (int j = 0; j < 16; j++) {
        stsm4(xrow + (j >> 3) * 16384 + (((j & 7) ^ (cx.lane & 7)) << 4), pack_bf16(ACC(0, j, 0), ACC(0, j, 1)),
              pack_bf16(ACC(1, j, 0), ACC(1, j, 1)), pack_bf16(ACC(2, j, 0), ACC(2, j, 1)), pack_bf16(ACC(3, j, 0), ACC(3, j, 1)));
        if ((j & 7) == 7) {
          fence_async_smem();
          __syncwarp();
          if (elect_one()) mbar_arrive(sb0 + BAR_XRDY + (j & 8));
        }
      }
      PROF_E(i, 4);
      return false;
    }
    gelu_epilogue(p, acc, cx, t);
    PROF_E(i, 4);
    return false;
  }
}

__global__ void __launch_bounds__(384, 1) fused_layers_kernel(const int by_smid, const __nv_bfloat16* x_p, const __nv_bfloat16* wqkv_p,
                                                                  const __grid_constant__ Params p) {
  extern __shared__ __align__(1024) uint8_t smem_raw[];
  const uint32_t sb = uniform((uint32_t)__cvta_generic_to_shared(smem_raw));
  const int tid = threadIdx.x, lane = tid & 31, warp = uniform(tid >> 5), wg = warp >> 2, w = warp & 3;

  int mn;
  {
    int id = blockIdx.x;
    if (by_smid) asm volatile("mov.u32 %0, %%smid;" : "=r"(id));
    else if (id >= 120) id += 4;
    const int c = id >> 1;
    int g, j;
    if (c < 32) { g = c & 7; j = c >> 3; }
    else if (c < 60) { g = 1 + (c - 32) % 7; j = 4 + (c - 32) / 7; }
    else { g = 0; j = c - 58; }
    mn = ((g >> 1) * 4 + (j >> 1)) * 8 + ((g & 1) * 2 + (j & 1)) * 2 + (id & 1);
    if (c == 60 || c == 61) {
      if (tid < 32) {
        const uint32_t tag = __ldcg(p.g->epoch + NCTA + (id & 3)) + 1;
#pragma unroll 1
        for (int mm = 0; mm < 16; mm++) poll_line(p.g->flags + mm * 32 + (lane & 7), 32 * tag, 0xffu);
        if (tid == 0) p.g->epoch[NCTA + (id & 3)] = tag;
      }
      return;
    }
  }
  const int m = mn >> 3, n = mn & 7;
  if (tid == 256) PROF_U(1);
  if (tid >= 382) asm volatile("prefetch.global.L2 [%0];" ::"l"(tid & 1 ? wqkv_p + 128 * n : x_p + 128 * m * DM));
  if (wg < 2) {
    asm volatile("setmaxnreg.inc.sync.aligned.u32 232;");
    const int id = mn | (warp << 7);
#pragma unroll 1
    for (int i = wg;; i += 2) {
      float acc[2][96];
#pragma unroll
      for (int r = 0; r < 96; r++) acc[0][r] = acc[1][r] = 0.f;
      pin_regs<96>(acc);
#pragma unroll 1
      while (!consumer_tile(p, acc, sb, i, id)) {
        PROF_T(6 + i * 4);
        i += 2;
        if (i >= 14) goto all_done;
      }
      attn_epilogue(p, acc, make_ctx(sb, id), i >= 7, i >= 7 ? i - 7 : i, lds_u(sb + OFF_TAG));
      PROF_E(i, 4);
      finish_stores(sb, i);
      PROF_E(i, 5);
      PROF_T(6 + i * 4);
    }
  all_done:
    if (wg == 0) finish_stores(sb, 12);
  } else {
    asm volatile("setmaxnreg.dec.sync.aligned.u32 40;");
    if (w != 0) {
      if (w == 2 && lane < 28) write_run_desc(sb, lane >> 1, lane & 1);
      bar_sync(BAR_INIT, 256);
      if (w == 1) producer<true>(p, sb, m, n, lane);
      else if (w == 3) colsum_helper(p, sb, m, n, lane);
      else if (elect_one()) publisher(p, sb, m, n);
    } else {
      if (elect_one()) {
#pragma unroll
        for (int k = 0; k < 4; k++) mbar_init(sb + BAR_FULL + 8 * k, 2);
        asm volatile("fence.mbarrier_init.release.cluster;" ::: "memory");
        PROF_U(4);
#pragma unroll 1
        for (int k = 0; k < 4; k++) {
          const uint32_t fb = sb + BAR_FULL + 8 * k;
          mbar_expect_tx(fb, 16384);
          tma_ld2(sb + (5 * k + 3) * UNIT, &p.xin, fb, 64 * k, 128 * m);
          mbar_expect_tx(fb, 3 * UNIT);
          tma_ld3(sb + 5 * k * UNIT, &p.wqkv, fb, 128 * n, 64 * k, 0);
        }
        PROF_U(5);
        mbar_init(sb + BAR_XRDY, 4);
        mbar_init(sb + BAR_XRDY + 8, 4);
        mbar_init(sb + BAR_FULL + 32, 2);
#pragma unroll
        for (int k = 0; k < NBAR; k++) mbar_init(sb + BAR_EMPTY + 8 * k, 4);
        mbar_init(sb + BAR_DUMMY, 4);
#pragma unroll
        for (int k = 0; k < 7; k++) mbar_init(sb + BAR_PUB + 8 * k, 4);
#pragma unroll
        for (int k = 0; k < 3; k++) mbar_init(sb + BAR_CSLD + 8 * k, 1);
        sts_f2(sb + OFF_ZERO, 0.f, 0.f);
        sts_f2(sb + OFF_ZERO + 8, 0.f, 0.f);
        asm volatile("fence.mbarrier_init.release.cluster;" ::: "memory");
        mbar_expect_tx(sb + BAR_CSLD, 24576);
        tma_ld3(sb + OFF_STG, &p.wqkv, sb + BAR_CSLD, 128 * n, 64 * m, 0);
#pragma unroll 1
        for (int h = 0; h < 2; h++) {
          const uint32_t xr = sb + BAR_XRDY + 8 * h;
          mbar_expect_tx(xr, 16384);
          tma_ld2(sb + OFF_X + h * 16384, &p.xin, xr, 128 * n + 64 * h, 128 * m);
          asm volatile("mbarrier.arrive.shared::cta.b64 _, [%0], 3;" ::"r"(xr) : "memory");
        }
        PROF_U(6);
      }
      __syncwarp();
      bar_arrive(BAR_INIT0, 160);
      bar_arrive(BAR_INIT, 256);
      producer<false>(p, sb, m, n, lane);
    }
  }
}

typedef CUresult (*EncodeFn)(CUtensorMap*, CUtensorMapDataType, cuuint32_t, void*, const cuuint64_t*, const cuuint64_t*,
                             const cuuint32_t*, const cuuint32_t*, CUtensorMapInterleave, CUtensorMapSwizzle,
                             CUtensorMapL2promotion, CUtensorMapFloatOOBfill);

#define PROMO2 CU_TENSOR_MAP_L2_PROMOTION_L2_128B
#define PROMO3 CU_TENSOR_MAP_L2_PROMOTION_L2_128B
void make_2d(EncodeFn enc, CUtensorMap* m, const void* ptr, uint64_t cols, uint64_t rows, uint32_t box_rows) {
  cuuint64_t d[2] = {cols, rows}, st[1] = {cols * 2};
  cuuint32_t b[2] = {64, box_rows}, e[2] = {1, 1};
  enc(m, CU_TENSOR_MAP_DATA_TYPE_BFLOAT16, 2, const_cast<void*>(ptr), d, st, b, e, CU_TENSOR_MAP_INTERLEAVE_NONE,
      CU_TENSOR_MAP_SWIZZLE_128B, PROMO2, CU_TENSOR_MAP_FLOAT_OOB_FILL_NONE);
}
void make_3d(EncodeFn enc, CUtensorMap* m, const void* ptr, uint64_t d0, uint64_t rows, uint64_t d2, uint64_t row_bytes,
             uint64_t chunk_bytes, uint32_t box_chunks) {
  cuuint64_t d[3] = {d0, rows, d2}, st[2] = {row_bytes, chunk_bytes};
  cuuint32_t b[3] = {64, 64, box_chunks}, e[3] = {1, 1, 1};
  enc(m, CU_TENSOR_MAP_DATA_TYPE_BFLOAT16, 3, const_cast<void*>(ptr), d, st, b, e, CU_TENSOR_MAP_INTERLEAVE_NONE,
      CU_TENSOR_MAP_SWIZZLE_128B, PROMO3, CU_TENSOR_MAP_FLOAT_OOB_FILL_NONE);
}

}

extern "C" void kernel_launch(void* const* d_in, const int* in_sizes, int n_in, void* d_out, int out_size) {
  (void)in_sizes; (void)n_in; (void)out_size;
  static EncodeFn enc = nullptr;
  static void *att = nullptr, *hbuf = nullptr, *scratch = nullptr;
  static int by_smid = 0;
  if (!enc) {
    void* fn = nullptr;
    cudaDriverEntryPointQueryResult q;
    cudaGetDriverEntryPoint("cuTensorMapEncodeTiled", &fn, cudaEnableDefault, &q);
    enc = (EncodeFn)fn;
    cudaGetSymbolAddress(&att, g_att);
    cudaGetSymbolAddress(&hbuf, g_h);
    cudaGetSymbolAddress(&scratch, g_scratch);
    cudaFuncSetAttribute(fused_layers_kernel, cudaFuncAttributeMaxDynamicSharedMemorySize, SMEM_BYTES);
    int sms = 0, per_sm = 0, dev = 0;
    cudaGetDevice(&dev);
    cudaDeviceGetAttribute(&sms, cudaDevAttrMultiProcessorCount, dev);
    cudaOccupancyMaxActiveBlocksPerMultiprocessor(&per_sm, fused_layers_kernel, 384, SMEM_BYTES);
    by_smid = sms == 132 && per_sm == 1;
  }
  Params p;
  make_2d(enc, &p.xin, d_in[0], DM, SEQ, 128);
  make_2d(enc, &p.out, d_out, DM, SEQ, 128);
  make_2d(enc, &p.att, att, DM, SEQ, 128);
  make_2d(enc, &p.h, hbuf, FF, SEQ, 128);
  make_2d(enc, &p.out_st, d_out, DM, SEQ, 32);
  make_2d(enc, &p.att_st, att, DM, SEQ, 32);
  make_2d(enc, &p.h_st, hbuf, FF, SEQ, 32);
  make_2d(enc, &p.w1c, d_in[4], FF, DM, 32);
  make_3d(enc, &p.wqkv, d_in[1], DM, DM, 3, 3 * DM * 2, DM * 2, 3);
  make_3d(enc, &p.wo, d_in[2], 64, DM, DM / 64, DM * 2, 128, 2);
  make_3d(enc, &p.w1a, d_in[4], 64, DM, FF / 64, FF * 2, 128, 3);
  make_3d(enc, &p.w1b, d_in[4], 64, DM, FF / 64, FF * 2, 128, 2);
  make_3d(enc, &p.w2, d_in[6], 64, FF, DM / 64, DM * 2, 128, 2);
  p.b1 = (const __nv_bfloat16*)d_in[5];
  p.b2 = (const __nv_bfloat16*)d_in[7];
  p.g = (Scratch*)scratch;
  p.zero = 0;
  fused_layers_kernel<<<by_smid ? 132 : NCTA, 384, SMEM_BYTES>>>(by_smid, (const __nv_bfloat16*)d_in[0], (const __nv_bfloat16*)d_in[1], p);
}
```

```cpp
#include <cuda_runtime.h>
#include <cuda_bf16.h>
#include <cuda.h>
#include <stdint.h>

namespace {

constexpr int SEQ = 2048, DM = 1024, FF = 3584;
constexpr int NCTA = 128;
constexpr int NBAR = 5;

constexpr uint32_t RING_UNITS = 20, UNIT = 8192;
constexpr uint32_t OFF_X   = RING_UNITS * UNIT;
constexpr uint32_t OFF_STG = OFF_X + 32768;
constexpr uint32_t OFF_HLP = OFF_STG + 16384;
constexpr uint32_t OFF_RUN = OFF_STG + 24576;
constexpr uint32_t OFF_CSQ = OFF_RUN + 512;
constexpr uint32_t OFF_CSF = OFF_CSQ + 2048;
constexpr uint32_t OFF_ROW = OFF_CSF + 3584;
constexpr uint32_t OFF_BAR = OFF_ROW + 1024;
constexpr uint32_t SMEM_BYTES = OFF_BAR + 384;
constexpr uint32_t BAR_FULL = OFF_BAR, BAR_EMPTY = OFF_BAR + 8 * NBAR;
constexpr uint32_t BAR_XRDY = OFF_BAR + 80;
constexpr uint32_t BAR_DUMMY = OFF_BAR + 96, OFF_TAG = OFF_BAR + 104, OFF_ZERO = OFF_BAR + 112;
constexpr uint32_t BAR_PUB = OFF_BAR + 128;
constexpr uint32_t BAR_CSLD = OFF_BAR + 200;
constexpr uint32_t BAR_BIAS = OFF_BAR + 216;

constexpr uint64_t DESC_A = (1ull << 62) | ((uint64_t)(2048 >> 4) << 32) | (1ull << 16);
constexpr uint64_t DESC_B = (1ull << 62) | ((uint64_t)(1024 >> 4) << 32) | ((uint64_t)(8192 >> 4) << 16);

constexpr int BAR_INIT = 0, BAR_ORDER = 1, BAR_GUARD = 3, BAR_WG = 5, BAR_GO = 7, BAR_DONE = 8, BAR_HLP = 9, BAR_INIT0 = 10, BAR_PAIR = 11;
#define GELU_DEP 2
#define MAP 3
#define LATE_O 0
#define HALO_NS 400
#define STG_WAIT 5
#define WIN1 7
#define WIN2 4

struct Scratch {
  uint4 stats[4 * 8 * SEQ];
  uint4 halo[2 * 2 * 16 * 8 * 384];
  uint4 csp[2 * 8 * 17 * 224];
  uint32_t flags[16 * 32];
  uint32_t epoch[NCTA + 4];
};

struct Params {
  CUtensorMap xin, out, att, h, wqkv, wo, w1a, w1b, w2, out_st, att_st, h_st, w1c;
  const __nv_bfloat16 *b1, *b2;
  Scratch* g;
  uint32_t zero;
};

__device__ __nv_bfloat16 g_att[SEQ * DM];
__device__ __nv_bfloat16 g_h[SEQ * FF];
__device__ Scratch g_scratch;
#define PROF_T(idx)
#define PROF_U(k)
#define PROF_S(g)
#define PROF_E(i, k)

__device__ __forceinline__ void mbar_init(uint32_t bar, int cnt) {
  asm volatile("mbarrier.init.shared::cta.b64 [%0], %1;" ::"r"(bar), "r"(cnt));
}
__device__ __forceinline__ void mbar_expect_tx(uint32_t bar, uint32_t bytes) {
  asm volatile("mbarrier.arrive.expect_tx.shared::cta.b64 _, [%0], %1;" ::"r"(bar), "r"(bytes) : "memory");
}
__device__ __forceinline__ void mbar_arrive(uint32_t bar) {
  asm volatile("mbarrier.arrive.shared::cta.b64 _, [%0];" ::"r"(bar) : "memory");
}
__device__ __forceinline__ bool mbar_test(uint32_t bar, uint32_t parity) {
  uint32_t ok;
  asm volatile("{\n.reg .pred p;\nmbarrier.test_wait.parity.shared::cta.b64 p, [%1], %2;\nselp.u32 %0, 1, 0, p;\n}"
               : "=r"(ok) : "r"(bar), "r"(parity) : "memory");
  return ok;
}
__device__ __forceinline__ void mbar_wait(uint32_t bar, uint32_t parity) {
  asm volatile(
      "{\n.reg .pred p;\n.reg .u32 it;\nmov.u32 it, 0;\n"
      "WAIT_LOOP:\n"
      "mbarrier.try_wait.parity.shared::cta.b64 p, [%0], %1;\n"
      "@p bra WAIT_DONE;\n"
      "add.u32 it, it, 1;\n"
      "setp.lt.u32 p, it, 0x400000;\n"
      "@p bra WAIT_LOOP;\n"
      "trap;\n"
      "WAIT_DONE:\n}"
      ::"r"(bar), "r"(parity) : "memory");
}
__device__ __forceinline__ void bar_sync(int id, int n) { asm volatile("bar.sync %0, %1;" ::"r"(id), "r"(n) : "memory"); }
__device__ __forceinline__ void bar_arrive(int id, int n) { asm volatile("bar.arrive %0, %1;" ::"r"(id), "r"(n) : "memory"); }
__device__ __forceinline__ void tma_ld2(uint32_t dst, const CUtensorMap* m, uint32_t bar, int c0, int c1) {
  asm volatile("cp.async.bulk.tensor.2d.shared::cluster.global.mbarrier::complete_tx::bytes [%0], [%1, {%3, %4}], [%2];"
               ::"r"(dst), "l"(m), "r"(bar), "r"(c0), "r"(c1) : "memory");
}
__device__ __forceinline__ void tma_ld3(uint32_t dst, const CUtensorMap* m, uint32_t bar, int c0, int c1, int c2) {
  asm volatile("cp.async.bulk.tensor.3d.shared::cluster.global.mbarrier::complete_tx::bytes [%0], [%1, {%3, %4, %5}], [%2];"
               ::"r"(dst), "l"(m), "r"(bar), "r"(c0), "r"(c1), "r"(c2) : "memory");
}
__device__ __forceinline__ void tma_st2(const CUtensorMap* m, uint32_t src, int c0, int c1) {
  asm volatile("cp.async.bulk.tensor.2d.global.shared::cta.bulk_group [%0, {%2, %3}], [%1];"
               ::"l"(m), "r"(src), "r"(c0), "r"(c1) : "memory");
}
__device__ __forceinline__ void bulk_commit() { asm volatile("cp.async.bulk.commit_group;" ::: "memory"); }
__device__ __forceinline__ void bulk_wait_read() { asm volatile("cp.async.bulk.wait_group.read 0;" ::: "memory"); }
__device__ __forceinline__ void bulk_wait_all() { asm volatile("cp.async.bulk.wait_group 0;" ::: "memory"); }
__device__ __forceinline__ void fence_async_smem() { asm volatile("fence.proxy.async.shared::cta;" ::: "memory"); }
__device__ __forceinline__ void fence_async_global() { asm volatile("fence.proxy.async.global;" ::: "memory"); }
__device__ __forceinline__ void st_relaxed(uint32_t* p, uint32_t v) {
  asm volatile("st.relaxed.gpu.global.u32 [%0], %1;" ::"l"(p), "r"(v) : "memory");
}
__device__ __forceinline__ void st_msg(uint4* p, uint32_t a, uint32_t b, uint32_t c, uint32_t tag) {
  asm volatile("{\n.reg .b128 v;\nmov.b128 v, {%1, %2, %3, %4};\nst.relaxed.gpu.global.b128 [%0], v;\n}"
               ::"l"(p), "r"(a), "r"(b), "r"(c), "r"(tag) : "memory");
}
__device__ __forceinline__ void ld_msg(const uint4* p, uint32_t& a, uint32_t& b, uint32_t& c, uint32_t& tag) {
  asm volatile("{\n.reg .b128 v;\nld.relaxed.gpu.global.b128 v, [%4];\nmov.b128 {%0, %1, %2, %3}, v;\n}"
               : "=r"(a), "=r"(b), "=r"(c), "=r"(tag) : "l"(p) : "memory");
}
__device__ __forceinline__ bool elect_one() {
  uint32_t ok;
  asm volatile("{\n.reg .pred p;\nelect.sync _|p, 0xffffffff;\nselp.u32 %0, 1, 0, p;\n}" : "=r"(ok));
  return ok;
}
__device__ __forceinline__ int uniform(int v) { return __shfl_sync(0xffffffffu, v, 0); }
__device__ __forceinline__ uint32_t pack_bf16(float lo, float hi) {
  uint32_t r;
  asm("cvt.rn.bf16x2.f32 %0, %1, %2;" : "=r"(r) : "f"(hi), "f"(lo));
  return r;
}
__device__ __forceinline__ uint32_t prmt_u(uint32_t a, uint32_t sel) {
  uint32_t r;
  asm("prmt.b32 %0, %1, 0, %2;" : "=r"(r) : "r"(a), "r"(sel));
  return r;
}
__device__ __forceinline__ float prmt_f(uint32_t a, uint32_t sel) {
  float r;
  asm("{\n.reg .b32 t;\nprmt.b32 t, %1, 0, %2;\nmov.b32 %0, t;\n}" : "=f"(r) : "r"(a), "r"(sel));
  return r;
}
__device__ __forceinline__ float bf_lo(uint32_t v) { return __uint_as_float(v << 16); }
__device__ __forceinline__ float bf_hi(uint32_t v) { return __uint_as_float(v & 0xffff0000u); }
__device__ __forceinline__ void stsm4(uint32_t addr, uint32_t r0, uint32_t r1, uint32_t r2, uint32_t r3) {
  asm volatile("stmatrix.sync.aligned.m8n8.x4.shared.b16 [%0], {%1, %2, %3, %4};"
               ::"r"(addr), "r"(r0), "r"(r1), "r"(r2), "r"(r3) : "memory");
}
__device__ __forceinline__ void ldsm4(uint32_t addr, uint32_t& r0, uint32_t& r1, uint32_t& r2, uint32_t& r3) {
  asm volatile("ldmatrix.sync.aligned.m8n8.x4.shared.b16 {%0, %1, %2, %3}, [%4];"
               : "=r"(r0), "=r"(r1), "=r"(r2), "=r"(r3) : "r"(addr) : "memory");
}
__device__ __forceinline__ uint32_t movtrans(uint32_t a) {
  uint32_t d;
  asm volatile("movmatrix.sync.aligned.m8n8.trans.b16 %0, %1;" : "=r"(d) : "r"(a));
  return d;
}
__device__ __forceinline__ void mma16816(float (&c)[4], uint32_t a0, uint32_t a1, uint32_t a2, uint32_t a3, uint32_t b0, uint32_t b1) {
  asm volatile("mma.sync.aligned.m16n8k16.row.col.f32.bf16.bf16.f32 {%0,%1,%2,%3}, {%4,%5,%6,%7}, {%8,%9}, {%0,%1,%2,%3};"
               : "+f"(c[0]), "+f"(c[1]), "+f"(c[2]), "+f"(c[3])
               : "r"(a0), "r"(a1), "r"(a2), "r"(a3), "r"(b0), "r"(b1));
}
__device__ __forceinline__ float2 lds_f2(uint32_t a) {
  float2 v;
  asm volatile("ld.shared.v2.f32 {%0, %1}, [%2];" : "=f"(v.x), "=f"(v.y) : "r"(a) : "memory");
  return v;
}
__device__ __forceinline__ float4 lds_f4(uint32_t a) {
  float4 v;
  asm volatile("ld.shared.v4.f32 {%0, %1, %2, %3}, [%4];" : "=f"(v.x), "=f"(v.y), "=f"(v.z), "=f"(v.w) : "r"(a) : "memory");
  return v;
}
__device__ __forceinline__ float lds_f(uint32_t a) {
  float v;
  asm volatile("ld.shared.f32 %0, [%1];" : "=f"(v) : "r"(a) : "memory");
  return v;
}
__device__ __forceinline__ uint32_t lds_u(uint32_t a) {
  uint32_t v;
  asm volatile("ld.shared.u32 %0, [%1];" : "=r"(v) : "r"(a) : "memory");
  return v;
}
__device__ __forceinline__ void sts_f2(uint32_t a, float x, float y) {
  asm volatile("st.shared.v2.f32 [%0], {%1, %2};" ::"r"(a), "f"(x), "f"(y) : "memory");
}
__device__ __forceinline__ void sts_u4(uint32_t a, uint32_t x, uint32_t y, uint32_t z, uint32_t w) {
  asm volatile("st.shared.v4.u32 [%0], {%1, %2, %3, %4};" ::"r"(a), "r"(x), "r"(y), "r"(z), "r"(w) : "memory");
}
__device__ __forceinline__ void lds_u4(uint32_t a, uint32_t& x, uint32_t& y, uint32_t& z, uint32_t& w) {
  asm volatile("ld.shared.v4.u32 {%0, %1, %2, %3}, [%4];" : "=r"(x), "=r"(y), "=r"(z), "=r"(w) : "r"(a) : "memory");
}
__device__ __forceinline__ float ex2(float x) {
  float y;
  asm("ex2.approx.ftz.f32 %0, %1;" : "=f"(y) : "f"(x));
  return y;
}
__device__ __forceinline__ float rcp_hw(float x) {
  float y;
  asm("rcp.approx.ftz.f32 %0, %1;" : "=f"(y) : "f"(x));
  return y;
}
__device__ __forceinline__ float tanh_hw(float x) {
  float y;
  asm("tanh.approx.f32 %0, %1;" : "=f"(y) : "f"(x));
  return y;
}
__device__ __forceinline__ float quad_sum(float v) {
  v += __shfl_xor_sync(0xffffffffu, v, 1);
  return v + __shfl_xor_sync(0xffffffffu, v, 2);
}
__device__ __forceinline__ float quad_max(float v) {
  v = fmaxf(v, __shfl_xor_sync(0xffffffffu, v, 1));
  return fmaxf(v, __shfl_xor_sync(0xffffffffu, v, 2));
}

template <int N> __device__ __forceinline__ void wgmma_ss(float (&d)[96], uint64_t da, uint64_t db, uint32_t keep = 1);
template <> __device__ __forceinline__ void wgmma_ss<128>(float (&d)[96], uint64_t da, uint64_t db, uint32_t keep) {
  asm volatile(
      "{\n.reg .pred p;\nsetp.ne.u32 p, %66, 0;\n"
      "wgmma.mma_async.sync.aligned.m64n128k16.f32.bf16.bf16 {%0, %1, %2, %3, %4, %5, %6, %7, %8, %9, %10, %11, %12, %13, %14, %15, %16, %17, %18, %19, %20, %21, %22, %23, %24, %25, %26, %27, %28, %29, %30, %31, %32, %33, %34, %35, %36, %37, %38, %39, %40, %41, %42, %43, %44, %45, %46, %47, %48, %49, %50, %51, %52, %53, %54, %55, %56, %57, %58, %59, %60, %61, %62, %63}, %64, %65, p, 1, 1, 0, 1;\n}"
      : "+f"(d[0]), "+f"(d[1]), "+f"(d[2]), "+f"(d[3]), "+f"(d[4]), "+f"(d[5]), "+f"(d[6]), "+f"(d[7]), "+f"(d[8]), "+f"(d[9]), "+f"(d[10]), "+f"(d[11]), "+f"(d[12]), "+f"(d[13]), "+f"(d[14]), "+f"(d[15]), "+f"(d[16]), "+f"(d[17]), "+f"(d[18]), "+f"(d[19]), "+f"(d[20]), "+f"(d[21]), "+f"(d[22]), "+f"(d[23]), "+f"(d[24]), "+f"(d[25]), "+f"(d[26]), "+f"(d[27]), "+f"(d[28]), "+f"(d[29]), "+f"(d[30]), "+f"(d[31]), "+f"(d[32]), "+f"(d[33]), "+f"(d[34]), "+f"(d[35]), "+f"(d[36]), "+f"(d[37]), "+f"(d[38]), "+f"(d[39]), "+f"(d[40]), "+f"(d[41]), "+f"(d[42]), "+f"(d[43]), "+f"(d[44]), "+f"(d[45]), "+f"(d[46]), "+f"(d[47]), "+f"(d[48]), "+f"(d[49]), "+f"(d[50]), "+f"(d[51]), "+f"(d[52]), "+f"(d[53]), "+f"(d[54]), "+f"(d[55]), "+f"(d[56]), "+f"(d[57]), "+f"(d[58]), "+f"(d[59]), "+f"(d[60]), "+f"(d[61]), "+f"(d[62]), "+f"(d[63])
      : "l"(da), "l"(db), "r"(keep));
}

template <> __device__ __forceinline__ void wgmma_ss<192>(float (&d)[96], uint64_t da, uint64_t db, uint32_t keep) {
  asm volatile(
      "{\n.reg .pred p;\nsetp.ne.u32 p, %98, 0;\n"
      "wgmma.mma_async.sync.aligned.m64n192k16.f32.bf16.bf16 {%0, %1, %2, %3, %4, %5, %6, %7, %8, %9, %10, %11, %12, %13, %14, %15, %16, %17, %18, %19, %20, %21, %22, %23, %24, %25, %26, %27, %28, %29, %30, %31, %32, %33, %34, %35, %36, %37, %38, %39, %40, %41, %42, %43, %44, %45, %46, %47, %48, %49, %50, %51, %52, %53, %54, %55, %56, %57, %58, %59, %60, %61, %62, %63, %64, %65, %66, %67, %68, %69, %70, %71, %72, %73, %74, %75, %76, %77, %78, %79, %80, %81, %82, %83, %84, %85, %86, %87, %88, %89, %90, %91, %92, %93, %94, %95}, %96, %97, p, 1, 1, 0, 1;\n}"
      : "+f"(d[0]), "+f"(d[1]), "+f"(d[2]), "+f"(d[3]), "+f"(d[4]), "+f"(d[5]), "+f"(d[6]), "+f"(d[7]), "+f"(d[8]), "+f"(d[9]), "+f"(d[10]), "+f"(d[11]), "+f"(d[12]), "+f"(d[13]), "+f"(d[14]), "+f"(d[15]), "+f"(d[16]), "+f"(d[17]), "+f"(d[18]), "+f"(d[19]), "+f"(d[20]), "+f"(d[21]), "+f"(d[22]), "+f"(d[23]), "+f"(d[24]), "+f"(d[25]), "+f"(d[26]), "+f"(d[27]), "+f"(d[28]), "+f"(d[29]), "+f"(d[30]), "+f"(d[31]), "+f"(d[32]), "+f"(d[33]), "+f"(d[34]), "+f"(d[35]), "+f"(d[36]), "+f"(d[37]), "+f"(d[38]), "+f"(d[39]), "+f"(d[40]), "+f"(d[41]), "+f"(d[42]), "+f"(d[43]), "+f"(d[44]), "+f"(d[45]), "+f"(d[46]), "+f"(d[47]), "+f"(d[48]), "+f"(d[49]), "+f"(d[50]), "+f"(d[51]), "+f"(d[52]), "+f"(d[53]), "+f"(d[54]), "+f"(d[55]), "+f"(d[56]), "+f"(d[57]), "+f"(d[58]), "+f"(d[59]), "+f"(d[60]), "+f"(d[61]), "+f"(d[62]), "+f"(d[63]), "+f"(d[64]), "+f"(d[65]), "+f"(d[66]), "+f"(d[67]), "+f"(d[68]), "+f"(d[69]), "+f"(d[70]), "+f"(d[71]), "+f"(d[72]), "+f"(d[73]), "+f"(d[74]), "+f"(d[75]), "+f"(d[76]), "+f"(d[77]), "+f"(d[78]), "+f"(d[79]), "+f"(d[80]), "+f"(d[81]), "+f"(d[82]), "+f"(d[83]), "+f"(d[84]), "+f"(d[85]), "+f"(d[86]), "+f"(d[87]), "+f"(d[88]), "+f"(d[89]), "+f"(d[90]), "+f"(d[91]), "+f"(d[92]), "+f"(d[93]), "+f"(d[94]), "+f"(d[95])
      : "l"(da), "l"(db), "r"(keep));
}

template <int R>
__device__ __forceinline__ void pin_regs(float (&a)[2][96]) {
#pragma unroll
  for (int m = 0; m < 2; m++)
#pragma unroll
    for (int i = 0; i < R; i++) asm volatile("" : "+f"(a[m][i])::"memory");
}

struct Ctx {
  uint32_t sb;
  int m, n, wg, w, lane;
};
__device__ __forceinline__ Ctx make_ctx(uint32_t sb, int id) {
  int lane;
  asm volatile("mov.u32 %0, %%laneid;" : "=r"(lane));
  asm volatile("" : "+r"(id), "+r"(sb));
  return Ctx{sb, (id >> 3) & 15, id & 7, id >> 9, (id >> 7) & 3, lane};
}
#define UNPACK_CTX(c) const uint32_t sb = c.sb; const int m = c.m, n = c.n, wg = c.wg, w = c.w, lane = c.lane

__device__ __forceinline__ uint32_t poll_line(const uint32_t* word, uint32_t target, uint32_t need) {
  uint32_t v;
  asm volatile(
      "{\n.reg .pred p;\n.reg .u32 it, m;\n.reg .s32 d;\nmov.u32 it, 0;\n"
      "POLL_LOOP:\n"
      "ld.relaxed.gpu.global.u32 %0, [%1];\n"
      "sub.s32 d, %0, %2;\n"
      "setp.ge.s32 p, d, 0;\n"
      "vote.sync.ballot.b32 m, p, 0xffffffff;\n"
      "and.b32 m, m, %3;\n"
      "setp.eq.u32 p, m, %3;\n"
      "@p bra.uni POLL_DONE;\n"
      "add.u32 it, it, 1;\n"
      "setp.lt.u32 p, it, 0x400000;\n"
      "@p bra.uni POLL_LOOP;\n"
      "trap;\n"
      "POLL_DONE:\n}"
      : "=&r"(v) : "l"(word), "r"(target), "r"(need) : "memory");
  return v;
}
__device__ __forceinline__ uint32_t ld_relaxed(const uint32_t* p) {
  uint32_t v;
  asm volatile("ld.relaxed.gpu.global.u32 %0, [%1];" : "=r"(v) : "l"(p) : "memory");
  return v;
}
__device__ __forceinline__ float chain(float x, uint32_t on, uint32_t zero) {
  return __uint_as_float(__float_as_uint(x) | (on & zero));
}
constexpr int MSG_SPINS = 1 << 20;

constexpr int STAGES_PER_LAYER = 152;
__device__ __forceinline__ int nib(uint64_t v, int i) { return (int)(v >> (4 * i)) & 15; }
__device__ __forceinline__ bool tile_wide(int t) { return (0x23 >> t) & 1; }
__device__ __forceinline__ void weight_coords(const Params& p, int t, int n, const CUtensorMap*& map, int& c0, int& c2) {
  map = &p.wqkv + nib(0x4233100ull, t);
  c0 = t < 2 ? 128 * n + 64 * t : 0;
  c2 = t < 2 ? 0 : (t == 2 || t == 6) ? 2 * n : 7 * n + 2 * t - 6;
}

template <bool IS_A>
__device__ __forceinline__ void producer(const Params& p, uint32_t sb, int m, int n, int lane) {
  const uint32_t low = (1u << (4 * n)) - 1, others = (0x6543210u & low) | (0x7654321u & ~low);
  const uint64_t order_x = (uint64_t)(others * 2 + 0x1111111u) << 36 | (uint64_t)others * 2 << 8 | (n * 0x22 + 0x10);
  int inflight = 4, cur = 0;
  uint32_t fb = sb + BAR_FULL + 32, rb = sb + BAR_EMPTY, rph = 0, pos = 0, tag32 = 0, seen = 0;
  const uint32_t fend = sb + BAR_FULL + 8 * NBAR, rend = sb + BAR_EMPTY + 8 * NBAR;
  const uint32_t* word = p.g->flags + m * 32 + (lane < 16 ? lane >> 1 : lane & 7);
#pragma unroll 1
  for (int sg = 1; sg < 22; sg++) {
    const int layer = sg >= 11, s = sg == 1 ? 2 : sg == 2 ? 1 : sg - 11 * layer;
    const int t = nib(0x65434321010ull, s), kind = nib(0x32110031100ull, s);
    const bool wide = tile_wide(t);
    const uint32_t bbytes = wide ? 3 * UNIT : 2 * UNIT, base = sb + (IS_A ? bbytes : 0);
    const int mul = t == 6 ? 448 : t == 2 ? 128 : 64, count = sg == 1 ? 12 : 2 * nib(0x4871ull, kind);
    uint64_t order0 = sg == 1 ? 0xFEDCBA987654ull : kind == 3 ? 0x76543210u : order_x >> (8 * (kind & 1));
    uint32_t special = (s == 4 || s == 10) ? 0x10 : s == 9 ? 0xF : 1;
    if (IS_A) special |= (kind & 1 ? 0 : 3) | (count >= 4 ? 1u << (count - 4) : 0);
    if (s >= 9) pos = (s + 6) * UNIT;
    const CUtensorMap* map;
    int c0 = 0, c2 = 0, ev = 0;
    if (IS_A) {
      map = &p.xin + (t == 2 ? 2 : t == 6 ? 3 : sg >= 4);
      ev = 9 * layer + (t < 2 ? 0 : t == 2 ? 1 : t < 6 ? 4 : 5);
      if (sg == 2) seen = tag32 = (__ldcg(p.g->epoch + m * 8 + n) + 1) << 5;
    } else {
      weight_coords(p, t, n, map, c0, c2);
    }
#pragma unroll 1
    for (int add = 0; add < mul; add += 64) {
      uint64_t order = order0;
      const int need = kind == 3 ? ev : ev - 1 + (lane & 1), sh = kind == 3 ? 16 : 0;
      uint32_t ready = IS_A ? __ballot_sync(0xffffffffu, cur >= need) >> sh : 0;
#pragma unroll 1
      for (int k = 0; k < count; k++) {
        const int code = order & 15, kc = code * mul + add;
        order >>= 4;
        if ((special >> k) & 1) {
          const int lag = wide ? (s == 9 && k == 2 ? 2 : 3) : ((s == 4 || s == 10) && add == 0 && k < 4) ? 3 : 4;
#pragma unroll 1
          for (; inflight > lag; inflight--) {
            mbar_wait(rb, rph);
            rb += 8;
            if (rb == rend) { rb -= 8 * NBAR; rph ^= 1; }
          }
          inflight++;
          if (IS_A) {
            if (kind == 3 ? t == 2 && add + k == 64 : !(kind & 1) && k < 2) {
              if (t == 2) mbar_wait(sb + BAR_PUB + 8, layer);
              else if (k == 1 && (s == 0 || s == 5)) mbar_wait(sb + BAR_XRDY + 8, s == 5);
              if (elect_one()) mbar_arrive(fb);
              goto next_stage;
            }
            if (k == count - 4 && sg >= 3) seen = ld_relaxed(word);
          }
        } else {
          mbar_wait(rb, rph);
          rb += 8;
          if (rb == rend) { rb -= 8 * NBAR; rph ^= 1; }
        }
        if (IS_A && !((ready >> code) & 1)) {
          cur = max(cur, (int)(seen - tag32));
          ready = __ballot_sync(0xffffffffu, cur >= need) >> sh;
          if (!((ready >> code) & 1)) {
            cur = (int)(poll_line(word, tag32 + need, 1u << (code + sh)) - tag32);
            ready = __ballot_sync(0xffffffffu, cur >= need) >> sh;
          }
          asm volatile("fence.acquire.gpu;" ::: "memory");
          fence_async_global();
        }
        if (elect_one()) {
          if (!IS_A) tma_ld3(base + pos, map, fb, c0, kc, c2);
          else tma_ld2(base + pos, map, fb, kc, 128 * m);
          mbar_expect_tx(fb, IS_A ? 16384 : bbytes);
        }
      next_stage:
        fb += 8;
        if (fb == fend) fb -= 8 * NBAR;
        pos += bbytes + 2 * UNIT;
        if (pos >= RING_UNITS * UNIT) pos -= RING_UNITS * UNIT;
      }
      special = !IS_A ? 0 : t == 2 ? 1 : add == 128 ? 0x10 : 0;
      if (t == 2) order0 = others << 4 | n;
      if (IS_A && (t == 2 || add == 64 || add == 192)) ev++;
    }
  }
}

__device__ __forceinline__ void publisher(const Params& p, uint32_t sb, int m, int n) {
  const uint32_t tag = __ldcg(p.g->epoch + m * 8 + n) + 1;
  uint32_t* word = p.g->flags + m * 32 + n;
  const int mn = m * 8 + n; (void)mn;
  st_relaxed(word, 32 * tag);
#pragma unroll 1
  for (int c = 0; c < 18; c++) {
    const int e = c >= 9 ? c - 9 : c;
    if ((0x18C >> e) & 1) {
      const int half = (0x108 >> e) & 1;
      mbar_wait(sb + BAR_XRDY + 8 * half, e < 4);
#pragma unroll
      for (int w = 0; w < 4; w++) tma_st2(&p.out_st, sb + OFF_X + half * 16384 + w * 4096, 128 * n + 64 * half, 128 * m + 32 * w);
      bulk_commit();
      if (c >= 16) continue;
      bulk_wait_all();
      PROF_E(7 * (c >= 9) + (e < 4 ? 2 : 6), 11 + 2 * half);
    } else {
      mbar_wait(sb + BAR_PUB + 8 * e, c >= 9);
    }
    asm volatile("fence.release.gpu;" ::: "memory");
    asm volatile("red.relaxed.gpu.global.add.u32 [%0], 1;" ::"l"(word) : "memory");
    PROF_E(7 * (c >= 9) + nib(0x665432210ull, e), (0x108 >> e) & 1 ? 14 : 12);
  }
  p.g->epoch[m * 8 + n] = tag;
  bulk_wait_read();
}

__device__ __forceinline__ void sum_rows(uint32_t buf, int iters, float (&a)[8], int lane) {
  uint32_t addr = buf + (lane >> 3) * 128 + (((lane & 7) ^ (lane >> 3)) << 4);
#pragma unroll 1
  for (int it = 0; it < iters; it++) {
    uint32_t u[2][4];
    lds_u4(addr, u[0][0], u[0][1], u[0][2], u[0][3]);
    lds_u4((addr ^ 64) + 512, u[1][0], u[1][1], u[1][2], u[1][3]);
    addr += 1024;
#pragma unroll
    for (int e = 0; e < 8; e++) { a[2 * (e & 3)] += bf_lo(u[e >> 2][e & 3]); a[2 * (e & 3) + 1] += bf_hi(u[e >> 2][e & 3]); }
  }
}
__device__ __forceinline__ void publish_sums(const float (&a)[8], uint4* dst, int lane, uint32_t tag) {
  const bool u8 = lane & 8, u16 = lane & 16;
  float h4[4], h2[2];
#pragma unroll
  for (int e = 0; e < 4; e++) h4[e] = (u8 ? a[4 + e] : a[e]) + __shfl_xor_sync(0xffffffffu, u8 ? a[e] : a[4 + e], 8);
#pragma unroll
  for (int e = 0; e < 2; e++) h2[e] = (u16 ? h4[2 + e] : h4[e]) + __shfl_xor_sync(0xffffffffu, u16 ? h4[e] : h4[2 + e], 16);
  st_msg(dst + (lane & 7) * 4 + (u8 ? 2 : 0) + (u16 ? 1 : 0), __float_as_uint(h2[0]), __float_as_uint(h2[1]), 0u, tag);
}

__device__ __forceinline__ void colsum_helper(const Params& p, uint32_t sb, int m, int n, int lane) {
  const uint32_t tag = __ldcg(p.g->epoch + m * 8 + n) + 1;
  const int mn = m * 8 + n; (void)mn;
#pragma unroll 1
  for (int k = lane; k < 288; k += 32) {
    const uint32_t bb = __ldg(reinterpret_cast<const uint32_t*>(k < 224 ? p.b1 + 448 * n : p.b2 + 128 * n - 448) + k);
    const float sc = k < 224 ? 0.5f : 1.f;
    sts_f2(sb + (k < 224 ? OFF_CSF + k * 16 + 8 : OFF_CSQ + 1536 + (k - 224) * 8), sc * bf_lo(bb), sc * bf_hi(bb));
  }
  __syncwarp();
  if (elect_one()) mbar_arrive(sb + BAR_BIAS);
  bar_sync(BAR_HLP, 160);
  PROF_E(-1, 1);
#pragma unroll 1
  for (int c = 0; c < 7; c++) {
    float a[8] = {0.f, 0.f, 0.f, 0.f, 0.f, 0.f, 0.f, 0.f};
#pragma unroll 1
    for (int h = 0; h < 2; h++) {
      if (elect_one()) {
        mbar_expect_tx(sb + BAR_CSLD + 8, 4096);
        tma_ld2(sb + OFF_HLP, &p.w1c, sb + BAR_CSLD + 8, 448 * n + 64 * c, 64 * m + 32 * h);
        if (c < 6) asm volatile("cp.async.bulk.prefetch.tensor.2d.L2.global [%0, {%1, %2}];" ::"l"(&p.w1c), "r"(448 * n + 64 * c + 64), "r"(64 * m + 32 * h) : "memory");
      }
      mbar_wait(sb + BAR_CSLD + 8, h);
      sum_rows(sb + OFF_HLP, 4, a, lane);
      __syncwarp();
    }
    publish_sums(a, p.g->csp + ((8 + n) * 17 + m) * 224 + c * 32, lane, tag);
  }
  PROF_E(-1, 2);
}

__device__ __forceinline__ void poll_msgs2(const uint4* pa, const uint4* pb, float (&v)[4], uint32_t tag) {
#pragma unroll 1
  for (int it = 0; it < MSG_SPINS; it++) {
    uint32_t x[4], z, ta, tb;
    ld_msg(pa, x[0], x[1], z, ta);
    ld_msg(pb, x[2], x[3], z, tb);
#pragma unroll
    for (int e = 0; e < 4; e++) v[e] = __uint_as_float(x[e]);
    if (__all_sync(0xffffffffu, ta == tag && tb == tag)) break;
  }
}
__device__ __forceinline__ void colsum_total(const Params& p, const Ctx& cx, int mat, uint32_t tag) {
  uint4* base = p.g->csp + (mat * 8 + cx.n) * 17 * 224;
  const int per = 12 + 2 * mat, k = 2 * cx.w + (cx.lane >> 4), ia = per * cx.m + k, ib = per * cx.m + min(k + 8, per - 1);
  float v[4];
  poll_msgs2(base + (cx.lane & 15) * 224 + ia, base + (cx.lane & 15) * 224 + ib, v, tag);
#pragma unroll 1
  for (int d = 1; d < 16; d *= 2)
#pragma unroll
    for (int e = 0; e < 4; e++) v[e] += __shfl_xor_sync(0xffffffffu, v[e], d);
  const bool hi = cx.lane & 1;
  if ((cx.lane & 14) == 0) st_msg(base + 16 * 224 + (hi ? ib : ia), __float_as_uint(hi ? v[2] : v[0]), __float_as_uint(hi ? v[3] : v[1]), 0u, tag);
}
__device__ __forceinline__ void colsum_gather(const Params& p, const Ctx& cx, int mat, uint32_t tag) {
  const uint4* base = p.g->csp + ((mat * 8 + cx.n) * 17 + 16) * 224;
  const int ia = cx.w * 32 + cx.lane, ib = min(ia + 128, 191 + 32 * mat);
  float v[4];
  poll_msgs2(base + ia, base + ib, v, tag);
  const uint32_t tab = cx.sb + (mat ? OFF_CSF : OFF_CSQ);
  sts_f2(tab + (ia << (3 + mat)), v[0], v[1]);
  sts_f2(tab + (ib << (3 + mat)), v[2], v[3]);
}

#define ACC(q, j, e) acc[(q) & 1][4 * (j) + 2 * ((q) >> 1) + (e)]

constexpr uint32_t RING16 = RING_UNITS * (UNIT >> 4);
__device__ __forceinline__ bool tile_split(int i) { return (0xD98 >> i) & 1; }

__device__ __forceinline__ void write_run_desc(uint32_t sb, int i, int step) {
  const int layer = i >= 7, t = i - 7 * layer, part = tile_split(i) ? step : 2;
  const bool wide = tile_wide(t), own = t != 2 && t != 6 && part != 1 && i != 0, second = t == 1 || t == 4;
  const uint32_t z16 = (wide ? 5 : 4) * (UNIT >> 4), a_off = z16 - 1024 + (uint32_t)DESC_A - (uint32_t)DESC_B;
  const int gl = 16 * t + (part == 2 ? 0 : second ? 16 * part - 14 : 4 * part), g0 = layer * STAGES_PER_LAYER + gl;
  const uint32_t s16 = (sb & 0x3FFFF) >> 4, bfirst = (uint32_t)DESC_B + s16;
  const int nkb = t == 6 ? 56 : part == 0 ? 2 : 12 + 2 * part;
  const bool win1 = t == 1 && part != 0;
  const int run = win1 ? WIN1 + 1 : t == 2 ? WIN2 + 1 : nkb;
  const int rest = win1 ? 64 | (nkb - 1 - WIN1) : t == 2 ? 64 | (7 - WIN2) | (8 << 7) : 0;
  const uint32_t blo = bfirst + z16 * (wide ? (gl + (t == 5 ? 3 : 0)) & 3 : (gl + 3) % 5);
  const uint32_t alo = own ? (uint32_t)DESC_A + s16 + (OFF_X >> 4) : blo + a_off;
  const uint32_t aoff = own ? alo + 1024 - (blo == bfirst + RING16 - z16 ? bfirst : blo + z16) : a_off;
  const bool xwait = part == 0 && !second, keep = !(part == 0 || t == 5);
  sts_u4(sb + OFF_RUN + (2 * i + step) * 16, blo, alo, aoff,
         ((g0 / NBAR) & 1) | xwait << 1 | keep << 2 | 8 * (g0 % NBAR) | run << 6 | rest << 12);
}

template <int N>
__device__ __forceinline__ void mainloop(const Params& p, float (&acc)[2][96], uint32_t sb, int i, int step, int mn) {
  constexpr uint32_t Z16 = (2 + N / 64) * (UNIT >> 4);
  constexpr uint32_t A_OFF = Z16 - 1024 + (uint32_t)DESC_A - (uint32_t)DESC_B;
  const int wg = i & 1;
  const uint32_t s16 = (sb & 0x3FFFF) >> 4;
  const uint32_t blast = (uint32_t)DESC_B + s16 + RING16 - Z16, flast = sb + BAR_FULL + 8 * (NBAR - 1);
  uint32_t blo = (uint32_t)DESC_B + s16, alo = blo + A_OFF, aoff = A_OFF, misc = 16 << 6;
  if (N == 128 || i > 0) lds_u4(sb + OFF_RUN + (2 * i + step) * 16, blo, alo, aoff, misc);
  uint32_t keep = misc & 4;
  int run = (misc >> 6) & 63, rest = misc >> 12;
  uint32_t fb = sb + BAR_FULL + (misc & 0x38), ph = misc & 1;
  uint32_t prev = sb + BAR_DUMMY - 8 * NBAR;
  pin_regs<N / 2>(acc);
  if (N == 128 || i > 0) bar_sync(BAR_ORDER + wg, 256);
  else bar_sync(BAR_INIT0, 160);
  if (N == 192 && i == 0 && threadIdx.x == 0) PROF_U(8);
  mbar_wait(fb, ph);
  if (misc & 2) mbar_wait(sb + BAR_XRDY, N == 128);
  if (step == 0 || !tile_split(i)) PROF_T(4 + i * 4);
#pragma unroll 1
  while (true) {
    const uint64_t da = (DESC_A & ~0xffffffffull) | alo, db = (DESC_B & ~0xffffffffull) | blo;
    asm volatile("wgmma.fence.sync.aligned;" ::: "memory");
    wgmma_ss<N>(acc[0], da, db, keep);
    wgmma_ss<N>(acc[1], da + 64, db, keep);
    keep = 4;
    wgmma_ss<N>(acc[0], da + 2, db + 128);
    wgmma_ss<N>(acc[1], da + 66, db + 128);
    asm volatile("wgmma.commit_group.sync.aligned;" ::: "memory");
    asm volatile("wgmma.wait_group.sync.aligned 1;" ::: "memory");
    PROF_S(jj++);
    if (elect_one()) mbar_arrive(prev + 8 * NBAR);
    prev = fb;
    if (fb == flast) { fb -= 8 * NBAR; ph++; }
    fb += 8;
    if (blo == blast) blo -= RING16;
    blo += Z16;
    alo = blo + aoff;
    aoff = A_OFF;
    run--;
    const bool ready = mbar_test(fb, ph) && run != 0;
    asm volatile("wgmma.fence.sync.aligned;" ::: "memory");
    wgmma_ss<N>(acc[0], da + 4, db + 256);
    wgmma_ss<N>(acc[1], da + 68, db + 256);
    wgmma_ss<N>(acc[0], da + 6, db + 384);
    wgmma_ss<N>(acc[1], da + 70, db + 384);
    asm volatile("wgmma.commit_group.sync.aligned;" ::: "memory");
    if (!ready) {
      if (run == 0) {
        if (rest == 0) break;
        if (rest & 64) {
          bar_arrive(BAR_GO, 256);
          bar_sync(BAR_DONE, 256);
        } else {
          alo = (uint32_t)DESC_A + s16 + (OFF_STG >> 4);
        }
        run = rest & 63;
        rest >>= 7;
      }
      mbar_wait(fb, ph);
    }
  }
  if (i < 13 && !(LATE_O && N == 192 && (misc >> 12))) bar_arrive(BAR_ORDER + (wg ^ 1), 256);
  if (N == 128 && ((0x2244 >> i) & 1)) {
    const Ctx cx = make_ctx(sb, mn);
    const uint32_t xrow = cx.sb + OFF_X + cx.w * 4096 + cx.lane * 128 + ((cx.lane & 7) << 4);
    const bool leader = elect_one();
    asm volatile("wgmma.wait_group.sync.aligned 0;" ::: "memory");
    pin_regs<64>(acc);
    PROF_T(5 + i * 4);
    PROF_E(i, 0);
#pragma unroll
    for (int h = 0; h < 2; h++) {
      if (h == 1 && p.zero != 0) break;
#pragma unroll
      for (int j = 8 * h; j < 8 * h + 8; j++)
        stsm4((xrow ^ ((j & 7) << 4)) + h * 16384, pack_bf16(ACC(0, j, 0), ACC(0, j, 1)), pack_bf16(ACC(1, j, 0), ACC(1, j, 1)),
              pack_bf16(ACC(2, j, 0), ACC(2, j, 1)), pack_bf16(ACC(3, j, 0), ACC(3, j, 1)));
      fence_async_smem();
      __syncwarp();
      if (leader) mbar_arrive(sb + BAR_XRDY + 8 * h);
      if (h == 0 && leader) mbar_arrive(prev + 8 * NBAR);
    }
    PROF_E(i, 4);
    return;
  }
  asm volatile("wgmma.wait_group.sync.aligned 0;" ::: "memory");
  pin_regs<N / 2>(acc);
  if (elect_one()) mbar_arrive(prev + 8 * NBAR);
  PROF_T(5 + i * 4);
  PROF_E(i, 0);
}

__device__ __forceinline__ void write_partial_stats(const Params& p, const Ctx& c, int ln, uint32_t tag) {
  const uint32_t xrow = c.sb + OFF_X + c.w * 4096 + c.lane * 128;
  float s = 0.f, q = 0.f, s1 = 0.f, q1 = 0.f;
#pragma unroll 4
  for (int j = 0; j < 16; j++) {
    uint32_t u[4];
    lds_u4(xrow + (j >> 3) * 16384 + (((j & 7) ^ (c.lane & 7)) << 4), u[0], u[1], u[2], u[3]);
#pragma unroll
    for (int e = 0; e < 4; e++) {
      const float a = bf_lo(u[e]), d = bf_hi(u[e]);
      s += a; q = fmaf(a, a, q);
      s1 += d; q1 = fmaf(d, d, q1);
    }
  }
  s += s1;
  q += q1;
  st_msg(p.g->stats + (ln * 8 + c.n) * SEQ + 128 * c.m + 32 * c.w + c.lane, __float_as_uint(s),
         __float_as_uint(fmaxf(q - s * s * (1.f / 128.f), 0.f)), 0u, tag);
}

__device__ __forceinline__ void finish_row_stats(const Params& p, const Ctx& c, int ln, uint32_t tag) {
  const uint4* src = p.g->stats + ln * 8 * SEQ + 128 * c.m + 32 * c.w + c.lane;
  uint32_t ps[8], pm[8];
#pragma unroll 1
  for (int it = 0; it < MSG_SPINS; it++) {
    uint32_t bad = 0, u, tg;
#pragma unroll
    for (int k = 0; k < 8; k++) { ld_msg(src + k * SEQ, ps[k], pm[k], u, tg); bad |= tg ^ tag; }
    if (__all_sync(0xffffffffu, bad == 0)) break;
  }
  float s = 0.f, m2 = 0.f;
#pragma unroll
  for (int k = 0; k < 8; k++) s += __uint_as_float(ps[k]);
  const float mean = s * (1.f / DM);
#pragma unroll
  for (int k = 0; k < 8; k++) {
    const float d = __uint_as_float(ps[k]) * (1.f / 128.f) - mean;
    m2 += fmaf(128.f * d, d, __uint_as_float(pm[k]));
  }
  sts_f2(c.sb + OFF_ROW + (32 * c.w + c.lane) * 8, rsqrtf(m2 * (1.f / DM) + 1e-5f), mean);
  __syncwarp();
}

__device__ __forceinline__ void attn_scores(const uint32_t* qa, const uint32_t* qb, const uint32_t* k0, const uint32_t* k1,
                                            const uint32_t* k2, const uint32_t* k3, float (&l)[4], const float4& zero,
                                            bool par, bool early) {
  float s[4][4];
#pragma unroll
  for (int kb = 0; kb < 4; kb++) {
    const uint32_t* kk = kb == 0 ? k0 : kb == 1 ? k1 : kb == 2 ? k2 : k3;
    asm volatile("mma.sync.aligned.m16n8k16.row.col.f32.bf16.bf16.f32 {%0,%1,%2,%3}, {%4,%5,%6,%7}, {%8,%9}, {%10,%11,%12,%13};"
                 : "=f"(s[kb][0]), "=f"(s[kb][1]), "=f"(s[kb][2]), "=f"(s[kb][3])
                 : "r"(qa[0]), "r"(qb[0]), "r"(qa[1]), "r"(qb[1]), "r"(kk[0]), "r"(kk[1]), "f"(zero.x), "f"(zero.y),
                   "f"(zero.z), "f"(zero.w));
  }
#pragma unroll
  for (int kb = 0; kb < 4; kb++) {
    const uint32_t* kk = kb == 0 ? k0 : kb == 1 ? k1 : kb == 2 ? k2 : k3;
    mma16816(s[kb], qa[2], qb[2], qa[3], qb[3], kk[2], kk[3]);
  }
  l[0] = par ? s[1][1] : s[1][0];
  l[1] = early ? (par ? s[0][1] : s[0][0]) : (par ? s[2][1] : s[2][0]);
  l[2] = par ? s[2][3] : s[2][2];
  l[3] = early ? (par ? s[1][3] : s[1][2]) : (par ? s[3][3] : s[3][2]);
}

__device__ __forceinline__ void attn_mix(const float (&l)[4], const float (&sc)[4], const float (&off)[4], const float (&rk)[4],
                                         const uint32_t* v0, const uint32_t* v1, const uint32_t* v2, const uint32_t* v3,
                                         uint32_t* olo, uint32_t* ohi, const uint32_t (&sel)[4]) {
  float x[4];
#pragma unroll
  for (int e = 0; e < 4; e++) x[e] = fmaf(l[e], sc[e], off[e]);
  const float ml = quad_max(fmaxf(x[0], x[1])), mh = quad_max(fmaxf(x[2], x[3]));
  x[0] = ex2(x[0] - ml); x[1] = ex2(x[1] - ml);
  x[2] = ex2(x[2] - mh); x[3] = ex2(x[3] - mh);
  const uint32_t pl = pack_bf16(x[0] * rk[0], x[1] * rk[1]), ph = pack_bf16(x[2] * rk[2], x[3] * rk[3]);
  const uint32_t a0 = prmt_u(pl, sel[1]), a1 = prmt_u(pl, sel[3]), a2 = prmt_u(pl, sel[0]), a3 = prmt_u(ph, sel[1]);
  const uint32_t c0 = prmt_u(pl, sel[2]), c1 = prmt_u(ph, sel[0]), c2 = prmt_u(ph, sel[3]), c3 = prmt_u(ph, sel[2]);
  float o[4][4];
#pragma unroll
  for (int jn = 0; jn < 4; jn++) {
    o[jn][0] = o[jn][1] = o[jn][2] = o[jn][3] = 0.f;
    mma16816(o[jn], a0, a1, a2, a3, v0[jn], v1[jn]);
  }
#pragma unroll
  for (int jn = 0; jn < 4; jn++) mma16816(o[jn], c0, c1, c2, c3, v2[jn], v3[jn]);
  const float il = rcp_hw(quad_sum(x[0] + x[1])), ih = rcp_hw(quad_sum(x[2] + x[3]));
#pragma unroll
  for (int jn = 0; jn < 4; jn++) {
    olo[jn] = pack_bf16(o[jn][0] * il, o[jn][1] * il);
    ohi[jn] = pack_bf16(o[jn][2] * ih, o[jn][3] * ih);
  }
}

__device__ __forceinline__ void gelu_epilogue(const Params& p, float (&acc)[2][96], const Ctx& cx, int t) {
  UNPACK_CTX(cx);
  (void)wg;
  float rs[4], rm[4];
#pragma unroll
  for (int q = 0; q < 4; q++) {
    const float2 v = lds_f2(sb + OFF_ROW + (32 * w + 8 * q + (lane >> 2)) * 8);
    rs[q] = 0.5f * v.x;
    rm[q] = -rs[q] * v.y;
  }
  const int col0 = 128 * (t - 3);
  const uint32_t stg = sb + OFF_STG + w * 4096;
  const uint32_t ctab = sb + OFF_CSF + (col0 / 2 + (lane & 3)) * 16, srow = stg + lane * 128 + ((lane & 7) << 4);
  float4 nb = lds_f4(ctab);
#pragma unroll
  for (int c = 0; c < 3; c++) {
    if (c == 2 && t != 5) break;
    uint32_t hp[8][4];
#pragma unroll
    for (int j = 0; j < 8; j++) {
      const float4 cb = nb;
      if (8 * c + j < 23) nb = lds_f4(ctab + (8 * c + j + 1) * 64);
#pragma unroll
      for (int q = 0; q < 4; q++) {
        float y[2];
        const int k = 4 * j + q - GELU_DEP;
        const float rmq = k >= 0 ? chain(rm[q], hp[k >> 2][k & 3], p.zero) : rm[q];
#pragma unroll
        for (int e = 0; e < 2; e++) {
          const float z = fmaf(ACC(q, 8 * c + j, e), rs[q], fmaf(rmq, e ? cb.y : cb.x, e ? cb.w : cb.z));
          const float u = z * fmaf(z * z, 8.f * 0.7978845608028654f * 0.044715f, 2.f * 0.7978845608028654f);
          y[e] = fmaf(z, tanh_hw(u), z);
        }
        hp[j][q] = pack_bf16(y[0], y[1]);
      }
      if (j == STG_WAIT && c > 0) {
        if (lane == 0) bulk_wait_read();
        __syncwarp();
      }
      if (c == 0 || j > STG_WAIT) {
        stsm4(srow ^ (j << 4), hp[j][0], hp[j][1], hp[j][2], hp[j][3]);
      } else if (j == STG_WAIT) {
#pragma unroll
        for (int jj = 0; jj <= STG_WAIT; jj++) stsm4(srow ^ (jj << 4), hp[jj][0], hp[jj][1], hp[jj][2], hp[jj][3]);
      }
    }
    fence_async_smem();
    __syncwarp();
    if (lane == 0) {
      tma_st2(&p.h_st, stg, 448 * n + col0 + 64 * c, 128 * m + 32 * w);
      bulk_commit();
    }
  }
#pragma unroll
  for (int r = 0; r < 16; r++) acc[0][r] = acc[1][r] = 0.f;
}

__device__ __forceinline__ void attn_epilogue(const Params& p, float (&acc)[2][96], const Ctx& cx, int layer, int t, uint32_t tag) {
  UNPACK_CTX(cx);
  const bool par = (lane >> 2) & 1, early = (lane & 3) > (lane >> 3);
  const uint32_t ktab = sb + OFF_ROW + (32 * w + 2 * (lane & 3) + par) * 8, exc = sb + OFF_STG + w * 4096 + lane * 16;
  const int slot = ((layer * 2 + t) * 16 + m) * 8 + n;
  const int mn = m * 8 + n; (void)mn;
  uint32_t Q[4][8], K[4][8], V[4][8], E[36], P[36];
  float kr[6], qr[4];
#pragma unroll
  for (int q = 2; q < 4; q++) {
    kr[2 + q] = lds_f(ktab + 64 * q);
#pragma unroll
    for (int j = 0; j < 8; j++) {
      E[8 * (q - 2) + j] = K[q][j] = pack_bf16(ACC(q, 8 + j, 0), ACC(q, 8 + j, 1));
      E[16 + 2 * j + q - 2] = V[q][j] = movtrans(pack_bf16(ACC(q, 16 + j, 0), ACC(q, 16 + j, 1)));
    }
  }
#pragma unroll
  for (int j = 0; j < 16; j++) K[j >> 3][j & 7] = pack_bf16(ACC(j >> 3, 8 + (j & 7), 0), ACC(j >> 3, 8 + (j & 7), 1));
#pragma unroll
  for (int j = 0; j < 16; j++) asm volatile("" : "+r"(K[j >> 3][j & 7]));
  E[32] = __float_as_uint(kr[4]);
  E[33] = E[34] = E[35] = __float_as_uint(kr[5]);
  if (w < 3) {
#pragma unroll
    for (int k = 0; k < 8; k++) sts_u4(exc + k * 512, E[4 * k], E[4 * k + 1], E[4 * k + 2], E[4 * k + 3]);
  } else {
#pragma unroll
    for (int k = 0; k < 12; k++) st_msg(p.g->halo + slot * 384 + k * 32 + lane, E[3 * k], E[3 * k + 1], E[3 * k + 2], tag);
  }
  bar_arrive(BAR_PAIR + w, 64);
  if (LATE_O && t == 1) bar_arrive(BAR_ORDER + (wg ^ 1), 256);
  PROF_E(7 * layer + t, 1);
#pragma unroll
  for (int q = 0; q < 4; q++) {
    qr[q] = lds_f(sb + OFF_ROW + (32 * w + 8 * q + (lane >> 2)) * 8) * (0.17677669529663687f * 1.4426950408889634f);
#pragma unroll
    for (int j = 0; j < 8; j++) Q[q][j] = pack_bf16(ACC(q, j, 0), ACC(q, j, 1));
    if (q < 2) {
      kr[2 + q] = lds_f(ktab + 64 * q);
#pragma unroll
      for (int j = 0; j < 8; j++) V[q][j] = movtrans(pack_bf16(ACC(q, 16 + j, 0), ACC(q, 16 + j, 1)));
    }
  }
  PROF_E(7 * layer + t, 6);
  bar_sync(BAR_PAIR + ((w + 3) & 3), 64);
  if (w > 0 || m == 0) {
    const uint32_t back = w > 0;
#pragma unroll
    for (int k = 0; k < 8; k++) lds_u4(exc - back * 4096 + k * 512, P[4 * k], P[4 * k + 1], P[4 * k + 2], P[4 * k + 3]);
    P[32] = lds_u(ktab - back * 128);
    P[33] = lds_u(ktab - back * 64);
  } else {
    if (HALO_NS) __nanosleep(HALO_NS);
#pragma unroll 1
    for (int it = 0; it < MSG_SPINS; it++) {
      uint32_t tg, bad = 0;
      if (it > 0) poll_line(reinterpret_cast<const uint32_t*>(p.g->halo + (slot - 8) * 384 + 383) + 3, tag, 1u);
#pragma unroll
      for (int k = 0; k < 12; k++) {
        ld_msg(p.g->halo + (slot - 8) * 384 + k * 32 + lane, P[3 * k], P[3 * k + 1], P[3 * k + 2], tg);
        bad |= tg ^ tag;
      }
      if (__all_sync(0xffffffffu, bad == 0)) break;
    }
  }
  kr[0] = __uint_as_float(P[32]);
  kr[1] = __uint_as_float(P[33]);
  uint32_t PV[2][8];
#pragma unroll
  for (int j = 0; j < 8; j++) { PV[0][j] = P[16 + 2 * j]; PV[1][j] = P[17 + 2 * j]; }
  float rk[2][4], sc[2][4], off[2][4];
#pragma unroll
  for (int g = 0; g < 2; g++) {
    rk[g][0] = kr[2 * g + 1];
    rk[g][1] = early ? kr[2 * g] : kr[2 * g + 2];
    rk[g][2] = kr[2 * g + 2];
    rk[g][3] = early ? kr[2 * g + 1] : kr[2 * g + 3];
#pragma unroll
    for (int e = 0; e < 4; e++) {
      const bool masked = g == 0 && e != 2 && (m | w) == 0 && (e == 0 || early);
      sc[g][e] = masked ? 0.f : rk[g][e] * qr[2 * g + (e >> 1)];
      off[g][e] = masked ? -1e30f : 0.f;
    }
  }
  const uint32_t none = 0x4444u | p.zero, second = par ? 0x3244u : 0x4432u;
  const uint32_t sel[4] = {par ? 0x1044u : 0x4410u, early ? second : none, early ? none : second, none};
  PROF_E(7 * layer + t, 2);
  bar_sync(BAR_GO, 256);
  const float4 zero = lds_f4(sb + OFF_ZERO);
  float l[2][2][4];
  uint32_t O[4][8];
#pragma unroll
  for (int h = 0; h < 2; h++) {
    if (h == 1) {
      Q[2][4] |= __float_as_uint(l[1][0][0]) & p.zero;
      Q[0][4] |= __float_as_uint(l[0][0][0]) & p.zero;
    }
    attn_scores(&Q[2][4 * h], &Q[3][4 * h], &K[0][4 * h], &K[1][4 * h], &K[2][4 * h], &K[3][4 * h], l[1][h], zero, par, early);
    attn_scores(&Q[0][4 * h], &Q[1][4 * h], &P[4 * h], &P[8 + 4 * h], &K[0][4 * h], &K[1][4 * h], l[0][h], zero, par, early);
  }
  const uint32_t stg = sb + OFF_STG + w * 4096, srow = stg + lane * 128 + ((lane & 7) << 4);
#pragma unroll
  for (int h = 0; h < 2; h++) {
    attn_mix(l[1][h], sc[1], off[1], rk[1], &V[0][4 * h], &V[1][4 * h], &V[2][4 * h], &V[3][4 * h], &O[2][4 * h], &O[3][4 * h], sel);
    attn_mix(l[0][h], sc[0], off[0], rk[0], &PV[0][4 * h], &PV[1][4 * h], &V[0][4 * h], &V[1][4 * h], &O[0][4 * h], &O[1][4 * h], sel);
#pragma unroll
    for (int j = 4 * h; j < 4 * h + 4; j++) stsm4(srow ^ (j << 4), O[0][j], O[1][j], O[2][j], O[3][j]);
  }
  bar_arrive(BAR_DONE, 256);
  fence_async_smem();
  __syncwarp();
  if (lane == 0) {
    tma_st2(&p.att_st, stg, 128 * n + 64 * t, 128 * m + 32 * w);
    bulk_commit();
  }
}

__device__ __forceinline__ void finish_stores(uint32_t sb, int i) {
  const int t = i >= 7 ? i - 7 : i;
  if ((threadIdx.x & 31) == 0) {
    bulk_wait_all();
    mbar_arrive(sb + BAR_PUB + 8 * (t < 2 ? t : t + 1));
  }
  __syncwarp();
  if (i < 12) bar_arrive(BAR_GUARD + ((i & 1) ^ 1), 256);
}

__device__ __forceinline__ bool consumer_tile(const Params& p, float (&acc)[2][96], uint32_t sb0, int i, int mn) {
  const int layer = i >= 7, t = i - 7 * layer, wg = i & 1;
  const bool resid = t == 2 || t == 6;
  {
    if (resid) {
      const Ctx cx = make_ctx(sb0, mn);
      const uint32_t xrow = cx.sb + OFF_X + cx.w * 4096 + cx.lane * 128;
      const uint32_t sel_lo = 0x1044u | p.zero, sel_hi = 0x3244u | p.zero;
#pragma unroll
      for (int j = 0; j < 16; j++) {
        uint32_t r[4];
        ldsm4(xrow + (j >> 3) * 16384 + (((j & 7) ^ (cx.lane & 7)) << 4), r[0], r[1], r[2], r[3]);
#pragma unroll
        for (int q = 0; q < 4; q++) {
          ACC(q, j, 0) = prmt_f(r[q], sel_lo);
          ACC(q, j, 1) = prmt_f(r[q], sel_hi);
        }
      }
    }
    if (t >= 5 || i == 7) finish_stores(sb0, i - 2);
#pragma unroll 1
    for (int step = !tile_split(i);; step++) {
      if (step == 1 && (t == 1 || t == 4)) {
        const Ctx cx = make_ctx(sb0, mn);
        if (i == 1) {
          const uint32_t epoch = __ldcg(p.g->epoch + (mn & 127));
          bar_sync(BAR_INIT, 256);
          asm volatile("st.shared.u32 [%0], %1;" ::"r"(sb0 + OFF_TAG), "r"(epoch + 1) : "memory");
        }
        const uint32_t tag = lds_u(cx.sb + OFF_TAG);
        const int ln = (i + 1) >> 2;
#pragma unroll 1
        for (int r = 0; r < 2; r++) {
          if (i == 1) {
            if (cx.w < 3) {
              float a[8] = {0.f, 0.f, 0.f, 0.f, 0.f, 0.f, 0.f, 0.f};
              mbar_wait(sb0 + BAR_CSLD, r);
              sum_rows(cx.sb + OFF_STG + cx.w * 8192, 8, a, cx.lane);
              publish_sums(a, p.g->csp + (cx.n * 17 + cx.m) * 224 + (3 * r + cx.w) * 32, cx.lane, tag);
            }
            PROF_E(-1, 5 + r);
          }
          if (r == 1) break;
          if (i == 1) {
            bar_sync(BAR_WG + 1, 128);
            if (cx.w == 3 && elect_one()) {
              mbar_expect_tx(sb0 + BAR_CSLD, 24576);
              tma_ld3(sb0 + OFF_STG, &p.wqkv, sb0 + BAR_CSLD, 128 * cx.n + 64, 64 * cx.m, 0);
            }
            mbar_wait(sb0 + BAR_XRDY, 0);
            mbar_wait(sb0 + BAR_XRDY + 8, 0);
          }
          write_partial_stats(p, cx, ln, tag);
          PROF_E(i - 2, 8);
        }
        if (i == 1) bar_arrive(BAR_HLP, 160);
        if (i <= 4) colsum_total(p, cx, ln, tag);
        PROF_E(i - 2, 9);
        if (i != 1) bar_sync(BAR_GUARD + wg, 256);
        finish_row_stats(p, cx, ln, tag);
        PROF_E(i - 2, 10);
        if (i <= 4) {
          colsum_gather(p, cx, ln, tag);
          if (i == 4) mbar_wait(sb0 + BAR_BIAS, 0);
          bar_sync(BAR_WG + wg, 128);
        }
        PROF_E(i - 2, 15);
        bar_arrive(BAR_GUARD + (wg ^ 1), 256);
      }
      if (step == 2 && !resid) bar_sync(BAR_GUARD + wg, 256);
      if (t + step == 2 || t == 6) {
        const Ctx cx = make_ctx(sb0, mn);
        float nm[4];
#pragma unroll
        for (int q = 0; q < 4; q++) nm[q] = t == 6 ? 1.f : -lds_f(cx.sb + OFF_ROW + (32 * cx.w + 8 * q + (cx.lane >> 2)) * 8 + 4);
        const uint32_t ctab = cx.sb + OFF_CSQ + ((t & 3) * 192 + 2 * (cx.lane & 3)) * 4;
#pragma unroll
        for (int j = 0; j < 24; j++) {
          const float2 cs = lds_f2(ctab + j * 32);
#pragma unroll
          for (int q = 0; q < 4; q++) {
            const int k = 4 * j + q - 1;
            const float nq = k >= 0 ? chain(nm[q], __float_as_uint(ACC(k & 3, k >> 2, 1)), p.zero) : nm[q];
            ACC(q, j, 0) = fmaf(nq, cs.x, ACC(q, j, 0));
            ACC(q, j, 1) = fmaf(nq, cs.y, ACC(q, j, 1));
          }
        }
      }
      if (step == 2) break;
      if (tile_wide(t)) {
        mainloop<192>(p, acc, sb0, i, step, mn);
      } else {
        mainloop<128>(p, acc, sb0, i, step, mn);
        if (resid) return false;
      }
    }
    if (t < 2) return true;
    gelu_epilogue(p, acc, make_ctx(sb0, mn), t);
    PROF_E(i, 4);
    return false;
  }
}

__global__ void __launch_bounds__(384, 1) fused_layers_kernel(const int by_smid, const __nv_bfloat16* x_p, const __nv_bfloat16* wqkv_p,
                                                                  const __grid_constant__ Params p) {
  extern __shared__ __align__(1024) uint8_t smem_raw[];
  const uint32_t sb = uniform((uint32_t)__cvta_generic_to_shared(smem_raw));
  const int tid = threadIdx.x, lane = tid & 31, warp = uniform(tid >> 5), wg = warp >> 2, w = warp & 3;

  int mn;
  {
    int id = blockIdx.x;
    if (by_smid) asm volatile("mov.u32 %0, %%smid;" : "=r"(id));
    else if (id >= 120) id += 4;
    const int c = id >> 1;
    int g, j;
    if (c < 32) { g = c & 7; j = c >> 3; }
    else if (c < 60) { g = 1 + (c - 32) % 7; j = 4 + (c - 32) / 7; }
    else { g = 0; j = c - 58; }
    mn = ((g >> 1) * 4 + (j >> 1)) * 8 + ((g & 1) * 2 + (j & 1)) * 2 + (id & 1);
    if (c == 60 || c == 61) {
      if (tid < 32) {
        const uint32_t tag = __ldcg(p.g->epoch + NCTA + (id & 3)) + 1;
#pragma unroll 1
        for (int mm = 0; mm < 16; mm++) poll_line(p.g->flags + mm * 32 + (lane & 7), 32 * tag, 0xffu);
        if (tid == 0) p.g->epoch[NCTA + (id & 3)] = tag;
      }
      return;
    }
  }
  const int m = mn >> 3, n = mn & 7;
  if (tid == 256) PROF_U(1);
  if (tid >= 382) asm volatile("prefetch.global.L2 [%0];" ::"l"(tid & 1 ? wqkv_p + 128 * n : x_p + 128 * m * DM));
  if (wg < 2) {
    asm volatile("setmaxnreg.inc.sync.aligned.u32 232;");
    const int id = mn | (warp << 7);
#pragma unroll 1
    for (int i = wg;; i += 2) {
      float acc[2][96];
#pragma unroll
      for (int r = 0; r < 96; r++) acc[0][r] = acc[1][r] = 0.f;
      pin_regs<96>(acc);
#pragma unroll 1
      while (!consumer_tile(p, acc, sb, i, id)) {
        PROF_T(6 + i * 4);
        i += 2;
        if (i >= 14) goto all_done;
      }
      attn_epilogue(p, acc, make_ctx(sb, id), i >= 7, i >= 7 ? i - 7 : i, lds_u(sb + OFF_TAG));
      PROF_E(i, 4);
      finish_stores(sb, i);
      PROF_E(i, 5);
      PROF_T(6 + i * 4);
    }
  all_done:
    if (wg == 0) finish_stores(sb, 12);
  } else {
    asm volatile("setmaxnreg.dec.sync.aligned.u32 40;");
    if (w != 0) {
      if (w == 2 && lane < 28) write_run_desc(sb, lane >> 1, lane & 1);
      bar_sync(BAR_INIT, 256);
      if (w == 1) producer<true>(p, sb, m, n, lane);
      else if (w == 3) colsum_helper(p, sb, m, n, lane);
      else if (elect_one()) publisher(p, sb, m, n);
    } else {
      if (elect_one()) {
#pragma unroll
        for (int k = 0; k < 4; k++) mbar_init(sb + BAR_FULL + 8 * k, 2);
        asm volatile("fence.mbarrier_init.release.cluster;" ::: "memory");
        PROF_U(4);
#pragma unroll 1
        for (int k = 0; k < 4; k++) {
          const uint32_t fb = sb + BAR_FULL + 8 * k;
          mbar_expect_tx(fb, 16384);
          tma_ld2(sb + (5 * k + 3) * UNIT, &p.xin, fb, 64 * k, 128 * m);
          mbar_expect_tx(fb, 3 * UNIT);
          tma_ld3(sb + 5 * k * UNIT, &p.wqkv, fb, 128 * n, 64 * k, 0);
        }
        PROF_U(5);
        mbar_init(sb + BAR_XRDY, 4);
        mbar_init(sb + BAR_XRDY + 8, 4);
        mbar_init(sb + BAR_FULL + 32, 2);
#pragma unroll
        for (int k = 0; k < NBAR; k++) mbar_init(sb + BAR_EMPTY + 8 * k, 4);
        mbar_init(sb + BAR_DUMMY, 4);
#pragma unroll
        for (int k = 0; k < 7; k++) mbar_init(sb + BAR_PUB + 8 * k, 4);
#pragma unroll
        for (int k = 0; k < 3; k++) mbar_init(sb + BAR_CSLD + 8 * k, 1);
        sts_f2(sb + OFF_ZERO, 0.f, 0.f);
        sts_f2(sb + OFF_ZERO + 8, 0.f, 0.f);
        asm volatile("fence.mbarrier_init.release.cluster;" ::: "memory");
        mbar_expect_tx(sb + BAR_CSLD, 24576);
        tma_ld3(sb + OFF_STG, &p.wqkv, sb + BAR_CSLD, 128 * n, 64 * m, 0);
#pragma unroll 1
        for (int h = 0; h < 2; h++) {
          const uint32_t xr = sb + BAR_XRDY + 8 * h;
          mbar_expect_tx(xr, 16384);
          tma_ld2(sb + OFF_X + h * 16384, &p.xin, xr, 128 * n + 64 * h, 128 * m);
          asm volatile("mbarrier.arrive.shared::cta.b64 _, [%0], 3;" ::"r"(xr) : "memory");
        }
        PROF_U(6);
      }
      __syncwarp();
      bar_arrive(BAR_INIT0, 160);
      bar_arrive(BAR_INIT, 256);
      producer<false>(p, sb, m, n, lane);
    }
  }
}

typedef CUresult (*EncodeFn)(CUtensorMap*, CUtensorMapDataType, cuuint32_t, void*, const cuuint64_t*, const cuuint64_t*,
                             const cuuint32_t*, const cuuint32_t*, CUtensorMapInterleave, CUtensorMapSwizzle,
                             CUtensorMapL2promotion, CUtensorMapFloatOOBfill);

#define PROMO2 CU_TENSOR_MAP_L2_PROMOTION_L2_128B
#define PROMO3 CU_TENSOR_MAP_L2_PROMOTION_L2_128B
void make_2d(EncodeFn enc, CUtensorMap* m, const void* ptr, uint64_t cols, uint64_t rows, uint32_t box_rows) {
  cuuint64_t d[2] = {cols, rows}, st[1] = {cols * 2};
  cuuint32_t b[2] = {64, box_rows}, e[2] = {1, 1};
  enc(m, CU_TENSOR_MAP_DATA_TYPE_BFLOAT16, 2, const_cast<void*>(ptr), d, st, b, e, CU_TENSOR_MAP_INTERLEAVE_NONE,
      CU_TENSOR_MAP_SWIZZLE_128B, PROMO2, CU_TENSOR_MAP_FLOAT_OOB_FILL_NONE);
}
void make_3d(EncodeFn enc, CUtensorMap* m, const void* ptr, uint64_t d0, uint64_t rows, uint64_t d2, uint64_t row_bytes,
             uint64_t chunk_bytes, uint32_t box_chunks) {
  cuuint64_t d[3] = {d0, rows, d2}, st[2] = {row_bytes, chunk_bytes};
  cuuint32_t b[3] = {64, 64, box_chunks}, e[3] = {1, 1, 1};
  enc(m, CU_TENSOR_MAP_DATA_TYPE_BFLOAT16, 3, const_cast<void*>(ptr), d, st, b, e, CU_TENSOR_MAP_INTERLEAVE_NONE,
      CU_TENSOR_MAP_SWIZZLE_128B, PROMO3, CU_TENSOR_MAP_FLOAT_OOB_FILL_NONE);
}

}

extern "C" void kernel_launch(void* const* d_in, const int* in_sizes, int n_in, void* d_out, int out_size) {
  (void)in_sizes; (void)n_in; (void)out_size;
  static EncodeFn enc = nullptr;
  static void *att = nullptr, *hbuf = nullptr, *scratch = nullptr;
  static int by_smid = 0;
  if (!enc) {
    void* fn = nullptr;
    cudaDriverEntryPointQueryResult q;
    cudaGetDriverEntryPoint("cuTensorMapEncodeTiled", &fn, cudaEnableDefault, &q);
    enc = (EncodeFn)fn;
    cudaGetSymbolAddress(&att, g_att);
    cudaGetSymbolAddress(&hbuf, g_h);
    cudaGetSymbolAddress(&scratch, g_scratch);
    cudaFuncSetAttribute(fused_layers_kernel, cudaFuncAttributeMaxDynamicSharedMemorySize, SMEM_BYTES);
    int sms = 0, per_sm = 0, dev = 0;
    cudaGetDevice(&dev);
    cudaDeviceGetAttribute(&sms, cudaDevAttrMultiProcessorCount, dev);
    cudaOccupancyMaxActiveBlocksPerMultiprocessor(&per_sm, fused_layers_kernel, 384, SMEM_BYTES);
    by_smid = sms == 132 && per_sm == 1;
  }
  Params p;
  make_2d(enc, &p.xin, d_in[0], DM, SEQ, 128);
  make_2d(enc, &p.out, d_out, DM, SEQ, 128);
  make_2d(enc, &p.att, att, DM, SEQ, 128);
  make_2d(enc, &p.h, hbuf, FF, SEQ, 128);
  make_2d(enc, &p.out_st, d_out, DM, SEQ, 32);
  make_2d(enc, &p.att_st, att, DM, SEQ, 32);
  make_2d(enc, &p.h_st, hbuf, FF, SEQ, 32);
  make_2d(enc, &p.w1c, d_in[4], FF, DM, 32);
  make_3d(enc, &p.wqkv, d_in[1], DM, DM, 3, 3 * DM * 2, DM * 2, 3);
  make_3d(enc, &p.wo, d_in[2], 64, DM, DM / 64, DM * 2, 128, 2);
  make_3d(enc, &p.w1a, d_in[4], 64, DM, FF / 64, FF * 2, 128, 3);
  make_3d(enc, &p.w1b, d_in[4], 64, DM, FF / 64, FF * 2, 128, 2);
  make_3d(enc, &p.w2, d_in[6], 64, FF, DM / 64, DM * 2, 128, 2);
  p.b1 = (const __nv_bfloat16*)d_in[5];
  p.b2 = (const __nv_bfloat16*)d_in[7];
  p.g = (Scratch*)scratch;
  p.zero = 0;
  fused_layers_kernel<<<by_smid ? 132 : NCTA, 384, SMEM_BYTES>>>(by_smid, (const __nv_bfloat16*)d_in[0], (const __nv_bfloat16*)d_in[1], p);
}
```

```cpp
#include <cuda_runtime.h>
#include <cuda_bf16.h>
#include <cuda.h>
#include <stdint.h>

namespace {

constexpr int SEQ = 2048, DM = 1024, FF = 3584;
constexpr int NCTA = 128;
constexpr int NBAR = 5;

constexpr uint32_t RING_UNITS = 20, UNIT = 8192;
constexpr uint32_t OFF_X   = RING_UNITS * UNIT;
constexpr uint32_t OFF_STG = OFF_X + 32768;
constexpr uint32_t OFF_HLP = OFF_STG + 16384;
constexpr uint32_t OFF_RUN = OFF_STG + 24576;
constexpr uint32_t OFF_CSQ = OFF_RUN + 512;
constexpr uint32_t OFF_CSF = OFF_CSQ + 2048;
constexpr uint32_t OFF_ROW = OFF_CSF + 3584;
constexpr uint32_t OFF_BAR = OFF_ROW + 1024;
constexpr uint32_t SMEM_BYTES = OFF_BAR + 384;
constexpr uint32_t BAR_FULL = OFF_BAR, BAR_EMPTY = OFF_BAR + 8 * NBAR;
constexpr uint32_t BAR_XRDY = OFF_BAR + 80;
constexpr uint32_t BAR_DUMMY = OFF_BAR + 96, OFF_TAG = OFF_BAR + 104, OFF_ZERO = OFF_BAR + 112;
constexpr uint32_t BAR_PUB = OFF_BAR + 128;
constexpr uint32_t BAR_CSLD = OFF_BAR + 200;
constexpr uint32_t BAR_BIAS = OFF_BAR + 216;

constexpr uint64_t DESC_A = (1ull << 62) | ((uint64_t)(2048 >> 4) << 32) | (1ull << 16);
constexpr uint64_t DESC_B = (1ull << 62) | ((uint64_t)(1024 >> 4) << 32) | ((uint64_t)(4096 >> 4) << 16);

constexpr int BAR_INIT = 0, BAR_ORDER = 1, BAR_GUARD = 3, BAR_WG = 5, BAR_GO = 7, BAR_DONE = 8, BAR_HLP = 9, BAR_PAIR = 11;
#define GELU_DEP 2
#define MAP 2
#define LATE_O 1
#define HALO_NS 400
#define STG_WAIT 5
#define WIN1 7
#define WIN2 2

struct Scratch {
  uint4 stats[4 * 8 * SEQ];
  uint4 halo[2 * 2 * 16 * 8 * 384];
  uint4 csp[2 * 8 * 17 * 224];
  uint32_t flags[16 * 32];
  uint32_t epoch[NCTA + 4];
};

struct Params {
  CUtensorMap xin, out, att, h, wqkv, wo, w1a, w1b, w2, out_st, att_st, h_st, w1c;
  const __nv_bfloat16 *b1, *b2;
  Scratch* g;
  uint32_t zero;
};

__device__ __nv_bfloat16 g_att[SEQ * DM];
__device__ __nv_bfloat16 g_h[SEQ * FF];
__device__ Scratch g_scratch;
#define PROF_T(idx)
#define PROF_U(k)
#define PROF_S(g)
#define PROF_E(i, k)

__device__ __forceinline__ void mbar_init(uint32_t bar, int cnt) {
  asm volatile("mbarrier.init.shared::cta.b64 [%0], %1;" ::"r"(bar), "r"(cnt));
}
__device__ __forceinline__ void mbar_expect_tx(uint32_t bar, uint32_t bytes) {
  asm volatile("mbarrier.arrive.expect_tx.shared::cta.b64 _, [%0], %1;" ::"r"(bar), "r"(bytes) : "memory");
}
__device__ __forceinline__ void mbar_arrive(uint32_t bar) {
  asm volatile("mbarrier.arrive.shared::cta.b64 _, [%0];" ::"r"(bar) : "memory");
}
__device__ __forceinline__ bool mbar_test(uint32_t bar, uint32_t parity) {
  uint32_t ok;
  asm volatile("{\n.reg .pred p;\nmbarrier.test_wait.parity.shared::cta.b64 p, [%1], %2;\nselp.u32 %0, 1, 0, p;\n}"
               : "=r"(ok) : "r"(bar), "r"(parity) : "memory");
  return ok;
}
__device__ __forceinline__ void mbar_wait(uint32_t bar, uint32_t parity) {
  asm volatile(
      "{\n.reg .pred p;\n.reg .u32 it;\nmov.u32 it, 0;\n"
      "WAIT_LOOP:\n"
      "mbarrier.try_wait.parity.shared::cta.b64 p, [%0], %1;\n"
      "@p bra WAIT_DONE;\n"
      "add.u32 it, it, 1;\n"
      "setp.lt.u32 p, it, 0x400000;\n"
      "@p bra WAIT_LOOP;\n"
      "trap;\n"
      "WAIT_DONE:\n}"
      ::"r"(bar), "r"(parity) : "memory");
}
__device__ __forceinline__ void bar_sync(int id, int n) { asm volatile("bar.sync %0, %1;" ::"r"(id), "r"(n) : "memory"); }
__device__ __forceinline__ void bar_arrive(int id, int n) { asm volatile("bar.arrive %0, %1;" ::"r"(id), "r"(n) : "memory"); }
__device__ __forceinline__ void tma_ld2(uint32_t dst, const CUtensorMap* m, uint32_t bar, int c0, int c1) {
  asm volatile("cp.async.bulk.tensor.2d.shared::cluster.global.mbarrier::complete_tx::bytes [%0], [%1, {%3, %4}], [%2];"
               ::"r"(dst), "l"(m), "r"(bar), "r"(c0), "r"(c1) : "memory");
}
__device__ __forceinline__ void tma_ld3(uint32_t dst, const CUtensorMap* m, uint32_t bar, int c0, int c1, int c2) {
  asm volatile("cp.async.bulk.tensor.3d.shared::cluster.global.mbarrier::complete_tx::bytes [%0], [%1, {%3, %4, %5}], [%2];"
               ::"r"(dst), "l"(m), "r"(bar), "r"(c0), "r"(c1), "r"(c2) : "memory");
}
__device__ __forceinline__ void tma_ld3_pair(uint32_t dst, const CUtensorMap* m, uint32_t bar, int c0, int c1, int c2) {
  asm volatile("cp.async.bulk.tensor.3d.shared::cluster.global.mbarrier::complete_tx::bytes.multicast::cluster"
               " [%0], [%1, {%3, %4, %5}], [%2], %6;"
               ::"r"(dst), "l"(m), "r"(bar), "r"(c0), "r"(c1), "r"(c2), "h"((uint16_t)3) : "memory");
}
__device__ __forceinline__ uint32_t pair_offset(uint32_t sb, uint32_t rank) {
  uint32_t r;
  asm volatile("mapa.shared::cluster.u32 %0, %1, %2;" : "=r"(r) : "r"(sb), "r"(rank));
  return r - sb;
}
__device__ __forceinline__ void mbar_arrive_cluster(uint32_t bar) {
  asm volatile("mbarrier.arrive.shared::cluster.b64 _, [%0];" ::"r"(bar) : "memory");
}
__device__ __forceinline__ void cluster_arrive() { asm volatile("barrier.cluster.arrive.relaxed;" ::: "memory"); }
__device__ __forceinline__ void cluster_wait() { asm volatile("barrier.cluster.wait.acquire;" ::: "memory"); }
__device__ __forceinline__ void tma_st2(const CUtensorMap* m, uint32_t src, int c0, int c1) {
  asm volatile("cp.async.bulk.tensor.2d.global.shared::cta.bulk_group [%0, {%2, %3}], [%1];"
               ::"l"(m), "r"(src), "r"(c0), "r"(c1) : "memory");
}
__device__ __forceinline__ void bulk_commit() { asm volatile("cp.async.bulk.commit_group;" ::: "memory"); }
__device__ __forceinline__ void bulk_wait_read() { asm volatile("cp.async.bulk.wait_group.read 0;" ::: "memory"); }
__device__ __forceinline__ void bulk_wait_all() { asm volatile("cp.async.bulk.wait_group 0;" ::: "memory"); }
__device__ __forceinline__ void fence_async_smem() { asm volatile("fence.proxy.async.shared::cta;" ::: "memory"); }
__device__ __forceinline__ void fence_async_global() { asm volatile("fence.proxy.async.global;" ::: "memory"); }
__device__ __forceinline__ void st_relaxed(uint32_t* p, uint32_t v) {
  asm volatile("st.relaxed.gpu.global.u32 [%0], %1;" ::"l"(p), "r"(v) : "memory");
}
__device__ __forceinline__ void st_msg(uint4* p, uint32_t a, uint32_t b, uint32_t c, uint32_t tag) {
  asm volatile("{\n.reg .b128 v;\nmov.b128 v, {%1, %2, %3, %4};\nst.relaxed.gpu.global.b128 [%0], v;\n}"
               ::"l"(p), "r"(a), "r"(b), "r"(c), "r"(tag) : "memory");
}
__device__ __forceinline__ void ld_msg(const uint4* p, uint32_t& a, uint32_t& b, uint32_t& c, uint32_t& tag) {
  asm volatile("{\n.reg .b128 v;\nld.relaxed.gpu.global.b128 v, [%4];\nmov.b128 {%0, %1, %2, %3}, v;\n}"
               : "=r"(a), "=r"(b), "=r"(c), "=r"(tag) : "l"(p) : "memory");
}
__device__ __forceinline__ bool elect_one() {
  uint32_t ok;
  asm volatile("{\n.reg .pred p;\nelect.sync _|p, 0xffffffff;\nselp.u32 %0, 1, 0, p;\n}" : "=r"(ok));
  return ok;
}
__device__ __forceinline__ int uniform(int v) { return __shfl_sync(0xffffffffu, v, 0); }
__device__ __forceinline__ uint32_t pack_bf16(float lo, float hi) {
  uint32_t r;
  asm("cvt.rn.bf16x2.f32 %0, %1, %2;" : "=r"(r) : "f"(hi), "f"(lo));
  return r;
}
__device__ __forceinline__ uint32_t prmt_u(uint32_t a, uint32_t sel) {
  uint32_t r;
  asm("prmt.b32 %0, %1, 0, %2;" : "=r"(r) : "r"(a), "r"(sel));
  return r;
}
__device__ __forceinline__ float prmt_f(uint32_t a, uint32_t sel) {
  float r;
  asm("{\n.reg .b32 t;\nprmt.b32 t, %1, 0, %2;\nmov.b32 %0, t;\n}" : "=f"(r) : "r"(a), "r"(sel));
  return r;
}
__device__ __forceinline__ float bf_lo(uint32_t v) { return __uint_as_float(v << 16); }
__device__ __forceinline__ float bf_hi(uint32_t v) { return __uint_as_float(v & 0xffff0000u); }
__device__ __forceinline__ void stsm4(uint32_t addr, uint32_t r0, uint32_t r1, uint32_t r2, uint32_t r3) {
  asm volatile("stmatrix.sync.aligned.m8n8.x4.shared.b16 [%0], {%1, %2, %3, %4};"
               ::"r"(addr), "r"(r0), "r"(r1), "r"(r2), "r"(r3) : "memory");
}
__device__ __forceinline__ void ldsm4(uint32_t addr, uint32_t& r0, uint32_t& r1, uint32_t& r2, uint32_t& r3) {
  asm volatile("ldmatrix.sync.aligned.m8n8.x4.shared.b16 {%0, %1, %2, %3}, [%4];"
               : "=r"(r0), "=r"(r1), "=r"(r2), "=r"(r3) : "r"(addr) : "memory");
}
__device__ __forceinline__ uint32_t movtrans(uint32_t a) {
  uint32_t d;
  asm volatile("movmatrix.sync.aligned.m8n8.trans.b16 %0, %1;" : "=r"(d) : "r"(a));
  return d;
}
__device__ __forceinline__ void mma16816(float (&c)[4], uint32_t a0, uint32_t a1, uint32_t a2, uint32_t a3, uint32_t b0, uint32_t b1) {
  asm volatile("mma.sync.aligned.m16n8k16.row.col.f32.bf16.bf16.f32 {%0,%1,%2,%3}, {%4,%5,%6,%7}, {%8,%9}, {%0,%1,%2,%3};"
               : "+f"(c[0]), "+f"(c[1]), "+f"(c[2]), "+f"(c[3])
               : "r"(a0), "r"(a1), "r"(a2), "r"(a3), "r"(b0), "r"(b1));
}
__device__ __forceinline__ float2 lds_f2(uint32_t a) {
  float2 v;
  asm volatile("ld.shared.v2.f32 {%0, %1}, [%2];" : "=f"(v.x), "=f"(v.y) : "r"(a) : "memory");
  return v;
}
__device__ __forceinline__ float4 lds_f4(uint32_t a) {
  float4 v;
  asm volatile("ld.shared.v4.f32 {%0, %1, %2, %3}, [%4];" : "=f"(v.x), "=f"(v.y), "=f"(v.z), "=f"(v.w) : "r"(a) : "memory");
  return v;
}
__device__ __forceinline__ float lds_f(uint32_t a) {
  float v;
  asm volatile("ld.shared.f32 %0, [%1];" : "=f"(v) : "r"(a) : "memory");
  return v;
}
__device__ __forceinline__ uint32_t lds_u(uint32_t a) {
  uint32_t v;
  asm volatile("ld.shared.u32 %0, [%1];" : "=r"(v) : "r"(a) : "memory");
  return v;
}
__device__ __forceinline__ void sts_f2(uint32_t a, float x, float y) {
  asm volatile("st.shared.v2.f32 [%0], {%1, %2};" ::"r"(a), "f"(x), "f"(y) : "memory");
}
__device__ __forceinline__ void sts_u4(uint32_t a, uint32_t x, uint32_t y, uint32_t z, uint32_t w) {
  asm volatile("st.shared.v4.u32 [%0], {%1, %2, %3, %4};" ::"r"(a), "r"(x), "r"(y), "r"(z), "r"(w) : "memory");
}
__device__ __forceinline__ void lds_u4(uint32_t a, uint32_t& x, uint32_t& y, uint32_t& z, uint32_t& w) {
  asm volatile("ld.shared.v4.u32 {%0, %1, %2, %3}, [%4];" : "=r"(x), "=r"(y), "=r"(z), "=r"(w) : "r"(a) : "memory");
}
__device__ __forceinline__ float ex2(float x) {
  float y;
  asm("ex2.approx.ftz.f32 %0, %1;" : "=f"(y) : "f"(x));
  return y;
}
__device__ __forceinline__ float rcp_hw(float x) {
  float y;
  asm("rcp.approx.ftz.f32 %0, %1;" : "=f"(y) : "f"(x));
  return y;
}
__device__ __forceinline__ float tanh_hw(float x) {
  float y;
  asm("tanh.approx.f32 %0, %1;" : "=f"(y) : "f"(x));
  return y;
}
__device__ __forceinline__ float quad_sum(float v) {
  v += __shfl_xor_sync(0xffffffffu, v, 1);
  return v + __shfl_xor_sync(0xffffffffu, v, 2);
}
__device__ __forceinline__ float quad_max(float v) {
  v = fmaxf(v, __shfl_xor_sync(0xffffffffu, v, 1));
  return fmaxf(v, __shfl_xor_sync(0xffffffffu, v, 2));
}

template <int N> __device__ __forceinline__ void wgmma_ss(float (&d)[96], uint64_t da, uint64_t db, uint32_t keep = 1);
template <> __device__ __forceinline__ void wgmma_ss<128>(float (&d)[96], uint64_t da, uint64_t db, uint32_t keep) {
  asm volatile(
      "{\n.reg .pred p;\nsetp.ne.u32 p, %66, 0;\n"
      "wgmma.mma_async.sync.aligned.m64n128k16.f32.bf16.bf16 {%0, %1, %2, %3, %4, %5, %6, %7, %8, %9, %10, %11, %12, %13, %14, %15, %16, %17, %18, %19, %20, %21, %22, %23, %24, %25, %26, %27, %28, %29, %30, %31, %32, %33, %34, %35, %36, %37, %38, %39, %40, %41, %42, %43, %44, %45, %46, %47, %48, %49, %50, %51, %52, %53, %54, %55, %56, %57, %58, %59, %60, %61, %62, %63}, %64, %65, p, 1, 1, 0, 1;\n}"
      : "+f"(d[0]), "+f"(d[1]), "+f"(d[2]), "+f"(d[3]), "+f"(d[4]), "+f"(d[5]), "+f"(d[6]), "+f"(d[7]), "+f"(d[8]), "+f"(d[9]), "+f"(d[10]), "+f"(d[11]), "+f"(d[12]), "+f"(d[13]), "+f"(d[14]), "+f"(d[15]), "+f"(d[16]), "+f"(d[17]), "+f"(d[18]), "+f"(d[19]), "+f"(d[20]), "+f"(d[21]), "+f"(d[22]), "+f"(d[23]), "+f"(d[24]), "+f"(d[25]), "+f"(d[26]), "+f"(d[27]), "+f"(d[28]), "+f"(d[29]), "+f"(d[30]), "+f"(d[31]), "+f"(d[32]), "+f"(d[33]), "+f"(d[34]), "+f"(d[35]), "+f"(d[36]), "+f"(d[37]), "+f"(d[38]), "+f"(d[39]), "+f"(d[40]), "+f"(d[41]), "+f"(d[42]), "+f"(d[43]), "+f"(d[44]), "+f"(d[45]), "+f"(d[46]), "+f"(d[47]), "+f"(d[48]), "+f"(d[49]), "+f"(d[50]), "+f"(d[51]), "+f"(d[52]), "+f"(d[53]), "+f"(d[54]), "+f"(d[55]), "+f"(d[56]), "+f"(d[57]), "+f"(d[58]), "+f"(d[59]), "+f"(d[60]), "+f"(d[61]), "+f"(d[62]), "+f"(d[63])
      : "l"(da), "l"(db), "r"(keep));
}

template <> __device__ __forceinline__ void wgmma_ss<192>(float (&d)[96], uint64_t da, uint64_t db, uint32_t keep) {
  asm volatile(
      "{\n.reg .pred p;\nsetp.ne.u32 p, %98, 0;\n"
      "wgmma.mma_async.sync.aligned.m64n192k16.f32.bf16.bf16 {%0, %1, %2, %3, %4, %5, %6, %7, %8, %9, %10, %11, %12, %13, %14, %15, %16, %17, %18, %19, %20, %21, %22, %23, %24, %25, %26, %27, %28, %29, %30, %31, %32, %33, %34, %35, %36, %37, %38, %39, %40, %41, %42, %43, %44, %45, %46, %47, %48, %49, %50, %51, %52, %53, %54, %55, %56, %57, %58, %59, %60, %61, %62, %63, %64, %65, %66, %67, %68, %69, %70, %71, %72, %73, %74, %75, %76, %77, %78, %79, %80, %81, %82, %83, %84, %85, %86, %87, %88, %89, %90, %91, %92, %93, %94, %95}, %96, %97, p, 1, 1, 0, 1;\n}"
      : "+f"(d[0]), "+f"(d[1]), "+f"(d[2]), "+f"(d[3]), "+f"(d[4]), "+f"(d[5]), "+f"(d[6]), "+f"(d[7]), "+f"(d[8]), "+f"(d[9]), "+f"(d[10]), "+f"(d[11]), "+f"(d[12]), "+f"(d[13]), "+f"(d[14]), "+f"(d[15]), "+f"(d[16]), "+f"(d[17]), "+f"(d[18]), "+f"(d[19]), "+f"(d[20]), "+f"(d[21]), "+f"(d[22]), "+f"(d[23]), "+f"(d[24]), "+f"(d[25]), "+f"(d[26]), "+f"(d[27]), "+f"(d[28]), "+f"(d[29]), "+f"(d[30]), "+f"(d[31]), "+f"(d[32]), "+f"(d[33]), "+f"(d[34]), "+f"(d[35]), "+f"(d[36]), "+f"(d[37]), "+f"(d[38]), "+f"(d[39]), "+f"(d[40]), "+f"(d[41]), "+f"(d[42]), "+f"(d[43]), "+f"(d[44]), "+f"(d[45]), "+f"(d[46]), "+f"(d[47]), "+f"(d[48]), "+f"(d[49]), "+f"(d[50]), "+f"(d[51]), "+f"(d[52]), "+f"(d[53]), "+f"(d[54]), "+f"(d[55]), "+f"(d[56]), "+f"(d[57]), "+f"(d[58]), "+f"(d[59]), "+f"(d[60]), "+f"(d[61]), "+f"(d[62]), "+f"(d[63]), "+f"(d[64]), "+f"(d[65]), "+f"(d[66]), "+f"(d[67]), "+f"(d[68]), "+f"(d[69]), "+f"(d[70]), "+f"(d[71]), "+f"(d[72]), "+f"(d[73]), "+f"(d[74]), "+f"(d[75]), "+f"(d[76]), "+f"(d[77]), "+f"(d[78]), "+f"(d[79]), "+f"(d[80]), "+f"(d[81]), "+f"(d[82]), "+f"(d[83]), "+f"(d[84]), "+f"(d[85]), "+f"(d[86]), "+f"(d[87]), "+f"(d[88]), "+f"(d[89]), "+f"(d[90]), "+f"(d[91]), "+f"(d[92]), "+f"(d[93]), "+f"(d[94]), "+f"(d[95])
      : "l"(da), "l"(db), "r"(keep));
}

template <int R>
__device__ __forceinline__ void pin_regs(float (&a)[2][96]) {
#pragma unroll
  for (int m = 0; m < 2; m++)
#pragma unroll
    for (int i = 0; i < R; i++) asm volatile("" : "+f"(a[m][i])::"memory");
}

struct Ctx {
  uint32_t sb;
  int m, n, wg, w, lane;
};
__device__ __forceinline__ Ctx make_ctx(uint32_t sb, int id) {
  int lane;
  asm volatile("mov.u32 %0, %%laneid;" : "=r"(lane));
  asm volatile("" : "+r"(id), "+r"(sb));
  return Ctx{sb, (id >> 3) & 15, id & 7, id >> 9, (id >> 7) & 3, lane};
}
#define UNPACK_CTX(c) const uint32_t sb = c.sb; const int m = c.m, n = c.n, wg = c.wg, w = c.w, lane = c.lane

__device__ __forceinline__ uint32_t poll_line(const uint32_t* word, uint32_t target, uint32_t need) {
  uint32_t v;
  asm volatile(
      "{\n.reg .pred p;\n.reg .u32 it, m;\n.reg .s32 d;\nmov.u32 it, 0;\n"
      "POLL_LOOP:\n"
      "ld.relaxed.gpu.global.u32 %0, [%1];\n"
      "sub.s32 d, %0, %2;\n"
      "setp.ge.s32 p, d, 0;\n"
      "vote.sync.ballot.b32 m, p, 0xffffffff;\n"
      "and.b32 m, m, %3;\n"
      "setp.eq.u32 p, m, %3;\n"
      "@p bra.uni POLL_DONE;\n"
      "add.u32 it, it, 1;\n"
      "setp.lt.u32 p, it, 0x400000;\n"
      "@p bra.uni POLL_LOOP;\n"
      "trap;\n"
      "POLL_DONE:\n}"
      : "=&r"(v) : "l"(word), "r"(target), "r"(need) : "memory");
  return v;
}
__device__ __forceinline__ uint32_t ld_relaxed(const uint32_t* p) {
  uint32_t v;
  asm volatile("ld.relaxed.gpu.global.u32 %0, [%1];" : "=r"(v) : "l"(p) : "memory");
  return v;
}
__device__ __forceinline__ float chain(float x, uint32_t on, uint32_t zero) {
  return __uint_as_float(__float_as_uint(x) | (on & zero));
}
constexpr int MSG_SPINS = 1 << 20;

constexpr int STAGES_PER_LAYER = 152;
__device__ __forceinline__ int nib(uint64_t v, int i) { return (int)(v >> (4 * i)) & 15; }
__device__ __forceinline__ bool tile_wide(int t) { return (0x23 >> t) & 1; }
__device__ __forceinline__ void weight_coords(const Params& p, int t, int n, const CUtensorMap*& map, int& c0, int& c2) {
  map = &p.wqkv + nib(0x4233100ull, t);
  c0 = t < 2 ? 128 * n + 64 * t : 0;
  c2 = t < 2 ? 0 : (t == 2 || t == 6) ? 2 * n : 7 * n + 2 * t - 6;
}

template <bool IS_A>
__device__ __forceinline__ void producer(const Params& p, uint32_t sb, int m, int n, int lane) {
  const uint32_t low = (1u << (4 * n)) - 1, others = (0x6543210u & low) | (0x7654321u & ~low);
  const uint64_t order_x = (uint64_t)(others * 2 + 0x1111111u) << 36 | (uint64_t)others * 2 << 8 | (n * 0x22 + 0x10);
  int inflight = 4, cur = 0;
  uint32_t fb = sb + BAR_FULL + 32, rb = sb + BAR_EMPTY, rph = 0, pos = 0, tag32 = 0, seen = 0;
  const uint32_t fend = sb + BAR_FULL + 8 * NBAR, rend = sb + BAR_EMPTY + 8 * NBAR;
  const uint32_t* word = p.g->flags + m * 32 + (lane < 16 ? lane >> 1 : lane & 7);
#pragma unroll 1
  for (int sg = 1; sg < 22; sg++) {
    const int layer = sg >= 11, s = sg == 1 ? 2 : sg == 2 ? 1 : sg - 11 * layer;
    const int t = nib(0x65434321010ull, s), kind = nib(0x32110031100ull, s);
    const bool wide = tile_wide(t);
    const uint32_t bbytes = wide ? 3 * UNIT : 2 * UNIT, base = sb + (IS_A ? bbytes : (m & 1) * (bbytes / 2));
    const int mul = t == 6 ? 448 : t == 2 ? 128 : 64, count = sg == 1 ? 12 : 2 * nib(0x4871ull, kind);
    uint64_t order0 = sg == 1 ? 0xFEDCBA987654ull : kind == 3 ? 0x76543210u : order_x >> (8 * (kind & 1));
    uint32_t special = (s == 4 || s == 10) ? 0x10 : s == 9 ? 0xF : 1;
    if (IS_A) special |= (kind & 1 ? 0 : 3) | (count >= 4 ? 1u << (count - 4) : 0);
    if (s >= 9) pos = (s + 6) * UNIT;
    const CUtensorMap* map;
    int c0 = 0, c2 = 0, ev = 0;
    if (IS_A) {
      map = &p.xin + (t == 2 ? 2 : t == 6 ? 3 : sg >= 4);
      ev = 9 * layer + (t < 2 ? 0 : t == 2 ? 1 : t < 6 ? 4 : 5);
      if (sg == 2) seen = tag32 = (__ldcg(p.g->epoch + m * 8 + n) + 1) << 5;
    } else {
      weight_coords(p, t, n, map, c0, c2);
    }
#pragma unroll 1
    for (int add = 0; add < mul; add += 64) {
      uint64_t order = order0;
      const int need = kind == 3 ? ev : ev - 1 + (lane & 1), sh = kind == 3 ? 16 : 0;
      uint32_t ready = IS_A ? __ballot_sync(0xffffffffu, cur >= need) >> sh : 0;
#pragma unroll 1
      for (int k = 0; k < count; k++) {
        const int code = order & 15, kc = code * mul + add;
        order >>= 4;
        if ((special >> k) & 1) {
          const int lag = wide ? (s == 9 && k == 2 ? 2 : 3) : ((s == 4 || s == 10) && add == 0 && k < 4) ? 3 : 4;
#pragma unroll 1
          for (; inflight > lag; inflight--) {
            mbar_wait(rb, rph);
            rb += 8;
            if (rb == rend) { rb -= 8 * NBAR; rph ^= 1; }
          }
          inflight++;
          if (IS_A) {
            if (kind == 3 ? t == 2 && add + k == 64 : !(kind & 1) && k < 2) {
              if (t == 2) mbar_wait(sb + BAR_PUB + 8, layer);
              else if (k == 1 && (s == 0 || s == 5)) mbar_wait(sb + BAR_XRDY + 8, s == 5);
              if (elect_one()) mbar_arrive(fb);
              goto next_stage;
            }
            if (k == count - 4 && sg >= 3) seen = ld_relaxed(word);
          }
        } else {
          mbar_wait(rb, rph);
          rb += 8;
          if (rb == rend) { rb -= 8 * NBAR; rph ^= 1; }
        }
        if (IS_A && !((ready >> code) & 1)) {
          cur = max(cur, (int)(seen - tag32));
          ready = __ballot_sync(0xffffffffu, cur >= need) >> sh;
          if (!((ready >> code) & 1)) {
            cur = (int)(poll_line(word, tag32 + need, 1u << (code + sh)) - tag32);
            ready = __ballot_sync(0xffffffffu, cur >= need) >> sh;
          }
          asm volatile("fence.acquire.gpu;" ::: "memory");
          fence_async_global();
        }
        if (elect_one()) {
          if (!IS_A) tma_ld3_pair(base + pos, map, fb, c0, kc + 32 * (m & 1), c2);
          else tma_ld2(base + pos, map, fb, kc, 128 * m);
          mbar_expect_tx(fb, IS_A ? 16384 : bbytes);
        }
      next_stage:
        fb += 8;
        if (fb == fend) fb -= 8 * NBAR;
        pos += bbytes + 2 * UNIT;
        if (pos >= RING_UNITS * UNIT) pos -= RING_UNITS * UNIT;
      }
      special = !IS_A ? 0 : t == 2 ? 1 : add == 128 ? 0x10 : 0;
      if (t == 2) order0 = others << 4 | n;
      if (IS_A && (t == 2 || add == 64 || add == 192)) ev++;
    }
  }
}

__device__ __forceinline__ void publisher(const Params& p, uint32_t sb, int m, int n) {
  const uint32_t tag = __ldcg(p.g->epoch + m * 8 + n) + 1;
  uint32_t* word = p.g->flags + m * 32 + n;
  const int mn = m * 8 + n; (void)mn;
  st_relaxed(word, 32 * tag);
#pragma unroll 1
  for (int c = 0; c < 18; c++) {
    const int e = c >= 9 ? c - 9 : c;
    if ((0x18C >> e) & 1) {
      const int half = (0x108 >> e) & 1;
      mbar_wait(sb + BAR_XRDY + 8 * half, e < 4);
#pragma unroll
      for (int w = 0; w < 4; w++) tma_st2(&p.out_st, sb + OFF_X + half * 16384 + w * 4096, 128 * n + 64 * half, 128 * m + 32 * w);
      bulk_commit();
      if (c >= 16) continue;
      bulk_wait_all();
      PROF_E(7 * (c >= 9) + (e < 4 ? 2 : 6), 11 + 2 * half);
    } else {
      mbar_wait(sb + BAR_PUB + 8 * e, c >= 9);
    }
    asm volatile("fence.release.gpu;" ::: "memory");
    asm volatile("red.relaxed.gpu.global.add.u32 [%0], 1;" ::"l"(word) : "memory");
    PROF_E(7 * (c >= 9) + nib(0x665432210ull, e), (0x108 >> e) & 1 ? 14 : 12);
  }
  p.g->epoch[m * 8 + n] = tag;
  bulk_wait_read();
}

__device__ __forceinline__ void sum_rows(uint32_t buf, int iters, float (&a)[8], int lane) {
  uint32_t addr = buf + (lane >> 3) * 128 + (((lane & 7) ^ (lane >> 3)) << 4);
#pragma unroll 1
  for (int it = 0; it < iters; it++) {
    uint32_t u[2][4];
    lds_u4(addr, u[0][0], u[0][1], u[0][2], u[0][3]);
    lds_u4((addr ^ 64) + 512, u[1][0], u[1][1], u[1][2], u[1][3]);
    addr += 1024;
#pragma unroll
    for (int e = 0; e < 8; e++) { a[2 * (e & 3)] += bf_lo(u[e >> 2][e & 3]); a[2 * (e & 3) + 1] += bf_hi(u[e >> 2][e & 3]); }
  }
}
__device__ __forceinline__ void publish_sums(const float (&a)[8], uint4* dst, int lane, uint32_t tag) {
  const bool u8 = lane & 8, u16 = lane & 16;
  float h4[4], h2[2];
#pragma unroll
  for (int e = 0; e < 4; e++) h4[e] = (u8 ? a[4 + e] : a[e]) + __shfl_xor_sync(0xffffffffu, u8 ? a[e] : a[4 + e], 8);
#pragma unroll
  for (int e = 0; e < 2; e++) h2[e] = (u16 ? h4[2 + e] : h4[e]) + __shfl_xor_sync(0xffffffffu, u16 ? h4[e] : h4[2 + e], 16);
  st_msg(dst + (lane & 7) * 4 + (u8 ? 2 : 0) + (u16 ? 1 : 0), __float_as_uint(h2[0]), __float_as_uint(h2[1]), 0u, tag);
}

__device__ __forceinline__ void colsum_helper(const Params& p, uint32_t sb, int m, int n, int lane) {
  const uint32_t tag = __ldcg(p.g->epoch + m * 8 + n) + 1;
  const int mn = m * 8 + n; (void)mn;
#pragma unroll 1
  for (int k = lane; k < 288; k += 32) {
    const uint32_t bb = __ldg(reinterpret_cast<const uint32_t*>(k < 224 ? p.b1 + 448 * n : p.b2 + 128 * n - 448) + k);
    const float sc = k < 224 ? 0.5f : 1.f;
    sts_f2(sb + (k < 224 ? OFF_CSF + k * 16 + 8 : OFF_CSQ + 1536 + (k - 224) * 8), sc * bf_lo(bb), sc * bf_hi(bb));
  }
  __syncwarp();
  if (elect_one()) mbar_arrive(sb + BAR_BIAS);
  bar_sync(BAR_HLP, 160);
  PROF_E(-1, 1);
#pragma unroll 1
  for (int c = 0; c < 7; c++) {
    float a[8] = {0.f, 0.f, 0.f, 0.f, 0.f, 0.f, 0.f, 0.f};
#pragma unroll 1
    for (int h = 0; h < 2; h++) {
      if (elect_one()) {
        mbar_expect_tx(sb + BAR_CSLD + 8, 4096);
        tma_ld2(sb + OFF_HLP, &p.w1c, sb + BAR_CSLD + 8, 448 * n + 64 * c, 64 * m + 32 * h);
        if (c < 6) asm volatile("cp.async.bulk.prefetch.tensor.2d.L2.global [%0, {%1, %2}];" ::"l"(&p.w1c), "r"(448 * n + 64 * c + 64), "r"(64 * m + 32 * h) : "memory");
      }
      mbar_wait(sb + BAR_CSLD + 8, h);
      sum_rows(sb + OFF_HLP, 4, a, lane);
      __syncwarp();
    }
    publish_sums(a, p.g->csp + ((8 + n) * 17 + m) * 224 + c * 32, lane, tag);
  }
  PROF_E(-1, 2);
}

__device__ __forceinline__ void poll_msgs2(const uint4* pa, const uint4* pb, float (&v)[4], uint32_t tag) {
#pragma unroll 1
  for (int it = 0; it < MSG_SPINS; it++) {
    uint32_t x[4], z, ta, tb;
    ld_msg(pa, x[0], x[1], z, ta);
    ld_msg(pb, x[2], x[3], z, tb);
#pragma unroll
    for (int e = 0; e < 4; e++) v[e] = __uint_as_float(x[e]);
    if (__all_sync(0xffffffffu, ta == tag && tb == tag)) break;
  }
}
__device__ __forceinline__ void colsum_total(const Params& p, const Ctx& cx, int mat, uint32_t tag) {
  uint4* base = p.g->csp + (mat * 8 + cx.n) * 17 * 224;
  const int per = 12 + 2 * mat, k = 2 * cx.w + (cx.lane >> 4), ia = per * cx.m + k, ib = per * cx.m + min(k + 8, per - 1);
  float v[4];
  poll_msgs2(base + (cx.lane & 15) * 224 + ia, base + (cx.lane & 15) * 224 + ib, v, tag);
#pragma unroll 1
  for (int d = 1; d < 16; d *= 2)
#pragma unroll
    for (int e = 0; e < 4; e++) v[e] += __shfl_xor_sync(0xffffffffu, v[e], d);
  const bool hi = cx.lane & 1;
  if ((cx.lane & 14) == 0) st_msg(base + 16 * 224 + (hi ? ib : ia), __float_as_uint(hi ? v[2] : v[0]), __float_as_uint(hi ? v[3] : v[1]), 0u, tag);
}
__device__ __forceinline__ void colsum_gather(const Params& p, const Ctx& cx, int mat, uint32_t tag) {
  const uint4* base = p.g->csp + ((mat * 8 + cx.n) * 17 + 16) * 224;
  const int ia = cx.w * 32 + cx.lane, ib = min(ia + 128, 191 + 32 * mat);
  float v[4];
  poll_msgs2(base + ia, base + ib, v, tag);
  const uint32_t tab = cx.sb + (mat ? OFF_CSF : OFF_CSQ);
  sts_f2(tab + (ia << (3 + mat)), v[0], v[1]);
  sts_f2(tab + (ib << (3 + mat)), v[2], v[3]);
}

#define ACC(q, j, e) acc[(q) & 1][4 * (j) + 2 * ((q) >> 1) + (e)]

constexpr uint32_t RING16 = RING_UNITS * (UNIT >> 4);
__device__ __forceinline__ bool tile_split(int i) { return (0xD98 >> i) & 1; }

__device__ __forceinline__ void write_run_desc(uint32_t sb, int i, int step) {
  const int layer = i >= 7, t = i - 7 * layer, part = tile_split(i) ? step : 2;
  const bool wide = tile_wide(t), own = t != 2 && t != 6 && part != 1 && i != 0, second = t == 1 || t == 4;
  const uint32_t z16 = (wide ? 5 : 4) * (UNIT >> 4), a_off = z16 - 1024 + (uint32_t)DESC_A - (uint32_t)DESC_B;
  const int gl = 16 * t + (part == 2 ? 0 : second ? 16 * part - 14 : 4 * part), g0 = layer * STAGES_PER_LAYER + gl;
  const uint32_t s16 = (sb & 0x3FFFF) >> 4, bfirst = (uint32_t)DESC_B + s16;
  const int nkb = t == 6 ? 56 : part == 0 ? 2 : 12 + 2 * part;
  const bool win1 = t == 1 && part != 0;
  const int run = win1 ? WIN1 + 1 : t == 2 ? WIN2 + 1 : nkb;
  const int rest = win1 ? 64 | (nkb - 1 - WIN1) : t == 2 ? 64 | (7 - WIN2) | (8 << 7) : 0;
  const uint32_t blo = bfirst + z16 * (wide ? (gl + (t == 5 ? 3 : 0)) & 3 : (gl + 3) % 5);
  const uint32_t alo = own ? (uint32_t)DESC_A + s16 + (OFF_X >> 4) : blo + a_off;
  const uint32_t aoff = own ? alo + 1024 - (blo == bfirst + RING16 - z16 ? bfirst : blo + z16) : a_off;
  const bool xwait = part == 0 && !second, keep = !(part == 0 || t == 5);
  sts_u4(sb + OFF_RUN + (2 * i + step) * 16, blo, alo, aoff,
         ((g0 / NBAR) & 1) | xwait << 1 | keep << 2 | 8 * (g0 % NBAR) | run << 6 | rest << 12);
}

template <int N>
__device__ __forceinline__ void mainloop(const Params& p, float (&acc)[2][96], uint32_t sb, int i, int step, int mn) {
  constexpr uint32_t Z16 = (2 + N / 64) * (UNIT >> 4);
  constexpr uint32_t A_OFF = Z16 - 1024 + (uint32_t)DESC_A - (uint32_t)DESC_B;
  const int wg = i & 1;
  const uint32_t s16 = (sb & 0x3FFFF) >> 4;
  const uint32_t blast = (uint32_t)DESC_B + s16 + RING16 - Z16, flast = sb + BAR_FULL + 8 * (NBAR - 1);
  uint32_t blo = (uint32_t)DESC_B + s16, alo = blo + A_OFF, aoff = A_OFF, misc = 16 << 6;
  if (N == 128 || i > 0) lds_u4(sb + OFF_RUN + (2 * i + step) * 16, blo, alo, aoff, misc);
  uint32_t keep = misc & 4;
  int run = (misc >> 6) & 63, rest = misc >> 12;
  uint32_t fb = sb + BAR_FULL + (misc & 0x38), ph = misc & 1;
  uint32_t prev = sb + BAR_DUMMY - 8 * NBAR;
  const uint32_t lane_id = (threadIdx.x & 31) | p.zero, rel = pair_offset(sb, lane_id & 1) + 8 * NBAR;
  pin_regs<N / 2>(acc);
  if (N == 128 || i > 0) bar_sync(BAR_ORDER + wg, 256);
  else cluster_wait();
  if (N == 192 && i == 0 && threadIdx.x == 0) PROF_U(8);
  mbar_wait(fb, ph);
  if (misc & 2) mbar_wait(sb + BAR_XRDY, N == 128);
  if (step == 0 || !tile_split(i)) PROF_T(4 + i * 4);
#pragma unroll 1
  while (true) {
    const uint64_t da = (DESC_A & ~0xffffffffull) | alo, db = (DESC_B & ~0xffffffffull) | blo;
    asm volatile("wgmma.fence.sync.aligned;" ::: "memory");
    wgmma_ss<N>(acc[0], da, db, keep);
    wgmma_ss<N>(acc[1], da + 64, db, keep);
    keep = 4;
    wgmma_ss<N>(acc[0], da + 2, db + 128);
    wgmma_ss<N>(acc[1], da + 66, db + 128);
    asm volatile("wgmma.commit_group.sync.aligned;" ::: "memory");
    asm volatile("wgmma.wait_group.sync.aligned 1;" ::: "memory");
    PROF_S(jj++);
    if (lane_id < 2) mbar_arrive_cluster(prev + rel);
    prev = fb;
    if (fb == flast) { fb -= 8 * NBAR; ph++; }
    fb += 8;
    if (blo == blast) blo -= RING16;
    blo += Z16;
    alo = blo + aoff;
    aoff = A_OFF;
    run--;
    const bool ready = mbar_test(fb, ph) && run != 0;
    asm volatile("wgmma.fence.sync.aligned;" ::: "memory");
    wgmma_ss<N>(acc[0], da + 4, db + 4 * N);
    wgmma_ss<N>(acc[1], da + 68, db + 4 * N);
    wgmma_ss<N>(acc[0], da + 6, db + 4 * N + 128);
    wgmma_ss<N>(acc[1], da + 70, db + 4 * N + 128);
    asm volatile("wgmma.commit_group.sync.aligned;" ::: "memory");
    if (!ready) {
      if (run == 0) {
        if (rest == 0) break;
        if (rest & 64) {
          bar_arrive(BAR_GO, 256);
          bar_sync(BAR_DONE, 256);
        } else {
          alo = (uint32_t)DESC_A + s16 + (OFF_STG >> 4);
        }
        run = rest & 63;
        rest >>= 7;
      }
      mbar_wait(fb, ph);
    }
  }
  if (i < 13 && !(LATE_O && N == 192 && (misc >> 12))) bar_arrive(BAR_ORDER + (wg ^ 1), 256);
  if (N == 128 && ((0x2244 >> i) & 1)) {
    const Ctx cx = make_ctx(sb, mn);
    const uint32_t xrow = cx.sb + OFF_X + cx.w * 4096 + cx.lane * 128 + ((cx.lane & 7) << 4);
    const bool leader = elect_one();
    asm volatile("wgmma.wait_group.sync.aligned 0;" ::: "memory");
    pin_regs<64>(acc);
    PROF_T(5 + i * 4);
    PROF_E(i, 0);
#pragma unroll
    for (int h = 0; h < 2; h++) {
      if (h == 1 && p.zero != 0) break;
#pragma unroll
      for (int j = 8 * h; j < 8 * h + 8; j++)
        stsm4((xrow ^ ((j & 7) << 4)) + h * 16384, pack_bf16(ACC(0, j, 0), ACC(0, j, 1)), pack_bf16(ACC(1, j, 0), ACC(1, j, 1)),
              pack_bf16(ACC(2, j, 0), ACC(2, j, 1)), pack_bf16(ACC(3, j, 0), ACC(3, j, 1)));
      fence_async_smem();
      __syncwarp();
      if (leader) mbar_arrive(sb + BAR_XRDY + 8 * h);
      if (h == 0 && lane_id < 2) mbar_arrive_cluster(prev + rel);
    }
    PROF_E(i, 4);
    return;
  }
  asm volatile("wgmma.wait_group.sync.aligned 0;" ::: "memory");
  pin_regs<N / 2>(acc);
  if (lane_id < 2) mbar_arrive_cluster(prev + rel);
  PROF_T(5 + i * 4);
  PROF_E(i, 0);
}

__device__ __forceinline__ void write_partial_stats(const Params& p, const Ctx& c, int ln, uint32_t tag) {
  const uint32_t xrow = c.sb + OFF_X + c.w * 4096 + c.lane * 128;
  float s = 0.f, q = 0.f, s1 = 0.f, q1 = 0.f;
#pragma unroll 4
  for (int j = 0; j < 16; j++) {
    uint32_t u[4];
    lds_u4(xrow + (j >> 3) * 16384 + (((j & 7) ^ (c.lane & 7)) << 4), u[0], u[1], u[2], u[3]);
#pragma unroll
    for (int e = 0; e < 4; e++) {
      const float a = bf_lo(u[e]), d = bf_hi(u[e]);
      s += a; q = fmaf(a, a, q);
      s1 += d; q1 = fmaf(d, d, q1);
    }
  }
  s += s1;
  q += q1;
  st_msg(p.g->stats + (ln * 8 + c.n) * SEQ + 128 * c.m + 32 * c.w + c.lane, __float_as_uint(s),
         __float_as_uint(fmaxf(q - s * s * (1.f / 128.f), 0.f)), 0u, tag);
}

__device__ __forceinline__ void finish_row_stats(const Params& p, const Ctx& c, int ln, uint32_t tag) {
  const uint4* src = p.g->stats + ln * 8 * SEQ + 128 * c.m + 32 * c.w + c.lane;
  uint32_t ps[8], pm[8];
#pragma unroll 1
  for (int it = 0; it < MSG_SPINS; it++) {
    uint32_t bad = 0, u, tg;
#pragma unroll
    for (int k = 0; k < 8; k++) { ld_msg(src + k * SEQ, ps[k], pm[k], u, tg); bad |= tg ^ tag; }
    if (__all_sync(0xffffffffu, bad == 0)) break;
  }
  float s = 0.f, m2 = 0.f;
#pragma unroll
  for (int k = 0; k < 8; k++) s += __uint_as_float(ps[k]);
  const float mean = s * (1.f / DM);
#pragma unroll
  for (int k = 0; k < 8; k++) {
    const float d = __uint_as_float(ps[k]) * (1.f / 128.f) - mean;
    m2 += fmaf(128.f * d, d, __uint_as_float(pm[k]));
  }
  sts_f2(c.sb + OFF_ROW + (32 * c.w + c.lane) * 8, rsqrtf(m2 * (1.f / DM) + 1e-5f), mean);
  __syncwarp();
}

__device__ __forceinline__ void attn_scores(const uint32_t* qa, const uint32_t* qb, const uint32_t* k0, const uint32_t* k1,
                                            const uint32_t* k2, const uint32_t* k3, float (&l)[4], const float4& zero,
                                            bool par, bool early) {
  float s[4][4];
#pragma unroll
  for (int kb = 0; kb < 4; kb++) {
    const uint32_t* kk = kb == 0 ? k0 : kb == 1 ? k1 : kb == 2 ? k2 : k3;
    asm volatile("mma.sync.aligned.m16n8k16.row.col.f32.bf16.bf16.f32 {%0,%1,%2,%3}, {%4,%5,%6,%7}, {%8,%9}, {%10,%11,%12,%13};"
                 : "=f"(s[kb][0]), "=f"(s[kb][1]), "=f"(s[kb][2]), "=f"(s[kb][3])
                 : "r"(qa[0]), "r"(qb[0]), "r"(qa[1]), "r"(qb[1]), "r"(kk[0]), "r"(kk[1]), "f"(zero.x), "f"(zero.y),
                   "f"(zero.z), "f"(zero.w));
  }
#pragma unroll
  for (int kb = 0; kb < 4; kb++) {
    const uint32_t* kk = kb == 0 ? k0 : kb == 1 ? k1 : kb == 2 ? k2 : k3;
    mma16816(s[kb], qa[2], qb[2], qa[3], qb[3], kk[2], kk[3]);
  }
  l[0] = par ? s[1][1] : s[1][0];
  l[1] = early ? (par ? s[0][1] : s[0][0]) : (par ? s[2][1] : s[2][0]);
  l[2] = par ? s[2][3] : s[2][2];
  l[3] = early ? (par ? s[1][3] : s[1][2]) : (par ? s[3][3] : s[3][2]);
}

__device__ __forceinline__ void attn_mix(const float (&l)[4], const float (&sc)[4], const float (&off)[4], const float (&rk)[4],
                                         const uint32_t* v0, const uint32_t* v1, const uint32_t* v2, const uint32_t* v3,
                                         uint32_t* olo, uint32_t* ohi, const uint32_t (&sel)[4]) {
  float x[4];
#pragma unroll
  for (int e = 0; e < 4; e++) x[e] = fmaf(l[e], sc[e], off[e]);
  const float ml = quad_max(fmaxf(x[0], x[1])), mh = quad_max(fmaxf(x[2], x[3]));
  x[0] = ex2(x[0] - ml); x[1] = ex2(x[1] - ml);
  x[2] = ex2(x[2] - mh); x[3] = ex2(x[3] - mh);
  const uint32_t pl = pack_bf16(x[0] * rk[0], x[1] * rk[1]), ph = pack_bf16(x[2] * rk[2], x[3] * rk[3]);
  const uint32_t a0 = prmt_u(pl, sel[1]), a1 = prmt_u(pl, sel[3]), a2 = prmt_u(pl, sel[0]), a3 = prmt_u(ph, sel[1]);
  const uint32_t c0 = prmt_u(pl, sel[2]), c1 = prmt_u(ph, sel[0]), c2 = prmt_u(ph, sel[3]), c3 = prmt_u(ph, sel[2]);
  float o[4][4];
#pragma unroll
  for (int jn = 0; jn < 4; jn++) {
    o[jn][0] = o[jn][1] = o[jn][2] = o[jn][3] = 0.f;
    mma16816(o[jn], a0, a1, a2, a3, v0[jn], v1[jn]);
  }
#pragma unroll
  for (int jn = 0; jn < 4; jn++) mma16816(o[jn], c0, c1, c2, c3, v2[jn], v3[jn]);
  const float il = rcp_hw(quad_sum(x[0] + x[1])), ih = rcp_hw(quad_sum(x[2] + x[3]));
#pragma unroll
  for (int jn = 0; jn < 4; jn++) {
    olo[jn] = pack_bf16(o[jn][0] * il, o[jn][1] * il);
    ohi[jn] = pack_bf16(o[jn][2] * ih, o[jn][3] * ih);
  }
}

__device__ __forceinline__ void gelu_epilogue(const Params& p, float (&acc)[2][96], const Ctx& cx, int t) {
  UNPACK_CTX(cx);
  (void)wg;
  float rs[4], rm[4];
#pragma unroll
  for (int q = 0; q < 4; q++) {
    const float2 v = lds_f2(sb + OFF_ROW + (32 * w + 8 * q + (lane >> 2)) * 8);
    rs[q] = 0.5f * v.x;
    rm[q] = -rs[q] * v.y;
  }
  const int col0 = 128 * (t - 3);
  const uint32_t stg = sb + OFF_STG + w * 4096;
  const uint32_t ctab = sb + OFF_CSF + (col0 / 2 + (lane & 3)) * 16, srow = stg + lane * 128 + ((lane & 7) << 4);
  float4 nb = lds_f4(ctab);
#pragma unroll
  for (int c = 0; c < 3; c++) {
    if (c == 2 && t != 5) break;
    uint32_t hp[8][4];
#pragma unroll
    for (int j = 0; j < 8; j++) {
      const float4 cb = nb;
      if (8 * c + j < 23) nb = lds_f4(ctab + (8 * c + j + 1) * 64);
#pragma unroll
      for (int q = 0; q < 4; q++) {
        float y[2];
        const int k = 4 * j + q - GELU_DEP;
        const float rmq = k >= 0 ? chain(rm[q], hp[k >> 2][k & 3], p.zero) : rm[q];
#pragma unroll
        for (int e = 0; e < 2; e++) {
          const float z = fmaf(ACC(q, 8 * c + j, e), rs[q], fmaf(rmq, e ? cb.y : cb.x, e ? cb.w : cb.z));
          const float u = z * fmaf(z * z, 8.f * 0.7978845608028654f * 0.044715f, 2.f * 0.7978845608028654f);
          y[e] = fmaf(z, tanh_hw(u), z);
        }
        hp[j][q] = pack_bf16(y[0], y[1]);
      }
      if (j == STG_WAIT && c > 0) {
        if (lane == 0) bulk_wait_read();
        __syncwarp();
      }
      if (c == 0 || j > STG_WAIT) {
        stsm4(srow ^ (j << 4), hp[j][0], hp[j][1], hp[j][2], hp[j][3]);
      } else if (j == STG_WAIT) {
#pragma unroll
        for (int jj = 0; jj <= STG_WAIT; jj++) stsm4(srow ^ (jj << 4), hp[jj][0], hp[jj][1], hp[jj][2], hp[jj][3]);
      }
    }
    fence_async_smem();
    __syncwarp();
    if (lane == 0) {
      tma_st2(&p.h_st, stg, 448 * n + col0 + 64 * c, 128 * m + 32 * w);
      bulk_commit();
    }
  }
#pragma unroll
  for (int r = 0; r < 16; r++) acc[0][r] = acc[1][r] = 0.f;
}

__device__ __forceinline__ void attn_epilogue(const Params& p, float (&acc)[2][96], const Ctx& cx, int layer, int t, uint32_t tag) {
  UNPACK_CTX(cx);
  const bool par = (lane >> 2) & 1, early = (lane & 3) > (lane >> 3);
  const uint32_t ktab = sb + OFF_ROW + (32 * w + 2 * (lane & 3) + par) * 8, exc = sb + OFF_STG + w * 4096 + lane * 16;
  const int slot = ((layer * 2 + t) * 16 + m) * 8 + n;
  const int mn = m * 8 + n; (void)mn;
  uint32_t Q[4][8], K[4][8], V[4][8], E[36], P[36];
  float kr[6], qr[4];
#pragma unroll
  for (int q = 2; q < 4; q++) {
    kr[2 + q] = lds_f(ktab + 64 * q);
#pragma unroll
    for (int j = 0; j < 8; j++) {
      E[8 * (q - 2) + j] = K[q][j] = pack_bf16(ACC(q, 8 + j, 0), ACC(q, 8 + j, 1));
      E[16 + 2 * j + q - 2] = V[q][j] = movtrans(pack_bf16(ACC(q, 16 + j, 0), ACC(q, 16 + j, 1)));
    }
  }
#pragma unroll
  for (int j = 0; j < 16; j++) K[j >> 3][j & 7] = pack_bf16(ACC(j >> 3, 8 + (j & 7), 0), ACC(j >> 3, 8 + (j & 7), 1));
#pragma unroll
  for (int j = 0; j < 16; j++) asm volatile("" : "+r"(K[j >> 3][j & 7]));
  E[32] = __float_as_uint(kr[4]);
  E[33] = E[34] = E[35] = __float_as_uint(kr[5]);
  if (w < 3) {
#pragma unroll
    for (int k = 0; k < 8; k++) sts_u4(exc + k * 512, E[4 * k], E[4 * k + 1], E[4 * k + 2], E[4 * k + 3]);
  } else {
#pragma unroll
    for (int k = 0; k < 12; k++) st_msg(p.g->halo + slot * 384 + k * 32 + lane, E[3 * k], E[3 * k + 1], E[3 * k + 2], tag);
  }
  bar_arrive(BAR_PAIR + w, 64);
  if (LATE_O && t == 1) bar_arrive(BAR_ORDER + (wg ^ 1), 256);
  PROF_E(7 * layer + t, 1);
#pragma unroll
  for (int q = 0; q < 4; q++) {
    qr[q] = lds_f(sb + OFF_ROW + (32 * w + 8 * q + (lane >> 2)) * 8) * (0.17677669529663687f * 1.4426950408889634f);
#pragma unroll
    for (int j = 0; j < 8; j++) Q[q][j] = pack_bf16(ACC(q, j, 0), ACC(q, j, 1));
    if (q < 2) {
      kr[2 + q] = lds_f(ktab + 64 * q);
#pragma unroll
      for (int j = 0; j < 8; j++) V[q][j] = movtrans(pack_bf16(ACC(q, 16 + j, 0), ACC(q, 16 + j, 1)));
    }
  }
  PROF_E(7 * layer + t, 6);
  bar_sync(BAR_PAIR + ((w + 3) & 3), 64);
  if (w > 0 || m == 0) {
    const uint32_t back = w > 0;
#pragma unroll
    for (int k = 0; k < 8; k++) lds_u4(exc - back * 4096 + k * 512, P[4 * k], P[4 * k + 1], P[4 * k + 2], P[4 * k + 3]);
    P[32] = lds_u(ktab - back * 128);
    P[33] = lds_u(ktab - back * 64);
  } else {
    if (HALO_NS) __nanosleep(HALO_NS);
#pragma unroll 1
    for (int it = 0; it < MSG_SPINS; it++) {
      uint32_t tg, bad = 0;
      if (it > 0) poll_line(reinterpret_cast<const uint32_t*>(p.g->halo + (slot - 8) * 384 + 383) + 3, tag, 1u);
#pragma unroll
      for (int k = 0; k < 12; k++) {
        ld_msg(p.g->halo + (slot - 8) * 384 + k * 32 + lane, P[3 * k], P[3 * k + 1], P[3 * k + 2], tg);
        bad |= tg ^ tag;
      }
      if (__all_sync(0xffffffffu, bad == 0)) break;
    }
  }
  kr[0] = __uint_as_float(P[32]);
  kr[1] = __uint_as_float(P[33]);
  uint32_t PV[2][8];
#pragma unroll
  for (int j = 0; j < 8; j++) { PV[0][j] = P[16 + 2 * j]; PV[1][j] = P[17 + 2 * j]; }
  float rk[2][4], sc[2][4], off[2][4];
#pragma unroll
  for (int g = 0; g < 2; g++) {
    rk[g][0] = kr[2 * g + 1];
    rk[g][1] = early ? kr[2 * g] : kr[2 * g + 2];
    rk[g][2] = kr[2 * g + 2];
    rk[g][3] = early ? kr[2 * g + 1] : kr[2 * g + 3];
#pragma unroll
    for (int e = 0; e < 4; e++) {
      const bool masked = g == 0 && e != 2 && (m | w) == 0 && (e == 0 || early);
      sc[g][e] = masked ? 0.f : rk[g][e] * qr[2 * g + (e >> 1)];
      off[g][e] = masked ? -1e30f : 0.f;
    }
  }
  const uint32_t none = 0x4444u | p.zero, second = par ? 0x3244u : 0x4432u;
  const uint32_t sel[4] = {par ? 0x1044u : 0x4410u, early ? second : none, early ? none : second, none};
  PROF_E(7 * layer + t, 2);
  bar_sync(BAR_GO, 256);
  const float4 zero = lds_f4(sb + OFF_ZERO);
  float l[2][2][4];
  uint32_t O[4][8];
#pragma unroll
  for (int h = 0; h < 2; h++) {
    if (h == 1) {
      Q[2][4] |= __float_as_uint(l[1][0][0]) & p.zero;
      Q[0][4] |= __float_as_uint(l[0][0][0]) & p.zero;
    }
    attn_scores(&Q[2][4 * h], &Q[3][4 * h], &K[0][4 * h], &K[1][4 * h], &K[2][4 * h], &K[3][4 * h], l[1][h], zero, par, early);
    attn_scores(&Q[0][4 * h], &Q[1][4 * h], &P[4 * h], &P[8 + 4 * h], &K[0][4 * h], &K[1][4 * h], l[0][h], zero, par, early);
  }
  const uint32_t stg = sb + OFF_STG + w * 4096, srow = stg + lane * 128 + ((lane & 7) << 4);
#pragma unroll
  for (int h = 0; h < 2; h++) {
    attn_mix(l[1][h], sc[1], off[1], rk[1], &V[0][4 * h], &V[1][4 * h], &V[2][4 * h], &V[3][4 * h], &O[2][4 * h], &O[3][4 * h], sel);
    attn_mix(l[0][h], sc[0], off[0], rk[0], &PV[0][4 * h], &PV[1][4 * h], &V[0][4 * h], &V[1][4 * h], &O[0][4 * h], &O[1][4 * h], sel);
#pragma unroll
    for (int j = 4 * h; j < 4 * h + 4; j++) stsm4(srow ^ (j << 4), O[0][j], O[1][j], O[2][j], O[3][j]);
  }
  bar_arrive(BAR_DONE, 256);
  fence_async_smem();
  __syncwarp();
  if (lane == 0) {
    tma_st2(&p.att_st, stg, 128 * n + 64 * t, 128 * m + 32 * w);
    bulk_commit();
  }
}

__device__ __forceinline__ void finish_stores(uint32_t sb, int i) {
  const int t = i >= 7 ? i - 7 : i;
  if ((threadIdx.x & 31) == 0) {
    bulk_wait_all();
    mbar_arrive(sb + BAR_PUB + 8 * (t < 2 ? t : t + 1));
  }
  __syncwarp();
  if (i < 12) bar_arrive(BAR_GUARD + ((i & 1) ^ 1), 256);
}

__device__ __forceinline__ bool consumer_tile(const Params& p, float (&acc)[2][96], uint32_t sb0, int i, int mn) {
  const int layer = i >= 7, t = i - 7 * layer, wg = i & 1;
  const bool resid = t == 2 || t == 6;
  {
    if (resid) {
      const Ctx cx = make_ctx(sb0, mn);
      const uint32_t xrow = cx.sb + OFF_X + cx.w * 4096 + cx.lane * 128;
      const uint32_t sel_lo = 0x1044u | p.zero, sel_hi = 0x3244u | p.zero;
#pragma unroll
      for (int j = 0; j < 16; j++) {
        uint32_t r[4];
        ldsm4(xrow + (j >> 3) * 16384 + (((j & 7) ^ (cx.lane & 7)) << 4), r[0], r[1], r[2], r[3]);
#pragma unroll
        for (int q = 0; q < 4; q++) {
          ACC(q, j, 0) = prmt_f(r[q], sel_lo);
          ACC(q, j, 1) = prmt_f(r[q], sel_hi);
        }
      }
    }
    if (t >= 5 || i == 7) finish_stores(sb0, i - 2);
#pragma unroll 1
    for (int step = !tile_split(i);; step++) {
      if (step == 1 && (t == 1 || t == 4)) {
        const Ctx cx = make_ctx(sb0, mn);
        if (i == 1) {
          const uint32_t epoch = __ldcg(p.g->epoch + (mn & 127));
          cluster_wait();
          asm volatile("st.shared.u32 [%0], %1;" ::"r"(sb0 + OFF_TAG), "r"(epoch + 1) : "memory");
        }
        const uint32_t tag = lds_u(cx.sb + OFF_TAG);
        const int ln = (i + 1) >> 2;
#pragma unroll 1
        for (int r = 0; r < 2; r++) {
          if (i == 1) {
            if (cx.w < 3) {
              float a[8] = {0.f, 0.f, 0.f, 0.f, 0.f, 0.f, 0.f, 0.f};
              mbar_wait(sb0 + BAR_CSLD, r);
#pragma unroll 1
              for (int h = 0; h < 2; h++) sum_rows(cx.sb + OFF_STG + h * 12288 + cx.w * 4096, 4, a, cx.lane);
              publish_sums(a, p.g->csp + (cx.n * 17 + cx.m) * 224 + (3 * r + cx.w) * 32, cx.lane, tag);
            }
            PROF_E(-1, 5 + r);
          }
          if (r == 1) break;
          if (i == 1) {
            bar_sync(BAR_WG + 1, 128);
            if (cx.w == 3 && elect_one()) {
              mbar_expect_tx(sb0 + BAR_CSLD, 24576);
              tma_ld3(sb0 + OFF_STG, &p.wqkv, sb0 + BAR_CSLD, 128 * cx.n + 64, 64 * cx.m, 0);
              tma_ld3(sb0 + OFF_STG + 12288, &p.wqkv, sb0 + BAR_CSLD, 128 * cx.n + 64, 64 * cx.m + 32, 0);
            }
            mbar_wait(sb0 + BAR_XRDY, 0);
            mbar_wait(sb0 + BAR_XRDY + 8, 0);
          }
          write_partial_stats(p, cx, ln, tag);
          PROF_E(i - 2, 8);
        }
        if (i == 1) {
          bar_arrive(BAR_HLP, 160);
          bar_sync(BAR_INIT, 160);
        }
        if (i <= 4) colsum_total(p, cx, ln, tag);
        PROF_E(i - 2, 9);
        if (i != 1) bar_sync(BAR_GUARD + wg, 256);
        finish_row_stats(p, cx, ln, tag);
        PROF_E(i - 2, 10);
        if (i <= 4) {
          colsum_gather(p, cx, ln, tag);
          if (i == 4) mbar_wait(sb0 + BAR_BIAS, 0);
          bar_sync(BAR_WG + wg, 128);
        }
        PROF_E(i - 2, 15);
        bar_arrive(BAR_GUARD + (wg ^ 1), 256);
      }
      if (step == 2 && !resid) bar_sync(BAR_GUARD + wg, 256);
      if (t + step == 2 || t == 6) {
        const Ctx cx = make_ctx(sb0, mn);
        float nm[4];
#pragma unroll
        for (int q = 0; q < 4; q++) nm[q] = t == 6 ? 1.f : -lds_f(cx.sb + OFF_ROW + (32 * cx.w + 8 * q + (cx.lane >> 2)) * 8 + 4);
        const uint32_t ctab = cx.sb + OFF_CSQ + ((t & 3) * 192 + 2 * (cx.lane & 3)) * 4;
#pragma unroll
        for (int j = 0; j < 24; j++) {
          const float2 cs = lds_f2(ctab + j * 32);
#pragma unroll
          for (int q = 0; q < 4; q++) {
            const int k = 4 * j + q - 1;
            const float nq = k >= 0 ? chain(nm[q], __float_as_uint(ACC(k & 3, k >> 2, 1)), p.zero) : nm[q];
            ACC(q, j, 0) = fmaf(nq, cs.x, ACC(q, j, 0));
            ACC(q, j, 1) = fmaf(nq, cs.y, ACC(q, j, 1));
          }
        }
      }
      if (step == 2) break;
      if (tile_wide(t)) {
        mainloop<192>(p, acc, sb0, i, step, mn);
      } else {
        mainloop<128>(p, acc, sb0, i, step, mn);
        if (resid) return false;
      }
    }
    if (t < 2) return true;
    gelu_epilogue(p, acc, make_ctx(sb0, mn), t);
    PROF_E(i, 4);
    return false;
  }
}

__global__ void __cluster_dims__(2, 1, 1) __launch_bounds__(384, 1) fused_layers_kernel(const int by_smid, const __nv_bfloat16* x_p, const __nv_bfloat16* wqkv_p,
                                                                  const __grid_constant__ Params p) {
  extern __shared__ __align__(1024) uint8_t smem_raw[];
  const uint32_t sb = uniform((uint32_t)__cvta_generic_to_shared(smem_raw));
  const int tid = threadIdx.x, lane = tid & 31, warp = uniform(tid >> 5), wg = warp >> 2, w = warp & 3;

  int mn;
  {
    int id = blockIdx.x;
    if (by_smid) asm volatile("mov.u32 %0, %%smid;" : "=r"(id));
    else if (id >= 120) id += 4;
    const int c = id >> 1;
    int g, j;
    if (c < 32) { g = c & 7; j = c >> 3; }
    else if (c < 60) { g = 1 + (c - 32) % 7; j = 4 + (c - 32) / 7; }
    else { g = 0; j = c - 58; }
    const int r = blockIdx.x & 1;
    mn = (g * 2 + r) * 8 + j;
    if (c == 60 || c == 61) {
      if (tid < 32) {
        const uint32_t tag = __ldcg(p.g->epoch + NCTA + (id & 3)) + 1;
#pragma unroll 1
        for (int mm = 0; mm < 16; mm++) poll_line(p.g->flags + mm * 32 + (lane & 7), 32 * tag, 0xffu);
        if (tid == 0) p.g->epoch[NCTA + (id & 3)] = tag;
      }
      return;
    }
  }
  const int m = mn >> 3, n = mn & 7;
  if (tid == 256) PROF_U(1);
  if (tid >= 382) asm volatile("prefetch.global.L2 [%0];" ::"l"(tid & 1 ? wqkv_p + 128 * n : x_p + 128 * m * DM));
  if (wg < 2) {
    cluster_arrive();
    asm volatile("setmaxnreg.inc.sync.aligned.u32 232;");
    const int id = mn | (warp << 7);
#pragma unroll 1
    for (int i = wg;; i += 2) {
      float acc[2][96];
#pragma unroll
      for (int r = 0; r < 96; r++) acc[0][r] = acc[1][r] = 0.f;
      pin_regs<96>(acc);
#pragma unroll 1
      while (!consumer_tile(p, acc, sb, i, id)) {
        PROF_T(6 + i * 4);
        i += 2;
        if (i >= 14) goto all_done;
      }
      attn_epilogue(p, acc, make_ctx(sb, id), i >= 7, i >= 7 ? i - 7 : i, lds_u(sb + OFF_TAG));
      PROF_E(i, 4);
      finish_stores(sb, i);
      PROF_E(i, 5);
      PROF_T(6 + i * 4);
    }
  all_done:
    if (wg == 0) {
      finish_stores(sb, 12);
    } else {
      cluster_arrive();
      cluster_wait();
    }
  } else {
    asm volatile("setmaxnreg.dec.sync.aligned.u32 40;");
    if (w != 0) {
      if (w == 1 && elect_one()) {
        mbar_init(sb + BAR_FULL + 32, 2);
#pragma unroll
        for (int k = 0; k < NBAR; k++) mbar_init(sb + BAR_EMPTY + 8 * k, 8);
#pragma unroll
        for (int k = 0; k < 3; k++) mbar_init(sb + BAR_XRDY + 8 * k, 4);
#pragma unroll
        for (int k = 0; k < 7; k++) mbar_init(sb + BAR_PUB + 8 * k, 4);
#pragma unroll
        for (int k = 0; k < 3; k++) mbar_init(sb + BAR_CSLD + 8 * k, 1);
        sts_f2(sb + OFF_ZERO, 0.f, 0.f);
        sts_f2(sb + OFF_ZERO + 8, 0.f, 0.f);
        asm volatile("fence.mbarrier_init.release.cluster;" ::: "memory");
      }
      __syncwarp();
      cluster_arrive();
      if (w == 2) {
        if (lane < 28) write_run_desc(sb, lane >> 1, lane & 1);
        bar_arrive(BAR_INIT, 160);
      }
      cluster_wait();
      if (w == 1) producer<true>(p, sb, m, n, lane);
      else if (w == 3) colsum_helper(p, sb, m, n, lane);
      else if (elect_one()) publisher(p, sb, m, n);
    } else {
      const bool leader = elect_one();
      if (leader) {
#pragma unroll
        for (int k = 0; k < 4; k++) mbar_init(sb + BAR_FULL + 8 * k, 2);
        asm volatile("fence.mbarrier_init.release.cluster;" ::: "memory");
        PROF_U(4);
      }
      __syncwarp();
      cluster_arrive();
      if (leader) {
#pragma unroll 1
        for (int k = 0; k < 4; k++) {
          const uint32_t fb = sb + BAR_FULL + 8 * k;
          mbar_expect_tx(fb, 16384);
          tma_ld2(sb + (5 * k + 3) * UNIT, &p.xin, fb, 64 * k, 128 * m);
          mbar_expect_tx(fb, 3 * UNIT);
          tma_ld3(sb + 5 * k * UNIT, &p.wqkv, fb, 128 * n, 64 * k, 0);
          tma_ld3(sb + 5 * k * UNIT + 12288, &p.wqkv, fb, 128 * n, 64 * k + 32, 0);
        }
        PROF_U(5);
      }
      __syncwarp();
      cluster_wait();
      if (leader) {
        mbar_expect_tx(sb + BAR_CSLD, 24576);
        tma_ld3(sb + OFF_STG, &p.wqkv, sb + BAR_CSLD, 128 * n, 64 * m, 0);
        tma_ld3(sb + OFF_STG + 12288, &p.wqkv, sb + BAR_CSLD, 128 * n, 64 * m + 32, 0);
#pragma unroll 1
        for (int h = 0; h < 2; h++) {
          const uint32_t xr = sb + BAR_XRDY + 8 * h;
          mbar_expect_tx(xr, 16384);
          tma_ld2(sb + OFF_X + h * 16384, &p.xin, xr, 128 * n + 64 * h, 128 * m);
          asm volatile("mbarrier.arrive.shared::cta.b64 _, [%0], 3;" ::"r"(xr) : "memory");
        }
        PROF_U(6);
      }
      __syncwarp();
      producer<false>(p, sb, m, n, lane);
    }
  }
}

typedef CUresult (*EncodeFn)(CUtensorMap*, CUtensorMapDataType, cuuint32_t, void*, const cuuint64_t*, const cuuint64_t*,
                             const cuuint32_t*, const cuuint32_t*, CUtensorMapInterleave, CUtensorMapSwizzle,
                             CUtensorMapL2promotion, CUtensorMapFloatOOBfill);

#define PROMO2 CU_TENSOR_MAP_L2_PROMOTION_L2_128B
#define PROMO3 CU_TENSOR_MAP_L2_PROMOTION_L2_128B
void make_2d(EncodeFn enc, CUtensorMap* m, const void* ptr, uint64_t cols, uint64_t rows, uint32_t box_rows) {
  cuuint64_t d[2] = {cols, rows}, st[1] = {cols * 2};
  cuuint32_t b[2] = {64, box_rows}, e[2] = {1, 1};
  enc(m, CU_TENSOR_MAP_DATA_TYPE_BFLOAT16, 2, const_cast<void*>(ptr), d, st, b, e, CU_TENSOR_MAP_INTERLEAVE_NONE,
      CU_TENSOR_MAP_SWIZZLE_128B, PROMO2, CU_TENSOR_MAP_FLOAT_OOB_FILL_NONE);
}
void make_3d(EncodeFn enc, CUtensorMap* m, const void* ptr, uint64_t d0, uint64_t rows, uint64_t d2, uint64_t row_bytes,
             uint64_t chunk_bytes, uint32_t box_chunks) {
  cuuint64_t d[3] = {d0, rows, d2}, st[2] = {row_bytes, chunk_bytes};
  cuuint32_t b[3] = {64, 32, box_chunks}, e[3] = {1, 1, 1};
  enc(m, CU_TENSOR_MAP_DATA_TYPE_BFLOAT16, 3, const_cast<void*>(ptr), d, st, b, e, CU_TENSOR_MAP_INTERLEAVE_NONE,
      CU_TENSOR_MAP_SWIZZLE_128B, PROMO3, CU_TENSOR_MAP_FLOAT_OOB_FILL_NONE);
}

}

extern "C" void kernel_launch(void* const* d_in, const int* in_sizes, int n_in, void* d_out, int out_size) {
  (void)in_sizes; (void)n_in; (void)out_size;
  static EncodeFn enc = nullptr;
  static void *att = nullptr, *hbuf = nullptr, *scratch = nullptr;
  static int by_smid = 0;
  if (!enc) {
    void* fn = nullptr;
    cudaDriverEntryPointQueryResult q;
    cudaGetDriverEntryPoint("cuTensorMapEncodeTiled", &fn, cudaEnableDefault, &q);
    enc = (EncodeFn)fn;
    cudaGetSymbolAddress(&att, g_att);
    cudaGetSymbolAddress(&hbuf, g_h);
    cudaGetSymbolAddress(&scratch, g_scratch);
    cudaFuncSetAttribute(fused_layers_kernel, cudaFuncAttributeMaxDynamicSharedMemorySize, SMEM_BYTES);
    int sms = 0, clusters = 0, dev = 0;
    cudaGetDevice(&dev);
    cudaDeviceGetAttribute(&sms, cudaDevAttrMultiProcessorCount, dev);
    cudaLaunchConfig_t cfg = {};
    cfg.gridDim = dim3(132);
    cfg.blockDim = dim3(384);
    cfg.dynamicSmemBytes = SMEM_BYTES;
    cudaLaunchAttribute at[1];
    at[0].id = cudaLaunchAttributeClusterDimension;
    at[0].val.clusterDim.x = 2; at[0].val.clusterDim.y = 1; at[0].val.clusterDim.z = 1;
    cfg.attrs = at;
    cfg.numAttrs = 1;
    if (cudaOccupancyMaxActiveClusters(&clusters, fused_layers_kernel, &cfg) != cudaSuccess) (void)cudaGetLastError();
    by_smid = sms == 132 && clusters == 66;
  }
  Params p;
  make_2d(enc, &p.xin, d_in[0], DM, SEQ, 128);
  make_2d(enc, &p.out, d_out, DM, SEQ, 128);
  make_2d(enc, &p.att, att, DM, SEQ, 128);
  make_2d(enc, &p.h, hbuf, FF, SEQ, 128);
  make_2d(enc, &p.out_st, d_out, DM, SEQ, 32);
  make_2d(enc, &p.att_st, att, DM, SEQ, 32);
  make_2d(enc, &p.h_st, hbuf, FF, SEQ, 32);
  make_2d(enc, &p.w1c, d_in[4], FF, DM, 32);
  make_3d(enc, &p.wqkv, d_in[1], DM, DM, 3, 3 * DM * 2, DM * 2, 3);
  make_3d(enc, &p.wo, d_in[2], 64, DM, DM / 64, DM * 2, 128, 2);
  make_3d(enc, &p.w1a, d_in[4], 64, DM, FF / 64, FF * 2, 128, 3);
  make_3d(enc, &p.w1b, d_in[4], 64, DM, FF / 64, FF * 2, 128, 2);
  make_3d(enc, &p.w2, d_in[6], 64, FF, DM / 64, DM * 2, 128, 2);
  p.b1 = (const __nv_bfloat16*)d_in[5];
  p.b2 = (const __nv_bfloat16*)d_in[7];
  p.g = (Scratch*)scratch;
  p.zero = 0;
  fused_layers_kernel<<<by_smid ? 132 : NCTA, 384, SMEM_BYTES>>>(by_smid, (const __nv_bfloat16*)d_in[0], (const __nv_bfloat16*)d_in[1], p);
}
```

```cpp
#include <cuda_runtime.h>
#include <cuda_bf16.h>
#include <cuda.h>
#include <stdint.h>

namespace {

constexpr int SEQ = 2048, DM = 1024, FF = 3584;
constexpr int NCTA = 128;
constexpr int NBAR = 5;

constexpr uint32_t RING_UNITS = 20, UNIT = 8192;
constexpr uint32_t OFF_X   = RING_UNITS * UNIT;
constexpr uint32_t OFF_STG = OFF_X + 32768;
constexpr uint32_t OFF_HLP = OFF_STG + 16384;
constexpr uint32_t OFF_RUN = OFF_STG + 24576;
constexpr uint32_t OFF_CSQ = OFF_RUN + 512;
constexpr uint32_t OFF_CSF = OFF_CSQ + 2048;
constexpr uint32_t OFF_ROW = OFF_CSF + 3584;
constexpr uint32_t OFF_BAR = OFF_ROW + 1024;
constexpr uint32_t SMEM_BYTES = OFF_BAR + 384;
constexpr uint32_t BAR_FULL = OFF_BAR, BAR_EMPTY = OFF_BAR + 8 * NBAR;
constexpr uint32_t BAR_XRDY = OFF_BAR + 80;
constexpr uint32_t BAR_DUMMY = OFF_BAR + 96, OFF_TAG = OFF_BAR + 104, OFF_ZERO = OFF_BAR + 112;
constexpr uint32_t BAR_PUB = OFF_BAR + 128;
constexpr uint32_t BAR_CSLD = OFF_BAR + 200;
constexpr uint32_t BAR_BIAS = OFF_BAR + 216;

constexpr uint64_t DESC_A = (1ull << 62) | ((uint64_t)(2048 >> 4) << 32) | (1ull << 16);
constexpr uint64_t DESC_B = (1ull << 62) | ((uint64_t)(1024 >> 4) << 32) | ((uint64_t)(4096 >> 4) << 16);

constexpr int BAR_INIT = 0, BAR_ORDER = 1, BAR_GUARD = 3, BAR_WG = 5, BAR_GO = 7, BAR_DONE = 8, BAR_HLP = 9, BAR_PAIR = 11;
#define GELU_DEP 2
#define MAP 2
#define LATE_O 1
#define HALO_NS 200
#define STG_WAIT 5
#define WIN1 8
#define WIN2 2

struct Scratch {
  uint4 stats[4 * 8 * SEQ];
  uint4 halo[2 * 2 * 16 * 8 * 384];
  uint4 csp[2 * 8 * 17 * 224];
  uint32_t flags[16 * 32];
  uint32_t epoch[NCTA + 4];
};

struct Params {
  CUtensorMap xin, out, att, h, wqkv, wo, w1a, w1b, w2, out_st, att_st, h_st, w1c;
  const __nv_bfloat16 *b1, *b2;
  Scratch* g;
  uint32_t zero;
};

__device__ __nv_bfloat16 g_att[SEQ * DM];
__device__ __nv_bfloat16 g_h[SEQ * FF];
__device__ Scratch g_scratch;
#define PROF_T(idx)
#define PROF_U(k)
#define PROF_S(g)
#define PROF_E(i, k)

__device__ __forceinline__ void mbar_init(uint32_t bar, int cnt) {
  asm volatile("mbarrier.init.shared::cta.b64 [%0], %1;" ::"r"(bar), "r"(cnt));
}
__device__ __forceinline__ void mbar_expect_tx(uint32_t bar, uint32_t bytes) {
  asm volatile("mbarrier.arrive.expect_tx.shared::cta.b64 _, [%0], %1;" ::"r"(bar), "r"(bytes) : "memory");
}
__device__ __forceinline__ void mbar_arrive(uint32_t bar) {
  asm volatile("mbarrier.arrive.shared::cta.b64 _, [%0];" ::"r"(bar) : "memory");
}
__device__ __forceinline__ bool mbar_test(uint32_t bar, uint32_t parity) {
  uint32_t ok;
  asm volatile("{\n.reg .pred p;\nmbarrier.test_wait.parity.shared::cta.b64 p, [%1], %2;\nselp.u32 %0, 1, 0, p;\n}"
               : "=r"(ok) : "r"(bar), "r"(parity) : "memory");
  return ok;
}
__device__ __forceinline__ void mbar_wait(uint32_t bar, uint32_t parity) {
  asm volatile(
      "{\n.reg .pred p;\n.reg .u32 it;\nmov.u32 it, 0;\n"
      "WAIT_LOOP:\n"
      "mbarrier.try_wait.parity.shared::cta.b64 p, [%0], %1;\n"
      "@p bra WAIT_DONE;\n"
      "add.u32 it, it, 1;\n"
      "setp.lt.u32 p, it, 0x400000;\n"
      "@p bra WAIT_LOOP;\n"
      "trap;\n"
      "WAIT_DONE:\n}"
      ::"r"(bar), "r"(parity) : "memory");
}
__device__ __forceinline__ void bar_sync(int id, int n) { asm volatile("bar.sync %0, %1;" ::"r"(id), "r"(n) : "memory"); }
__device__ __forceinline__ void bar_arrive(int id, int n) { asm volatile("bar.arrive %0, %1;" ::"r"(id), "r"(n) : "memory"); }
__device__ __forceinline__ void tma_ld2(uint32_t dst, const CUtensorMap* m, uint32_t bar, int c0, int c1) {
  asm volatile("cp.async.bulk.tensor.2d.shared::cluster.global.mbarrier::complete_tx::bytes [%0], [%1, {%3, %4}], [%2];"
               ::"r"(dst), "l"(m), "r"(bar), "r"(c0), "r"(c1) : "memory");
}
__device__ __forceinline__ void tma_ld3(uint32_t dst, const CUtensorMap* m, uint32_t bar, int c0, int c1, int c2) {
  asm volatile("cp.async.bulk.tensor.3d.shared::cluster.global.mbarrier::complete_tx::bytes [%0], [%1, {%3, %4, %5}], [%2];"
               ::"r"(dst), "l"(m), "r"(bar), "r"(c0), "r"(c1), "r"(c2) : "memory");
}
__device__ __forceinline__ void tma_ld3_pair(uint32_t dst, const CUtensorMap* m, uint32_t bar, int c0, int c1, int c2) {
  asm volatile("cp.async.bulk.tensor.3d.shared::cluster.global.mbarrier::complete_tx::bytes.multicast::cluster"
               " [%0], [%1, {%3, %4, %5}], [%2], %6;"
               ::"r"(dst), "l"(m), "r"(bar), "r"(c0), "r"(c1), "r"(c2), "h"((uint16_t)3) : "memory");
}
__device__ __forceinline__ uint32_t pair_offset(uint32_t sb, uint32_t rank) {
  uint32_t r;
  asm volatile("mapa.shared::cluster.u32 %0, %1, %2;" : "=r"(r) : "r"(sb), "r"(rank));
  return r - sb;
}
__device__ __forceinline__ void mbar_arrive_cluster(uint32_t bar) {
  asm volatile("mbarrier.arrive.shared::cluster.b64 _, [%0];" ::"r"(bar) : "memory");
}
__device__ __forceinline__ void cluster_arrive() { asm volatile("barrier.cluster.arrive.relaxed;" ::: "memory"); }
__device__ __forceinline__ void cluster_wait() { asm volatile("barrier.cluster.wait.acquire;" ::: "memory"); }
__device__ __forceinline__ void tma_st2(const CUtensorMap* m, uint32_t src, int c0, int c1) {
  asm volatile("cp.async.bulk.tensor.2d.global.shared::cta.bulk_group [%0, {%2, %3}], [%1];"
               ::"l"(m), "r"(src), "r"(c0), "r"(c1) : "memory");
}
__device__ __forceinline__ void bulk_commit() { asm volatile("cp.async.bulk.commit_group;" ::: "memory"); }
__device__ __forceinline__ void bulk_wait_read() { asm volatile("cp.async.bulk.wait_group.read 0;" ::: "memory"); }
__device__ __forceinline__ void bulk_wait_all() { asm volatile("cp.async.bulk.wait_group 0;" ::: "memory"); }
__device__ __forceinline__ void fence_async_smem() { asm volatile("fence.proxy.async.shared::cta;" ::: "memory"); }
__device__ __forceinline__ void fence_async_global() { asm volatile("fence.proxy.async.global;" ::: "memory"); }
__device__ __forceinline__ void st_relaxed(uint32_t* p, uint32_t v) {
  asm volatile("st.relaxed.gpu.global.u32 [%0], %1;" ::"l"(p), "r"(v) : "memory");
}
__device__ __forceinline__ void st_msg(uint4* p, uint32_t a, uint32_t b, uint32_t c, uint32_t tag) {
  asm volatile("{\n.reg .b128 v;\nmov.b128 v, {%1, %2, %3, %4};\nst.relaxed.gpu.global.b128 [%0], v;\n}"
               ::"l"(p), "r"(a), "r"(b), "r"(c), "r"(tag) : "memory");
}
__device__ __forceinline__ void ld_msg(const uint4* p, uint32_t& a, uint32_t& b, uint32_t& c, uint32_t& tag) {
  asm volatile("{\n.reg .b128 v;\nld.relaxed.gpu.global.b128 v, [%4];\nmov.b128 {%0, %1, %2, %3}, v;\n}"
               : "=r"(a), "=r"(b), "=r"(c), "=r"(tag) : "l"(p) : "memory");
}
__device__ __forceinline__ bool elect_one() {
  uint32_t ok;
  asm volatile("{\n.reg .pred p;\nelect.sync _|p, 0xffffffff;\nselp.u32 %0, 1, 0, p;\n}" : "=r"(ok));
  return ok;
}
__device__ __forceinline__ int uniform(int v) { return __shfl_sync(0xffffffffu, v, 0); }
__device__ __forceinline__ uint32_t pack_bf16(float lo, float hi) {
  uint32_t r;
  asm("cvt.rn.bf16x2.f32 %0, %1, %2;" : "=r"(r) : "f"(hi), "f"(lo));
  return r;
}
__device__ __forceinline__ uint32_t prmt_u(uint32_t a, uint32_t sel) {
  uint32_t r;
  asm("prmt.b32 %0, %1, 0, %2;" : "=r"(r) : "r"(a), "r"(sel));
  return r;
}
__device__ __forceinline__ float prmt_f(uint32_t a, uint32_t sel) {
  float r;
  asm("{\n.reg .b32 t;\nprmt.b32 t, %1, 0, %2;\nmov.b32 %0, t;\n}" : "=f"(r) : "r"(a), "r"(sel));
  return r;
}
__device__ __forceinline__ float bf_lo(uint32_t v) { return __uint_as_float(v << 16); }
__device__ __forceinline__ float bf_hi(uint32_t v) { return __uint_as_float(v & 0xffff0000u); }
__device__ __forceinline__ void stsm4(uint32_t addr, uint32_t r0, uint32_t r1, uint32_t r2, uint32_t r3) {
  asm volatile("stmatrix.sync.aligned.m8n8.x4.shared.b16 [%0], {%1, %2, %3, %4};"
               ::"r"(addr), "r"(r0), "r"(r1), "r"(r2), "r"(r3) : "memory");
}
__device__ __forceinline__ void ldsm4(uint32_t addr, uint32_t& r0, uint32_t& r1, uint32_t& r2, uint32_t& r3) {
  asm volatile("ldmatrix.sync.aligned.m8n8.x4.shared.b16 {%0, %1, %2, %3}, [%4];"
               : "=r"(r0), "=r"(r1), "=r"(r2), "=r"(r3) : "r"(addr) : "memory");
}
__device__ __forceinline__ uint32_t movtrans(uint32_t a) {
  uint32_t d;
  asm volatile("movmatrix.sync.aligned.m8n8.trans.b16 %0, %1;" : "=r"(d) : "r"(a));
  return d;
}
__device__ __forceinline__ void mma16816(float (&c)[4], uint32_t a0, uint32_t a1, uint32_t a2, uint32_t a3, uint32_t b0, uint32_t b1) {
  asm volatile("mma.sync.aligned.m16n8k16.row.col.f32.bf16.bf16.f32 {%0,%1,%2,%3}, {%4,%5,%6,%7}, {%8,%9}, {%0,%1,%2,%3};"
               : "+f"(c[0]), "+f"(c[1]), "+f"(c[2]), "+f"(c[3])
               : "r"(a0), "r"(a1), "r"(a2), "r"(a3), "r"(b0), "r"(b1));
}
__device__ __forceinline__ float2 lds_f2(uint32_t a) {
  float2 v;
  asm volatile("ld.shared.v2.f32 {%0, %1}, [%2];" : "=f"(v.x), "=f"(v.y) : "r"(a) : "memory");
  return v;
}
__device__ __forceinline__ float4 lds_f4(uint32_t a) {
  float4 v;
  asm volatile("ld.shared.v4.f32 {%0, %1, %2, %3}, [%4];" : "=f"(v.x), "=f"(v.y), "=f"(v.z), "=f"(v.w) : "r"(a) : "memory");
  return v;
}
__device__ __forceinline__ float lds_f(uint32_t a) {
  float v;
  asm volatile("ld.shared.f32 %0, [%1];" : "=f"(v) : "r"(a) : "memory");
  return v;
}
__device__ __forceinline__ uint32_t lds_u(uint32_t a) {
  uint32_t v;
  asm volatile("ld.shared.u32 %0, [%1];" : "=r"(v) : "r"(a) : "memory");
  return v;
}
__device__ __forceinline__ void sts_f2(uint32_t a, float x, float y) {
  asm volatile("st.shared.v2.f32 [%0], {%1, %2};" ::"r"(a), "f"(x), "f"(y) : "memory");
}
__device__ __forceinline__ void sts_u4(uint32_t a, uint32_t x, uint32_t y, uint32_t z, uint32_t w) {
  asm volatile("st.shared.v4.u32 [%0], {%1, %2, %3, %4};" ::"r"(a), "r"(x), "r"(y), "r"(z), "r"(w) : "memory");
}
__device__ __forceinline__ void lds_u4(uint32_t a, uint32_t& x, uint32_t& y, uint32_t& z, uint32_t& w) {
  asm volatile("ld.shared.v4.u32 {%0, %1, %2, %3}, [%4];" : "=r"(x), "=r"(y), "=r"(z), "=r"(w) : "r"(a) : "memory");
}
__device__ __forceinline__ float ex2(float x) {
  float y;
  asm("ex2.approx.ftz.f32 %0, %1;" : "=f"(y) : "f"(x));
  return y;
}
__device__ __forceinline__ float rcp_hw(float x) {
  float y;
  asm("rcp.approx.ftz.f32 %0, %1;" : "=f"(y) : "f"(x));
  return y;
}
__device__ __forceinline__ float tanh_hw(float x) {
  float y;
  asm("tanh.approx.f32 %0, %1;" : "=f"(y) : "f"(x));
  return y;
}
__device__ __forceinline__ float quad_sum(float v) {
  v += __shfl_xor_sync(0xffffffffu, v, 1);
  return v + __shfl_xor_sync(0xffffffffu, v, 2);
}
__device__ __forceinline__ float quad_max(float v) {
  v = fmaxf(v, __shfl_xor_sync(0xffffffffu, v, 1));
  return fmaxf(v, __shfl_xor_sync(0xffffffffu, v, 2));
}

template <int N> __device__ __forceinline__ void wgmma_ss(float (&d)[96], uint64_t da, uint64_t db, uint32_t keep = 1);
template <> __device__ __forceinline__ void wgmma_ss<128>(float (&d)[96], uint64_t da, uint64_t db, uint32_t keep) {
  asm volatile(
      "{\n.reg .pred p;\nsetp.ne.u32 p, %66, 0;\n"
      "wgmma.mma_async.sync.aligned.m64n128k16.f32.bf16.bf16 {%0, %1, %2, %3, %4, %5, %6, %7, %8, %9, %10, %11, %12, %13, %14, %15, %16, %17, %18, %19, %20, %21, %22, %23, %24, %25, %26, %27, %28, %29, %30, %31, %32, %33, %34, %35, %36, %37, %38, %39, %40, %41, %42, %43, %44, %45, %46, %47, %48, %49, %50, %51, %52, %53, %54, %55, %56, %57, %58, %59, %60, %61, %62, %63}, %64, %65, p, 1, 1, 0, 1;\n}"
      : "+f"(d[0]), "+f"(d[1]), "+f"(d[2]), "+f"(d[3]), "+f"(d[4]), "+f"(d[5]), "+f"(d[6]), "+f"(d[7]), "+f"(d[8]), "+f"(d[9]), "+f"(d[10]), "+f"(d[11]), "+f"(d[12]), "+f"(d[13]), "+f"(d[14]), "+f"(d[15]), "+f"(d[16]), "+f"(d[17]), "+f"(d[18]), "+f"(d[19]), "+f"(d[20]), "+f"(d[21]), "+f"(d[22]), "+f"(d[23]), "+f"(d[24]), "+f"(d[25]), "+f"(d[26]), "+f"(d[27]), "+f"(d[28]), "+f"(d[29]), "+f"(d[30]), "+f"(d[31]), "+f"(d[32]), "+f"(d[33]), "+f"(d[34]), "+f"(d[35]), "+f"(d[36]), "+f"(d[37]), "+f"(d[38]), "+f"(d[39]), "+f"(d[40]), "+f"(d[41]), "+f"(d[42]), "+f"(d[43]), "+f"(d[44]), "+f"(d[45]), "+f"(d[46]), "+f"(d[47]), "+f"(d[48]), "+f"(d[49]), "+f"(d[50]), "+f"(d[51]), "+f"(d[52]), "+f"(d[53]), "+f"(d[54]), "+f"(d[55]), "+f"(d[56]), "+f"(d[57]), "+f"(d[58]), "+f"(d[59]), "+f"(d[60]), "+f"(d[61]), "+f"(d[62]), "+f"(d[63])
      : "l"(da), "l"(db), "r"(keep));
}

template <> __device__ __forceinline__ void wgmma_ss<192>(float (&d)[96], uint64_t da, uint64_t db, uint32_t keep) {
  asm volatile(
      "{\n.reg .pred p;\nsetp.ne.u32 p, %98, 0;\n"
      "wgmma.mma_async.sync.aligned.m64n192k16.f32.bf16.bf16 {%0, %1, %2, %3, %4, %5, %6, %7, %8, %9, %10, %11, %12, %13, %14, %15, %16, %17, %18, %19, %20, %21, %22, %23, %24, %25, %26, %27, %28, %29, %30, %31, %32, %33, %34, %35, %36, %37, %38, %39, %40, %41, %42, %43, %44, %45, %46, %47, %48, %49, %50, %51, %52, %53, %54, %55, %56, %57, %58, %59, %60, %61, %62, %63, %64, %65, %66, %67, %68, %69, %70, %71, %72, %73, %74, %75, %76, %77, %78, %79, %80, %81, %82, %83, %84, %85, %86, %87, %88, %89, %90, %91, %92, %93, %94, %95}, %96, %97, p, 1, 1, 0, 1;\n}"
      : "+f"(d[0]), "+f"(d[1]), "+f"(d[2]), "+f"(d[3]), "+f"(d[4]), "+f"(d[5]), "+f"(d[6]), "+f"(d[7]), "+f"(d[8]), "+f"(d[9]), "+f"(d[10]), "+f"(d[11]), "+f"(d[12]), "+f"(d[13]), "+f"(d[14]), "+f"(d[15]), "+f"(d[16]), "+f"(d[17]), "+f"(d[18]), "+f"(d[19]), "+f"(d[20]), "+f"(d[21]), "+f"(d[22]), "+f"(d[23]), "+f"(d[24]), "+f"(d[25]), "+f"(d[26]), "+f"(d[27]), "+f"(d[28]), "+f"(d[29]), "+f"(d[30]), "+f"(d[31]), "+f"(d[32]), "+f"(d[33]), "+f"(d[34]), "+f"(d[35]), "+f"(d[36]), "+f"(d[37]), "+f"(d[38]), "+f"(d[39]), "+f"(d[40]), "+f"(d[41]), "+f"(d[42]), "+f"(d[43]), "+f"(d[44]), "+f"(d[45]), "+f"(d[46]), "+f"(d[47]), "+f"(d[48]), "+f"(d[49]), "+f"(d[50]), "+f"(d[51]), "+f"(d[52]), "+f"(d[53]), "+f"(d[54]), "+f"(d[55]), "+f"(d[56]), "+f"(d[57]), "+f"(d[58]), "+f"(d[59]), "+f"(d[60]), "+f"(d[61]), "+f"(d[62]), "+f"(d[63]), "+f"(d[64]), "+f"(d[65]), "+f"(d[66]), "+f"(d[67]), "+f"(d[68]), "+f"(d[69]), "+f"(d[70]), "+f"(d[71]), "+f"(d[72]), "+f"(d[73]), "+f"(d[74]), "+f"(d[75]), "+f"(d[76]), "+f"(d[77]), "+f"(d[78]), "+f"(d[79]), "+f"(d[80]), "+f"(d[81]), "+f"(d[82]), "+f"(d[83]), "+f"(d[84]), "+f"(d[85]), "+f"(d[86]), "+f"(d[87]), "+f"(d[88]), "+f"(d[89]), "+f"(d[90]), "+f"(d[91]), "+f"(d[92]), "+f"(d[93]), "+f"(d[94]), "+f"(d[95])
      : "l"(da), "l"(db), "r"(keep));
}

template <int R>
__device__ __forceinline__ void pin_regs(float (&a)[2][96]) {
#pragma unroll
  for (int m = 0; m < 2; m++)
#pragma unroll
    for (int i = 0; i < R; i++) asm volatile("" : "+f"(a[m][i])::"memory");
}

struct Ctx {
  uint32_t sb;
  int m, n, wg, w, lane;
};
__device__ __forceinline__ Ctx make_ctx(uint32_t sb, int id) {
  int lane;
  asm volatile("mov.u32 %0, %%laneid;" : "=r"(lane));
  asm volatile("" : "+r"(id), "+r"(sb));
  return Ctx{sb, (id >> 3) & 15, id & 7, id >> 9, (id >> 7) & 3, lane};
}
#define UNPACK_CTX(c) const uint32_t sb = c.sb; const int m = c.m, n = c.n, wg = c.wg, w = c.w, lane = c.lane

__device__ __forceinline__ uint32_t poll_line(const uint32_t* word, uint32_t target, uint32_t need) {
  uint32_t v;
  asm volatile(
      "{\n.reg .pred p;\n.reg .u32 it, m;\n.reg .s32 d;\nmov.u32 it, 0;\n"
      "POLL_LOOP:\n"
      "ld.relaxed.gpu.global.u32 %0, [%1];\n"
      "sub.s32 d, %0, %2;\n"
      "setp.ge.s32 p, d, 0;\n"
      "vote.sync.ballot.b32 m, p, 0xffffffff;\n"
      "and.b32 m, m, %3;\n"
      "setp.eq.u32 p, m, %3;\n"
      "@p bra.uni POLL_DONE;\n"
      "add.u32 it, it, 1;\n"
      "setp.lt.u32 p, it, 0x400000;\n"
      "@p bra.uni POLL_LOOP;\n"
      "trap;\n"
      "POLL_DONE:\n}"
      : "=&r"(v) : "l"(word), "r"(target), "r"(need) : "memory");
  return v;
}
__device__ __forceinline__ uint32_t ld_relaxed(const uint32_t* p) {
  uint32_t v;
  asm volatile("ld.relaxed.gpu.global.u32 %0, [%1];" : "=r"(v) : "l"(p) : "memory");
  return v;
}
__device__ __forceinline__ float chain(float x, uint32_t on, uint32_t zero) {
  return __uint_as_float(__float_as_uint(x) | (on & zero));
}
constexpr int MSG_SPINS = 1 << 20;

constexpr int STAGES_PER_LAYER = 152;
__device__ __forceinline__ int nib(uint64_t v, int i) { return (int)(v >> (4 * i)) & 15; }
__device__ __forceinline__ bool tile_wide(int t) { return (0x23 >> t) & 1; }
__device__ __forceinline__ void weight_coords(const Params& p, int t, int n, const CUtensorMap*& map, int& c0, int& c2) {
  map = &p.wqkv + nib(0x4233100ull, t);
  c0 = t < 2 ? 128 * n + 64 * t : 0;
  c2 = t < 2 ? 0 : (t == 2 || t == 6) ? 2 * n : 7 * n + 2 * t - 6;
}

template <bool IS_A>
__device__ __forceinline__ void producer(const Params& p, uint32_t sb, int m, int n, int lane) {
  const uint32_t low = (1u << (4 * n)) - 1, others = (0x6543210u & low) | (0x7654321u & ~low);
  const uint64_t order_x = (uint64_t)(others * 2 + 0x1111111u) << 36 | (uint64_t)others * 2 << 8 | (n * 0x22 + 0x10);
  int inflight = 4, cur = 0;
  uint32_t fb = sb + BAR_FULL + 32, rb = sb + BAR_EMPTY, rph = 0, pos = 0, tag32 = 0, seen = 0;
  const uint32_t fend = sb + BAR_FULL + 8 * NBAR, rend = sb + BAR_EMPTY + 8 * NBAR;
  const uint32_t* word = p.g->flags + m * 32 + (lane < 16 ? lane >> 1 : lane & 7);
#pragma unroll 1
  for (int sg = 1; sg < 22; sg++) {
    const int layer = sg >= 11, s = sg == 1 ? 2 : sg == 2 ? 1 : sg - 11 * layer;
    const int t = nib(0x65434321010ull, s), kind = nib(0x32110031100ull, s);
    const bool wide = tile_wide(t);
    const uint32_t bbytes = wide ? 3 * UNIT : 2 * UNIT, base = sb + (IS_A ? bbytes : (m & 1) * (bbytes / 2));
    const int mul = t == 6 ? 448 : t == 2 ? 128 : 64, count = sg == 1 ? 12 : 2 * nib(0x4871ull, kind);
    uint64_t order0 = sg == 1 ? 0xFEDCBA987654ull : kind == 3 ? 0x76543210u : order_x >> (8 * (kind & 1));
    uint32_t special = (s == 4 || s == 10) ? 0x10 : s == 9 ? 0xF : 1;
    if (IS_A) special |= (kind & 1 ? 0 : 3) | (count >= 4 ? 1u << (count - 4) : 0);
    if (s >= 9) pos = (s + 6) * UNIT;
    const CUtensorMap* map;
    int c0 = 0, c2 = 0, ev = 0;
    if (IS_A) {
      map = &p.xin + (t == 2 ? 2 : t == 6 ? 3 : sg >= 4);
      ev = 9 * layer + (t < 2 ? 0 : t == 2 ? 1 : t < 6 ? 4 : 5);
      if (sg == 2) seen = tag32 = (__ldcg(p.g->epoch + m * 8 + n) + 1) << 5;
    } else {
      weight_coords(p, t, n, map, c0, c2);
    }
#pragma unroll 1
    for (int add = 0; add < mul; add += 64) {
      uint64_t order = order0;
      const int need = kind == 3 ? ev : ev - 1 + (lane & 1), sh = kind == 3 ? 16 : 0;
      uint32_t ready = IS_A ? __ballot_sync(0xffffffffu, cur >= need) >> sh : 0;
#pragma unroll 1
      for (int k = 0; k < count; k++) {
        const int code = order & 15, kc = code * mul + add;
        order >>= 4;
        if ((special >> k) & 1) {
          const int lag = wide ? (s == 9 && k == 2 ? 2 : 3) : ((s == 4 || s == 10) && add == 0 && k < 4) ? 3 : 4;
#pragma unroll 1
          for (; inflight > lag; inflight--) {
            mbar_wait(rb, rph);
            rb += 8;
            if (rb == rend) { rb -= 8 * NBAR; rph ^= 1; }
          }
          inflight++;
          if (IS_A) {
            if (kind == 3 ? t == 2 && add + k == 64 : !(kind & 1) && k < 2) {
              if (t == 2) mbar_wait(sb + BAR_PUB + 8, layer);
              else if (k == 1 && (s == 0 || s == 5)) mbar_wait(sb + BAR_XRDY + 8, s == 5);
              if (elect_one()) mbar_arrive(fb);
              goto next_stage;
            }
            if (k == count - 4 && sg >= 3) seen = ld_relaxed(word);
          }
        } else {
          mbar_wait(rb, rph);
          rb += 8;
          if (rb == rend) { rb -= 8 * NBAR; rph ^= 1; }
        }
        if (IS_A && !((ready >> code) & 1)) {
          cur = max(cur, (int)(seen - tag32));
          ready = __ballot_sync(0xffffffffu, cur >= need) >> sh;
          if (!((ready >> code) & 1)) {
            cur = (int)(poll_line(word, tag32 + need, 1u << (code + sh)) - tag32);
            ready = __ballot_sync(0xffffffffu, cur >= need) >> sh;
          }
          asm volatile("fence.acquire.gpu;" ::: "memory");
          fence_async_global();
        }
        if (elect_one()) {
          if (!IS_A) tma_ld3_pair(base + pos, map, fb, c0, kc + 32 * (m & 1), c2);
          else tma_ld2(base + pos, map, fb, kc, 128 * m);
          mbar_expect_tx(fb, IS_A ? 16384 : bbytes);
        }
      next_stage:
        fb += 8;
        if (fb == fend) fb -= 8 * NBAR;
        pos += bbytes + 2 * UNIT;
        if (pos >= RING_UNITS * UNIT) pos -= RING_UNITS * UNIT;
      }
      special = !IS_A ? 0 : t == 2 ? 1 : add == 128 ? 0x10 : 0;
      if (t == 2) order0 = others << 4 | n;
      if (IS_A && (t == 2 || add == 64 || add == 192)) ev++;
    }
  }
}

__device__ __forceinline__ void publisher(const Params& p, uint32_t sb, int m, int n) {
  const uint32_t tag = __ldcg(p.g->epoch + m * 8 + n) + 1;
  uint32_t* word = p.g->flags + m * 32 + n;
  const int mn = m * 8 + n; (void)mn;
  st_relaxed(word, 32 * tag);
#pragma unroll 1
  for (int c = 0; c < 18; c++) {
    const int e = c >= 9 ? c - 9 : c;
    if ((0x18C >> e) & 1) {
      const int half = (0x108 >> e) & 1;
      mbar_wait(sb + BAR_XRDY + 8 * half, e < 4);
#pragma unroll
      for (int w = 0; w < 4; w++) tma_st2(&p.out_st, sb + OFF_X + half * 16384 + w * 4096, 128 * n + 64 * half, 128 * m + 32 * w);
      bulk_commit();
      if (c >= 16) continue;
      bulk_wait_all();
      PROF_E(7 * (c >= 9) + (e < 4 ? 2 : 6), 11 + 2 * half);
    } else {
      mbar_wait(sb + BAR_PUB + 8 * e, c >= 9);
    }
    asm volatile("fence.release.gpu;" ::: "memory");
    asm volatile("red.relaxed.gpu.global.add.u32 [%0], 1;" ::"l"(word) : "memory");
    PROF_E(7 * (c >= 9) + nib(0x665432210ull, e), (0x108 >> e) & 1 ? 14 : 12);
  }
  p.g->epoch[m * 8 + n] = tag;
  bulk_wait_read();
}

__device__ __forceinline__ void sum_rows(uint32_t buf, int iters, float (&a)[8], int lane) {
  uint32_t addr = buf + (lane >> 3) * 128 + (((lane & 7) ^ (lane >> 3)) << 4);
#pragma unroll 1
  for (int it = 0; it < iters; it++) {
    uint32_t u[2][4];
    lds_u4(addr, u[0][0], u[0][1], u[0][2], u[0][3]);
    lds_u4((addr ^ 64) + 512, u[1][0], u[1][1], u[1][2], u[1][3]);
    addr += 1024;
#pragma unroll
    for (int e = 0; e < 8; e++) { a[2 * (e & 3)] += bf_lo(u[e >> 2][e & 3]); a[2 * (e & 3) + 1] += bf_hi(u[e >> 2][e & 3]); }
  }
}
__device__ __forceinline__ void publish_sums(const float (&a)[8], uint4* dst, int lane, uint32_t tag) {
  const bool u8 = lane & 8, u16 = lane & 16;
  float h4[4], h2[2];
#pragma unroll
  for (int e = 0; e < 4; e++) h4[e] = (u8 ? a[4 + e] : a[e]) + __shfl_xor_sync(0xffffffffu, u8 ? a[e] : a[4 + e], 8);
#pragma unroll
  for (int e = 0; e < 2; e++) h2[e] = (u16 ? h4[2 + e] : h4[e]) + __shfl_xor_sync(0xffffffffu, u16 ? h4[e] : h4[2 + e], 16);
  st_msg(dst + (lane & 7) * 4 + (u8 ? 2 : 0) + (u16 ? 1 : 0), __float_as_uint(h2[0]), __float_as_uint(h2[1]), 0u, tag);
}

__device__ __forceinline__ void colsum_helper(const Params& p, uint32_t sb, int m, int n, int lane) {
  const uint32_t tag = __ldcg(p.g->epoch + m * 8 + n) + 1;
  const int mn = m * 8 + n; (void)mn;
#pragma unroll 1
  for (int k = lane; k < 288; k += 32) {
    const uint32_t bb = __ldg(reinterpret_cast<const uint32_t*>(k < 224 ? p.b1 + 448 * n : p.b2 + 128 * n - 448) + k);
    const float sc = k < 224 ? 0.5f : 1.f;
    sts_f2(sb + (k < 224 ? OFF_CSF + k * 16 + 8 : OFF_CSQ + 1536 + (k - 224) * 8), sc * bf_lo(bb), sc * bf_hi(bb));
  }
  __syncwarp();
  if (elect_one()) mbar_arrive(sb + BAR_BIAS);
  bar_sync(BAR_HLP, 160);
  PROF_E(-1, 1);
#pragma unroll 1
  for (int c = 0; c < 7; c++) {
    float a[8] = {0.f, 0.f, 0.f, 0.f, 0.f, 0.f, 0.f, 0.f};
#pragma unroll 1
    for (int h = 0; h < 2; h++) {
      if (elect_one()) {
        mbar_expect_tx(sb + BAR_CSLD + 8, 4096);
        tma_ld2(sb + OFF_HLP, &p.w1c, sb + BAR_CSLD + 8, 448 * n + 64 * c, 64 * m + 32 * h);
        if (c < 6) asm volatile("cp.async.bulk.prefetch.tensor.2d.L2.global [%0, {%1, %2}];" ::"l"(&p.w1c), "r"(448 * n + 64 * c + 64), "r"(64 * m + 32 * h) : "memory");
      }
      mbar_wait(sb + BAR_CSLD + 8, h);
      sum_rows(sb + OFF_HLP, 4, a, lane);
      __syncwarp();
    }
    publish_sums(a, p.g->csp + ((8 + n) * 17 + m) * 224 + c * 32, lane, tag);
  }
  PROF_E(-1, 2);
}

__device__ __forceinline__ void poll_msgs2(const uint4* pa, const uint4* pb, float (&v)[4], uint32_t tag) {
#pragma unroll 1
  for (int it = 0; it < MSG_SPINS; it++) {
    uint32_t x[4], z, ta, tb;
    ld_msg(pa, x[0], x[1], z, ta);
    ld_msg(pb, x[2], x[3], z, tb);
#pragma unroll
    for (int e = 0; e < 4; e++) v[e] = __uint_as_float(x[e]);
    if (__all_sync(0xffffffffu, ta == tag && tb == tag)) break;
  }
}
__device__ __forceinline__ void colsum_total(const Params& p, const Ctx& cx, int mat, uint32_t tag) {
  uint4* base = p.g->csp + (mat * 8 + cx.n) * 17 * 224;
  const int per = 12 + 2 * mat, k = 2 * cx.w + (cx.lane >> 4), ia = per * cx.m + k, ib = per * cx.m + min(k + 8, per - 1);
  float v[4];
  poll_msgs2(base + (cx.lane & 15) * 224 + ia, base + (cx.lane & 15) * 224 + ib, v, tag);
#pragma unroll 1
  for (int d = 1; d < 16; d *= 2)
#pragma unroll
    for (int e = 0; e < 4; e++) v[e] += __shfl_xor_sync(0xffffffffu, v[e], d);
  const bool hi = cx.lane & 1;
  if ((cx.lane & 14) == 0) st_msg(base + 16 * 224 + (hi ? ib : ia), __float_as_uint(hi ? v[2] : v[0]), __float_as_uint(hi ? v[3] : v[1]), 0u, tag);
}
__device__ __forceinline__ void colsum_gather(const Params& p, const Ctx& cx, int mat, uint32_t tag) {
  const uint4* base = p.g->csp + ((mat * 8 + cx.n) * 17 + 16) * 224;
  const int ia = cx.w * 32 + cx.lane, ib = min(ia + 128, 191 + 32 * mat);
  float v[4];
  poll_msgs2(base + ia, base + ib, v, tag);
  const uint32_t tab = cx.sb + (mat ? OFF_CSF : OFF_CSQ);
  sts_f2(tab + (ia << (3 + mat)), v[0], v[1]);
  sts_f2(tab + (ib << (3 + mat)), v[2], v[3]);
}

#define ACC(q, j, e) acc[(q) & 1][4 * (j) + 2 * ((q) >> 1) + (e)]

constexpr uint32_t RING16 = RING_UNITS * (UNIT >> 4);
__device__ __forceinline__ bool tile_split(int i) { return (0xD98 >> i) & 1; }

__device__ __forceinline__ void write_run_desc(uint32_t sb, int i, int step) {
  const int layer = i >= 7, t = i - 7 * layer, part = tile_split(i) ? step : 2;
  const bool wide = tile_wide(t), own = t != 2 && t != 6 && part != 1 && i != 0, second = t == 1 || t == 4;
  const uint32_t z16 = (wide ? 5 : 4) * (UNIT >> 4), a_off = z16 - 1024 + (uint32_t)DESC_A - (uint32_t)DESC_B;
  const int gl = 16 * t + (part == 2 ? 0 : second ? 16 * part - 14 : 4 * part), g0 = layer * STAGES_PER_LAYER + gl;
  const uint32_t s16 = (sb & 0x3FFFF) >> 4, bfirst = (uint32_t)DESC_B + s16;
  const int nkb = t == 6 ? 56 : part == 0 ? 2 : 12 + 2 * part;
  const bool win1 = t == 1 && part != 0;
  const int run = win1 ? WIN1 + 1 : t == 2 ? WIN2 + 1 : nkb;
  const int rest = win1 ? 64 | (nkb - 1 - WIN1) : t == 2 ? 64 | (7 - WIN2) | (8 << 7) : 0;
  const uint32_t blo = bfirst + z16 * (wide ? (gl + (t == 5 ? 3 : 0)) & 3 : (gl + 3) % 5);
  const uint32_t alo = own ? (uint32_t)DESC_A + s16 + (OFF_X >> 4) : blo + a_off;
  const uint32_t aoff = own ? alo + 1024 - (blo == bfirst + RING16 - z16 ? bfirst : blo + z16) : a_off;
  const bool xwait = part == 0 && !second, keep = !(part == 0 || t == 5);
  sts_u4(sb + OFF_RUN + (2 * i + step) * 16, blo, alo, aoff,
         ((g0 / NBAR) & 1) | xwait << 1 | keep << 2 | 8 * (g0 % NBAR) | run << 6 | rest << 12);
}

template <int N>
__device__ __forceinline__ void mainloop(const Params& p, float (&acc)[2][96], uint32_t sb, int i, int step, int mn) {
  constexpr uint32_t Z16 = (2 + N / 64) * (UNIT >> 4);
  constexpr uint32_t A_OFF = Z16 - 1024 + (uint32_t)DESC_A - (uint32_t)DESC_B;
  const int wg = i & 1;
  const uint32_t s16 = (sb & 0x3FFFF) >> 4;
  const uint32_t blast = (uint32_t)DESC_B + s16 + RING16 - Z16, flast = sb + BAR_FULL + 8 * (NBAR - 1);
  uint32_t blo = (uint32_t)DESC_B + s16, alo = blo + A_OFF, aoff = A_OFF, misc = 16 << 6;
  if (N == 128 || i > 0) lds_u4(sb + OFF_RUN + (2 * i + step) * 16, blo, alo, aoff, misc);
  uint32_t keep = misc & 4;
  int run = (misc >> 6) & 63, rest = misc >> 12;
  uint32_t fb = sb + BAR_FULL + (misc & 0x38), ph = misc & 1;
  uint32_t prev = sb + BAR_DUMMY - 8 * NBAR;
  const uint32_t lane_id = (threadIdx.x & 31) | p.zero, rel = pair_offset(sb, lane_id & 1) + 8 * NBAR;
  pin_regs<N / 2>(acc);
  if (N == 128 || i > 0) bar_sync(BAR_ORDER + wg, 256);
  else cluster_wait();
  if (N == 192 && i == 0 && threadIdx.x == 0) PROF_U(8);
  mbar_wait(fb, ph);
  if (misc & 2) mbar_wait(sb + BAR_XRDY, N == 128);
  if (step == 0 || !tile_split(i)) PROF_T(4 + i * 4);
#pragma unroll 1
  while (true) {
    const uint64_t da = (DESC_A & ~0xffffffffull) | alo, db = (DESC_B & ~0xffffffffull) | blo;
    asm volatile("wgmma.fence.sync.aligned;" ::: "memory");
    wgmma_ss<N>(acc[0], da, db, keep);
    wgmma_ss<N>(acc[1], da + 64, db, keep);
    keep = 4;
    wgmma_ss<N>(acc[0], da + 2, db + 128);
    wgmma_ss<N>(acc[1], da + 66, db + 128);
    asm volatile("wgmma.commit_group.sync.aligned;" ::: "memory");
    asm volatile("wgmma.wait_group.sync.aligned 1;" ::: "memory");
    PROF_S(jj++);
    if (lane_id < 2) mbar_arrive_cluster(prev + rel);
    prev = fb;
    if (fb == flast) { fb -= 8 * NBAR; ph++; }
    fb += 8;
    if (blo == blast) blo -= RING16;
    blo += Z16;
    alo = blo + aoff;
    aoff = A_OFF;
    run--;
    const bool ready = mbar_test(fb, ph) && run != 0;
    asm volatile("wgmma.fence.sync.aligned;" ::: "memory");
    wgmma_ss<N>(acc[0], da + 4, db + 4 * N);
    wgmma_ss<N>(acc[1], da + 68, db + 4 * N);
    wgmma_ss<N>(acc[0], da + 6, db + 4 * N + 128);
    wgmma_ss<N>(acc[1], da + 70, db + 4 * N + 128);
    asm volatile("wgmma.commit_group.sync.aligned;" ::: "memory");
    if (!ready) {
      if (run == 0) {
        if (rest == 0) break;
        if (rest & 64) {
          bar_arrive(BAR_GO, 256);
          bar_sync(BAR_DONE, 256);
        } else {
          alo = (uint32_t)DESC_A + s16 + (OFF_STG >> 4);
        }
        run = rest & 63;
        rest >>= 7;
      }
      mbar_wait(fb, ph);
    }
  }
  if (i < 13 && !(LATE_O && N == 192 && (misc >> 12))) bar_arrive(BAR_ORDER + (wg ^ 1), 256);
  if (N == 128 && ((0x2244 >> i) & 1)) {
    const Ctx cx = make_ctx(sb, mn);
    const uint32_t xrow = cx.sb + OFF_X + cx.w * 4096 + cx.lane * 128 + ((cx.lane & 7) << 4);
    const bool leader = elect_one();
    asm volatile("wgmma.wait_group.sync.aligned 0;" ::: "memory");
    pin_regs<64>(acc);
    PROF_T(5 + i * 4);
    PROF_E(i, 0);
#pragma unroll
    for (int h = 0; h < 2; h++) {
      if (h == 1 && p.zero != 0) break;
#pragma unroll
      for (int j = 8 * h; j < 8 * h + 8; j++)
        stsm4((xrow ^ ((j & 7) << 4)) + h * 16384, pack_bf16(ACC(0, j, 0), ACC(0, j, 1)), pack_bf16(ACC(1, j, 0), ACC(1, j, 1)),
              pack_bf16(ACC(2, j, 0), ACC(2, j, 1)), pack_bf16(ACC(3, j, 0), ACC(3, j, 1)));
      fence_async_smem();
      __syncwarp();
      if (leader) mbar_arrive(sb + BAR_XRDY + 8 * h);
      if (h == 0 && lane_id < 2) mbar_arrive_cluster(prev + rel);
    }
    PROF_E(i, 4);
    return;
  }
  asm volatile("wgmma.wait_group.sync.aligned 0;" ::: "memory");
  pin_regs<N / 2>(acc);
  if (lane_id < 2) mbar_arrive_cluster(prev + rel);
  PROF_T(5 + i * 4);
  PROF_E(i, 0);
}

__device__ __forceinline__ void write_partial_stats(const Params& p, const Ctx& c, int ln, uint32_t tag) {
  const uint32_t xrow = c.sb + OFF_X + c.w * 4096 + c.lane * 128;
  float s = 0.f, q = 0.f, s1 = 0.f, q1 = 0.f;
#pragma unroll 4
  for (int j = 0; j < 16; j++) {
    uint32_t u[4];
    lds_u4(xrow + (j >> 3) * 16384 + (((j & 7) ^ (c.lane & 7)) << 4), u[0], u[1], u[2], u[3]);
#pragma unroll
    for (int e = 0; e < 4; e++) {
      const float a = bf_lo(u[e]), d = bf_hi(u[e]);
      s += a; q = fmaf(a, a, q);
      s1 += d; q1 = fmaf(d, d, q1);
    }
  }
  s += s1;
  q += q1;
  st_msg(p.g->stats + (ln * 8 + c.n) * SEQ + 128 * c.m + 32 * c.w + c.lane, __float_as_uint(s),
         __float_as_uint(fmaxf(q - s * s * (1.f / 128.f), 0.f)), 0u, tag);
}

__device__ __forceinline__ void finish_row_stats(const Params& p, const Ctx& c, int ln, uint32_t tag) {
  const uint4* src = p.g->stats + ln * 8 * SEQ + 128 * c.m + 32 * c.w + c.lane;
  uint32_t ps[8], pm[8];
#pragma unroll 1
  for (int it = 0; it < MSG_SPINS; it++) {
    uint32_t bad = 0, u, tg;
#pragma unroll
    for (int k = 0; k < 8; k++) { ld_msg(src + k * SEQ, ps[k], pm[k], u, tg); bad |= tg ^ tag; }
    if (__all_sync(0xffffffffu, bad == 0)) break;
  }
  float s = 0.f, m2 = 0.f;
#pragma unroll
  for (int k = 0; k < 8; k++) s += __uint_as_float(ps[k]);
  const float mean = s * (1.f / DM);
#pragma unroll
  for (int k = 0; k < 8; k++) {
    const float d = __uint_as_float(ps[k]) * (1.f / 128.f) - mean;
    m2 += fmaf(128.f * d, d, __uint_as_float(pm[k]));
  }
  sts_f2(c.sb + OFF_ROW + (32 * c.w + c.lane) * 8, rsqrtf(m2 * (1.f / DM) + 1e-5f), mean);
  __syncwarp();
}

__device__ __forceinline__ void attn_scores(const uint32_t* qa, const uint32_t* qb, const uint32_t* k0, const uint32_t* k1,
                                            const uint32_t* k2, const uint32_t* k3, float (&l)[4], const float4& zero,
                                            bool par, bool early) {
  float s[4][4];
#pragma unroll
  for (int kb = 0; kb < 4; kb++) {
    const uint32_t* kk = kb == 0 ? k0 : kb == 1 ? k1 : kb == 2 ? k2 : k3;
    asm volatile("mma.sync.aligned.m16n8k16.row.col.f32.bf16.bf16.f32 {%0,%1,%2,%3}, {%4,%5,%6,%7}, {%8,%9}, {%10,%11,%12,%13};"
                 : "=f"(s[kb][0]), "=f"(s[kb][1]), "=f"(s[kb][2]), "=f"(s[kb][3])
                 : "r"(qa[0]), "r"(qb[0]), "r"(qa[1]), "r"(qb[1]), "r"(kk[0]), "r"(kk[1]), "f"(zero.x), "f"(zero.y),
                   "f"(zero.z), "f"(zero.w));
  }
#pragma unroll
  for (int kb = 0; kb < 4; kb++) {
    const uint32_t* kk = kb == 0 ? k0 : kb == 1 ? k1 : kb == 2 ? k2 : k3;
    mma16816(s[kb], qa[2], qb[2], qa[3], qb[3], kk[2], kk[3]);
  }
  l[0] = par ? s[1][1] : s[1][0];
  l[1] = early ? (par ? s[0][1] : s[0][0]) : (par ? s[2][1] : s[2][0]);
  l[2] = par ? s[2][3] : s[2][2];
  l[3] = early ? (par ? s[1][3] : s[1][2]) : (par ? s[3][3] : s[3][2]);
}

__device__ __forceinline__ void attn_mix(const float (&l)[4], const float (&sc)[4], const float (&off)[4], const float (&rk)[4],
                                         const uint32_t* v0, const uint32_t* v1, const uint32_t* v2, const uint32_t* v3,
                                         uint32_t* olo, uint32_t* ohi, const uint32_t (&sel)[4]) {
  float x[4];
#pragma unroll
  for (int e = 0; e < 4; e++) x[e] = fmaf(l[e], sc[e], off[e]);
  const float ml = quad_max(fmaxf(x[0], x[1])), mh = quad_max(fmaxf(x[2], x[3]));
  x[0] = ex2(x[0] - ml); x[1] = ex2(x[1] - ml);
  x[2] = ex2(x[2] - mh); x[3] = ex2(x[3] - mh);
  const uint32_t pl = pack_bf16(x[0] * rk[0], x[1] * rk[1]), ph = pack_bf16(x[2] * rk[2], x[3] * rk[3]);
  const uint32_t a0 = prmt_u(pl, sel[1]), a1 = prmt_u(pl, sel[3]), a2 = prmt_u(pl, sel[0]), a3 = prmt_u(ph, sel[1]);
  const uint32_t c0 = prmt_u(pl, sel[2]), c1 = prmt_u(ph, sel[0]), c2 = prmt_u(ph, sel[3]), c3 = prmt_u(ph, sel[2]);
  float o[4][4];
#pragma unroll
  for (int jn = 0; jn < 4; jn++) {
    o[jn][0] = o[jn][1] = o[jn][2] = o[jn][3] = 0.f;
    mma16816(o[jn], a0, a1, a2, a3, v0[jn], v1[jn]);
  }
#pragma unroll
  for (int jn = 0; jn < 4; jn++) mma16816(o[jn], c0, c1, c2, c3, v2[jn], v3[jn]);
  const float il = rcp_hw(quad_sum(x[0] + x[1])), ih = rcp_hw(quad_sum(x[2] + x[3]));
#pragma unroll
  for (int jn = 0; jn < 4; jn++) {
    olo[jn] = pack_bf16(o[jn][0] * il, o[jn][1] * il);
    ohi[jn] = pack_bf16(o[jn][2] * ih, o[jn][3] * ih);
  }
}

__device__ __forceinline__ void gelu_epilogue(const Params& p, float (&acc)[2][96], const Ctx& cx, int t) {
  UNPACK_CTX(cx);
  (void)wg;
  float rs[4], rm[4];
#pragma unroll
  for (int q = 0; q < 4; q++) {
    const float2 v = lds_f2(sb + OFF_ROW + (32 * w + 8 * q + (lane >> 2)) * 8);
    rs[q] = 0.5f * v.x;
    rm[q] = -rs[q] * v.y;
  }
  const int col0 = 128 * (t - 3);
  const uint32_t stg = sb + OFF_STG + w * 4096;
  const uint32_t ctab = sb + OFF_CSF + (col0 / 2 + (lane & 3)) * 16, srow = stg + lane * 128 + ((lane & 7) << 4);
  float4 nb = lds_f4(ctab);
#pragma unroll
  for (int c = 0; c < 3; c++) {
    if (c == 2 && t != 5) break;
    uint32_t hp[8][4];
#pragma unroll
    for (int j = 0; j < 8; j++) {
      const float4 cb = nb;
      if (8 * c + j < 23) nb = lds_f4(ctab + (8 * c + j + 1) * 64);
#pragma unroll
      for (int q = 0; q < 4; q++) {
        float y[2];
        const int k = 4 * j + q - GELU_DEP;
        const float rmq = k >= 0 ? chain(rm[q], hp[k >> 2][k & 3], p.zero) : rm[q];
#pragma unroll
        for (int e = 0; e < 2; e++) {
          const float z = fmaf(ACC(q, 8 * c + j, e), rs[q], fmaf(rmq, e ? cb.y : cb.x, e ? cb.w : cb.z));
          const float u = z * fmaf(z * z, 8.f * 0.7978845608028654f * 0.044715f, 2.f * 0.7978845608028654f);
          y[e] = fmaf(z, tanh_hw(u), z);
        }
        hp[j][q] = pack_bf16(y[0], y[1]);
      }
      if (j == STG_WAIT && c > 0) {
        if (lane == 0) bulk_wait_read();
        __syncwarp();
      }
      if (c == 0 || j > STG_WAIT) {
        stsm4(srow ^ (j << 4), hp[j][0], hp[j][1], hp[j][2], hp[j][3]);
      } else if (j == STG_WAIT) {
#pragma unroll
        for (int jj = 0; jj <= STG_WAIT; jj++) stsm4(srow ^ (jj << 4), hp[jj][0], hp[jj][1], hp[jj][2], hp[jj][3]);
      }
    }
    fence_async_smem();
    __syncwarp();
    if (lane == 0) {
      tma_st2(&p.h_st, stg, 448 * n + col0 + 64 * c, 128 * m + 32 * w);
      bulk_commit();
    }
  }
#pragma unroll
  for (int r = 0; r < 16; r++) acc[0][r] = acc[1][r] = 0.f;
}

__device__ __forceinline__ void attn_epilogue(const Params& p, float (&acc)[2][96], const Ctx& cx, int layer, int t, uint32_t tag) {
  UNPACK_CTX(cx);
  const bool par = (lane >> 2) & 1, early = (lane & 3) > (lane >> 3);
  const uint32_t ktab = sb + OFF_ROW + (32 * w + 2 * (lane & 3) + par) * 8, exc = sb + OFF_STG + w * 4096 + lane * 16;
  const int slot = ((layer * 2 + t) * 16 + m) * 8 + n;
  const int mn = m * 8 + n; (void)mn;
  uint32_t Q[4][8], K[4][8], V[4][8], E[36], P[36];
  float kr[6], qr[4];
#pragma unroll
  for (int q = 2; q < 4; q++) {
    kr[2 + q] = lds_f(ktab + 64 * q);
#pragma unroll
    for (int j = 0; j < 8; j++) {
      E[8 * (q - 2) + j] = K[q][j] = pack_bf16(ACC(q, 8 + j, 0), ACC(q, 8 + j, 1));
      E[16 + 2 * j + q - 2] = V[q][j] = movtrans(pack_bf16(ACC(q, 16 + j, 0), ACC(q, 16 + j, 1)));
    }
  }
#pragma unroll
  for (int j = 0; j < 16; j++) K[j >> 3][j & 7] = pack_bf16(ACC(j >> 3, 8 + (j & 7), 0), ACC(j >> 3, 8 + (j & 7), 1));
#pragma unroll
  for (int j = 0; j < 16; j++) asm volatile("" : "+r"(K[j >> 3][j & 7]));
  E[32] = __float_as_uint(kr[4]);
  E[33] = E[34] = E[35] = __float_as_uint(kr[5]);
  if (w < 3) {
#pragma unroll
    for (int k = 0; k < 8; k++) sts_u4(exc + k * 512, E[4 * k], E[4 * k + 1], E[4 * k + 2], E[4 * k + 3]);
  } else {
#pragma unroll
    for (int k = 0; k < 12; k++) st_msg(p.g->halo + slot * 384 + k * 32 + lane, E[3 * k], E[3 * k + 1], E[3 * k + 2], tag);
  }
  bar_arrive(BAR_PAIR + w, 64);
  if (LATE_O && t == 1) bar_arrive(BAR_ORDER + (wg ^ 1), 256);
  PROF_E(7 * layer + t, 1);
#pragma unroll
  for (int q = 0; q < 4; q++) {
    qr[q] = lds_f(sb + OFF_ROW + (32 * w + 8 * q + (lane >> 2)) * 8) * (0.17677669529663687f * 1.4426950408889634f);
#pragma unroll
    for (int j = 0; j < 8; j++) Q[q][j] = pack_bf16(ACC(q, j, 0), ACC(q, j, 1));
    if (q < 2) {
      kr[2 + q] = lds_f(ktab + 64 * q);
#pragma unroll
      for (int j = 0; j < 8; j++) V[q][j] = movtrans(pack_bf16(ACC(q, 16 + j, 0), ACC(q, 16 + j, 1)));
    }
  }
  PROF_E(7 * layer + t, 6);
  bar_sync(BAR_PAIR + ((w + 3) & 3), 64);
  if (w > 0 || m == 0) {
    const uint32_t back = w > 0;
#pragma unroll
    for (int k = 0; k < 8; k++) lds_u4(exc - back * 4096 + k * 512, P[4 * k], P[4 * k + 1], P[4 * k + 2], P[4 * k + 3]);
    P[32] = lds_u(ktab - back * 128);
    P[33] = lds_u(ktab - back * 64);
  } else {
    if (HALO_NS) __nanosleep(HALO_NS);
#pragma unroll 1
    for (int it = 0; it < MSG_SPINS; it++) {
      uint32_t tg, bad = 0;
      if (it > 0) poll_line(reinterpret_cast<const uint32_t*>(p.g->halo + (slot - 8) * 384 + 383) + 3, tag, 1u);
#pragma unroll
      for (int k = 0; k < 12; k++) {
        ld_msg(p.g->halo + (slot - 8) * 384 + k * 32 + lane, P[3 * k], P[3 * k + 1], P[3 * k + 2], tg);
        bad |= tg ^ tag;
      }
      if (__all_sync(0xffffffffu, bad == 0)) break;
    }
  }
  kr[0] = __uint_as_float(P[32]);
  kr[1] = __uint_as_float(P[33]);
  uint32_t PV[2][8];
#pragma unroll
  for (int j = 0; j < 8; j++) { PV[0][j] = P[16 + 2 * j]; PV[1][j] = P[17 + 2 * j]; }
  float rk[2][4], sc[2][4], off[2][4];
#pragma unroll
  for (int g = 0; g < 2; g++) {
    rk[g][0] = kr[2 * g + 1];
    rk[g][1] = early ? kr[2 * g] : kr[2 * g + 2];
    rk[g][2] = kr[2 * g + 2];
    rk[g][3] = early ? kr[2 * g + 1] : kr[2 * g + 3];
#pragma unroll
    for (int e = 0; e < 4; e++) {
      const bool masked = g == 0 && e != 2 && (m | w) == 0 && (e == 0 || early);
      sc[g][e] = masked ? 0.f : rk[g][e] * qr[2 * g + (e >> 1)];
      off[g][e] = masked ? -1e30f : 0.f;
    }
  }
  const uint32_t none = 0x4444u | p.zero, second = par ? 0x3244u : 0x4432u;
  const uint32_t sel[4] = {par ? 0x1044u : 0x4410u, early ? second : none, early ? none : second, none};
  PROF_E(7 * layer + t, 2);
  bar_sync(BAR_GO, 256);
  const float4 zero = lds_f4(sb + OFF_ZERO);
  float l[2][2][4];
  uint32_t O[4][8];
#pragma unroll
  for (int h = 0; h < 2; h++) {
    if (h == 1) {
      Q[2][4] |= __float_as_uint(l[1][0][0]) & p.zero;
      Q[0][4] |= __float_as_uint(l[0][0][0]) & p.zero;
    }
    attn_scores(&Q[2][4 * h], &Q[3][4 * h], &K[0][4 * h], &K[1][4 * h], &K[2][4 * h], &K[3][4 * h], l[1][h], zero, par, early);
    attn_scores(&Q[0][4 * h], &Q[1][4 * h], &P[4 * h], &P[8 + 4 * h], &K[0][4 * h], &K[1][4 * h], l[0][h], zero, par, early);
  }
  const uint32_t stg = sb + OFF_STG + w * 4096, srow = stg + lane * 128 + ((lane & 7) << 4);
#pragma unroll
  for (int h = 0; h < 2; h++) {
    attn_mix(l[1][h], sc[1], off[1], rk[1], &V[0][4 * h], &V[1][4 * h], &V[2][4 * h], &V[3][4 * h], &O[2][4 * h], &O[3][4 * h], sel);
    attn_mix(l[0][h], sc[0], off[0], rk[0], &PV[0][4 * h], &PV[1][4 * h], &V[0][4 * h], &V[1][4 * h], &O[0][4 * h], &O[1][4 * h], sel);
#pragma unroll
    for (int j = 4 * h; j < 4 * h + 4; j++) stsm4(srow ^ (j << 4), O[0][j], O[1][j], O[2][j], O[3][j]);
  }
  bar_arrive(BAR_DONE, 256);
  fence_async_smem();
  __syncwarp();
  if (lane == 0) {
    tma_st2(&p.att_st, stg, 128 * n + 64 * t, 128 * m + 32 * w);
    bulk_commit();
  }
}

template <bool PACED>
__device__ __forceinline__ void rank1_update(const Params& p, float (&acc)[2][96], const Ctx& cx, int t) {
  float nm[4];
#pragma unroll
  for (int q = 0; q < 4; q++) nm[q] = t == 6 ? 1.f : -lds_f(cx.sb + OFF_ROW + (32 * cx.w + 8 * q + (cx.lane >> 2)) * 8 + 4);
  const uint32_t ctab = cx.sb + OFF_CSQ + ((t & 3) * 192 + 2 * (cx.lane & 3)) * 4;
#pragma unroll
  for (int j = 0; j < 24; j++) {
    const float2 cs = lds_f2(ctab + j * 32);
#pragma unroll
    for (int q = 0; q < 4; q++) {
      const int k = 4 * j + q - 1;
      const float nq = PACED && k >= 0 ? chain(nm[q], __float_as_uint(ACC(k & 3, k >> 2, 1)), p.zero) : nm[q];
      ACC(q, j, 0) = fmaf(nq, cs.x, ACC(q, j, 0));
      ACC(q, j, 1) = fmaf(nq, cs.y, ACC(q, j, 1));
    }
  }
}

__device__ __forceinline__ void finish_stores(uint32_t sb, int i) {
  const int t = i >= 7 ? i - 7 : i;
  if ((threadIdx.x & 31) == 0) {
    bulk_wait_all();
    mbar_arrive(sb + BAR_PUB + 8 * (t < 2 ? t : t + 1));
  }
  __syncwarp();
  if (i < 12) bar_arrive(BAR_GUARD + ((i & 1) ^ 1), 256);
}

__device__ __forceinline__ bool consumer_tile(const Params& p, float (&acc)[2][96], uint32_t sb0, int i, int mn) {
  const int layer = i >= 7, t = i - 7 * layer, wg = i & 1;
  const bool resid = t == 2 || t == 6;
  {
    if (resid) {
      const Ctx cx = make_ctx(sb0, mn);
      const uint32_t xrow = cx.sb + OFF_X + cx.w * 4096 + cx.lane * 128;
      const uint32_t sel_lo = 0x1044u | p.zero, sel_hi = 0x3244u | p.zero;
#pragma unroll
      for (int j = 0; j < 16; j++) {
        uint32_t r[4];
        ldsm4(xrow + (j >> 3) * 16384 + (((j & 7) ^ (cx.lane & 7)) << 4), r[0], r[1], r[2], r[3]);
#pragma unroll
        for (int q = 0; q < 4; q++) {
          ACC(q, j, 0) = prmt_f(r[q], sel_lo);
          ACC(q, j, 1) = prmt_f(r[q], sel_hi);
        }
      }
    }
    if (t >= 5 || i == 7) finish_stores(sb0, i - 2);
#pragma unroll 1
    for (int step = !tile_split(i);; step++) {
      if (step == 1 && (t == 1 || t == 4)) {
        const Ctx cx = make_ctx(sb0, mn);
        if (i == 1) {
          const uint32_t epoch = __ldcg(p.g->epoch + (mn & 127));
          cluster_wait();
          asm volatile("st.shared.u32 [%0], %1;" ::"r"(sb0 + OFF_TAG), "r"(epoch + 1) : "memory");
        }
        const uint32_t tag = lds_u(cx.sb + OFF_TAG);
        const int ln = (i + 1) >> 2;
#pragma unroll 1
        for (int r = 0; r < 2; r++) {
          if (i == 1) {
            if (cx.w < 3) {
              float a[8] = {0.f, 0.f, 0.f, 0.f, 0.f, 0.f, 0.f, 0.f};
              mbar_wait(sb0 + BAR_CSLD, r);
#pragma unroll 1
              for (int h = 0; h < 2; h++) sum_rows(cx.sb + OFF_STG + h * 12288 + cx.w * 4096, 4, a, cx.lane);
              publish_sums(a, p.g->csp + (cx.n * 17 + cx.m) * 224 + (3 * r + cx.w) * 32, cx.lane, tag);
            }
            PROF_E(-1, 5 + r);
          }
          if (r == 1) break;
          if (i == 1) {
            bar_sync(BAR_WG + 1, 128);
            if (cx.w == 3 && elect_one()) {
              mbar_expect_tx(sb0 + BAR_CSLD, 24576);
              tma_ld3(sb0 + OFF_STG, &p.wqkv, sb0 + BAR_CSLD, 128 * cx.n + 64, 64 * cx.m, 0);
              tma_ld3(sb0 + OFF_STG + 12288, &p.wqkv, sb0 + BAR_CSLD, 128 * cx.n + 64, 64 * cx.m + 32, 0);
            }
            mbar_wait(sb0 + BAR_XRDY, 0);
            mbar_wait(sb0 + BAR_XRDY + 8, 0);
          }
          write_partial_stats(p, cx, ln, tag);
          PROF_E(i - 2, 8);
        }
        if (i == 1) {
          bar_arrive(BAR_HLP, 160);
          bar_sync(BAR_INIT, 160);
        }
        if (i <= 4) colsum_total(p, cx, ln, tag);
        PROF_E(i - 2, 9);
        if (i != 1) bar_sync(BAR_GUARD + wg, 256);
        finish_row_stats(p, cx, ln, tag);
        PROF_E(i - 2, 10);
        if (i == 4) {
          colsum_gather(p, cx, 1, tag);
          mbar_wait(sb0 + BAR_BIAS, 0);
        }
        PROF_E(i - 2, 15);
        bar_arrive(BAR_GUARD + (wg ^ 1), 256);
      }
      if (step == 2 && !resid) bar_sync(BAR_GUARD + wg, 256);
      if (step == 2 && i == 0) {
        colsum_gather(p, make_ctx(sb0, mn), 0, lds_u(sb0 + OFF_TAG));
        bar_sync(BAR_WG, 128);
      }
      if (i == 1) {
        if (step == 2) rank1_update<false>(p, acc, make_ctx(sb0, mn), t);
      } else if (t + step == 2 || t == 6) {
        rank1_update<true>(p, acc, make_ctx(sb0, mn), t);
      }
      if (step == 2) break;
      if (tile_wide(t)) {
        mainloop<192>(p, acc, sb0, i, step, mn);
      } else {
        mainloop<128>(p, acc, sb0, i, step, mn);
        if (resid) return false;
      }
    }
    if (t < 2) return true;
    gelu_epilogue(p, acc, make_ctx(sb0, mn), t);
    PROF_E(i, 4);
    return false;
  }
}

__global__ void __cluster_dims__(2, 1, 1) __launch_bounds__(384, 1) fused_layers_kernel(const int by_smid, const __nv_bfloat16* x_p, const __nv_bfloat16* wqkv_p,
                                                                  const __grid_constant__ Params p) {
  extern __shared__ __align__(1024) uint8_t smem_raw[];
  const uint32_t sb = uniform((uint32_t)__cvta_generic_to_shared(smem_raw));
  const int tid = threadIdx.x, lane = tid & 31, warp = uniform(tid >> 5), wg = warp >> 2, w = warp & 3;

  int mn;
  {
    int id = blockIdx.x;
    if (by_smid) asm volatile("mov.u32 %0, %%smid;" : "=r"(id));
    else if (id >= 120) id += 4;
    const int c = id >> 1;
    int g, j;
    if (c < 32) { g = c & 7; j = c >> 3; }
    else if (c < 60) { g = 1 + (c - 32) % 7; j = 4 + (c - 32) / 7; }
    else { g = 0; j = c - 58; }
    const int r = blockIdx.x & 1;
    mn = (g * 2 + r) * 8 + j;
    if (c == 60 || c == 61) {
      if (tid < 32) {
        const uint32_t tag = __ldcg(p.g->epoch + NCTA + (id & 3)) + 1;
#pragma unroll 1
        for (int mm = 0; mm < 16; mm++) poll_line(p.g->flags + mm * 32 + (lane & 7), 32 * tag, 0xffu);
        if (tid == 0) p.g->epoch[NCTA + (id & 3)] = tag;
      }
      return;
    }
  }
  const int m = mn >> 3, n = mn & 7;
  if (tid == 256) PROF_U(1);
  if (tid >= 382) asm volatile("prefetch.global.L2 [%0];" ::"l"(tid & 1 ? wqkv_p + 128 * n : x_p + 128 * m * DM));
  if (wg < 2) {
    cluster_arrive();
    asm volatile("setmaxnreg.inc.sync.aligned.u32 232;");
    const int id = mn | (warp << 7);
#pragma unroll 1
    for (int i = wg;; i += 2) {
      float acc[2][96];
#pragma unroll
      for (int r = 0; r < 96; r++) acc[0][r] = acc[1][r] = 0.f;
      pin_regs<96>(acc);
#pragma unroll 1
      while (!consumer_tile(p, acc, sb, i, id)) {
        PROF_T(6 + i * 4);
        i += 2;
        if (i >= 14) goto all_done;
      }
      attn_epilogue(p, acc, make_ctx(sb, id), i >= 7, i >= 7 ? i - 7 : i, lds_u(sb + OFF_TAG));
      PROF_E(i, 4);
      finish_stores(sb, i);
      PROF_E(i, 5);
      PROF_T(6 + i * 4);
    }
  all_done:
    if (wg == 0) {
      finish_stores(sb, 12);
    } else {
      cluster_arrive();
      cluster_wait();
    }
  } else {
    asm volatile("setmaxnreg.dec.sync.aligned.u32 40;");
    if (w != 0) {
      if (w == 1 && elect_one()) {
        mbar_init(sb + BAR_FULL + 32, 2);
#pragma unroll
        for (int k = 0; k < NBAR; k++) mbar_init(sb + BAR_EMPTY + 8 * k, 8);
#pragma unroll
        for (int k = 0; k < 3; k++) mbar_init(sb + BAR_XRDY + 8 * k, 4);
#pragma unroll
        for (int k = 0; k < 7; k++) mbar_init(sb + BAR_PUB + 8 * k, 4);
#pragma unroll
        for (int k = 0; k < 3; k++) mbar_init(sb + BAR_CSLD + 8 * k, 1);
        sts_f2(sb + OFF_ZERO, 0.f, 0.f);
        sts_f2(sb + OFF_ZERO + 8, 0.f, 0.f);
        asm volatile("fence.mbarrier_init.release.cluster;" ::: "memory");
      }
      __syncwarp();
      cluster_arrive();
      if (w == 2) {
        if (lane < 28) write_run_desc(sb, lane >> 1, lane & 1);
        bar_arrive(BAR_INIT, 160);
      }
      cluster_wait();
      if (w == 1) producer<true>(p, sb, m, n, lane);
      else if (w == 3) colsum_helper(p, sb, m, n, lane);
      else if (elect_one()) publisher(p, sb, m, n);
    } else {
      const bool leader = elect_one();
      if (leader) {
#pragma unroll
        for (int k = 0; k < 4; k++) mbar_init(sb + BAR_FULL + 8 * k, 2);
        asm volatile("fence.mbarrier_init.release.cluster;" ::: "memory");
        PROF_U(4);
      }
      __syncwarp();
      cluster_arrive();
      if (leader) {
#pragma unroll 1
        for (int k = 0; k < 4; k++) {
          const uint32_t fb = sb + BAR_FULL + 8 * k;
          mbar_expect_tx(fb, 16384);
          tma_ld2(sb + (5 * k + 3) * UNIT, &p.xin, fb, 64 * k, 128 * m);
          mbar_expect_tx(fb, 3 * UNIT);
          tma_ld3(sb + 5 * k * UNIT, &p.wqkv, fb, 128 * n, 64 * k, 0);
          tma_ld3(sb + 5 * k * UNIT + 12288, &p.wqkv, fb, 128 * n, 64 * k + 32, 0);
        }
        PROF_U(5);
      }
      __syncwarp();
      cluster_wait();
      if (leader) {
        mbar_expect_tx(sb + BAR_CSLD, 24576);
        tma_ld3(sb + OFF_STG, &p.wqkv, sb + BAR_CSLD, 128 * n, 64 * m, 0);
        tma_ld3(sb + OFF_STG + 12288, &p.wqkv, sb + BAR_CSLD, 128 * n, 64 * m + 32, 0);
#pragma unroll 1
        for (int h = 0; h < 2; h++) {
          const uint32_t xr = sb + BAR_XRDY + 8 * h;
          mbar_expect_tx(xr, 16384);
          tma_ld2(sb + OFF_X + h * 16384, &p.xin, xr, 128 * n + 64 * h, 128 * m);
          asm volatile("mbarrier.arrive.shared::cta.b64 _, [%0], 3;" ::"r"(xr) : "memory");
        }
        PROF_U(6);
      }
      __syncwarp();
      producer<false>(p, sb, m, n, lane);
    }
  }
}

typedef CUresult (*EncodeFn)(CUtensorMap*, CUtensorMapDataType, cuuint32_t, void*, const cuuint64_t*, const cuuint64_t*,
                             const cuuint32_t*, const cuuint32_t*, CUtensorMapInterleave, CUtensorMapSwizzle,
                             CUtensorMapL2promotion, CUtensorMapFloatOOBfill);

#define PROMO2 CU_TENSOR_MAP_L2_PROMOTION_L2_128B
#define PROMO3 CU_TENSOR_MAP_L2_PROMOTION_L2_128B
void make_2d(EncodeFn enc, CUtensorMap* m, const void* ptr, uint64_t cols, uint64_t rows, uint32_t box_rows) {
  cuuint64_t d[2] = {cols, rows}, st[1] = {cols * 2};
  cuuint32_t b[2] = {64, box_rows}, e[2] = {1, 1};
  enc(m, CU_TENSOR_MAP_DATA_TYPE_BFLOAT16, 2, const_cast<void*>(ptr), d, st, b, e, CU_TENSOR_MAP_INTERLEAVE_NONE,
      CU_TENSOR_MAP_SWIZZLE_128B, PROMO2, CU_TENSOR_MAP_FLOAT_OOB_FILL_NONE);
}
void make_3d(EncodeFn enc, CUtensorMap* m, const void* ptr, uint64_t d0, uint64_t rows, uint64_t d2, uint64_t row_bytes,
             uint64_t chunk_bytes, uint32_t box_chunks) {
  cuuint64_t d[3] = {d0, rows, d2}, st[2] = {row_bytes, chunk_bytes};
  cuuint32_t b[3] = {64, 32, box_chunks}, e[3] = {1, 1, 1};
  enc(m, CU_TENSOR_MAP_DATA_TYPE_BFLOAT16, 3, const_cast<void*>(ptr), d, st, b, e, CU_TENSOR_MAP_INTERLEAVE_NONE,
      CU_TENSOR_MAP_SWIZZLE_128B, PROMO3, CU_TENSOR_MAP_FLOAT_OOB_FILL_NONE);
}

}

extern "C" void kernel_launch(void* const* d_in, const int* in_sizes, int n_in, void* d_out, int out_size) {
  (void)in_sizes; (void)n_in; (void)out_size;
  static EncodeFn enc = nullptr;
  static void *att = nullptr, *hbuf = nullptr, *scratch = nullptr;
  static int by_smid = 0;
  if (!enc) {
    void* fn = nullptr;
    cudaDriverEntryPointQueryResult q;
    cudaGetDriverEntryPoint("cuTensorMapEncodeTiled", &fn, cudaEnableDefault, &q);
    enc = (EncodeFn)fn;
    cudaGetSymbolAddress(&att, g_att);
    cudaGetSymbolAddress(&hbuf, g_h);
    cudaGetSymbolAddress(&scratch, g_scratch);
    cudaFuncSetAttribute(fused_layers_kernel, cudaFuncAttributeMaxDynamicSharedMemorySize, SMEM_BYTES);
    int sms = 0, clusters = 0, dev = 0;
    cudaGetDevice(&dev);
    cudaDeviceGetAttribute(&sms, cudaDevAttrMultiProcessorCount, dev);
    cudaLaunchConfig_t cfg = {};
    cfg.gridDim = dim3(132);
    cfg.blockDim = dim3(384);
    cfg.dynamicSmemBytes = SMEM_BYTES;
    cudaLaunchAttribute at[1];
    at[0].id = cudaLaunchAttributeClusterDimension;
    at[0].val.clusterDim.x = 2; at[0].val.clusterDim.y = 1; at[0].val.clusterDim.z = 1;
    cfg.attrs = at;
    cfg.numAttrs = 1;
    if (cudaOccupancyMaxActiveClusters(&clusters, fused_layers_kernel, &cfg) != cudaSuccess) (void)cudaGetLastError();
    by_smid = sms == 132 && clusters == 66;
  }
  Params p;
  make_2d(enc, &p.xin, d_in[0], DM, SEQ, 128);
  make_2d(enc, &p.out, d_out, DM, SEQ, 128);
  make_2d(enc, &p.att, att, DM, SEQ, 128);
  make_2d(enc, &p.h, hbuf, FF, SEQ, 128);
  make_2d(enc, &p.out_st, d_out, DM, SEQ, 32);
  make_2d(enc, &p.att_st, att, DM, SEQ, 32);
  make_2d(enc, &p.h_st, hbuf, FF, SEQ, 32);
  make_2d(enc, &p.w1c, d_in[4], FF, DM, 32);
  make_3d(enc, &p.wqkv, d_in[1], DM, DM, 3, 3 * DM * 2, DM * 2, 3);
  make_3d(enc, &p.wo, d_in[2], 64, DM, DM / 64, DM * 2, 128, 2);
  make_3d(enc, &p.w1a, d_in[4], 64, DM, FF / 64, FF * 2, 128, 3);
  make_3d(enc, &p.w1b, d_in[4], 64, DM, FF / 64, FF * 2, 128, 2);
  make_3d(enc, &p.w2, d_in[6], 64, FF, DM / 64, DM * 2, 128, 2);
  p.b1 = (const __nv_bfloat16*)d_in[5];
  p.b2 = (const __nv_bfloat16*)d_in[7];
  p.g = (Scratch*)scratch;
  p.zero = 0;
  fused_layers_kernel<<<by_smid ? 132 : NCTA, 384, SMEM_BYTES>>>(by_smid, (const __nv_bfloat16*)d_in[0], (const __nv_bfloat16*)d_in[1], p);
}
```

```cpp
#include <cuda_runtime.h>
#include <cuda_bf16.h>
#include <cuda.h>
#include <stdint.h>

namespace {

constexpr int SEQ = 2048, DM = 1024, FF = 3584;
constexpr int NCTA = 128;
constexpr int NBAR = 5;

constexpr uint32_t RING_UNITS = 20, UNIT = 8192;
constexpr uint32_t OFF_X   = RING_UNITS * UNIT;
constexpr uint32_t OFF_STG = OFF_X + 32768;
constexpr uint32_t OFF_HLP = OFF_STG + 16384;
constexpr uint32_t OFF_RUN = OFF_STG + 24576;
constexpr uint32_t OFF_CSQ = OFF_RUN + 512;
constexpr uint32_t OFF_CSF = OFF_CSQ + 2048;
constexpr uint32_t OFF_ROW = OFF_CSF + 3584;
constexpr uint32_t OFF_BAR = OFF_ROW + 1024;
constexpr uint32_t SMEM_BYTES = OFF_BAR + 384;
constexpr uint32_t BAR_FULL = OFF_BAR, BAR_EMPTY = OFF_BAR + 8 * NBAR;
constexpr uint32_t BAR_XRDY = OFF_BAR + 80;
constexpr uint32_t BAR_DUMMY = OFF_BAR + 96, OFF_TAG = OFF_BAR + 104, OFF_ZERO = OFF_BAR + 112;
constexpr uint32_t BAR_PUB = OFF_BAR + 128;
constexpr uint32_t BAR_CSLD = OFF_BAR + 200;
constexpr uint32_t BAR_XGO = OFF_BAR + 224;
constexpr uint32_t BAR_BIAS = OFF_BAR + 216;

constexpr uint64_t DESC_A = (1ull << 62) | ((uint64_t)(2048 >> 4) << 32) | (1ull << 16);
constexpr uint64_t DESC_B = (1ull << 62) | ((uint64_t)(1024 >> 4) << 32) | ((uint64_t)(4096 >> 4) << 16);

constexpr int BAR_INIT = 0, BAR_ORDER = 1, BAR_GUARD = 3, BAR_WG = 5, BAR_GO = 7, BAR_DONE = 8, BAR_HLP = 9, BAR_PAIR = 11;
#define GELU_DEP 2
#define MAP 2
#define LATE_O 1
#define HALO_NS 200
#define STG_WAIT 5
#define HOLD_ATT 0
#define STAT_NS 800
#define WIN1 8
#define WIN2 2

struct Scratch {
  uint4 stats[4 * 8 * SEQ];
  uint4 halo[2 * 2 * 16 * 8 * 384];
  uint4 csp[2 * 8 * 17 * 224];
  uint32_t flags[16 * 32];
  uint32_t epoch[NCTA + 4];
};

struct Params {
  CUtensorMap xin, out, att, h, wqkv, wo, w1a, w1b, w2, out_st, att_st, h_st, w1c;
  const __nv_bfloat16 *b1, *b2;
  Scratch* g;
  uint32_t zero;
};

__device__ __nv_bfloat16 g_att[SEQ * DM];
__device__ __nv_bfloat16 g_h[SEQ * FF];
__device__ Scratch g_scratch;
#define PROF_T(idx)
#define PROF_U(k)
#define PROF_S(g)
#define PROF_E(i, k)

__device__ __forceinline__ void mbar_init(uint32_t bar, int cnt) {
  asm volatile("mbarrier.init.shared::cta.b64 [%0], %1;" ::"r"(bar), "r"(cnt));
}
__device__ __forceinline__ void mbar_expect_tx(uint32_t bar, uint32_t bytes) {
  asm volatile("mbarrier.arrive.expect_tx.shared::cta.b64 _, [%0], %1;" ::"r"(bar), "r"(bytes) : "memory");
}
__device__ __forceinline__ void mbar_arrive(uint32_t bar) {
  asm volatile("mbarrier.arrive.shared::cta.b64 _, [%0];" ::"r"(bar) : "memory");
}
__device__ __forceinline__ bool mbar_test(uint32_t bar, uint32_t parity) {
  uint32_t ok;
  asm volatile("{\n.reg .pred p;\nmbarrier.test_wait.parity.shared::cta.b64 p, [%1], %2;\nselp.u32 %0, 1, 0, p;\n}"
               : "=r"(ok) : "r"(bar), "r"(parity) : "memory");
  return ok;
}
__device__ __forceinline__ void mbar_wait(uint32_t bar, uint32_t parity) {
  asm volatile(
      "{\n.reg .pred p;\n.reg .u32 it;\nmov.u32 it, 0;\n"
      "WAIT_LOOP:\n"
      "mbarrier.try_wait.parity.shared::cta.b64 p, [%0], %1;\n"
      "@p bra WAIT_DONE;\n"
      "add.u32 it, it, 1;\n"
      "setp.lt.u32 p, it, 0x400000;\n"
      "@p bra WAIT_LOOP;\n"
      "trap;\n"
      "WAIT_DONE:\n}"
      ::"r"(bar), "r"(parity) : "memory");
}
__device__ __forceinline__ void bar_sync(int id, int n) { asm volatile("bar.sync %0, %1;" ::"r"(id), "r"(n) : "memory"); }
__device__ __forceinline__ void bar_arrive(int id, int n) { asm volatile("bar.arrive %0, %1;" ::"r"(id), "r"(n) : "memory"); }
__device__ __forceinline__ void tma_ld2(uint32_t dst, const CUtensorMap* m, uint32_t bar, int c0, int c1) {
  asm volatile("cp.async.bulk.tensor.2d.shared::cluster.global.mbarrier::complete_tx::bytes [%0], [%1, {%3, %4}], [%2];"
               ::"r"(dst), "l"(m), "r"(bar), "r"(c0), "r"(c1) : "memory");
}
__device__ __forceinline__ void tma_ld3(uint32_t dst, const CUtensorMap* m, uint32_t bar, int c0, int c1, int c2) {
  asm volatile("cp.async.bulk.tensor.3d.shared::cluster.global.mbarrier::complete_tx::bytes [%0], [%1, {%3, %4, %5}], [%2];"
               ::"r"(dst), "l"(m), "r"(bar), "r"(c0), "r"(c1), "r"(c2) : "memory");
}
__device__ __forceinline__ void tma_ld3_pair(uint32_t dst, const CUtensorMap* m, uint32_t bar, int c0, int c1, int c2) {
  asm volatile("cp.async.bulk.tensor.3d.shared::cluster.global.mbarrier::complete_tx::bytes.multicast::cluster"
               " [%0], [%1, {%3, %4, %5}], [%2], %6;"
               ::"r"(dst), "l"(m), "r"(bar), "r"(c0), "r"(c1), "r"(c2), "h"((uint16_t)3) : "memory");
}
__device__ __forceinline__ uint32_t pair_offset(uint32_t sb, uint32_t rank) {
  uint32_t r;
  asm volatile("mapa.shared::cluster.u32 %0, %1, %2;" : "=r"(r) : "r"(sb), "r"(rank));
  return r - sb;
}
__device__ __forceinline__ void mbar_arrive_cluster(uint32_t bar) {
  asm volatile("mbarrier.arrive.shared::cluster.b64 _, [%0];" ::"r"(bar) : "memory");
}
__device__ __forceinline__ void cluster_arrive() { asm volatile("barrier.cluster.arrive.relaxed;" ::: "memory"); }
__device__ __forceinline__ void cluster_wait() { asm volatile("barrier.cluster.wait.acquire;" ::: "memory"); }
__device__ __forceinline__ void tma_st2(const CUtensorMap* m, uint32_t src, int c0, int c1) {
  asm volatile("cp.async.bulk.tensor.2d.global.shared::cta.bulk_group [%0, {%2, %3}], [%1];"
               ::"l"(m), "r"(src), "r"(c0), "r"(c1) : "memory");
}
__device__ __forceinline__ void bulk_commit() { asm volatile("cp.async.bulk.commit_group;" ::: "memory"); }
__device__ __forceinline__ void bulk_wait_read() { asm volatile("cp.async.bulk.wait_group.read 0;" ::: "memory"); }
__device__ __forceinline__ void bulk_wait_all() { asm volatile("cp.async.bulk.wait_group 0;" ::: "memory"); }
__device__ __forceinline__ void fence_async_smem() { asm volatile("fence.proxy.async.shared::cta;" ::: "memory"); }
__device__ __forceinline__ void fence_async_global() { asm volatile("fence.proxy.async.global;" ::: "memory"); }
__device__ __forceinline__ void st_relaxed(uint32_t* p, uint32_t v) {
  asm volatile("st.relaxed.gpu.global.u32 [%0], %1;" ::"l"(p), "r"(v) : "memory");
}
__device__ __forceinline__ void st_msg(uint4* p, uint32_t a, uint32_t b, uint32_t c, uint32_t tag) {
  asm volatile("{\n.reg .b128 v;\nmov.b128 v, {%1, %2, %3, %4};\nst.relaxed.gpu.global.b128 [%0], v;\n}"
               ::"l"(p), "r"(a), "r"(b), "r"(c), "r"(tag) : "memory");
}
__device__ __forceinline__ void ld_msg(const uint4* p, uint32_t& a, uint32_t& b, uint32_t& c, uint32_t& tag) {
  asm volatile("{\n.reg .b128 v;\nld.relaxed.gpu.global.b128 v, [%4];\nmov.b128 {%0, %1, %2, %3}, v;\n}"
               : "=r"(a), "=r"(b), "=r"(c), "=r"(tag) : "l"(p) : "memory");
}
__device__ __forceinline__ bool elect_one() {
  uint32_t ok;
  asm volatile("{\n.reg .pred p;\nelect.sync _|p, 0xffffffff;\nselp.u32 %0, 1, 0, p;\n}" : "=r"(ok));
  return ok;
}
__device__ __forceinline__ int uniform(int v) { return __shfl_sync(0xffffffffu, v, 0); }
__device__ __forceinline__ uint32_t pack_bf16(float lo, float hi) {
  uint32_t r;
  asm("cvt.rn.bf16x2.f32 %0, %1, %2;" : "=r"(r) : "f"(hi), "f"(lo));
  return r;
}
__device__ __forceinline__ uint32_t prmt_u(uint32_t a, uint32_t sel) {
  uint32_t r;
  asm("prmt.b32 %0, %1, 0, %2;" : "=r"(r) : "r"(a), "r"(sel));
  return r;
}
__device__ __forceinline__ float prmt_f(uint32_t a, uint32_t sel) {
  float r;
  asm("{\n.reg .b32 t;\nprmt.b32 t, %1, 0, %2;\nmov.b32 %0, t;\n}" : "=f"(r) : "r"(a), "r"(sel));
  return r;
}
__device__ __forceinline__ float bf_lo(uint32_t v) { return __uint_as_float(v << 16); }
__device__ __forceinline__ float bf_hi(uint32_t v) { return __uint_as_float(v & 0xffff0000u); }
__device__ __forceinline__ void stsm4(uint32_t addr, uint32_t r0, uint32_t r1, uint32_t r2, uint32_t r3) {
  asm volatile("stmatrix.sync.aligned.m8n8.x4.shared.b16 [%0], {%1, %2, %3, %4};"
               ::"r"(addr), "r"(r0), "r"(r1), "r"(r2), "r"(r3) : "memory");
}
__device__ __forceinline__ void ldsm4(uint32_t addr, uint32_t& r0, uint32_t& r1, uint32_t& r2, uint32_t& r3) {
  asm volatile("ldmatrix.sync.aligned.m8n8.x4.shared.b16 {%0, %1, %2, %3}, [%4];"
               : "=r"(r0), "=r"(r1), "=r"(r2), "=r"(r3) : "r"(addr) : "memory");
}
__device__ __forceinline__ uint32_t movtrans(uint32_t a) {
  uint32_t d;
  asm volatile("movmatrix.sync.aligned.m8n8.trans.b16 %0, %1;" : "=r"(d) : "r"(a));
  return d;
}
__device__ __forceinline__ void mma16816(float (&c)[4], uint32_t a0, uint32_t a1, uint32_t a2, uint32_t a3, uint32_t b0, uint32_t b1) {
  asm volatile("mma.sync.aligned.m16n8k16.row.col.f32.bf16.bf16.f32 {%0,%1,%2,%3}, {%4,%5,%6,%7}, {%8,%9}, {%0,%1,%2,%3};"
               : "+f"(c[0]), "+f"(c[1]), "+f"(c[2]), "+f"(c[3])
               : "r"(a0), "r"(a1), "r"(a2), "r"(a3), "r"(b0), "r"(b1));
}
__device__ __forceinline__ float2 lds_f2(uint32_t a) {
  float2 v;
  asm volatile("ld.shared.v2.f32 {%0, %1}, [%2];" : "=f"(v.x), "=f"(v.y) : "r"(a) : "memory");
  return v;
}
__device__ __forceinline__ float4 lds_f4(uint32_t a) {
  float4 v;
  asm volatile("ld.shared.v4.f32 {%0, %1, %2, %3}, [%4];" : "=f"(v.x), "=f"(v.y), "=f"(v.z), "=f"(v.w) : "r"(a) : "memory");
  return v;
}
__device__ __forceinline__ float lds_f(uint32_t a) {
  float v;
  asm volatile("ld.shared.f32 %0, [%1];" : "=f"(v) : "r"(a) : "memory");
  return v;
}
__device__ __forceinline__ uint32_t lds_u(uint32_t a) {
  uint32_t v;
  asm volatile("ld.shared.u32 %0, [%1];" : "=r"(v) : "r"(a) : "memory");
  return v;
}
__device__ __forceinline__ void sts_f2(uint32_t a, float x, float y) {
  asm volatile("st.shared.v2.f32 [%0], {%1, %2};" ::"r"(a), "f"(x), "f"(y) : "memory");
}
__device__ __forceinline__ void sts_u4(uint32_t a, uint32_t x, uint32_t y, uint32_t z, uint32_t w) {
  asm volatile("st.shared.v4.u32 [%0], {%1, %2, %3, %4};" ::"r"(a), "r"(x), "r"(y), "r"(z), "r"(w) : "memory");
}
__device__ __forceinline__ void lds_u4(uint32_t a, uint32_t& x, uint32_t& y, uint32_t& z, uint32_t& w) {
  asm volatile("ld.shared.v4.u32 {%0, %1, %2, %3}, [%4];" : "=r"(x), "=r"(y), "=r"(z), "=r"(w) : "r"(a) : "memory");
}
__device__ __forceinline__ float ex2(float x) {
  float y;
  asm("ex2.approx.ftz.f32 %0, %1;" : "=f"(y) : "f"(x));
  return y;
}
__device__ __forceinline__ float rcp_hw(float x) {
  float y;
  asm("rcp.approx.ftz.f32 %0, %1;" : "=f"(y) : "f"(x));
  return y;
}
__device__ __forceinline__ float tanh_hw(float x) {
  float y;
  asm("tanh.approx.f32 %0, %1;" : "=f"(y) : "f"(x));
  return y;
}
__device__ __forceinline__ float quad_sum(float v) {
  v += __shfl_xor_sync(0xffffffffu, v, 1);
  return v + __shfl_xor_sync(0xffffffffu, v, 2);
}
__device__ __forceinline__ float quad_max(float v) {
  v = fmaxf(v, __shfl_xor_sync(0xffffffffu, v, 1));
  return fmaxf(v, __shfl_xor_sync(0xffffffffu, v, 2));
}

template <int N> __device__ __forceinline__ void wgmma_ss(float (&d)[96], uint64_t da, uint64_t db, uint32_t keep = 1);
template <> __device__ __forceinline__ void wgmma_ss<128>(float (&d)[96], uint64_t da, uint64_t db, uint32_t keep) {
  asm volatile(
      "{\n.reg .pred p;\nsetp.ne.u32 p, %66, 0;\n"
      "wgmma.mma_async.sync.aligned.m64n128k16.f32.bf16.bf16 {%0, %1, %2, %3, %4, %5, %6, %7, %8, %9, %10, %11, %12, %13, %14, %15, %16, %17, %18, %19, %20, %21, %22, %23, %24, %25, %26, %27, %28, %29, %30, %31, %32, %33, %34, %35, %36, %37, %38, %39, %40, %41, %42, %43, %44, %45, %46, %47, %48, %49, %50, %51, %52, %53, %54, %55, %56, %57, %58, %59, %60, %61, %62, %63}, %64, %65, p, 1, 1, 0, 1;\n}"
      : "+f"(d[0]), "+f"(d[1]), "+f"(d[2]), "+f"(d[3]), "+f"(d[4]), "+f"(d[5]), "+f"(d[6]), "+f"(d[7]), "+f"(d[8]), "+f"(d[9]), "+f"(d[10]), "+f"(d[11]), "+f"(d[12]), "+f"(d[13]), "+f"(d[14]), "+f"(d[15]), "+f"(d[16]), "+f"(d[17]), "+f"(d[18]), "+f"(d[19]), "+f"(d[20]), "+f"(d[21]), "+f"(d[22]), "+f"(d[23]), "+f"(d[24]), "+f"(d[25]), "+f"(d[26]), "+f"(d[27]), "+f"(d[28]), "+f"(d[29]), "+f"(d[30]), "+f"(d[31]), "+f"(d[32]), "+f"(d[33]), "+f"(d[34]), "+f"(d[35]), "+f"(d[36]), "+f"(d[37]), "+f"(d[38]), "+f"(d[39]), "+f"(d[40]), "+f"(d[41]), "+f"(d[42]), "+f"(d[43]), "+f"(d[44]), "+f"(d[45]), "+f"(d[46]), "+f"(d[47]), "+f"(d[48]), "+f"(d[49]), "+f"(d[50]), "+f"(d[51]), "+f"(d[52]), "+f"(d[53]), "+f"(d[54]), "+f"(d[55]), "+f"(d[56]), "+f"(d[57]), "+f"(d[58]), "+f"(d[59]), "+f"(d[60]), "+f"(d[61]), "+f"(d[62]), "+f"(d[63])
      : "l"(da), "l"(db), "r"(keep));
}

template <> __device__ __forceinline__ void wgmma_ss<192>(float (&d)[96], uint64_t da, uint64_t db, uint32_t keep) {
  asm volatile(
      "{\n.reg .pred p;\nsetp.ne.u32 p, %98, 0;\n"
      "wgmma.mma_async.sync.aligned.m64n192k16.f32.bf16.bf16 {%0, %1, %2, %3, %4, %5, %6, %7, %8, %9, %10, %11, %12, %13, %14, %15, %16, %17, %18, %19, %20, %21, %22, %23, %24, %25, %26, %27, %28, %29, %30, %31, %32, %33, %34, %35, %36, %37, %38, %39, %40, %41, %42, %43, %44, %45, %46, %47, %48, %49, %50, %51, %52, %53, %54, %55, %56, %57, %58, %59, %60, %61, %62, %63, %64, %65, %66, %67, %68, %69, %70, %71, %72, %73, %74, %75, %76, %77, %78, %79, %80, %81, %82, %83, %84, %85, %86, %87, %88, %89, %90, %91, %92, %93, %94, %95}, %96, %97, p, 1, 1, 0, 1;\n}"
      : "+f"(d[0]), "+f"(d[1]), "+f"(d[2]), "+f"(d[3]), "+f"(d[4]), "+f"(d[5]), "+f"(d[6]), "+f"(d[7]), "+f"(d[8]), "+f"(d[9]), "+f"(d[10]), "+f"(d[11]), "+f"(d[12]), "+f"(d[13]), "+f"(d[14]), "+f"(d[15]), "+f"(d[16]), "+f"(d[17]), "+f"(d[18]), "+f"(d[19]), "+f"(d[20]), "+f"(d[21]), "+f"(d[22]), "+f"(d[23]), "+f"(d[24]), "+f"(d[25]), "+f"(d[26]), "+f"(d[27]), "+f"(d[28]), "+f"(d[29]), "+f"(d[30]), "+f"(d[31]), "+f"(d[32]), "+f"(d[33]), "+f"(d[34]), "+f"(d[35]), "+f"(d[36]), "+f"(d[37]), "+f"(d[38]), "+f"(d[39]), "+f"(d[40]), "+f"(d[41]), "+f"(d[42]), "+f"(d[43]), "+f"(d[44]), "+f"(d[45]), "+f"(d[46]), "+f"(d[47]), "+f"(d[48]), "+f"(d[49]), "+f"(d[50]), "+f"(d[51]), "+f"(d[52]), "+f"(d[53]), "+f"(d[54]), "+f"(d[55]), "+f"(d[56]), "+f"(d[57]), "+f"(d[58]), "+f"(d[59]), "+f"(d[60]), "+f"(d[61]), "+f"(d[62]), "+f"(d[63]), "+f"(d[64]), "+f"(d[65]), "+f"(d[66]), "+f"(d[67]), "+f"(d[68]), "+f"(d[69]), "+f"(d[70]), "+f"(d[71]), "+f"(d[72]), "+f"(d[73]), "+f"(d[74]), "+f"(d[75]), "+f"(d[76]), "+f"(d[77]), "+f"(d[78]), "+f"(d[79]), "+f"(d[80]), "+f"(d[81]), "+f"(d[82]), "+f"(d[83]), "+f"(d[84]), "+f"(d[85]), "+f"(d[86]), "+f"(d[87]), "+f"(d[88]), "+f"(d[89]), "+f"(d[90]), "+f"(d[91]), "+f"(d[92]), "+f"(d[93]), "+f"(d[94]), "+f"(d[95])
      : "l"(da), "l"(db), "r"(keep));
}

template <int R>
__device__ __forceinline__ void pin_regs(float (&a)[2][96]) {
#pragma unroll
  for (int m = 0; m < 2; m++)
#pragma unroll
    for (int i = 0; i < R; i++) asm volatile("" : "+f"(a[m][i])::"memory");
}

struct Ctx {
  uint32_t sb;
  int m, n, wg, w, lane;
};
__device__ __forceinline__ Ctx make_ctx(uint32_t sb, int id) {
  int lane;
  asm volatile("mov.u32 %0, %%laneid;" : "=r"(lane));
  asm volatile("" : "+r"(id), "+r"(sb));
  return Ctx{sb, (id >> 3) & 15, id & 7, id >> 9, (id >> 7) & 3, lane};
}
#define UNPACK_CTX(c) const uint32_t sb = c.sb; const int m = c.m, n = c.n, wg = c.wg, w = c.w, lane = c.lane

__device__ __forceinline__ uint32_t poll_line(const uint32_t* word, uint32_t target, uint32_t need) {
  uint32_t v;
  asm volatile(
      "{\n.reg .pred p;\n.reg .u32 it, m;\n.reg .s32 d;\nmov.u32 it, 0;\n"
      "POLL_LOOP:\n"
      "ld.relaxed.gpu.global.u32 %0, [%1];\n"
      "sub.s32 d, %0, %2;\n"
      "setp.ge.s32 p, d, 0;\n"
      "vote.sync.ballot.b32 m, p, 0xffffffff;\n"
      "and.b32 m, m, %3;\n"
      "setp.eq.u32 p, m, %3;\n"
      "@p bra.uni POLL_DONE;\n"
      "add.u32 it, it, 1;\n"
      "setp.lt.u32 p, it, 0x400000;\n"
      "@p bra.uni POLL_LOOP;\n"
      "trap;\n"
      "POLL_DONE:\n}"
      : "=&r"(v) : "l"(word), "r"(target), "r"(need) : "memory");
  return v;
}
__device__ __forceinline__ uint32_t ld_relaxed(const uint32_t* p) {
  uint32_t v;
  asm volatile("ld.relaxed.gpu.global.u32 %0, [%1];" : "=r"(v) : "l"(p) : "memory");
  return v;
}
__device__ __forceinline__ float chain(float x, uint32_t on, uint32_t zero) {
  return __uint_as_float(__float_as_uint(x) | (on & zero));
}
constexpr int MSG_SPINS = 1 << 20;

constexpr int STAGES_PER_LAYER = 152;
__device__ __forceinline__ int nib(uint64_t v, int i) { return (int)(v >> (4 * i)) & 15; }
__device__ __forceinline__ bool tile_wide(int t) { return (0x23 >> t) & 1; }
__device__ __forceinline__ void weight_coords(const Params& p, int t, int n, const CUtensorMap*& map, int& c0, int& c2) {
  map = &p.wqkv + nib(0x4233100ull, t);
  c0 = t < 2 ? 128 * n + 64 * t : 0;
  c2 = t < 2 ? 0 : (t == 2 || t == 6) ? 2 * n : 7 * n + 2 * t - 6;
}

template <bool IS_A>
__device__ __forceinline__ void producer(const Params& p, uint32_t sb, int m, int n, int lane) {
  const uint32_t low = (1u << (4 * n)) - 1, others = (0x6543210u & low) | (0x7654321u & ~low);
  const uint64_t order_x = (uint64_t)(others * 2 + 0x1111111u) << 36 | (uint64_t)others * 2 << 8 | (n * 0x22 + 0x10);
  int inflight = 4, cur = 0;
  uint32_t fb = sb + BAR_FULL + 32, rb = sb + BAR_EMPTY, rph = 0, pos = 0, tag32 = 0, seen = 0;
  const uint32_t fend = sb + BAR_FULL + 8 * NBAR, rend = sb + BAR_EMPTY + 8 * NBAR;
  const uint32_t* word = p.g->flags + m * 32 + (lane < 16 ? lane >> 1 : lane & 7);
#pragma unroll 1
  for (int sg = 1; sg < 22; sg++) {
    const int layer = sg >= 11, s = sg == 1 ? 2 : sg == 2 ? 1 : sg - 11 * layer;
    const int t = nib(0x65434321010ull, s), kind = nib(0x32110031100ull, s);
    const bool wide = tile_wide(t);
    const uint32_t bbytes = wide ? 3 * UNIT : 2 * UNIT, base = sb + (IS_A ? bbytes : (m & 1) * (bbytes / 2));
    if (IS_A && kind == 0) {
      if (sg == 2) seen = tag32 = (__ldcg(p.g->epoch + m * 8 + n) + 1) << 5;
#pragma unroll 1
      for (int k = 0; k < 2; k++) {
#pragma unroll 1
        for (; inflight > (wide ? 3 : 4); inflight--) {
          mbar_wait(rb, rph);
          rb += 8;
          if (rb == rend) { rb -= 8 * NBAR; rph ^= 1; }
        }
        if (elect_one()) mbar_arrive(fb);
        inflight++;
        fb += 8;
        if (fb == fend) fb -= 8 * NBAR;
        pos += bbytes + 2 * UNIT;
        if (pos >= RING_UNITS * UNIT) pos -= RING_UNITS * UNIT;
      }
      continue;
    }
    const int mul = t == 6 ? 448 : t == 2 ? 128 : 64, count = sg == 1 ? 12 : 2 * nib(0x4871ull, kind);
    uint64_t order0 = sg == 1 ? 0xFEDCBA987654ull : kind == 3 ? 0x76543210u : order_x >> (8 * (kind & 1));
    uint32_t special = (s == 4 || s == 10) ? 0x10 : s == 9 ? 0xF : s == 0;
    if (IS_A) special |= (kind & 1 ? 0 : 3) | (count >= 4 ? 1u << (count - 4) : 0);
    if (s >= 9) pos = (s + 6) * UNIT;
    const CUtensorMap* map;
    int c0 = 0, c2 = 0, ev = 0;
    if (IS_A) {
      map = &p.xin + (t == 2 ? 2 : t == 6 ? 3 : sg >= 4);
      ev = 9 * layer + (t < 2 ? 0 : t == 2 ? 1 : t < 6 ? 4 : 5);
      if (elect_one()) asm volatile("prefetch.tensormap [%0];" ::"l"(map) : "memory");
    } else {
      weight_coords(p, t, n, map, c0, c2);
    }
#pragma unroll 1
    for (int add = 0; add < mul; add += 64) {
      uint64_t order = order0;
      const int need = kind == 3 ? ev : ev - 1 + (lane & 1), sh = kind == 3 ? 16 : 0;
      uint32_t ready = IS_A ? __ballot_sync(0xffffffffu, cur >= need) >> sh : 0;
#pragma unroll 1
      for (int k = 0; k < count; k++) {
        const int code = order & 15, kc = code * mul + add;
        order >>= 4;
        if ((special >> k) & 1) {
          const int lag = wide ? (s == 9 && k == 2 ? 2 : 3) : ((s == 4 || s == 10) && add == 0 && k < 4) ? 3 : 4;
#pragma unroll 1
          for (; inflight > lag; inflight--) {
            mbar_wait(rb, rph);
            rb += 8;
            if (rb == rend) { rb -= 8 * NBAR; rph ^= 1; }
          }
          inflight++;
          if (IS_A) {
            if (kind == 3 ? t == 2 && add + k == 64 : !(kind & 1) && k < 2) {
              if (t == 2) mbar_wait(sb + BAR_PUB + 8, layer);
              if (elect_one()) mbar_arrive(fb);
              goto next_stage;
            }
            if (k == count - 4 && sg >= 3) seen = ld_relaxed(word);
          }
        } else {
          mbar_wait(rb, rph);
          rb += 8;
          if (rb == rend) { rb -= 8 * NBAR; rph ^= 1; }
        }
        if (IS_A && !((ready >> code) & 1)) {
          cur = max(cur, (int)(seen - tag32));
          ready = __ballot_sync(0xffffffffu, cur >= need) >> sh;
          if (!((ready >> code) & 1)) {
            cur = (int)(poll_line(word, tag32 + need, 1u << (code + sh)) - tag32);
            ready = __ballot_sync(0xffffffffu, cur >= need) >> sh;
          }
          asm volatile("fence.acquire.gpu;" ::: "memory");
          fence_async_global();
          seen = ld_relaxed(word);
        }
        if (elect_one()) {
          if (!IS_A) tma_ld3_pair(base + pos, map, fb, c0, kc + 32 * (m & 1), c2);
          else tma_ld2(base + pos, map, fb, kc, 128 * m);
          mbar_expect_tx(fb, IS_A ? 16384 : bbytes);
        }
      next_stage:
        fb += 8;
        if (fb == fend) fb -= 8 * NBAR;
        pos += bbytes + 2 * UNIT;
        if (pos >= RING_UNITS * UNIT) pos -= RING_UNITS * UNIT;
      }
      special = !IS_A ? 0 : t == 2 ? 1 : add == 128 ? 0x10 : 0;
      if (t == 2) order0 = others << 4 | n;
      if (IS_A && (t == 2 || add == 64 || add == 192)) ev++;
    }
  }
}

__device__ __forceinline__ void publisher(const Params& p, uint32_t sb, int m, int n) {
  const uint32_t tag = __ldcg(p.g->epoch + m * 8 + n) + 1;
  uint32_t* word = p.g->flags + m * 32 + n;
  const int mn = m * 8 + n; (void)mn;
  st_relaxed(word, 32 * tag);
#pragma unroll 1
  for (int c = 0; c < 17; c++) {
    const int e = c >= 9 ? c - 9 : c;
    if (e == 2 || e == 7) {
      asm volatile("prefetch.tensormap [%0];" ::"l"(&p.out) : "memory");
      mbar_wait(sb + BAR_XRDY, e == 2);
      tma_st2(&p.out, sb + OFF_X, 128 * n, 128 * m);
      bulk_commit();
      if (c == 16) break;
      mbar_wait(sb + BAR_XRDY + 8, e == 2);
      bulk_wait_all();
      mbar_arrive(sb + BAR_XGO);
      PROF_E(7 * (c >= 9) + (e < 4 ? 2 : 6), 11);
    } else {
      mbar_wait(sb + BAR_PUB + 8 * e, c >= 9);
    }
    asm volatile("fence.release.gpu;" ::: "memory");
    asm volatile("red.relaxed.gpu.global.add.u32 [%0], 1;" ::"l"(word) : "memory");
    PROF_E(7 * (c >= 9) + nib(0x665432210ull, e), (0x108 >> e) & 1 ? 14 : 12);
  }
  p.g->epoch[m * 8 + n] = tag;
  bulk_wait_read();
}

__device__ __forceinline__ void sum_rows(uint32_t buf, int iters, float (&a)[8], int lane) {
  uint32_t addr = buf + (lane >> 3) * 128 + (((lane & 7) ^ (lane >> 3)) << 4);
#pragma unroll 1
  for (int it = 0; it < iters; it++) {
    uint32_t u[2][4];
    lds_u4(addr, u[0][0], u[0][1], u[0][2], u[0][3]);
    lds_u4((addr ^ 64) + 512, u[1][0], u[1][1], u[1][2], u[1][3]);
    addr += 1024;
#pragma unroll
    for (int e = 0; e < 8; e++) { a[2 * (e & 3)] += bf_lo(u[e >> 2][e & 3]); a[2 * (e & 3) + 1] += bf_hi(u[e >> 2][e & 3]); }
  }
}
__device__ __forceinline__ void publish_sums(const float (&a)[8], uint4* dst, int lane, uint32_t tag) {
  const bool u8 = lane & 8, u16 = lane & 16;
  float h4[4], h2[2];
#pragma unroll
  for (int e = 0; e < 4; e++) h4[e] = (u8 ? a[4 + e] : a[e]) + __shfl_xor_sync(0xffffffffu, u8 ? a[e] : a[4 + e], 8);
#pragma unroll
  for (int e = 0; e < 2; e++) h2[e] = (u16 ? h4[2 + e] : h4[e]) + __shfl_xor_sync(0xffffffffu, u16 ? h4[e] : h4[2 + e], 16);
  st_msg(dst + (lane & 7) * 4 + (u8 ? 2 : 0) + (u16 ? 1 : 0), __float_as_uint(h2[0]), __float_as_uint(h2[1]), 0u, tag);
}

__device__ __forceinline__ void colsum_helper(const Params& p, uint32_t sb, int m, int n, int lane) {
  const uint32_t tag = __ldcg(p.g->epoch + m * 8 + n) + 1;
  const int mn = m * 8 + n; (void)mn;
#pragma unroll 1
  for (int k = lane; k < 288; k += 32) {
    const uint32_t bb = __ldg(reinterpret_cast<const uint32_t*>(k < 224 ? p.b1 + 448 * n : p.b2 + 128 * n - 448) + k);
    const float sc = k < 224 ? 0.5f : 1.f;
    sts_f2(sb + (k < 224 ? OFF_CSF + k * 16 + 8 : OFF_CSQ + 1536 + (k - 224) * 8), sc * bf_lo(bb), sc * bf_hi(bb));
  }
  __syncwarp();
  if (elect_one()) mbar_arrive(sb + BAR_BIAS);
  bar_sync(BAR_HLP, 160);
  PROF_E(-1, 1);
#pragma unroll 1
  for (int c = 0; c < 7; c++) {
    float a[8] = {0.f, 0.f, 0.f, 0.f, 0.f, 0.f, 0.f, 0.f};
#pragma unroll 1
    for (int h = 0; h < 2; h++) {
      if (elect_one()) {
        mbar_expect_tx(sb + BAR_CSLD + 8, 4096);
        tma_ld2(sb + OFF_HLP, &p.w1c, sb + BAR_CSLD + 8, 448 * n + 64 * c, 64 * m + 32 * h);
        if (c < 6) asm volatile("cp.async.bulk.prefetch.tensor.2d.L2.global [%0, {%1, %2}];" ::"l"(&p.w1c), "r"(448 * n + 64 * c + 64), "r"(64 * m + 32 * h) : "memory");
      }
      mbar_wait(sb + BAR_CSLD + 8, h);
      sum_rows(sb + OFF_HLP, 4, a, lane);
      __syncwarp();
    }
    publish_sums(a, p.g->csp + ((8 + n) * 17 + m) * 224 + c * 32, lane, tag);
  }
  PROF_E(-1, 2);
}

__device__ __forceinline__ void poll_msgs2(const uint4* pa, const uint4* pb, float (&v)[4], uint32_t tag) {
#pragma unroll 1
  for (int it = 0; it < MSG_SPINS; it++) {
    uint32_t x[4], z, ta, tb;
    ld_msg(pa, x[0], x[1], z, ta);
    ld_msg(pb, x[2], x[3], z, tb);
#pragma unroll
    for (int e = 0; e < 4; e++) v[e] = __uint_as_float(x[e]);
    if (__all_sync(0xffffffffu, ta == tag && tb == tag)) break;
  }
}
__device__ __forceinline__ void colsum_total(const Params& p, const Ctx& cx, int mat, uint32_t tag) {
  uint4* base = p.g->csp + (mat * 8 + cx.n) * 17 * 224;
  const int per = 12 + 2 * mat, k = 2 * cx.w + (cx.lane >> 4), ia = per * cx.m + k, ib = per * cx.m + min(k + 8, per - 1);
  float v[4];
  poll_msgs2(base + (cx.lane & 15) * 224 + ia, base + (cx.lane & 15) * 224 + ib, v, tag);
#pragma unroll 1
  for (int d = 1; d < 16; d *= 2)
#pragma unroll
    for (int e = 0; e < 4; e++) v[e] += __shfl_xor_sync(0xffffffffu, v[e], d);
  const bool hi = cx.lane & 1;
  if ((cx.lane & 14) == 0) st_msg(base + 16 * 224 + (hi ? ib : ia), __float_as_uint(hi ? v[2] : v[0]), __float_as_uint(hi ? v[3] : v[1]), 0u, tag);
}
__device__ __forceinline__ void colsum_gather(const Params& p, const Ctx& cx, int mat, uint32_t tag) {
  const uint4* base = p.g->csp + ((mat * 8 + cx.n) * 17 + 16) * 224;
  const int ia = cx.w * 32 + cx.lane, ib = min(ia + 128, 191 + 32 * mat);
  float v[4];
  poll_msgs2(base + ia, base + ib, v, tag);
  const uint32_t tab = cx.sb + (mat ? OFF_CSF : OFF_CSQ);
  sts_f2(tab + (ia << (3 + mat)), v[0], v[1]);
  sts_f2(tab + (ib << (3 + mat)), v[2], v[3]);
}

#define ACC(q, j, e) acc[(q) & 1][4 * (j) + 2 * ((q) >> 1) + (e)]

constexpr uint32_t RING16 = RING_UNITS * (UNIT >> 4);
__device__ __forceinline__ bool tile_split(int i) { return (0xD98 >> i) & 1; }

__device__ __forceinline__ void write_run_desc(uint32_t sb, int i, int step) {
  const int layer = i >= 7, t = i - 7 * layer, part = tile_split(i) ? step : 2;
  const bool wide = tile_wide(t), own = t != 2 && t != 6 && part != 1 && i != 0, second = t == 1 || t == 4;
  const uint32_t z16 = (wide ? 5 : 4) * (UNIT >> 4), a_off = z16 - 1024 + (uint32_t)DESC_A - (uint32_t)DESC_B;
  const int gl = 16 * t + (part == 2 ? 0 : second ? 16 * part - 14 : 4 * part), g0 = layer * STAGES_PER_LAYER + gl;
  const uint32_t s16 = (sb & 0x3FFFF) >> 4, bfirst = (uint32_t)DESC_B + s16;
  const int nkb = t == 6 ? 56 : part == 0 ? 2 : 12 + 2 * part;
  const bool win1 = t == 1 && part != 0;
  const int run = win1 ? WIN1 + 1 : t == 2 ? WIN2 + 1 : nkb;
  const int rest = win1 ? 64 | (nkb - 1 - WIN1) : t == 2 ? 64 | (7 - WIN2) | (8 << 7) : 0;
  const uint32_t blo = bfirst + z16 * (wide ? (gl + (t == 5 ? 3 : 0)) & 3 : (gl + 3) % 5);
  const uint32_t alo = own ? (uint32_t)DESC_A + s16 + (OFF_X >> 4) : blo + a_off;
  const uint32_t aoff = own ? alo + 1024 - (blo == bfirst + RING16 - z16 ? bfirst : blo + z16) : a_off;
  const bool xwait = part == 0 && !second, keep = !(part == 0 || t == 5);
  sts_u4(sb + OFF_RUN + (2 * i + step) * 16, blo, alo, aoff,
         ((g0 / NBAR) & 1) | xwait << 1 | keep << 2 | 8 * (g0 % NBAR) | run << 6 | rest << 12);
}

template <int N>
__device__ __forceinline__ void mainloop(const Params& p, float (&acc)[2][96], uint32_t sb, int i, int step, int mn) {
  constexpr uint32_t Z16 = (2 + N / 64) * (UNIT >> 4);
  constexpr uint32_t A_OFF = Z16 - 1024 + (uint32_t)DESC_A - (uint32_t)DESC_B;
  const int wg = i & 1;
  const uint32_t s16 = (sb & 0x3FFFF) >> 4;
  const uint32_t blast = (uint32_t)DESC_B + s16 + RING16 - Z16, flast = sb + BAR_FULL + 8 * (NBAR - 1);
  uint32_t blo = (uint32_t)DESC_B + s16, alo = blo + A_OFF, aoff = A_OFF, misc = 16 << 6;
  if (N == 128 || i > 0) lds_u4(sb + OFF_RUN + (2 * i + step) * 16, blo, alo, aoff, misc);
  uint32_t keep = misc & 4;
  int run = (misc >> 6) & 63, rest = misc >> 12;
  uint32_t fb = sb + BAR_FULL + (misc & 0x38), ph = misc & 1;
  uint32_t prev = sb + BAR_DUMMY - 8 * NBAR;
  const uint32_t lane_id = (threadIdx.x & 31) | p.zero, rel = pair_offset(sb, lane_id & 1) + 8 * NBAR;
  pin_regs<N / 2>(acc);
  if (N == 128 || i > 0) bar_sync(BAR_ORDER + wg, 256);
  else cluster_wait();
  if (N == 192 && i == 0 && threadIdx.x == 0) PROF_U(8);
  mbar_wait(fb, ph);
    if (misc & 2) mbar_wait(sb + BAR_XGO, N == 192);
  if (step == 0 || !tile_split(i)) PROF_T(4 + i * 4);
#pragma unroll 1
  while (true) {
    const uint64_t da = (DESC_A & ~0xffffffffull) | alo, db = (DESC_B & ~0xffffffffull) | blo;
    asm volatile("wgmma.fence.sync.aligned;" ::: "memory");
    wgmma_ss<N>(acc[0], da, db, keep);
    wgmma_ss<N>(acc[1], da + 64, db, keep);
    keep = 4;
    wgmma_ss<N>(acc[0], da + 2, db + 128);
    wgmma_ss<N>(acc[1], da + 66, db + 128);
    asm volatile("wgmma.commit_group.sync.aligned;" ::: "memory");
    asm volatile("wgmma.wait_group.sync.aligned 1;" ::: "memory");
    PROF_S(jj++);
    if (lane_id < 2) mbar_arrive_cluster(prev + rel);
    prev = fb;
    if (fb == flast) { fb -= 8 * NBAR; ph++; }
    fb += 8;
    if (blo == blast) blo -= RING16;
    blo += Z16;
    alo = blo + aoff;
    aoff = A_OFF;
    run--;
    const bool ready = mbar_test(fb, ph) && run != 0;
    asm volatile("wgmma.fence.sync.aligned;" ::: "memory");
    wgmma_ss<N>(acc[0], da + 4, db + 4 * N);
    wgmma_ss<N>(acc[1], da + 68, db + 4 * N);
    wgmma_ss<N>(acc[0], da + 6, db + 4 * N + 128);
    wgmma_ss<N>(acc[1], da + 70, db + 4 * N + 128);
    asm volatile("wgmma.commit_group.sync.aligned;" ::: "memory");
    if (!ready) {
      if (run == 0) {
        if (rest == 0) break;
        if (rest & 64) {
          bar_arrive(BAR_GO, 256);
          bar_sync(BAR_DONE, 256);
        } else {
          alo = (uint32_t)DESC_A + s16 + (OFF_STG >> 4);
        }
        run = rest & 63;
        rest >>= 7;
      }
      mbar_wait(fb, ph);
    }
  }
  if (i < 13 && !(LATE_O && N == 192 && (misc >> 12))) bar_arrive(BAR_ORDER + (wg ^ 1), 256);
  if (N == 128 && ((0x2244 >> i) & 1)) {
    const Ctx cx = make_ctx(sb, mn);
    const uint32_t xrow = cx.sb + OFF_X + cx.w * 4096 + cx.lane * 128 + ((cx.lane & 7) << 4);
    const bool leader = elect_one();
    asm volatile("wgmma.wait_group.sync.aligned 0;" ::: "memory");
    pin_regs<64>(acc);
    PROF_T(5 + i * 4);
    PROF_E(i, 0);
#pragma unroll
    for (int h = 0; h < 2; h++) {
      if (h == 1 && p.zero != 0) break;
#pragma unroll
      for (int j = 8 * h; j < 8 * h + 8; j++)
        stsm4((xrow ^ ((j & 7) << 4)) + h * 16384, pack_bf16(ACC(0, j, 0), ACC(0, j, 1)), pack_bf16(ACC(1, j, 0), ACC(1, j, 1)),
              pack_bf16(ACC(2, j, 0), ACC(2, j, 1)), pack_bf16(ACC(3, j, 0), ACC(3, j, 1)));
      fence_async_smem();
      __syncwarp();
      if (leader) mbar_arrive(sb + BAR_XRDY + 8 * h);
      if (h == 0 && lane_id < 2) mbar_arrive_cluster(prev + rel);
    }
    PROF_E(i, 4);
    if (i < 13) mbar_wait(sb + BAR_XGO, i == 6);
    if (cx.lane == 0) {
      tma_st2(&p.out_st, cx.sb + OFF_X + 16384 + cx.w * 4096, 128 * cx.n + 64, 128 * cx.m + 32 * cx.w);
      bulk_commit();
      if (i == 13) bulk_wait_read();
    }
    __syncwarp();
    return;
  }
  asm volatile("wgmma.wait_group.sync.aligned 0;" ::: "memory");
  pin_regs<N / 2>(acc);
  if (lane_id < 2) mbar_arrive_cluster(prev + rel);
  PROF_T(5 + i * 4);
  PROF_E(i, 0);
}

__device__ __forceinline__ void write_partial_stats(const Params& p, const Ctx& c, int ln, uint32_t tag) {
  const uint32_t xrow = c.sb + OFF_X + c.w * 4096 + c.lane * 128;
  float s = 0.f, q = 0.f, s1 = 0.f, q1 = 0.f;
#pragma unroll 4
  for (int j = 0; j < 16; j++) {
    uint32_t u[4];
    lds_u4(xrow + (j >> 3) * 16384 + (((j & 7) ^ (c.lane & 7)) << 4), u[0], u[1], u[2], u[3]);
#pragma unroll
    for (int e = 0; e < 4; e++) {
      const float a = bf_lo(u[e]), d = bf_hi(u[e]);
      s += a; q = fmaf(a, a, q);
      s1 += d; q1 = fmaf(d, d, q1);
    }
  }
  s += s1;
  q += q1;
  st_msg(p.g->stats + (ln * 8 + c.n) * SEQ + 128 * c.m + 32 * c.w + c.lane, __float_as_uint(s),
         __float_as_uint(fmaxf(q - s * s * (1.f / 128.f), 0.f)), 0u, tag);
}

__device__ __forceinline__ void finish_row_stats(const Params& p, const Ctx& c, int ln, uint32_t tag) {
  const uint4* src = p.g->stats + ln * 8 * SEQ + 128 * c.m + 32 * c.w + c.lane;
  uint32_t ps[8], pm[8];
#pragma unroll 1
  for (int it = 0; it < MSG_SPINS; it++) {
    uint32_t bad = 0, u, tg;
    if (ln > 1 || it > 0) __nanosleep(STAT_NS);
#pragma unroll
    for (int k = 0; k < 8; k++) { ld_msg(src + k * SEQ, ps[k], pm[k], u, tg); bad |= tg ^ tag; }
    if (__all_sync(0xffffffffu, bad == 0)) break;
  }
  float s = 0.f, m2 = 0.f;
#pragma unroll
  for (int k = 0; k < 8; k++) s += __uint_as_float(ps[k]);
  const float mean = s * (1.f / DM);
#pragma unroll
  for (int k = 0; k < 8; k++) {
    const float d = __uint_as_float(ps[k]) * (1.f / 128.f) - mean;
    m2 += fmaf(128.f * d, d, __uint_as_float(pm[k]));
  }
  sts_f2(c.sb + OFF_ROW + (32 * c.w + c.lane) * 8, rsqrtf(m2 * (1.f / DM) + 1e-5f), mean);
  __syncwarp();
}

__device__ __forceinline__ void attn_scores(const uint32_t* qa, const uint32_t* qb, const uint32_t* k0, const uint32_t* k1,
                                            const uint32_t* k2, const uint32_t* k3, float (&l)[4], const float4& zero,
                                            bool par, bool early) {
  float s[4][4];
#pragma unroll
  for (int kb = 0; kb < 4; kb++) {
    const uint32_t* kk = kb == 0 ? k0 : kb == 1 ? k1 : kb == 2 ? k2 : k3;
    asm volatile("mma.sync.aligned.m16n8k16.row.col.f32.bf16.bf16.f32 {%0,%1,%2,%3}, {%4,%5,%6,%7}, {%8,%9}, {%10,%11,%12,%13};"
                 : "=f"(s[kb][0]), "=f"(s[kb][1]), "=f"(s[kb][2]), "=f"(s[kb][3])
                 : "r"(qa[0]), "r"(qb[0]), "r"(qa[1]), "r"(qb[1]), "r"(kk[0]), "r"(kk[1]), "f"(zero.x), "f"(zero.y),
                   "f"(zero.z), "f"(zero.w));
  }
#pragma unroll
  for (int kb = 0; kb < 4; kb++) {
    const uint32_t* kk = kb == 0 ? k0 : kb == 1 ? k1 : kb == 2 ? k2 : k3;
    mma16816(s[kb], qa[2], qb[2], qa[3], qb[3], kk[2], kk[3]);
  }
  l[0] = par ? s[1][1] : s[1][0];
  l[1] = early ? (par ? s[0][1] : s[0][0]) : (par ? s[2][1] : s[2][0]);
  l[2] = par ? s[2][3] : s[2][2];
  l[3] = early ? (par ? s[1][3] : s[1][2]) : (par ? s[3][3] : s[3][2]);
}

__device__ __forceinline__ void attn_mix(const float (&l)[4], const float (&sc)[4], const float (&off)[4], const float (&rk)[4],
                                         const uint32_t* v0, const uint32_t* v1, const uint32_t* v2, const uint32_t* v3,
                                         uint32_t* olo, uint32_t* ohi, const uint32_t (&sel)[4]) {
  float x[4];
#pragma unroll
  for (int e = 0; e < 4; e++) x[e] = fmaf(l[e], sc[e], off[e]);
  const float ml = quad_max(fmaxf(x[0], x[1])), mh = quad_max(fmaxf(x[2], x[3]));
  x[0] = ex2(x[0] - ml); x[1] = ex2(x[1] - ml);
  x[2] = ex2(x[2] - mh); x[3] = ex2(x[3] - mh);
  const uint32_t pl = pack_bf16(x[0] * rk[0], x[1] * rk[1]), ph = pack_bf16(x[2] * rk[2], x[3] * rk[3]);
  const uint32_t a0 = prmt_u(pl, sel[1]), a1 = prmt_u(pl, sel[3]), a2 = prmt_u(pl, sel[0]), a3 = prmt_u(ph, sel[1]);
  const uint32_t c0 = prmt_u(pl, sel[2]), c1 = prmt_u(ph, sel[0]), c2 = prmt_u(ph, sel[3]), c3 = prmt_u(ph, sel[2]);
  float o[4][4];
#pragma unroll
  for (int jn = 0; jn < 4; jn++) {
    o[jn][0] = o[jn][1] = o[jn][2] = o[jn][3] = 0.f;
    mma16816(o[jn], a0, a1, a2, a3, v0[jn], v1[jn]);
  }
#pragma unroll
  for (int jn = 0; jn < 4; jn++) mma16816(o[jn], c0, c1, c2, c3, v2[jn], v3[jn]);
  const float il = rcp_hw(quad_sum(x[0] + x[1])), ih = rcp_hw(quad_sum(x[2] + x[3]));
#pragma unroll
  for (int jn = 0; jn < 4; jn++) {
    olo[jn] = pack_bf16(o[jn][0] * il, o[jn][1] * il);
    ohi[jn] = pack_bf16(o[jn][2] * ih, o[jn][3] * ih);
  }
}

__device__ __forceinline__ void gelu_epilogue(const Params& p, float (&acc)[2][96], const Ctx& cx, int t) {
  UNPACK_CTX(cx);
  (void)wg;
  float rs[4], rm[4];
#pragma unroll
  for (int q = 0; q < 4; q++) {
    const float2 v = lds_f2(sb + OFF_ROW + (32 * w + 8 * q + (lane >> 2)) * 8);
    rs[q] = 0.5f * v.x;
    rm[q] = -rs[q] * v.y;
  }
  const int col0 = 128 * (t - 3);
  const uint32_t stg = sb + OFF_STG + w * 4096;
  const uint32_t ctab = sb + OFF_CSF + (col0 / 2 + (lane & 3)) * 16, srow = stg + lane * 128 + ((lane & 7) << 4);
  float4 nb = lds_f4(ctab);
#pragma unroll
  for (int c = 0; c < 3; c++) {
    if (c == 2 && t != 5) break;
    uint32_t hp[8][4];
#pragma unroll
    for (int j = 0; j < 8; j++) {
      const float4 cb = nb;
      if (8 * c + j < 23) nb = lds_f4(ctab + (8 * c + j + 1) * 64);
#pragma unroll
      for (int q = 0; q < 4; q++) {
        float y[2];
        const int k = 4 * j + q - GELU_DEP;
        const float rmq = k >= 0 ? chain(rm[q], hp[k >> 2][k & 3], p.zero) : rm[q];
#pragma unroll
        for (int e = 0; e < 2; e++) {
          const float z = fmaf(ACC(q, 8 * c + j, e), rs[q], fmaf(rmq, e ? cb.y : cb.x, e ? cb.w : cb.z));
          const float u = z * fmaf(z * z, 8.f * 0.7978845608028654f * 0.044715f, 2.f * 0.7978845608028654f);
          y[e] = fmaf(z, tanh_hw(u), z);
        }
        hp[j][q] = pack_bf16(y[0], y[1]);
      }
      if (j == STG_WAIT && c > 0) {
        if (lane == 0) bulk_wait_read();
        __syncwarp();
      }
      if (c == 0 || j > STG_WAIT) {
        stsm4(srow ^ (j << 4), hp[j][0], hp[j][1], hp[j][2], hp[j][3]);
      } else if (j == STG_WAIT) {
#pragma unroll
        for (int jj = 0; jj <= STG_WAIT; jj++) stsm4(srow ^ (jj << 4), hp[jj][0], hp[jj][1], hp[jj][2], hp[jj][3]);
      }
    }
    fence_async_smem();
    __syncwarp();
    if (lane == 0) {
      tma_st2(&p.h_st, stg, 448 * n + col0 + 64 * c, 128 * m + 32 * w);
      bulk_commit();
    }
  }
#pragma unroll
  for (int r = 0; r < 16; r++) acc[0][r] = acc[1][r] = 0.f;
}

__device__ __forceinline__ void attn_epilogue(const Params& p, float (&acc)[2][96], const Ctx& cx, int layer, int t, uint32_t tag) {
  UNPACK_CTX(cx);
  const bool par = (lane >> 2) & 1, early = (lane & 3) > (lane >> 3);
  const uint32_t ktab = sb + OFF_ROW + (32 * w + 2 * (lane & 3) + par) * 8, exc = sb + OFF_STG + w * 4096 + lane * 16;
  const int slot = ((layer * 2 + t) * 16 + m) * 8 + n;
  const int mn = m * 8 + n; (void)mn;
  uint32_t Q[4][8], K[4][8], V[4][8], E[36], P[36];
  float kr[6], qr[4];
#pragma unroll
  for (int q = 2; q < 4; q++) {
    kr[2 + q] = lds_f(ktab + 64 * q);
#pragma unroll
    for (int j = 0; j < 8; j++) {
      E[8 * (q - 2) + j] = K[q][j] = pack_bf16(ACC(q, 8 + j, 0), ACC(q, 8 + j, 1));
      E[16 + 2 * j + q - 2] = V[q][j] = movtrans(pack_bf16(ACC(q, 16 + j, 0), ACC(q, 16 + j, 1)));
    }
  }
#pragma unroll
  for (int j = 0; j < 16; j++) K[j >> 3][j & 7] = pack_bf16(ACC(j >> 3, 8 + (j & 7), 0), ACC(j >> 3, 8 + (j & 7), 1));
#pragma unroll
  for (int j = 0; j < 16; j++) asm volatile("" : "+r"(K[j >> 3][j & 7]));
  E[32] = __float_as_uint(kr[4]);
  E[33] = E[34] = E[35] = __float_as_uint(kr[5]);
  if (w < 3) {
#pragma unroll
    for (int k = 0; k < 8; k++) sts_u4(exc + k * 512, E[4 * k], E[4 * k + 1], E[4 * k + 2], E[4 * k + 3]);
  } else {
#pragma unroll
    for (int k = 0; k < 12; k++) st_msg(p.g->halo + slot * 384 + k * 32 + lane, E[3 * k], E[3 * k + 1], E[3 * k + 2], tag);
  }
  bar_arrive(BAR_PAIR + w, 64);
  if (LATE_O && t == 1) bar_arrive(BAR_ORDER + (wg ^ 1), 256);
  PROF_E(7 * layer + t, 1);
#pragma unroll
  for (int q = 0; q < 4; q++) {
    qr[q] = lds_f(sb + OFF_ROW + (32 * w + 8 * q + (lane >> 2)) * 8) * (0.17677669529663687f * 1.4426950408889634f);
#pragma unroll
    for (int j = 0; j < 8; j++) Q[q][j] = pack_bf16(ACC(q, j, 0), ACC(q, j, 1));
    if (q < 2) {
      kr[2 + q] = lds_f(ktab + 64 * q);
#pragma unroll
      for (int j = 0; j < 8; j++) V[q][j] = movtrans(pack_bf16(ACC(q, 16 + j, 0), ACC(q, 16 + j, 1)));
    }
  }
  PROF_E(7 * layer + t, 6);
  bar_sync(BAR_PAIR + ((w + 3) & 3), 64);
  if (w > 0 || m == 0) {
    const uint32_t back = w > 0;
#pragma unroll
    for (int k = 0; k < 8; k++) lds_u4(exc - back * 4096 + k * 512, P[4 * k], P[4 * k + 1], P[4 * k + 2], P[4 * k + 3]);
    P[32] = lds_u(ktab - back * 128);
    P[33] = lds_u(ktab - back * 64);
  } else {
    if (HALO_NS) __nanosleep(HALO_NS);
#pragma unroll 1
    for (int it = 0; it < MSG_SPINS; it++) {
      uint32_t tg, bad = 0;
      if (it > 0) poll_line(reinterpret_cast<const uint32_t*>(p.g->halo + (slot - 8) * 384 + 383) + 3, tag, 1u);
#pragma unroll
      for (int k = 0; k < 12; k++) {
        ld_msg(p.g->halo + (slot - 8) * 384 + k * 32 + lane, P[3 * k], P[3 * k + 1], P[3 * k + 2], tg);
        bad |= tg ^ tag;
      }
      if (__all_sync(0xffffffffu, bad == 0)) break;
    }
  }
  kr[0] = __uint_as_float(P[32]);
  kr[1] = __uint_as_float(P[33]);
  uint32_t PV[2][8];
#pragma unroll
  for (int j = 0; j < 8; j++) { PV[0][j] = P[16 + 2 * j]; PV[1][j] = P[17 + 2 * j]; }
  float rk[2][4], sc[2][4], off[2][4];
#pragma unroll
  for (int g = 0; g < 2; g++) {
    rk[g][0] = kr[2 * g + 1];
    rk[g][1] = early ? kr[2 * g] : kr[2 * g + 2];
    rk[g][2] = kr[2 * g + 2];
    rk[g][3] = early ? kr[2 * g + 1] : kr[2 * g + 3];
#pragma unroll
    for (int e = 0; e < 4; e++) {
      const bool masked = g == 0 && e != 2 && (m | w) == 0 && (e == 0 || early);
      sc[g][e] = masked ? 0.f : rk[g][e] * qr[2 * g + (e >> 1)];
      off[g][e] = masked ? -1e30f : 0.f;
    }
  }
  const uint32_t none = 0x4444u | p.zero, second = par ? 0x3244u : 0x4432u;
  const uint32_t sel[4] = {par ? 0x1044u : 0x4410u, early ? second : none, early ? none : second, none};
  if (w == 0 && elect_one()) asm volatile("prefetch.tensormap [%0];" ::"l"(&p.att_st) : "memory");
  PROF_E(7 * layer + t, 2);
  bar_sync(BAR_GO, 256);
  const float4 zero = lds_f4(sb + OFF_ZERO);
  float l[2][2][4];
  uint32_t O[4][8];
#pragma unroll
  for (int h = 0; h < 2; h++) {
    if (h == 1) {
      Q[2][4] |= __float_as_uint(l[1][0][0]) & p.zero;
      Q[0][4] |= __float_as_uint(l[0][0][0]) & p.zero;
    }
    attn_scores(&Q[2][4 * h], &Q[3][4 * h], &K[0][4 * h], &K[1][4 * h], &K[2][4 * h], &K[3][4 * h], l[1][h], zero, par, early);
    attn_scores(&Q[0][4 * h], &Q[1][4 * h], &P[4 * h], &P[8 + 4 * h], &K[0][4 * h], &K[1][4 * h], l[0][h], zero, par, early);
  }
  const uint32_t stg = sb + OFF_STG + w * 4096, srow = stg + lane * 128 + ((lane & 7) << 4);
#pragma unroll
  for (int h = 0; h < 2; h++) {
    attn_mix(l[1][h], sc[1], off[1], rk[1], &V[0][4 * h], &V[1][4 * h], &V[2][4 * h], &V[3][4 * h], &O[2][4 * h], &O[3][4 * h], sel);
    attn_mix(l[0][h], sc[0], off[0], rk[0], &PV[0][4 * h], &PV[1][4 * h], &V[0][4 * h], &V[1][4 * h], &O[0][4 * h], &O[1][4 * h], sel);
#pragma unroll
    for (int j = 4 * h; j < 4 * h + 4; j++) stsm4(srow ^ (j << 4), O[0][j], O[1][j], O[2][j], O[3][j]);
  }
  if (!HOLD_ATT || t == 0) bar_arrive(BAR_DONE, 256);
  fence_async_smem();
  __syncwarp();
  if (lane == 0) {
    tma_st2(&p.att_st, stg, 128 * n + 64 * t, 128 * m + 32 * w);
    bulk_commit();
  }
}

template <bool PACED>
__device__ __forceinline__ void rank1_update(const Params& p, float (&acc)[2][96], const Ctx& cx, int t) {
  float nm[4];
#pragma unroll
  for (int q = 0; q < 4; q++) nm[q] = t == 6 ? 1.f : -lds_f(cx.sb + OFF_ROW + (32 * cx.w + 8 * q + (cx.lane >> 2)) * 8 + 4);
  const uint32_t ctab = cx.sb + OFF_CSQ + ((t & 3) * 192 + 2 * (cx.lane & 3)) * 4;
#pragma unroll
  for (int j = 0; j < 24; j++) {
    const float2 cs = lds_f2(ctab + j * 32);
#pragma unroll
    for (int q = 0; q < 4; q++) {
      const int k = 4 * j + q - 1;
      const float nq = PACED && k >= 0 ? chain(nm[q], __float_as_uint(ACC(k & 3, k >> 2, 1)), p.zero) : nm[q];
      ACC(q, j, 0) = fmaf(nq, cs.x, ACC(q, j, 0));
      ACC(q, j, 1) = fmaf(nq, cs.y, ACC(q, j, 1));
    }
  }
}

__device__ __forceinline__ void finish_stores(uint32_t sb, int i) {
  const int t = i >= 7 ? i - 7 : i;
  if ((threadIdx.x & 31) == 0) {
    bulk_wait_all();
    mbar_arrive(sb + BAR_PUB + 8 * (t < 2 ? t : t + 1));
  }
  __syncwarp();
  if (i < 12) bar_arrive(BAR_GUARD + ((i & 1) ^ 1), 256);
}

__device__ __forceinline__ bool consumer_tile(const Params& p, float (&acc)[2][96], uint32_t sb0, int i, int mn) {
  const int layer = i >= 7, t = i - 7 * layer, wg = i & 1;
  const bool resid = t == 2 || t == 6;
  {
    if (resid) {
      const Ctx cx = make_ctx(sb0, mn);
      const uint32_t xrow = cx.sb + OFF_X + cx.w * 4096 + cx.lane * 128;
      const uint32_t sel_lo = 0x1044u | p.zero, sel_hi = 0x3244u | p.zero;
#pragma unroll
      for (int j = 0; j < 16; j++) {
        uint32_t r[4];
        ldsm4(xrow + (j >> 3) * 16384 + (((j & 7) ^ (cx.lane & 7)) << 4), r[0], r[1], r[2], r[3]);
#pragma unroll
        for (int q = 0; q < 4; q++) {
          ACC(q, j, 0) = prmt_f(r[q], sel_lo);
          ACC(q, j, 1) = prmt_f(r[q], sel_hi);
        }
      }
    }
    if (t >= 5 || i == 7) finish_stores(sb0, i - 2);
#pragma unroll 1
    for (int step = !tile_split(i);; step++) {
      if (step == 1 && (t == 1 || t == 4)) {
        const Ctx cx = make_ctx(sb0, mn);
        if (i == 1) {
          const uint32_t epoch = __ldcg(p.g->epoch + (mn & 127));
          cluster_wait();
          asm volatile("st.shared.u32 [%0], %1;" ::"r"(sb0 + OFF_TAG), "r"(epoch + 1) : "memory");
        }
        if (i != 1 && cx.lane == 0) {
          bulk_wait_all();
          mbar_arrive(sb0 + BAR_PUB + (t == 4 ? 24 : 64));
        }
        __syncwarp();
        const uint32_t tag = lds_u(cx.sb + OFF_TAG);
        const int ln = (i + 1) >> 2;
#pragma unroll 1
        for (int r = 0; r < 2; r++) {
          if (i == 1) {
            if (cx.w < 3) {
              float a[8] = {0.f, 0.f, 0.f, 0.f, 0.f, 0.f, 0.f, 0.f};
              mbar_wait(sb0 + BAR_CSLD, r);
#pragma unroll 1
              for (int h = 0; h < 2; h++) sum_rows(cx.sb + OFF_STG + h * 12288 + cx.w * 4096, 4, a, cx.lane);
              publish_sums(a, p.g->csp + (cx.n * 17 + cx.m) * 224 + (3 * r + cx.w) * 32, cx.lane, tag);
            }
            PROF_E(-1, 5 + r);
          }
          if (r == 1) break;
          if (i == 1) {
            bar_sync(BAR_WG + 1, 128);
            if (cx.w == 3 && elect_one()) {
              mbar_expect_tx(sb0 + BAR_CSLD, 24576);
              tma_ld3(sb0 + OFF_STG, &p.wqkv, sb0 + BAR_CSLD, 128 * cx.n + 64, 64 * cx.m, 0);
              tma_ld3(sb0 + OFF_STG + 12288, &p.wqkv, sb0 + BAR_CSLD, 128 * cx.n + 64, 64 * cx.m + 32, 0);
            }
            mbar_wait(sb0 + BAR_XRDY, 0);
            mbar_wait(sb0 + BAR_XRDY + 8, 0);
          }
          write_partial_stats(p, cx, ln, tag);
          PROF_E(i - 2, 8);
        }
        if (i == 1) {
          bar_arrive(BAR_HLP, 160);
          bar_sync(BAR_INIT, 160);
        }
        if (i <= 4) colsum_total(p, cx, ln, tag);
        PROF_E(i - 2, 9);
        if (i != 1) bar_sync(BAR_GUARD + wg, 256);
        finish_row_stats(p, cx, ln, tag);
        PROF_E(i - 2, 10);
        if (i == 4) {
          colsum_gather(p, cx, 1, tag);
          mbar_wait(sb0 + BAR_BIAS, 0);
        }
        PROF_E(i - 2, 15);
        bar_arrive(BAR_GUARD + (wg ^ 1), 256);
      }
      if (step == 2 && !resid) bar_sync(BAR_GUARD + wg, 256);
      if (step == 2 && i == 0) {
        colsum_gather(p, make_ctx(sb0, mn), 0, lds_u(sb0 + OFF_TAG));
        bar_sync(BAR_WG, 128);
      }
      if (i == 1) {
        if (step == 2) rank1_update<false>(p, acc, make_ctx(sb0, mn), t);
      } else if (t + step == 2 || t == 6) {
        rank1_update<true>(p, acc, make_ctx(sb0, mn), t);
      }
      if (step == 2) break;
      if (tile_wide(t)) {
        mainloop<192>(p, acc, sb0, i, step, mn);
      } else {
        mainloop<128>(p, acc, sb0, i, step, mn);
        if (resid) return false;
      }
    }
    if (t < 2) return true;
    gelu_epilogue(p, acc, make_ctx(sb0, mn), t);
    PROF_E(i, 4);
    return false;
  }
}

__global__ void __cluster_dims__(2, 1, 1) __launch_bounds__(384, 1) fused_layers_kernel(const int by_smid, const __nv_bfloat16* x_p, const __nv_bfloat16* wqkv_p,
                                                                  const __grid_constant__ Params p) {
  extern __shared__ __align__(1024) uint8_t smem_raw[];
  const uint32_t sb = uniform((uint32_t)__cvta_generic_to_shared(smem_raw));
  const int tid = threadIdx.x, lane = tid & 31, warp = uniform(tid >> 5), wg = warp >> 2, w = warp & 3;

  int mn;
  {
    int id = blockIdx.x;
    if (by_smid) asm volatile("mov.u32 %0, %%smid;" : "=r"(id));
    else if (id >= 120) id += 4;
    const int c = id >> 1;
    int g, j;
    if (c < 32) { g = c & 7; j = c >> 3; }
    else if (c < 60) { g = 1 + (c - 32) % 7; j = 4 + (c - 32) / 7; }
    else { g = 0; j = c - 58; }
    const int r = blockIdx.x & 1;
    mn = (g * 2 + r) * 8 + j;
    if (c == 60 || c == 61) {
      if (tid < 32) {
        const uint32_t tag = __ldcg(p.g->epoch + NCTA + (id & 3)) + 1;
#pragma unroll 1
        for (int mm = 0; mm < 16; mm++) poll_line(p.g->flags + mm * 32 + (lane & 7), 32 * tag, 0xffu);
        if (tid == 0) p.g->epoch[NCTA + (id & 3)] = tag;
      }
      return;
    }
  }
  const int m = mn >> 3, n = mn & 7;
  if (tid == 256) PROF_U(1);
  if (tid >= 382) asm volatile("prefetch.global.L2 [%0];" ::"l"(tid & 1 ? wqkv_p + 128 * n : x_p + 128 * m * DM));
  if (wg < 2) {
    cluster_arrive();
    asm volatile("setmaxnreg.inc.sync.aligned.u32 232;");
    const int id = mn | (warp << 7);
#pragma unroll 1
    for (int i = wg;; i += 2) {
      float acc[2][96];
#pragma unroll
      for (int r = 0; r < 96; r++) acc[0][r] = acc[1][r] = 0.f;
      pin_regs<96>(acc);
#pragma unroll 1
      while (!consumer_tile(p, acc, sb, i, id)) {
        PROF_T(6 + i * 4);
        i += 2;
        if (i >= 14) goto all_done;
      }
      attn_epilogue(p, acc, make_ctx(sb, id), i >= 7, i >= 7 ? i - 7 : i, lds_u(sb + OFF_TAG));
      PROF_E(i, 4);
      finish_stores(sb, i);
      if (HOLD_ATT && (i == 1 || i == 8)) bar_arrive(BAR_DONE, 256);
      PROF_E(i, 5);
      PROF_T(6 + i * 4);
    }
  all_done:
    if (wg == 0) {
      finish_stores(sb, 12);
    } else {
      cluster_arrive();
      cluster_wait();
    }
  } else {
    asm volatile("setmaxnreg.dec.sync.aligned.u32 40;");
    if (w != 0) {
      if (w == 1 && elect_one()) {
        mbar_init(sb + BAR_FULL + 32, 2);
#pragma unroll
        for (int k = 0; k < NBAR; k++) mbar_init(sb + BAR_EMPTY + 8 * k, 8);
#pragma unroll
        for (int k = 0; k < 3; k++) mbar_init(sb + BAR_XRDY + 8 * k, 4);
#pragma unroll
        for (int k = 0; k < 9; k++) mbar_init(sb + BAR_PUB + 8 * k, 4);
#pragma unroll
        for (int k = 0; k < 4; k++) mbar_init(sb + BAR_CSLD + 8 * k, 1);
        sts_f2(sb + OFF_ZERO, 0.f, 0.f);
        sts_f2(sb + OFF_ZERO + 8, 0.f, 0.f);
        asm volatile("fence.mbarrier_init.release.cluster;" ::: "memory");
      }
      __syncwarp();
      cluster_arrive();
      if (w == 2) {
        if (lane < 28) write_run_desc(sb, lane >> 1, lane & 1);
        bar_arrive(BAR_INIT, 160);
      }
      cluster_wait();
      if (w == 1) producer<true>(p, sb, m, n, lane);
      else if (w == 3) colsum_helper(p, sb, m, n, lane);
      else if (elect_one()) publisher(p, sb, m, n);
    } else {
      const bool leader = elect_one();
      if (leader) {
#pragma unroll
        for (int k = 0; k < 4; k++) mbar_init(sb + BAR_FULL + 8 * k, 2);
        asm volatile("fence.mbarrier_init.release.cluster;" ::: "memory");
        PROF_U(4);
      }
      __syncwarp();
      cluster_arrive();
      if (leader) {
#pragma unroll 1
        for (int k = 0; k < 4; k++) {
          const uint32_t fb = sb + BAR_FULL + 8 * k;
          mbar_expect_tx(fb, 16384);
          tma_ld2(sb + (5 * k + 3) * UNIT, &p.xin, fb, 64 * k, 128 * m);
          mbar_expect_tx(fb, 3 * UNIT);
          tma_ld3(sb + 5 * k * UNIT, &p.wqkv, fb, 128 * n, 64 * k, 0);
          tma_ld3(sb + 5 * k * UNIT + 12288, &p.wqkv, fb, 128 * n, 64 * k + 32, 0);
        }
        PROF_U(5);
      }
      __syncwarp();
      cluster_wait();
      if (leader) {
        mbar_expect_tx(sb + BAR_CSLD, 24576);
        tma_ld3(sb + OFF_STG, &p.wqkv, sb + BAR_CSLD, 128 * n, 64 * m, 0);
        tma_ld3(sb + OFF_STG + 12288, &p.wqkv, sb + BAR_CSLD, 128 * n, 64 * m + 32, 0);
#pragma unroll 1
        for (int h = 0; h < 2; h++) {
          const uint32_t xr = sb + BAR_XRDY + 8 * h;
          mbar_expect_tx(xr, 16384);
          tma_ld2(sb + OFF_X + h * 16384, &p.xin, xr, 128 * n + 64 * h, 128 * m);
          asm volatile("mbarrier.arrive.shared::cta.b64 _, [%0], 3;" ::"r"(xr) : "memory");
        }
        PROF_U(6);
      }
      __syncwarp();
      producer<false>(p, sb, m, n, lane);
    }
  }
}

typedef CUresult (*EncodeFn)(CUtensorMap*, CUtensorMapDataType, cuuint32_t, void*, const cuuint64_t*, const cuuint64_t*,
                             const cuuint32_t*, const cuuint32_t*, CUtensorMapInterleave, CUtensorMapSwizzle,
                             CUtensorMapL2promotion, CUtensorMapFloatOOBfill);

#define PROMO2 CU_TENSOR_MAP_L2_PROMOTION_L2_128B
#define PROMO3 CU_TENSOR_MAP_L2_PROMOTION_L2_128B
void make_2d(EncodeFn enc, CUtensorMap* m, const void* ptr, uint64_t cols, uint64_t rows, uint32_t box_rows) {
  cuuint64_t d[2] = {cols, rows}, st[1] = {cols * 2};
  cuuint32_t b[2] = {64, box_rows}, e[2] = {1, 1};
  enc(m, CU_TENSOR_MAP_DATA_TYPE_BFLOAT16, 2, const_cast<void*>(ptr), d, st, b, e, CU_TENSOR_MAP_INTERLEAVE_NONE,
      CU_TENSOR_MAP_SWIZZLE_128B, PROMO2, CU_TENSOR_MAP_FLOAT_OOB_FILL_NONE);
}
void make_3d(EncodeFn enc, CUtensorMap* m, const void* ptr, uint64_t d0, uint64_t rows, uint64_t d2, uint64_t row_bytes,
             uint64_t chunk_bytes, uint32_t box_chunks) {
  cuuint64_t d[3] = {d0, rows, d2}, st[2] = {row_bytes, chunk_bytes};
  cuuint32_t b[3] = {64, 32, box_chunks}, e[3] = {1, 1, 1};
  enc(m, CU_TENSOR_MAP_DATA_TYPE_BFLOAT16, 3, const_cast<void*>(ptr), d, st, b, e, CU_TENSOR_MAP_INTERLEAVE_NONE,
      CU_TENSOR_MAP_SWIZZLE_128B, PROMO3, CU_TENSOR_MAP_FLOAT_OOB_FILL_NONE);
}

}

extern "C" void kernel_launch(void* const* d_in, const int* in_sizes, int n_in, void* d_out, int out_size) {
  (void)in_sizes; (void)n_in; (void)out_size;
  static EncodeFn enc = nullptr;
  static void *att = nullptr, *hbuf = nullptr, *scratch = nullptr;
  static int by_smid = 0;
  if (!enc) {
    void* fn = nullptr;
    cudaDriverEntryPointQueryResult q;
    cudaGetDriverEntryPoint("cuTensorMapEncodeTiled", &fn, cudaEnableDefault, &q);
    enc = (EncodeFn)fn;
    cudaGetSymbolAddress(&att, g_att);
    cudaGetSymbolAddress(&hbuf, g_h);
    cudaGetSymbolAddress(&scratch, g_scratch);
    cudaFuncSetAttribute(fused_layers_kernel, cudaFuncAttributeMaxDynamicSharedMemorySize, SMEM_BYTES);
    int sms = 0, clusters = 0, dev = 0;
    cudaGetDevice(&dev);
    cudaDeviceGetAttribute(&sms, cudaDevAttrMultiProcessorCount, dev);
    cudaLaunchConfig_t cfg = {};
    cfg.gridDim = dim3(132);
    cfg.blockDim = dim3(384);
    cfg.dynamicSmemBytes = SMEM_BYTES;
    cudaLaunchAttribute at[1];
    at[0].id = cudaLaunchAttributeClusterDimension;
    at[0].val.clusterDim.x = 2; at[0].val.clusterDim.y = 1; at[0].val.clusterDim.z = 1;
    cfg.attrs = at;
    cfg.numAttrs = 1;
    if (cudaOccupancyMaxActiveClusters(&clusters, fused_layers_kernel, &cfg) != cudaSuccess) (void)cudaGetLastError();
    by_smid = sms == 132 && clusters == 66;
  }
  Params p;
  make_2d(enc, &p.xin, d_in[0], DM, SEQ, 128);
  make_2d(enc, &p.out, d_out, DM, SEQ, 128);
  make_2d(enc, &p.att, att, DM, SEQ, 128);
  make_2d(enc, &p.h, hbuf, FF, SEQ, 128);
  make_2d(enc, &p.out_st, d_out, DM, SEQ, 32);
  make_2d(enc, &p.att_st, att, DM, SEQ, 32);
  make_2d(enc, &p.h_st, hbuf, FF, SEQ, 32);
  make_2d(enc, &p.w1c, d_in[4], FF, DM, 32);
  make_3d(enc, &p.wqkv, d_in[1], DM, DM, 3, 3 * DM * 2, DM * 2, 3);
  make_3d(enc, &p.wo, d_in[2], 64, DM, DM / 64, DM * 2, 128, 2);
  make_3d(enc, &p.w1a, d_in[4], 64, DM, FF / 64, FF * 2, 128, 3);
  make_3d(enc, &p.w1b, d_in[4], 64, DM, FF / 64, FF * 2, 128, 2);
  make_3d(enc, &p.w2, d_in[6], 64, FF, DM / 64, DM * 2, 128, 2);
  p.b1 = (const __nv_bfloat16*)d_in[5];
  p.b2 = (const __nv_bfloat16*)d_in[7];
  p.g = (Scratch*)scratch;
  p.zero = 0;
  fused_layers_kernel<<<by_smid ? 132 : NCTA, 384, SMEM_BYTES>>>(by_smid, (const __nv_bfloat16*)d_in[0], (const __nv_bfloat16*)d_in[1], p);
}
```

```cpp
#include <cuda_runtime.h>
#include <cuda_bf16.h>
#include <cuda.h>
#include <stdint.h>

namespace {

constexpr int SEQ = 2048, DM = 1024, FF = 3584;
constexpr int NCTA = 128;
constexpr int NBAR = 5;

constexpr uint32_t RING_UNITS = 20, UNIT = 8192;
constexpr uint32_t OFF_X   = RING_UNITS * UNIT;
constexpr uint32_t OFF_STG = OFF_X + 32768;
constexpr uint32_t OFF_HLP = OFF_STG + 16384;
constexpr uint32_t OFF_RUN = OFF_STG + 24576;
constexpr uint32_t OFF_CSQ = OFF_RUN + 512;
constexpr uint32_t OFF_CSF = OFF_CSQ + 2048;
constexpr uint32_t OFF_ROW = OFF_CSF + 3584;
constexpr uint32_t OFF_BAR = OFF_ROW + 1024;
constexpr uint32_t SMEM_BYTES = OFF_BAR + 384;
constexpr uint32_t BAR_FULL = OFF_BAR, BAR_EMPTY = OFF_BAR + 8 * NBAR;
constexpr uint32_t BAR_XRDY = OFF_BAR + 80;
constexpr uint32_t BAR_DUMMY = OFF_BAR + 96, OFF_TAG = OFF_BAR + 104, OFF_ZERO = OFF_BAR + 112;
constexpr uint32_t BAR_PUB = OFF_BAR + 128;
constexpr uint32_t BAR_CSLD = OFF_BAR + 200;
constexpr uint32_t BAR_XGO = OFF_BAR + 224;
constexpr uint32_t BAR_BIAS = OFF_BAR + 216;

constexpr uint64_t DESC_A = (1ull << 62) | ((uint64_t)(2048 >> 4) << 32) | (1ull << 16);
constexpr uint64_t DESC_B = (1ull << 62) | ((uint64_t)(1024 >> 4) << 32) | ((uint64_t)(4096 >> 4) << 16);

constexpr int BAR_INIT = 0, BAR_ORDER = 1, BAR_GUARD = 3, BAR_WG = 5, BAR_GO = 7, BAR_DONE = 8, BAR_HLP = 9, BAR_PAIR = 11;
#define GELU_DEP 2
#define MAP 2
#define LATE_O 1
#define HALO_NS 200
#define STG_WAIT 5
#define STAT_NS 800
#define HOLDM 3
#define BDELAY 100
#define WIN1 8
#define WIN2 2

struct Scratch {
  uint4 stats[4 * 8 * SEQ];
  uint4 halo[2 * 2 * 16 * 8 * 384];
  uint4 csp[2 * 8 * 17 * 224];
  uint32_t flags[16 * 32];
  uint32_t epoch[NCTA + 4];
};

struct Params {
  CUtensorMap xin, out, att, h, wqkv, wo, w1a, w1b, w2, att_st, h_st, w1c;
  const __nv_bfloat16 *b1, *b2;
  Scratch* g;
  uint32_t zero;
};

__device__ __nv_bfloat16 g_att[SEQ * DM];
__device__ __nv_bfloat16 g_h[SEQ * FF];
__device__ Scratch g_scratch;
#define PROF_T(idx)
#define PROF_U(k)
#define PROF_S(g)
#define PROF_E(i, k)

__device__ __forceinline__ void mbar_init(uint32_t bar, int cnt) {
  asm volatile("mbarrier.init.shared::cta.b64 [%0], %1;" ::"r"(bar), "r"(cnt));
}
__device__ __forceinline__ void mbar_expect_tx(uint32_t bar, uint32_t bytes) {
  asm volatile("mbarrier.arrive.expect_tx.shared::cta.b64 _, [%0], %1;" ::"r"(bar), "r"(bytes) : "memory");
}
__device__ __forceinline__ void mbar_arrive(uint32_t bar) {
  asm volatile("mbarrier.arrive.shared::cta.b64 _, [%0];" ::"r"(bar) : "memory");
}
__device__ __forceinline__ bool mbar_test(uint32_t bar, uint32_t parity) {
  uint32_t ok;
  asm volatile("{\n.reg .pred p;\nmbarrier.test_wait.parity.shared::cta.b64 p, [%1], %2;\nselp.u32 %0, 1, 0, p;\n}"
               : "=r"(ok) : "r"(bar), "r"(parity) : "memory");
  return ok;
}
__device__ __forceinline__ void mbar_wait(uint32_t bar, uint32_t parity) {
  asm volatile(
      "{\n.reg .pred p;\n.reg .u32 it;\nmov.u32 it, 0;\n"
      "WAIT_LOOP:\n"
      "mbarrier.try_wait.parity.shared::cta.b64 p, [%0], %1;\n"
      "@p bra WAIT_DONE;\n"
      "add.u32 it, it, 1;\n"
      "setp.lt.u32 p, it, 0x400000;\n"
      "@p bra WAIT_LOOP;\n"
      "trap;\n"
      "WAIT_DONE:\n}"
      ::"r"(bar), "r"(parity) : "memory");
}
__device__ __forceinline__ void bar_sync(int id, int n) { asm volatile("bar.sync %0, %1;" ::"r"(id), "r"(n) : "memory"); }
__device__ __forceinline__ void bar_arrive(int id, int n) { asm volatile("bar.arrive %0, %1;" ::"r"(id), "r"(n) : "memory"); }
__device__ __forceinline__ void tma_ld2(uint32_t dst, const CUtensorMap* m, uint32_t bar, int c0, int c1) {
  asm volatile("cp.async.bulk.tensor.2d.shared::cluster.global.mbarrier::complete_tx::bytes [%0], [%1, {%3, %4}], [%2];"
               ::"r"(dst), "l"(m), "r"(bar), "r"(c0), "r"(c1) : "memory");
}
__device__ __forceinline__ void tma_ld3(uint32_t dst, const CUtensorMap* m, uint32_t bar, int c0, int c1, int c2) {
  asm volatile("cp.async.bulk.tensor.3d.shared::cluster.global.mbarrier::complete_tx::bytes [%0], [%1, {%3, %4, %5}], [%2];"
               ::"r"(dst), "l"(m), "r"(bar), "r"(c0), "r"(c1), "r"(c2) : "memory");
}
__device__ __forceinline__ void tma_ld3_pair(uint32_t dst, const CUtensorMap* m, uint32_t bar, int c0, int c1, int c2) {
  asm volatile("cp.async.bulk.tensor.3d.shared::cluster.global.mbarrier::complete_tx::bytes.multicast::cluster"
               " [%0], [%1, {%3, %4, %5}], [%2], %6;"
               ::"r"(dst), "l"(m), "r"(bar), "r"(c0), "r"(c1), "r"(c2), "h"((uint16_t)3) : "memory");
}
__device__ __forceinline__ uint32_t pair_offset(uint32_t sb, uint32_t rank) {
  uint32_t r;
  asm volatile("mapa.shared::cluster.u32 %0, %1, %2;" : "=r"(r) : "r"(sb), "r"(rank));
  return r - sb;
}
__device__ __forceinline__ void mbar_arrive_cluster(uint32_t bar) {
  asm volatile("mbarrier.arrive.shared::cluster.b64 _, [%0];" ::"r"(bar) : "memory");
}
__device__ __forceinline__ void cluster_arrive() { asm volatile("barrier.cluster.arrive.relaxed;" ::: "memory"); }
__device__ __forceinline__ void cluster_wait() { asm volatile("barrier.cluster.wait.acquire;" ::: "memory"); }
__device__ __forceinline__ void tma_st2(const CUtensorMap* m, uint32_t src, int c0, int c1) {
  asm volatile("cp.async.bulk.tensor.2d.global.shared::cta.bulk_group [%0, {%2, %3}], [%1];"
               ::"l"(m), "r"(src), "r"(c0), "r"(c1) : "memory");
}
__device__ __forceinline__ void bulk_commit() { asm volatile("cp.async.bulk.commit_group;" ::: "memory"); }
__device__ __forceinline__ void bulk_wait_read() { asm volatile("cp.async.bulk.wait_group.read 0;" ::: "memory"); }
__device__ __forceinline__ void bulk_wait_all() { asm volatile("cp.async.bulk.wait_group 0;" ::: "memory"); }
__device__ __forceinline__ void fence_async_smem() { asm volatile("fence.proxy.async.shared::cta;" ::: "memory"); }
__device__ __forceinline__ void fence_async_global() { asm volatile("fence.proxy.async.global;" ::: "memory"); }
__device__ __forceinline__ void st_relaxed(uint32_t* p, uint32_t v) {
  asm volatile("st.relaxed.gpu.global.u32 [%0], %1;" ::"l"(p), "r"(v) : "memory");
}
__device__ __forceinline__ void st_msg(uint4* p, uint32_t a, uint32_t b, uint32_t c, uint32_t tag) {
  asm volatile("{\n.reg .b128 v;\nmov.b128 v, {%1, %2, %3, %4};\nst.relaxed.gpu.global.b128 [%0], v;\n}"
               ::"l"(p), "r"(a), "r"(b), "r"(c), "r"(tag) : "memory");
}
__device__ __forceinline__ void ld_msg(const uint4* p, uint32_t& a, uint32_t& b, uint32_t& c, uint32_t& tag) {
  asm volatile("{\n.reg .b128 v;\nld.relaxed.gpu.global.b128 v, [%4];\nmov.b128 {%0, %1, %2, %3}, v;\n}"
               : "=r"(a), "=r"(b), "=r"(c), "=r"(tag) : "l"(p) : "memory");
}
__device__ __forceinline__ bool elect_one() {
  uint32_t ok;
  asm volatile("{\n.reg .pred p;\nelect.sync _|p, 0xffffffff;\nselp.u32 %0, 1, 0, p;\n}" : "=r"(ok));
  return ok;
}
__device__ __forceinline__ int uniform(int v) { return __shfl_sync(0xffffffffu, v, 0); }
__device__ __forceinline__ uint32_t pack_bf16(float lo, float hi) {
  uint32_t r;
  asm("cvt.rn.bf16x2.f32 %0, %1, %2;" : "=r"(r) : "f"(hi), "f"(lo));
  return r;
}
__device__ __forceinline__ uint32_t prmt_u(uint32_t a, uint32_t sel) {
  uint32_t r;
  asm("prmt.b32 %0, %1, 0, %2;" : "=r"(r) : "r"(a), "r"(sel));
  return r;
}
__device__ __forceinline__ float prmt_f(uint32_t a, uint32_t sel) {
  float r;
  asm("{\n.reg .b32 t;\nprmt.b32 t, %1, 0, %2;\nmov.b32 %0, t;\n}" : "=f"(r) : "r"(a), "r"(sel));
  return r;
}
__device__ __forceinline__ float bf_lo(uint32_t v) { return __uint_as_float(v << 16); }
__device__ __forceinline__ float bf_hi(uint32_t v) { return __uint_as_float(v & 0xffff0000u); }
__device__ __forceinline__ void stsm4(uint32_t addr, uint32_t r0, uint32_t r1, uint32_t r2, uint32_t r3) {
  asm volatile("stmatrix.sync.aligned.m8n8.x4.shared.b16 [%0], {%1, %2, %3, %4};"
               ::"r"(addr), "r"(r0), "r"(r1), "r"(r2), "r"(r3) : "memory");
}
__device__ __forceinline__ void ldsm4(uint32_t addr, uint32_t& r0, uint32_t& r1, uint32_t& r2, uint32_t& r3) {
  asm volatile("ldmatrix.sync.aligned.m8n8.x4.shared.b16 {%0, %1, %2, %3}, [%4];"
               : "=r"(r0), "=r"(r1), "=r"(r2), "=r"(r3) : "r"(addr) : "memory");
}
__device__ __forceinline__ uint32_t movtrans(uint32_t a) {
  uint32_t d;
  asm volatile("movmatrix.sync.aligned.m8n8.trans.b16 %0, %1;" : "=r"(d) : "r"(a));
  return d;
}
__device__ __forceinline__ void mma16816(float (&c)[4], uint32_t a0, uint32_t a1, uint32_t a2, uint32_t a3, uint32_t b0, uint32_t b1) {
  asm volatile("mma.sync.aligned.m16n8k16.row.col.f32.bf16.bf16.f32 {%0,%1,%2,%3}, {%4,%5,%6,%7}, {%8,%9}, {%0,%1,%2,%3};"
               : "+f"(c[0]), "+f"(c[1]), "+f"(c[2]), "+f"(c[3])
               : "r"(a0), "r"(a1), "r"(a2), "r"(a3), "r"(b0), "r"(b1));
}
__device__ __forceinline__ float2 lds_f2(uint32_t a) {
  float2 v;
  asm volatile("ld.shared.v2.f32 {%0, %1}, [%2];" : "=f"(v.x), "=f"(v.y) : "r"(a) : "memory");
  return v;
}
__device__ __forceinline__ float4 lds_f4(uint32_t a) {
  float4 v;
  asm volatile("ld.shared.v4.f32 {%0, %1, %2, %3}, [%4];" : "=f"(v.x), "=f"(v.y), "=f"(v.z), "=f"(v.w) : "r"(a) : "memory");
  return v;
}
__device__ __forceinline__ float lds_f(uint32_t a) {
  float v;
  asm volatile("ld.shared.f32 %0, [%1];" : "=f"(v) : "r"(a) : "memory");
  return v;
}
__device__ __forceinline__ uint32_t lds_u(uint32_t a) {
  uint32_t v;
  asm volatile("ld.shared.u32 %0, [%1];" : "=r"(v) : "r"(a) : "memory");
  return v;
}
__device__ __forceinline__ void sts_f2(uint32_t a, float x, float y) {
  asm volatile("st.shared.v2.f32 [%0], {%1, %2};" ::"r"(a), "f"(x), "f"(y) : "memory");
}
__device__ __forceinline__ void sts_u4(uint32_t a, uint32_t x, uint32_t y, uint32_t z, uint32_t w) {
  asm volatile("st.shared.v4.u32 [%0], {%1, %2, %3, %4};" ::"r"(a), "r"(x), "r"(y), "r"(z), "r"(w) : "memory");
}
__device__ __forceinline__ void lds_u4(uint32_t a, uint32_t& x, uint32_t& y, uint32_t& z, uint32_t& w) {
  asm volatile("ld.shared.v4.u32 {%0, %1, %2, %3}, [%4];" : "=r"(x), "=r"(y), "=r"(z), "=r"(w) : "r"(a) : "memory");
}
__device__ __forceinline__ float ex2(float x) {
  float y;
  asm("ex2.approx.ftz.f32 %0, %1;" : "=f"(y) : "f"(x));
  return y;
}
__device__ __forceinline__ float rcp_hw(float x) {
  float y;
  asm("rcp.approx.ftz.f32 %0, %1;" : "=f"(y) : "f"(x));
  return y;
}
__device__ __forceinline__ float tanh_hw(float x) {
  float y;
  asm("tanh.approx.f32 %0, %1;" : "=f"(y) : "f"(x));
  return y;
}
__device__ __forceinline__ float quad_sum(float v) {
  v += __shfl_xor_sync(0xffffffffu, v, 1);
  return v + __shfl_xor_sync(0xffffffffu, v, 2);
}
__device__ __forceinline__ float quad_max(float v) {
  v = fmaxf(v, __shfl_xor_sync(0xffffffffu, v, 1));
  return fmaxf(v, __shfl_xor_sync(0xffffffffu, v, 2));
}

template <int N> __device__ __forceinline__ void wgmma_ss(float (&d)[96], uint64_t da, uint64_t db, uint32_t keep = 1);
template <> __device__ __forceinline__ void wgmma_ss<128>(float (&d)[96], uint64_t da, uint64_t db, uint32_t keep) {
  asm volatile(
      "{\n.reg .pred p;\nsetp.ne.u32 p, %66, 0;\n"
      "wgmma.mma_async.sync.aligned.m64n128k16.f32.bf16.bf16 {%0, %1, %2, %3, %4, %5, %6, %7, %8, %9, %10, %11, %12, %13, %14, %15, %16, %17, %18, %19, %20, %21, %22, %23, %24, %25, %26, %27, %28, %29, %30, %31, %32, %33, %34, %35, %36, %37, %38, %39, %40, %41, %42, %43, %44, %45, %46, %47, %48, %49, %50, %51, %52, %53, %54, %55, %56, %57, %58, %59, %60, %61, %62, %63}, %64, %65, p, 1, 1, 0, 1;\n}"
      : "+f"(d[0]), "+f"(d[1]), "+f"(d[2]), "+f"(d[3]), "+f"(d[4]), "+f"(d[5]), "+f"(d[6]), "+f"(d[7]), "+f"(d[8]), "+f"(d[9]), "+f"(d[10]), "+f"(d[11]), "+f"(d[12]), "+f"(d[13]), "+f"(d[14]), "+f"(d[15]), "+f"(d[16]), "+f"(d[17]), "+f"(d[18]), "+f"(d[19]), "+f"(d[20]), "+f"(d[21]), "+f"(d[22]), "+f"(d[23]), "+f"(d[24]), "+f"(d[25]), "+f"(d[26]), "+f"(d[27]), "+f"(d[28]), "+f"(d[29]), "+f"(d[30]), "+f"(d[31]), "+f"(d[32]), "+f"(d[33]), "+f"(d[34]), "+f"(d[35]), "+f"(d[36]), "+f"(d[37]), "+f"(d[38]), "+f"(d[39]), "+f"(d[40]), "+f"(d[41]), "+f"(d[42]), "+f"(d[43]), "+f"(d[44]), "+f"(d[45]), "+f"(d[46]), "+f"(d[47]), "+f"(d[48]), "+f"(d[49]), "+f"(d[50]), "+f"(d[51]), "+f"(d[52]), "+f"(d[53]), "+f"(d[54]), "+f"(d[55]), "+f"(d[56]), "+f"(d[57]), "+f"(d[58]), "+f"(d[59]), "+f"(d[60]), "+f"(d[61]), "+f"(d[62]), "+f"(d[63])
      : "l"(da), "l"(db), "r"(keep));
}

template <> __device__ __forceinline__ void wgmma_ss<192>(float (&d)[96], uint64_t da, uint64_t db, uint32_t keep) {
  asm volatile(
      "{\n.reg .pred p;\nsetp.ne.u32 p, %98, 0;\n"
      "wgmma.mma_async.sync.aligned.m64n192k16.f32.bf16.bf16 {%0, %1, %2, %3, %4, %5, %6, %7, %8, %9, %10, %11, %12, %13, %14, %15, %16, %17, %18, %19, %20, %21, %22, %23, %24, %25, %26, %27, %28, %29, %30, %31, %32, %33, %34, %35, %36, %37, %38, %39, %40, %41, %42, %43, %44, %45, %46, %47, %48, %49, %50, %51, %52, %53, %54, %55, %56, %57, %58, %59, %60, %61, %62, %63, %64, %65, %66, %67, %68, %69, %70, %71, %72, %73, %74, %75, %76, %77, %78, %79, %80, %81, %82, %83, %84, %85, %86, %87, %88, %89, %90, %91, %92, %93, %94, %95}, %96, %97, p, 1, 1, 0, 1;\n}"
      : "+f"(d[0]), "+f"(d[1]), "+f"(d[2]), "+f"(d[3]), "+f"(d[4]), "+f"(d[5]), "+f"(d[6]), "+f"(d[7]), "+f"(d[8]), "+f"(d[9]), "+f"(d[10]), "+f"(d[11]), "+f"(d[12]), "+f"(d[13]), "+f"(d[14]), "+f"(d[15]), "+f"(d[16]), "+f"(d[17]), "+f"(d[18]), "+f"(d[19]), "+f"(d[20]), "+f"(d[21]), "+f"(d[22]), "+f"(d[23]), "+f"(d[24]), "+f"(d[25]), "+f"(d[26]), "+f"(d[27]), "+f"(d[28]), "+f"(d[29]), "+f"(d[30]), "+f"(d[31]), "+f"(d[32]), "+f"(d[33]), "+f"(d[34]), "+f"(d[35]), "+f"(d[36]), "+f"(d[37]), "+f"(d[38]), "+f"(d[39]), "+f"(d[40]), "+f"(d[41]), "+f"(d[42]), "+f"(d[43]), "+f"(d[44]), "+f"(d[45]), "+f"(d[46]), "+f"(d[47]), "+f"(d[48]), "+f"(d[49]), "+f"(d[50]), "+f"(d[51]), "+f"(d[52]), "+f"(d[53]), "+f"(d[54]), "+f"(d[55]), "+f"(d[56]), "+f"(d[57]), "+f"(d[58]), "+f"(d[59]), "+f"(d[60]), "+f"(d[61]), "+f"(d[62]), "+f"(d[63]), "+f"(d[64]), "+f"(d[65]), "+f"(d[66]), "+f"(d[67]), "+f"(d[68]), "+f"(d[69]), "+f"(d[70]), "+f"(d[71]), "+f"(d[72]), "+f"(d[73]), "+f"(d[74]), "+f"(d[75]), "+f"(d[76]), "+f"(d[77]), "+f"(d[78]), "+f"(d[79]), "+f"(d[80]), "+f"(d[81]), "+f"(d[82]), "+f"(d[83]), "+f"(d[84]), "+f"(d[85]), "+f"(d[86]), "+f"(d[87]), "+f"(d[88]), "+f"(d[89]), "+f"(d[90]), "+f"(d[91]), "+f"(d[92]), "+f"(d[93]), "+f"(d[94]), "+f"(d[95])
      : "l"(da), "l"(db), "r"(keep));
}

template <int R>
__device__ __forceinline__ void pin_regs(float (&a)[2][96]) {
#pragma unroll
  for (int m = 0; m < 2; m++)
#pragma unroll
    for (int i = 0; i < R; i++) asm volatile("" : "+f"(a[m][i])::"memory");
}

struct Ctx {
  uint32_t sb;
  int m, n, wg, w, lane;
};
__device__ __forceinline__ Ctx make_ctx(uint32_t sb, int id) {
  int lane;
  asm volatile("mov.u32 %0, %%laneid;" : "=r"(lane));
  asm volatile("" : "+r"(id), "+r"(sb));
  return Ctx{sb, (id >> 3) & 15, id & 7, id >> 9, (id >> 7) & 3, lane};
}
#define UNPACK_CTX(c) const uint32_t sb = c.sb; const int m = c.m, n = c.n, wg = c.wg, w = c.w, lane = c.lane

__device__ __forceinline__ uint32_t poll_line(const uint32_t* word, uint32_t target, uint32_t need) {
  uint32_t v;
  asm volatile(
      "{\n.reg .pred p;\n.reg .u32 it, m;\n.reg .s32 d;\nmov.u32 it, 0;\n"
      "POLL_LOOP:\n"
      "ld.relaxed.gpu.global.u32 %0, [%1];\n"
      "sub.s32 d, %0, %2;\n"
      "setp.ge.s32 p, d, 0;\n"
      "vote.sync.ballot.b32 m, p, 0xffffffff;\n"
      "and.b32 m, m, %3;\n"
      "setp.eq.u32 p, m, %3;\n"
      "@p bra.uni POLL_DONE;\n"
      "add.u32 it, it, 1;\n"
      "setp.lt.u32 p, it, 0x400000;\n"
      "@p bra.uni POLL_LOOP;\n"
      "trap;\n"
      "POLL_DONE:\n}"
      : "=&r"(v) : "l"(word), "r"(target), "r"(need) : "memory");
  return v;
}
__device__ __forceinline__ uint32_t ld_relaxed(const uint32_t* p) {
  uint32_t v;
  asm volatile("ld.relaxed.gpu.global.u32 %0, [%1];" : "=r"(v) : "l"(p) : "memory");
  return v;
}
__device__ __forceinline__ float chain(float x, uint32_t on, uint32_t zero) {
  return __uint_as_float(__float_as_uint(x) | (on & zero));
}
constexpr int MSG_SPINS = 1 << 20;

constexpr int STAGES_PER_LAYER = 152;
__device__ __forceinline__ int nib(uint64_t v, int i) { return (int)(v >> (4 * i)) & 15; }
__device__ __forceinline__ bool tile_wide(int t) { return (0x23 >> t) & 1; }
__device__ __forceinline__ void weight_coords(const Params& p, int t, int n, const CUtensorMap*& map, int& c0, int& c2) {
  map = &p.wqkv + nib(0x4233100ull, t);
  c0 = t < 2 ? 128 * n + 64 * t : 0;
  c2 = t < 2 ? 0 : (t == 2 || t == 6) ? 2 * n : 7 * n + 2 * t - 6;
}

template <bool IS_A>
__device__ __forceinline__ void producer(const Params& p, uint32_t sb, int m, int n, int lane) {
  const uint32_t low = (1u << (4 * n)) - 1, others = (0x6543210u & low) | (0x7654321u & ~low);
  const uint64_t order_x = (uint64_t)(others * 2 + 0x1111111u) << 36 | (uint64_t)others * 2 << 8 | (n * 0x22 + 0x10);
  int inflight = 4, cur = 0;
  uint32_t fb = sb + BAR_FULL + 32, rb = sb + BAR_EMPTY, rph = 0, pos = 0, tag32 = 0, seen = 0;
  const uint32_t fend = sb + BAR_FULL + 8 * NBAR, rend = sb + BAR_EMPTY + 8 * NBAR;
  const uint32_t* word = p.g->flags + m * 32 + (lane < 16 ? lane >> 1 : lane & 7);
#pragma unroll 1
  for (int sg = 1; sg < 22; sg++) {
    const int layer = sg >= 11, s = sg == 1 ? 2 : sg == 2 ? 1 : sg - 11 * layer;
    const int t = nib(0x65434321010ull, s), kind = nib(0x32110031100ull, s);
    const bool wide = tile_wide(t);
    const uint32_t bbytes = wide ? 3 * UNIT : 2 * UNIT, base = sb + (IS_A ? bbytes : (m & 1) * (bbytes / 2));
    if (IS_A && kind == 0) {
      if (sg == 2) seen = tag32 = (__ldcg(p.g->epoch + m * 8 + n) + 1) << 5;
#pragma unroll 1
      for (int k = 0; k < 2; k++) {
#pragma unroll 1
        for (; inflight > (wide ? 3 : 4); inflight--) {
          mbar_wait(rb, rph);
          rb += 8;
          if (rb == rend) { rb -= 8 * NBAR; rph ^= 1; }
        }
        if (elect_one()) mbar_arrive(fb);
        inflight++;
        fb += 8;
        if (fb == fend) fb -= 8 * NBAR;
        pos += bbytes + 2 * UNIT;
        if (pos >= RING_UNITS * UNIT) pos -= RING_UNITS * UNIT;
      }
      continue;
    }
    const int mul = t == 6 ? 448 : t == 2 ? 128 : 64, count = sg == 1 ? 12 : 2 * nib(0x4871ull, kind);
    uint64_t order0 = sg == 1 ? 0xFEDCBA987654ull : kind == 3 ? 0x76543210u : order_x >> (8 * (kind & 1));
    uint32_t special = (s == 4 || s == 10) ? 0x10 : s == 9 ? 0xF : s == 0;
    if (IS_A) special |= (kind & 1 ? 0 : 3) | (count >= 4 ? 1u << (count - 4) : 0);
    if (s >= 9) pos = (s + 6) * UNIT;
    const CUtensorMap* map;
    int c0 = 0, c2 = 0, ev = 0;
    if (IS_A) {
      map = &p.xin + (t == 2 ? 2 : t == 6 ? 3 : sg >= 4);
      ev = 9 * layer + (t < 2 ? 0 : t == 2 ? 1 : t < 6 ? 4 : 5);
      if (elect_one()) asm volatile("prefetch.tensormap [%0];" ::"l"(map) : "memory");
    } else {
      weight_coords(p, t, n, map, c0, c2);
    }
#pragma unroll 1
    for (int add = 0; add < mul; add += 64) {
      uint64_t order = order0;
      const int need = kind == 3 ? ev : ev - 1 + (lane & 1), sh = kind == 3 ? 16 : 0;
      uint32_t ready = IS_A ? __ballot_sync(0xffffffffu, cur >= need) >> sh : 0;
#pragma unroll 1
      for (int k = 0; k < count; k++) {
        const int code = order & 15, kc = code * mul + add;
        order >>= 4;
        if ((special >> k) & 1) {
          const int lag = wide ? (s == 9 && k == 2 ? 2 : 3) : ((s == 4 || s == 10) && add == 0 && k < 4) ? 3 : 4;
#pragma unroll 1
          for (; inflight > lag; inflight--) {
            mbar_wait(rb, rph);
            rb += 8;
            if (rb == rend) { rb -= 8 * NBAR; rph ^= 1; }
          }
          inflight++;
          if (IS_A) {
            if (kind == 3 ? t == 2 && add + k == 64 : !(kind & 1) && k < 2) {
              if (t == 2) mbar_wait(sb + BAR_PUB + 8, layer);
              if (elect_one()) mbar_arrive(fb);
              goto next_stage;
            }
            if (k == count - 4 && sg >= 3) seen = ld_relaxed(word);
          }
        } else {
          mbar_wait(rb, rph);
          rb += 8;
          if (rb == rend) { rb -= 8 * NBAR; rph ^= 1; }
        }
        if (IS_A && !((ready >> code) & 1)) {
          cur = max(cur, (int)(seen - tag32));
          ready = __ballot_sync(0xffffffffu, cur >= need) >> sh;
          if (!((ready >> code) & 1)) {
            cur = (int)(poll_line(word, tag32 + need, 1u << (code + sh)) - tag32);
            ready = __ballot_sync(0xffffffffu, cur >= need) >> sh;
          }
          asm volatile("fence.acquire.gpu;" ::: "memory");
          fence_async_global();
          seen = ld_relaxed(word);
        }
        if (elect_one()) {
          if (!IS_A) tma_ld3_pair(base + pos, map, fb, c0, kc + 32 * (m & 1), c2);
          else tma_ld2(base + pos, map, fb, kc, 128 * m);
          mbar_expect_tx(fb, IS_A ? 16384 : bbytes);
        }
      next_stage:
        fb += 8;
        if (fb == fend) fb -= 8 * NBAR;
        pos += bbytes + 2 * UNIT;
        if (pos >= RING_UNITS * UNIT) pos -= RING_UNITS * UNIT;
      }
      special = !IS_A ? 0 : t == 2 ? 1 : add == 128 ? 0x10 : 0;
      if (t == 2) order0 = others << 4 | n;
      if (IS_A && (t == 2 || add == 64 || add == 192)) ev++;
    }
  }
}

__device__ __forceinline__ void publisher(const Params& p, uint32_t sb, int m, int n) {
  const uint32_t tag = __ldcg(p.g->epoch + m * 8 + n) + 1;
  uint32_t* word = p.g->flags + m * 32 + n;
  const int mn = m * 8 + n; (void)mn;
  st_relaxed(word, 32 * tag);
#pragma unroll 1
  for (int c = 0; c < 17; c++) {
    const int e = c >= 9 ? c - 9 : c;
    if (e == 2 || e == 7) {
      asm volatile("prefetch.tensormap [%0];" ::"l"(&p.out) : "memory");
      mbar_wait(sb + BAR_XRDY, e == 2);
      tma_st2(&p.out, sb + OFF_X, 128 * n, 128 * m);
      bulk_commit();
      if (c == 16) break;
      mbar_wait(sb + BAR_XRDY + 8, e == 2);
      bulk_wait_all();
      mbar_arrive(sb + BAR_XGO);
      PROF_E(7 * (c >= 9) + (e < 4 ? 2 : 6), 11);
    } else {
      mbar_wait(sb + BAR_PUB + 8 * e, c >= 9);
    }
    asm volatile("fence.release.gpu;" ::: "memory");
    asm volatile("red.relaxed.gpu.global.add.u32 [%0], 1;" ::"l"(word) : "memory");
    PROF_E(7 * (c >= 9) + nib(0x665432210ull, e), (0x108 >> e) & 1 ? 14 : 12);
  }
  p.g->epoch[m * 8 + n] = tag;
  bulk_wait_read();
}

__device__ __forceinline__ void sum_rows(uint32_t buf, int iters, float (&a)[8], int lane) {
  uint32_t addr = buf + (lane >> 3) * 128 + (((lane & 7) ^ (lane >> 3)) << 4);
#pragma unroll 1
  for (int it = 0; it < iters; it++) {
    uint32_t u[2][4];
    lds_u4(addr, u[0][0], u[0][1], u[0][2], u[0][3]);
    lds_u4((addr ^ 64) + 512, u[1][0], u[1][1], u[1][2], u[1][3]);
    addr += 1024;
#pragma unroll
    for (int e = 0; e < 8; e++) { a[2 * (e & 3)] += bf_lo(u[e >> 2][e & 3]); a[2 * (e & 3) + 1] += bf_hi(u[e >> 2][e & 3]); }
  }
}
__device__ __forceinline__ void publish_sums(const float (&a)[8], uint4* dst, int lane, uint32_t tag) {
  const bool u8 = lane & 8, u16 = lane & 16;
  float h4[4], h2[2];
#pragma unroll
  for (int e = 0; e < 4; e++) h4[e] = (u8 ? a[4 + e] : a[e]) + __shfl_xor_sync(0xffffffffu, u8 ? a[e] : a[4 + e], 8);
#pragma unroll
  for (int e = 0; e < 2; e++) h2[e] = (u16 ? h4[2 + e] : h4[e]) + __shfl_xor_sync(0xffffffffu, u16 ? h4[e] : h4[2 + e], 16);
  st_msg(dst + (lane & 7) * 4 + (u8 ? 2 : 0) + (u16 ? 1 : 0), __float_as_uint(h2[0]), __float_as_uint(h2[1]), 0u, tag);
}

__device__ __forceinline__ void colsum_helper(const Params& p, uint32_t sb, int m, int n, int lane) {
  const uint32_t tag = __ldcg(p.g->epoch + m * 8 + n) + 1;
  const int mn = m * 8 + n; (void)mn;
#pragma unroll 1
  for (int k = lane; k < 288; k += 32) {
    const uint32_t bb = __ldg(reinterpret_cast<const uint32_t*>(k < 224 ? p.b1 + 448 * n : p.b2 + 128 * n - 448) + k);
    const float sc = k < 224 ? 0.5f : 1.f;
    sts_f2(sb + (k < 224 ? OFF_CSF + k * 16 + 8 : OFF_CSQ + 1536 + (k - 224) * 8), sc * bf_lo(bb), sc * bf_hi(bb));
  }
  __syncwarp();
  if (elect_one()) mbar_arrive(sb + BAR_BIAS);
  bar_sync(BAR_HLP, 160);
  PROF_E(-1, 1);
#pragma unroll 1
  for (int c = 0; c < 7; c++) {
    float a[8] = {0.f, 0.f, 0.f, 0.f, 0.f, 0.f, 0.f, 0.f};
#pragma unroll 1
    for (int h = 0; h < 2; h++) {
      if (elect_one()) {
        mbar_expect_tx(sb + BAR_CSLD + 8, 4096);
        tma_ld2(sb + OFF_HLP, &p.w1c, sb + BAR_CSLD + 8, 448 * n + 64 * c, 64 * m + 32 * h);
        if (c < 6) asm volatile("cp.async.bulk.prefetch.tensor.2d.L2.global [%0, {%1, %2}];" ::"l"(&p.w1c), "r"(448 * n + 64 * c + 64), "r"(64 * m + 32 * h) : "memory");
      }
      mbar_wait(sb + BAR_CSLD + 8, h);
      sum_rows(sb + OFF_HLP, 4, a, lane);
      __syncwarp();
    }
    publish_sums(a, p.g->csp + ((8 + n) * 17 + m) * 224 + c * 32, lane, tag);
  }
  PROF_E(-1, 2);
  if (elect_one()) {
#pragma unroll 1
    for (int k = 0; k < 4; k++) {
      if (k < 3) {
        mbar_wait(sb + BAR_XGO, k & 1);
        __nanosleep(BDELAY);
      } else {
        mbar_wait(sb + BAR_XRDY + 8, 0);
      }
      tma_st2(&p.out, sb + OFF_X + 16384, 128 * n + 64, 128 * m);
      bulk_commit();
      bulk_wait_all();
      asm volatile("mbarrier.arrive.shared::cta.b64 _, [%0], 4;" ::"r"(sb + BAR_PUB + (k & 1 ? 64 : 24)) : "memory");
    }
  }
}

__device__ __forceinline__ void poll_msgs2(const uint4* pa, const uint4* pb, float (&v)[4], uint32_t tag) {
#pragma unroll 1
  for (int it = 0; it < MSG_SPINS; it++) {
    uint32_t x[4], z, ta, tb;
    ld_msg(pa, x[0], x[1], z, ta);
    ld_msg(pb, x[2], x[3], z, tb);
#pragma unroll
    for (int e = 0; e < 4; e++) v[e] = __uint_as_float(x[e]);
    if (__all_sync(0xffffffffu, ta == tag && tb == tag)) break;
  }
}
__device__ __forceinline__ void colsum_total(const Params& p, const Ctx& cx, int mat, uint32_t tag) {
  uint4* base = p.g->csp + (mat * 8 + cx.n) * 17 * 224;
  const int per = 12 + 2 * mat, k = 2 * cx.w + (cx.lane >> 4), ia = per * cx.m + k, ib = per * cx.m + min(k + 8, per - 1);
  float v[4];
  poll_msgs2(base + (cx.lane & 15) * 224 + ia, base + (cx.lane & 15) * 224 + ib, v, tag);
#pragma unroll 1
  for (int d = 1; d < 16; d *= 2)
#pragma unroll
    for (int e = 0; e < 4; e++) v[e] += __shfl_xor_sync(0xffffffffu, v[e], d);
  const bool hi = cx.lane & 1;
  if ((cx.lane & 14) == 0) st_msg(base + 16 * 224 + (hi ? ib : ia), __float_as_uint(hi ? v[2] : v[0]), __float_as_uint(hi ? v[3] : v[1]), 0u, tag);
}
__device__ __forceinline__ void colsum_gather(const Params& p, const Ctx& cx, int mat, uint32_t tag) {
  const uint4* base = p.g->csp + ((mat * 8 + cx.n) * 17 + 16) * 224;
  const int ia = cx.w * 32 + cx.lane, ib = min(ia + 128, 191 + 32 * mat);
  float v[4];
  poll_msgs2(base + ia, base + ib, v, tag);
  const uint32_t tab = cx.sb + (mat ? OFF_CSF : OFF_CSQ);
  sts_f2(tab + (ia << (3 + mat)), v[0], v[1]);
  sts_f2(tab + (ib << (3 + mat)), v[2], v[3]);
}

#define ACC(q, j, e) acc[(q) & 1][4 * (j) + 2 * ((q) >> 1) + (e)]

constexpr uint32_t RING16 = RING_UNITS * (UNIT >> 4);
__device__ __forceinline__ bool tile_split(int i) { return (0xD98 >> i) & 1; }

__device__ __forceinline__ void write_run_desc(uint32_t sb, int i, int step) {
  const int layer = i >= 7, t = i - 7 * layer, part = tile_split(i) ? step : 2;
  const bool wide = tile_wide(t), own = t != 2 && t != 6 && part != 1 && i != 0, second = t == 1 || t == 4;
  const uint32_t z16 = (wide ? 5 : 4) * (UNIT >> 4), a_off = z16 - 1024 + (uint32_t)DESC_A - (uint32_t)DESC_B;
  const int gl = 16 * t + (part == 2 ? 0 : second ? 16 * part - 14 : 4 * part), g0 = layer * STAGES_PER_LAYER + gl;
  const uint32_t s16 = (sb & 0x3FFFF) >> 4, bfirst = (uint32_t)DESC_B + s16;
  const int nkb = t == 6 ? 56 : part == 0 ? 2 : 12 + 2 * part;
  const bool win1 = t == 1 && part != 0;
  const int run = win1 ? WIN1 + 1 : t == 2 ? WIN2 + 1 : nkb;
  const int rest = win1 ? 64 | (nkb - 1 - WIN1) : t == 2 ? 64 | (7 - WIN2) | (8 << 7) : 0;
  const uint32_t blo = bfirst + z16 * (wide ? (gl + (t == 5 ? 3 : 0)) & 3 : (gl + 3) % 5);
  const uint32_t alo = own ? (uint32_t)DESC_A + s16 + (OFF_X >> 4) : blo + a_off;
  const uint32_t aoff = own ? alo + 1024 - (blo == bfirst + RING16 - z16 ? bfirst : blo + z16) : a_off;
  const bool xwait = part == 0 && !second, keep = !(part == 0 || t == 5);
  sts_u4(sb + OFF_RUN + (2 * i + step) * 16, blo, alo, aoff,
         ((g0 / NBAR) & 1) | xwait << 1 | keep << 2 | 8 * (g0 % NBAR) | run << 6 | rest << 12);
}

template <int N>
__device__ __forceinline__ void mainloop(const Params& p, float (&acc)[2][96], uint32_t sb, int i, int step, int mn) {
  constexpr uint32_t Z16 = (2 + N / 64) * (UNIT >> 4);
  constexpr uint32_t A_OFF = Z16 - 1024 + (uint32_t)DESC_A - (uint32_t)DESC_B;
  const int wg = i & 1;
  const uint32_t s16 = (sb & 0x3FFFF) >> 4;
  const uint32_t blast = (uint32_t)DESC_B + s16 + RING16 - Z16, flast = sb + BAR_FULL + 8 * (NBAR - 1);
  uint32_t blo = (uint32_t)DESC_B + s16, alo = blo + A_OFF, aoff = A_OFF, misc = 16 << 6;
  if (N == 128 || i > 0) lds_u4(sb + OFF_RUN + (2 * i + step) * 16, blo, alo, aoff, misc);
  uint32_t keep = misc & 4;
  int run = (misc >> 6) & 63, rest = misc >> 12;
  uint32_t fb = sb + BAR_FULL + (misc & 0x38), ph = misc & 1;
  uint32_t prev = sb + BAR_DUMMY - 8 * NBAR;
  const uint32_t lane_id = (threadIdx.x & 31) | p.zero, rel = pair_offset(sb, lane_id & 1) + 8 * NBAR;
  pin_regs<N / 2>(acc);
  if (N == 128 || i > 0) bar_sync(BAR_ORDER + wg, 256);
  else cluster_wait();
  if (N == 192 && i == 0 && threadIdx.x == 0) PROF_U(8);
  mbar_wait(fb, ph);
    if (misc & 2) {
    if ((HOLDM >> (N == 192)) & 1) mbar_wait(sb + BAR_XGO, N == 192);
    else mbar_wait(sb + BAR_XRDY + 8, N == 128);
  }
  if (step == 0 || !tile_split(i)) PROF_T(4 + i * 4);
#pragma unroll 1
  while (true) {
    const uint64_t da = (DESC_A & ~0xffffffffull) | alo, db = (DESC_B & ~0xffffffffull) | blo;
    asm volatile("wgmma.fence.sync.aligned;" ::: "memory");
    wgmma_ss<N>(acc[0], da, db, keep);
    wgmma_ss<N>(acc[1], da + 64, db, keep);
    keep = 4;
    wgmma_ss<N>(acc[0], da + 2, db + 128);
    wgmma_ss<N>(acc[1], da + 66, db + 128);
    asm volatile("wgmma.commit_group.sync.aligned;" ::: "memory");
    asm volatile("wgmma.wait_group.sync.aligned 1;" ::: "memory");
    PROF_S(jj++);
    if (lane_id < 2) mbar_arrive_cluster(prev + rel);
    prev = fb;
    if (fb == flast) { fb -= 8 * NBAR; ph++; }
    fb += 8;
    if (blo == blast) blo -= RING16;
    blo += Z16;
    alo = blo + aoff;
    aoff = A_OFF;
    run--;
    const bool ready = mbar_test(fb, ph) && run != 0;
    asm volatile("wgmma.fence.sync.aligned;" ::: "memory");
    wgmma_ss<N>(acc[0], da + 4, db + 4 * N);
    wgmma_ss<N>(acc[1], da + 68, db + 4 * N);
    wgmma_ss<N>(acc[0], da + 6, db + 4 * N + 128);
    wgmma_ss<N>(acc[1], da + 70, db + 4 * N + 128);
    asm volatile("wgmma.commit_group.sync.aligned;" ::: "memory");
    if (!ready) {
      if (run == 0) {
        if (rest == 0) break;
        if (rest & 64) {
          bar_arrive(BAR_GO, 256);
          bar_sync(BAR_DONE, 256);
        } else {
          alo = (uint32_t)DESC_A + s16 + (OFF_STG >> 4);
        }
        run = rest & 63;
        rest >>= 7;
      }
      mbar_wait(fb, ph);
    }
  }
  if (i < 13 && !(LATE_O && N == 192 && (misc >> 12))) bar_arrive(BAR_ORDER + (wg ^ 1), 256);
  if (N == 128 && ((0x2244 >> i) & 1)) {
    const Ctx cx = make_ctx(sb, mn);
    const uint32_t xrow = cx.sb + OFF_X + cx.w * 4096 + cx.lane * 128 + ((cx.lane & 7) << 4);
    const bool leader = elect_one();
    asm volatile("wgmma.wait_group.sync.aligned 0;" ::: "memory");
    pin_regs<64>(acc);
    PROF_T(5 + i * 4);
    PROF_E(i, 0);
#pragma unroll
    for (int h = 0; h < 2; h++) {
      if (h == 1 && p.zero != 0) break;
#pragma unroll
      for (int j = 8 * h; j < 8 * h + 8; j++)
        stsm4((xrow ^ ((j & 7) << 4)) + h * 16384, pack_bf16(ACC(0, j, 0), ACC(0, j, 1)), pack_bf16(ACC(1, j, 0), ACC(1, j, 1)),
              pack_bf16(ACC(2, j, 0), ACC(2, j, 1)), pack_bf16(ACC(3, j, 0), ACC(3, j, 1)));
      fence_async_smem();
      __syncwarp();
      if (leader) mbar_arrive(sb + BAR_XRDY + 8 * h);
      if (h == 0 && lane_id < 2) mbar_arrive_cluster(prev + rel);
    }
    PROF_E(i, 4);
    return;
  }
  asm volatile("wgmma.wait_group.sync.aligned 0;" ::: "memory");
  pin_regs<N / 2>(acc);
  if (lane_id < 2) mbar_arrive_cluster(prev + rel);
  PROF_T(5 + i * 4);
  PROF_E(i, 0);
}

__device__ __forceinline__ void write_partial_stats(const Params& p, const Ctx& c, int ln, uint32_t tag) {
  const uint32_t xrow = c.sb + OFF_X + c.w * 4096 + c.lane * 128;
  float s = 0.f, q = 0.f, s1 = 0.f, q1 = 0.f;
#pragma unroll 4
  for (int j = 0; j < 16; j++) {
    uint32_t u[4];
    lds_u4(xrow + (j >> 3) * 16384 + (((j & 7) ^ (c.lane & 7)) << 4), u[0], u[1], u[2], u[3]);
#pragma unroll
    for (int e = 0; e < 4; e++) {
      const float a = bf_lo(u[e]), d = bf_hi(u[e]);
      s += a; q = fmaf(a, a, q);
      s1 += d; q1 = fmaf(d, d, q1);
    }
  }
  s += s1;
  q += q1;
  st_msg(p.g->stats + (ln * 8 + c.n) * SEQ + 128 * c.m + 32 * c.w + c.lane, __float_as_uint(s),
         __float_as_uint(fmaxf(q - s * s * (1.f / 128.f), 0.f)), 0u, tag);
}

__device__ __forceinline__ void finish_row_stats(const Params& p, const Ctx& c, int ln, uint32_t tag) {
  const uint4* src = p.g->stats + ln * 8 * SEQ + 128 * c.m + 32 * c.w + c.lane;
  uint32_t ps[8], pm[8];
#pragma unroll 1
  for (int it = 0; it < MSG_SPINS; it++) {
    uint32_t bad = 0, u, tg;
    if (ln > 1 || it > 0) __nanosleep(STAT_NS);
#pragma unroll
    for (int k = 0; k < 8; k++) { ld_msg(src + k * SEQ, ps[k], pm[k], u, tg); bad |= tg ^ tag; }
    if (__all_sync(0xffffffffu, bad == 0)) break;
  }
  float s = 0.f, m2 = 0.f;
#pragma unroll
  for (int k = 0; k < 8; k++) s += __uint_as_float(ps[k]);
  const float mean = s * (1.f / DM);
#pragma unroll
  for (int k = 0; k < 8; k++) {
    const float d = __uint_as_float(ps[k]) * (1.f / 128.f) - mean;
    m2 += fmaf(128.f * d, d, __uint_as_float(pm[k]));
  }
  sts_f2(c.sb + OFF_ROW + (32 * c.w + c.lane) * 8, rsqrtf(m2 * (1.f / DM) + 1e-5f), mean);
  __syncwarp();
}

__device__ __forceinline__ void attn_scores(const uint32_t* qa, const uint32_t* qb, const uint32_t* k0, const uint32_t* k1,
                                            const uint32_t* k2, const uint32_t* k3, float (&l)[4], const float4& zero,
                                            bool par, bool early) {
  float s[4][4];
#pragma unroll
  for (int kb = 0; kb < 4; kb++) {
    const uint32_t* kk = kb == 0 ? k0 : kb == 1 ? k1 : kb == 2 ? k2 : k3;
    asm volatile("mma.sync.aligned.m16n8k16.row.col.f32.bf16.bf16.f32 {%0,%1,%2,%3}, {%4,%5,%6,%7}, {%8,%9}, {%10,%11,%12,%13};"
                 : "=f"(s[kb][0]), "=f"(s[kb][1]), "=f"(s[kb][2]), "=f"(s[kb][3])
                 : "r"(qa[0]), "r"(qb[0]), "r"(qa[1]), "r"(qb[1]), "r"(kk[0]), "r"(kk[1]), "f"(zero.x), "f"(zero.y),
                   "f"(zero.z), "f"(zero.w));
  }
#pragma unroll
  for (int kb = 0; kb < 4; kb++) {
    const uint32_t* kk = kb == 0 ? k0 : kb == 1 ? k1 : kb == 2 ? k2 : k3;
    mma16816(s[kb], qa[2], qb[2], qa[3], qb[3], kk[2], kk[3]);
  }
  l[0] = par ? s[1][1] : s[1][0];
  l[1] = early ? (par ? s[0][1] : s[0][0]) : (par ? s[2][1] : s[2][0]);
  l[2] = par ? s[2][3] : s[2][2];
  l[3] = early ? (par ? s[1][3] : s[1][2]) : (par ? s[3][3] : s[3][2]);
}

__device__ __forceinline__ void attn_mix(const float (&l)[4], const float (&sc)[4], const float (&off)[4], const float (&rk)[4],
                                         const uint32_t* v0, const uint32_t* v1, const uint32_t* v2, const uint32_t* v3,
                                         uint32_t* olo, uint32_t* ohi, const uint32_t (&sel)[4]) {
  float x[4];
#pragma unroll
  for (int e = 0; e < 4; e++) x[e] = fmaf(l[e], sc[e], off[e]);
  const float ml = quad_max(fmaxf(x[0], x[1])), mh = quad_max(fmaxf(x[2], x[3]));
  x[0] = ex2(x[0] - ml); x[1] = ex2(x[1] - ml);
  x[2] = ex2(x[2] - mh); x[3] = ex2(x[3] - mh);
  const uint32_t pl = pack_bf16(x[0] * rk[0], x[1] * rk[1]), ph = pack_bf16(x[2] * rk[2], x[3] * rk[3]);
  const uint32_t a0 = prmt_u(pl, sel[1]), a1 = prmt_u(pl, sel[3]), a2 = prmt_u(pl, sel[0]), a3 = prmt_u(ph, sel[1]);
  const uint32_t c0 = prmt_u(pl, sel[2]), c1 = prmt_u(ph, sel[0]), c2 = prmt_u(ph, sel[3]), c3 = prmt_u(ph, sel[2]);
  float o[4][4];
#pragma unroll
  for (int jn = 0; jn < 4; jn++) {
    o[jn][0] = o[jn][1] = o[jn][2] = o[jn][3] = 0.f;
    mma16816(o[jn], a0, a1, a2, a3, v0[jn], v1[jn]);
  }
#pragma unroll
  for (int jn = 0; jn < 4; jn++) mma16816(o[jn], c0, c1, c2, c3, v2[jn], v3[jn]);
  const float il = rcp_hw(quad_sum(x[0] + x[1])), ih = rcp_hw(quad_sum(x[2] + x[3]));
#pragma unroll
  for (int jn = 0; jn < 4; jn++) {
    olo[jn] = pack_bf16(o[jn][0] * il, o[jn][1] * il);
    ohi[jn] = pack_bf16(o[jn][2] * ih, o[jn][3] * ih);
  }
}

__device__ __forceinline__ void gelu_epilogue(const Params& p, float (&acc)[2][96], const Ctx& cx, int t) {
  UNPACK_CTX(cx);
  (void)wg;
  float rs[4], rm[4];
#pragma unroll
  for (int q = 0; q < 4; q++) {
    const float2 v = lds_f2(sb + OFF_ROW + (32 * w + 8 * q + (lane >> 2)) * 8);
    rs[q] = 0.5f * v.x;
    rm[q] = -rs[q] * v.y;
  }
  const int col0 = 128 * (t - 3);
  const uint32_t stg = sb + OFF_STG + w * 4096;
  const uint32_t ctab = sb + OFF_CSF + (col0 / 2 + (lane & 3)) * 16, srow = stg + lane * 128 + ((lane & 7) << 4);
  float4 nb = lds_f4(ctab);
#pragma unroll
  for (int c = 0; c < 3; c++) {
    if (c == 2 && t != 5) break;
    uint32_t hp[8][4];
#pragma unroll
    for (int j = 0; j < 8; j++) {
      const float4 cb = nb;
      if (8 * c + j < 23) nb = lds_f4(ctab + (8 * c + j + 1) * 64);
#pragma unroll
      for (int q = 0; q < 4; q++) {
        float y[2];
        const int k = 4 * j + q - GELU_DEP;
        const float rmq = k >= 0 ? chain(rm[q], hp[k >> 2][k & 3], p.zero) : rm[q];
#pragma unroll
        for (int e = 0; e < 2; e++) {
          const float z = fmaf(ACC(q, 8 * c + j, e), rs[q], fmaf(rmq, e ? cb.y : cb.x, e ? cb.w : cb.z));
          const float u = z * fmaf(z * z, 8.f * 0.7978845608028654f * 0.044715f, 2.f * 0.7978845608028654f);
          y[e] = fmaf(z, tanh_hw(u), z);
        }
        hp[j][q] = pack_bf16(y[0], y[1]);
      }
      if (j == STG_WAIT && c > 0) {
        if (lane == 0) bulk_wait_read();
        __syncwarp();
      }
      if (c == 0 || j > STG_WAIT) {
        stsm4(srow ^ (j << 4), hp[j][0], hp[j][1], hp[j][2], hp[j][3]);
      } else if (j == STG_WAIT) {
#pragma unroll
        for (int jj = 0; jj <= STG_WAIT; jj++) stsm4(srow ^ (jj << 4), hp[jj][0], hp[jj][1], hp[jj][2], hp[jj][3]);
      }
    }
    fence_async_smem();
    __syncwarp();
    if (lane == 0) {
      tma_st2(&p.h_st, stg, 448 * n + col0 + 64 * c, 128 * m + 32 * w);
      bulk_commit();
    }
  }
#pragma unroll
  for (int r = 0; r < 16; r++) acc[0][r] = acc[1][r] = 0.f;
}

__device__ __forceinline__ void attn_epilogue(const Params& p, float (&acc)[2][96], const Ctx& cx, int layer, int t, uint32_t tag) {
  UNPACK_CTX(cx);
  const bool par = (lane >> 2) & 1, early = (lane & 3) > (lane >> 3);
  const uint32_t ktab = sb + OFF_ROW + (32 * w + 2 * (lane & 3) + par) * 8, exc = sb + OFF_STG + w * 4096 + lane * 16;
  const int slot = ((layer * 2 + t) * 16 + m) * 8 + n;
  const int mn = m * 8 + n; (void)mn;
  uint32_t Q[4][8], K[4][8], V[4][8], E[36], P[36];
  float kr[6], qr[4];
#pragma unroll
  for (int q = 2; q < 4; q++) {
    kr[2 + q] = lds_f(ktab + 64 * q);
#pragma unroll
    for (int j = 0; j < 8; j++) {
      E[8 * (q - 2) + j] = K[q][j] = pack_bf16(ACC(q, 8 + j, 0), ACC(q, 8 + j, 1));
      E[16 + 2 * j + q - 2] = V[q][j] = movtrans(pack_bf16(ACC(q, 16 + j, 0), ACC(q, 16 + j, 1)));
    }
  }
#pragma unroll
  for (int j = 0; j < 16; j++) K[j >> 3][j & 7] = pack_bf16(ACC(j >> 3, 8 + (j & 7), 0), ACC(j >> 3, 8 + (j & 7), 1));
#pragma unroll
  for (int j = 0; j < 16; j++) asm volatile("" : "+r"(K[j >> 3][j & 7]));
  E[32] = __float_as_uint(kr[4]);
  E[33] = E[34] = E[35] = __float_as_uint(kr[5]);
  if (w < 3) {
#pragma unroll
    for (int k = 0; k < 8; k++) sts_u4(exc + k * 512, E[4 * k], E[4 * k + 1], E[4 * k + 2], E[4 * k + 3]);
  } else {
#pragma unroll
    for (int k = 0; k < 12; k++) st_msg(p.g->halo + slot * 384 + k * 32 + lane, E[3 * k], E[3 * k + 1], E[3 * k + 2], tag);
  }
  bar_arrive(BAR_PAIR + w, 64);
  if (LATE_O && t == 1) bar_arrive(BAR_ORDER + (wg ^ 1), 256);
  PROF_E(7 * layer + t, 1);
#pragma unroll
  for (int q = 0; q < 4; q++) {
    qr[q] = lds_f(sb + OFF_ROW + (32 * w + 8 * q + (lane >> 2)) * 8) * (0.17677669529663687f * 1.4426950408889634f);
#pragma unroll
    for (int j = 0; j < 8; j++) Q[q][j] = pack_bf16(ACC(q, j, 0), ACC(q, j, 1));
    if (q < 2) {
      kr[2 + q] = lds_f(ktab + 64 * q);
#pragma unroll
      for (int j = 0; j < 8; j++) V[q][j] = movtrans(pack_bf16(ACC(q, 16 + j, 0), ACC(q, 16 + j, 1)));
    }
  }
  PROF_E(7 * layer + t, 6);
  bar_sync(BAR_PAIR + ((w + 3) & 3), 64);
  if (w > 0 || m == 0) {
    const uint32_t back = w > 0;
#pragma unroll
    for (int k = 0; k < 8; k++) lds_u4(exc - back * 4096 + k * 512, P[4 * k], P[4 * k + 1], P[4 * k + 2], P[4 * k + 3]);
    P[32] = lds_u(ktab - back * 128);
    P[33] = lds_u(ktab - back * 64);
  } else {
    if (HALO_NS) __nanosleep(HALO_NS);
#pragma unroll 1
    for (int it = 0; it < MSG_SPINS; it++) {
      uint32_t tg, bad = 0;
      if (it > 0) poll_line(reinterpret_cast<const uint32_t*>(p.g->halo + (slot - 8) * 384 + 383) + 3, tag, 1u);
#pragma unroll
      for (int k = 0; k < 12; k++) {
        ld_msg(p.g->halo + (slot - 8) * 384 + k * 32 + lane, P[3 * k], P[3 * k + 1], P[3 * k + 2], tg);
        bad |= tg ^ tag;
      }
      if (__all_sync(0xffffffffu, bad == 0)) break;
    }
  }
  kr[0] = __uint_as_float(P[32]);
  kr[1] = __uint_as_float(P[33]);
  uint32_t PV[2][8];
#pragma unroll
  for (int j = 0; j < 8; j++) { PV[0][j] = P[16 + 2 * j]; PV[1][j] = P[17 + 2 * j]; }
  float rk[2][4], sc[2][4], off[2][4];
#pragma unroll
  for (int g = 0; g < 2; g++) {
    rk[g][0] = kr[2 * g + 1];
    rk[g][1] = early ? kr[2 * g] : kr[2 * g + 2];
    rk[g][2] = kr[2 * g + 2];
    rk[g][3] = early ? kr[2 * g + 1] : kr[2 * g + 3];
#pragma unroll
    for (int e = 0; e < 4; e++) {
      const bool masked = g == 0 && e != 2 && (m | w) == 0 && (e == 0 || early);
      sc[g][e] = masked ? 0.f : rk[g][e] * qr[2 * g + (e >> 1)];
      off[g][e] = masked ? -1e30f : 0.f;
    }
  }
  const uint32_t none = 0x4444u | p.zero, second = par ? 0x3244u : 0x4432u;
  const uint32_t sel[4] = {par ? 0x1044u : 0x4410u, early ? second : none, early ? none : second, none};
  if (w == 0 && elect_one()) asm volatile("prefetch.tensormap [%0];" ::"l"(&p.att_st) : "memory");
  PROF_E(7 * layer + t, 2);
  bar_sync(BAR_GO, 256);
  const float4 zero = lds_f4(sb + OFF_ZERO);
  float l[2][2][4];
  uint32_t O[4][8];
#pragma unroll
  for (int h = 0; h < 2; h++) {
    if (h == 1) {
      Q[2][4] |= __float_as_uint(l[1][0][0]) & p.zero;
      Q[0][4] |= __float_as_uint(l[0][0][0]) & p.zero;
    }
    attn_scores(&Q[2][4 * h], &Q[3][4 * h], &K[0][4 * h], &K[1][4 * h], &K[2][4 * h], &K[3][4 * h], l[1][h], zero, par, early);
    attn_scores(&Q[0][4 * h], &Q[1][4 * h], &P[4 * h], &P[8 + 4 * h], &K[0][4 * h], &K[1][4 * h], l[0][h], zero, par, early);
  }
  const uint32_t stg = sb + OFF_STG + w * 4096, srow = stg + lane * 128 + ((lane & 7) << 4);
#pragma unroll
  for (int h = 0; h < 2; h++) {
    attn_mix(l[1][h], sc[1], off[1], rk[1], &V[0][4 * h], &V[1][4 * h], &V[2][4 * h], &V[3][4 * h], &O[2][4 * h], &O[3][4 * h], sel);
    attn_mix(l[0][h], sc[0], off[0], rk[0], &PV[0][4 * h], &PV[1][4 * h], &V[0][4 * h], &V[1][4 * h], &O[0][4 * h], &O[1][4 * h], sel);
#pragma unroll
    for (int j = 4 * h; j < 4 * h + 4; j++) stsm4(srow ^ (j << 4), O[0][j], O[1][j], O[2][j], O[3][j]);
  }
  bar_arrive(BAR_DONE, 256);
  fence_async_smem();
  __syncwarp();
  if (lane == 0) {
    tma_st2(&p.att_st, stg, 128 * n + 64 * t, 128 * m + 32 * w);
    bulk_commit();
  }
}

template <bool PACED>
__device__ __forceinline__ void rank1_update(const Params& p, float (&acc)[2][96], const Ctx& cx, int t) {
  float nm[4];
#pragma unroll
  for (int q = 0; q < 4; q++) nm[q] = t == 6 ? 1.f : -lds_f(cx.sb + OFF_ROW + (32 * cx.w + 8 * q + (cx.lane >> 2)) * 8 + 4);
  const uint32_t ctab = cx.sb + OFF_CSQ + ((t & 3) * 192 + 2 * (cx.lane & 3)) * 4;
#pragma unroll
  for (int j = 0; j < 24; j++) {
    const float2 cs = lds_f2(ctab + j * 32);
#pragma unroll
    for (int q = 0; q < 4; q++) {
      const int k = 4 * j + q - 1;
      const float nq = PACED && k >= 0 ? chain(nm[q], __float_as_uint(ACC(k & 3, k >> 2, 1)), p.zero) : nm[q];
      ACC(q, j, 0) = fmaf(nq, cs.x, ACC(q, j, 0));
      ACC(q, j, 1) = fmaf(nq, cs.y, ACC(q, j, 1));
    }
  }
}

__device__ __forceinline__ void finish_stores(uint32_t sb, int i) {
  const int t = i >= 7 ? i - 7 : i;
  if ((threadIdx.x & 31) == 0) {
    bulk_wait_all();
    mbar_arrive(sb + BAR_PUB + 8 * (t < 2 ? t : t + 1));
  }
  __syncwarp();
  if (i < 12) bar_arrive(BAR_GUARD + ((i & 1) ^ 1), 256);
}

__device__ __forceinline__ bool consumer_tile(const Params& p, float (&acc)[2][96], uint32_t sb0, int i, int mn) {
  const int layer = i >= 7, t = i - 7 * layer, wg = i & 1;
  const bool resid = t == 2 || t == 6;
  {
    if (resid) {
      const Ctx cx = make_ctx(sb0, mn);
      const uint32_t xrow = cx.sb + OFF_X + cx.w * 4096 + cx.lane * 128;
      const uint32_t sel_lo = 0x1044u | p.zero, sel_hi = 0x3244u | p.zero;
#pragma unroll
      for (int j = 0; j < 16; j++) {
        uint32_t r[4];
        ldsm4(xrow + (j >> 3) * 16384 + (((j & 7) ^ (cx.lane & 7)) << 4), r[0], r[1], r[2], r[3]);
#pragma unroll
        for (int q = 0; q < 4; q++) {
          ACC(q, j, 0) = prmt_f(r[q], sel_lo);
          ACC(q, j, 1) = prmt_f(r[q], sel_hi);
        }
      }
    }
    if (t >= 5 || i == 7) finish_stores(sb0, i - 2);
#pragma unroll 1
    for (int step = !tile_split(i);; step++) {
      if (step == 1 && (t == 1 || t == 4)) {
        const Ctx cx = make_ctx(sb0, mn);
        if (i == 1) {
          const uint32_t epoch = __ldcg(p.g->epoch + (mn & 127));
          cluster_wait();
          asm volatile("st.shared.u32 [%0], %1;" ::"r"(sb0 + OFF_TAG), "r"(epoch + 1) : "memory");
        }
        const uint32_t tag = lds_u(cx.sb + OFF_TAG);
        const int ln = (i + 1) >> 2;
#pragma unroll 1
        for (int r = 0; r < 2; r++) {
          if (i == 1) {
            if (cx.w < 3) {
              float a[8] = {0.f, 0.f, 0.f, 0.f, 0.f, 0.f, 0.f, 0.f};
              mbar_wait(sb0 + BAR_CSLD, r);
#pragma unroll 1
              for (int h = 0; h < 2; h++) sum_rows(cx.sb + OFF_STG + h * 12288 + cx.w * 4096, 4, a, cx.lane);
              publish_sums(a, p.g->csp + (cx.n * 17 + cx.m) * 224 + (3 * r + cx.w) * 32, cx.lane, tag);
            }
            PROF_E(-1, 5 + r);
          }
          if (r == 1) break;
          if (i == 1) {
            bar_sync(BAR_WG + 1, 128);
            if (cx.w == 3 && elect_one()) {
              mbar_expect_tx(sb0 + BAR_CSLD, 24576);
              tma_ld3(sb0 + OFF_STG, &p.wqkv, sb0 + BAR_CSLD, 128 * cx.n + 64, 64 * cx.m, 0);
              tma_ld3(sb0 + OFF_STG + 12288, &p.wqkv, sb0 + BAR_CSLD, 128 * cx.n + 64, 64 * cx.m + 32, 0);
            }
            mbar_wait(sb0 + BAR_XRDY, 0);
            mbar_wait(sb0 + BAR_XRDY + 8, 0);
          }
          write_partial_stats(p, cx, ln, tag);
          PROF_E(i - 2, 8);
        }
        if (i == 1) {
          bar_arrive(BAR_HLP, 160);
          bar_sync(BAR_INIT, 160);
        }
        if (i <= 4) colsum_total(p, cx, ln, tag);
        PROF_E(i - 2, 9);
        if (i != 1) bar_sync(BAR_GUARD + wg, 256);
        finish_row_stats(p, cx, ln, tag);
        PROF_E(i - 2, 10);
        if (i == 4) {
          colsum_gather(p, cx, 1, tag);
          mbar_wait(sb0 + BAR_BIAS, 0);
        }
        PROF_E(i - 2, 15);
        bar_arrive(BAR_GUARD + (wg ^ 1), 256);
      }
      if (step == 2 && !resid) bar_sync(BAR_GUARD + wg, 256);
      if (step == 2 && i == 0) {
        colsum_gather(p, make_ctx(sb0, mn), 0, lds_u(sb0 + OFF_TAG));
        bar_sync(BAR_WG, 128);
      }
      if (i == 1) {
        if (step == 2) rank1_update<false>(p, acc, make_ctx(sb0, mn), t);
      } else if (t + step == 2 || t == 6) {
        rank1_update<true>(p, acc, make_ctx(sb0, mn), t);
      }
      if (step == 2) break;
      if (tile_wide(t)) {
        mainloop<192>(p, acc, sb0, i, step, mn);
      } else {
        mainloop<128>(p, acc, sb0, i, step, mn);
        if (resid) return false;
      }
    }
    if (t < 2) return true;
    gelu_epilogue(p, acc, make_ctx(sb0, mn), t);
    PROF_E(i, 4);
    return false;
  }
}

__global__ void __cluster_dims__(2, 1, 1) __launch_bounds__(384, 1) fused_layers_kernel(const int by_smid, const __nv_bfloat16* x_p, const __nv_bfloat16* wqkv_p,
                                                                  const __grid_constant__ Params p) {
  extern __shared__ __align__(1024) uint8_t smem_raw[];
  const uint32_t sb = uniform((uint32_t)__cvta_generic_to_shared(smem_raw));
  const int tid = threadIdx.x, lane = tid & 31, warp = uniform(tid >> 5), wg = warp >> 2, w = warp & 3;

  int mn;
  {
    int id = blockIdx.x;
    if (by_smid) asm volatile("mov.u32 %0, %%smid;" : "=r"(id));
    else if (id >= 120) id += 4;
    const int c = id >> 1;
    int g, j;
    if (c < 32) { g = c & 7; j = c >> 3; }
    else if (c < 60) { g = 1 + (c - 32) % 7; j = 4 + (c - 32) / 7; }
    else { g = 0; j = c - 58; }
    const int r = blockIdx.x & 1;
    mn = (g * 2 + r) * 8 + j;
    if (c == 60 || c == 61) {
      if (tid < 32) {
        const uint32_t tag = __ldcg(p.g->epoch + NCTA + (id & 3)) + 1;
#pragma unroll 1
        for (int mm = 0; mm < 16; mm++) poll_line(p.g->flags + mm * 32 + (lane & 7), 32 * tag, 0xffu);
        if (tid == 0) p.g->epoch[NCTA + (id & 3)] = tag;
      }
      return;
    }
  }
  const int m = mn >> 3, n = mn & 7;
  if (tid == 256) PROF_U(1);
  if (tid >= 382) asm volatile("prefetch.global.L2 [%0];" ::"l"(tid & 1 ? wqkv_p + 128 * n : x_p + 128 * m * DM));
  if (wg < 2) {
    cluster_arrive();
    asm volatile("setmaxnreg.inc.sync.aligned.u32 232;");
    const int id = mn | (warp << 7);
#pragma unroll 1
    for (int i = wg;; i += 2) {
      float acc[2][96];
#pragma unroll
      for (int r = 0; r < 96; r++) acc[0][r] = acc[1][r] = 0.f;
      pin_regs<96>(acc);
#pragma unroll 1
      while (!consumer_tile(p, acc, sb, i, id)) {
        PROF_T(6 + i * 4);
        i += 2;
        if (i >= 14) goto all_done;
      }
      attn_epilogue(p, acc, make_ctx(sb, id), i >= 7, i >= 7 ? i - 7 : i, lds_u(sb + OFF_TAG));
      PROF_E(i, 4);
      finish_stores(sb, i);
      PROF_E(i, 5);
      PROF_T(6 + i * 4);
    }
  all_done:
    if (wg == 0) {
      finish_stores(sb, 12);
    } else {
      cluster_arrive();
      cluster_wait();
    }
  } else {
    asm volatile("setmaxnreg.dec.sync.aligned.u32 40;");
    if (w != 0) {
      if (w == 1 && elect_one()) {
        mbar_init(sb + BAR_FULL + 32, 2);
#pragma unroll
        for (int k = 0; k < NBAR; k++) mbar_init(sb + BAR_EMPTY + 8 * k, 8);
#pragma unroll
        for (int k = 0; k < 3; k++) mbar_init(sb + BAR_XRDY + 8 * k, 4);
#pragma unroll
        for (int k = 0; k < 9; k++) mbar_init(sb + BAR_PUB + 8 * k, 4);
#pragma unroll
        for (int k = 0; k < 4; k++) mbar_init(sb + BAR_CSLD + 8 * k, 1);
        sts_f2(sb + OFF_ZERO, 0.f, 0.f);
        sts_f2(sb + OFF_ZERO + 8, 0.f, 0.f);
        asm volatile("fence.mbarrier_init.release.cluster;" ::: "memory");
      }
      __syncwarp();
      cluster_arrive();
      if (w == 2) {
        if (lane < 28) write_run_desc(sb, lane >> 1, lane & 1);
        bar_arrive(BAR_INIT, 160);
      }
      cluster_wait();
      if (w == 1) producer<true>(p, sb, m, n, lane);
      else if (w == 3) colsum_helper(p, sb, m, n, lane);
      else if (elect_one()) publisher(p, sb, m, n);
    } else {
      const bool leader = elect_one();
      if (leader) {
#pragma unroll
        for (int k = 0; k < 4; k++) mbar_init(sb + BAR_FULL + 8 * k, 2);
        asm volatile("fence.mbarrier_init.release.cluster;" ::: "memory");
        PROF_U(4);
      }
      __syncwarp();
      cluster_arrive();
      if (leader) {
#pragma unroll 1
        for (int k = 0; k < 4; k++) {
          const uint32_t fb = sb + BAR_FULL + 8 * k;
          mbar_expect_tx(fb, 16384);
          tma_ld2(sb + (5 * k + 3) * UNIT, &p.xin, fb, 64 * k, 128 * m);
          mbar_expect_tx(fb, 3 * UNIT);
          tma_ld3(sb + 5 * k * UNIT, &p.wqkv, fb, 128 * n, 64 * k, 0);
          tma_ld3(sb + 5 * k * UNIT + 12288, &p.wqkv, fb, 128 * n, 64 * k + 32, 0);
        }
        PROF_U(5);
      }
      __syncwarp();
      cluster_wait();
      if (leader) {
        mbar_expect_tx(sb + BAR_CSLD, 24576);
        tma_ld3(sb + OFF_STG, &p.wqkv, sb + BAR_CSLD, 128 * n, 64 * m, 0);
        tma_ld3(sb + OFF_STG + 12288, &p.wqkv, sb + BAR_CSLD, 128 * n, 64 * m + 32, 0);
#pragma unroll 1
        for (int h = 0; h < 2; h++) {
          const uint32_t xr = sb + BAR_XRDY + 8 * h;
          mbar_expect_tx(xr, 16384);
          tma_ld2(sb + OFF_X + h * 16384, &p.xin, xr, 128 * n + 64 * h, 128 * m);
          asm volatile("mbarrier.arrive.shared::cta.b64 _, [%0], 3;" ::"r"(xr) : "memory");
        }
        PROF_U(6);
      }
      __syncwarp();
      producer<false>(p, sb, m, n, lane);
    }
  }
}

typedef CUresult (*EncodeFn)(CUtensorMap*, CUtensorMapDataType, cuuint32_t, void*, const cuuint64_t*, const cuuint64_t*,
                             const cuuint32_t*, const cuuint32_t*, CUtensorMapInterleave, CUtensorMapSwizzle,
                             CUtensorMapL2promotion, CUtensorMapFloatOOBfill);

#define PROMO2 CU_TENSOR_MAP_L2_PROMOTION_L2_128B
#define PROMO3 CU_TENSOR_MAP_L2_PROMOTION_L2_128B
void make_2d(EncodeFn enc, CUtensorMap* m, const void* ptr, uint64_t cols, uint64_t rows, uint32_t box_rows) {
  cuuint64_t d[2] = {cols, rows}, st[1] = {cols * 2};
  cuuint32_t b[2] = {64, box_rows}, e[2] = {1, 1};
  enc(m, CU_TENSOR_MAP_DATA_TYPE_BFLOAT16, 2, const_cast<void*>(ptr), d, st, b, e, CU_TENSOR_MAP_INTERLEAVE_NONE,
      CU_TENSOR_MAP_SWIZZLE_128B, PROMO2, CU_TENSOR_MAP_FLOAT_OOB_FILL_NONE);
}
void make_3d(EncodeFn enc, CUtensorMap* m, const void* ptr, uint64_t d0, uint64_t rows, uint64_t d2, uint64_t row_bytes,
             uint64_t chunk_bytes, uint32_t box_chunks) {
  cuuint64_t d[3] = {d0, rows, d2}, st[2] = {row_bytes, chunk_bytes};
  cuuint32_t b[3] = {64, 32, box_chunks}, e[3] = {1, 1, 1};
  enc(m, CU_TENSOR_MAP_DATA_TYPE_BFLOAT16, 3, const_cast<void*>(ptr), d, st, b, e, CU_TENSOR_MAP_INTERLEAVE_NONE,
      CU_TENSOR_MAP_SWIZZLE_128B, PROMO3, CU_TENSOR_MAP_FLOAT_OOB_FILL_NONE);
}

}

extern "C" void kernel_launch(void* const* d_in, const int* in_sizes, int n_in, void* d_out, int out_size) {
  (void)in_sizes; (void)n_in; (void)out_size;
  static EncodeFn enc = nullptr;
  static void *att = nullptr, *hbuf = nullptr, *scratch = nullptr;
  static int by_smid = 0;
  if (!enc) {
    void* fn = nullptr;
    cudaDriverEntryPointQueryResult q;
    cudaGetDriverEntryPoint("cuTensorMapEncodeTiled", &fn, cudaEnableDefault, &q);
    enc = (EncodeFn)fn;
    cudaGetSymbolAddress(&att, g_att);
    cudaGetSymbolAddress(&hbuf, g_h);
    cudaGetSymbolAddress(&scratch, g_scratch);
    cudaFuncSetAttribute(fused_layers_kernel, cudaFuncAttributeMaxDynamicSharedMemorySize, SMEM_BYTES);
    int sms = 0, clusters = 0, dev = 0;
    cudaGetDevice(&dev);
    cudaDeviceGetAttribute(&sms, cudaDevAttrMultiProcessorCount, dev);
    cudaLaunchConfig_t cfg = {};
    cfg.gridDim = dim3(132);
    cfg.blockDim = dim3(384);
    cfg.dynamicSmemBytes = SMEM_BYTES;
    cudaLaunchAttribute at[1];
    at[0].id = cudaLaunchAttributeClusterDimension;
    at[0].val.clusterDim.x = 2; at[0].val.clusterDim.y = 1; at[0].val.clusterDim.z = 1;
    cfg.attrs = at;
    cfg.numAttrs = 1;
    if (cudaOccupancyMaxActiveClusters(&clusters, fused_layers_kernel, &cfg) != cudaSuccess) (void)cudaGetLastError();
    by_smid = sms == 132 && clusters == 66;
  }
  Params p;
  make_2d(enc, &p.xin, d_in[0], DM, SEQ, 128);
  make_2d(enc, &p.out, d_out, DM, SEQ, 128);
  make_2d(enc, &p.att, att, DM, SEQ, 128);
  make_2d(enc, &p.h, hbuf, FF, SEQ, 128);
  make_2d(enc, &p.att_st, att, DM, SEQ, 32);
  make_2d(enc, &p.h_st, hbuf, FF, SEQ, 32);
  make_2d(enc, &p.w1c, d_in[4], FF, DM, 32);
  make_3d(enc, &p.wqkv, d_in[1], DM, DM, 3, 3 * DM * 2, DM * 2, 3);
  make_3d(enc, &p.wo, d_in[2], 64, DM, DM / 64, DM * 2, 128, 2);
  make_3d(enc, &p.w1a, d_in[4], 64, DM, FF / 64, FF * 2, 128, 3);
  make_3d(enc, &p.w1b, d_in[4], 64, DM, FF / 64, FF * 2, 128, 2);
  make_3d(enc, &p.w2, d_in[6], 64, FF, DM / 64, DM * 2, 128, 2);
  p.b1 = (const __nv_bfloat16*)d_in[5];
  p.b2 = (const __nv_bfloat16*)d_in[7];
  p.g = (Scratch*)scratch;
  p.zero = 0;
  fused_layers_kernel<<<by_smid ? 132 : NCTA, 384, SMEM_BYTES>>>(by_smid, (const __nv_bfloat16*)d_in[0], (const __nv_bfloat16*)d_in[1], p);
}
```

```cpp
#include <cuda_runtime.h>
#include <cuda_bf16.h>
#include <cuda.h>
#include <stdint.h>

namespace {

constexpr int SEQ = 2048, DM = 1024, FF = 3584;
constexpr int NCTA = 128;
constexpr int NBAR = 5;

constexpr uint32_t RING_UNITS = 20, UNIT = 8192;
constexpr uint32_t OFF_X   = RING_UNITS * UNIT;
constexpr uint32_t OFF_STG = OFF_X + 32768;
constexpr uint32_t OFF_HLP = OFF_STG + 16384;
constexpr uint32_t OFF_RUN = OFF_STG + 24576;
constexpr uint32_t OFF_CSQ = OFF_RUN + 512;
constexpr uint32_t OFF_CSF = OFF_CSQ + 2048;
constexpr uint32_t OFF_ROW = OFF_CSF + 3584;
constexpr uint32_t OFF_BAR = OFF_ROW + 1024;
constexpr uint32_t SMEM_BYTES = OFF_BAR + 384;
constexpr uint32_t BAR_FULL = OFF_BAR, BAR_EMPTY = OFF_BAR + 8 * NBAR;
constexpr uint32_t BAR_XRDY = OFF_BAR + 80;
constexpr uint32_t BAR_DUMMY = OFF_BAR + 96, OFF_TAG = OFF_BAR + 104, OFF_ZERO = OFF_BAR + 112;
constexpr uint32_t BAR_PUB = OFF_BAR + 128;
constexpr uint32_t BAR_CSLD = OFF_BAR + 200;
constexpr uint32_t BAR_XGO = OFF_BAR + 224;
constexpr uint32_t BAR_BIAS = OFF_BAR + 216;

constexpr uint64_t DESC_A = (1ull << 62) | ((uint64_t)(2048 >> 4) << 32) | (1ull << 16);
constexpr uint64_t DESC_B = (1ull << 62) | ((uint64_t)(1024 >> 4) << 32) | ((uint64_t)(4096 >> 4) << 16);

constexpr int BAR_INIT = 0, BAR_ORDER = 1, BAR_GUARD = 3, BAR_WG = 5, BAR_GO = 7, BAR_DONE = 8, BAR_HLP = 9, BAR_PAIR = 11;
#define GELU_DEP 2
#define MAP 2
#define LATE_O 1
#define HALO_NS 200
#define STG_WAIT 5
#define STAT_NS 800
#define HOLDM 3
#define BDELAY 100
#define STAG5 450
#define STAG4 0
#define STAG3 0
#define WIN1 8
#define WIN2 2

struct Scratch {
  uint4 stats[4 * 8 * SEQ];
  uint4 halo[2 * 2 * 16 * 8 * 384];
  uint4 csp[2 * 8 * 17 * 224];
  uint32_t flags[16 * 32];
  uint32_t epoch[NCTA + 4];
};

struct Params {
  CUtensorMap xin, out, att, h, wqkv, wo, w1a, w1b, w2, att_st, h_st, w1c;
  const __nv_bfloat16 *b1, *b2;
  Scratch* g;
  uint32_t zero;
};

__device__ __nv_bfloat16 g_att[SEQ * DM];
__device__ __nv_bfloat16 g_h[SEQ * FF];
__device__ Scratch g_scratch;
#define PROF_T(idx)
#define PROF_U(k)
#define PROF_S(g)
#define PROF_E(i, k)

__device__ __forceinline__ void mbar_init(uint32_t bar, int cnt) {
  asm volatile("mbarrier.init.shared::cta.b64 [%0], %1;" ::"r"(bar), "r"(cnt));
}
__device__ __forceinline__ void mbar_expect_tx(uint32_t bar, uint32_t bytes) {
  asm volatile("mbarrier.arrive.expect_tx.shared::cta.b64 _, [%0], %1;" ::"r"(bar), "r"(bytes) : "memory");
}
__device__ __forceinline__ void mbar_arrive(uint32_t bar) {
  asm volatile("mbarrier.arrive.shared::cta.b64 _, [%0];" ::"r"(bar) : "memory");
}
__device__ __forceinline__ bool mbar_test(uint32_t bar, uint32_t parity) {
  uint32_t ok;
  asm volatile("{\n.reg .pred p;\nmbarrier.test_wait.parity.shared::cta.b64 p, [%1], %2;\nselp.u32 %0, 1, 0, p;\n}"
               : "=r"(ok) : "r"(bar), "r"(parity) : "memory");
  return ok;
}
__device__ __forceinline__ void mbar_wait(uint32_t bar, uint32_t parity) {
  asm volatile(
      "{\n.reg .pred p;\n.reg .u32 it;\nmov.u32 it, 0;\n"
      "WAIT_LOOP:\n"
      "mbarrier.try_wait.parity.shared::cta.b64 p, [%0], %1;\n"
      "@p bra WAIT_DONE;\n"
      "add.u32 it, it, 1;\n"
      "setp.lt.u32 p, it, 0x400000;\n"
      "@p bra WAIT_LOOP;\n"
      "trap;\n"
      "WAIT_DONE:\n}"
      ::"r"(bar), "r"(parity) : "memory");
}
__device__ __forceinline__ void bar_sync(int id, int n) { asm volatile("bar.sync %0, %1;" ::"r"(id), "r"(n) : "memory"); }
__device__ __forceinline__ void bar_arrive(int id, int n) { asm volatile("bar.arrive %0, %1;" ::"r"(id), "r"(n) : "memory"); }
__device__ __forceinline__ void tma_ld2(uint32_t dst, const CUtensorMap* m, uint32_t bar, int c0, int c1) {
  asm volatile("cp.async.bulk.tensor.2d.shared::cluster.global.mbarrier::complete_tx::bytes [%0], [%1, {%3, %4}], [%2];"
               ::"r"(dst), "l"(m), "r"(bar), "r"(c0), "r"(c1) : "memory");
}
__device__ __forceinline__ void tma_ld3(uint32_t dst, const CUtensorMap* m, uint32_t bar, int c0, int c1, int c2) {
  asm volatile("cp.async.bulk.tensor.3d.shared::cluster.global.mbarrier::complete_tx::bytes [%0], [%1, {%3, %4, %5}], [%2];"
               ::"r"(dst), "l"(m), "r"(bar), "r"(c0), "r"(c1), "r"(c2) : "memory");
}
__device__ __forceinline__ void tma_ld3_pair(uint32_t dst, const CUtensorMap* m, uint32_t bar, int c0, int c1, int c2) {
  asm volatile("cp.async.bulk.tensor.3d.shared::cluster.global.mbarrier::complete_tx::bytes.multicast::cluster"
               " [%0], [%1, {%3, %4, %5}], [%2], %6;"
               ::"r"(dst), "l"(m), "r"(bar), "r"(c0), "r"(c1), "r"(c2), "h"((uint16_t)3) : "memory");
}
__device__ __forceinline__ uint32_t pair_offset(uint32_t sb, uint32_t rank) {
  uint32_t r;
  asm volatile("mapa.shared::cluster.u32 %0, %1, %2;" : "=r"(r) : "r"(sb), "r"(rank));
  return r - sb;
}
__device__ __forceinline__ void mbar_arrive_cluster(uint32_t bar) {
  asm volatile("mbarrier.arrive.shared::cluster.b64 _, [%0];" ::"r"(bar) : "memory");
}
__device__ __forceinline__ void cluster_arrive() { asm volatile("barrier.cluster.arrive.relaxed;" ::: "memory"); }
__device__ __forceinline__ void cluster_wait() { asm volatile("barrier.cluster.wait.acquire;" ::: "memory"); }
__device__ __forceinline__ void tma_st2(const CUtensorMap* m, uint32_t src, int c0, int c1) {
  asm volatile("cp.async.bulk.tensor.2d.global.shared::cta.bulk_group [%0, {%2, %3}], [%1];"
               ::"l"(m), "r"(src), "r"(c0), "r"(c1) : "memory");
}
__device__ __forceinline__ void bulk_commit() { asm volatile("cp.async.bulk.commit_group;" ::: "memory"); }
__device__ __forceinline__ void bulk_wait_read() { asm volatile("cp.async.bulk.wait_group.read 0;" ::: "memory"); }
__device__ __forceinline__ void bulk_wait_all() { asm volatile("cp.async.bulk.wait_group 0;" ::: "memory"); }
__device__ __forceinline__ void fence_async_smem() { asm volatile("fence.proxy.async.shared::cta;" ::: "memory"); }
__device__ __forceinline__ void fence_async_global() { asm volatile("fence.proxy.async.global;" ::: "memory"); }
__device__ __forceinline__ void st_relaxed(uint32_t* p, uint32_t v) {
  asm volatile("st.relaxed.gpu.global.u32 [%0], %1;" ::"l"(p), "r"(v) : "memory");
}
__device__ __forceinline__ void st_msg(uint4* p, uint32_t a, uint32_t b, uint32_t c, uint32_t tag) {
  asm volatile("{\n.reg .b128 v;\nmov.b128 v, {%1, %2, %3, %4};\nst.relaxed.gpu.global.b128 [%0], v;\n}"
               ::"l"(p), "r"(a), "r"(b), "r"(c), "r"(tag) : "memory");
}
__device__ __forceinline__ void ld_msg(const uint4* p, uint32_t& a, uint32_t& b, uint32_t& c, uint32_t& tag) {
  asm volatile("{\n.reg .b128 v;\nld.relaxed.gpu.global.b128 v, [%4];\nmov.b128 {%0, %1, %2, %3}, v;\n}"
               : "=r"(a), "=r"(b), "=r"(c), "=r"(tag) : "l"(p) : "memory");
}
__device__ __forceinline__ bool elect_one() {
  uint32_t ok;
  asm volatile("{\n.reg .pred p;\nelect.sync _|p, 0xffffffff;\nselp.u32 %0, 1, 0, p;\n}" : "=r"(ok));
  return ok;
}
__device__ __forceinline__ int uniform(int v) { return __shfl_sync(0xffffffffu, v, 0); }
__device__ __forceinline__ uint32_t pack_bf16(float lo, float hi) {
  uint32_t r;
  asm("cvt.rn.bf16x2.f32 %0, %1, %2;" : "=r"(r) : "f"(hi), "f"(lo));
  return r;
}
__device__ __forceinline__ uint32_t prmt_u(uint32_t a, uint32_t sel) {
  uint32_t r;
  asm("prmt.b32 %0, %1, 0, %2;" : "=r"(r) : "r"(a), "r"(sel));
  return r;
}
__device__ __forceinline__ float prmt_f(uint32_t a, uint32_t sel) {
  float r;
  asm("{\n.reg .b32 t;\nprmt.b32 t, %1, 0, %2;\nmov.b32 %0, t;\n}" : "=f"(r) : "r"(a), "r"(sel));
  return r;
}
__device__ __forceinline__ float bf_lo(uint32_t v) { return __uint_as_float(v << 16); }
__device__ __forceinline__ float bf_hi(uint32_t v) { return __uint_as_float(v & 0xffff0000u); }
__device__ __forceinline__ void stsm4(uint32_t addr, uint32_t r0, uint32_t r1, uint32_t r2, uint32_t r3) {
  asm volatile("stmatrix.sync.aligned.m8n8.x4.shared.b16 [%0], {%1, %2, %3, %4};"
               ::"r"(addr), "r"(r0), "r"(r1), "r"(r2), "r"(r3) : "memory");
}
__device__ __forceinline__ void ldsm4(uint32_t addr, uint32_t& r0, uint32_t& r1, uint32_t& r2, uint32_t& r3) {
  asm volatile("ldmatrix.sync.aligned.m8n8.x4.shared.b16 {%0, %1, %2, %3}, [%4];"
               : "=r"(r0), "=r"(r1), "=r"(r2), "=r"(r3) : "r"(addr) : "memory");
}
__device__ __forceinline__ uint32_t movtrans(uint32_t a) {
  uint32_t d;
  asm volatile("movmatrix.sync.aligned.m8n8.trans.b16 %0, %1;" : "=r"(d) : "r"(a));
  return d;
}
__device__ __forceinline__ void mma16816(float (&c)[4], uint32_t a0, uint32_t a1, uint32_t a2, uint32_t a3, uint32_t b0, uint32_t b1) {
  asm volatile("mma.sync.aligned.m16n8k16.row.col.f32.bf16.bf16.f32 {%0,%1,%2,%3}, {%4,%5,%6,%7}, {%8,%9}, {%0,%1,%2,%3};"
               : "+f"(c[0]), "+f"(c[1]), "+f"(c[2]), "+f"(c[3])
               : "r"(a0), "r"(a1), "r"(a2), "r"(a3), "r"(b0), "r"(b1));
}
__device__ __forceinline__ float2 lds_f2(uint32_t a) {
  float2 v;
  asm volatile("ld.shared.v2.f32 {%0, %1}, [%2];" : "=f"(v.x), "=f"(v.y) : "r"(a) : "memory");
  return v;
}
__device__ __forceinline__ float4 lds_f4(uint32_t a) {
  float4 v;
  asm volatile("ld.shared.v4.f32 {%0, %1, %2, %3}, [%4];" : "=f"(v.x), "=f"(v.y), "=f"(v.z), "=f"(v.w) : "r"(a) : "memory");
  return v;
}
__device__ __forceinline__ float lds_f(uint32_t a) {
  float v;
  asm volatile("ld.shared.f32 %0, [%1];" : "=f"(v) : "r"(a) : "memory");
  return v;
}
__device__ __forceinline__ uint32_t lds_u(uint32_t a) {
  uint32_t v;
  asm volatile("ld.shared.u32 %0, [%1];" : "=r"(v) : "r"(a) : "memory");
  return v;
}
__device__ __forceinline__ void sts_f2(uint32_t a, float x, float y) {
  asm volatile("st.shared.v2.f32 [%0], {%1, %2};" ::"r"(a), "f"(x), "f"(y) : "memory");
}
__device__ __forceinline__ void sts_u4(uint32_t a, uint32_t x, uint32_t y, uint32_t z, uint32_t w) {
  asm volatile("st.shared.v4.u32 [%0], {%1, %2, %3, %4};" ::"r"(a), "r"(x), "r"(y), "r"(z), "r"(w) : "memory");
}
__device__ __forceinline__ void lds_u4(uint32_t a, uint32_t& x, uint32_t& y, uint32_t& z, uint32_t& w) {
  asm volatile("ld.shared.v4.u32 {%0, %1, %2, %3}, [%4];" : "=r"(x), "=r"(y), "=r"(z), "=r"(w) : "r"(a) : "memory");
}
__device__ __forceinline__ float ex2(float x) {
  float y;
  asm("ex2.approx.ftz.f32 %0, %1;" : "=f"(y) : "f"(x));
  return y;
}
__device__ __forceinline__ float rcp_hw(float x) {
  float y;
  asm("rcp.approx.ftz.f32 %0, %1;" : "=f"(y) : "f"(x));
  return y;
}
__device__ __forceinline__ float tanh_hw(float x) {
  float y;
  asm("tanh.approx.f32 %0, %1;" : "=f"(y) : "f"(x));
  return y;
}
__device__ __forceinline__ float quad_sum(float v) {
  v += __shfl_xor_sync(0xffffffffu, v, 1);
  return v + __shfl_xor_sync(0xffffffffu, v, 2);
}
__device__ __forceinline__ float quad_max(float v) {
  v = fmaxf(v, __shfl_xor_sync(0xffffffffu, v, 1));
  return fmaxf(v, __shfl_xor_sync(0xffffffffu, v, 2));
}

template <int N> __device__ __forceinline__ void wgmma_ss(float (&d)[96], uint64_t da, uint64_t db, uint32_t keep = 1);
template <> __device__ __forceinline__ void wgmma_ss<128>(float (&d)[96], uint64_t da, uint64_t db, uint32_t keep) {
  asm volatile(
      "{\n.reg .pred p;\nsetp.ne.u32 p, %66, 0;\n"
      "wgmma.mma_async.sync.aligned.m64n128k16.f32.bf16.bf16 {%0, %1, %2, %3, %4, %5, %6, %7, %8, %9, %10, %11, %12, %13, %14, %15, %16, %17, %18, %19, %20, %21, %22, %23, %24, %25, %26, %27, %28, %29, %30, %31, %32, %33, %34, %35, %36, %37, %38, %39, %40, %41, %42, %43, %44, %45, %46, %47, %48, %49, %50, %51, %52, %53, %54, %55, %56, %57, %58, %59, %60, %61, %62, %63}, %64, %65, p, 1, 1, 0, 1;\n}"
      : "+f"(d[0]), "+f"(d[1]), "+f"(d[2]), "+f"(d[3]), "+f"(d[4]), "+f"(d[5]), "+f"(d[6]), "+f"(d[7]), "+f"(d[8]), "+f"(d[9]), "+f"(d[10]), "+f"(d[11]), "+f"(d[12]), "+f"(d[13]), "+f"(d[14]), "+f"(d[15]), "+f"(d[16]), "+f"(d[17]), "+f"(d[18]), "+f"(d[19]), "+f"(d[20]), "+f"(d[21]), "+f"(d[22]), "+f"(d[23]), "+f"(d[24]), "+f"(d[25]), "+f"(d[26]), "+f"(d[27]), "+f"(d[28]), "+f"(d[29]), "+f"(d[30]), "+f"(d[31]), "+f"(d[32]), "+f"(d[33]), "+f"(d[34]), "+f"(d[35]), "+f"(d[36]), "+f"(d[37]), "+f"(d[38]), "+f"(d[39]), "+f"(d[40]), "+f"(d[41]), "+f"(d[42]), "+f"(d[43]), "+f"(d[44]), "+f"(d[45]), "+f"(d[46]), "+f"(d[47]), "+f"(d[48]), "+f"(d[49]), "+f"(d[50]), "+f"(d[51]), "+f"(d[52]), "+f"(d[53]), "+f"(d[54]), "+f"(d[55]), "+f"(d[56]), "+f"(d[57]), "+f"(d[58]), "+f"(d[59]), "+f"(d[60]), "+f"(d[61]), "+f"(d[62]), "+f"(d[63])
      : "l"(da), "l"(db), "r"(keep));
}

template <> __device__ __forceinline__ void wgmma_ss<192>(float (&d)[96], uint64_t da, uint64_t db, uint32_t keep) {
  asm volatile(
      "{\n.reg .pred p;\nsetp.ne.u32 p, %98, 0;\n"
      "wgmma.mma_async.sync.aligned.m64n192k16.f32.bf16.bf16 {%0, %1, %2, %3, %4, %5, %6, %7, %8, %9, %10, %11, %12, %13, %14, %15, %16, %17, %18, %19, %20, %21, %22, %23, %24, %25, %26, %27, %28, %29, %30, %31, %32, %33, %34, %35, %36, %37, %38, %39, %40, %41, %42, %43, %44, %45, %46, %47, %48, %49, %50, %51, %52, %53, %54, %55, %56, %57, %58, %59, %60, %61, %62, %63, %64, %65, %66, %67, %68, %69, %70, %71, %72, %73, %74, %75, %76, %77, %78, %79, %80, %81, %82, %83, %84, %85, %86, %87, %88, %89, %90, %91, %92, %93, %94, %95}, %96, %97, p, 1, 1, 0, 1;\n}"
      : "+f"(d[0]), "+f"(d[1]), "+f"(d[2]), "+f"(d[3]), "+f"(d[4]), "+f"(d[5]), "+f"(d[6]), "+f"(d[7]), "+f"(d[8]), "+f"(d[9]), "+f"(d[10]), "+f"(d[11]), "+f"(d[12]), "+f"(d[13]), "+f"(d[14]), "+f"(d[15]), "+f"(d[16]), "+f"(d[17]), "+f"(d[18]), "+f"(d[19]), "+f"(d[20]), "+f"(d[21]), "+f"(d[22]), "+f"(d[23]), "+f"(d[24]), "+f"(d[25]), "+f"(d[26]), "+f"(d[27]), "+f"(d[28]), "+f"(d[29]), "+f"(d[30]), "+f"(d[31]), "+f"(d[32]), "+f"(d[33]), "+f"(d[34]), "+f"(d[35]), "+f"(d[36]), "+f"(d[37]), "+f"(d[38]), "+f"(d[39]), "+f"(d[40]), "+f"(d[41]), "+f"(d[42]), "+f"(d[43]), "+f"(d[44]), "+f"(d[45]), "+f"(d[46]), "+f"(d[47]), "+f"(d[48]), "+f"(d[49]), "+f"(d[50]), "+f"(d[51]), "+f"(d[52]), "+f"(d[53]), "+f"(d[54]), "+f"(d[55]), "+f"(d[56]), "+f"(d[57]), "+f"(d[58]), "+f"(d[59]), "+f"(d[60]), "+f"(d[61]), "+f"(d[62]), "+f"(d[63]), "+f"(d[64]), "+f"(d[65]), "+f"(d[66]), "+f"(d[67]), "+f"(d[68]), "+f"(d[69]), "+f"(d[70]), "+f"(d[71]), "+f"(d[72]), "+f"(d[73]), "+f"(d[74]), "+f"(d[75]), "+f"(d[76]), "+f"(d[77]), "+f"(d[78]), "+f"(d[79]), "+f"(d[80]), "+f"(d[81]), "+f"(d[82]), "+f"(d[83]), "+f"(d[84]), "+f"(d[85]), "+f"(d[86]), "+f"(d[87]), "+f"(d[88]), "+f"(d[89]), "+f"(d[90]), "+f"(d[91]), "+f"(d[92]), "+f"(d[93]), "+f"(d[94]), "+f"(d[95])
      : "l"(da), "l"(db), "r"(keep));
}

template <int R>
__device__ __forceinline__ void pin_regs(float (&a)[2][96]) {
#pragma unroll
  for (int m = 0; m < 2; m++)
#pragma unroll
    for (int i = 0; i < R; i++) asm volatile("" : "+f"(a[m][i])::"memory");
}

struct Ctx {
  uint32_t sb;
  int m, n, wg, w, lane;
};
__device__ __forceinline__ Ctx make_ctx(uint32_t sb, int id) {
  int lane;
  asm volatile("mov.u32 %0, %%laneid;" : "=r"(lane));
  asm volatile("" : "+r"(id), "+r"(sb));
  return Ctx{sb, (id >> 3) & 15, id & 7, id >> 9, (id >> 7) & 3, lane};
}
#define UNPACK_CTX(c) const uint32_t sb = c.sb; const int m = c.m, n = c.n, wg = c.wg, w = c.w, lane = c.lane

__device__ __forceinline__ uint32_t poll_line(const uint32_t* word, uint32_t target, uint32_t need) {
  uint32_t v;
  asm volatile(
      "{\n.reg .pred p;\n.reg .u32 it, m;\n.reg .s32 d;\nmov.u32 it, 0;\n"
      "POLL_LOOP:\n"
      "ld.relaxed.gpu.global.u32 %0, [%1];\n"
      "sub.s32 d, %0, %2;\n"
      "setp.ge.s32 p, d, 0;\n"
      "vote.sync.ballot.b32 m, p, 0xffffffff;\n"
      "and.b32 m, m, %3;\n"
      "setp.eq.u32 p, m, %3;\n"
      "@p bra.uni POLL_DONE;\n"
      "add.u32 it, it, 1;\n"
      "setp.lt.u32 p, it, 0x400000;\n"
      "@p bra.uni POLL_LOOP;\n"
      "trap;\n"
      "POLL_DONE:\n}"
      : "=&r"(v) : "l"(word), "r"(target), "r"(need) : "memory");
  return v;
}
__device__ __forceinline__ uint32_t ld_relaxed(const uint32_t* p) {
  uint32_t v;
  asm volatile("ld.relaxed.gpu.global.u32 %0, [%1];" : "=r"(v) : "l"(p) : "memory");
  return v;
}
__device__ __forceinline__ float chain(float x, uint32_t on, uint32_t zero) {
  return __uint_as_float(__float_as_uint(x) | (on & zero));
}
constexpr int MSG_SPINS = 1 << 20;

constexpr int STAGES_PER_LAYER = 152;
__device__ __forceinline__ int nib(uint64_t v, int i) { return (int)(v >> (4 * i)) & 15; }
__device__ __forceinline__ bool tile_wide(int t) { return (0x23 >> t) & 1; }
__device__ __forceinline__ void weight_coords(const Params& p, int t, int n, const CUtensorMap*& map, int& c0, int& c2) {
  map = &p.wqkv + nib(0x4233100ull, t);
  c0 = t < 2 ? 128 * n + 64 * t : 0;
  c2 = t < 2 ? 0 : (t == 2 || t == 6) ? 2 * n : 7 * n + 2 * t - 6;
}

template <bool IS_A>
__device__ __forceinline__ void producer(const Params& p, uint32_t sb, int m, int n, int lane) {
  const uint32_t low = (1u << (4 * n)) - 1, others = (0x6543210u & low) | (0x7654321u & ~low);
  const uint64_t order_x = (uint64_t)(others * 2 + 0x1111111u) << 36 | (uint64_t)others * 2 << 8 | (n * 0x22 + 0x10);
  int inflight = 4, cur = 0;
  uint32_t fb = sb + BAR_FULL + 32, rb = sb + BAR_EMPTY, rph = 0, pos = 0, tag32 = 0, seen = 0;
  const uint32_t fend = sb + BAR_FULL + 8 * NBAR, rend = sb + BAR_EMPTY + 8 * NBAR;
  const uint32_t* word = p.g->flags + m * 32 + (lane < 16 ? lane >> 1 : lane & 7);
#pragma unroll 1
  for (int sg = 1; sg < 22; sg++) {
    const int layer = sg >= 11, s = sg == 1 ? 2 : sg == 2 ? 1 : sg - 11 * layer;
    const int t = nib(0x65434321010ull, s), kind = nib(0x32110031100ull, s);
    const bool wide = tile_wide(t);
    const uint32_t bbytes = wide ? 3 * UNIT : 2 * UNIT, base = sb + (IS_A ? bbytes : (m & 1) * (bbytes / 2));
    if (IS_A && kind == 0) {
      if (sg == 2) seen = tag32 = (__ldcg(p.g->epoch + m * 8 + n) + 1) << 5;
#pragma unroll 1
      for (int k = 0; k < 2; k++) {
#pragma unroll 1
        for (; inflight > (wide ? 3 : 4); inflight--) {
          mbar_wait(rb, rph);
          rb += 8;
          if (rb == rend) { rb -= 8 * NBAR; rph ^= 1; }
        }
        if (elect_one()) mbar_arrive(fb);
        inflight++;
        fb += 8;
        if (fb == fend) fb -= 8 * NBAR;
        pos += bbytes + 2 * UNIT;
        if (pos >= RING_UNITS * UNIT) pos -= RING_UNITS * UNIT;
      }
      continue;
    }
    const int mul = t == 6 ? 448 : t == 2 ? 128 : 64, count = sg == 1 ? 12 : 2 * nib(0x4871ull, kind);
    uint64_t order0 = sg == 1 ? 0xFEDCBA987654ull : kind == 3 ? 0x76543210u : order_x >> (8 * (kind & 1));
    uint32_t special = (s == 4 || s == 10) ? 0x10 : s == 9 ? 0xF : s == 0;
    if (IS_A) special |= (kind & 1 ? 0 : 3) | (count >= 4 ? 1u << (count - 4) : 0);
    if (s >= 9) pos = (s + 6) * UNIT;
    const CUtensorMap* map;
    int c0 = 0, c2 = 0, ev = 0;
    if (IS_A) {
      map = &p.xin + (t == 2 ? 2 : t == 6 ? 3 : sg >= 4);
      ev = 9 * layer + (t < 2 ? 0 : t == 2 ? 1 : t < 6 ? 4 : 5);
      if (elect_one()) asm volatile("prefetch.tensormap [%0];" ::"l"(map) : "memory");
    } else {
      weight_coords(p, t, n, map, c0, c2);
    }
#pragma unroll 1
    for (int add = 0; add < mul; add += 64) {
      uint64_t order = order0;
      const int need = kind == 3 ? ev : ev - 1 + (lane & 1), sh = kind == 3 ? 16 : 0;
      uint32_t ready = IS_A ? __ballot_sync(0xffffffffu, cur >= need) >> sh : 0;
#pragma unroll 1
      for (int k = 0; k < count; k++) {
        const int code = order & 15, kc = code * mul + add;
        order >>= 4;
        if ((special >> k) & 1) {
          const int lag = wide ? (s == 9 && k == 2 ? 2 : 3) : ((s == 4 || s == 10) && add == 0 && k < 4) ? 3 : 4;
#pragma unroll 1
          for (; inflight > lag; inflight--) {
            mbar_wait(rb, rph);
            rb += 8;
            if (rb == rend) { rb -= 8 * NBAR; rph ^= 1; }
          }
          inflight++;
          if (IS_A) {
            if (kind == 3 ? t == 2 && add + k == 64 : !(kind & 1) && k < 2) {
              if (t == 2) mbar_wait(sb + BAR_PUB + 8, layer);
              if (elect_one()) mbar_arrive(fb);
              goto next_stage;
            }
            if (k == count - 4 && sg >= 3) seen = ld_relaxed(word);
          }
        } else {
          mbar_wait(rb, rph);
          rb += 8;
          if (rb == rend) { rb -= 8 * NBAR; rph ^= 1; }
        }
        if (IS_A && !((ready >> code) & 1)) {
          cur = max(cur, (int)(seen - tag32));
          ready = __ballot_sync(0xffffffffu, cur >= need) >> sh;
          if (!((ready >> code) & 1)) {
            cur = (int)(poll_line(word, tag32 + need, 1u << (code + sh)) - tag32);
            ready = __ballot_sync(0xffffffffu, cur >= need) >> sh;
          }
          asm volatile("fence.acquire.gpu;" ::: "memory");
          fence_async_global();
          seen = ld_relaxed(word);
        }
        if (elect_one()) {
          if (!IS_A) tma_ld3_pair(base + pos, map, fb, c0, kc + 32 * (m & 1), c2);
          else tma_ld2(base + pos, map, fb, kc, 128 * m);
          mbar_expect_tx(fb, IS_A ? 16384 : bbytes);
        }
      next_stage:
        fb += 8;
        if (fb == fend) fb -= 8 * NBAR;
        pos += bbytes + 2 * UNIT;
        if (pos >= RING_UNITS * UNIT) pos -= RING_UNITS * UNIT;
      }
      special = !IS_A ? 0 : t == 2 ? 1 : add == 128 ? 0x10 : 0;
      if (t == 2) order0 = others << 4 | n;
      if (IS_A && (t == 2 || add == 64 || add == 192)) ev++;
    }
  }
}

__device__ __forceinline__ void publisher(const Params& p, uint32_t sb, int m, int n) {
  const uint32_t tag = __ldcg(p.g->epoch + m * 8 + n) + 1;
  uint32_t* word = p.g->flags + m * 32 + n;
  const int mn = m * 8 + n; (void)mn;
  st_relaxed(word, 32 * tag);
#pragma unroll 1
  for (int c = 0; c < 17; c++) {
    const int e = c >= 9 ? c - 9 : c;
    if (e == 2 || e == 7) {
      asm volatile("prefetch.tensormap [%0];" ::"l"(&p.out) : "memory");
      mbar_wait(sb + BAR_XRDY, e == 2);
      tma_st2(&p.out, sb + OFF_X, 128 * n, 128 * m);
      bulk_commit();
      if (c == 16) break;
      mbar_wait(sb + BAR_XRDY + 8, e == 2);
      bulk_wait_all();
      mbar_arrive(sb + BAR_XGO);
      PROF_E(7 * (c >= 9) + (e < 4 ? 2 : 6), 11);
    } else {
      mbar_wait(sb + BAR_PUB + 8 * e, c >= 9);
    }
    asm volatile("fence.release.gpu;" ::: "memory");
    asm volatile("red.relaxed.gpu.global.add.u32 [%0], 1;" ::"l"(word) : "memory");
    PROF_E(7 * (c >= 9) + nib(0x665432210ull, e), (0x108 >> e) & 1 ? 14 : 12);
  }
  p.g->epoch[m * 8 + n] = tag;
  bulk_wait_read();
}

__device__ __forceinline__ void sum_rows(uint32_t buf, int iters, float (&a)[8], int lane) {
  uint32_t addr = buf + (lane >> 3) * 128 + (((lane & 7) ^ (lane >> 3)) << 4);
#pragma unroll 1
  for (int it = 0; it < iters; it++) {
    uint32_t u[2][4];
    lds_u4(addr, u[0][0], u[0][1], u[0][2], u[0][3]);
    lds_u4((addr ^ 64) + 512, u[1][0], u[1][1], u[1][2], u[1][3]);
    addr += 1024;
#pragma unroll
    for (int e = 0; e < 8; e++) { a[2 * (e & 3)] += bf_lo(u[e >> 2][e & 3]); a[2 * (e & 3) + 1] += bf_hi(u[e >> 2][e & 3]); }
  }
}
__device__ __forceinline__ void publish_sums(const float (&a)[8], uint4* dst, int lane, uint32_t tag) {
  const bool u8 = lane & 8, u16 = lane & 16;
  float h4[4], h2[2];
#pragma unroll
  for (int e = 0; e < 4; e++) h4[e] = (u8 ? a[4 + e] : a[e]) + __shfl_xor_sync(0xffffffffu, u8 ? a[e] : a[4 + e], 8);
#pragma unroll
  for (int e = 0; e < 2; e++) h2[e] = (u16 ? h4[2 + e] : h4[e]) + __shfl_xor_sync(0xffffffffu, u16 ? h4[e] : h4[2 + e], 16);
  st_msg(dst + (lane & 7) * 4 + (u8 ? 2 : 0) + (u16 ? 1 : 0), __float_as_uint(h2[0]), __float_as_uint(h2[1]), 0u, tag);
}

__device__ __forceinline__ void colsum_helper(const Params& p, uint32_t sb, int m, int n, int lane) {
  const uint32_t tag = __ldcg(p.g->epoch + m * 8 + n) + 1;
  const int mn = m * 8 + n; (void)mn;
#pragma unroll 1
  for (int k = lane; k < 288; k += 32) {
    const uint32_t bb = __ldg(reinterpret_cast<const uint32_t*>(k < 224 ? p.b1 + 448 * n : p.b2 + 128 * n - 448) + k);
    const float sc = k < 224 ? 0.5f : 1.f;
    sts_f2(sb + (k < 224 ? OFF_CSF + k * 16 + 8 : OFF_CSQ + 1536 + (k - 224) * 8), sc * bf_lo(bb), sc * bf_hi(bb));
  }
  __syncwarp();
  if (elect_one()) mbar_arrive(sb + BAR_BIAS);
  bar_sync(BAR_HLP, 160);
  PROF_E(-1, 1);
#pragma unroll 1
  for (int c = 0; c < 7; c++) {
    float a[8] = {0.f, 0.f, 0.f, 0.f, 0.f, 0.f, 0.f, 0.f};
#pragma unroll 1
    for (int h = 0; h < 2; h++) {
      if (elect_one()) {
        mbar_expect_tx(sb + BAR_CSLD + 8, 4096);
        tma_ld2(sb + OFF_HLP, &p.w1c, sb + BAR_CSLD + 8, 448 * n + 64 * c, 64 * m + 32 * h);
        if (c < 6) asm volatile("cp.async.bulk.prefetch.tensor.2d.L2.global [%0, {%1, %2}];" ::"l"(&p.w1c), "r"(448 * n + 64 * c + 64), "r"(64 * m + 32 * h) : "memory");
      }
      mbar_wait(sb + BAR_CSLD + 8, h);
      sum_rows(sb + OFF_HLP, 4, a, lane);
      __syncwarp();
    }
    publish_sums(a, p.g->csp + ((8 + n) * 17 + m) * 224 + c * 32, lane, tag);
  }
  PROF_E(-1, 2);
  if (elect_one()) {
#pragma unroll 1
    for (int k = 0; k < 4; k++) {
      if (k < 3) {
        mbar_wait(sb + BAR_XGO, k & 1);
        __nanosleep(BDELAY);
      } else {
        mbar_wait(sb + BAR_XRDY + 8, 0);
      }
      tma_st2(&p.out, sb + OFF_X + 16384, 128 * n + 64, 128 * m);
      bulk_commit();
      bulk_wait_all();
      asm volatile("mbarrier.arrive.shared::cta.b64 _, [%0], 4;" ::"r"(sb + BAR_PUB + (k & 1 ? 64 : 24)) : "memory");
    }
  }
}

__device__ __forceinline__ void poll_msgs2(const uint4* pa, const uint4* pb, float (&v)[4], uint32_t tag) {
#pragma unroll 1
  for (int it = 0; it < MSG_SPINS; it++) {
    uint32_t x[4], z, ta, tb;
    ld_msg(pa, x[0], x[1], z, ta);
    ld_msg(pb, x[2], x[3], z, tb);
#pragma unroll
    for (int e = 0; e < 4; e++) v[e] = __uint_as_float(x[e]);
    if (__all_sync(0xffffffffu, ta == tag && tb == tag)) break;
  }
}
__device__ __forceinline__ void colsum_total(const Params& p, const Ctx& cx, int mat, uint32_t tag) {
  uint4* base = p.g->csp + (mat * 8 + cx.n) * 17 * 224;
  const int per = 12 + 2 * mat, k = 2 * cx.w + (cx.lane >> 4), ia = per * cx.m + k, ib = per * cx.m + min(k + 8, per - 1);
  float v[4];
  poll_msgs2(base + (cx.lane & 15) * 224 + ia, base + (cx.lane & 15) * 224 + ib, v, tag);
#pragma unroll 1
  for (int d = 1; d < 16; d *= 2)
#pragma unroll
    for (int e = 0; e < 4; e++) v[e] += __shfl_xor_sync(0xffffffffu, v[e], d);
  const bool hi = cx.lane & 1;
  if ((cx.lane & 14) == 0) st_msg(base + 16 * 224 + (hi ? ib : ia), __float_as_uint(hi ? v[2] : v[0]), __float_as_uint(hi ? v[3] : v[1]), 0u, tag);
}
__device__ __forceinline__ void colsum_gather(const Params& p, const Ctx& cx, int mat, uint32_t tag) {
  const uint4* base = p.g->csp + ((mat * 8 + cx.n) * 17 + 16) * 224;
  const int ia = cx.w * 32 + cx.lane, ib = min(ia + 128, 191 + 32 * mat);
  float v[4];
  poll_msgs2(base + ia, base + ib, v, tag);
  const uint32_t tab = cx.sb + (mat ? OFF_CSF : OFF_CSQ);
  sts_f2(tab + (ia << (3 + mat)), v[0], v[1]);
  sts_f2(tab + (ib << (3 + mat)), v[2], v[3]);
}

#define ACC(q, j, e) acc[(q) & 1][4 * (j) + 2 * ((q) >> 1) + (e)]

constexpr uint32_t RING16 = RING_UNITS * (UNIT >> 4);
__device__ __forceinline__ bool tile_split(int i) { return (0xD98 >> i) & 1; }

__device__ __forceinline__ void write_run_desc(uint32_t sb, int i, int step) {
  const int layer = i >= 7, t = i - 7 * layer, part = tile_split(i) ? step : 2;
  const bool wide = tile_wide(t), own = t != 2 && t != 6 && part != 1 && i != 0, second = t == 1 || t == 4;
  const uint32_t z16 = (wide ? 5 : 4) * (UNIT >> 4), a_off = z16 - 1024 + (uint32_t)DESC_A - (uint32_t)DESC_B;
  const int gl = 16 * t + (part == 2 ? 0 : second ? 16 * part - 14 : 4 * part), g0 = layer * STAGES_PER_LAYER + gl;
  const uint32_t s16 = (sb & 0x3FFFF) >> 4, bfirst = (uint32_t)DESC_B + s16;
  const int nkb = t == 6 ? 56 : part == 0 ? 2 : 12 + 2 * part;
  const bool win1 = t == 1 && part != 0;
  const int run = win1 ? WIN1 + 1 : t == 2 ? WIN2 + 1 : nkb;
  const int rest = win1 ? 64 | (nkb - 1 - WIN1) : t == 2 ? 64 | (7 - WIN2) | (8 << 7) : 0;
  const uint32_t blo = bfirst + z16 * (wide ? (gl + (t == 5 ? 3 : 0)) & 3 : (gl + 3) % 5);
  const uint32_t alo = own ? (uint32_t)DESC_A + s16 + (OFF_X >> 4) : blo + a_off;
  const uint32_t aoff = own ? alo + 1024 - (blo == bfirst + RING16 - z16 ? bfirst : blo + z16) : a_off;
  const bool xwait = part == 0 && !second, keep = !(part == 0 || t == 5);
  sts_u4(sb + OFF_RUN + (2 * i + step) * 16, blo, alo, aoff,
         ((g0 / NBAR) & 1) | xwait << 1 | keep << 2 | 8 * (g0 % NBAR) | run << 6 | rest << 12);
}

template <int N>
__device__ __forceinline__ void mainloop(const Params& p, float (&acc)[2][96], uint32_t sb, int i, int step, int mn) {
  constexpr uint32_t Z16 = (2 + N / 64) * (UNIT >> 4);
  constexpr uint32_t A_OFF = Z16 - 1024 + (uint32_t)DESC_A - (uint32_t)DESC_B;
  const int wg = i & 1;
  const uint32_t s16 = (sb & 0x3FFFF) >> 4;
  const uint32_t blast = (uint32_t)DESC_B + s16 + RING16 - Z16, flast = sb + BAR_FULL + 8 * (NBAR - 1);
  uint32_t blo = (uint32_t)DESC_B + s16, alo = blo + A_OFF, aoff = A_OFF, misc = 16 << 6;
  if (N == 128 || i > 0) lds_u4(sb + OFF_RUN + (2 * i + step) * 16, blo, alo, aoff, misc);
  uint32_t keep = misc & 4;
  int run = (misc >> 6) & 63, rest = misc >> 12;
  uint32_t fb = sb + BAR_FULL + (misc & 0x38), ph = misc & 1;
  uint32_t prev = sb + BAR_DUMMY - 8 * NBAR;
  const uint32_t lane_id = (threadIdx.x & 31) | p.zero, rel = pair_offset(sb, lane_id & 1) + 8 * NBAR;
  pin_regs<N / 2>(acc);
  if (N == 128 || i > 0) bar_sync(BAR_ORDER + wg, 256);
  else cluster_wait();
  if (N == 192 && i == 0 && threadIdx.x == 0) PROF_U(8);
  mbar_wait(fb, ph);
    if (misc & 2) {
    if ((HOLDM >> (N == 192)) & 1) mbar_wait(sb + BAR_XGO, N == 192);
    else mbar_wait(sb + BAR_XRDY + 8, N == 128);
  }
  if (step == 0 || !tile_split(i)) PROF_T(4 + i * 4);
#pragma unroll 1
  while (true) {
    const uint64_t da = (DESC_A & ~0xffffffffull) | alo, db = (DESC_B & ~0xffffffffull) | blo;
    asm volatile("wgmma.fence.sync.aligned;" ::: "memory");
    wgmma_ss<N>(acc[0], da, db, keep);
    wgmma_ss<N>(acc[1], da + 64, db, keep);
    keep = 4;
    wgmma_ss<N>(acc[0], da + 2, db + 128);
    wgmma_ss<N>(acc[1], da + 66, db + 128);
    asm volatile("wgmma.commit_group.sync.aligned;" ::: "memory");
    asm volatile("wgmma.wait_group.sync.aligned 1;" ::: "memory");
    PROF_S(jj++);
    if (lane_id < 2) mbar_arrive_cluster(prev + rel);
    prev = fb;
    if (fb == flast) { fb -= 8 * NBAR; ph++; }
    fb += 8;
    if (blo == blast) blo -= RING16;
    blo += Z16;
    alo = blo + aoff;
    aoff = A_OFF;
    run--;
    const bool ready = mbar_test(fb, ph) && run != 0;
    asm volatile("wgmma.fence.sync.aligned;" ::: "memory");
    wgmma_ss<N>(acc[0], da + 4, db + 4 * N);
    wgmma_ss<N>(acc[1], da + 68, db + 4 * N);
    wgmma_ss<N>(acc[0], da + 6, db + 4 * N + 128);
    wgmma_ss<N>(acc[1], da + 70, db + 4 * N + 128);
    asm volatile("wgmma.commit_group.sync.aligned;" ::: "memory");
    if (!ready) {
      if (run == 0) {
        if (rest == 0) break;
        if (rest & 64) {
          bar_arrive(BAR_GO, 256);
          bar_sync(BAR_DONE, 256);
        } else {
          alo = (uint32_t)DESC_A + s16 + (OFF_STG >> 4);
        }
        run = rest & 63;
        rest >>= 7;
      }
      mbar_wait(fb, ph);
    }
  }
  if (i < 13 && !(LATE_O && N == 192 && (misc >> 12))) bar_arrive(BAR_ORDER + (wg ^ 1), 256);
  if (N == 128 && ((0x2244 >> i) & 1)) {
    const Ctx cx = make_ctx(sb, mn);
    const uint32_t xrow = cx.sb + OFF_X + cx.w * 4096 + cx.lane * 128 + ((cx.lane & 7) << 4);
    const bool leader = elect_one();
    asm volatile("wgmma.wait_group.sync.aligned 0;" ::: "memory");
    pin_regs<64>(acc);
    PROF_T(5 + i * 4);
    PROF_E(i, 0);
#pragma unroll
    for (int h = 0; h < 2; h++) {
      if (h == 1 && p.zero != 0) break;
#pragma unroll
      for (int j = 8 * h; j < 8 * h + 8; j++)
        stsm4((xrow ^ ((j & 7) << 4)) + h * 16384, pack_bf16(ACC(0, j, 0), ACC(0, j, 1)), pack_bf16(ACC(1, j, 0), ACC(1, j, 1)),
              pack_bf16(ACC(2, j, 0), ACC(2, j, 1)), pack_bf16(ACC(3, j, 0), ACC(3, j, 1)));
      fence_async_smem();
      __syncwarp();
      if (leader) mbar_arrive(sb + BAR_XRDY + 8 * h);
      if (h == 0 && lane_id < 2) mbar_arrive_cluster(prev + rel);
    }
    PROF_E(i, 4);
    return;
  }
  asm volatile("wgmma.wait_group.sync.aligned 0;" ::: "memory");
  pin_regs<N / 2>(acc);
  if (lane_id < 2) mbar_arrive_cluster(prev + rel);
  PROF_T(5 + i * 4);
  PROF_E(i, 0);
}

__device__ __forceinline__ void write_partial_stats(const Params& p, const Ctx& c, int ln, uint32_t tag) {
  const uint32_t xrow = c.sb + OFF_X + c.w * 4096 + c.lane * 128;
  float s = 0.f, q = 0.f, s1 = 0.f, q1 = 0.f;
#pragma unroll 4
  for (int j = 0; j < 16; j++) {
    uint32_t u[4];
    lds_u4(xrow + (j >> 3) * 16384 + (((j & 7) ^ (c.lane & 7)) << 4), u[0], u[1], u[2], u[3]);
#pragma unroll
    for (int e = 0; e < 4; e++) {
      const float a = bf_lo(u[e]), d = bf_hi(u[e]);
      s += a; q = fmaf(a, a, q);
      s1 += d; q1 = fmaf(d, d, q1);
    }
  }
  s += s1;
  q += q1;
  st_msg(p.g->stats + (ln * 8 + c.n) * SEQ + 128 * c.m + 32 * c.w + c.lane, __float_as_uint(s),
         __float_as_uint(fmaxf(q - s * s * (1.f / 128.f), 0.f)), 0u, tag);
}

__device__ __forceinline__ void finish_row_stats(const Params& p, const Ctx& c, int ln, uint32_t tag) {
  const uint4* src = p.g->stats + ln * 8 * SEQ + 128 * c.m + 32 * c.w + c.lane;
  uint32_t ps[8], pm[8];
#pragma unroll 1
  for (int it = 0; it < MSG_SPINS; it++) {
    uint32_t bad = 0, u, tg;
    if (ln > 1 || it > 0) __nanosleep(STAT_NS);
#pragma unroll
    for (int k = 0; k < 8; k++) { ld_msg(src + k * SEQ, ps[k], pm[k], u, tg); bad |= tg ^ tag; }
    if (__all_sync(0xffffffffu, bad == 0)) break;
  }
  float s = 0.f, m2 = 0.f;
#pragma unroll
  for (int k = 0; k < 8; k++) s += __uint_as_float(ps[k]);
  const float mean = s * (1.f / DM);
#pragma unroll
  for (int k = 0; k < 8; k++) {
    const float d = __uint_as_float(ps[k]) * (1.f / 128.f) - mean;
    m2 += fmaf(128.f * d, d, __uint_as_float(pm[k]));
  }
  sts_f2(c.sb + OFF_ROW + (32 * c.w + c.lane) * 8, rsqrtf(m2 * (1.f / DM) + 1e-5f), mean);
  __syncwarp();
}

__device__ __forceinline__ void attn_scores(const uint32_t* qa, const uint32_t* qb, const uint32_t* k0, const uint32_t* k1,
                                            const uint32_t* k2, const uint32_t* k3, float (&l)[4], const float4& zero,
                                            bool par, bool early) {
  float s[4][4];
#pragma unroll
  for (int kb = 0; kb < 4; kb++) {
    const uint32_t* kk = kb == 0 ? k0 : kb == 1 ? k1 : kb == 2 ? k2 : k3;
    asm volatile("mma.sync.aligned.m16n8k16.row.col.f32.bf16.bf16.f32 {%0,%1,%2,%3}, {%4,%5,%6,%7}, {%8,%9}, {%10,%11,%12,%13};"
                 : "=f"(s[kb][0]), "=f"(s[kb][1]), "=f"(s[kb][2]), "=f"(s[kb][3])
                 : "r"(qa[0]), "r"(qb[0]), "r"(qa[1]), "r"(qb[1]), "r"(kk[0]), "r"(kk[1]), "f"(zero.x), "f"(zero.y),
                   "f"(zero.z), "f"(zero.w));
  }
#pragma unroll
  for (int kb = 0; kb < 4; kb++) {
    const uint32_t* kk = kb == 0 ? k0 : kb == 1 ? k1 : kb == 2 ? k2 : k3;
    mma16816(s[kb], qa[2], qb[2], qa[3], qb[3], kk[2], kk[3]);
  }
  l[0] = par ? s[1][1] : s[1][0];
  l[1] = early ? (par ? s[0][1] : s[0][0]) : (par ? s[2][1] : s[2][0]);
  l[2] = par ? s[2][3] : s[2][2];
  l[3] = early ? (par ? s[1][3] : s[1][2]) : (par ? s[3][3] : s[3][2]);
}

__device__ __forceinline__ void attn_mix(const float (&l)[4], const float (&sc)[4], const float (&off)[4], const float (&rk)[4],
                                         const uint32_t* v0, const uint32_t* v1, const uint32_t* v2, const uint32_t* v3,
                                         uint32_t* olo, uint32_t* ohi, const uint32_t (&sel)[4]) {
  float x[4];
#pragma unroll
  for (int e = 0; e < 4; e++) x[e] = fmaf(l[e], sc[e], off[e]);
  const float ml = quad_max(fmaxf(x[0], x[1])), mh = quad_max(fmaxf(x[2], x[3]));
  x[0] = ex2(x[0] - ml); x[1] = ex2(x[1] - ml);
  x[2] = ex2(x[2] - mh); x[3] = ex2(x[3] - mh);
  const uint32_t pl = pack_bf16(x[0] * rk[0], x[1] * rk[1]), ph = pack_bf16(x[2] * rk[2], x[3] * rk[3]);
  const uint32_t a0 = prmt_u(pl, sel[1]), a1 = prmt_u(pl, sel[3]), a2 = prmt_u(pl, sel[0]), a3 = prmt_u(ph, sel[1]);
  const uint32_t c0 = prmt_u(pl, sel[2]), c1 = prmt_u(ph, sel[0]), c2 = prmt_u(ph, sel[3]), c3 = prmt_u(ph, sel[2]);
  float o[4][4];
#pragma unroll
  for (int jn = 0; jn < 4; jn++) {
    o[jn][0] = o[jn][1] = o[jn][2] = o[jn][3] = 0.f;
    mma16816(o[jn], a0, a1, a2, a3, v0[jn], v1[jn]);
  }
#pragma unroll
  for (int jn = 0; jn < 4; jn++) mma16816(o[jn], c0, c1, c2, c3, v2[jn], v3[jn]);
  const float il = rcp_hw(quad_sum(x[0] + x[1])), ih = rcp_hw(quad_sum(x[2] + x[3]));
#pragma unroll
  for (int jn = 0; jn < 4; jn++) {
    olo[jn] = pack_bf16(o[jn][0] * il, o[jn][1] * il);
    ohi[jn] = pack_bf16(o[jn][2] * ih, o[jn][3] * ih);
  }
}

__device__ __forceinline__ void gelu_epilogue(const Params& p, float (&acc)[2][96], const Ctx& cx, int t) {
  UNPACK_CTX(cx);
  (void)wg;
  float rs[4], rm[4];
#pragma unroll
  for (int q = 0; q < 4; q++) {
    const float2 v = lds_f2(sb + OFF_ROW + (32 * w + 8 * q + (lane >> 2)) * 8);
    rs[q] = 0.5f * v.x;
    rm[q] = -rs[q] * v.y;
  }
  const int col0 = 128 * (t - 3);
  const uint32_t stg = sb + OFF_STG + w * 4096;
  const uint32_t ctab = sb + OFF_CSF + (col0 / 2 + (lane & 3)) * 16, srow = stg + lane * 128 + ((lane & 7) << 4);
  __nanosleep((t == 5 ? STAG5 : t == 4 ? STAG4 : STAG3) * w);
  float4 nb = lds_f4(ctab);
#pragma unroll
  for (int c = 0; c < 3; c++) {
    if (c == 2 && t != 5) break;
    uint32_t hp[8][4];
#pragma unroll
    for (int j = 0; j < 8; j++) {
      const float4 cb = nb;
      if (8 * c + j < 23) nb = lds_f4(ctab + (8 * c + j + 1) * 64);
#pragma unroll
      for (int q = 0; q < 4; q++) {
        float y[2];
        const int k = 4 * j + q - GELU_DEP;
        const float rmq = k >= 0 ? chain(rm[q], hp[k >> 2][k & 3], p.zero) : rm[q];
#pragma unroll
        for (int e = 0; e < 2; e++) {
          const float z = fmaf(ACC(q, 8 * c + j, e), rs[q], fmaf(rmq, e ? cb.y : cb.x, e ? cb.w : cb.z));
          const float u = z * fmaf(z * z, 8.f * 0.7978845608028654f * 0.044715f, 2.f * 0.7978845608028654f);
          y[e] = fmaf(z, tanh_hw(u), z);
        }
        hp[j][q] = pack_bf16(y[0], y[1]);
      }
      if (j == STG_WAIT && c > 0) {
        if (lane == 0) bulk_wait_read();
        __syncwarp();
      }
      if (c == 0 || j > STG_WAIT) {
        stsm4(srow ^ (j << 4), hp[j][0], hp[j][1], hp[j][2], hp[j][3]);
      } else if (j == STG_WAIT) {
#pragma unroll
        for (int jj = 0; jj <= STG_WAIT; jj++) stsm4(srow ^ (jj << 4), hp[jj][0], hp[jj][1], hp[jj][2], hp[jj][3]);
      }
    }
    fence_async_smem();
    __syncwarp();
    if (lane == 0) {
      tma_st2(&p.h_st, stg, 448 * n + col0 + 64 * c, 128 * m + 32 * w);
      bulk_commit();
    }
  }
#pragma unroll
  for (int r = 0; r < 16; r++) acc[0][r] = acc[1][r] = 0.f;
}

__device__ __forceinline__ void attn_epilogue(const Params& p, float (&acc)[2][96], const Ctx& cx, int layer, int t, uint32_t tag) {
  UNPACK_CTX(cx);
  const bool par = (lane >> 2) & 1, early = (lane & 3) > (lane >> 3);
  const uint32_t ktab = sb + OFF_ROW + (32 * w + 2 * (lane & 3) + par) * 8, exc = sb + OFF_STG + w * 4096 + lane * 16;
  const int slot = ((layer * 2 + t) * 16 + m) * 8 + n;
  const int mn = m * 8 + n; (void)mn;
  uint32_t Q[4][8], K[4][8], V[4][8], E[36], P[36];
  float kr[6], qr[4];
#pragma unroll
  for (int q = 2; q < 4; q++) {
    kr[2 + q] = lds_f(ktab + 64 * q);
#pragma unroll
    for (int j = 0; j < 8; j++) {
      E[8 * (q - 2) + j] = K[q][j] = pack_bf16(ACC(q, 8 + j, 0), ACC(q, 8 + j, 1));
      E[16 + 2 * j + q - 2] = V[q][j] = movtrans(pack_bf16(ACC(q, 16 + j, 0), ACC(q, 16 + j, 1)));
    }
  }
#pragma unroll
  for (int j = 0; j < 16; j++) K[j >> 3][j & 7] = pack_bf16(ACC(j >> 3, 8 + (j & 7), 0), ACC(j >> 3, 8 + (j & 7), 1));
#pragma unroll
  for (int j = 0; j < 16; j++) asm volatile("" : "+r"(K[j >> 3][j & 7]));
  E[32] = __float_as_uint(kr[4]);
  E[33] = E[34] = E[35] = __float_as_uint(kr[5]);
  if (w < 3) {
#pragma unroll
    for (int k = 0; k < 8; k++) sts_u4(exc + k * 512, E[4 * k], E[4 * k + 1], E[4 * k + 2], E[4 * k + 3]);
  } else {
#pragma unroll
    for (int k = 0; k < 12; k++) st_msg(p.g->halo + slot * 384 + k * 32 + lane, E[3 * k], E[3 * k + 1], E[3 * k + 2], tag);
  }
  bar_arrive(BAR_PAIR + w, 64);
  if (LATE_O && t == 1) bar_arrive(BAR_ORDER + (wg ^ 1), 256);
  PROF_E(7 * layer + t, 1);
#pragma unroll
  for (int q = 0; q < 4; q++) {
    qr[q] = lds_f(sb + OFF_ROW + (32 * w + 8 * q + (lane >> 2)) * 8) * (0.17677669529663687f * 1.4426950408889634f);
#pragma unroll
    for (int j = 0; j < 8; j++) Q[q][j] = pack_bf16(ACC(q, j, 0), ACC(q, j, 1));
    if (q < 2) {
      kr[2 + q] = lds_f(ktab + 64 * q);
#pragma unroll
      for (int j = 0; j < 8; j++) V[q][j] = movtrans(pack_bf16(ACC(q, 16 + j, 0), ACC(q, 16 + j, 1)));
    }
  }
  PROF_E(7 * layer + t, 6);
  bar_sync(BAR_PAIR + ((w + 3) & 3), 64);
  if (w > 0 || m == 0) {
    const uint32_t back = w > 0;
#pragma unroll
    for (int k = 0; k < 8; k++) lds_u4(exc - back * 4096 + k * 512, P[4 * k], P[4 * k + 1], P[4 * k + 2], P[4 * k + 3]);
    P[32] = lds_u(ktab - back * 128);
    P[33] = lds_u(ktab - back * 64);
  } else {
    if (HALO_NS) __nanosleep(HALO_NS);
#pragma unroll 1
    for (int it = 0; it < MSG_SPINS; it++) {
      uint32_t tg, bad = 0;
      if (it > 0) poll_line(reinterpret_cast<const uint32_t*>(p.g->halo + (slot - 8) * 384 + 383) + 3, tag, 1u);
#pragma unroll
      for (int k = 0; k < 12; k++) {
        ld_msg(p.g->halo + (slot - 8) * 384 + k * 32 + lane, P[3 * k], P[3 * k + 1], P[3 * k + 2], tg);
        bad |= tg ^ tag;
      }
      if (__all_sync(0xffffffffu, bad == 0)) break;
    }
  }
  kr[0] = __uint_as_float(P[32]);
  kr[1] = __uint_as_float(P[33]);
  uint32_t PV[2][8];
#pragma unroll
  for (int j = 0; j < 8; j++) { PV[0][j] = P[16 + 2 * j]; PV[1][j] = P[17 + 2 * j]; }
  float rk[2][4], sc[2][4], off[2][4];
#pragma unroll
  for (int g = 0; g < 2; g++) {
    rk[g][0] = kr[2 * g + 1];
    rk[g][1] = early ? kr[2 * g] : kr[2 * g + 2];
    rk[g][2] = kr[2 * g + 2];
    rk[g][3] = early ? kr[2 * g + 1] : kr[2 * g + 3];
#pragma unroll
    for (int e = 0; e < 4; e++) {
      const bool masked = g == 0 && e != 2 && (m | w) == 0 && (e == 0 || early);
      sc[g][e] = masked ? 0.f : rk[g][e] * qr[2 * g + (e >> 1)];
      off[g][e] = masked ? -1e30f : 0.f;
    }
  }
  const uint32_t none = 0x4444u | p.zero, second = par ? 0x3244u : 0x4432u;
  const uint32_t sel[4] = {par ? 0x1044u : 0x4410u, early ? second : none, early ? none : second, none};
  if (w == 0 && elect_one()) asm volatile("prefetch.tensormap [%0];" ::"l"(&p.att_st) : "memory");
  PROF_E(7 * layer + t, 2);
  bar_sync(BAR_GO, 256);
  const float4 zero = lds_f4(sb + OFF_ZERO);
  float l[2][2][4];
  uint32_t O[4][8];
#pragma unroll
  for (int h = 0; h < 2; h++) {
    if (h == 1) {
      Q[2][4] |= __float_as_uint(l[1][0][0]) & p.zero;
      Q[0][4] |= __float_as_uint(l[0][0][0]) & p.zero;
    }
    attn_scores(&Q[2][4 * h], &Q[3][4 * h], &K[0][4 * h], &K[1][4 * h], &K[2][4 * h], &K[3][4 * h], l[1][h], zero, par, early);
    attn_scores(&Q[0][4 * h], &Q[1][4 * h], &P[4 * h], &P[8 + 4 * h], &K[0][4 * h], &K[1][4 * h], l[0][h], zero, par, early);
  }
  const uint32_t stg = sb + OFF_STG + w * 4096, srow = stg + lane * 128 + ((lane & 7) << 4);
#pragma unroll
  for (int h = 0; h < 2; h++) {
    attn_mix(l[1][h], sc[1], off[1], rk[1], &V[0][4 * h], &V[1][4 * h], &V[2][4 * h], &V[3][4 * h], &O[2][4 * h], &O[3][4 * h], sel);
    attn_mix(l[0][h], sc[0], off[0], rk[0], &PV[0][4 * h], &PV[1][4 * h], &V[0][4 * h], &V[1][4 * h], &O[0][4 * h], &O[1][4 * h], sel);
#pragma unroll
    for (int j = 4 * h; j < 4 * h + 4; j++) stsm4(srow ^ (j << 4), O[0][j], O[1][j], O[2][j], O[3][j]);
  }
  bar_arrive(BAR_DONE, 256);
  fence_async_smem();
  __syncwarp();
  if (lane == 0) {
    tma_st2(&p.att_st, stg, 128 * n + 64 * t, 128 * m + 32 * w);
    bulk_commit();
  }
}

template <bool PACED>
__device__ __forceinline__ void rank1_update(const Params& p, float (&acc)[2][96], const Ctx& cx, int t) {
  float nm[4];
#pragma unroll
  for (int q = 0; q < 4; q++) nm[q] = t == 6 ? 1.f : -lds_f(cx.sb + OFF_ROW + (32 * cx.w + 8 * q + (cx.lane >> 2)) * 8 + 4);
  const uint32_t ctab = cx.sb + OFF_CSQ + ((t & 3) * 192 + 2 * (cx.lane & 3)) * 4;
#pragma unroll
  for (int j = 0; j < 24; j++) {
    const float2 cs = lds_f2(ctab + j * 32);
#pragma unroll
    for (int q = 0; q < 4; q++) {
      const int k = 4 * j + q - 1;
      const float nq = PACED && k >= 0 ? chain(nm[q], __float_as_uint(ACC(k & 3, k >> 2, 1)), p.zero) : nm[q];
      ACC(q, j, 0) = fmaf(nq, cs.x, ACC(q, j, 0));
      ACC(q, j, 1) = fmaf(nq, cs.y, ACC(q, j, 1));
    }
  }
}

__device__ __forceinline__ void finish_stores(uint32_t sb, int i) {
  const int t = i >= 7 ? i - 7 : i;
  if ((threadIdx.x & 31) == 0) {
    bulk_wait_all();
    mbar_arrive(sb + BAR_PUB + 8 * (t < 2 ? t : t + 1));
  }
  __syncwarp();
  if (i < 12) bar_arrive(BAR_GUARD + ((i & 1) ^ 1), 256);
}

__device__ __forceinline__ bool consumer_tile(const Params& p, float (&acc)[2][96], uint32_t sb0, int i, int mn) {
  const int layer = i >= 7, t = i - 7 * layer, wg = i & 1;
  const bool resid = t == 2 || t == 6;
  {
    if (resid) {
      const Ctx cx = make_ctx(sb0, mn);
      const uint32_t xrow = cx.sb + OFF_X + cx.w * 4096 + cx.lane * 128;
      const uint32_t sel_lo = 0x1044u | p.zero, sel_hi = 0x3244u | p.zero;
#pragma unroll
      for (int j = 0; j < 16; j++) {
        uint32_t r[4];
        ldsm4(xrow + (j >> 3) * 16384 + (((j & 7) ^ (cx.lane & 7)) << 4), r[0], r[1], r[2], r[3]);
#pragma unroll
        for (int q = 0; q < 4; q++) {
          ACC(q, j, 0) = prmt_f(r[q], sel_lo);
          ACC(q, j, 1) = prmt_f(r[q], sel_hi);
        }
      }
    }
    if (t >= 5 || i == 7) finish_stores(sb0, i - 2);
#pragma unroll 1
    for (int step = !tile_split(i);; step++) {
      if (step == 1 && (t == 1 || t == 4)) {
        const Ctx cx = make_ctx(sb0, mn);
        if (i == 1) {
          const uint32_t epoch = __ldcg(p.g->epoch + (mn & 127));
          cluster_wait();
          asm volatile("st.shared.u32 [%0], %1;" ::"r"(sb0 + OFF_TAG), "r"(epoch + 1) : "memory");
        }
        const uint32_t tag = lds_u(cx.sb + OFF_TAG);
        const int ln = (i + 1) >> 2;
#pragma unroll 1
        for (int r = 0; r < 2; r++) {
          if (i == 1) {
            if (cx.w < 3) {
              float a[8] = {0.f, 0.f, 0.f, 0.f, 0.f, 0.f, 0.f, 0.f};
              mbar_wait(sb0 + BAR_CSLD, r);
#pragma unroll 1
              for (int h = 0; h < 2; h++) sum_rows(cx.sb + OFF_STG + h * 12288 + cx.w * 4096, 4, a, cx.lane);
              publish_sums(a, p.g->csp + (cx.n * 17 + cx.m) * 224 + (3 * r + cx.w) * 32, cx.lane, tag);
            }
            PROF_E(-1, 5 + r);
          }
          if (r == 1) break;
          if (i == 1) {
            bar_sync(BAR_WG + 1, 128);
            if (cx.w == 3 && elect_one()) {
              mbar_expect_tx(sb0 + BAR_CSLD, 24576);
              tma_ld3(sb0 + OFF_STG, &p.wqkv, sb0 + BAR_CSLD, 128 * cx.n + 64, 64 * cx.m, 0);
              tma_ld3(sb0 + OFF_STG + 12288, &p.wqkv, sb0 + BAR_CSLD, 128 * cx.n + 64, 64 * cx.m + 32, 0);
            }
            mbar_wait(sb0 + BAR_XRDY, 0);
            mbar_wait(sb0 + BAR_XRDY + 8, 0);
          }
          write_partial_stats(p, cx, ln, tag);
          PROF_E(i - 2, 8);
        }
        if (i == 1) {
          bar_arrive(BAR_HLP, 160);
          bar_sync(BAR_INIT, 160);
        }
        if (i <= 4) colsum_total(p, cx, ln, tag);
        PROF_E(i - 2, 9);
        if (i != 1) bar_sync(BAR_GUARD + wg, 256);
        finish_row_stats(p, cx, ln, tag);
        PROF_E(i - 2, 10);
        if (i == 4) {
          colsum_gather(p, cx, 1, tag);
          mbar_wait(sb0 + BAR_BIAS, 0);
        }
        PROF_E(i - 2, 15);
        bar_arrive(BAR_GUARD + (wg ^ 1), 256);
      }
      if (step == 2 && !resid) bar_sync(BAR_GUARD + wg, 256);
      if (step == 2 && i == 0) {
        colsum_gather(p, make_ctx(sb0, mn), 0, lds_u(sb0 + OFF_TAG));
        bar_sync(BAR_WG, 128);
      }
      if (i == 1) {
        if (step == 2) rank1_update<false>(p, acc, make_ctx(sb0, mn), t);
      } else if (t + step == 2 || t == 6) {
        rank1_update<true>(p, acc, make_ctx(sb0, mn), t);
      }
      if (step == 2) break;
      if (tile_wide(t)) {
        mainloop<192>(p, acc, sb0, i, step, mn);
      } else {
        mainloop<128>(p, acc, sb0, i, step, mn);
        if (resid) return false;
      }
    }
    if (t < 2) return true;
    gelu_epilogue(p, acc, make_ctx(sb0, mn), t);
    PROF_E(i, 4);
    return false;
  }
}

__global__ void __cluster_dims__(2, 1, 1) __launch_bounds__(384, 1) fused_layers_kernel(const int by_smid, const __nv_bfloat16* x_p, const __nv_bfloat16* wqkv_p,
                                                                  const __grid_constant__ Params p) {
  extern __shared__ __align__(1024) uint8_t smem_raw[];
  const uint32_t sb = uniform((uint32_t)__cvta_generic_to_shared(smem_raw));
  const int tid = threadIdx.x, lane = tid & 31, warp = uniform(tid >> 5), wg = warp >> 2, w = warp & 3;

  int mn;
  {
    int id = blockIdx.x;
    if (by_smid) asm volatile("mov.u32 %0, %%smid;" : "=r"(id));
    else if (id >= 120) id += 4;
    const int c = id >> 1;
    int g, j;
    if (c < 32) { g = c & 7; j = c >> 3; }
    else if (c < 60) { g = 1 + (c - 32) % 7; j = 4 + (c - 32) / 7; }
    else { g = 0; j = c - 58; }
    const int r = blockIdx.x & 1;
    mn = (g * 2 + r) * 8 + j;
    if (c == 60 || c == 61) {
      if (tid < 32) {
        const uint32_t tag = __ldcg(p.g->epoch + NCTA + (id & 3)) + 1;
#pragma unroll 1
        for (int mm = 0; mm < 16; mm++) poll_line(p.g->flags + mm * 32 + (lane & 7), 32 * tag, 0xffu);
        if (tid == 0) p.g->epoch[NCTA + (id & 3)] = tag;
      }
      return;
    }
  }
  const int m = mn >> 3, n = mn & 7;
  if (tid == 256) PROF_U(1);
  if (tid >= 382) asm volatile("prefetch.global.L2 [%0];" ::"l"(tid & 1 ? wqkv_p + 128 * n : x_p + 128 * m * DM));
  if (wg < 2) {
    cluster_arrive();
    asm volatile("setmaxnreg.inc.sync.aligned.u32 232;");
    const int id = mn | (warp << 7);
#pragma unroll 1
    for (int i = wg;; i += 2) {
      float acc[2][96];
#pragma unroll
      for (int r = 0; r < 96; r++) acc[0][r] = acc[1][r] = 0.f;
      pin_regs<96>(acc);
#pragma unroll 1
      while (!consumer_tile(p, acc, sb, i, id)) {
        PROF_T(6 + i * 4);
        i += 2;
        if (i >= 14) goto all_done;
      }
      attn_epilogue(p, acc, make_ctx(sb, id), i >= 7, i >= 7 ? i - 7 : i, lds_u(sb + OFF_TAG));
      PROF_E(i, 4);
      finish_stores(sb, i);
      PROF_E(i, 5);
      PROF_T(6 + i * 4);
    }
  all_done:
    if (wg == 0) {
      finish_stores(sb, 12);
    } else {
      cluster_arrive();
      cluster_wait();
    }
  } else {
    asm volatile("setmaxnreg.dec.sync.aligned.u32 40;");
    if (w != 0) {
      if (w == 1 && elect_one()) {
        mbar_init(sb + BAR_FULL + 32, 2);
#pragma unroll
        for (int k = 0; k < NBAR; k++) mbar_init(sb + BAR_EMPTY + 8 * k, 8);
#pragma unroll
        for (int k = 0; k < 3; k++) mbar_init(sb + BAR_XRDY + 8 * k, 4);
#pragma unroll
        for (int k = 0; k < 9; k++) mbar_init(sb + BAR_PUB + 8 * k, 4);
#pragma unroll
        for (int k = 0; k < 4; k++) mbar_init(sb + BAR_CSLD + 8 * k, 1);
        sts_f2(sb + OFF_ZERO, 0.f, 0.f);
        sts_f2(sb + OFF_ZERO + 8, 0.f, 0.f);
        asm volatile("fence.mbarrier_init.release.cluster;" ::: "memory");
      }
      __syncwarp();
      cluster_arrive();
      if (w == 2) {
        if (lane < 28) write_run_desc(sb, lane >> 1, lane & 1);
        bar_arrive(BAR_INIT, 160);
      }
      cluster_wait();
      if (w == 1) producer<true>(p, sb, m, n, lane);
      else if (w == 3) colsum_helper(p, sb, m, n, lane);
      else if (elect_one()) publisher(p, sb, m, n);
    } else {
      const bool leader = elect_one();
      if (leader) {
#pragma unroll
        for (int k = 0; k < 4; k++) mbar_init(sb + BAR_FULL + 8 * k, 2);
        asm volatile("fence.mbarrier_init.release.cluster;" ::: "memory");
        PROF_U(4);
      }
      __syncwarp();
      cluster_arrive();
      if (leader) {
#pragma unroll 1
        for (int k = 0; k < 4; k++) {
          const uint32_t fb = sb + BAR_FULL + 8 * k;
          mbar_expect_tx(fb, 16384);
          tma_ld2(sb + (5 * k + 3) * UNIT, &p.xin, fb, 64 * k, 128 * m);
          mbar_expect_tx(fb, 3 * UNIT);
          tma_ld3(sb + 5 * k * UNIT, &p.wqkv, fb, 128 * n, 64 * k, 0);
          tma_ld3(sb + 5 * k * UNIT + 12288, &p.wqkv, fb, 128 * n, 64 * k + 32, 0);
        }
        PROF_U(5);
      }
      __syncwarp();
      cluster_wait();
      if (leader) {
        mbar_expect_tx(sb + BAR_CSLD, 24576);
        tma_ld3(sb + OFF_STG, &p.wqkv, sb + BAR_CSLD, 128 * n, 64 * m, 0);
        tma_ld3(sb + OFF_STG + 12288, &p.wqkv, sb + BAR_CSLD, 128 * n, 64 * m + 32, 0);
#pragma unroll 1
        for (int h = 0; h < 2; h++) {
          const uint32_t xr = sb + BAR_XRDY + 8 * h;
          mbar_expect_tx(xr, 16384);
          tma_ld2(sb + OFF_X + h * 16384, &p.xin, xr, 128 * n + 64 * h, 128 * m);
          asm volatile("mbarrier.arrive.shared::cta.b64 _, [%0], 3;" ::"r"(xr) : "memory");
        }
        PROF_U(6);
      }
      __syncwarp();
      producer<false>(p, sb, m, n, lane);
    }
  }
}

typedef CUresult (*EncodeFn)(CUtensorMap*, CUtensorMapDataType, cuuint32_t, void*, const cuuint64_t*, const cuuint64_t*,
                             const cuuint32_t*, const cuuint32_t*, CUtensorMapInterleave, CUtensorMapSwizzle,
                             CUtensorMapL2promotion, CUtensorMapFloatOOBfill);

#define PROMO2 CU_TENSOR_MAP_L2_PROMOTION_L2_128B
#define PROMO3 CU_TENSOR_MAP_L2_PROMOTION_L2_128B
void make_2d(EncodeFn enc, CUtensorMap* m, const void* ptr, uint64_t cols, uint64_t rows, uint32_t box_rows) {
  cuuint64_t d[2] = {cols, rows}, st[1] = {cols * 2};
  cuuint32_t b[2] = {64, box_rows}, e[2] = {1, 1};
  enc(m, CU_TENSOR_MAP_DATA_TYPE_BFLOAT16, 2, const_cast<void*>(ptr), d, st, b, e, CU_TENSOR_MAP_INTERLEAVE_NONE,
      CU_TENSOR_MAP_SWIZZLE_128B, PROMO2, CU_TENSOR_MAP_FLOAT_OOB_FILL_NONE);
}
void make_3d(EncodeFn enc, CUtensorMap* m, const void* ptr, uint64_t d0, uint64_t rows, uint64_t d2, uint64_t row_bytes,
             uint64_t chunk_bytes, uint32_t box_chunks) {
  cuuint64_t d[3] = {d0, rows, d2}, st[2] = {row_bytes, chunk_bytes};
  cuuint32_t b[3] = {64, 32, box_chunks}, e[3] = {1, 1, 1};
  enc(m, CU_TENSOR_MAP_DATA_TYPE_BFLOAT16, 3, const_cast<void*>(ptr), d, st, b, e, CU_TENSOR_MAP_INTERLEAVE_NONE,
      CU_TENSOR_MAP_SWIZZLE_128B, PROMO3, CU_TENSOR_MAP_FLOAT_OOB_FILL_NONE);
}

}

extern "C" void kernel_launch(void* const* d_in, const int* in_sizes, int n_in, void* d_out, int out_size) {
  (void)in_sizes; (void)n_in; (void)out_size;
  static EncodeFn enc = nullptr;
  static void *att = nullptr, *hbuf = nullptr, *scratch = nullptr;
  static int by_smid = 0;
  if (!enc) {
    void* fn = nullptr;
    cudaDriverEntryPointQueryResult q;
    cudaGetDriverEntryPoint("cuTensorMapEncodeTiled", &fn, cudaEnableDefault, &q);
    enc = (EncodeFn)fn;
    cudaGetSymbolAddress(&att, g_att);
    cudaGetSymbolAddress(&hbuf, g_h);
    cudaGetSymbolAddress(&scratch, g_scratch);
    cudaFuncSetAttribute(fused_layers_kernel, cudaFuncAttributeMaxDynamicSharedMemorySize, SMEM_BYTES);
    int sms = 0, clusters = 0, dev = 0;
    cudaGetDevice(&dev);
    cudaDeviceGetAttribute(&sms, cudaDevAttrMultiProcessorCount, dev);
    cudaLaunchConfig_t cfg = {};
    cfg.gridDim = dim3(132);
    cfg.blockDim = dim3(384);
    cfg.dynamicSmemBytes = SMEM_BYTES;
    cudaLaunchAttribute at[1];
    at[0].id = cudaLaunchAttributeClusterDimension;
    at[0].val.clusterDim.x = 2; at[0].val.clusterDim.y = 1; at[0].val.clusterDim.z = 1;
    cfg.attrs = at;
    cfg.numAttrs = 1;
    if (cudaOccupancyMaxActiveClusters(&clusters, fused_layers_kernel, &cfg) != cudaSuccess) (void)cudaGetLastError();
    by_smid = sms == 132 && clusters == 66;
  }
  Params p;
  make_2d(enc, &p.xin, d_in[0], DM, SEQ, 128);
  make_2d(enc, &p.out, d_out, DM, SEQ, 128);
  make_2d(enc, &p.att, att, DM, SEQ, 128);
  make_2d(enc, &p.h, hbuf, FF, SEQ, 128);
  make_2d(enc, &p.att_st, att, DM, SEQ, 32);
  make_2d(enc, &p.h_st, hbuf, FF, SEQ, 32);
  make_2d(enc, &p.w1c, d_in[4], FF, DM, 32);
  make_3d(enc, &p.wqkv, d_in[1], DM, DM, 3, 3 * DM * 2, DM * 2, 3);
  make_3d(enc, &p.wo, d_in[2], 64, DM, DM / 64, DM * 2, 128, 2);
  make_3d(enc, &p.w1a, d_in[4], 64, DM, FF / 64, FF * 2, 128, 3);
  make_3d(enc, &p.w1b, d_in[4], 64, DM, FF / 64, FF * 2, 128, 2);
  make_3d(enc, &p.w2, d_in[6], 64, FF, DM / 64, DM * 2, 128, 2);
  p.b1 = (const __nv_bfloat16*)d_in[5];
  p.b2 = (const __nv_bfloat16*)d_in[7];
  p.g = (Scratch*)scratch;
  p.zero = 0;
  fused_layers_kernel<<<by_smid ? 132 : NCTA, 384, SMEM_BYTES>>>(by_smid, (const __nv_bfloat16*)d_in[0], (const __nv_bfloat16*)d_in[1], p);
}
```

```cpp
#include <cuda_runtime.h>
#include <cuda_bf16.h>
#include <cuda.h>
#include <stdint.h>

namespace {

constexpr int SEQ = 2048, DM = 1024, FF = 3584;
constexpr int NCTA = 128;
constexpr int NBAR = 5;

constexpr uint32_t RING_UNITS = 20, UNIT = 8192;
constexpr uint32_t OFF_X   = RING_UNITS * UNIT;
constexpr uint32_t OFF_STG = OFF_X + 32768;
constexpr uint32_t OFF_HLP = OFF_STG + 16384;
constexpr uint32_t OFF_RUN = OFF_STG + 24576;
constexpr uint32_t OFF_CSQ = OFF_RUN + 512;
constexpr uint32_t OFF_CSF = OFF_CSQ + 2048;
constexpr uint32_t OFF_ROW = OFF_CSF + 3584;
constexpr uint32_t OFF_BAR = OFF_ROW + 1024;
constexpr uint32_t SMEM_BYTES = OFF_BAR + 384;
constexpr uint32_t BAR_FULL = OFF_BAR, BAR_EMPTY = OFF_BAR + 8 * NBAR;
constexpr uint32_t BAR_XRDY = OFF_BAR + 80;
constexpr uint32_t BAR_DUMMY = OFF_BAR + 96, OFF_TAG = OFF_BAR + 104, OFF_ZERO = OFF_BAR + 112;
constexpr uint32_t BAR_PUB = OFF_BAR + 128;
constexpr uint32_t BAR_CSLD = OFF_BAR + 200;
constexpr uint32_t BAR_XGO = OFF_BAR + 224;
constexpr uint32_t BAR_BIAS = OFF_BAR + 216;

constexpr uint64_t DESC_A = (1ull << 62) | ((uint64_t)(2048 >> 4) << 32) | (1ull << 16);
constexpr uint64_t DESC_B = (1ull << 62) | ((uint64_t)(1024 >> 4) << 32) | ((uint64_t)(4096 >> 4) << 16);

constexpr int BAR_INIT = 0, BAR_ORDER = 1, BAR_GUARD = 3, BAR_WG = 5, BAR_GO = 7, BAR_DONE = 8, BAR_HLP = 9, BAR_PAIR = 11;
#define GELU_DEP 2
#define MAP 2
#define LATE_O 1
#define HALO_NS 200
#define STG_WAIT 5
#define STAT_NS 800
#define HOLDM 3
#define BDELAY 100
#define STAG5 450
#define STAG4 0
#define STAG3 0
#define PRENORM 0
#define WIN1 8
#define WIN2 2

struct Scratch {
  uint4 stats[4 * 8 * SEQ];
  uint4 halo[2 * 2 * 16 * 8 * 384];
  uint4 csp[2 * 8 * 17 * 224];
  uint32_t flags[16 * 32];
  uint32_t epoch[NCTA + 4];
};

struct Params {
  CUtensorMap xin, out, att, h, wqkv, wo, w1a, w1b, w2, att_st, h_st, w1c;
  const __nv_bfloat16 *b1, *b2;
  Scratch* g;
  uint32_t zero;
};

__device__ __nv_bfloat16 g_att[SEQ * DM];
__device__ __nv_bfloat16 g_h[SEQ * FF];
__device__ Scratch g_scratch;
#define PROF_T(idx)
#define PROF_U(k)
#define PROF_S(g)
#define PROF_E(i, k)

__device__ __forceinline__ void mbar_init(uint32_t bar, int cnt) {
  asm volatile("mbarrier.init.shared::cta.b64 [%0], %1;" ::"r"(bar), "r"(cnt));
}
__device__ __forceinline__ void mbar_expect_tx(uint32_t bar, uint32_t bytes) {
  asm volatile("mbarrier.arrive.expect_tx.shared::cta.b64 _, [%0], %1;" ::"r"(bar), "r"(bytes) : "memory");
}
__device__ __forceinline__ void mbar_arrive(uint32_t bar) {
  asm volatile("mbarrier.arrive.shared::cta.b64 _, [%0];" ::"r"(bar) : "memory");
}
__device__ __forceinline__ bool mbar_test(uint32_t bar, uint32_t parity) {
  uint32_t ok;
  asm volatile("{\n.reg .pred p;\nmbarrier.test_wait.parity.shared::cta.b64 p, [%1], %2;\nselp.u32 %0, 1, 0, p;\n}"
               : "=r"(ok) : "r"(bar), "r"(parity) : "memory");
  return ok;
}
__device__ __forceinline__ void mbar_wait(uint32_t bar, uint32_t parity) {
  asm volatile(
      "{\n.reg .pred p;\n.reg .u32 it;\nmov.u32 it, 0;\n"
      "WAIT_LOOP:\n"
      "mbarrier.try_wait.parity.shared::cta.b64 p, [%0], %1;\n"
      "@p bra WAIT_DONE;\n"
      "add.u32 it, it, 1;\n"
      "setp.lt.u32 p, it, 0x400000;\n"
      "@p bra WAIT_LOOP;\n"
      "trap;\n"
      "WAIT_DONE:\n}"
      ::"r"(bar), "r"(parity) : "memory");
}
__device__ __forceinline__ void bar_sync(int id, int n) { asm volatile("bar.sync %0, %1;" ::"r"(id), "r"(n) : "memory"); }
__device__ __forceinline__ void bar_arrive(int id, int n) { asm volatile("bar.arrive %0, %1;" ::"r"(id), "r"(n) : "memory"); }
__device__ __forceinline__ void tma_ld2(uint32_t dst, const CUtensorMap* m, uint32_t bar, int c0, int c1) {
  asm volatile("cp.async.bulk.tensor.2d.shared::cluster.global.mbarrier::complete_tx::bytes [%0], [%1, {%3, %4}], [%2];"
               ::"r"(dst), "l"(m), "r"(bar), "r"(c0), "r"(c1) : "memory");
}
__device__ __forceinline__ void tma_ld_act(uint32_t dst, const CUtensorMap* m, uint32_t bar, int col, int blk) {
  asm volatile("cp.async.bulk.tensor.4d.shared::cluster.global.mbarrier::complete_tx::bytes [%0], [%1, {%3, %5, %5, %4}], [%2];"
               ::"r"(dst), "l"(m), "r"(bar), "r"(col), "r"(2 * blk), "r"(0) : "memory");
}
__device__ __forceinline__ void tma_st_act(const CUtensorMap* m, uint32_t src, int col, int blk) {
  asm volatile("cp.async.bulk.tensor.4d.global.shared::cta.bulk_group [%0, {%2, %4, %4, %3}], [%1];"
               ::"l"(m), "r"(src), "r"(col), "r"(2 * blk), "r"(0) : "memory");
}
__device__ __forceinline__ void tma_ld3(uint32_t dst, const CUtensorMap* m, uint32_t bar, int c0, int c1, int c2) {
  asm volatile("cp.async.bulk.tensor.3d.shared::cluster.global.mbarrier::complete_tx::bytes [%0], [%1, {%3, %4, %5}], [%2];"
               ::"r"(dst), "l"(m), "r"(bar), "r"(c0), "r"(c1), "r"(c2) : "memory");
}
__device__ __forceinline__ void tma_ld3_pair(uint32_t dst, const CUtensorMap* m, uint32_t bar, int c0, int c1, int c2) {
  asm volatile("cp.async.bulk.tensor.3d.shared::cluster.global.mbarrier::complete_tx::bytes.multicast::cluster"
               " [%0], [%1, {%3, %4, %5}], [%2], %6;"
               ::"r"(dst), "l"(m), "r"(bar), "r"(c0), "r"(c1), "r"(c2), "h"((uint16_t)3) : "memory");
}
__device__ __forceinline__ uint32_t pair_offset(uint32_t sb, uint32_t rank) {
  uint32_t r;
  asm volatile("mapa.shared::cluster.u32 %0, %1, %2;" : "=r"(r) : "r"(sb), "r"(rank));
  return r - sb;
}
__device__ __forceinline__ void mbar_arrive_cluster(uint32_t bar) {
  asm volatile("mbarrier.arrive.shared::cluster.b64 _, [%0];" ::"r"(bar) : "memory");
}
__device__ __forceinline__ void cluster_arrive() { asm volatile("barrier.cluster.arrive.relaxed;" ::: "memory"); }
__device__ __forceinline__ void cluster_wait() { asm volatile("barrier.cluster.wait.acquire;" ::: "memory"); }
__device__ __forceinline__ void tma_st2(const CUtensorMap* m, uint32_t src, int c0, int c1) {
  asm volatile("cp.async.bulk.tensor.2d.global.shared::cta.bulk_group [%0, {%2, %3}], [%1];"
               ::"l"(m), "r"(src), "r"(c0), "r"(c1) : "memory");
}
__device__ __forceinline__ void bulk_commit() { asm volatile("cp.async.bulk.commit_group;" ::: "memory"); }
__device__ __forceinline__ void bulk_wait_read() { asm volatile("cp.async.bulk.wait_group.read 0;" ::: "memory"); }
__device__ __forceinline__ void bulk_wait_all() { asm volatile("cp.async.bulk.wait_group 0;" ::: "memory"); }
__device__ __forceinline__ void fence_async_smem() { asm volatile("fence.proxy.async.shared::cta;" ::: "memory"); }
__device__ __forceinline__ void fence_async_global() { asm volatile("fence.proxy.async.global;" ::: "memory"); }
__device__ __forceinline__ void st_relaxed(uint32_t* p, uint32_t v) {
  asm volatile("st.relaxed.gpu.global.u32 [%0], %1;" ::"l"(p), "r"(v) : "memory");
}
__device__ __forceinline__ void st_msg(uint4* p, uint32_t a, uint32_t b, uint32_t c, uint32_t tag) {
  asm volatile("{\n.reg .b128 v;\nmov.b128 v, {%1, %2, %3, %4};\nst.relaxed.gpu.global.b128 [%0], v;\n}"
               ::"l"(p), "r"(a), "r"(b), "r"(c), "r"(tag) : "memory");
}
__device__ __forceinline__ void ld_msg(const uint4* p, uint32_t& a, uint32_t& b, uint32_t& c, uint32_t& tag) {
  asm volatile("{\n.reg .b128 v;\nld.relaxed.gpu.global.b128 v, [%4];\nmov.b128 {%0, %1, %2, %3}, v;\n}"
               : "=r"(a), "=r"(b), "=r"(c), "=r"(tag) : "l"(p) : "memory");
}
__device__ __forceinline__ bool elect_one() {
  uint32_t ok;
  asm volatile("{\n.reg .pred p;\nelect.sync _|p, 0xffffffff;\nselp.u32 %0, 1, 0, p;\n}" : "=r"(ok));
  return ok;
}
__device__ __forceinline__ int uniform(int v) { return __shfl_sync(0xffffffffu, v, 0); }
__device__ __forceinline__ uint32_t pack_bf16(float lo, float hi) {
  uint32_t r;
  asm("cvt.rn.bf16x2.f32 %0, %1, %2;" : "=r"(r) : "f"(hi), "f"(lo));
  return r;
}
__device__ __forceinline__ float prmt_f(uint32_t a, uint32_t sel) {
  float r;
  asm("{\n.reg .b32 t;\nprmt.b32 t, %1, 0, %2;\nmov.b32 %0, t;\n}" : "=f"(r) : "r"(a), "r"(sel));
  return r;
}
__device__ __forceinline__ float bf_lo(uint32_t v) { return __uint_as_float(v << 16); }
__device__ __forceinline__ float bf_hi(uint32_t v) { return __uint_as_float(v & 0xffff0000u); }
__device__ __forceinline__ void stsm4(uint32_t addr, uint32_t r0, uint32_t r1, uint32_t r2, uint32_t r3) {
  asm volatile("stmatrix.sync.aligned.m8n8.x4.shared.b16 [%0], {%1, %2, %3, %4};"
               ::"r"(addr), "r"(r0), "r"(r1), "r"(r2), "r"(r3) : "memory");
}
__device__ __forceinline__ void ldsm4(uint32_t addr, uint32_t& r0, uint32_t& r1, uint32_t& r2, uint32_t& r3) {
  asm volatile("ldmatrix.sync.aligned.m8n8.x4.shared.b16 {%0, %1, %2, %3}, [%4];"
               : "=r"(r0), "=r"(r1), "=r"(r2), "=r"(r3) : "r"(addr) : "memory");
}
__device__ __forceinline__ uint32_t movtrans(uint32_t a) {
  uint32_t d;
  asm volatile("movmatrix.sync.aligned.m8n8.trans.b16 %0, %1;" : "=r"(d) : "r"(a));
  return d;
}
__device__ __forceinline__ void mma16816(float (&c)[4], uint32_t a0, uint32_t a1, uint32_t a2, uint32_t a3, uint32_t b0, uint32_t b1) {
  asm volatile("mma.sync.aligned.m16n8k16.row.col.f32.bf16.bf16.f32 {%0,%1,%2,%3}, {%4,%5,%6,%7}, {%8,%9}, {%0,%1,%2,%3};"
               : "+f"(c[0]), "+f"(c[1]), "+f"(c[2]), "+f"(c[3])
               : "r"(a0), "r"(a1), "r"(a2), "r"(a3), "r"(b0), "r"(b1));
}
__device__ __forceinline__ void mma1688(float (&c)[4], uint32_t a0, uint32_t a1, uint32_t b0) {
  asm volatile("mma.sync.aligned.m16n8k8.row.col.f32.bf16.bf16.f32 {%0,%1,%2,%3}, {%4,%5}, {%6}, {%0,%1,%2,%3};"
               : "+f"(c[0]), "+f"(c[1]), "+f"(c[2]), "+f"(c[3]) : "r"(a0), "r"(a1), "r"(b0));
}
__device__ __forceinline__ float2 lds_f2(uint32_t a) {
  float2 v;
  asm volatile("ld.shared.v2.f32 {%0, %1}, [%2];" : "=f"(v.x), "=f"(v.y) : "r"(a) : "memory");
  return v;
}
__device__ __forceinline__ float4 lds_f4(uint32_t a) {
  float4 v;
  asm volatile("ld.shared.v4.f32 {%0, %1, %2, %3}, [%4];" : "=f"(v.x), "=f"(v.y), "=f"(v.z), "=f"(v.w) : "r"(a) : "memory");
  return v;
}
__device__ __forceinline__ float lds_f(uint32_t a) {
  float v;
  asm volatile("ld.shared.f32 %0, [%1];" : "=f"(v) : "r"(a) : "memory");
  return v;
}
__device__ __forceinline__ uint32_t lds_u(uint32_t a) {
  uint32_t v;
  asm volatile("ld.shared.u32 %0, [%1];" : "=r"(v) : "r"(a) : "memory");
  return v;
}
__device__ __forceinline__ void sts_f2(uint32_t a, float x, float y) {
  asm volatile("st.shared.v2.f32 [%0], {%1, %2};" ::"r"(a), "f"(x), "f"(y) : "memory");
}
__device__ __forceinline__ void sts_u4(uint32_t a, uint32_t x, uint32_t y, uint32_t z, uint32_t w) {
  asm volatile("st.shared.v4.u32 [%0], {%1, %2, %3, %4};" ::"r"(a), "r"(x), "r"(y), "r"(z), "r"(w) : "memory");
}
__device__ __forceinline__ void lds_u4(uint32_t a, uint32_t& x, uint32_t& y, uint32_t& z, uint32_t& w) {
  asm volatile("ld.shared.v4.u32 {%0, %1, %2, %3}, [%4];" : "=r"(x), "=r"(y), "=r"(z), "=r"(w) : "r"(a) : "memory");
}
__device__ __forceinline__ float ex2(float x) {
  float y;
  asm("ex2.approx.ftz.f32 %0, %1;" : "=f"(y) : "f"(x));
  return y;
}
__device__ __forceinline__ float rcp_hw(float x) {
  float y;
  asm("rcp.approx.ftz.f32 %0, %1;" : "=f"(y) : "f"(x));
  return y;
}
__device__ __forceinline__ float tanh_hw(float x) {
  float y;
  asm("tanh.approx.f32 %0, %1;" : "=f"(y) : "f"(x));
  return y;
}
__device__ __forceinline__ float quad_sum(float v) {
  v += __shfl_xor_sync(0xffffffffu, v, 1);
  return v + __shfl_xor_sync(0xffffffffu, v, 2);
}
__device__ __forceinline__ float quad_max(float v) {
  v = fmaxf(v, __shfl_xor_sync(0xffffffffu, v, 1));
  return fmaxf(v, __shfl_xor_sync(0xffffffffu, v, 2));
}

template <int N> __device__ __forceinline__ void wgmma_ss(float (&d)[96], uint64_t da, uint64_t db, uint32_t keep = 1);
template <> __device__ __forceinline__ void wgmma_ss<128>(float (&d)[96], uint64_t da, uint64_t db, uint32_t keep) {
  asm volatile(
      "{\n.reg .pred p;\nsetp.ne.u32 p, %66, 0;\n"
      "wgmma.mma_async.sync.aligned.m64n128k16.f32.bf16.bf16 {%0, %1, %2, %3, %4, %5, %6, %7, %8, %9, %10, %11, %12, %13, %14, %15, %16, %17, %18, %19, %20, %21, %22, %23, %24, %25, %26, %27, %28, %29, %30, %31, %32, %33, %34, %35, %36, %37, %38, %39, %40, %41, %42, %43, %44, %45, %46, %47, %48, %49, %50, %51, %52, %53, %54, %55, %56, %57, %58, %59, %60, %61, %62, %63}, %64, %65, p, 1, 1, 0, 1;\n}"
      : "+f"(d[0]), "+f"(d[1]), "+f"(d[2]), "+f"(d[3]), "+f"(d[4]), "+f"(d[5]), "+f"(d[6]), "+f"(d[7]), "+f"(d[8]), "+f"(d[9]), "+f"(d[10]), "+f"(d[11]), "+f"(d[12]), "+f"(d[13]), "+f"(d[14]), "+f"(d[15]), "+f"(d[16]), "+f"(d[17]), "+f"(d[18]), "+f"(d[19]), "+f"(d[20]), "+f"(d[21]), "+f"(d[22]), "+f"(d[23]), "+f"(d[24]), "+f"(d[25]), "+f"(d[26]), "+f"(d[27]), "+f"(d[28]), "+f"(d[29]), "+f"(d[30]), "+f"(d[31]), "+f"(d[32]), "+f"(d[33]), "+f"(d[34]), "+f"(d[35]), "+f"(d[36]), "+f"(d[37]), "+f"(d[38]), "+f"(d[39]), "+f"(d[40]), "+f"(d[41]), "+f"(d[42]), "+f"(d[43]), "+f"(d[44]), "+f"(d[45]), "+f"(d[46]), "+f"(d[47]), "+f"(d[48]), "+f"(d[49]), "+f"(d[50]), "+f"(d[51]), "+f"(d[52]), "+f"(d[53]), "+f"(d[54]), "+f"(d[55]), "+f"(d[56]), "+f"(d[57]), "+f"(d[58]), "+f"(d[59]), "+f"(d[60]), "+f"(d[61]), "+f"(d[62]), "+f"(d[63])
      : "l"(da), "l"(db), "r"(keep));
}

template <> __device__ __forceinline__ void wgmma_ss<192>(float (&d)[96], uint64_t da, uint64_t db, uint32_t keep) {
  asm volatile(
      "{\n.reg .pred p;\nsetp.ne.u32 p, %98, 0;\n"
      "wgmma.mma_async.sync.aligned.m64n192k16.f32.bf16.bf16 {%0, %1, %2, %3, %4, %5, %6, %7, %8, %9, %10, %11, %12, %13, %14, %15, %16, %17, %18, %19, %20, %21, %22, %23, %24, %25, %26, %27, %28, %29, %30, %31, %32, %33, %34, %35, %36, %37, %38, %39, %40, %41, %42, %43, %44, %45, %46, %47, %48, %49, %50, %51, %52, %53, %54, %55, %56, %57, %58, %59, %60, %61, %62, %63, %64, %65, %66, %67, %68, %69, %70, %71, %72, %73, %74, %75, %76, %77, %78, %79, %80, %81, %82, %83, %84, %85, %86, %87, %88, %89, %90, %91, %92, %93, %94, %95}, %96, %97, p, 1, 1, 0, 1;\n}"
      : "+f"(d[0]), "+f"(d[1]), "+f"(d[2]), "+f"(d[3]), "+f"(d[4]), "+f"(d[5]), "+f"(d[6]), "+f"(d[7]), "+f"(d[8]), "+f"(d[9]), "+f"(d[10]), "+f"(d[11]), "+f"(d[12]), "+f"(d[13]), "+f"(d[14]), "+f"(d[15]), "+f"(d[16]), "+f"(d[17]), "+f"(d[18]), "+f"(d[19]), "+f"(d[20]), "+f"(d[21]), "+f"(d[22]), "+f"(d[23]), "+f"(d[24]), "+f"(d[25]), "+f"(d[26]), "+f"(d[27]), "+f"(d[28]), "+f"(d[29]), "+f"(d[30]), "+f"(d[31]), "+f"(d[32]), "+f"(d[33]), "+f"(d[34]), "+f"(d[35]), "+f"(d[36]), "+f"(d[37]), "+f"(d[38]), "+f"(d[39]), "+f"(d[40]), "+f"(d[41]), "+f"(d[42]), "+f"(d[43]), "+f"(d[44]), "+f"(d[45]), "+f"(d[46]), "+f"(d[47]), "+f"(d[48]), "+f"(d[49]), "+f"(d[50]), "+f"(d[51]), "+f"(d[52]), "+f"(d[53]), "+f"(d[54]), "+f"(d[55]), "+f"(d[56]), "+f"(d[57]), "+f"(d[58]), "+f"(d[59]), "+f"(d[60]), "+f"(d[61]), "+f"(d[62]), "+f"(d[63]), "+f"(d[64]), "+f"(d[65]), "+f"(d[66]), "+f"(d[67]), "+f"(d[68]), "+f"(d[69]), "+f"(d[70]), "+f"(d[71]), "+f"(d[72]), "+f"(d[73]), "+f"(d[74]), "+f"(d[75]), "+f"(d[76]), "+f"(d[77]), "+f"(d[78]), "+f"(d[79]), "+f"(d[80]), "+f"(d[81]), "+f"(d[82]), "+f"(d[83]), "+f"(d[84]), "+f"(d[85]), "+f"(d[86]), "+f"(d[87]), "+f"(d[88]), "+f"(d[89]), "+f"(d[90]), "+f"(d[91]), "+f"(d[92]), "+f"(d[93]), "+f"(d[94]), "+f"(d[95])
      : "l"(da), "l"(db), "r"(keep));
}

template <int R>
__device__ __forceinline__ void pin_regs(float (&a)[2][96]) {
#pragma unroll
  for (int m = 0; m < 2; m++)
#pragma unroll
    for (int i = 0; i < R; i++) asm volatile("" : "+f"(a[m][i])::"memory");
}

struct Ctx {
  uint32_t sb;
  int m, n, wg, w, lane;
};
__device__ __forceinline__ Ctx make_ctx(uint32_t sb, int id) {
  int lane;
  asm volatile("mov.u32 %0, %%laneid;" : "=r"(lane));
  asm volatile("" : "+r"(id), "+r"(sb));
  return Ctx{sb, (id >> 3) & 15, id & 7, id >> 9, (id >> 7) & 3, lane};
}
#define UNPACK_CTX(c) const uint32_t sb = c.sb; const int m = c.m, n = c.n, wg = c.wg, w = c.w, lane = c.lane

__device__ __forceinline__ uint32_t poll_line(const uint32_t* word, uint32_t target, uint32_t need) {
  uint32_t v;
  asm volatile(
      "{\n.reg .pred p;\n.reg .u32 it, m;\n.reg .s32 d;\nmov.u32 it, 0;\n"
      "POLL_LOOP:\n"
      "ld.relaxed.gpu.global.u32 %0, [%1];\n"
      "sub.s32 d, %0, %2;\n"
      "setp.ge.s32 p, d, 0;\n"
      "vote.sync.ballot.b32 m, p, 0xffffffff;\n"
      "and.b32 m, m, %3;\n"
      "setp.eq.u32 p, m, %3;\n"
      "@p bra.uni POLL_DONE;\n"
      "add.u32 it, it, 1;\n"
      "setp.lt.u32 p, it, 0x400000;\n"
      "@p bra.uni POLL_LOOP;\n"
      "trap;\n"
      "POLL_DONE:\n}"
      : "=&r"(v) : "l"(word), "r"(target), "r"(need) : "memory");
  return v;
}
__device__ __forceinline__ uint32_t ld_relaxed(const uint32_t* p) {
  uint32_t v;
  asm volatile("ld.relaxed.gpu.global.u32 %0, [%1];" : "=r"(v) : "l"(p) : "memory");
  return v;
}
__device__ __forceinline__ float chain(float x, uint32_t on, uint32_t zero) {
  return __uint_as_float(__float_as_uint(x) | (on & zero));
}
constexpr int MSG_SPINS = 1 << 20;

constexpr int STAGES_PER_LAYER = 152;
__device__ __forceinline__ int nib(uint64_t v, int i) { return (int)(v >> (4 * i)) & 15; }
__device__ __forceinline__ bool tile_wide(int t) { return (0x23 >> t) & 1; }
__device__ __forceinline__ void weight_coords(const Params& p, int t, int n, const CUtensorMap*& map, int& c0, int& c2) {
  map = &p.wqkv + nib(0x4233100ull, t);
  c0 = t < 2 ? 128 * n + 64 * t : 0;
  c2 = t < 2 ? 0 : (t == 2 || t == 6) ? 2 * n : 7 * n + 2 * t - 6;
}

template <bool IS_A>
__device__ __forceinline__ void producer(const Params& p, uint32_t sb, int m, int n, int lane) {
  const uint32_t low = (1u << (4 * n)) - 1, others = (0x6543210u & low) | (0x7654321u & ~low);
  const uint64_t order_x = (uint64_t)(others * 2 + 0x1111111u) << 36 | (uint64_t)others * 2 << 8 | (n * 0x22 + 0x10);
  int inflight = 4, cur = 0;
  uint32_t fb = sb + BAR_FULL + 32, rb = sb + BAR_EMPTY, rph = 0, pos = 0, tag32 = 0, seen = 0;
  const uint32_t fend = sb + BAR_FULL + 8 * NBAR, rend = sb + BAR_EMPTY + 8 * NBAR;
  const uint32_t* word = p.g->flags + m * 32 + (lane < 16 ? lane >> 1 : lane & 7);
#pragma unroll 1
  for (int sg = 1; sg < 22; sg++) {
    const int layer = sg >= 11, s = sg == 1 ? 2 : sg == 2 ? 1 : sg - 11 * layer;
    const int t = nib(0x65434321010ull, s), kind = nib(0x32110031100ull, s);
    const bool wide = tile_wide(t);
    const uint32_t bbytes = wide ? 3 * UNIT : 2 * UNIT, base = sb + (IS_A ? bbytes : (m & 1) * (bbytes / 2));
    if (IS_A && kind == 0) {
      if (sg == 2) seen = tag32 = (__ldcg(p.g->epoch + m * 8 + n) + 1) << 5;
#pragma unroll 1
      for (int k = 0; k < 2; k++) {
#pragma unroll 1
        for (; inflight > (wide ? 3 : 4); inflight--) {
          mbar_wait(rb, rph);
          rb += 8;
          if (rb == rend) { rb -= 8 * NBAR; rph ^= 1; }
        }
        if (elect_one()) mbar_arrive(fb);
        inflight++;
        fb += 8;
        if (fb == fend) fb -= 8 * NBAR;
        pos += bbytes + 2 * UNIT;
        if (pos >= RING_UNITS * UNIT) pos -= RING_UNITS * UNIT;
      }
      continue;
    }
    const int mul = t == 6 ? 448 : t == 2 ? 128 : 64, count = sg == 1 ? 12 : 2 * nib(0x4871ull, kind);
    uint64_t order0 = sg == 1 ? 0xFEDCBA987654ull : kind == 3 ? 0x76543210u : order_x >> (8 * (kind & 1));
    uint32_t special = (s == 4 || s == 10) ? 0x10 : s == 9 ? 0xF : s == 0;
    if (IS_A) special |= (kind & 1 ? 0 : 3) | (count >= 4 ? 1u << (count - 4) : 0);
    if (s >= 9) pos = (s + 6) * UNIT;
    const CUtensorMap* map;
    int c0 = 0, c2 = 0, ev = 0;
    if (IS_A) {
      map = &p.xin + (t == 2 ? 2 : t == 6 ? 3 : sg >= 4);
      ev = 9 * layer + (t < 2 ? 0 : t == 2 ? 1 : t < 6 ? 4 : 5);
      if (elect_one()) asm volatile("prefetch.tensormap [%0];" ::"l"(map) : "memory");
    } else {
      weight_coords(p, t, n, map, c0, c2);
    }
#pragma unroll 1
    for (int add = 0; add < mul; add += 64) {
      uint64_t order = order0;
      const int need = kind == 3 ? ev : ev - 1 + (lane & 1), sh = kind == 3 ? 16 : 0;
      uint32_t ready = IS_A ? __ballot_sync(0xffffffffu, cur >= need) >> sh : 0;
#pragma unroll 1
      for (int k = 0; k < count; k++) {
        const int code = order & 15, kc = code * mul + add;
        order >>= 4;
        if ((special >> k) & 1) {
          const int lag = wide ? (s == 9 && k == 2 ? 2 : 3) : ((s == 4 || s == 10) && add == 0 && k < 4) ? 3 : 4;
#pragma unroll 1
          for (; inflight > lag; inflight--) {
            mbar_wait(rb, rph);
            rb += 8;
            if (rb == rend) { rb -= 8 * NBAR; rph ^= 1; }
          }
          inflight++;
          if (IS_A) {
            if (kind == 3 ? t == 2 && add + k == 64 : !(kind & 1) && k < 2) {
              if (t == 2) mbar_wait(sb + BAR_PUB + 8, layer);
              if (elect_one()) mbar_arrive(fb);
              goto next_stage;
            }
            if (k == count - 4 && sg >= 3) seen = ld_relaxed(word);
          }
        } else {
          mbar_wait(rb, rph);
          rb += 8;
          if (rb == rend) { rb -= 8 * NBAR; rph ^= 1; }
        }
        if (IS_A && !((ready >> code) & 1)) {
          cur = max(cur, (int)(seen - tag32));
          ready = __ballot_sync(0xffffffffu, cur >= need) >> sh;
          if (!((ready >> code) & 1)) {
            cur = (int)(poll_line(word, tag32 + need, 1u << (code + sh)) - tag32);
            ready = __ballot_sync(0xffffffffu, cur >= need) >> sh;
          }
          asm volatile("fence.acquire.gpu;" ::: "memory");
          fence_async_global();
          seen = ld_relaxed(word);
        }
        if (elect_one()) {
          if (!IS_A) tma_ld3_pair(base + pos, map, fb, c0, kc + 32 * (m & 1), c2);
          else tma_ld_act(base + pos, map, fb, kc, m);
          mbar_expect_tx(fb, IS_A ? 16384 : bbytes);
        }
      next_stage:
        fb += 8;
        if (fb == fend) fb -= 8 * NBAR;
        pos += bbytes + 2 * UNIT;
        if (pos >= RING_UNITS * UNIT) pos -= RING_UNITS * UNIT;
      }
      special = !IS_A ? 0 : t == 2 ? 1 : add == 128 ? 0x10 : 0;
      if (t == 2) order0 = others << 4 | n;
      if (IS_A && (t == 2 || add == 64 || add == 192)) ev++;
    }
  }
}

__device__ __forceinline__ void publisher(const Params& p, uint32_t sb, int m, int n) {
  const uint32_t tag = __ldcg(p.g->epoch + m * 8 + n) + 1;
  uint32_t* word = p.g->flags + m * 32 + n;
  const int mn = m * 8 + n; (void)mn;
  st_relaxed(word, 32 * tag);
#pragma unroll 1
  for (int c = 0; c < 17; c++) {
    const int e = c >= 9 ? c - 9 : c;
    if (e == 2 || e == 7) {
      asm volatile("prefetch.tensormap [%0];" ::"l"(&p.out) : "memory");
      mbar_wait(sb + BAR_XRDY, e == 2);
      tma_st_act(&p.out, sb + OFF_X, 128 * n, m);
      bulk_commit();
      if (c == 16) break;
      mbar_wait(sb + BAR_XRDY + 8, e == 2);
      bulk_wait_all();
      mbar_arrive(sb + BAR_XGO);
      PROF_E(7 * (c >= 9) + (e < 4 ? 2 : 6), 11);
    } else {
      mbar_wait(sb + BAR_PUB + 8 * e, c >= 9);
    }
    asm volatile("fence.release.gpu;" ::: "memory");
    asm volatile("red.relaxed.gpu.global.add.u32 [%0], 1;" ::"l"(word) : "memory");
    PROF_E(7 * (c >= 9) + nib(0x665432210ull, e), (0x108 >> e) & 1 ? 14 : 12);
  }
  p.g->epoch[m * 8 + n] = tag;
  bulk_wait_read();
}

__device__ __forceinline__ void sum_rows(uint32_t buf, int iters, float (&a)[8], int lane) {
  uint32_t addr = buf + (lane >> 3) * 128 + (((lane & 7) ^ (lane >> 3)) << 4);
#pragma unroll 1
  for (int it = 0; it < iters; it++) {
    uint32_t u[2][4];
    lds_u4(addr, u[0][0], u[0][1], u[0][2], u[0][3]);
    lds_u4((addr ^ 64) + 512, u[1][0], u[1][1], u[1][2], u[1][3]);
    addr += 1024;
#pragma unroll
    for (int e = 0; e < 8; e++) { a[2 * (e & 3)] += bf_lo(u[e >> 2][e & 3]); a[2 * (e & 3) + 1] += bf_hi(u[e >> 2][e & 3]); }
  }
}
__device__ __forceinline__ void publish_sums(const float (&a)[8], uint4* dst, int lane, uint32_t tag) {
  const bool u8 = lane & 8, u16 = lane & 16;
  float h4[4], h2[2];
#pragma unroll
  for (int e = 0; e < 4; e++) h4[e] = (u8 ? a[4 + e] : a[e]) + __shfl_xor_sync(0xffffffffu, u8 ? a[e] : a[4 + e], 8);
#pragma unroll
  for (int e = 0; e < 2; e++) h2[e] = (u16 ? h4[2 + e] : h4[e]) + __shfl_xor_sync(0xffffffffu, u16 ? h4[e] : h4[2 + e], 16);
  st_msg(dst + (lane & 7) * 4 + (u8 ? 2 : 0) + (u16 ? 1 : 0), __float_as_uint(h2[0]), __float_as_uint(h2[1]), 0u, tag);
}

__device__ __forceinline__ void colsum_helper(const Params& p, uint32_t sb, int m, int n, int lane) {
  const uint32_t tag = __ldcg(p.g->epoch + m * 8 + n) + 1;
  const int mn = m * 8 + n; (void)mn;
#pragma unroll 1
  for (int k = lane; k < 288; k += 32) {
    const uint32_t bb = __ldg(reinterpret_cast<const uint32_t*>(k < 224 ? p.b1 + 448 * n : p.b2 + 128 * n - 448) + k);
    const float sc = k < 224 ? 0.5f : 1.f;
    sts_f2(sb + (k < 224 ? OFF_CSF + k * 16 + 8 : OFF_CSQ + 1536 + (k - 224) * 8), sc * bf_lo(bb), sc * bf_hi(bb));
  }
  __syncwarp();
  if (elect_one()) mbar_arrive(sb + BAR_BIAS);
  bar_sync(BAR_HLP, 160);
  PROF_E(-1, 1);
#pragma unroll 1
  for (int c = 0; c < 7; c++) {
    float a[8] = {0.f, 0.f, 0.f, 0.f, 0.f, 0.f, 0.f, 0.f};
#pragma unroll 1
    for (int h = 0; h < 2; h++) {
      if (elect_one()) {
        mbar_expect_tx(sb + BAR_CSLD + 8, 4096);
        tma_ld2(sb + OFF_HLP, &p.w1c, sb + BAR_CSLD + 8, 448 * n + 64 * c, 64 * m + 32 * h);
        if (c < 6) asm volatile("cp.async.bulk.prefetch.tensor.2d.L2.global [%0, {%1, %2}];" ::"l"(&p.w1c), "r"(448 * n + 64 * c + 64), "r"(64 * m + 32 * h) : "memory");
      }
      mbar_wait(sb + BAR_CSLD + 8, h);
      sum_rows(sb + OFF_HLP, 4, a, lane);
      __syncwarp();
    }
    publish_sums(a, p.g->csp + ((8 + n) * 17 + m) * 224 + c * 32, lane, tag);
  }
  PROF_E(-1, 2);
  if (elect_one()) {
#pragma unroll 1
    for (int k = 0; k < 4; k++) {
      if (k < 3) {
        mbar_wait(sb + BAR_XGO, k & 1);
        __nanosleep(BDELAY);
      } else {
        mbar_wait(sb + BAR_XRDY + 8, 0);
      }
      tma_st_act(&p.out, sb + OFF_X + 16384, 128 * n + 64, m);
      bulk_commit();
      bulk_wait_all();
      asm volatile("mbarrier.arrive.shared::cta.b64 _, [%0], 4;" ::"r"(sb + BAR_PUB + (k & 1 ? 64 : 24)) : "memory");
    }
  }
}

__device__ __forceinline__ void poll_msgs2(const uint4* pa, const uint4* pb, float (&v)[4], uint32_t tag) {
#pragma unroll 1
  for (int it = 0; it < MSG_SPINS; it++) {
    uint32_t x[4], z, ta, tb;
    ld_msg(pa, x[0], x[1], z, ta);
    ld_msg(pb, x[2], x[3], z, tb);
#pragma unroll
    for (int e = 0; e < 4; e++) v[e] = __uint_as_float(x[e]);
    if (__all_sync(0xffffffffu, ta == tag && tb == tag)) break;
  }
}
__device__ __forceinline__ void colsum_total(const Params& p, const Ctx& cx, int mat, uint32_t tag) {
  uint4* base = p.g->csp + (mat * 8 + cx.n) * 17 * 224;
  const int per = 12 + 2 * mat, k = 2 * cx.w + (cx.lane >> 4), ia = per * cx.m + k, ib = per * cx.m + min(k + 8, per - 1);
  float v[4];
  poll_msgs2(base + (cx.lane & 15) * 224 + ia, base + (cx.lane & 15) * 224 + ib, v, tag);
#pragma unroll 1
  for (int d = 1; d < 16; d *= 2)
#pragma unroll
    for (int e = 0; e < 4; e++) v[e] += __shfl_xor_sync(0xffffffffu, v[e], d);
  const bool hi = cx.lane & 1;
  if ((cx.lane & 14) == 0) st_msg(base + 16 * 224 + (hi ? ib : ia), __float_as_uint(hi ? v[2] : v[0]), __float_as_uint(hi ? v[3] : v[1]), 0u, tag);
}
__device__ __forceinline__ void colsum_gather(const Params& p, const Ctx& cx, int mat, uint32_t tag) {
  const uint4* base = p.g->csp + ((mat * 8 + cx.n) * 17 + 16) * 224;
  const int ia = cx.w * 32 + cx.lane, ib = min(ia + 128, 191 + 32 * mat);
  float v[4];
  poll_msgs2(base + ia, base + ib, v, tag);
  const uint32_t tab = cx.sb + (mat ? OFF_CSF : OFF_CSQ);
  sts_f2(tab + (ia << (3 + mat)), v[0], v[1]);
  sts_f2(tab + (ib << (3 + mat)), v[2], v[3]);
}

#define ACC(q, j, e) acc[(q) & 1][4 * (j) + 2 * ((q) >> 1) + (e)]

constexpr uint32_t RING16 = RING_UNITS * (UNIT >> 4);
__device__ __forceinline__ bool tile_split(int i) { return (0xD98 >> i) & 1; }

__device__ __forceinline__ void write_run_desc(uint32_t sb, int i, int step) {
  const int layer = i >= 7, t = i - 7 * layer, part = tile_split(i) ? step : 2;
  const bool wide = tile_wide(t), own = t != 2 && t != 6 && part != 1 && i != 0, second = t == 1 || t == 4;
  const uint32_t z16 = (wide ? 5 : 4) * (UNIT >> 4), a_off = z16 - 1024 + (uint32_t)DESC_A - (uint32_t)DESC_B;
  const int gl = 16 * t + (part == 2 ? 0 : second ? 16 * part - 14 : 4 * part), g0 = layer * STAGES_PER_LAYER + gl;
  const uint32_t s16 = (sb & 0x3FFFF) >> 4, bfirst = (uint32_t)DESC_B + s16;
  const int nkb = t == 6 ? 56 : part == 0 ? 2 : 12 + 2 * part;
  const bool win1 = t == 1 && part != 0;
  const int run = win1 ? WIN1 + 1 : t == 2 ? WIN2 + 1 : nkb;
  const int rest = win1 ? 64 | (nkb - 1 - WIN1) : t == 2 ? 64 | (7 - WIN2) | (8 << 7) : 0;
  const uint32_t blo = bfirst + z16 * (wide ? (gl + (t == 5 ? 3 : 0)) & 3 : (gl + 3) % 5);
  const uint32_t alo = own ? (uint32_t)DESC_A + s16 + (OFF_X >> 4) : blo + a_off;
  const uint32_t aoff = own ? alo + 1024 - (blo == bfirst + RING16 - z16 ? bfirst : blo + z16) : a_off;
  const bool xwait = part == 0 && !second, keep = !(part == 0 || t == 5);
  sts_u4(sb + OFF_RUN + (2 * i + step) * 16, blo, alo, aoff,
         ((g0 / NBAR) & 1) | xwait << 1 | keep << 2 | 8 * (g0 % NBAR) | run << 6 | rest << 12);
}

template <int N>
__device__ __forceinline__ void mainloop(const Params& p, float (&acc)[2][96], uint32_t sb, int i, int step, int mn) {
  constexpr uint32_t Z16 = (2 + N / 64) * (UNIT >> 4);
  constexpr uint32_t A_OFF = Z16 - 1024 + (uint32_t)DESC_A - (uint32_t)DESC_B;
  const int wg = i & 1;
  const uint32_t s16 = (sb & 0x3FFFF) >> 4;
  const uint32_t blast = (uint32_t)DESC_B + s16 + RING16 - Z16, flast = sb + BAR_FULL + 8 * (NBAR - 1);
  uint32_t blo = (uint32_t)DESC_B + s16, alo = blo + A_OFF, aoff = A_OFF, misc = 16 << 6;
  if (N == 128 || i > 0) lds_u4(sb + OFF_RUN + (2 * i + step) * 16, blo, alo, aoff, misc);
  uint32_t keep = misc & 4;
  int run = (misc >> 6) & 63, rest = misc >> 12;
  uint32_t fb = sb + BAR_FULL + (misc & 0x38), ph = misc & 1;
  uint32_t prev = sb + BAR_DUMMY - 8 * NBAR;
  const uint32_t lane_id = (threadIdx.x & 31) | p.zero, rel = pair_offset(sb, lane_id & 1) + 8 * NBAR;
  pin_regs<N / 2>(acc);
  if (N == 128 || i > 0) bar_sync(BAR_ORDER + wg, 256);
  else cluster_wait();
  if (N == 192 && i == 0 && threadIdx.x == 0) PROF_U(8);
  mbar_wait(fb, ph);
    if (misc & 2) {
    if ((HOLDM >> (N == 192)) & 1) mbar_wait(sb + BAR_XGO, N == 192);
    else mbar_wait(sb + BAR_XRDY + 8, N == 128);
  }
  if (step == 0 || !tile_split(i)) PROF_T(4 + i * 4);
#pragma unroll 1
  while (true) {
    const uint64_t da = (DESC_A & ~0xffffffffull) | alo, db = (DESC_B & ~0xffffffffull) | blo;
    asm volatile("wgmma.fence.sync.aligned;" ::: "memory");
    wgmma_ss<N>(acc[0], da, db, keep);
    wgmma_ss<N>(acc[1], da + 64, db, keep);
    keep = 4;
    wgmma_ss<N>(acc[0], da + 2, db + 128);
    wgmma_ss<N>(acc[1], da + 66, db + 128);
    asm volatile("wgmma.commit_group.sync.aligned;" ::: "memory");
    asm volatile("wgmma.wait_group.sync.aligned 1;" ::: "memory");
    PROF_S(jj++);
    if (lane_id < 2) mbar_arrive_cluster(prev + rel);
    prev = fb;
    if (fb == flast) { fb -= 8 * NBAR; ph++; }
    fb += 8;
    if (blo == blast) blo -= RING16;
    blo += Z16;
    alo = blo + aoff;
    aoff = A_OFF;
    run--;
    const bool ready = mbar_test(fb, ph) && run != 0;
    asm volatile("wgmma.fence.sync.aligned;" ::: "memory");
    wgmma_ss<N>(acc[0], da + 4, db + 4 * N);
    wgmma_ss<N>(acc[1], da + 68, db + 4 * N);
    wgmma_ss<N>(acc[0], da + 6, db + 4 * N + 128);
    wgmma_ss<N>(acc[1], da + 70, db + 4 * N + 128);
    asm volatile("wgmma.commit_group.sync.aligned;" ::: "memory");
    if (!ready) {
      if (run == 0) {
        if (rest == 0) break;
        if (rest & 64) {
          bar_arrive(BAR_GO, 256);
          bar_sync(BAR_DONE, 256);
        } else {
          alo = (uint32_t)DESC_A + s16 + (OFF_STG >> 4);
        }
        run = rest & 63;
        rest >>= 7;
      }
      mbar_wait(fb, ph);
    }
  }
  if (i < 13 && !(LATE_O && N == 192 && (misc >> 12))) bar_arrive(BAR_ORDER + (wg ^ 1), 256);
  if (N == 128 && ((0x2244 >> i) & 1)) {
    const Ctx cx = make_ctx(sb, mn);
    const uint32_t xrow = cx.sb + OFF_X + cx.w * 4096 + cx.lane * 128 + ((cx.lane & 7) << 4);
    const bool leader = elect_one();
    asm volatile("wgmma.wait_group.sync.aligned 0;" ::: "memory");
    pin_regs<64>(acc);
    PROF_T(5 + i * 4);
    PROF_E(i, 0);
#pragma unroll
    for (int h = 0; h < 2; h++) {
      if (h == 1 && p.zero != 0) break;
#pragma unroll
      for (int j = 8 * h; j < 8 * h + 8; j++)
        stsm4((xrow ^ ((j & 7) << 4)) + h * 16384, pack_bf16(ACC(0, j, 0), ACC(0, j, 1)), pack_bf16(ACC(1, j, 0), ACC(1, j, 1)),
              pack_bf16(ACC(2, j, 0), ACC(2, j, 1)), pack_bf16(ACC(3, j, 0), ACC(3, j, 1)));
      fence_async_smem();
      __syncwarp();
      if (leader) mbar_arrive(sb + BAR_XRDY + 8 * h);
      if (h == 0 && lane_id < 2) mbar_arrive_cluster(prev + rel);
    }
    PROF_E(i, 4);
    return;
  }
  asm volatile("wgmma.wait_group.sync.aligned 0;" ::: "memory");
  pin_regs<N / 2>(acc);
  if (lane_id < 2) mbar_arrive_cluster(prev + rel);
  PROF_T(5 + i * 4);
  PROF_E(i, 0);
}

__device__ __forceinline__ void write_partial_stats(const Params& p, const Ctx& c, int ln, uint32_t tag) {
  const uint32_t xrow = c.sb + OFF_X + c.w * 4096 + c.lane * 128;
  float s = 0.f, q = 0.f, s1 = 0.f, q1 = 0.f;
#pragma unroll 4
  for (int j = 0; j < 16; j++) {
    uint32_t u[4];
    lds_u4(xrow + (j >> 3) * 16384 + (((j & 7) ^ (c.lane & 7)) << 4), u[0], u[1], u[2], u[3]);
#pragma unroll
    for (int e = 0; e < 4; e++) {
      const float a = bf_lo(u[e]), d = bf_hi(u[e]);
      s += a; q = fmaf(a, a, q);
      s1 += d; q1 = fmaf(d, d, q1);
    }
  }
  s += s1;
  q += q1;
  st_msg(p.g->stats + (ln * 8 + c.n) * SEQ + 128 * c.m + 32 * c.w + c.lane, __float_as_uint(s),
         __float_as_uint(fmaxf(q - s * s * (1.f / 128.f), 0.f)), 0u, tag);
}

__device__ __forceinline__ void finish_row_stats(const Params& p, const Ctx& c, int ln, uint32_t tag) {
  const uint4* src = p.g->stats + ln * 8 * SEQ + 128 * c.m + 32 * c.w + c.lane;
  uint32_t ps[8], pm[8];
#pragma unroll 1
  for (int it = 0; it < MSG_SPINS; it++) {
    uint32_t bad = 0, u, tg;
    if (ln > 1 || it > 0) __nanosleep(STAT_NS);
#pragma unroll
    for (int k = 0; k < 8; k++) { ld_msg(src + k * SEQ, ps[k], pm[k], u, tg); bad |= tg ^ tag; }
    if (__all_sync(0xffffffffu, bad == 0)) break;
  }
  float s = 0.f, m2 = 0.f;
#pragma unroll
  for (int k = 0; k < 8; k++) s += __uint_as_float(ps[k]);
  const float mean = s * (1.f / DM);
#pragma unroll
  for (int k = 0; k < 8; k++) {
    const float d = __uint_as_float(ps[k]) * (1.f / 128.f) - mean;
    m2 += fmaf(128.f * d, d, __uint_as_float(pm[k]));
  }
  sts_f2(c.sb + OFF_ROW + (32 * c.w + c.lane) * 8, rsqrtf(m2 * (1.f / DM) + 1e-5f), mean);
  __syncwarp();
}

__device__ __forceinline__ void attn_scores(const uint32_t* qa, const uint32_t* qb, const uint32_t* kp, const uint32_t* ka,
                                            const uint32_t* kb, float (&l)[4], const float4& zero, const bool (&early)[2]) {
  float s[3][4];
#pragma unroll
  for (int x = 0; x < 3; x++) {
    const uint32_t* kk = x == 0 ? kp : x == 1 ? ka : kb;
    asm volatile("mma.sync.aligned.m16n8k16.row.col.f32.bf16.bf16.f32 {%0,%1,%2,%3}, {%4,%5,%6,%7}, {%8,%9}, {%10,%11,%12,%13};"
                 : "=f"(s[x][0]), "=f"(s[x][1]), "=f"(s[x][2]), "=f"(s[x][3])
                 : "r"(qa[0]), "r"(qb[0]), "r"(qa[1]), "r"(qb[1]), "r"(kk[0]), "r"(kk[1]), "f"(zero.x), "f"(zero.y),
                   "f"(zero.z), "f"(zero.w));
  }
#pragma unroll
  for (int x = 0; x < 3; x++) {
    const uint32_t* kk = x == 0 ? kp : x == 1 ? ka : kb;
    mma16816(s[x], qa[2], qb[2], qa[3], qb[3], kk[2], kk[3]);
  }
#pragma unroll
  for (int e = 0; e < 2; e++) {
    l[e] = early[e] ? s[0][e] : s[1][e];
    l[2 + e] = early[e] ? s[1][2 + e] : s[2][2 + e];
  }
}

__device__ __forceinline__ void attn_mix(const float (&l)[4], const float (&sc)[4], const float (&off)[4], const float (&rk)[4],
                                         const uint32_t* vp, const uint32_t* va, const uint32_t* vb, uint32_t* olo,
                                         uint32_t* ohi, uint32_t mask, uint32_t zero) {
  float x[4];
#pragma unroll
  for (int e = 0; e < 4; e++) x[e] = fmaf(l[e], sc[e], off[e]);
  const float ml = quad_max(fmaxf(x[0], x[1])), mh = quad_max(fmaxf(x[2], x[3]));
  x[0] = ex2(x[0] - ml); x[1] = ex2(x[1] - ml);
  x[2] = ex2(x[2] - mh); x[3] = ex2(x[3] - mh);
  const float il = rcp_hw(quad_sum(x[0] + x[1])), ih = rcp_hw(quad_sum(x[2] + x[3]));
  const uint32_t pl = pack_bf16(x[0] * rk[0], x[1] * rk[1]), ph = pack_bf16(x[2] * rk[2], x[3] * rk[3]);
  const uint32_t a0 = pl & ~mask, a1 = ph & mask, a2 = pl & zero, a3 = ph & ~mask, c0 = pl & mask, c1 = ph & zero;
  float o[4][4];
#pragma unroll
  for (int jn = 0; jn < 4; jn++) {
    o[jn][0] = o[jn][1] = o[jn][2] = o[jn][3] = 0.f;
    mma16816(o[jn], a0, a1, a2, a3, va[jn], vb[jn]);
  }
#pragma unroll
  for (int jn = 0; jn < 4; jn++) mma1688(o[jn], c0, c1, vp[jn]);
#pragma unroll
  for (int jn = 0; jn < 4; jn++) {
    olo[jn] = pack_bf16(o[jn][0] * il, o[jn][1] * il);
    ohi[jn] = pack_bf16(o[jn][2] * ih, o[jn][3] * ih);
  }
}

__device__ __forceinline__ void gelu_epilogue(const Params& p, float (&acc)[2][96], const Ctx& cx, int t) {
  UNPACK_CTX(cx);
  (void)wg;
  float rs[4], rm[4];
#pragma unroll
  for (int q = 0; q < 4; q++) {
    const float2 v = lds_f2(sb + OFF_ROW + (32 * w + 8 * q + (lane >> 2)) * 8);
    rs[q] = 0.5f * v.x;
    rm[q] = -rs[q] * v.y;
  }
  const int col0 = 128 * (t - 3);
  const uint32_t stg = sb + OFF_STG + w * 4096;
  const uint32_t ctab = sb + OFF_CSF + (col0 / 2 + (lane & 3)) * 16, srow = stg + lane * 128 + ((lane & 7) << 4);
  __nanosleep((t == 5 ? STAG5 : t == 4 ? STAG4 : STAG3) * w);
  float4 nb = lds_f4(ctab);
#pragma unroll
  for (int c = 0; c < 3; c++) {
    if (c == 2 && t != 5) break;
    uint32_t hp[8][4];
#pragma unroll
    for (int j = 0; j < 8; j++) {
      const float4 cb = nb;
      if (8 * c + j < 23) nb = lds_f4(ctab + (8 * c + j + 1) * 64);
#pragma unroll
      for (int q = 0; q < 4; q++) {
        float y[2];
        const int k = 4 * j + q - GELU_DEP;
        const float rmq = k >= 0 ? chain(rm[q], hp[k >> 2][k & 3], p.zero) : rm[q];
#pragma unroll
        for (int e = 0; e < 2; e++) {
          const float z = fmaf(ACC(q, 8 * c + j, e), rs[q], fmaf(rmq, e ? cb.y : cb.x, e ? cb.w : cb.z));
          const float u = z * fmaf(z * z, 8.f * 0.7978845608028654f * 0.044715f, 2.f * 0.7978845608028654f);
          y[e] = fmaf(z, tanh_hw(u), z);
        }
        hp[j][q] = pack_bf16(y[0], y[1]);
      }
      if (j == STG_WAIT && c > 0) {
        if (lane == 0) bulk_wait_read();
        __syncwarp();
      }
      if (c == 0 || j > STG_WAIT) {
        stsm4(srow ^ (j << 4), hp[j][0], hp[j][1], hp[j][2], hp[j][3]);
      } else if (j == STG_WAIT) {
#pragma unroll
        for (int jj = 0; jj <= STG_WAIT; jj++) stsm4(srow ^ (jj << 4), hp[jj][0], hp[jj][1], hp[jj][2], hp[jj][3]);
      }
    }
    fence_async_smem();
    __syncwarp();
    if (lane == 0) {
      tma_st2(&p.h_st, stg, 448 * n + col0 + 64 * c, 128 * m + 32 * w);
      bulk_commit();
    }
  }
#pragma unroll
  for (int r = 0; r < 16; r++) acc[0][r] = acc[1][r] = 0.f;
}

__device__ __forceinline__ void attn_epilogue(const Params& p, float (&acc)[2][96], const Ctx& cx, int layer, int t, uint32_t tag) {
  UNPACK_CTX(cx);
  const uint32_t ktab = sb + OFF_ROW + (32 * w + 2 * (lane & 3)) * 8, exc = sb + OFF_STG + (w & 1) * 2048 + lane * 16;
  uint4* const halo = p.g->halo + (((layer * 2 + t) * 16 + m) * 8 + n) * 384 + (w & 1) * 192;
  const int mn = m * 8 + n; (void)mn;
  uint32_t Q[4][8], K[4][8], V[4][8], E[18], P[18];
  float kr[5][2], qr[4];
  {
    const float4 r = lds_f4(ktab + 192);
    E[16] = __float_as_uint(kr[4][0] = r.x);
    E[17] = __float_as_uint(kr[4][1] = r.z);
  }
#pragma unroll
  for (int j = 0; j < 8; j++) {
    E[j] = K[3][j] = pack_bf16(ACC(3, 8 + j, 0), ACC(3, 8 + j, 1));
    E[8 + j] = V[3][j] = movtrans(pack_bf16(ACC(3, 16 + j, 0), ACC(3, 16 + j, 1)));
  }
  if (w < 2) {
#pragma unroll
    for (int k = 0; k < 4; k++) sts_u4(exc + k * 512, E[4 * k], E[4 * k + 1], E[4 * k + 2], E[4 * k + 3]);
  } else {
#pragma unroll
    for (int k = 0; k < 6; k++) st_msg(halo + k * 32 + lane, E[3 * k], E[3 * k + 1], E[3 * k + 2], tag);
  }
  bar_arrive(BAR_PAIR + w, 64);
  if (LATE_O && t == 1) bar_arrive(BAR_ORDER + (wg ^ 1), 256);
  PROF_E(7 * layer + t, 1);
#pragma unroll
  for (int q = 0; q < 4; q++) {
    qr[q] = lds_f(sb + OFF_ROW + (32 * w + 8 * q + (lane >> 2)) * 8) * (0.17677669529663687f * 1.4426950408889634f);
#pragma unroll
    for (int j = 0; j < 8; j++) Q[q][j] = pack_bf16(ACC(q, j, 0), ACC(q, j, 1));
    if (q < 3) {
      const float4 r = lds_f4(ktab + 64 * q);
      kr[1 + q][0] = r.x;
      kr[1 + q][1] = r.z;
#pragma unroll
      for (int j = 0; j < 8; j++) {
        K[q][j] = pack_bf16(ACC(q, 8 + j, 0), ACC(q, 8 + j, 1));
        V[q][j] = movtrans(pack_bf16(ACC(q, 16 + j, 0), ACC(q, 16 + j, 1)));
      }
    }
  }
  PROF_E(7 * layer + t, 6);
  bar_sync(BAR_PAIR + (w ^ 2), 64);
  if (w >= 2 || m == 0) {
#pragma unroll
    for (int k = 0; k < 4; k++) lds_u4(exc + k * 512, P[4 * k], P[4 * k + 1], P[4 * k + 2], P[4 * k + 3]);
    const float4 r = lds_f4(ktab - (w >> 1) * 320);
    P[16] = __float_as_uint(r.x);
    P[17] = __float_as_uint(r.z);
  } else {
    if (HALO_NS) __nanosleep(HALO_NS);
#pragma unroll 1
    for (int it = 0; it < MSG_SPINS; it++) {
      uint32_t tg, bad = 0;
      if (it > 0) poll_line(reinterpret_cast<const uint32_t*>(halo - 8 * 384 + 191) + 3, tag, 1u);
#pragma unroll
      for (int k = 0; k < 6; k++) {
        ld_msg(halo - 8 * 384 + k * 32 + lane, P[3 * k], P[3 * k + 1], P[3 * k + 2], tg);
        bad |= tg ^ tag;
      }
      if (__all_sync(0xffffffffu, bad == 0)) break;
    }
  }
  kr[0][0] = __uint_as_float(P[16]);
  kr[0][1] = __uint_as_float(P[17]);
  const bool early[2] = {2 * (lane & 3) > (lane >> 2), 2 * (lane & 3) + 1 > (lane >> 2)};
  const uint32_t mask = (early[0] ? 0xffffu : 0u) | (early[1] ? 0xffff0000u : 0u);
  float rk[2][4], sc[2][4], off[2][4];
#pragma unroll
  for (int g = 0; g < 2; g++) {
#pragma unroll
    for (int e = 0; e < 4; e++) {
      const int q = 2 * g + (e >> 1);
      const bool masked = q == 0 && m == 0 && w < 2 && early[e & 1];
      rk[g][e] = early[e & 1] ? kr[q][e & 1] : kr[q + 1][e & 1];
      sc[g][e] = masked ? 0.f : rk[g][e] * qr[q];
      off[g][e] = masked ? -1e30f : 0.f;
    }
  }
  if (w == 0 && elect_one()) asm volatile("prefetch.tensormap [%0];" ::"l"(&p.att_st) : "memory");
  PROF_E(7 * layer + t, 2);
  bar_sync(BAR_GO, 256);
  const float4 zero = lds_f4(sb + OFF_ZERO);
  float l[2][2][4];
  uint32_t O[4][8];
#pragma unroll
  for (int h = 0; h < 2; h++) {
    if (h == 1) {
      Q[2][4] |= __float_as_uint(l[1][0][0]) & p.zero;
      Q[0][4] |= __float_as_uint(l[0][0][0]) & p.zero;
    }
    attn_scores(&Q[2][4 * h], &Q[3][4 * h], &K[1][4 * h], &K[2][4 * h], &K[3][4 * h], l[1][h], zero, early);
    attn_scores(&Q[0][4 * h], &Q[1][4 * h], &P[4 * h], &K[0][4 * h], &K[1][4 * h], l[0][h], zero, early);
  }
  const uint32_t stg = sb + OFF_STG + w * 4096, srow = stg + lane * 128 + ((lane & 7) << 4);
#pragma unroll
  for (int h = 0; h < 2; h++) {
    attn_mix(l[1][h], sc[1], off[1], rk[1], &V[1][4 * h], &V[2][4 * h], &V[3][4 * h], &O[2][4 * h], &O[3][4 * h], mask, p.zero);
    attn_mix(l[0][h], sc[0], off[0], rk[0], &P[8 + 4 * h], &V[0][4 * h], &V[1][4 * h], &O[0][4 * h], &O[1][4 * h], mask, p.zero);
#pragma unroll
    for (int j = 4 * h; j < 4 * h + 4; j++) stsm4(srow ^ (j << 4), O[0][j], O[1][j], O[2][j], O[3][j]);
  }
  bar_arrive(BAR_DONE, 256);
  fence_async_smem();
  __syncwarp();
  if (lane == 0) {
    tma_st2(&p.att_st, stg, 128 * n + 64 * t, 128 * m + 32 * w);
    bulk_commit();
  }
}

template <bool PACED>
__device__ __forceinline__ void rank1_update(const Params& p, float (&acc)[2][96], const Ctx& cx, int t) {
  float nm[4];
#pragma unroll
  for (int q = 0; q < 4; q++) nm[q] = t == 6 ? 1.f : -lds_f(cx.sb + OFF_ROW + (32 * cx.w + 8 * q + (cx.lane >> 2)) * 8 + 4);
  const uint32_t ctab = cx.sb + OFF_CSQ + ((t & 3) * 192 + 2 * (cx.lane & 3)) * 4;
#pragma unroll
  for (int j = 0; j < 24; j++) {
    const float2 cs = lds_f2(ctab + j * 32);
#pragma unroll
    for (int q = 0; q < 4; q++) {
      const int k = 4 * j + q - 1;
      const float nq = PACED && k >= 0 ? chain(nm[q], __float_as_uint(ACC(k & 3, k >> 2, 1)), p.zero) : nm[q];
      ACC(q, j, 0) = fmaf(nq, cs.x, ACC(q, j, 0));
      ACC(q, j, 1) = fmaf(nq, cs.y, ACC(q, j, 1));
    }
  }
}

__device__ __forceinline__ void finish_stores(uint32_t sb, int i) {
  const int t = i >= 7 ? i - 7 : i;
  if ((threadIdx.x & 31) == 0) {
    bulk_wait_all();
    mbar_arrive(sb + BAR_PUB + 8 * (t < 2 ? t : t + 1));
  }
  __syncwarp();
  if (i < 12) bar_arrive(BAR_GUARD + ((i & 1) ^ 1), 256);
}

__device__ __forceinline__ bool consumer_tile(const Params& p, float (&acc)[2][96], uint32_t sb0, int i, int mn) {
  const int layer = i >= 7, t = i - 7 * layer, wg = i & 1;
  const bool resid = t == 2 || t == 6;
  {
    if (resid) {
      const Ctx cx = make_ctx(sb0, mn);
      const uint32_t xrow = cx.sb + OFF_X + cx.w * 4096 + cx.lane * 128;
      const uint32_t sel_lo = 0x1044u | p.zero, sel_hi = 0x3244u | p.zero;
#pragma unroll
      for (int j = 0; j < 16; j++) {
        uint32_t r[4];
        ldsm4(xrow + (j >> 3) * 16384 + (((j & 7) ^ (cx.lane & 7)) << 4), r[0], r[1], r[2], r[3]);
#pragma unroll
        for (int q = 0; q < 4; q++) {
          ACC(q, j, 0) = prmt_f(r[q], sel_lo);
          ACC(q, j, 1) = prmt_f(r[q], sel_hi);
        }
      }
    }
    if (t >= 5 || i == 7) finish_stores(sb0, i - 2);
#pragma unroll 1
    for (int step = !tile_split(i);; step++) {
      if (step == 1 && (t == 1 || t == 4)) {
        const Ctx cx = make_ctx(sb0, mn);
        if (i == 1) {
          const uint32_t epoch = __ldcg(p.g->epoch + (mn & 127));
          cluster_wait();
          asm volatile("st.shared.u32 [%0], %1;" ::"r"(sb0 + OFF_TAG), "r"(epoch + 1) : "memory");
        }
        const uint32_t tag = lds_u(cx.sb + OFF_TAG);
        const int ln = (i + 1) >> 2;
#pragma unroll 1
        for (int r = 0; r < 2; r++) {
          if (i == 1) {
            if (cx.w < 3) {
              float a[8] = {0.f, 0.f, 0.f, 0.f, 0.f, 0.f, 0.f, 0.f};
              mbar_wait(sb0 + BAR_CSLD, r);
#pragma unroll 1
              for (int h = 0; h < 2; h++) sum_rows(cx.sb + OFF_STG + h * 12288 + cx.w * 4096, 4, a, cx.lane);
              publish_sums(a, p.g->csp + (cx.n * 17 + cx.m) * 224 + (3 * r + cx.w) * 32, cx.lane, tag);
            }
            PROF_E(-1, 5 + r);
          }
          if (r == 1) break;
          if (i == 1) {
            bar_sync(BAR_WG + 1, 128);
            if (cx.w == 3 && elect_one()) {
              mbar_expect_tx(sb0 + BAR_CSLD, 24576);
              tma_ld3(sb0 + OFF_STG, &p.wqkv, sb0 + BAR_CSLD, 128 * cx.n + 64, 64 * cx.m, 0);
              tma_ld3(sb0 + OFF_STG + 12288, &p.wqkv, sb0 + BAR_CSLD, 128 * cx.n + 64, 64 * cx.m + 32, 0);
            }
            mbar_wait(sb0 + BAR_XRDY, 0);
            mbar_wait(sb0 + BAR_XRDY + 8, 0);
          }
          write_partial_stats(p, cx, ln, tag);
          PROF_E(i - 2, 8);
        }
        if (i == 1) {
          bar_arrive(BAR_HLP, 160);
          bar_sync(BAR_INIT, 160);
        }
        if (i <= 4) colsum_total(p, cx, ln, tag);
        PROF_E(i - 2, 9);
        if (i != 1) bar_sync(BAR_GUARD + wg, 256);
        finish_row_stats(p, cx, ln, tag);
        PROF_E(i - 2, 10);
        if (i == 4) {
          colsum_gather(p, cx, 1, tag);
          mbar_wait(sb0 + BAR_BIAS, 0);
        }
        PROF_E(i - 2, 15);
        bar_arrive(BAR_GUARD + (wg ^ 1), 256);
      }
      if (step == 2 && !resid) bar_sync(BAR_GUARD + wg, 256);
      if (step == 2 && i == 0) {
        colsum_gather(p, make_ctx(sb0, mn), 0, lds_u(sb0 + OFF_TAG));
        bar_sync(BAR_WG, 128);
      }
      if (i == 1) {
        if (step == 2) rank1_update<false>(p, acc, make_ctx(sb0, mn), t);
      } else if (t + step == 2 || t == 6) {
        rank1_update<true>(p, acc, make_ctx(sb0, mn), t);
      }
      if (step == 2) break;
      if (tile_wide(t)) {
        mainloop<192>(p, acc, sb0, i, step, mn);
      } else {
        mainloop<128>(p, acc, sb0, i, step, mn);
        if (resid) return false;
      }
    }
    if (t < 2) return true;
    gelu_epilogue(p, acc, make_ctx(sb0, mn), t);
    PROF_E(i, 4);
    return false;
  }
}

__global__ void __cluster_dims__(2, 1, 1) __launch_bounds__(384, 1) fused_layers_kernel(const int by_smid, const __nv_bfloat16* x_p, const __nv_bfloat16* wqkv_p,
                                                                  const __grid_constant__ Params p) {
  extern __shared__ __align__(1024) uint8_t smem_raw[];
  const uint32_t sb = uniform((uint32_t)__cvta_generic_to_shared(smem_raw));
  const int tid = threadIdx.x, lane = tid & 31, warp = uniform(tid >> 5), wg = warp >> 2, w = warp & 3;

  int mn;
  {
    int id = blockIdx.x;
    if (by_smid) asm volatile("mov.u32 %0, %%smid;" : "=r"(id));
    else if (id >= 120) id += 4;
    const int c = id >> 1;
    int g, j;
    if (c < 32) { g = c & 7; j = c >> 3; }
    else if (c < 60) { g = 1 + (c - 32) % 7; j = 4 + (c - 32) / 7; }
    else { g = 0; j = c - 58; }
    const int r = blockIdx.x & 1;
    mn = (g * 2 + r) * 8 + j;
    if (c == 60 || c == 61) {
      if (tid < 32) {
        const uint32_t tag = __ldcg(p.g->epoch + NCTA + (id & 3)) + 1;
#pragma unroll 1
        for (int mm = 0; mm < 16; mm++) poll_line(p.g->flags + mm * 32 + (lane & 7), 32 * tag, 0xffu);
        if (tid == 0) p.g->epoch[NCTA + (id & 3)] = tag;
      }
      return;
    }
  }
  const int m = mn >> 3, n = mn & 7;
  if (tid == 256) PROF_U(1);
  if (tid >= 382) asm volatile("prefetch.global.L2 [%0];" ::"l"(tid & 1 ? wqkv_p + 128 * n : x_p + 128 * m * DM));
  if (wg < 2) {
    cluster_arrive();
    asm volatile("setmaxnreg.inc.sync.aligned.u32 232;");
    const int id = mn | (warp << 7);
#pragma unroll 1
    for (int i = wg;; i += 2) {
      float acc[2][96];
#pragma unroll
      for (int r = 0; r < 96; r++) acc[0][r] = acc[1][r] = 0.f;
      pin_regs<96>(acc);
#pragma unroll 1
      while (!consumer_tile(p, acc, sb, i, id)) {
        PROF_T(6 + i * 4);
        i += 2;
        if (i >= 14) goto all_done;
      }
      attn_epilogue(p, acc, make_ctx(sb, id), i >= 7, i >= 7 ? i - 7 : i, lds_u(sb + OFF_TAG));
      PROF_E(i, 4);
      finish_stores(sb, i);
      PROF_E(i, 5);
      PROF_T(6 + i * 4);
    }
  all_done:
    if (wg == 0) {
      finish_stores(sb, 12);
    } else {
      cluster_arrive();
      cluster_wait();
    }
  } else {
    asm volatile("setmaxnreg.dec.sync.aligned.u32 40;");
    if (w != 0) {
      if (w == 1 && elect_one()) {
        mbar_init(sb + BAR_FULL + 32, 2);
#pragma unroll
        for (int k = 0; k < NBAR; k++) mbar_init(sb + BAR_EMPTY + 8 * k, 8);
#pragma unroll
        for (int k = 0; k < 3; k++) mbar_init(sb + BAR_XRDY + 8 * k, 4);
#pragma unroll
        for (int k = 0; k < 9; k++) mbar_init(sb + BAR_PUB + 8 * k, 4);
#pragma unroll
        for (int k = 0; k < 4; k++) mbar_init(sb + BAR_CSLD + 8 * k, 1);
        sts_f2(sb + OFF_ZERO, 0.f, 0.f);
        sts_f2(sb + OFF_ZERO + 8, 0.f, 0.f);
        asm volatile("fence.mbarrier_init.release.cluster;" ::: "memory");
      }
      __syncwarp();
      cluster_arrive();
      if (w == 2) {
        if (lane < 28) write_run_desc(sb, lane >> 1, lane & 1);
        bar_arrive(BAR_INIT, 160);
      }
      cluster_wait();
      if (w == 1) producer<true>(p, sb, m, n, lane);
      else if (w == 3) colsum_helper(p, sb, m, n, lane);
      else if (elect_one()) publisher(p, sb, m, n);
    } else {
      const bool leader = elect_one();
      if (leader) {
#pragma unroll
        for (int k = 0; k < 4; k++) mbar_init(sb + BAR_FULL + 8 * k, 2);
        asm volatile("fence.mbarrier_init.release.cluster;" ::: "memory");
        PROF_U(4);
      }
      __syncwarp();
      cluster_arrive();
      if (leader) {
#pragma unroll 1
        for (int k = 0; k < 4; k++) {
          const uint32_t fb = sb + BAR_FULL + 8 * k;
          mbar_expect_tx(fb, 16384);
          tma_ld_act(sb + (5 * k + 3) * UNIT, &p.xin, fb, 64 * k, m);
          mbar_expect_tx(fb, 3 * UNIT);
          tma_ld3(sb + 5 * k * UNIT, &p.wqkv, fb, 128 * n, 64 * k, 0);
          tma_ld3(sb + 5 * k * UNIT + 12288, &p.wqkv, fb, 128 * n, 64 * k + 32, 0);
        }
        PROF_U(5);
      }
      __syncwarp();
      cluster_wait();
      if (leader) {
        mbar_expect_tx(sb + BAR_CSLD, 24576);
        tma_ld3(sb + OFF_STG, &p.wqkv, sb + BAR_CSLD, 128 * n, 64 * m, 0);
        tma_ld3(sb + OFF_STG + 12288, &p.wqkv, sb + BAR_CSLD, 128 * n, 64 * m + 32, 0);
#pragma unroll 1
        for (int h = 0; h < 2; h++) {
          const uint32_t xr = sb + BAR_XRDY + 8 * h;
          mbar_expect_tx(xr, 16384);
          tma_ld_act(sb + OFF_X + h * 16384, &p.xin, xr, 128 * n + 64 * h, m);
          asm volatile("mbarrier.arrive.shared::cta.b64 _, [%0], 3;" ::"r"(xr) : "memory");
        }
        PROF_U(6);
      }
      __syncwarp();
      producer<false>(p, sb, m, n, lane);
    }
  }
}

typedef CUresult (*EncodeFn)(CUtensorMap*, CUtensorMapDataType, cuuint32_t, void*, const cuuint64_t*, const cuuint64_t*,
                             const cuuint32_t*, const cuuint32_t*, CUtensorMapInterleave, CUtensorMapSwizzle,
                             CUtensorMapL2promotion, CUtensorMapFloatOOBfill);

#define PROMO2 CU_TENSOR_MAP_L2_PROMOTION_L2_128B
#define PROMO3 CU_TENSOR_MAP_L2_PROMOTION_L2_128B
void make_2d(EncodeFn enc, CUtensorMap* m, const void* ptr, uint64_t cols, uint64_t rows, uint32_t box_rows) {
  cuuint64_t d[2] = {cols, rows}, st[1] = {cols * 2};
  cuuint32_t b[2] = {64, box_rows}, e[2] = {1, 1};
  enc(m, CU_TENSOR_MAP_DATA_TYPE_BFLOAT16, 2, const_cast<void*>(ptr), d, st, b, e, CU_TENSOR_MAP_INTERLEAVE_NONE,
      CU_TENSOR_MAP_SWIZZLE_128B, PROMO2, CU_TENSOR_MAP_FLOAT_OOB_FILL_NONE);
}
void make_act(EncodeFn enc, CUtensorMap* m, const void* ptr, uint64_t cols, bool split) {
  const uint64_t row = cols * 2;
  cuuint64_t d[4] = {cols, 32, 2, SEQ / 64}, st[3] = {split ? 2 * row : row, split ? row : 32 * row, 64 * row};
  cuuint32_t b[4] = {64, 32, 2, 2}, e[4] = {1, 1, 1, 1};
  enc(m, CU_TENSOR_MAP_DATA_TYPE_BFLOAT16, 4, const_cast<void*>(ptr), d, st, b, e, CU_TENSOR_MAP_INTERLEAVE_NONE,
      CU_TENSOR_MAP_SWIZZLE_128B, PROMO2, CU_TENSOR_MAP_FLOAT_OOB_FILL_NONE);
}
void make_3d(EncodeFn enc, CUtensorMap* m, const void* ptr, uint64_t d0, uint64_t rows, uint64_t d2, uint64_t row_bytes,
             uint64_t chunk_bytes, uint32_t box_chunks) {
  cuuint64_t d[3] = {d0, rows, d2}, st[2] = {row_bytes, chunk_bytes};
  cuuint32_t b[3] = {64, 32, box_chunks}, e[3] = {1, 1, 1};
  enc(m, CU_TENSOR_MAP_DATA_TYPE_BFLOAT16, 3, const_cast<void*>(ptr), d, st, b, e, CU_TENSOR_MAP_INTERLEAVE_NONE,
      CU_TENSOR_MAP_SWIZZLE_128B, PROMO3, CU_TENSOR_MAP_FLOAT_OOB_FILL_NONE);
}

}

extern "C" void kernel_launch(void* const* d_in, const int* in_sizes, int n_in, void* d_out, int out_size) {
  (void)in_sizes; (void)n_in; (void)out_size;
  static EncodeFn enc = nullptr;
  static void *att = nullptr, *hbuf = nullptr, *scratch = nullptr;
  static int by_smid = 0;
  if (!enc) {
    void* fn = nullptr;
    cudaDriverEntryPointQueryResult q;
    cudaGetDriverEntryPoint("cuTensorMapEncodeTiled", &fn, cudaEnableDefault, &q);
    enc = (EncodeFn)fn;
    cudaGetSymbolAddress(&att, g_att);
    cudaGetSymbolAddress(&hbuf, g_h);
    cudaGetSymbolAddress(&scratch, g_scratch);
    cudaFuncSetAttribute(fused_layers_kernel, cudaFuncAttributeMaxDynamicSharedMemorySize, SMEM_BYTES);
    int sms = 0, clusters = 0, dev = 0;
    cudaGetDevice(&dev);
    cudaDeviceGetAttribute(&sms, cudaDevAttrMultiProcessorCount, dev);
    cudaLaunchConfig_t cfg = {};
    cfg.gridDim = dim3(132);
    cfg.blockDim = dim3(384);
    cfg.dynamicSmemBytes = SMEM_BYTES;
    cudaLaunchAttribute at[1];
    at[0].id = cudaLaunchAttributeClusterDimension;
    at[0].val.clusterDim.x = 2; at[0].val.clusterDim.y = 1; at[0].val.clusterDim.z = 1;
    cfg.attrs = at;
    cfg.numAttrs = 1;
    if (cudaOccupancyMaxActiveClusters(&clusters, fused_layers_kernel, &cfg) != cudaSuccess) (void)cudaGetLastError();
    by_smid = sms == 132 && clusters == 66;
  }
  Params p;
  make_act(enc, &p.xin, d_in[0], DM, true);
  make_act(enc, &p.out, d_out, DM, true);
  make_act(enc, &p.att, att, DM, false);
  make_act(enc, &p.h, hbuf, FF, false);
  make_2d(enc, &p.att_st, att, DM, SEQ, 32);
  make_2d(enc, &p.h_st, hbuf, FF, SEQ, 32);
  make_2d(enc, &p.w1c, d_in[4], FF, DM, 32);
  make_3d(enc, &p.wqkv, d_in[1], DM, DM, 3, 3 * DM * 2, DM * 2, 3);
  make_3d(enc, &p.wo, d_in[2], 64, DM, DM / 64, DM * 2, 128, 2);
  make_3d(enc, &p.w1a, d_in[4], 64, DM, FF / 64, FF * 2, 128, 3);
  make_3d(enc, &p.w1b, d_in[4], 64, DM, FF / 64, FF * 2, 128, 2);
  make_3d(enc, &p.w2, d_in[6], 64, FF, DM / 64, DM * 2, 128, 2);
  p.b1 = (const __nv_bfloat16*)d_in[5];
  p.b2 = (const __nv_bfloat16*)d_in[7];
  p.g = (Scratch*)scratch;
  p.zero = 0;
  fused_layers_kernel<<<by_smid ? 132 : NCTA, 384, SMEM_BYTES>>>(by_smid, (const __nv_bfloat16*)d_in[0], (const __nv_bfloat16*)d_in[1], p);
}
```

```cpp
#include <cuda_runtime.h>
#include <cuda_bf16.h>
#include <cuda.h>
#include <stdint.h>

namespace {

constexpr int SEQ = 2048, DM = 1024, FF = 3584;
constexpr int NCTA = 128;
constexpr int NBAR = 5;

constexpr uint32_t RING_UNITS = 20, UNIT = 8192;
constexpr uint32_t OFF_X   = RING_UNITS * UNIT;
constexpr uint32_t OFF_STG = OFF_X + 32768;
constexpr uint32_t OFF_HLP = OFF_STG + 16384;
constexpr uint32_t OFF_RUN = OFF_STG + 24576;
constexpr uint32_t OFF_CSQ = OFF_RUN + 512;
constexpr uint32_t OFF_CSF = OFF_CSQ + 2048;
constexpr uint32_t OFF_ROW = OFF_CSF + 3584;
constexpr uint32_t OFF_BAR = OFF_ROW + 1024;
constexpr uint32_t SMEM_BYTES = OFF_BAR + 384;
constexpr uint32_t BAR_FULL = OFF_BAR, BAR_EMPTY = OFF_BAR + 8 * NBAR;
constexpr uint32_t BAR_XRDY = OFF_BAR + 80;
constexpr uint32_t BAR_DUMMY = OFF_BAR + 96, OFF_TAG = OFF_BAR + 104, OFF_ZERO = OFF_BAR + 112;
constexpr uint32_t BAR_PUB = OFF_BAR + 128;
constexpr uint32_t BAR_CSLD = OFF_BAR + 200;
constexpr uint32_t BAR_XGO = OFF_BAR + 224;
constexpr uint32_t BAR_BIAS = OFF_BAR + 216;

constexpr uint64_t DESC_A = (1ull << 62) | ((uint64_t)(2048 >> 4) << 32) | (1ull << 16);
constexpr uint64_t DESC_B = (1ull << 62) | ((uint64_t)(1024 >> 4) << 32) | ((uint64_t)(4096 >> 4) << 16);

constexpr int BAR_INIT = 0, BAR_ORDER = 1, BAR_GUARD = 3, BAR_WG = 5, BAR_GO = 7, BAR_DONE = 8, BAR_HLP = 9, BAR_INIT0 = 10, BAR_PAIR = 11;
#define GELU_DEP 2
#define MAP 2
#define LATE_O 1
#define HALO_NS 200
#define STG_WAIT 5
#define STAT_NS 800
#define BDELAY 100
#define STAG5 450
#define STAG4 0
#define STAG3 0
#define PACE0 0
#define PACE_M 150
#define PACE_N 500
#define CS_NS 500
#define WIN1 8
#define WIN2 2

struct Scratch {
  uint4 stats[4 * 8 * SEQ];
  uint4 halo[2 * 2 * 16 * 8 * 384];
  uint4 csp[2 * 8 * 17 * 224];
  uint32_t flags[16 * 32];
  uint32_t epoch[NCTA + 4];
};

struct Maps {
  CUtensorMap xin, out, att, h, wqkv, wo, w1a, w1b, w2, att_st, h_st, w1c;
};
struct Scalars {
  Scratch* g;
  const __nv_bfloat16 *b1, *b2;
  uint32_t zero;
};
struct Params : Scalars {
  const Maps& t;
};

__device__ __nv_bfloat16 g_att[SEQ * DM];
__device__ __nv_bfloat16 g_h[SEQ * FF];
__device__ Scratch g_scratch;
#define PROF_T(idx)
#define PROF_U(k)
#define PROF_S(g)
#define PROF_E(i, k)

__device__ __forceinline__ void mbar_init(uint32_t bar, int cnt) {
  asm volatile("mbarrier.init.shared::cta.b64 [%0], %1;" ::"r"(bar), "r"(cnt));
}
__device__ __forceinline__ void mbar_expect_tx(uint32_t bar, uint32_t bytes) {
  asm volatile("mbarrier.arrive.expect_tx.shared::cta.b64 _, [%0], %1;" ::"r"(bar), "r"(bytes) : "memory");
}
__device__ __forceinline__ void mbar_arrive(uint32_t bar) {
  asm volatile("mbarrier.arrive.shared::cta.b64 _, [%0];" ::"r"(bar) : "memory");
}
__device__ __forceinline__ bool mbar_test(uint32_t bar, uint32_t parity) {
  uint32_t ok;
  asm volatile("{\n.reg .pred p;\nmbarrier.test_wait.parity.shared::cta.b64 p, [%1], %2;\nselp.u32 %0, 1, 0, p;\n}"
               : "=r"(ok) : "r"(bar), "r"(parity) : "memory");
  return ok;
}
__device__ __forceinline__ void mbar_wait(uint32_t bar, uint32_t parity) {
  asm volatile(
      "{\n.reg .pred p;\n.reg .u32 it;\nmov.u32 it, 0;\n"
      "WAIT_LOOP:\n"
      "mbarrier.try_wait.parity.shared::cta.b64 p, [%0], %1;\n"
      "@p bra WAIT_DONE;\n"
      "add.u32 it, it, 1;\n"
      "setp.lt.u32 p, it, 0x400000;\n"
      "@p bra WAIT_LOOP;\n"
      "trap;\n"
      "WAIT_DONE:\n}"
      ::"r"(bar), "r"(parity) : "memory");
}
__device__ __forceinline__ void bar_sync(int id, int n) { asm volatile("bar.sync %0, %1;" ::"r"(id), "r"(n) : "memory"); }
__device__ __forceinline__ void bar_arrive(int id, int n) { asm volatile("bar.arrive %0, %1;" ::"r"(id), "r"(n) : "memory"); }
__device__ __forceinline__ void tma_ld2(uint32_t dst, const CUtensorMap* m, uint32_t bar, int c0, int c1) {
  asm volatile("cp.async.bulk.tensor.2d.shared::cluster.global.mbarrier::complete_tx::bytes [%0], [%1, {%3, %4}], [%2];"
               ::"r"(dst), "l"(m), "r"(bar), "r"(c0), "r"(c1) : "memory");
}
__device__ __forceinline__ void tma_ld_act(uint32_t dst, const CUtensorMap* m, uint32_t bar, int col, int blk) {
  asm volatile("cp.async.bulk.tensor.4d.shared::cluster.global.mbarrier::complete_tx::bytes [%0], [%1, {%3, %5, %5, %4}], [%2];"
               ::"r"(dst), "l"(m), "r"(bar), "r"(col), "r"(2 * blk), "r"(0) : "memory");
}
__device__ __forceinline__ void tma_st_act(const CUtensorMap* m, uint32_t src, int col, int blk) {
  asm volatile("cp.async.bulk.tensor.4d.global.shared::cta.bulk_group [%0, {%2, %4, %4, %3}], [%1];"
               ::"l"(m), "r"(src), "r"(col), "r"(2 * blk), "r"(0) : "memory");
}
__device__ __forceinline__ void tma_ld3(uint32_t dst, const CUtensorMap* m, uint32_t bar, int c0, int c1, int c2) {
  asm volatile("cp.async.bulk.tensor.3d.shared::cluster.global.mbarrier::complete_tx::bytes [%0], [%1, {%3, %4, %5}], [%2];"
               ::"r"(dst), "l"(m), "r"(bar), "r"(c0), "r"(c1), "r"(c2) : "memory");
}
__device__ __forceinline__ void tma_ld3_pair(uint32_t dst, const CUtensorMap* m, uint32_t bar, int c0, int c1, int c2) {
  asm volatile("cp.async.bulk.tensor.3d.shared::cluster.global.mbarrier::complete_tx::bytes.multicast::cluster"
               " [%0], [%1, {%3, %4, %5}], [%2], %6;"
               ::"r"(dst), "l"(m), "r"(bar), "r"(c0), "r"(c1), "r"(c2), "h"((uint16_t)3) : "memory");
}
__device__ __forceinline__ uint32_t pair_offset(uint32_t sb, uint32_t rank) {
  uint32_t r;
  asm volatile("mapa.shared::cluster.u32 %0, %1, %2;" : "=r"(r) : "r"(sb), "r"(rank));
  return r - sb;
}
__device__ __forceinline__ void mbar_arrive_cluster(uint32_t bar) {
  asm volatile("mbarrier.arrive.shared::cluster.b64 _, [%0];" ::"r"(bar) : "memory");
}
__device__ __forceinline__ void cluster_arrive() { asm volatile("barrier.cluster.arrive.relaxed;" ::: "memory"); }
__device__ __forceinline__ void cluster_wait() { asm volatile("barrier.cluster.wait.acquire;" ::: "memory"); }
__device__ __forceinline__ void tma_st2(const CUtensorMap* m, uint32_t src, int c0, int c1) {
  asm volatile("cp.async.bulk.tensor.2d.global.shared::cta.bulk_group [%0, {%2, %3}], [%1];"
               ::"l"(m), "r"(src), "r"(c0), "r"(c1) : "memory");
}
__device__ __forceinline__ void bulk_commit() { asm volatile("cp.async.bulk.commit_group;" ::: "memory"); }
__device__ __forceinline__ void bulk_wait_read() { asm volatile("cp.async.bulk.wait_group.read 0;" ::: "memory"); }
__device__ __forceinline__ void bulk_wait_all() { asm volatile("cp.async.bulk.wait_group 0;" ::: "memory"); }
__device__ __forceinline__ void fence_async_smem() { asm volatile("fence.proxy.async.shared::cta;" ::: "memory"); }
__device__ __forceinline__ void fence_async_global() { asm volatile("fence.proxy.async.global;" ::: "memory"); }
__device__ __forceinline__ void st_relaxed(uint32_t* p, uint32_t v) {
  asm volatile("st.relaxed.gpu.global.u32 [%0], %1;" ::"l"(p), "r"(v) : "memory");
}
__device__ __forceinline__ void st_msg(uint4* p, uint32_t a, uint32_t b, uint32_t c, uint32_t tag) {
  asm volatile("{\n.reg .b128 v;\nmov.b128 v, {%1, %2, %3, %4};\nst.relaxed.gpu.global.b128 [%0], v;\n}"
               ::"l"(p), "r"(a), "r"(b), "r"(c), "r"(tag) : "memory");
}
__device__ __forceinline__ void ld_msg(const uint4* p, uint32_t& a, uint32_t& b, uint32_t& c, uint32_t& tag) {
  asm volatile("{\n.reg .b128 v;\nld.relaxed.gpu.global.b128 v, [%4];\nmov.b128 {%0, %1, %2, %3}, v;\n}"
               : "=r"(a), "=r"(b), "=r"(c), "=r"(tag) : "l"(p) : "memory");
}
__device__ __forceinline__ bool elect_one() {
  uint32_t ok;
  asm volatile("{\n.reg .pred p;\nelect.sync _|p, 0xffffffff;\nselp.u32 %0, 1, 0, p;\n}" : "=r"(ok));
  return ok;
}
__device__ __forceinline__ uint32_t lanemask_lt() {
  uint32_t v;
  asm("mov.u32 %0, %%lanemask_lt;" : "=r"(v));
  return v;
}
__device__ __forceinline__ int uniform(int v) { return __shfl_sync(0xffffffffu, v, 0); }
__device__ __forceinline__ uint32_t pack_bf16(float lo, float hi) {
  uint32_t r;
  asm("cvt.rn.bf16x2.f32 %0, %1, %2;" : "=r"(r) : "f"(hi), "f"(lo));
  return r;
}
__device__ __forceinline__ float prmt_f(uint32_t a, uint32_t sel) {
  float r;
  asm("{\n.reg .b32 t;\nprmt.b32 t, %1, 0, %2;\nmov.b32 %0, t;\n}" : "=f"(r) : "r"(a), "r"(sel));
  return r;
}
__device__ __forceinline__ float bf_lo(uint32_t v) { return __uint_as_float(v << 16); }
__device__ __forceinline__ float bf_hi(uint32_t v) { return __uint_as_float(v & 0xffff0000u); }
__device__ __forceinline__ void stsm4(uint32_t addr, uint32_t r0, uint32_t r1, uint32_t r2, uint32_t r3) {
  asm volatile("stmatrix.sync.aligned.m8n8.x4.shared.b16 [%0], {%1, %2, %3, %4};"
               ::"r"(addr), "r"(r0), "r"(r1), "r"(r2), "r"(r3) : "memory");
}
__device__ __forceinline__ void ldsm4(uint32_t addr, uint32_t& r0, uint32_t& r1, uint32_t& r2, uint32_t& r3) {
  asm volatile("ldmatrix.sync.aligned.m8n8.x4.shared.b16 {%0, %1, %2, %3}, [%4];"
               : "=r"(r0), "=r"(r1), "=r"(r2), "=r"(r3) : "r"(addr) : "memory");
}
__device__ __forceinline__ uint32_t movtrans(uint32_t a) {
  uint32_t d;
  asm volatile("movmatrix.sync.aligned.m8n8.trans.b16 %0, %1;" : "=r"(d) : "r"(a));
  return d;
}
__device__ __forceinline__ void mma16816(float (&c)[4], uint32_t a0, uint32_t a1, uint32_t a2, uint32_t a3, uint32_t b0, uint32_t b1) {
  asm volatile("mma.sync.aligned.m16n8k16.row.col.f32.bf16.bf16.f32 {%0,%1,%2,%3}, {%4,%5,%6,%7}, {%8,%9}, {%0,%1,%2,%3};"
               : "+f"(c[0]), "+f"(c[1]), "+f"(c[2]), "+f"(c[3])
               : "r"(a0), "r"(a1), "r"(a2), "r"(a3), "r"(b0), "r"(b1));
}
__device__ __forceinline__ void mma1688(float (&c)[4], uint32_t a0, uint32_t a1, uint32_t b0) {
  asm volatile("mma.sync.aligned.m16n8k8.row.col.f32.bf16.bf16.f32 {%0,%1,%2,%3}, {%4,%5}, {%6}, {%0,%1,%2,%3};"
               : "+f"(c[0]), "+f"(c[1]), "+f"(c[2]), "+f"(c[3]) : "r"(a0), "r"(a1), "r"(b0));
}
__device__ __forceinline__ float2 lds_f2(uint32_t a) {
  float2 v;
  asm volatile("ld.shared.v2.f32 {%0, %1}, [%2];" : "=f"(v.x), "=f"(v.y) : "r"(a) : "memory");
  return v;
}
__device__ __forceinline__ float4 lds_f4(uint32_t a) {
  float4 v;
  asm volatile("ld.shared.v4.f32 {%0, %1, %2, %3}, [%4];" : "=f"(v.x), "=f"(v.y), "=f"(v.z), "=f"(v.w) : "r"(a) : "memory");
  return v;
}
__device__ __forceinline__ float lds_f(uint32_t a) {
  float v;
  asm volatile("ld.shared.f32 %0, [%1];" : "=f"(v) : "r"(a) : "memory");
  return v;
}
__device__ __forceinline__ uint32_t lds_u(uint32_t a) {
  uint32_t v;
  asm volatile("ld.shared.u32 %0, [%1];" : "=r"(v) : "r"(a) : "memory");
  return v;
}
__device__ __forceinline__ void sts_f2(uint32_t a, float x, float y) {
  asm volatile("st.shared.v2.f32 [%0], {%1, %2};" ::"r"(a), "f"(x), "f"(y) : "memory");
}
__device__ __forceinline__ void sts_u4(uint32_t a, uint32_t x, uint32_t y, uint32_t z, uint32_t w) {
  asm volatile("st.shared.v4.u32 [%0], {%1, %2, %3, %4};" ::"r"(a), "r"(x), "r"(y), "r"(z), "r"(w) : "memory");
}
__device__ __forceinline__ void lds_u4(uint32_t a, uint32_t& x, uint32_t& y, uint32_t& z, uint32_t& w) {
  asm volatile("ld.shared.v4.u32 {%0, %1, %2, %3}, [%4];" : "=r"(x), "=r"(y), "=r"(z), "=r"(w) : "r"(a) : "memory");
}
__device__ __forceinline__ float ex2(float x) {
  float y;
  asm("ex2.approx.ftz.f32 %0, %1;" : "=f"(y) : "f"(x));
  return y;
}
__device__ __forceinline__ float rcp_hw(float x) {
  float y;
  asm("rcp.approx.ftz.f32 %0, %1;" : "=f"(y) : "f"(x));
  return y;
}
__device__ __forceinline__ float tanh_hw(float x) {
  float y;
  asm("tanh.approx.f32 %0, %1;" : "=f"(y) : "f"(x));
  return y;
}
__device__ __forceinline__ float quad_sum(float v) {
  v += __shfl_xor_sync(0xffffffffu, v, 1);
  return v + __shfl_xor_sync(0xffffffffu, v, 2);
}
__device__ __forceinline__ float quad_max(float v) {
  v = fmaxf(v, __shfl_xor_sync(0xffffffffu, v, 1));
  return fmaxf(v, __shfl_xor_sync(0xffffffffu, v, 2));
}

template <int N> __device__ __forceinline__ void wgmma_ss(float (&d)[96], uint64_t da, uint64_t db, uint32_t keep = 1);
template <> __device__ __forceinline__ void wgmma_ss<128>(float (&d)[96], uint64_t da, uint64_t db, uint32_t keep) {
  asm volatile(
      "{\n.reg .pred p;\nsetp.ne.u32 p, %66, 0;\n"
      "wgmma.mma_async.sync.aligned.m64n128k16.f32.bf16.bf16 {%0, %1, %2, %3, %4, %5, %6, %7, %8, %9, %10, %11, %12, %13, %14, %15, %16, %17, %18, %19, %20, %21, %22, %23, %24, %25, %26, %27, %28, %29, %30, %31, %32, %33, %34, %35, %36, %37, %38, %39, %40, %41, %42, %43, %44, %45, %46, %47, %48, %49, %50, %51, %52, %53, %54, %55, %56, %57, %58, %59, %60, %61, %62, %63}, %64, %65, p, 1, 1, 0, 1;\n}"
      : "+f"(d[0]), "+f"(d[1]), "+f"(d[2]), "+f"(d[3]), "+f"(d[4]), "+f"(d[5]), "+f"(d[6]), "+f"(d[7]), "+f"(d[8]), "+f"(d[9]), "+f"(d[10]), "+f"(d[11]), "+f"(d[12]), "+f"(d[13]), "+f"(d[14]), "+f"(d[15]), "+f"(d[16]), "+f"(d[17]), "+f"(d[18]), "+f"(d[19]), "+f"(d[20]), "+f"(d[21]), "+f"(d[22]), "+f"(d[23]), "+f"(d[24]), "+f"(d[25]), "+f"(d[26]), "+f"(d[27]), "+f"(d[28]), "+f"(d[29]), "+f"(d[30]), "+f"(d[31]), "+f"(d[32]), "+f"(d[33]), "+f"(d[34]), "+f"(d[35]), "+f"(d[36]), "+f"(d[37]), "+f"(d[38]), "+f"(d[39]), "+f"(d[40]), "+f"(d[41]), "+f"(d[42]), "+f"(d[43]), "+f"(d[44]), "+f"(d[45]), "+f"(d[46]), "+f"(d[47]), "+f"(d[48]), "+f"(d[49]), "+f"(d[50]), "+f"(d[51]), "+f"(d[52]), "+f"(d[53]), "+f"(d[54]), "+f"(d[55]), "+f"(d[56]), "+f"(d[57]), "+f"(d[58]), "+f"(d[59]), "+f"(d[60]), "+f"(d[61]), "+f"(d[62]), "+f"(d[63])
      : "l"(da), "l"(db), "r"(keep));
}

template <> __device__ __forceinline__ void wgmma_ss<192>(float (&d)[96], uint64_t da, uint64_t db, uint32_t keep) {
  asm volatile(
      "{\n.reg .pred p;\nsetp.ne.u32 p, %98, 0;\n"
      "wgmma.mma_async.sync.aligned.m64n192k16.f32.bf16.bf16 {%0, %1, %2, %3, %4, %5, %6, %7, %8, %9, %10, %11, %12, %13, %14, %15, %16, %17, %18, %19, %20, %21, %22, %23, %24, %25, %26, %27, %28, %29, %30, %31, %32, %33, %34, %35, %36, %37, %38, %39, %40, %41, %42, %43, %44, %45, %46, %47, %48, %49, %50, %51, %52, %53, %54, %55, %56, %57, %58, %59, %60, %61, %62, %63, %64, %65, %66, %67, %68, %69, %70, %71, %72, %73, %74, %75, %76, %77, %78, %79, %80, %81, %82, %83, %84, %85, %86, %87, %88, %89, %90, %91, %92, %93, %94, %95}, %96, %97, p, 1, 1, 0, 1;\n}"
      : "+f"(d[0]), "+f"(d[1]), "+f"(d[2]), "+f"(d[3]), "+f"(d[4]), "+f"(d[5]), "+f"(d[6]), "+f"(d[7]), "+f"(d[8]), "+f"(d[9]), "+f"(d[10]), "+f"(d[11]), "+f"(d[12]), "+f"(d[13]), "+f"(d[14]), "+f"(d[15]), "+f"(d[16]), "+f"(d[17]), "+f"(d[18]), "+f"(d[19]), "+f"(d[20]), "+f"(d[21]), "+f"(d[22]), "+f"(d[23]), "+f"(d[24]), "+f"(d[25]), "+f"(d[26]), "+f"(d[27]), "+f"(d[28]), "+f"(d[29]), "+f"(d[30]), "+f"(d[31]), "+f"(d[32]), "+f"(d[33]), "+f"(d[34]), "+f"(d[35]), "+f"(d[36]), "+f"(d[37]), "+f"(d[38]), "+f"(d[39]), "+f"(d[40]), "+f"(d[41]), "+f"(d[42]), "+f"(d[43]), "+f"(d[44]), "+f"(d[45]), "+f"(d[46]), "+f"(d[47]), "+f"(d[48]), "+f"(d[49]), "+f"(d[50]), "+f"(d[51]), "+f"(d[52]), "+f"(d[53]), "+f"(d[54]), "+f"(d[55]), "+f"(d[56]), "+f"(d[57]), "+f"(d[58]), "+f"(d[59]), "+f"(d[60]), "+f"(d[61]), "+f"(d[62]), "+f"(d[63]), "+f"(d[64]), "+f"(d[65]), "+f"(d[66]), "+f"(d[67]), "+f"(d[68]), "+f"(d[69]), "+f"(d[70]), "+f"(d[71]), "+f"(d[72]), "+f"(d[73]), "+f"(d[74]), "+f"(d[75]), "+f"(d[76]), "+f"(d[77]), "+f"(d[78]), "+f"(d[79]), "+f"(d[80]), "+f"(d[81]), "+f"(d[82]), "+f"(d[83]), "+f"(d[84]), "+f"(d[85]), "+f"(d[86]), "+f"(d[87]), "+f"(d[88]), "+f"(d[89]), "+f"(d[90]), "+f"(d[91]), "+f"(d[92]), "+f"(d[93]), "+f"(d[94]), "+f"(d[95])
      : "l"(da), "l"(db), "r"(keep));
}

template <int R>
__device__ __forceinline__ void pin_regs(float (&a)[2][96]) {
#pragma unroll
  for (int m = 0; m < 2; m++)
#pragma unroll
    for (int i = 0; i < R; i++) asm volatile("" : "+f"(a[m][i])::"memory");
}

struct Ctx {
  uint32_t sb;
  int m, n, wg, w, lane;
};
__device__ __forceinline__ Ctx make_ctx(uint32_t sb, int id) {
  int lane;
  asm volatile("mov.u32 %0, %%laneid;" : "=r"(lane));
  asm volatile("" : "+r"(id), "+r"(sb));
  return Ctx{sb, (id >> 3) & 15, id & 7, id >> 9, (id >> 7) & 3, lane};
}
#define UNPACK_CTX(c) const uint32_t sb = c.sb; const int m = c.m, n = c.n, wg = c.wg, w = c.w, lane = c.lane

__device__ __forceinline__ uint32_t poll_line(const uint32_t* word, uint32_t target, uint32_t need) {
  uint32_t v;
  asm volatile(
      "{\n.reg .pred p;\n.reg .u32 it, m;\n.reg .s32 d;\nmov.u32 it, 0;\n"
      "POLL_LOOP:\n"
      "ld.relaxed.gpu.global.u32 %0, [%1];\n"
      "sub.s32 d, %0, %2;\n"
      "setp.ge.s32 p, d, 0;\n"
      "vote.sync.ballot.b32 m, p, 0xffffffff;\n"
      "and.b32 m, m, %3;\n"
      "setp.eq.u32 p, m, %3;\n"
      "@p bra.uni POLL_DONE;\n"
      "add.u32 it, it, 1;\n"
      "setp.lt.u32 p, it, 0x400000;\n"
      "@p bra.uni POLL_LOOP;\n"
      "trap;\n"
      "POLL_DONE:\n}"
      : "=&r"(v) : "l"(word), "r"(target), "r"(need) : "memory");
  return v;
}
__device__ __forceinline__ uint32_t ld_relaxed(const uint32_t* p) {
  uint32_t v;
  asm volatile("ld.relaxed.gpu.global.u32 %0, [%1];" : "=r"(v) : "l"(p) : "memory");
  return v;
}
__device__ __forceinline__ float chain(float x, uint32_t on, uint32_t zero) {
  return __uint_as_float(__float_as_uint(x) | (on & zero));
}
constexpr int MSG_SPINS = 1 << 20;

constexpr int STAGES_PER_LAYER = 152;
__device__ __forceinline__ int nib(uint64_t v, int i) { return (int)(v >> (4 * i)) & 15; }
__device__ __forceinline__ bool tile_wide(int t) { return (0x23 >> t) & 1; }
__device__ __forceinline__ void weight_coords(const Params& p, int t, int n, const CUtensorMap*& map, int& c0, int& c2) {
  map = &p.t.wqkv + nib(0x4233100ull, t);
  c0 = t < 2 ? 128 * n + 64 * t : 0;
  c2 = t < 2 ? 0 : (t == 2 || t == 6) ? 2 * n : 7 * n + 2 * t - 6;
}

template <bool IS_A>
__device__ __forceinline__ void producer(const Params& p, uint32_t sb, int m, int n, int lane) {
  const uint32_t low = (1u << (4 * n)) - 1, others = (0x6543210u & low) | (0x7654321u & ~low);
  const uint64_t order_x = (uint64_t)(others * 2 + 0x1111111u) << 36 | (uint64_t)others * 2 << 8 | (n * 0x22 + 0x10);
  int inflight = 4, cur = 0;
  uint32_t fb = sb + BAR_FULL + 32, rb = sb + BAR_EMPTY, rph = 0, pos = 0, tag32 = 0, seen = 0;
  const uint32_t fend = sb + BAR_FULL + 8 * NBAR, rend = sb + BAR_EMPTY + 8 * NBAR;
  const uint32_t* word = p.g->flags + m * 32 + (lane < 16 ? lane >> 1 : lane & 7);
#pragma unroll 1
  for (int sg = 1; sg < 22; sg++) {
    const int layer = sg >= 11, s = sg == 1 ? 2 : sg == 2 ? 1 : sg - 11 * layer;
    const int t = nib(0x65434321010ull, s), kind = nib(0x32110031100ull, s);
    const bool wide = tile_wide(t);
    const uint32_t bbytes = wide ? 3 * UNIT : 2 * UNIT, base = sb + (IS_A ? bbytes : (m & 1) * (bbytes / 2));
    if (IS_A && kind == 0) {
      if (sg == 2) seen = tag32 = (__ldcg(p.g->epoch + m * 8 + n) + 1) << 5;
#pragma unroll 1
      for (int k = 0; k < 2; k++) {
#pragma unroll 1
        for (; inflight > (wide ? 3 : 4); inflight--) {
          mbar_wait(rb, rph);
          rb += 8;
          if (rb == rend) { rb -= 8 * NBAR; rph ^= 1; }
        }
        if (elect_one()) mbar_arrive(fb);
        inflight++;
        fb += 8;
        if (fb == fend) fb -= 8 * NBAR;
        pos += bbytes + 2 * UNIT;
        if (pos >= RING_UNITS * UNIT) pos -= RING_UNITS * UNIT;
      }
      continue;
    }
    const int mul = t == 6 ? 448 : t == 2 ? 128 : 64, count = sg == 1 ? 12 : 2 * nib(0x4871ull, kind);
    uint64_t order0 = sg == 1 ? 0xFEDCBA987654ull : kind == 3 ? 0x76543210u : order_x >> (8 * (kind & 1));
    uint32_t special = (s == 4 || s == 10) ? 0x10 : s == 9 ? 0xF : s == 0;
    if (IS_A) special |= (kind & 1 ? 0 : 3) | (count >= 4 ? 1u << (count - 4) : 0);
    if (s >= 9) pos = (s + 6) * UNIT;
    const CUtensorMap* map;
    int c0 = 0, c2 = 0, ev = 0;
    if (IS_A) {
      map = &p.t.xin + (t == 2 ? 2 : t == 6 ? 3 : sg >= 4);
      ev = 9 * layer + (t < 2 ? 0 : t == 2 ? 1 : t < 6 ? 4 : 5);
      if (elect_one()) asm volatile("prefetch.tensormap [%0];" ::"l"(map) : "memory");
    } else {
      weight_coords(p, t, n, map, c0, c2);
    }
#pragma unroll 1
    for (int add = 0; add < mul; add += 64) {
      uint64_t order = order0;
      const int need = kind == 3 ? ev : ev - 1 + (lane & 1), sh = kind == 3 ? 16 : 0;
      uint32_t ready = IS_A ? __ballot_sync(0xffffffffu, cur >= need) >> sh : 0;
#pragma unroll 1
      for (int k = 0; k < count; k++) {
        const int code = order & 15, kc = code * mul + add;
        order >>= 4;
        if ((special >> k) & 1) {
          const int lag = wide ? (s == 9 && k == 2 ? 2 : 3) : ((s == 4 || s == 10) && add == 0 && k < 4) ? 3 : 4;
#pragma unroll 1
          for (; inflight > lag; inflight--) {
            mbar_wait(rb, rph);
            rb += 8;
            if (rb == rend) { rb -= 8 * NBAR; rph ^= 1; }
          }
          inflight++;
          if (IS_A) {
            if (kind == 3 ? t == 2 && add + k == 64 : !(kind & 1) && k < 2) {
              if (t == 2) mbar_wait(sb + BAR_PUB + 8, layer);
              if (elect_one()) mbar_arrive(fb);
              goto next_stage;
            }
            if (k == count - 4 && sg >= 3) seen = ld_relaxed(word);
          }
        } else {
          mbar_wait(rb, rph);
          rb += 8;
          if (rb == rend) { rb -= 8 * NBAR; rph ^= 1; }
        }
        if (IS_A && !((ready >> code) & 1)) {
          cur = max(cur, (int)(seen - tag32));
          ready = __ballot_sync(0xffffffffu, cur >= need) >> sh;
          if (!((ready >> code) & 1)) {
            cur = (int)(poll_line(word, tag32 + need, 1u << (code + sh)) - tag32);
            ready = __ballot_sync(0xffffffffu, cur >= need) >> sh;
          }
          asm volatile("fence.acquire.gpu;" ::: "memory");
          fence_async_global();
          seen = ld_relaxed(word);
        }
        if (elect_one()) {
          if (!IS_A) tma_ld3_pair(base + pos, map, fb, c0, kc + 32 * (m & 1), c2);
          else tma_ld_act(base + pos, map, fb, kc, m);
          mbar_expect_tx(fb, IS_A ? 16384 : bbytes);
        }
      next_stage:
        fb += 8;
        if (fb == fend) fb -= 8 * NBAR;
        pos += bbytes + 2 * UNIT;
        if (pos >= RING_UNITS * UNIT) pos -= RING_UNITS * UNIT;
      }
      special = !IS_A ? 0 : t == 2 ? 1 : add == 128 ? 0x10 : 0;
      if (t == 2) order0 = others << 4 | n;
      if (IS_A && (t == 2 || add == 64 || add == 192)) ev++;
    }
  }
}

__device__ __forceinline__ void publisher(const Params& p, uint32_t sb, int m, int n) {
  {
    const int ts = PACE0 + PACE_M * m, tx = PACE0 + PACE_N * n;
#pragma unroll 1
    for (int k = 0; k < 2; k++) {
      __nanosleep(k == 0 ? min(ts, tx) : abs(ts - tx));
      if ((ts <= tx) == (k == 0)) {
        mbar_expect_tx(sb + BAR_CSLD, 24576);
        tma_ld3(sb + OFF_STG, &p.t.wqkv, sb + BAR_CSLD, 128 * n, 64 * m, 0);
        tma_ld3(sb + OFF_STG + 12288, &p.t.wqkv, sb + BAR_CSLD, 128 * n, 64 * m + 32, 0);
      } else {
#pragma unroll 1
        for (int h = 0; h < 2; h++) {
          const uint32_t xr = sb + BAR_XRDY + 8 * h;
          mbar_expect_tx(xr, 16384);
          tma_ld_act(sb + OFF_X + h * 16384, &p.t.xin, xr, 128 * n + 64 * h, m);
          asm volatile("mbarrier.arrive.shared::cta.b64 _, [%0], 3;" ::"r"(xr) : "memory");
        }
      }
    }
  }
  const uint32_t tag = __ldcg(p.g->epoch + m * 8 + n) + 1;
  uint32_t* word = p.g->flags + m * 32 + n;
  const int mn = m * 8 + n; (void)mn;
  st_relaxed(word, 32 * tag);
#pragma unroll 1
  for (int c = 0; c < 17; c++) {
    const int e = c >= 9 ? c - 9 : c;
    if (e == 2 || e == 7) {
      asm volatile("prefetch.tensormap [%0];" ::"l"(&p.t.out) : "memory");
      mbar_wait(sb + BAR_XRDY, e == 2);
      tma_st_act(&p.t.out, sb + OFF_X, 128 * n, m);
      bulk_commit();
      if (c == 16) break;
      mbar_wait(sb + BAR_XRDY + 8, e == 2);
      bulk_wait_all();
      mbar_arrive(sb + BAR_XGO);
      PROF_E(7 * (c >= 9) + (e < 4 ? 2 : 6), 11);
    } else {
      mbar_wait(sb + BAR_PUB + 8 * e, c >= 9);
    }
    asm volatile("fence.release.gpu;" ::: "memory");
    asm volatile("red.relaxed.gpu.global.add.u32 [%0], 1;" ::"l"(word) : "memory");
    PROF_E(7 * (c >= 9) + nib(0x665432210ull, e), (0x108 >> e) & 1 ? 14 : 12);
  }
  p.g->epoch[m * 8 + n] = tag;
  bulk_wait_read();
}

__device__ __forceinline__ void sum_rows(uint32_t buf, int iters, float (&a)[8], int lane) {
  uint32_t addr = buf + (lane >> 3) * 128 + (((lane & 7) ^ (lane >> 3)) << 4);
#pragma unroll 1
  for (int it = 0; it < iters; it++) {
    uint32_t u[2][4];
    lds_u4(addr, u[0][0], u[0][1], u[0][2], u[0][3]);
    lds_u4((addr ^ 64) + 512, u[1][0], u[1][1], u[1][2], u[1][3]);
    addr += 1024;
#pragma unroll
    for (int e = 0; e < 8; e++) { a[2 * (e & 3)] += bf_lo(u[e >> 2][e & 3]); a[2 * (e & 3) + 1] += bf_hi(u[e >> 2][e & 3]); }
  }
}
__device__ __forceinline__ void publish_sums(const float (&a)[8], uint4* dst, int lane, uint32_t tag) {
  const bool u8 = lane & 8, u16 = lane & 16;
  float h4[4], h2[2];
#pragma unroll
  for (int e = 0; e < 4; e++) h4[e] = (u8 ? a[4 + e] : a[e]) + __shfl_xor_sync(0xffffffffu, u8 ? a[e] : a[4 + e], 8);
#pragma unroll
  for (int e = 0; e < 2; e++) h2[e] = (u16 ? h4[2 + e] : h4[e]) + __shfl_xor_sync(0xffffffffu, u16 ? h4[e] : h4[2 + e], 16);
  st_msg(dst + (lane & 7) * 4 + (u8 ? 2 : 0) + (u16 ? 1 : 0), __float_as_uint(h2[0]), __float_as_uint(h2[1]), 0u, tag);
}

__device__ __forceinline__ void colsum_helper(const Params& p, uint32_t sb, int m, int n, int lane) {
  const uint32_t tag = __ldcg(p.g->epoch + m * 8 + n) + 1;
  const int mn = m * 8 + n; (void)mn;
#pragma unroll 1
  for (int k = lane; k < 288; k += 32) {
    const uint32_t bb = __ldg(reinterpret_cast<const uint32_t*>(k < 224 ? p.b1 + 448 * n : p.b2 + 128 * n - 448) + k);
    const float sc = k < 224 ? 0.5f : 1.f;
    sts_f2(sb + (k < 224 ? OFF_CSF + k * 16 + 8 : OFF_CSQ + 1536 + (k - 224) * 8), sc * bf_lo(bb), sc * bf_hi(bb));
  }
  __syncwarp();
  if (elect_one()) mbar_arrive(sb + BAR_BIAS);
  bar_sync(BAR_HLP, 160);
  {
    uint4* base = p.g->csp + n * 17 * 224 + 12 * m + min(lane & 15, 11);
    float s0 = 0.f, s1 = 0.f;
#pragma unroll 1
    for (int g = 0; g < 2; g++) {
      uint32_t x[4], y[4];
#pragma unroll 1
      for (int it = 0; it < MSG_SPINS; it++) {
        uint32_t bad = 0, z, tg;
        if (g == 0 || it > 0) __nanosleep(CS_NS);
#pragma unroll
        for (int k = 0; k < 4; k++) { ld_msg(base + (g * 8 + (lane >> 4) * 4 + k) * 224, x[k], y[k], z, tg); bad |= tg ^ tag; }
        if (__all_sync(0xffffffffu, bad == 0)) break;
      }
#pragma unroll
      for (int k = 0; k < 4; k++) { s0 += __uint_as_float(x[k]); s1 += __uint_as_float(y[k]); }
    }
    s0 += __shfl_xor_sync(0xffffffffu, s0, 16);
    s1 += __shfl_xor_sync(0xffffffffu, s1, 16);
    if (lane < 12) st_msg(base + 16 * 224, __float_as_uint(s0), __float_as_uint(s1), 0u, tag);
    PROF_E(-1, 3);
  }
  PROF_E(-1, 1);
#pragma unroll 1
  for (int c = 0; c < 7; c++) {
    float a[8] = {0.f, 0.f, 0.f, 0.f, 0.f, 0.f, 0.f, 0.f};
#pragma unroll 1
    for (int h = 0; h < 2; h++) {
      if (elect_one()) {
        mbar_expect_tx(sb + BAR_CSLD + 8, 4096);
        tma_ld2(sb + OFF_HLP, &p.t.w1c, sb + BAR_CSLD + 8, 448 * n + 64 * c, 64 * m + 32 * h);
        if (c < 6) asm volatile("cp.async.bulk.prefetch.tensor.2d.L2.global [%0, {%1, %2}];" ::"l"(&p.t.w1c), "r"(448 * n + 64 * c + 64), "r"(64 * m + 32 * h) : "memory");
      }
      mbar_wait(sb + BAR_CSLD + 8, h);
      sum_rows(sb + OFF_HLP, 4, a, lane);
      __syncwarp();
    }
    publish_sums(a, p.g->csp + ((8 + n) * 17 + m) * 224 + c * 32, lane, tag);
  }
  PROF_E(-1, 2);
  if (elect_one()) {
#pragma unroll 1
    for (int k = 0; k < 4; k++) {
      if (k < 3) {
        mbar_wait(sb + BAR_XGO, k & 1);
        __nanosleep(BDELAY);
      } else {
        mbar_wait(sb + BAR_XRDY + 8, 0);
      }
      tma_st_act(&p.t.out, sb + OFF_X + 16384, 128 * n + 64, m);
      bulk_commit();
      bulk_wait_all();
      asm volatile("mbarrier.arrive.shared::cta.b64 _, [%0], 4;" ::"r"(sb + BAR_PUB + (k & 1 ? 64 : 24)) : "memory");
    }
  }
}

__device__ __forceinline__ void poll_msgs2(const uint4* pa, const uint4* pb, float (&v)[4], uint32_t tag) {
#pragma unroll 1
  for (int it = 0; it < MSG_SPINS; it++) {
    uint32_t x[4], z, ta, tb;
    ld_msg(pa, x[0], x[1], z, ta);
    ld_msg(pb, x[2], x[3], z, tb);
#pragma unroll
    for (int e = 0; e < 4; e++) v[e] = __uint_as_float(x[e]);
    if (__all_sync(0xffffffffu, ta == tag && tb == tag)) break;
  }
}
__device__ __forceinline__ void colsum_total(const Params& p, const Ctx& cx, int mat, uint32_t tag) {
  uint4* base = p.g->csp + (mat * 8 + cx.n) * 17 * 224;
  const int per = 12 + 2 * mat, k = 2 * cx.w + (cx.lane >> 4), ia = per * cx.m + k, ib = per * cx.m + min(k + 8, per - 1);
  float v[4];
  poll_msgs2(base + (cx.lane & 15) * 224 + ia, base + (cx.lane & 15) * 224 + ib, v, tag);
#pragma unroll 1
  for (int d = 1; d < 16; d *= 2)
#pragma unroll
    for (int e = 0; e < 4; e++) v[e] += __shfl_xor_sync(0xffffffffu, v[e], d);
  const bool hi = cx.lane & 1;
  if ((cx.lane & 14) == 0) st_msg(base + 16 * 224 + (hi ? ib : ia), __float_as_uint(hi ? v[2] : v[0]), __float_as_uint(hi ? v[3] : v[1]), 0u, tag);
}
__device__ __forceinline__ void colsum_gather(const Params& p, const Ctx& cx, int mat, uint32_t tag) {
  const uint4* base = p.g->csp + ((mat * 8 + cx.n) * 17 + 16) * 224;
  const int ia = cx.w * 32 + cx.lane, ib = min(ia + 128, 191 + 32 * mat);
  float v[4];
  poll_msgs2(base + ia, base + ib, v, tag);
  const uint32_t tab = cx.sb + (mat ? OFF_CSF : OFF_CSQ);
  sts_f2(tab + (ia << (3 + mat)), v[0], v[1]);
  sts_f2(tab + (ib << (3 + mat)), v[2], v[3]);
}

#define ACC(q, j, e) acc[(q) & 1][4 * (j) + 2 * ((q) >> 1) + (e)]

constexpr uint32_t RING16 = RING_UNITS * (UNIT >> 4);
__device__ __forceinline__ bool tile_split(int i) { return (0xD98 >> i) & 1; }

__device__ __forceinline__ void write_run_desc(uint32_t sb, int i, int step) {
  const int layer = i >= 7, t = i - 7 * layer, part = tile_split(i) ? step : 2;
  const bool wide = tile_wide(t), own = t != 2 && t != 6 && part != 1 && i != 0, second = t == 1 || t == 4;
  const uint32_t z16 = (wide ? 5 : 4) * (UNIT >> 4), a_off = z16 - 1024 + (uint32_t)DESC_A - (uint32_t)DESC_B;
  const int gl = 16 * t + (part == 2 ? 0 : second ? 16 * part - 14 : 4 * part), g0 = layer * STAGES_PER_LAYER + gl;
  const uint32_t s16 = (sb & 0x3FFFF) >> 4, bfirst = (uint32_t)DESC_B + s16;
  const int nkb = t == 6 ? 56 : part == 0 ? 2 : 12 + 2 * part;
  const bool win1 = t == 1 && part != 0;
  const int run = win1 ? WIN1 + 1 : t == 2 ? WIN2 + 1 : nkb;
  const int rest = win1 ? 64 | (nkb - 1 - WIN1) : t == 2 ? 64 | (7 - WIN2) | (8 << 7) : 0;
  const uint32_t blo = bfirst + z16 * (wide ? (gl + (t == 5 ? 3 : 0)) & 3 : (gl + 3) % 5);
  const uint32_t alo = own ? (uint32_t)DESC_A + s16 + (OFF_X >> 4) : blo + a_off;
  const uint32_t aoff = own ? alo + 1024 - (blo == bfirst + RING16 - z16 ? bfirst : blo + z16) : a_off;
  const bool xwait = part == 0 && !second, keep = !(part == 0 || t == 5);
  sts_u4(sb + OFF_RUN + (2 * i + step) * 16, blo, alo, aoff,
         ((g0 / NBAR) & 1) | xwait << 1 | keep << 2 | 8 * (g0 % NBAR) | run << 6 | rest << 12);
}

template <int N>
__device__ __forceinline__ void mainloop(const Params& p, float (&acc)[2][96], uint32_t sb, int i, int step, int mn) {
  constexpr uint32_t Z16 = (2 + N / 64) * (UNIT >> 4);
  constexpr uint32_t A_OFF = Z16 - 1024 + (uint32_t)DESC_A - (uint32_t)DESC_B;
  const int wg = i & 1;
  const uint32_t s16 = (sb & 0x3FFFF) >> 4;
  const uint32_t blast = (uint32_t)DESC_B + s16 + RING16 - Z16, flast = sb + BAR_FULL + 8 * (NBAR - 1);
  uint32_t blo = (uint32_t)DESC_B + s16, alo = blo + A_OFF, aoff = A_OFF, misc = 16 << 6;
  if (N == 128 || i > 0) lds_u4(sb + OFF_RUN + (2 * i + step) * 16, blo, alo, aoff, misc);
  uint32_t keep = misc & 4;
  int run = (misc >> 6) & 63, rest = misc >> 12;
  uint32_t fb = sb + BAR_FULL + (misc & 0x38), ph = misc & 1;
  uint32_t prev = sb + BAR_DUMMY - 8 * NBAR;
  const uint32_t lane_id = __popc(__ballot_sync(0xffffffffu, true) & lanemask_lt()), rel = pair_offset(sb, lane_id & 1) + 8 * NBAR;
  pin_regs<N / 2>(acc);
  if (N == 128 || i > 0) bar_sync(BAR_ORDER + wg, 256);
  else bar_sync(BAR_INIT0, 160);
  if (N == 192 && i == 0 && threadIdx.x == 0) PROF_U(8);
  mbar_wait(fb, ph);
  if (N == 192 && i == 0 && threadIdx.x == 0) PROF_U(9);
  if (N == 192 && i == 0) cluster_wait();
  if (misc & 2) mbar_wait(sb + BAR_XGO, N == 192);
  if (step == 0 || !tile_split(i)) PROF_T(4 + i * 4);
#pragma unroll 1
  while (true) {
    const uint64_t da = (DESC_A & ~0xffffffffull) | alo, db = (DESC_B & ~0xffffffffull) | blo;
    asm volatile("wgmma.fence.sync.aligned;" ::: "memory");
    wgmma_ss<N>(acc[0], da, db, keep);
    wgmma_ss<N>(acc[1], da + 64, db, keep);
    keep = 4;
    wgmma_ss<N>(acc[0], da + 2, db + 128);
    wgmma_ss<N>(acc[1], da + 66, db + 128);
    asm volatile("wgmma.commit_group.sync.aligned;" ::: "memory");
    asm volatile("wgmma.wait_group.sync.aligned 1;" ::: "memory");
    PROF_S(jj++);
    if (lane_id < 2) mbar_arrive_cluster(prev + rel);
    prev = fb;
    if (fb == flast) { fb -= 8 * NBAR; ph++; }
    fb += 8;
    if (blo == blast) blo -= RING16;
    blo += Z16;
    alo = blo + aoff;
    aoff = A_OFF;
    run--;
    const bool ready = mbar_test(fb, ph) && run != 0;
    asm volatile("wgmma.fence.sync.aligned;" ::: "memory");
    wgmma_ss<N>(acc[0], da + 4, db + 4 * N);
    wgmma_ss<N>(acc[1], da + 68, db + 4 * N);
    wgmma_ss<N>(acc[0], da + 6, db + 4 * N + 128);
    wgmma_ss<N>(acc[1], da + 70, db + 4 * N + 128);
    asm volatile("wgmma.commit_group.sync.aligned;" ::: "memory");
    if (!ready) {
      bool window = false;
      if (run == 0) {
        if (rest == 0) break;
        window = rest & 64;
        if (window) bar_arrive(BAR_GO, 256);
        else alo = (uint32_t)DESC_A + s16 + (OFF_STG >> 4);
        run = rest & 63;
        rest >>= 7;
      }
      mbar_wait(fb, ph);
      if (window) bar_sync(BAR_DONE, 256);
    }
  }
  if (i < 13 && !(LATE_O && N == 192 && (misc >> 12))) bar_arrive(BAR_ORDER + (wg ^ 1), 256);
  if (N == 128 && ((0x2244 >> i) & 1)) {
    const Ctx cx = make_ctx(sb, mn);
    const uint32_t xrow = cx.sb + OFF_X + cx.w * 4096 + cx.lane * 128 + ((cx.lane & 7) << 4);
    const bool leader = elect_one();
    asm volatile("wgmma.wait_group.sync.aligned 0;" ::: "memory");
    pin_regs<64>(acc);
    PROF_T(5 + i * 4);
    PROF_E(i, 0);
#pragma unroll
    for (int h = 0; h < 2; h++) {
      if (h == 1 && p.zero != 0) break;
#pragma unroll
      for (int j = 8 * h; j < 8 * h + 8; j++)
        stsm4((xrow ^ ((j & 7) << 4)) + h * 16384, pack_bf16(ACC(0, j, 0), ACC(0, j, 1)), pack_bf16(ACC(1, j, 0), ACC(1, j, 1)),
              pack_bf16(ACC(2, j, 0), ACC(2, j, 1)), pack_bf16(ACC(3, j, 0), ACC(3, j, 1)));
      fence_async_smem();
      __syncwarp();
      if (leader) mbar_arrive(sb + BAR_XRDY + 8 * h);
      if (h == 0 && lane_id < 2) mbar_arrive_cluster(prev + rel);
    }
    PROF_E(i, 4);
    return;
  }
  asm volatile("wgmma.wait_group.sync.aligned 0;" ::: "memory");
  pin_regs<N / 2>(acc);
  if (lane_id < 2) mbar_arrive_cluster(prev + rel);
  PROF_T(5 + i * 4);
  PROF_E(i, 0);
}

__device__ __forceinline__ void write_partial_stats(const Params& p, const Ctx& c, int ln, uint32_t tag) {
  const uint32_t xrow = c.sb + OFF_X + c.w * 4096 + c.lane * 128;
  float s = 0.f, q = 0.f, s1 = 0.f, q1 = 0.f;
#pragma unroll 4
  for (int j = 0; j < 16; j++) {
    uint32_t u[4];
    lds_u4(xrow + (j >> 3) * 16384 + (((j & 7) ^ (c.lane & 7)) << 4), u[0], u[1], u[2], u[3]);
#pragma unroll
    for (int e = 0; e < 4; e++) {
      const float a = bf_lo(u[e]), d = bf_hi(u[e]);
      s += a; q = fmaf(a, a, q);
      s1 += d; q1 = fmaf(d, d, q1);
    }
  }
  s += s1;
  q += q1;
  st_msg(p.g->stats + (ln * 8 + c.n) * SEQ + 128 * c.m + 32 * c.w + c.lane, __float_as_uint(s),
         __float_as_uint(fmaxf(q - s * s * (1.f / 128.f), 0.f)), 0u, tag);
}

__device__ __forceinline__ void finish_row_stats(const Params& p, const Ctx& c, int ln, uint32_t tag) {
  const uint4* src = p.g->stats + ln * 8 * SEQ + 128 * c.m + 32 * c.w + c.lane;
  uint32_t ps[8], pm[8];
#pragma unroll 1
  for (int it = 0; it < MSG_SPINS; it++) {
    uint32_t bad = 0, u, tg;
    if (ln > 1 || it > 0) __nanosleep(STAT_NS);
#pragma unroll
    for (int k = 0; k < 8; k++) { ld_msg(src + k * SEQ, ps[k], pm[k], u, tg); bad |= tg ^ tag; }
    if (__all_sync(0xffffffffu, bad == 0)) break;
  }
  float s = 0.f, m2 = 0.f;
#pragma unroll
  for (int k = 0; k < 8; k++) s += __uint_as_float(ps[k]);
  const float mean = s * (1.f / DM);
#pragma unroll
  for (int k = 0; k < 8; k++) {
    const float d = __uint_as_float(ps[k]) * (1.f / 128.f) - mean;
    m2 += fmaf(128.f * d, d, __uint_as_float(pm[k]));
  }
  sts_f2(c.sb + OFF_ROW + (32 * c.w + c.lane) * 8, rsqrtf(m2 * (1.f / DM) + 1e-5f), mean);
  __syncwarp();
}

__device__ __forceinline__ void attn_scores(const uint32_t* qa, const uint32_t* qb, const uint32_t* kp, const uint32_t* ka,
                                            const uint32_t* kb, float (&l)[4], const float4& zero, const bool (&early)[2]) {
  float s[3][4];
#pragma unroll
  for (int x = 0; x < 3; x++) {
    const uint32_t* kk = x == 0 ? kp : x == 1 ? ka : kb;
    asm volatile("mma.sync.aligned.m16n8k16.row.col.f32.bf16.bf16.f32 {%0,%1,%2,%3}, {%4,%5,%6,%7}, {%8,%9}, {%10,%11,%12,%13};"
                 : "=f"(s[x][0]), "=f"(s[x][1]), "=f"(s[x][2]), "=f"(s[x][3])
                 : "r"(qa[0]), "r"(qb[0]), "r"(qa[1]), "r"(qb[1]), "r"(kk[0]), "r"(kk[1]), "f"(zero.x), "f"(zero.y),
                   "f"(zero.z), "f"(zero.w));
  }
#pragma unroll
  for (int x = 0; x < 3; x++) {
    const uint32_t* kk = x == 0 ? kp : x == 1 ? ka : kb;
    mma16816(s[x], qa[2], qb[2], qa[3], qb[3], kk[2], kk[3]);
  }
#pragma unroll
  for (int e = 0; e < 2; e++) {
    l[e] = early[e] ? s[0][e] : s[1][e];
    l[2 + e] = early[e] ? s[1][2 + e] : s[2][2 + e];
  }
}

__device__ __forceinline__ void attn_mix(const float (&l)[4], const float (&sc)[4], const float (&off)[4], const float (&rk)[4],
                                         const uint32_t* vp, const uint32_t* va, const uint32_t* vb, float (&o)[4][4],
                                         float (&sum)[2], uint32_t mask, uint32_t zero) {
  float x[4];
#pragma unroll
  for (int e = 0; e < 4; e++) x[e] = fmaf(l[e], sc[e], off[e]);
  const float ml = quad_max(fmaxf(x[0], x[1])), mh = quad_max(fmaxf(x[2], x[3]));
  x[0] = ex2(x[0] - ml); x[1] = ex2(x[1] - ml);
  x[2] = ex2(x[2] - mh); x[3] = ex2(x[3] - mh);
  sum[0] = rcp_hw(quad_sum(x[0] + x[1]));
  sum[1] = rcp_hw(quad_sum(x[2] + x[3]));
  const uint32_t pl = pack_bf16(x[0] * rk[0], x[1] * rk[1]), ph = pack_bf16(x[2] * rk[2], x[3] * rk[3]);
  const uint32_t a0 = pl & ~mask, a1 = ph & mask, a2 = pl & zero, a3 = ph & ~mask, c0 = pl & mask, c1 = ph & zero;
#pragma unroll
  for (int jn = 0; jn < 4; jn++) {
    o[jn][0] = o[jn][1] = o[jn][2] = o[jn][3] = 0.f;
    mma16816(o[jn], a0, a1, a2, a3, va[jn], vb[jn]);
  }
#pragma unroll
  for (int jn = 0; jn < 4; jn++) mma1688(o[jn], c0, c1, vp[jn]);
}

__device__ __forceinline__ void gelu_epilogue(const Params& p, float (&acc)[2][96], const Ctx& cx, int t) {
  UNPACK_CTX(cx);
  (void)wg;
  float rs[4], rm[4];
#pragma unroll
  for (int q = 0; q < 4; q++) {
    const float2 v = lds_f2(sb + OFF_ROW + (32 * w + 8 * q + (lane >> 2)) * 8);
    rs[q] = 0.5f * v.x;
    rm[q] = -rs[q] * v.y;
  }
  const int col0 = 128 * (t - 3);
  const uint32_t stg = sb + OFF_STG + w * 4096;
  const uint32_t ctab = sb + OFF_CSF + (col0 / 2 + (lane & 3)) * 16, srow = stg + lane * 128 + ((lane & 7) << 4);
  __nanosleep((t == 5 ? STAG5 : t == 4 ? STAG4 : STAG3) * w);
  float4 nb = lds_f4(ctab);
#pragma unroll
  for (int c = 0; c < 3; c++) {
    if (c == 2 && t != 5) break;
    uint32_t hp[8][4];
#pragma unroll
    for (int j = 0; j < 8; j++) {
      const float4 cb = nb;
      if (8 * c + j < 23) nb = lds_f4(ctab + (8 * c + j + 1) * 64);
#pragma unroll
      for (int q = 0; q < 4; q++) {
        float y[2];
        const int k = 4 * j + q - GELU_DEP;
        const float rmq = k >= 0 ? chain(rm[q], hp[k >> 2][k & 3], p.zero) : rm[q];
#pragma unroll
        for (int e = 0; e < 2; e++) {
          const float z = fmaf(ACC(q, 8 * c + j, e), rs[q], fmaf(rmq, e ? cb.y : cb.x, e ? cb.w : cb.z));
          const float u = z * fmaf(z * z, 8.f * 0.7978845608028654f * 0.044715f, 2.f * 0.7978845608028654f);
          y[e] = fmaf(z, tanh_hw(u), z);
        }
        hp[j][q] = pack_bf16(y[0], y[1]);
      }
      if (j == STG_WAIT && c > 0) {
        if (lane == 0) bulk_wait_read();
        __syncwarp();
      }
      if (c == 0 || j > STG_WAIT) {
        stsm4(srow ^ (j << 4), hp[j][0], hp[j][1], hp[j][2], hp[j][3]);
      } else if (j == STG_WAIT) {
#pragma unroll
        for (int jj = 0; jj <= STG_WAIT; jj++) stsm4(srow ^ (jj << 4), hp[jj][0], hp[jj][1], hp[jj][2], hp[jj][3]);
      }
    }
    fence_async_smem();
    __syncwarp();
    if (lane == 0) {
      tma_st2(&p.t.h_st, stg, 448 * n + col0 + 64 * c, 128 * m + 32 * w);
      bulk_commit();
    }
  }
#pragma unroll
  for (int r = 0; r < 16; r++) acc[0][r] = acc[1][r] = 0.f;
}

__device__ __forceinline__ void attn_epilogue(const Params& p, float (&acc)[2][96], const Ctx& cx, int layer, int t, uint32_t tag) {
  UNPACK_CTX(cx);
  const uint32_t ktab = sb + OFF_ROW + (32 * w + 2 * (lane & 3)) * 8, exc = sb + OFF_STG + (w & 1) * 2048 + lane * 16;
  uint4* const halo = p.g->halo + (((layer * 2 + t) * 16 + m) * 8 + n) * 384 + (w & 1) * 192;
  const int mn = m * 8 + n; (void)mn;
  uint32_t Q[4][8], K[4][8], V[4][8], E[18], P[18];
  float kr[5][2], qr[4];
  {
    const float4 r = lds_f4(ktab + 192);
    E[16] = __float_as_uint(kr[4][0] = r.x);
    E[17] = __float_as_uint(kr[4][1] = r.z);
  }
#pragma unroll
  for (int j = 0; j < 8; j++) {
    E[j] = K[3][j] = pack_bf16(ACC(3, 8 + j, 0), ACC(3, 8 + j, 1));
    E[8 + j] = V[3][j] = movtrans(pack_bf16(ACC(3, 16 + j, 0), ACC(3, 16 + j, 1)));
  }
  if (w < 2) {
#pragma unroll
    for (int k = 0; k < 4; k++) sts_u4(exc + k * 512, E[4 * k], E[4 * k + 1], E[4 * k + 2], E[4 * k + 3]);
  } else {
#pragma unroll
    for (int k = 0; k < 6; k++) st_msg(halo + k * 32 + lane, E[3 * k], E[3 * k + 1], E[3 * k + 2], tag);
  }
  bar_arrive(BAR_PAIR + w, 64);
  if (LATE_O && t == 1) bar_arrive(BAR_ORDER + (wg ^ 1), 256);
  PROF_E(7 * layer + t, 1);
#pragma unroll
  for (int q = 0; q < 4; q++) {
    qr[q] = lds_f(sb + OFF_ROW + (32 * w + 8 * q + (lane >> 2)) * 8) * (0.17677669529663687f * 1.4426950408889634f);
#pragma unroll
    for (int j = 0; j < 8; j++) Q[q][j] = pack_bf16(ACC(q, j, 0), ACC(q, j, 1));
    if (q < 3) {
      const float4 r = lds_f4(ktab + 64 * q);
      kr[1 + q][0] = r.x;
      kr[1 + q][1] = r.z;
#pragma unroll
      for (int j = 0; j < 8; j++) {
        K[q][j] = pack_bf16(ACC(q, 8 + j, 0), ACC(q, 8 + j, 1));
        V[q][j] = movtrans(pack_bf16(ACC(q, 16 + j, 0), ACC(q, 16 + j, 1)));
      }
    }
  }
  PROF_E(7 * layer + t, 6);
  bar_sync(BAR_PAIR + (w ^ 2), 64);
  if (w >= 2 || m == 0) {
#pragma unroll
    for (int k = 0; k < 4; k++) lds_u4(exc + k * 512, P[4 * k], P[4 * k + 1], P[4 * k + 2], P[4 * k + 3]);
    const float4 r = lds_f4(ktab - (w >> 1) * 320);
    P[16] = __float_as_uint(r.x);
    P[17] = __float_as_uint(r.z);
  } else {
    if (HALO_NS) __nanosleep(HALO_NS);
#pragma unroll 1
    for (int it = 0; it < MSG_SPINS; it++) {
      uint32_t tg, bad = 0;
      if (it > 0) poll_line(reinterpret_cast<const uint32_t*>(halo - 8 * 384 + 191) + 3, tag, 1u);
#pragma unroll
      for (int k = 0; k < 6; k++) {
        ld_msg(halo - 8 * 384 + k * 32 + lane, P[3 * k], P[3 * k + 1], P[3 * k + 2], tg);
        bad |= tg ^ tag;
      }
      if (__all_sync(0xffffffffu, bad == 0)) break;
    }
  }
  kr[0][0] = __uint_as_float(P[16]);
  kr[0][1] = __uint_as_float(P[17]);
  const bool early[2] = {2 * (lane & 3) > (lane >> 2), 2 * (lane & 3) + 1 > (lane >> 2)};
  const uint32_t mask = (early[0] ? 0xffffu : 0u) | (early[1] ? 0xffff0000u : 0u);
  float rk[2][4], sc[2][4], off[2][4];
#pragma unroll
  for (int g = 0; g < 2; g++) {
#pragma unroll
    for (int e = 0; e < 4; e++) {
      const int q = 2 * g + (e >> 1);
      const bool masked = q == 0 && m == 0 && w < 2 && early[e & 1];
      rk[g][e] = early[e & 1] ? kr[q][e & 1] : kr[q + 1][e & 1];
      sc[g][e] = masked ? 0.f : rk[g][e] * qr[q];
      off[g][e] = masked ? -1e30f : 0.f;
    }
  }
  if (w == 0 && elect_one()) asm volatile("prefetch.tensormap [%0];" ::"l"(&p.t.att_st) : "memory");
  PROF_E(7 * layer + t, 2);
  bar_sync(BAR_GO, 256);
  const float4 zero = lds_f4(sb + OFF_ZERO);
  float l[2][2][4], o[2][2][4][4], sum[2][2][2];
#pragma unroll
  for (int h = 0; h < 2; h++) {
    if (h == 1) {
      Q[2][4] |= __float_as_uint(l[1][0][0]) & p.zero;
      Q[0][4] |= __float_as_uint(l[0][0][0]) & p.zero;
    }
    attn_scores(&Q[2][4 * h], &Q[3][4 * h], &K[1][4 * h], &K[2][4 * h], &K[3][4 * h], l[1][h], zero, early);
    attn_scores(&Q[0][4 * h], &Q[1][4 * h], &P[4 * h], &K[0][4 * h], &K[1][4 * h], l[0][h], zero, early);
  }
  const uint32_t stg = sb + OFF_STG + w * 4096, srow = stg + lane * 128 + ((lane & 7) << 4);
#pragma unroll
  for (int h = 0; h < 2; h++) {
    attn_mix(l[1][h], sc[1], off[1], rk[1], &V[1][4 * h], &V[2][4 * h], &V[3][4 * h], o[1][h], sum[1][h], mask, p.zero);
    attn_mix(l[0][h], sc[0], off[0], rk[0], &P[8 + 4 * h], &V[0][4 * h], &V[1][4 * h], o[0][h], sum[0][h], mask, p.zero);
#pragma unroll
    for (int j = 0; j < 4; j++) {
      const float(&a)[4] = o[0][h][j];
      const float(&c)[4] = o[1][h][j];
      stsm4(srow ^ ((4 * h + j) << 4), pack_bf16(a[0] * sum[0][h][0], a[1] * sum[0][h][0]), pack_bf16(a[2] * sum[0][h][1], a[3] * sum[0][h][1]),
            pack_bf16(c[0] * sum[1][h][0], c[1] * sum[1][h][0]), pack_bf16(c[2] * sum[1][h][1], c[3] * sum[1][h][1]));
    }
  }
  bar_arrive(BAR_DONE, 256);
  fence_async_smem();
  __syncwarp();
  if (lane == 0) {
    tma_st2(&p.t.att_st, stg, 128 * n + 64 * t, 128 * m + 32 * w);
    bulk_commit();
  }
}

template <bool PACED>
__device__ __forceinline__ void rank1_update(const Params& p, float (&acc)[2][96], const Ctx& cx, int t) {
  float nm[4];
#pragma unroll
  for (int q = 0; q < 4; q++) nm[q] = t == 6 ? 1.f : -lds_f(cx.sb + OFF_ROW + (32 * cx.w + 8 * q + (cx.lane >> 2)) * 8 + 4);
  const uint32_t ctab = cx.sb + OFF_CSQ + ((t & 3) * 192 + 2 * (cx.lane & 3)) * 4;
#pragma unroll
  for (int j = 0; j < 24; j++) {
    const float2 cs = lds_f2(ctab + j * 32);
#pragma unroll
    for (int q = 0; q < 4; q++) {
      const int k = 4 * j + q - 1;
      const float nq = PACED && k >= 0 ? chain(nm[q], __float_as_uint(ACC(k & 3, k >> 2, 1)), p.zero) : nm[q];
      ACC(q, j, 0) = fmaf(nq, cs.x, ACC(q, j, 0));
      ACC(q, j, 1) = fmaf(nq, cs.y, ACC(q, j, 1));
    }
  }
}

__device__ __forceinline__ void finish_stores(uint32_t sb, int i) {
  const int t = i >= 7 ? i - 7 : i;
  if ((threadIdx.x & 31) == 0) {
    bulk_wait_all();
    mbar_arrive(sb + BAR_PUB + 8 * (t < 2 ? t : t + 1));
  }
  __syncwarp();
  if (i < 12) bar_arrive(BAR_GUARD + ((i & 1) ^ 1), 256);
}

__device__ __forceinline__ bool consumer_tile(const Params& p, float (&acc)[2][96], uint32_t sb0, int i, int mn) {
  const int layer = i >= 7, t = i - 7 * layer, wg = i & 1;
  const bool resid = t == 2 || t == 6;
  {
    if (resid) {
      const Ctx cx = make_ctx(sb0, mn);
      const uint32_t xrow = cx.sb + OFF_X + cx.w * 4096 + cx.lane * 128;
      const uint32_t sel_lo = 0x1044u | p.zero, sel_hi = 0x3244u | p.zero;
#pragma unroll
      for (int j = 0; j < 16; j++) {
        uint32_t r[4];
        ldsm4(xrow + (j >> 3) * 16384 + (((j & 7) ^ (cx.lane & 7)) << 4), r[0], r[1], r[2], r[3]);
#pragma unroll
        for (int q = 0; q < 4; q++) {
          ACC(q, j, 0) = prmt_f(r[q], sel_lo);
          ACC(q, j, 1) = prmt_f(r[q], sel_hi);
        }
      }
    }
    if (t >= 5 || i == 7) finish_stores(sb0, i - 2);
#pragma unroll 1
    for (int step = !tile_split(i);; step++) {
      if (step == 1 && (t == 1 || t == 4)) {
        const Ctx cx = make_ctx(sb0, mn);
        if (i == 1) {
          const uint32_t epoch = __ldcg(p.g->epoch + (mn & 127));
          cluster_wait();
          asm volatile("st.shared.u32 [%0], %1;" ::"r"(sb0 + OFF_TAG), "r"(epoch + 1) : "memory");
        }
        const uint32_t tag = lds_u(cx.sb + OFF_TAG);
        const int ln = (i + 1) >> 2;
#pragma unroll 1
        for (int r = 0; r < 2; r++) {
          if (i == 1) {
            if (cx.w < 3) {
              float a[8] = {0.f, 0.f, 0.f, 0.f, 0.f, 0.f, 0.f, 0.f};
              mbar_wait(sb0 + BAR_CSLD, r);
#pragma unroll 1
              for (int h = 0; h < 2; h++) sum_rows(cx.sb + OFF_STG + h * 12288 + cx.w * 4096, 4, a, cx.lane);
              publish_sums(a, p.g->csp + (cx.n * 17 + cx.m) * 224 + (3 * r + cx.w) * 32, cx.lane, tag);
            }
            PROF_E(-1, 5 + r);
          }
          if (r == 1) break;
          if (i == 1) {
            bar_sync(BAR_WG + 1, 128);
            if (cx.w == 3 && elect_one()) {
              mbar_expect_tx(sb0 + BAR_CSLD, 24576);
              tma_ld3(sb0 + OFF_STG, &p.t.wqkv, sb0 + BAR_CSLD, 128 * cx.n + 64, 64 * cx.m, 0);
              tma_ld3(sb0 + OFF_STG + 12288, &p.t.wqkv, sb0 + BAR_CSLD, 128 * cx.n + 64, 64 * cx.m + 32, 0);
            }
            mbar_wait(sb0 + BAR_XRDY, 0);
            mbar_wait(sb0 + BAR_XRDY + 8, 0);
          }
          write_partial_stats(p, cx, ln, tag);
          PROF_E(i - 2, 8);
        }
        if (i == 1) {
          bar_arrive(BAR_HLP, 160);
          bar_sync(BAR_INIT, 160);
        }
        if (i == 4) colsum_total(p, cx, 1, tag);
        PROF_E(i - 2, 9);
        if (i != 1) bar_sync(BAR_GUARD + wg, 256);
        finish_row_stats(p, cx, ln, tag);
        PROF_E(i - 2, 10);
        if (i == 4) {
          colsum_gather(p, cx, 1, tag);
          mbar_wait(sb0 + BAR_BIAS, 0);
        }
        PROF_E(i - 2, 15);
        bar_arrive(BAR_GUARD + (wg ^ 1), 256);
      }
      if (step == 2 && !resid) bar_sync(BAR_GUARD + wg, 256);
      if (step == 2 && i == 0) {
        colsum_gather(p, make_ctx(sb0, mn), 0, lds_u(sb0 + OFF_TAG));
        bar_sync(BAR_WG, 128);
      }
      if (i == 1) {
        if (step == 2) rank1_update<false>(p, acc, make_ctx(sb0, mn), t);
      } else if (t + step == 2 || t == 6) {
        rank1_update<true>(p, acc, make_ctx(sb0, mn), t);
      }
      if (step == 2) break;
      if (tile_wide(t)) {
        mainloop<192>(p, acc, sb0, i, step, mn);
      } else {
        mainloop<128>(p, acc, sb0, i, step, mn);
        if (resid) return false;
      }
    }
    if (t < 2) return true;
    gelu_epilogue(p, acc, make_ctx(sb0, mn), t);
    PROF_E(i, 4);
    return false;
  }
}

template <bool BY_SMID>
__global__ void __cluster_dims__(2, 1, 1) __launch_bounds__(384, 1)
fused_layers_kernel(const Scalars scalars, const __grid_constant__ Maps maps) {
  if (threadIdx.x == 288 || threadIdx.x == 320)
    asm volatile("prefetch.tensormap [%0];" ::"l"(threadIdx.x == 288 ? &maps.xin : &maps.wqkv) : "memory");
  const Params p{scalars, maps};
  extern __shared__ __align__(1024) uint8_t smem_raw[];
  const uint32_t sb = uniform((uint32_t)__cvta_generic_to_shared(smem_raw));
  const int tid = threadIdx.x, lane = tid & 31, warp = uniform(tid >> 5), wg = warp >> 2, w = warp & 3;

  int mn;
  {
    int id = blockIdx.x;
    if (BY_SMID) asm volatile("mov.u32 %0, %%smid;" : "=r"(id));
    else if (id >= 120) id += 4;
    const int c = id >> 1;
    int g, j;
    if (c < 32) { g = c & 7; j = c >> 3; }
    else if (c < 60) { g = 1 + (c - 32) % 7; j = 4 + (c - 32) / 7; }
    else { g = 0; j = c - 58; }
    const int r = blockIdx.x & 1;
    mn = (g * 2 + r) * 8 + j;
    if (c == 60 || c == 61) {
      if (tid < 32) {
        const uint32_t tag = __ldcg(p.g->epoch + NCTA + (id & 3)) + 1;
#pragma unroll 1
        for (int mm = 0; mm < 16; mm++) poll_line(p.g->flags + mm * 32 + (lane & 7), 32 * tag, 0xffu);
        if (tid == 0) p.g->epoch[NCTA + (id & 3)] = tag;
      }
      return;
    }
  }
  const int m = mn >> 3, n = mn & 7;
  if (tid == 256) PROF_U(1);
  if (wg < 2) {
    cluster_arrive();
    asm volatile("setmaxnreg.inc.sync.aligned.u32 232;");
    const int id = mn | (warp << 7);
#pragma unroll 1
    for (int i = wg;; i += 2) {
      float acc[2][96];
#pragma unroll
      for (int r = 0; r < 96; r++) acc[0][r] = acc[1][r] = 0.f;
      pin_regs<96>(acc);
#pragma unroll 1
      while (!consumer_tile(p, acc, sb, i, id)) {
        PROF_T(6 + i * 4);
        i += 2;
        if (i >= 14) goto all_done;
      }
      attn_epilogue(p, acc, make_ctx(sb, id), i >= 7, i >= 7 ? i - 7 : i, lds_u(sb + OFF_TAG));
      PROF_E(i, 4);
      finish_stores(sb, i);
      PROF_E(i, 5);
      PROF_T(6 + i * 4);
    }
  all_done:
    if (wg == 0) {
      finish_stores(sb, 12);
    } else {
      cluster_arrive();
      cluster_wait();
    }
  } else {
    asm volatile("setmaxnreg.dec.sync.aligned.u32 40;");
    if (w != 0) {
      if (w == 1 && elect_one()) {
        mbar_init(sb + BAR_FULL + 32, 2);
#pragma unroll
        for (int k = 0; k < NBAR; k++) mbar_init(sb + BAR_EMPTY + 8 * k, 8);
#pragma unroll
        for (int k = 0; k < 3; k++) mbar_init(sb + BAR_XRDY + 8 * k, 4);
#pragma unroll
        for (int k = 0; k < 9; k++) mbar_init(sb + BAR_PUB + 8 * k, 4);
#pragma unroll
        for (int k = 0; k < 4; k++) mbar_init(sb + BAR_CSLD + 8 * k, 1);
        sts_f2(sb + OFF_ZERO, 0.f, 0.f);
        sts_f2(sb + OFF_ZERO + 8, 0.f, 0.f);
        asm volatile("fence.mbarrier_init.release.cluster;" ::: "memory");
      }
      __syncwarp();
      cluster_arrive();
      if (w == 2) {
        if (lane < 28) write_run_desc(sb, lane >> 1, lane & 1);
        bar_arrive(BAR_INIT, 160);
      }
      cluster_wait();
      if (w == 1) producer<true>(p, sb, m, n, lane);
      else if (w == 3) colsum_helper(p, sb, m, n, lane);
      else if (elect_one()) publisher(p, sb, m, n);
    } else {
      const bool leader = elect_one();
      if (leader) {
#pragma unroll
        for (int k = 0; k < 4; k++) mbar_init(sb + BAR_FULL + 8 * k, 2);
        asm volatile("fence.mbarrier_init.release.cluster;" ::: "memory");
        PROF_U(4);
      }
      __syncwarp();
      bar_arrive(BAR_INIT0, 160);
      cluster_arrive();
      if (leader) {
#pragma unroll 1
        for (int k = 0; k < 4; k++) {
          const uint32_t fb = sb + BAR_FULL + 8 * k;
          mbar_expect_tx(fb, 16384);
          tma_ld_act(sb + (5 * k + 3) * UNIT, &p.t.xin, fb, 64 * k, m);
          mbar_expect_tx(fb, 3 * UNIT);
          tma_ld3(sb + 5 * k * UNIT, &p.t.wqkv, fb, 128 * n, 64 * k, 0);
          tma_ld3(sb + 5 * k * UNIT + 12288, &p.t.wqkv, fb, 128 * n, 64 * k + 32, 0);
        }
        PROF_U(5);
      }
      __syncwarp();
      cluster_wait();
      producer<false>(p, sb, m, n, lane);
    }
  }
}

typedef CUresult (*EncodeFn)(CUtensorMap*, CUtensorMapDataType, cuuint32_t, void*, const cuuint64_t*, const cuuint64_t*,
                             const cuuint32_t*, const cuuint32_t*, CUtensorMapInterleave, CUtensorMapSwizzle,
                             CUtensorMapL2promotion, CUtensorMapFloatOOBfill);

#define PROMO2 CU_TENSOR_MAP_L2_PROMOTION_L2_128B
#define PROMO3 CU_TENSOR_MAP_L2_PROMOTION_L2_128B
void make_2d(EncodeFn enc, CUtensorMap* m, const void* ptr, uint64_t cols, uint64_t rows, uint32_t box_rows) {
  cuuint64_t d[2] = {cols, rows}, st[1] = {cols * 2};
  cuuint32_t b[2] = {64, box_rows}, e[2] = {1, 1};
  enc(m, CU_TENSOR_MAP_DATA_TYPE_BFLOAT16, 2, const_cast<void*>(ptr), d, st, b, e, CU_TENSOR_MAP_INTERLEAVE_NONE,
      CU_TENSOR_MAP_SWIZZLE_128B, PROMO2, CU_TENSOR_MAP_FLOAT_OOB_FILL_NONE);
}
void make_act(EncodeFn enc, CUtensorMap* m, const void* ptr, uint64_t cols, bool split) {
  const uint64_t row = cols * 2;
  cuuint64_t d[4] = {cols, 32, 2, SEQ / 64}, st[3] = {split ? 2 * row : row, split ? row : 32 * row, 64 * row};
  cuuint32_t b[4] = {64, 32, 2, 2}, e[4] = {1, 1, 1, 1};
  enc(m, CU_TENSOR_MAP_DATA_TYPE_BFLOAT16, 4, const_cast<void*>(ptr), d, st, b, e, CU_TENSOR_MAP_INTERLEAVE_NONE,
      CU_TENSOR_MAP_SWIZZLE_128B, PROMO2, CU_TENSOR_MAP_FLOAT_OOB_FILL_NONE);
}
void make_3d(EncodeFn enc, CUtensorMap* m, const void* ptr, uint64_t d0, uint64_t rows, uint64_t d2, uint64_t row_bytes,
             uint64_t chunk_bytes, uint32_t box_chunks) {
  cuuint64_t d[3] = {d0, rows, d2}, st[2] = {row_bytes, chunk_bytes};
  cuuint32_t b[3] = {64, 32, box_chunks}, e[3] = {1, 1, 1};
  enc(m, CU_TENSOR_MAP_DATA_TYPE_BFLOAT16, 3, const_cast<void*>(ptr), d, st, b, e, CU_TENSOR_MAP_INTERLEAVE_NONE,
      CU_TENSOR_MAP_SWIZZLE_128B, PROMO3, CU_TENSOR_MAP_FLOAT_OOB_FILL_NONE);
}

}

extern "C" void kernel_launch(void* const* d_in, const int* in_sizes, int n_in, void* d_out, int out_size) {
  (void)in_sizes; (void)n_in; (void)out_size;
  static EncodeFn enc = nullptr;
  static void *att = nullptr, *hbuf = nullptr, *scratch = nullptr;
  static int by_smid = 0;
  if (!enc) {
    void* fn = nullptr;
    cudaDriverEntryPointQueryResult q;
    cudaGetDriverEntryPoint("cuTensorMapEncodeTiled", &fn, cudaEnableDefault, &q);
    enc = (EncodeFn)fn;
    cudaGetSymbolAddress(&att, g_att);
    cudaGetSymbolAddress(&hbuf, g_h);
    cudaGetSymbolAddress(&scratch, g_scratch);
    cudaFuncSetAttribute(fused_layers_kernel<true>, cudaFuncAttributeMaxDynamicSharedMemorySize, SMEM_BYTES);
    cudaFuncSetAttribute(fused_layers_kernel<false>, cudaFuncAttributeMaxDynamicSharedMemorySize, SMEM_BYTES);
    int sms = 0, clusters = 0, dev = 0;
    cudaGetDevice(&dev);
    cudaDeviceGetAttribute(&sms, cudaDevAttrMultiProcessorCount, dev);
    cudaLaunchConfig_t cfg = {};
    cfg.gridDim = dim3(132);
    cfg.blockDim = dim3(384);
    cfg.dynamicSmemBytes = SMEM_BYTES;
    cudaLaunchAttribute at[1];
    at[0].id = cudaLaunchAttributeClusterDimension;
    at[0].val.clusterDim.x = 2; at[0].val.clusterDim.y = 1; at[0].val.clusterDim.z = 1;
    cfg.attrs = at;
    cfg.numAttrs = 1;
    if (cudaOccupancyMaxActiveClusters(&clusters, fused_layers_kernel<true>, &cfg) != cudaSuccess) (void)cudaGetLastError();
    by_smid = sms == 132 && clusters == 66;
  }
  Maps p;
  Scalars sc;
  make_act(enc, &p.xin, d_in[0], DM, true);
  make_act(enc, &p.out, d_out, DM, true);
  make_act(enc, &p.att, att, DM, false);
  make_act(enc, &p.h, hbuf, FF, false);
  make_2d(enc, &p.att_st, att, DM, SEQ, 32);
  make_2d(enc, &p.h_st, hbuf, FF, SEQ, 32);
  make_2d(enc, &p.w1c, d_in[4], FF, DM, 32);
  make_3d(enc, &p.wqkv, d_in[1], DM, DM, 3, 3 * DM * 2, DM * 2, 3);
  make_3d(enc, &p.wo, d_in[2], 64, DM, DM / 64, DM * 2, 128, 2);
  make_3d(enc, &p.w1a, d_in[4], 64, DM, FF / 64, FF * 2, 128, 3);
  make_3d(enc, &p.w1b, d_in[4], 64, DM, FF / 64, FF * 2, 128, 2);
  make_3d(enc, &p.w2, d_in[6], 64, FF, DM / 64, DM * 2, 128, 2);
  sc.b1 = (const __nv_bfloat16*)d_in[5];
  sc.b2 = (const __nv_bfloat16*)d_in[7];
  sc.g = (Scratch*)scratch;
  sc.zero = 0;
  if (by_smid) fused_layers_kernel<true><<<132, 384, SMEM_BYTES>>>(sc, p);
  else fused_layers_kernel<false><<<NCTA, 384, SMEM_BYTES>>>(sc, p);
}
```

```cpp
#include <cuda_runtime.h>
#include <cuda_bf16.h>
#include <cuda.h>
#include <stdint.h>

namespace {

constexpr int SEQ = 2048, DM = 1024, FF = 3584;
constexpr int NCTA = 128;
constexpr int NBAR = 5;

constexpr uint32_t RING_UNITS = 20, UNIT = 8192;
constexpr uint32_t OFF_X   = RING_UNITS * UNIT;
constexpr uint32_t OFF_STG = OFF_X + 32768;
constexpr uint32_t OFF_HLP = OFF_STG + 16384;
constexpr uint32_t OFF_RUN = OFF_STG + 24576;
constexpr uint32_t OFF_CSQ = OFF_RUN + 512;
constexpr uint32_t OFF_CSF = OFF_CSQ + 2048;
constexpr uint32_t OFF_ROW = OFF_CSF + 3584;
constexpr uint32_t OFF_BAR = OFF_ROW + 1024;
constexpr uint32_t SMEM_BYTES = OFF_BAR + 384;
constexpr uint32_t BAR_FULL = OFF_BAR, BAR_EMPTY = OFF_BAR + 8 * NBAR;
constexpr uint32_t BAR_XRDY = OFF_BAR + 80;
constexpr uint32_t BAR_DUMMY = OFF_BAR + 96, OFF_TAG = OFF_BAR + 104, OFF_ZERO = OFF_BAR + 112;
constexpr uint32_t BAR_PUB = OFF_BAR + 128;
constexpr uint32_t BAR_CSLD = OFF_BAR + 200;
constexpr uint32_t BAR_XGO = OFF_BAR + 224;
constexpr uint32_t BAR_BIAS = OFF_BAR + 216;

constexpr uint64_t DESC_A = (1ull << 62) | ((uint64_t)(2048 >> 4) << 32) | (1ull << 16);
constexpr uint64_t DESC_B = (1ull << 62) | ((uint64_t)(1024 >> 4) << 32) | ((uint64_t)(4096 >> 4) << 16);

constexpr int BAR_INIT = 0, BAR_ORDER = 1, BAR_GUARD = 3, BAR_WG = 5, BAR_GO = 7, BAR_DONE = 8, BAR_HLP = 9, BAR_INIT0 = 10, BAR_PAIR = 11;
#define GELU_DEP 2
#define MAP 2
#define LATE_O 1
#define HALO_NS 200
#define STG_WAIT 5
#define STAT_NS 800
#define BDELAY 400
#define STAG5 450
#define STAG4 0
#define STAG3 0
#define PACE0 0
#define PACE_M 100
#define PACE_N 300
#define CS_NS 500
#define BSPLIT 50
#define WIN1 8
#define WIN2 2

struct Scratch {
  uint4 stats[4 * 8 * SEQ];
  uint4 halo[2 * 2 * 16 * 8 * 384];
  uint4 csp[2 * 8 * 17 * 224];
  uint32_t flags[16 * 32];
  uint32_t epoch[NCTA + 4];
};

struct Maps {
  CUtensorMap xin, out, att, h, wqkv, wo, w1a, w1b, w2, att_st, h_st, w1c, out_w;
};
struct Scalars {
  Scratch* g;
  const __nv_bfloat16 *b1, *b2;
  uint32_t zero;
};
struct Params : Scalars {
  const Maps& t;
};

__device__ __nv_bfloat16 g_att[SEQ * DM];
__device__ __nv_bfloat16 g_h[SEQ * FF];
__device__ Scratch g_scratch;
#define PROF_T(idx)
#define PROF_U(k)
#define PROF_S(g)
#define PROF_E(i, k)

__device__ __forceinline__ void mbar_init(uint32_t bar, int cnt) {
  asm volatile("mbarrier.init.shared::cta.b64 [%0], %1;" ::"r"(bar), "r"(cnt));
}
__device__ __forceinline__ void mbar_expect_tx(uint32_t bar, uint32_t bytes) {
  asm volatile("mbarrier.arrive.expect_tx.shared::cta.b64 _, [%0], %1;" ::"r"(bar), "r"(bytes) : "memory");
}
__device__ __forceinline__ void mbar_arrive(uint32_t bar) {
  asm volatile("mbarrier.arrive.shared::cta.b64 _, [%0];" ::"r"(bar) : "memory");
}
__device__ __forceinline__ bool mbar_test(uint32_t bar, uint32_t parity) {
  uint32_t ok;
  asm volatile("{\n.reg .pred p;\nmbarrier.test_wait.parity.shared::cta.b64 p, [%1], %2;\nselp.u32 %0, 1, 0, p;\n}"
               : "=r"(ok) : "r"(bar), "r"(parity) : "memory");
  return ok;
}
__device__ __forceinline__ void mbar_wait(uint32_t bar, uint32_t parity) {
  asm volatile(
      "{\n.reg .pred p;\n.reg .u32 it;\nmov.u32 it, 0;\n"
      "WAIT_LOOP:\n"
      "mbarrier.try_wait.parity.shared::cta.b64 p, [%0], %1;\n"
      "@p bra WAIT_DONE;\n"
      "add.u32 it, it, 1;\n"
      "setp.lt.u32 p, it, 0x400000;\n"
      "@p bra WAIT_LOOP;\n"
      "trap;\n"
      "WAIT_DONE:\n}"
      ::"r"(bar), "r"(parity) : "memory");
}
__device__ __forceinline__ void bar_sync(int id, int n) { asm volatile("bar.sync %0, %1;" ::"r"(id), "r"(n) : "memory"); }
__device__ __forceinline__ void bar_arrive(int id, int n) { asm volatile("bar.arrive %0, %1;" ::"r"(id), "r"(n) : "memory"); }
__device__ __forceinline__ void tma_ld2(uint32_t dst, const CUtensorMap* m, uint32_t bar, int c0, int c1) {
  asm volatile("cp.async.bulk.tensor.2d.shared::cluster.global.mbarrier::complete_tx::bytes [%0], [%1, {%3, %4}], [%2];"
               ::"r"(dst), "l"(m), "r"(bar), "r"(c0), "r"(c1) : "memory");
}
__device__ __forceinline__ void tma_ld_act(uint32_t dst, const CUtensorMap* m, uint32_t bar, int col, int blk) {
  asm volatile("cp.async.bulk.tensor.4d.shared::cluster.global.mbarrier::complete_tx::bytes [%0], [%1, {%3, %5, %5, %4}], [%2];"
               ::"r"(dst), "l"(m), "r"(bar), "r"(col), "r"(2 * blk), "r"(0) : "memory");
}
__device__ __forceinline__ void tma_st_act(const CUtensorMap* m, uint32_t src, int col, int blk) {
  asm volatile("cp.async.bulk.tensor.4d.global.shared::cta.bulk_group [%0, {%2, %4, %4, %3}], [%1];"
               ::"l"(m), "r"(src), "r"(col), "r"(2 * blk), "r"(0) : "memory");
}
__device__ __forceinline__ void tma_st_warp(const CUtensorMap* m, uint32_t src, int col, int blk, int w) {
  asm volatile("cp.async.bulk.tensor.4d.global.shared::cta.bulk_group [%0, {%2, %5, %3, %4}], [%1];"
               ::"l"(m), "r"(src), "r"(col), "r"(w & 1), "r"(2 * blk + (w >> 1)), "r"(0) : "memory");
}
__device__ __forceinline__ void tma_ld3(uint32_t dst, const CUtensorMap* m, uint32_t bar, int c0, int c1, int c2) {
  asm volatile("cp.async.bulk.tensor.3d.shared::cluster.global.mbarrier::complete_tx::bytes [%0], [%1, {%3, %4, %5}], [%2];"
               ::"r"(dst), "l"(m), "r"(bar), "r"(c0), "r"(c1), "r"(c2) : "memory");
}
__device__ __forceinline__ void tma_ld3_pair(uint32_t dst, const CUtensorMap* m, uint32_t bar, int c0, int c1, int c2) {
  asm volatile("cp.async.bulk.tensor.3d.shared::cluster.global.mbarrier::complete_tx::bytes.multicast::cluster"
               " [%0], [%1, {%3, %4, %5}], [%2], %6;"
               ::"r"(dst), "l"(m), "r"(bar), "r"(c0), "r"(c1), "r"(c2), "h"((uint16_t)3) : "memory");
}
__device__ __forceinline__ uint32_t pair_offset(uint32_t sb, uint32_t rank) {
  uint32_t r;
  asm volatile("mapa.shared::cluster.u32 %0, %1, %2;" : "=r"(r) : "r"(sb), "r"(rank));
  return r - sb;
}
__device__ __forceinline__ void mbar_arrive_cluster(uint32_t bar) {
  asm volatile("mbarrier.arrive.shared::cluster.b64 _, [%0];" ::"r"(bar) : "memory");
}
__device__ __forceinline__ void cluster_arrive() { asm volatile("barrier.cluster.arrive.relaxed;" ::: "memory"); }
__device__ __forceinline__ void cluster_wait() { asm volatile("barrier.cluster.wait.acquire;" ::: "memory"); }
__device__ __forceinline__ void tma_st2(const CUtensorMap* m, uint32_t src, int c0, int c1) {
  asm volatile("cp.async.bulk.tensor.2d.global.shared::cta.bulk_group [%0, {%2, %3}], [%1];"
               ::"l"(m), "r"(src), "r"(c0), "r"(c1) : "memory");
}
__device__ __forceinline__ void bulk_commit() { asm volatile("cp.async.bulk.commit_group;" ::: "memory"); }
__device__ __forceinline__ void bulk_wait_read() { asm volatile("cp.async.bulk.wait_group.read 0;" ::: "memory"); }
__device__ __forceinline__ void bulk_wait_all() { asm volatile("cp.async.bulk.wait_group 0;" ::: "memory"); }
__device__ __forceinline__ void fence_async_smem() { asm volatile("fence.proxy.async.shared::cta;" ::: "memory"); }
__device__ __forceinline__ void fence_async_global() { asm volatile("fence.proxy.async.global;" ::: "memory"); }
__device__ __forceinline__ void st_relaxed(uint32_t* p, uint32_t v) {
  asm volatile("st.relaxed.gpu.global.u32 [%0], %1;" ::"l"(p), "r"(v) : "memory");
}
__device__ __forceinline__ void st_msg(uint4* p, uint32_t a, uint32_t b, uint32_t c, uint32_t tag) {
  asm volatile("{\n.reg .b128 v;\nmov.b128 v, {%1, %2, %3, %4};\nst.relaxed.gpu.global.b128 [%0], v;\n}"
               ::"l"(p), "r"(a), "r"(b), "r"(c), "r"(tag) : "memory");
}
__device__ __forceinline__ void ld_msg(const uint4* p, uint32_t& a, uint32_t& b, uint32_t& c, uint32_t& tag) {
  asm volatile("{\n.reg .b128 v;\nld.relaxed.gpu.global.b128 v, [%4];\nmov.b128 {%0, %1, %2, %3}, v;\n}"
               : "=r"(a), "=r"(b), "=r"(c), "=r"(tag) : "l"(p) : "memory");
}
__device__ __forceinline__ bool elect_one() {
  uint32_t ok;
  asm volatile("{\n.reg .pred p;\nelect.sync _|p, 0xffffffff;\nselp.u32 %0, 1, 0, p;\n}" : "=r"(ok));
  return ok;
}
__device__ __forceinline__ uint32_t lanemask_lt() {
  uint32_t v;
  asm("mov.u32 %0, %%lanemask_lt;" : "=r"(v));
  return v;
}
__device__ __forceinline__ int uniform(int v) { return __shfl_sync(0xffffffffu, v, 0); }
__device__ __forceinline__ uint32_t pack_bf16(float lo, float hi) {
  uint32_t r;
  asm("cvt.rn.bf16x2.f32 %0, %1, %2;" : "=r"(r) : "f"(hi), "f"(lo));
  return r;
}
__device__ __forceinline__ float prmt_f(uint32_t a, uint32_t sel) {
  float r;
  asm("{\n.reg .b32 t;\nprmt.b32 t, %1, 0, %2;\nmov.b32 %0, t;\n}" : "=f"(r) : "r"(a), "r"(sel));
  return r;
}
__device__ __forceinline__ float bf_lo(uint32_t v) { return __uint_as_float(v << 16); }
__device__ __forceinline__ float bf_hi(uint32_t v) { return __uint_as_float(v & 0xffff0000u); }
__device__ __forceinline__ void stsm4(uint32_t addr, uint32_t r0, uint32_t r1, uint32_t r2, uint32_t r3) {
  asm volatile("stmatrix.sync.aligned.m8n8.x4.shared.b16 [%0], {%1, %2, %3, %4};"
               ::"r"(addr), "r"(r0), "r"(r1), "r"(r2), "r"(r3) : "memory");
}
__device__ __forceinline__ void ldsm4(uint32_t addr, uint32_t& r0, uint32_t& r1, uint32_t& r2, uint32_t& r3) {
  asm volatile("ldmatrix.sync.aligned.m8n8.x4.shared.b16 {%0, %1, %2, %3}, [%4];"
               : "=r"(r0), "=r"(r1), "=r"(r2), "=r"(r3) : "r"(addr) : "memory");
}
__device__ __forceinline__ uint32_t movtrans(uint32_t a) {
  uint32_t d;
  asm volatile("movmatrix.sync.aligned.m8n8.trans.b16 %0, %1;" : "=r"(d) : "r"(a));
  return d;
}
__device__ __forceinline__ void mma16816(float (&c)[4], uint32_t a0, uint32_t a1, uint32_t a2, uint32_t a3, uint32_t b0, uint32_t b1) {
  asm volatile("mma.sync.aligned.m16n8k16.row.col.f32.bf16.bf16.f32 {%0,%1,%2,%3}, {%4,%5,%6,%7}, {%8,%9}, {%0,%1,%2,%3};"
               : "+f"(c[0]), "+f"(c[1]), "+f"(c[2]), "+f"(c[3])
               : "r"(a0), "r"(a1), "r"(a2), "r"(a3), "r"(b0), "r"(b1));
}
__device__ __forceinline__ void mma1688(float (&c)[4], uint32_t a0, uint32_t a1, uint32_t b0) {
  asm volatile("mma.sync.aligned.m16n8k8.row.col.f32.bf16.bf16.f32 {%0,%1,%2,%3}, {%4,%5}, {%6}, {%0,%1,%2,%3};"
               : "+f"(c[0]), "+f"(c[1]), "+f"(c[2]), "+f"(c[3]) : "r"(a0), "r"(a1), "r"(b0));
}
__device__ __forceinline__ float2 lds_f2(uint32_t a) {
  float2 v;
  asm volatile("ld.shared.v2.f32 {%0, %1}, [%2];" : "=f"(v.x), "=f"(v.y) : "r"(a) : "memory");
  return v;
}
__device__ __forceinline__ float4 lds_f4(uint32_t a) {
  float4 v;
  asm volatile("ld.shared.v4.f32 {%0, %1, %2, %3}, [%4];" : "=f"(v.x), "=f"(v.y), "=f"(v.z), "=f"(v.w) : "r"(a) : "memory");
  return v;
}
__device__ __forceinline__ float lds_f(uint32_t a) {
  float v;
  asm volatile("ld.shared.f32 %0, [%1];" : "=f"(v) : "r"(a) : "memory");
  return v;
}
__device__ __forceinline__ uint32_t lds_u(uint32_t a) {
  uint32_t v;
  asm volatile("ld.shared.u32 %0, [%1];" : "=r"(v) : "r"(a) : "memory");
  return v;
}
__device__ __forceinline__ void sts_f2(uint32_t a, float x, float y) {
  asm volatile("st.shared.v2.f32 [%0], {%1, %2};" ::"r"(a), "f"(x), "f"(y) : "memory");
}
__device__ __forceinline__ void sts_u4(uint32_t a, uint32_t x, uint32_t y, uint32_t z, uint32_t w) {
  asm volatile("st.shared.v4.u32 [%0], {%1, %2, %3, %4};" ::"r"(a), "r"(x), "r"(y), "r"(z), "r"(w) : "memory");
}
__device__ __forceinline__ void lds_u4(uint32_t a, uint32_t& x, uint32_t& y, uint32_t& z, uint32_t& w) {
  asm volatile("ld.shared.v4.u32 {%0, %1, %2, %3}, [%4];" : "=r"(x), "=r"(y), "=r"(z), "=r"(w) : "r"(a) : "memory");
}
__device__ __forceinline__ float ex2(float x) {
  float y;
  asm("ex2.approx.ftz.f32 %0, %1;" : "=f"(y) : "f"(x));
  return y;
}
__device__ __forceinline__ float rcp_hw(float x) {
  float y;
  asm("rcp.approx.ftz.f32 %0, %1;" : "=f"(y) : "f"(x));
  return y;
}
__device__ __forceinline__ float tanh_hw(float x) {
  float y;
  asm("tanh.approx.f32 %0, %1;" : "=f"(y) : "f"(x));
  return y;
}
__device__ __forceinline__ float quad_sum(float v) {
  v += __shfl_xor_sync(0xffffffffu, v, 1);
  return v + __shfl_xor_sync(0xffffffffu, v, 2);
}
__device__ __forceinline__ float quad_max(float v) {
  v = fmaxf(v, __shfl_xor_sync(0xffffffffu, v, 1));
  return fmaxf(v, __shfl_xor_sync(0xffffffffu, v, 2));
}

template <int N> __device__ __forceinline__ void wgmma_ss(float (&d)[96], uint64_t da, uint64_t db, uint32_t keep = 1);
template <> __device__ __forceinline__ void wgmma_ss<128>(float (&d)[96], uint64_t da, uint64_t db, uint32_t keep) {
  asm volatile(
      "{\n.reg .pred p;\nsetp.ne.u32 p, %66, 0;\n"
      "wgmma.mma_async.sync.aligned.m64n128k16.f32.bf16.bf16 {%0, %1, %2, %3, %4, %5, %6, %7, %8, %9, %10, %11, %12, %13, %14, %15, %16, %17, %18, %19, %20, %21, %22, %23, %24, %25, %26, %27, %28, %29, %30, %31, %32, %33, %34, %35, %36, %37, %38, %39, %40, %41, %42, %43, %44, %45, %46, %47, %48, %49, %50, %51, %52, %53, %54, %55, %56, %57, %58, %59, %60, %61, %62, %63}, %64, %65, p, 1, 1, 0, 1;\n}"
      : "+f"(d[0]), "+f"(d[1]), "+f"(d[2]), "+f"(d[3]), "+f"(d[4]), "+f"(d[5]), "+f"(d[6]), "+f"(d[7]), "+f"(d[8]), "+f"(d[9]), "+f"(d[10]), "+f"(d[11]), "+f"(d[12]), "+f"(d[13]), "+f"(d[14]), "+f"(d[15]), "+f"(d[16]), "+f"(d[17]), "+f"(d[18]), "+f"(d[19]), "+f"(d[20]), "+f"(d[21]), "+f"(d[22]), "+f"(d[23]), "+f"(d[24]), "+f"(d[25]), "+f"(d[26]), "+f"(d[27]), "+f"(d[28]), "+f"(d[29]), "+f"(d[30]), "+f"(d[31]), "+f"(d[32]), "+f"(d[33]), "+f"(d[34]), "+f"(d[35]), "+f"(d[36]), "+f"(d[37]), "+f"(d[38]), "+f"(d[39]), "+f"(d[40]), "+f"(d[41]), "+f"(d[42]), "+f"(d[43]), "+f"(d[44]), "+f"(d[45]), "+f"(d[46]), "+f"(d[47]), "+f"(d[48]), "+f"(d[49]), "+f"(d[50]), "+f"(d[51]), "+f"(d[52]), "+f"(d[53]), "+f"(d[54]), "+f"(d[55]), "+f"(d[56]), "+f"(d[57]), "+f"(d[58]), "+f"(d[59]), "+f"(d[60]), "+f"(d[61]), "+f"(d[62]), "+f"(d[63])
      : "l"(da), "l"(db), "r"(keep));
}

template <> __device__ __forceinline__ void wgmma_ss<192>(float (&d)[96], uint64_t da, uint64_t db, uint32_t keep) {
  asm volatile(
      "{\n.reg .pred p;\nsetp.ne.u32 p, %98, 0;\n"
      "wgmma.mma_async.sync.aligned.m64n192k16.f32.bf16.bf16 {%0, %1, %2, %3, %4, %5, %6, %7, %8, %9, %10, %11, %12, %13, %14, %15, %16, %17, %18, %19, %20, %21, %22, %23, %24, %25, %26, %27, %28, %29, %30, %31, %32, %33, %34, %35, %36, %37, %38, %39, %40, %41, %42, %43, %44, %45, %46, %47, %48, %49, %50, %51, %52, %53, %54, %55, %56, %57, %58, %59, %60, %61, %62, %63, %64, %65, %66, %67, %68, %69, %70, %71, %72, %73, %74, %75, %76, %77, %78, %79, %80, %81, %82, %83, %84, %85, %86, %87, %88, %89, %90, %91, %92, %93, %94, %95}, %96, %97, p, 1, 1, 0, 1;\n}"
      : "+f"(d[0]), "+f"(d[1]), "+f"(d[2]), "+f"(d[3]), "+f"(d[4]), "+f"(d[5]), "+f"(d[6]), "+f"(d[7]), "+f"(d[8]), "+f"(d[9]), "+f"(d[10]), "+f"(d[11]), "+f"(d[12]), "+f"(d[13]), "+f"(d[14]), "+f"(d[15]), "+f"(d[16]), "+f"(d[17]), "+f"(d[18]), "+f"(d[19]), "+f"(d[20]), "+f"(d[21]), "+f"(d[22]), "+f"(d[23]), "+f"(d[24]), "+f"(d[25]), "+f"(d[26]), "+f"(d[27]), "+f"(d[28]), "+f"(d[29]), "+f"(d[30]), "+f"(d[31]), "+f"(d[32]), "+f"(d[33]), "+f"(d[34]), "+f"(d[35]), "+f"(d[36]), "+f"(d[37]), "+f"(d[38]), "+f"(d[39]), "+f"(d[40]), "+f"(d[41]), "+f"(d[42]), "+f"(d[43]), "+f"(d[44]), "+f"(d[45]), "+f"(d[46]), "+f"(d[47]), "+f"(d[48]), "+f"(d[49]), "+f"(d[50]), "+f"(d[51]), "+f"(d[52]), "+f"(d[53]), "+f"(d[54]), "+f"(d[55]), "+f"(d[56]), "+f"(d[57]), "+f"(d[58]), "+f"(d[59]), "+f"(d[60]), "+f"(d[61]), "+f"(d[62]), "+f"(d[63]), "+f"(d[64]), "+f"(d[65]), "+f"(d[66]), "+f"(d[67]), "+f"(d[68]), "+f"(d[69]), "+f"(d[70]), "+f"(d[71]), "+f"(d[72]), "+f"(d[73]), "+f"(d[74]), "+f"(d[75]), "+f"(d[76]), "+f"(d[77]), "+f"(d[78]), "+f"(d[79]), "+f"(d[80]), "+f"(d[81]), "+f"(d[82]), "+f"(d[83]), "+f"(d[84]), "+f"(d[85]), "+f"(d[86]), "+f"(d[87]), "+f"(d[88]), "+f"(d[89]), "+f"(d[90]), "+f"(d[91]), "+f"(d[92]), "+f"(d[93]), "+f"(d[94]), "+f"(d[95])
      : "l"(da), "l"(db), "r"(keep));
}

template <int R>
__device__ __forceinline__ void pin_regs(float (&a)[2][96]) {
#pragma unroll
  for (int m = 0; m < 2; m++)
#pragma unroll
    for (int i = 0; i < R; i++) asm volatile("" : "+f"(a[m][i])::"memory");
}

struct Ctx {
  uint32_t sb;
  int m, n, wg, w, lane;
};
__device__ __forceinline__ Ctx make_ctx(uint32_t sb, int id) {
  int lane;
  asm volatile("mov.u32 %0, %%laneid;" : "=r"(lane));
  asm volatile("" : "+r"(id), "+r"(sb));
  return Ctx{sb, (id >> 3) & 15, id & 7, id >> 9, (id >> 7) & 3, lane};
}
#define UNPACK_CTX(c) const uint32_t sb = c.sb; const int m = c.m, n = c.n, wg = c.wg, w = c.w, lane = c.lane

__device__ __forceinline__ uint32_t poll_line(const uint32_t* word, uint32_t target, uint32_t need) {
  uint32_t v;
  asm volatile(
      "{\n.reg .pred p;\n.reg .u32 it, m;\n.reg .s32 d;\nmov.u32 it, 0;\n"
      "POLL_LOOP:\n"
      "ld.relaxed.gpu.global.u32 %0, [%1];\n"
      "sub.s32 d, %0, %2;\n"
      "setp.ge.s32 p, d, 0;\n"
      "vote.sync.ballot.b32 m, p, 0xffffffff;\n"
      "and.b32 m, m, %3;\n"
      "setp.eq.u32 p, m, %3;\n"
      "@p bra.uni POLL_DONE;\n"
      "add.u32 it, it, 1;\n"
      "setp.lt.u32 p, it, 0x400000;\n"
      "@p bra.uni POLL_LOOP;\n"
      "trap;\n"
      "POLL_DONE:\n}"
      : "=&r"(v) : "l"(word), "r"(target), "r"(need) : "memory");
  return v;
}
__device__ __forceinline__ uint32_t ld_relaxed(const uint32_t* p) {
  uint32_t v;
  asm volatile("ld.relaxed.gpu.global.u32 %0, [%1];" : "=r"(v) : "l"(p) : "memory");
  return v;
}
__device__ __forceinline__ float chain(float x, uint32_t on, uint32_t zero) {
  return __uint_as_float(__float_as_uint(x) | (on & zero));
}
constexpr int MSG_SPINS = 1 << 20;

constexpr int STAGES_PER_LAYER = 152;
__device__ __forceinline__ int nib(uint64_t v, int i) { return (int)(v >> (4 * i)) & 15; }
__device__ __forceinline__ bool tile_wide(int t) { return (0x23 >> t) & 1; }
__device__ __forceinline__ void weight_coords(const Params& p, int t, int n, const CUtensorMap*& map, int& c0, int& c2) {
  map = &p.t.wqkv + nib(0x4233100ull, t);
  c0 = t < 2 ? 128 * n + 64 * t : 0;
  c2 = t < 2 ? 0 : (t == 2 || t == 6) ? 2 * n : 7 * n + 2 * t - 6;
}

template <bool IS_A>
__device__ __forceinline__ void producer(const Params& p, uint32_t sb, int m, int n, int lane) {
  const uint32_t low = (1u << (4 * n)) - 1, others = (0x6543210u & low) | (0x7654321u & ~low);
  const uint64_t order_x = (uint64_t)(others * 2 + 0x1111111u) << 36 | (uint64_t)others * 2 << 8 | (n * 0x22 + 0x10);
  int inflight = 4, cur = 0;
  uint32_t fb = sb + BAR_FULL + 32, rb = sb + BAR_EMPTY, rph = 0, pos = 0, tag32 = 0, seen = 0;
  const uint32_t fend = sb + BAR_FULL + 8 * NBAR, rend = sb + BAR_EMPTY + 8 * NBAR;
  const uint32_t* word = p.g->flags + m * 32 + (lane < 16 ? lane >> 1 : lane & 7);
#pragma unroll 1
  for (int sg = 1; sg < 22; sg++) {
    const int layer = sg >= 11, s = sg == 1 ? 2 : sg == 2 ? 1 : sg - 11 * layer;
    const int t = nib(0x65434321010ull, s), kind = nib(0x32110031100ull, s);
    const bool wide = tile_wide(t);
    const uint32_t bbytes = wide ? 3 * UNIT : 2 * UNIT, base = sb + (IS_A ? bbytes : (m & 1) * (bbytes / 2));
    if (IS_A && kind == 0) {
      if (sg == 2) seen = tag32 = (__ldcg(p.g->epoch + m * 8 + n) + 1) << 5;
#pragma unroll 1
      for (int k = 0; k < 2; k++) {
#pragma unroll 1
        for (; inflight > (wide ? 3 : 4); inflight--) {
          mbar_wait(rb, rph);
          rb += 8;
          if (rb == rend) { rb -= 8 * NBAR; rph ^= 1; }
        }
        if (elect_one()) mbar_arrive(fb);
        inflight++;
        fb += 8;
        if (fb == fend) fb -= 8 * NBAR;
        pos += bbytes + 2 * UNIT;
        if (pos >= RING_UNITS * UNIT) pos -= RING_UNITS * UNIT;
      }
      continue;
    }
    const int mul = t == 6 ? 448 : t == 2 ? 128 : 64, count = sg == 1 ? 12 : 2 * nib(0x4871ull, kind);
    uint64_t order0 = sg == 1 ? 0xFEDCBA987654ull : kind == 3 ? 0x76543210u : order_x >> (8 * (kind & 1));
    uint32_t special = (s == 4 || s == 10) ? 0x10 : s == 9 ? 0xF : s == 0;
    if (IS_A) special |= (kind & 1 ? 0 : 3) | (count >= 4 ? 1u << (count - 4) : 0);
    if (s >= 9) pos = (s + 6) * UNIT;
    const CUtensorMap* map;
    int c0 = 0, c2 = 0, ev = 0;
    if (IS_A) {
      map = &p.t.xin + (t == 2 ? 2 : t == 6 ? 3 : sg >= 4);
      ev = 9 * layer + (t < 2 ? 0 : t == 2 ? 1 : t < 6 ? 4 : 5);
      if (elect_one()) asm volatile("prefetch.tensormap [%0];" ::"l"(map) : "memory");
    } else {
      weight_coords(p, t, n, map, c0, c2);
    }
#pragma unroll 1
    for (int add = 0; add < mul; add += 64) {
      uint64_t order = order0;
      const int need = kind == 3 ? ev : ev - 1 + (lane & 1), sh = kind == 3 ? 16 : 0;
      uint32_t ready = IS_A ? __ballot_sync(0xffffffffu, cur >= need) >> sh : 0;
#pragma unroll 1
      for (int k = 0; k < count; k++) {
        const int code = order & 15, kc = code * mul + add;
        order >>= 4;
        if ((special >> k) & 1) {
          const int lag = wide ? (s == 9 && k == 2 ? 2 : 3) : ((s == 4 || s == 10) && add == 0 && k < 4) ? 3 : 4;
#pragma unroll 1
          for (; inflight > lag; inflight--) {
            mbar_wait(rb, rph);
            rb += 8;
            if (rb == rend) { rb -= 8 * NBAR; rph ^= 1; }
          }
          inflight++;
          if (IS_A) {
            if (kind == 3 ? t == 2 && add + k == 64 : !(kind & 1) && k < 2) {
              if (t == 2) mbar_wait(sb + BAR_PUB + 8, layer);
              if (elect_one()) mbar_arrive(fb);
              goto next_stage;
            }
            if (k == count - 4 && sg >= 3) seen = ld_relaxed(word);
          }
        } else {
          mbar_wait(rb, rph);
          rb += 8;
          if (rb == rend) { rb -= 8 * NBAR; rph ^= 1; }
        }
        if (IS_A && !((ready >> code) & 1)) {
          cur = max(cur, (int)(seen - tag32));
          ready = __ballot_sync(0xffffffffu, cur >= need) >> sh;
          if (!((ready >> code) & 1)) {
            cur = (int)(poll_line(word, tag32 + need, 1u << (code + sh)) - tag32);
            ready = __ballot_sync(0xffffffffu, cur >= need) >> sh;
          }
          asm volatile("fence.acquire.gpu;" ::: "memory");
          fence_async_global();
          seen = ld_relaxed(word);
        }
        if (elect_one()) {
          if (!IS_A) tma_ld3_pair(base + pos, map, fb, c0, kc + 32 * (m & 1), c2);
          else tma_ld_act(base + pos, map, fb, kc, m);
          mbar_expect_tx(fb, IS_A ? 16384 : bbytes);
        }
      next_stage:
        fb += 8;
        if (fb == fend) fb -= 8 * NBAR;
        pos += bbytes + 2 * UNIT;
        if (pos >= RING_UNITS * UNIT) pos -= RING_UNITS * UNIT;
      }
      special = !IS_A ? 0 : t == 2 ? 1 : add == 128 ? 0x10 : 0;
      if (t == 2) order0 = others << 4 | n;
      if (IS_A && (t == 2 || add == 64 || add == 192)) ev++;
    }
  }
}

__device__ __forceinline__ void publisher(const Params& p, uint32_t sb, int m, int n) {
  {
    const int ts = PACE0 + PACE_M * m, tx = PACE0 + PACE_N * n;
#pragma unroll 1
    for (int k = 0; k < 2; k++) {
      __nanosleep(k == 0 ? min(ts, tx) : abs(ts - tx));
      if ((ts <= tx) == (k == 0)) {
        mbar_expect_tx(sb + BAR_CSLD, 24576);
        tma_ld3(sb + OFF_STG, &p.t.wqkv, sb + BAR_CSLD, 128 * n, 64 * m, 0);
        tma_ld3(sb + OFF_STG + 12288, &p.t.wqkv, sb + BAR_CSLD, 128 * n, 64 * m + 32, 0);
      } else {
#pragma unroll 1
        for (int h = 0; h < 2; h++) {
          const uint32_t xr = sb + BAR_XRDY + 8 * h;
          mbar_expect_tx(xr, 16384);
          tma_ld_act(sb + OFF_X + h * 16384, &p.t.xin, xr, 128 * n + 64 * h, m);
          asm volatile("mbarrier.arrive.shared::cta.b64 _, [%0], 3;" ::"r"(xr) : "memory");
        }
      }
    }
  }
  const uint32_t tag = __ldcg(p.g->epoch + m * 8 + n) + 1;
  uint32_t* word = p.g->flags + m * 32 + n;
  const int mn = m * 8 + n; (void)mn;
  st_relaxed(word, 32 * tag);
#pragma unroll 1
  for (int c = 0; c < 16; c++) {
    const int e = c >= 9 ? c - 9 : c;
    if (e == 2 || e == 7) {
      asm volatile("prefetch.tensormap [%0];" ::"l"(&p.t.out) : "memory");
      mbar_wait(sb + BAR_XRDY, e == 2);
      tma_st_act(&p.t.out, sb + OFF_X, 128 * n, m);
      bulk_commit();
      mbar_wait(sb + BAR_XRDY + 8, e == 2);
      bulk_wait_all();
      mbar_arrive(sb + BAR_XGO);
      PROF_E(7 * (c >= 9) + (e < 4 ? 2 : 6), 11);
    } else {
      mbar_wait(sb + BAR_PUB + 8 * e, c >= 9);
    }
    asm volatile("fence.release.gpu;" ::: "memory");
    asm volatile("red.relaxed.gpu.global.add.u32 [%0], 1;" ::"l"(word) : "memory");
    PROF_E(7 * (c >= 9) + nib(0x665432210ull, e), (0x108 >> e) & 1 ? 14 : 12);
  }
  p.g->epoch[m * 8 + n] = tag;
}

__device__ __forceinline__ void sum_rows(uint32_t buf, int iters, float (&a)[8], int lane) {
  uint32_t addr = buf + (lane >> 3) * 128 + (((lane & 7) ^ (lane >> 3)) << 4);
#pragma unroll 1
  for (int it = 0; it < iters; it++) {
    uint32_t u[2][4];
    lds_u4(addr, u[0][0], u[0][1], u[0][2], u[0][3]);
    lds_u4((addr ^ 64) + 512, u[1][0], u[1][1], u[1][2], u[1][3]);
    addr += 1024;
#pragma unroll
    for (int e = 0; e < 8; e++) { a[2 * (e & 3)] += bf_lo(u[e >> 2][e & 3]); a[2 * (e & 3) + 1] += bf_hi(u[e >> 2][e & 3]); }
  }
}
__device__ __forceinline__ void publish_sums(const float (&a)[8], uint4* dst, int lane, uint32_t tag) {
  const bool u8 = lane & 8, u16 = lane & 16;
  float h4[4], h2[2];
#pragma unroll
  for (int e = 0; e < 4; e++) h4[e] = (u8 ? a[4 + e] : a[e]) + __shfl_xor_sync(0xffffffffu, u8 ? a[e] : a[4 + e], 8);
#pragma unroll
  for (int e = 0; e < 2; e++) h2[e] = (u16 ? h4[2 + e] : h4[e]) + __shfl_xor_sync(0xffffffffu, u16 ? h4[e] : h4[2 + e], 16);
  st_msg(dst + (lane & 7) * 4 + (u8 ? 2 : 0) + (u16 ? 1 : 0), __float_as_uint(h2[0]), __float_as_uint(h2[1]), 0u, tag);
}

__device__ __forceinline__ void colsum_helper(const Params& p, uint32_t sb, int m, int n, int lane) {
  const uint32_t tag = __ldcg(p.g->epoch + m * 8 + n) + 1;
  const int mn = m * 8 + n; (void)mn;
#pragma unroll 1
  for (int k = lane; k < 288; k += 32) {
    const uint32_t bb = __ldg(reinterpret_cast<const uint32_t*>(k < 224 ? p.b1 + 448 * n : p.b2 + 128 * n - 448) + k);
    const float sc = k < 224 ? 0.5f : 1.f;
    sts_f2(sb + (k < 224 ? OFF_CSF + k * 16 + 8 : OFF_CSQ + 1536 + (k - 224) * 8), sc * bf_lo(bb), sc * bf_hi(bb));
  }
  __syncwarp();
  if (elect_one()) mbar_arrive(sb + BAR_BIAS);
  bar_sync(BAR_HLP, 160);
  {
    uint4* base = p.g->csp + n * 17 * 224 + 12 * m + min(lane & 15, 11);
    float s0 = 0.f, s1 = 0.f;
#pragma unroll 1
    for (int g = 0; g < 2; g++) {
      uint32_t x[4], y[4];
#pragma unroll 1
      for (int it = 0; it < MSG_SPINS; it++) {
        uint32_t bad = 0, z, tg;
        if (g == 0 || it > 0) __nanosleep(CS_NS);
#pragma unroll
        for (int k = 0; k < 4; k++) { ld_msg(base + (g * 8 + (lane >> 4) * 4 + k) * 224, x[k], y[k], z, tg); bad |= tg ^ tag; }
        if (__all_sync(0xffffffffu, bad == 0)) break;
      }
#pragma unroll
      for (int k = 0; k < 4; k++) { s0 += __uint_as_float(x[k]); s1 += __uint_as_float(y[k]); }
    }
    s0 += __shfl_xor_sync(0xffffffffu, s0, 16);
    s1 += __shfl_xor_sync(0xffffffffu, s1, 16);
    if (lane < 12) st_msg(base + 16 * 224, __float_as_uint(s0), __float_as_uint(s1), 0u, tag);
    PROF_E(-1, 3);
  }
  PROF_E(-1, 1);
#pragma unroll 1
  for (int c = 0; c < 7; c++) {
    float a[8] = {0.f, 0.f, 0.f, 0.f, 0.f, 0.f, 0.f, 0.f};
#pragma unroll 1
    for (int h = 0; h < 2; h++) {
      if (elect_one()) {
        mbar_expect_tx(sb + BAR_CSLD + 8, 4096);
        tma_ld2(sb + OFF_HLP, &p.t.w1c, sb + BAR_CSLD + 8, 448 * n + 64 * c, 64 * m + 32 * h);
        if (c < 6) asm volatile("cp.async.bulk.prefetch.tensor.2d.L2.global [%0, {%1, %2}];" ::"l"(&p.t.w1c), "r"(448 * n + 64 * c + 64), "r"(64 * m + 32 * h) : "memory");
      }
      mbar_wait(sb + BAR_CSLD + 8, h);
      sum_rows(sb + OFF_HLP, 4, a, lane);
      __syncwarp();
    }
    publish_sums(a, p.g->csp + ((8 + n) * 17 + m) * 224 + c * 32, lane, tag);
  }
  PROF_E(-1, 2);
  if (elect_one()) {
#pragma unroll 1
    for (int k = 0; k < 3; k++) {
      mbar_wait(sb + BAR_XGO, k & 1);
      __nanosleep(BDELAY);
#pragma unroll 1
      for (int w = 0; w < 4; w++) {
        tma_st_warp(&p.t.out_w, sb + OFF_X + 16384 + w * 4096, 128 * n + 64, m, w);
        bulk_commit();
        bulk_wait_read();
        if (w < 3) __nanosleep(BSPLIT);
      }
      bulk_wait_all();
      asm volatile("mbarrier.arrive.shared::cta.b64 _, [%0], 4;" ::"r"(sb + BAR_PUB + (k & 1 ? 64 : 24)) : "memory");
    }
  }
}

__device__ __forceinline__ void poll_msgs2(const uint4* pa, const uint4* pb, float (&v)[4], uint32_t tag) {
#pragma unroll 1
  for (int it = 0; it < MSG_SPINS; it++) {
    uint32_t x[4], z, ta, tb;
    ld_msg(pa, x[0], x[1], z, ta);
    ld_msg(pb, x[2], x[3], z, tb);
#pragma unroll
    for (int e = 0; e < 4; e++) v[e] = __uint_as_float(x[e]);
    if (__all_sync(0xffffffffu, ta == tag && tb == tag)) break;
  }
}
__device__ __forceinline__ void colsum_total(const Params& p, const Ctx& cx, int mat, uint32_t tag) {
  uint4* base = p.g->csp + (mat * 8 + cx.n) * 17 * 224;
  const int per = 12 + 2 * mat, k = 2 * cx.w + (cx.lane >> 4), ia = per * cx.m + k, ib = per * cx.m + min(k + 8, per - 1);
  float v[4];
  poll_msgs2(base + (cx.lane & 15) * 224 + ia, base + (cx.lane & 15) * 224 + ib, v, tag);
#pragma unroll 1
  for (int d = 1; d < 16; d *= 2)
#pragma unroll
    for (int e = 0; e < 4; e++) v[e] += __shfl_xor_sync(0xffffffffu, v[e], d);
  const bool hi = cx.lane & 1;
  if ((cx.lane & 14) == 0) st_msg(base + 16 * 224 + (hi ? ib : ia), __float_as_uint(hi ? v[2] : v[0]), __float_as_uint(hi ? v[3] : v[1]), 0u, tag);
}
__device__ __forceinline__ void colsum_gather(const Params& p, const Ctx& cx, int mat, uint32_t tag) {
  const uint4* base = p.g->csp + ((mat * 8 + cx.n) * 17 + 16) * 224;
  const int ia = cx.w * 32 + cx.lane, ib = min(ia + 128, 191 + 32 * mat);
  float v[4];
  poll_msgs2(base + ia, base + ib, v, tag);
  const uint32_t tab = cx.sb + (mat ? OFF_CSF : OFF_CSQ);
  sts_f2(tab + (ia << (3 + mat)), v[0], v[1]);
  sts_f2(tab + (ib << (3 + mat)), v[2], v[3]);
}

#define ACC(q, j, e) acc[(q) & 1][4 * (j) + 2 * ((q) >> 1) + (e)]

constexpr uint32_t RING16 = RING_UNITS * (UNIT >> 4);
__device__ __forceinline__ bool tile_split(int i) { return (0xD98 >> i) & 1; }

__device__ __forceinline__ void write_run_desc(uint32_t sb, int i, int step) {
  const int layer = i >= 7, t = i - 7 * layer, part = tile_split(i) ? step : 2;
  const bool wide = tile_wide(t), own = t != 2 && t != 6 && part != 1 && i != 0, second = t == 1 || t == 4;
  const uint32_t z16 = (wide ? 5 : 4) * (UNIT >> 4), a_off = z16 - 1024 + (uint32_t)DESC_A - (uint32_t)DESC_B;
  const int gl = 16 * t + (part == 2 ? 0 : second ? 16 * part - 14 : 4 * part), g0 = layer * STAGES_PER_LAYER + gl;
  const uint32_t s16 = (sb & 0x3FFFF) >> 4, bfirst = (uint32_t)DESC_B + s16;
  const int nkb = t == 6 ? 56 : part == 0 ? 2 : 12 + 2 * part;
  const bool win1 = t == 1 && part != 0;
  const int run = win1 ? WIN1 + 1 : t == 2 ? WIN2 + 1 : nkb;
  const int rest = win1 ? 64 | (nkb - 1 - WIN1) : t == 2 ? 64 | (7 - WIN2) | (8 << 7) : 0;
  const uint32_t blo = bfirst + z16 * (wide ? (gl + (t == 5 ? 3 : 0)) & 3 : (gl + 3) % 5);
  const uint32_t alo = own ? (uint32_t)DESC_A + s16 + (OFF_X >> 4) : blo + a_off;
  const uint32_t aoff = own ? alo + 1024 - (blo == bfirst + RING16 - z16 ? bfirst : blo + z16) : a_off;
  const bool xwait = part == 0 && !second, keep = !(part == 0 || t == 5);
  sts_u4(sb + OFF_RUN + (2 * i + step) * 16, blo, alo, aoff,
         ((g0 / NBAR) & 1) | xwait << 1 | keep << 2 | 8 * (g0 % NBAR) | run << 6 | rest << 12);
}

template <int N>
__device__ __forceinline__ void mainloop(const Params& p, float (&acc)[2][96], uint32_t sb, int i, int step, int mn) {
  constexpr uint32_t Z16 = (2 + N / 64) * (UNIT >> 4);
  constexpr uint32_t A_OFF = Z16 - 1024 + (uint32_t)DESC_A - (uint32_t)DESC_B;
  const int wg = i & 1;
  const uint32_t s16 = (sb & 0x3FFFF) >> 4;
  const uint32_t blast = (uint32_t)DESC_B + s16 + RING16 - Z16, flast = sb + BAR_FULL + 8 * (NBAR - 1);
  uint32_t blo = (uint32_t)DESC_B + s16, alo = blo + A_OFF, aoff = A_OFF, misc = 16 << 6;
  if (N == 128 || i > 0) lds_u4(sb + OFF_RUN + (2 * i + step) * 16, blo, alo, aoff, misc);
  uint32_t keep = misc & 4;
  int run = (misc >> 6) & 63, rest = misc >> 12;
  uint32_t fb = sb + BAR_FULL + (misc & 0x38), ph = misc & 1;
  uint32_t prev = sb + BAR_DUMMY - 8 * NBAR;
  const uint32_t lane_id = __popc(__ballot_sync(0xffffffffu, true) & lanemask_lt()), rel = pair_offset(sb, lane_id & 1) + 8 * NBAR;
  pin_regs<N / 2>(acc);
  if (N == 128 || i > 0) bar_sync(BAR_ORDER + wg, 256);
  else bar_sync(BAR_INIT0, 160);
  if (N == 192 && i == 0 && threadIdx.x == 0) PROF_U(8);
  mbar_wait(fb, ph);
  if (N == 192 && i == 0 && threadIdx.x == 0) PROF_U(9);
  if (N == 192 && i == 0) cluster_wait();
  if (misc & 2) mbar_wait(sb + BAR_XGO, N == 192);
  if (step == 0 || !tile_split(i)) PROF_T(4 + i * 4);
  if (step == 1 && tile_split(i)) PROF_E(i, 13);
#pragma unroll 1
  while (true) {
    const uint64_t da = (DESC_A & ~0xffffffffull) | alo, db = (DESC_B & ~0xffffffffull) | blo;
    asm volatile("wgmma.fence.sync.aligned;" ::: "memory");
    wgmma_ss<N>(acc[0], da, db, keep);
    wgmma_ss<N>(acc[1], da + 64, db, keep);
    keep = 4;
    wgmma_ss<N>(acc[0], da + 2, db + 128);
    wgmma_ss<N>(acc[1], da + 66, db + 128);
    asm volatile("wgmma.commit_group.sync.aligned;" ::: "memory");
    asm volatile("wgmma.wait_group.sync.aligned 1;" ::: "memory");
    PROF_S(jj++);
    if (lane_id < 2) mbar_arrive_cluster(prev + rel);
    prev = fb;
    if (fb == flast) { fb -= 8 * NBAR; ph++; }
    fb += 8;
    if (blo == blast) blo -= RING16;
    blo += Z16;
    alo = blo + aoff;
    aoff = A_OFF;
    run--;
    const bool ready = mbar_test(fb, ph) && run != 0;
    asm volatile("wgmma.fence.sync.aligned;" ::: "memory");
    wgmma_ss<N>(acc[0], da + 4, db + 4 * N);
    wgmma_ss<N>(acc[1], da + 68, db + 4 * N);
    wgmma_ss<N>(acc[0], da + 6, db + 4 * N + 128);
    wgmma_ss<N>(acc[1], da + 70, db + 4 * N + 128);
    asm volatile("wgmma.commit_group.sync.aligned;" ::: "memory");
    if (!ready) {
      bool window = false;
      if (run == 0) {
        if (rest == 0) break;
        window = rest & 64;
        if (window) bar_arrive(BAR_GO, 256);
        else alo = (uint32_t)DESC_A + s16 + (OFF_STG >> 4);
        run = rest & 63;
        rest >>= 7;
      }
      mbar_wait(fb, ph);
      if (window) bar_sync(BAR_DONE, 256);
    }
  }
  if (i < 13 && !(LATE_O && N == 192 && (misc >> 12))) bar_arrive(BAR_ORDER + (wg ^ 1), 256);
  if (N == 128 && ((0x2244 >> i) & 1)) {
    const Ctx cx = make_ctx(sb, mn);
    const uint32_t xrow = cx.sb + OFF_X + cx.w * 4096 + cx.lane * 128 + ((cx.lane & 7) << 4);
    const bool leader = elect_one();
    asm volatile("wgmma.wait_group.sync.aligned 0;" ::: "memory");
    pin_regs<64>(acc);
    PROF_T(5 + i * 4);
    PROF_E(i, 0);
#pragma unroll
    for (int h = 0; h < 2; h++) {
      if (h == 1 && p.zero != 0) break;
#pragma unroll
      for (int j = 8 * h; j < 8 * h + 8; j++)
        stsm4((xrow ^ ((j & 7) << 4)) + h * 16384, pack_bf16(ACC(0, j, 0), ACC(0, j, 1)), pack_bf16(ACC(1, j, 0), ACC(1, j, 1)),
              pack_bf16(ACC(2, j, 0), ACC(2, j, 1)), pack_bf16(ACC(3, j, 0), ACC(3, j, 1)));
      fence_async_smem();
      __syncwarp();
      if (leader) {
        mbar_arrive(sb + BAR_XRDY + 8 * h);
        if (i == 13) {
          tma_st_warp(&p.t.out_w, cx.sb + OFF_X + h * 16384 + cx.w * 4096, 128 * cx.n + 64 * h, cx.m, cx.w);
          bulk_commit();
          if (h == 1) bulk_wait_read();
        }
      }
      if (h == 0 && lane_id < 2) mbar_arrive_cluster(prev + rel);
    }
    PROF_E(i, 4);
    return;
  }
  asm volatile("wgmma.wait_group.sync.aligned 0;" ::: "memory");
  pin_regs<N / 2>(acc);
  if (lane_id < 2) mbar_arrive_cluster(prev + rel);
  PROF_T(5 + i * 4);
  PROF_E(i, 0);
}

__device__ __forceinline__ void write_partial_stats(const Params& p, const Ctx& c, int ln, uint32_t tag) {
  const uint32_t xrow = c.sb + OFF_X + c.w * 4096 + c.lane * 128;
  float s = 0.f, q = 0.f, s1 = 0.f, q1 = 0.f;
#pragma unroll 4
  for (int j = 0; j < 16; j++) {
    uint32_t u[4];
    lds_u4(xrow + (j >> 3) * 16384 + (((j & 7) ^ (c.lane & 7)) << 4), u[0], u[1], u[2], u[3]);
#pragma unroll
    for (int e = 0; e < 4; e++) {
      const float a = bf_lo(u[e]), d = bf_hi(u[e]);
      s += a; q = fmaf(a, a, q);
      s1 += d; q1 = fmaf(d, d, q1);
    }
  }
  s += s1;
  q += q1;
  st_msg(p.g->stats + (ln * 8 + c.n) * SEQ + 128 * c.m + 32 * c.w + c.lane, __float_as_uint(s),
         __float_as_uint(fmaxf(q - s * s * (1.f / 128.f), 0.f)), 0u, tag);
}

__device__ __forceinline__ void finish_row_stats(const Params& p, const Ctx& c, int ln, uint32_t tag) {
  const uint4* src = p.g->stats + ln * 8 * SEQ + 128 * c.m + 32 * c.w + c.lane;
  uint32_t ps[8], pm[8];
#pragma unroll 1
  for (int it = 0; it < MSG_SPINS; it++) {
    uint32_t bad = 0, u, tg;
    if (ln > 1 || it > 0) __nanosleep(STAT_NS);
#pragma unroll
    for (int k = 0; k < 8; k++) { ld_msg(src + k * SEQ, ps[k], pm[k], u, tg); bad |= tg ^ tag; }
    if (__all_sync(0xffffffffu, bad == 0)) break;
  }
  float s = 0.f, m2 = 0.f;
#pragma unroll
  for (int k = 0; k < 8; k++) s += __uint_as_float(ps[k]);
  const float mean = s * (1.f / DM);
#pragma unroll
  for (int k = 0; k < 8; k++) {
    const float d = __uint_as_float(ps[k]) * (1.f / 128.f) - mean;
    m2 += fmaf(128.f * d, d, __uint_as_float(pm[k]));
  }
  sts_f2(c.sb + OFF_ROW + (32 * c.w + c.lane) * 8, rsqrtf(m2 * (1.f / DM) + 1e-5f), mean);
  __syncwarp();
}

__device__ __forceinline__ void attn_scores(const uint32_t* qa, const uint32_t* qb, const uint32_t* kp, const uint32_t* ka,
                                            const uint32_t* kb, float (&l)[4], const float4& zero, const bool (&early)[2]) {
  float s[3][4];
#pragma unroll
  for (int x = 0; x < 3; x++) {
    const uint32_t* kk = x == 0 ? kp : x == 1 ? ka : kb;
    asm volatile("mma.sync.aligned.m16n8k16.row.col.f32.bf16.bf16.f32 {%0,%1,%2,%3}, {%4,%5,%6,%7}, {%8,%9}, {%10,%11,%12,%13};"
                 : "=f"(s[x][0]), "=f"(s[x][1]), "=f"(s[x][2]), "=f"(s[x][3])
                 : "r"(qa[0]), "r"(qb[0]), "r"(qa[1]), "r"(qb[1]), "r"(kk[0]), "r"(kk[1]), "f"(zero.x), "f"(zero.y),
                   "f"(zero.z), "f"(zero.w));
  }
#pragma unroll
  for (int x = 0; x < 3; x++) {
    const uint32_t* kk = x == 0 ? kp : x == 1 ? ka : kb;
    mma16816(s[x], qa[2], qb[2], qa[3], qb[3], kk[2], kk[3]);
  }
#pragma unroll
  for (int e = 0; e < 2; e++) {
    l[e] = early[e] ? s[0][e] : s[1][e];
    l[2 + e] = early[e] ? s[1][2 + e] : s[2][2 + e];
  }
}

__device__ __forceinline__ void attn_mix(const float (&l)[4], const float (&sc)[4], const float (&off)[4], const float (&rk)[4],
                                         const uint32_t* vp, const uint32_t* va, const uint32_t* vb, float (&o)[4][4],
                                         float (&sum)[2], uint32_t mask, uint32_t zero) {
  float x[4];
#pragma unroll
  for (int e = 0; e < 4; e++) x[e] = fmaf(l[e], sc[e], off[e]);
  const float ml = quad_max(fmaxf(x[0], x[1])), mh = quad_max(fmaxf(x[2], x[3]));
  x[0] = ex2(x[0] - ml); x[1] = ex2(x[1] - ml);
  x[2] = ex2(x[2] - mh); x[3] = ex2(x[3] - mh);
  sum[0] = rcp_hw(quad_sum(x[0] + x[1]));
  sum[1] = rcp_hw(quad_sum(x[2] + x[3]));
  const uint32_t pl = pack_bf16(x[0] * rk[0], x[1] * rk[1]), ph = pack_bf16(x[2] * rk[2], x[3] * rk[3]);
  const uint32_t a0 = pl & ~mask, a1 = ph & mask, a2 = pl & zero, a3 = ph & ~mask, c0 = pl & mask, c1 = ph & zero;
#pragma unroll
  for (int jn = 0; jn < 4; jn++) {
    o[jn][0] = o[jn][1] = o[jn][2] = o[jn][3] = 0.f;
    mma16816(o[jn], a0, a1, a2, a3, va[jn], vb[jn]);
  }
#pragma unroll
  for (int jn = 0; jn < 4; jn++) mma1688(o[jn], c0, c1, vp[jn]);
}

__device__ __forceinline__ void gelu_epilogue(const Params& p, float (&acc)[2][96], const Ctx& cx, int t) {
  UNPACK_CTX(cx);
  (void)wg;
  float rs[4], rm[4];
#pragma unroll
  for (int q = 0; q < 4; q++) {
    const float2 v = lds_f2(sb + OFF_ROW + (32 * w + 8 * q + (lane >> 2)) * 8);
    rs[q] = 0.5f * v.x;
    rm[q] = -rs[q] * v.y;
  }
  const int col0 = 128 * (t - 3);
  const uint32_t stg = sb + OFF_STG + w * 4096;
  const uint32_t ctab = sb + OFF_CSF + (col0 / 2 + (lane & 3)) * 16, srow = stg + lane * 128 + ((lane & 7) << 4);
  __nanosleep((t == 5 ? STAG5 : t == 4 ? STAG4 : STAG3) * w);
  float4 nb = lds_f4(ctab);
#pragma unroll
  for (int c = 0; c < 3; c++) {
    if (c == 2 && t != 5) break;
    uint32_t hp[8][4];
#pragma unroll
    for (int j = 0; j < 8; j++) {
      const float4 cb = nb;
      if (8 * c + j < 23) nb = lds_f4(ctab + (8 * c + j + 1) * 64);
#pragma unroll
      for (int q = 0; q < 4; q++) {
        float y[2];
        const int k = 4 * j + q - GELU_DEP;
        const float rmq = k >= 0 ? chain(rm[q], hp[k >> 2][k & 3], p.zero) : rm[q];
#pragma unroll
        for (int e = 0; e < 2; e++) {
          const float z = fmaf(ACC(q, 8 * c + j, e), rs[q], fmaf(rmq, e ? cb.y : cb.x, e ? cb.w : cb.z));
          const float u = z * fmaf(z * z, 8.f * 0.7978845608028654f * 0.044715f, 2.f * 0.7978845608028654f);
          y[e] = fmaf(z, tanh_hw(u), z);
        }
        hp[j][q] = pack_bf16(y[0], y[1]);
      }
      if (j == STG_WAIT && c > 0) {
        if (lane == 0) bulk_wait_read();
        __syncwarp();
      }
      if (c == 0 || j > STG_WAIT) {
        stsm4(srow ^ (j << 4), hp[j][0], hp[j][1], hp[j][2], hp[j][3]);
      } else if (j == STG_WAIT) {
#pragma unroll
        for (int jj = 0; jj <= STG_WAIT; jj++) stsm4(srow ^ (jj << 4), hp[jj][0], hp[jj][1], hp[jj][2], hp[jj][3]);
      }
    }
    fence_async_smem();
    __syncwarp();
    if (lane == 0) {
      tma_st2(&p.t.h_st, stg, 448 * n + col0 + 64 * c, 128 * m + 32 * w);
      bulk_commit();
    }
  }
#pragma unroll
  for (int r = 0; r < 16; r++) acc[0][r] = acc[1][r] = 0.f;
}

template <int PART>
__device__ __forceinline__ void rank1_update(const Params& p, float (&acc)[2][96], const Ctx& cx, int t) {
  float nm[4];
#pragma unroll
  for (int q = 0; q < 4; q++) nm[q] = t == 6 ? 1.f : -lds_f(cx.sb + OFF_ROW + (32 * cx.w + 8 * q + (cx.lane >> 2)) * 8 + 4);
  const uint32_t ctab = cx.sb + OFF_CSQ + ((t & 3) * 192 + 2 * (cx.lane & 3)) * 4;
#pragma unroll
  for (int j = PART == 1 ? 8 : 0; j < 24; j++) {
    const float2 cs = lds_f2(ctab + j * 32);
#pragma unroll
    for (int q = 0; q < 4; q++) {
      if (PART != 0 && (PART == 1) != (q == 3 && j >= 8)) continue;
      const int k = 4 * j + q - 1;
      const float nq = PART == 0 && k >= 0 ? chain(nm[q], __float_as_uint(ACC(k & 3, k >> 2, 1)), p.zero) : nm[q];
      ACC(q, j, 0) = fmaf(nq, cs.x, ACC(q, j, 0));
      ACC(q, j, 1) = fmaf(nq, cs.y, ACC(q, j, 1));
    }
  }
}

__device__ __forceinline__ void attn_epilogue(const Params& p, float (&acc)[2][96], const Ctx& cx, int layer, int t, uint32_t tag) {
  UNPACK_CTX(cx);
  const uint32_t ktab = sb + OFF_ROW + (32 * w + 2 * (lane & 3)) * 8, exc = sb + OFF_STG + (w & 1) * 2048 + lane * 16;
  uint4* const halo = p.g->halo + (((layer * 2 + t) * 16 + m) * 8 + n) * 384 + (w & 1) * 192;
  const int mn = m * 8 + n; (void)mn;
  uint32_t Q[4][8], K[4][8], V[4][8], E[18], P[18];
  float kr[5][2], qr[4];
  const bool late_fold = layer == 0 && t == 1;
  if (late_fold) rank1_update<1>(p, acc, cx, 1);
  {
    const float4 r = lds_f4(ktab + 192);
    E[16] = __float_as_uint(kr[4][0] = r.x);
    E[17] = __float_as_uint(kr[4][1] = r.z);
  }
#pragma unroll
  for (int j = 0; j < 8; j++) {
    E[j] = K[3][j] = pack_bf16(ACC(3, 8 + j, 0), ACC(3, 8 + j, 1));
    E[8 + j] = V[3][j] = movtrans(pack_bf16(ACC(3, 16 + j, 0), ACC(3, 16 + j, 1)));
  }
  if (w < 2) {
#pragma unroll
    for (int k = 0; k < 4; k++) sts_u4(exc + k * 512, E[4 * k], E[4 * k + 1], E[4 * k + 2], E[4 * k + 3]);
  } else {
#pragma unroll
    for (int k = 0; k < 6; k++) st_msg(halo + k * 32 + lane, E[3 * k], E[3 * k + 1], E[3 * k + 2], tag);
  }
  bar_arrive(BAR_PAIR + w, 64);
  if (LATE_O && t == 1) bar_arrive(BAR_ORDER + (wg ^ 1), 256);
  PROF_E(7 * layer + t, 1);
  if (late_fold) rank1_update<2>(p, acc, cx, 1);
#pragma unroll
  for (int q = 0; q < 4; q++) {
    qr[q] = lds_f(sb + OFF_ROW + (32 * w + 8 * q + (lane >> 2)) * 8) * (0.17677669529663687f * 1.4426950408889634f);
#pragma unroll
    for (int j = 0; j < 8; j++) Q[q][j] = pack_bf16(ACC(q, j, 0), ACC(q, j, 1));
    if (q < 3) {
      const float4 r = lds_f4(ktab + 64 * q);
      kr[1 + q][0] = r.x;
      kr[1 + q][1] = r.z;
#pragma unroll
      for (int j = 0; j < 8; j++) {
        K[q][j] = pack_bf16(ACC(q, 8 + j, 0), ACC(q, 8 + j, 1));
        V[q][j] = movtrans(pack_bf16(ACC(q, 16 + j, 0), ACC(q, 16 + j, 1)));
      }
    }
  }
  PROF_E(7 * layer + t, 6);
  bar_sync(BAR_PAIR + (w ^ 2), 64);
  if (w >= 2 || m == 0) {
#pragma unroll
    for (int k = 0; k < 4; k++) lds_u4(exc + k * 512, P[4 * k], P[4 * k + 1], P[4 * k + 2], P[4 * k + 3]);
    const float4 r = lds_f4(ktab - (w >> 1) * 320);
    P[16] = __float_as_uint(r.x);
    P[17] = __float_as_uint(r.z);
  } else {
    if (m & 1) __nanosleep(HALO_NS);
#pragma unroll 1
    for (int it = 0; it < MSG_SPINS; it++) {
      uint32_t tg, bad = 0;
      if (it > 0 || !(m & 1)) poll_line(reinterpret_cast<const uint32_t*>(halo - 8 * 384 + 191) + 3, tag, 1u);
#pragma unroll
      for (int k = 0; k < 6; k++) {
        ld_msg(halo - 8 * 384 + k * 32 + lane, P[3 * k], P[3 * k + 1], P[3 * k + 2], tg);
        bad |= tg ^ tag;
      }
      if (__all_sync(0xffffffffu, bad == 0)) break;
    }
  }
  kr[0][0] = __uint_as_float(P[16]);
  kr[0][1] = __uint_as_float(P[17]);
  const bool early[2] = {2 * (lane & 3) > (lane >> 2), 2 * (lane & 3) + 1 > (lane >> 2)};
  const uint32_t mask = (early[0] ? 0xffffu : 0u) | (early[1] ? 0xffff0000u : 0u);
  float rk[2][4], sc[2][4], off[2][4];
#pragma unroll
  for (int g = 0; g < 2; g++) {
#pragma unroll
    for (int e = 0; e < 4; e++) {
      const int q = 2 * g + (e >> 1);
      const bool masked = q == 0 && m == 0 && w < 2 && early[e & 1];
      rk[g][e] = early[e & 1] ? kr[q][e & 1] : kr[q + 1][e & 1];
      sc[g][e] = masked ? 0.f : rk[g][e] * qr[q];
      off[g][e] = masked ? -1e30f : 0.f;
    }
  }
  if (w == 0 && elect_one()) asm volatile("prefetch.tensormap [%0];" ::"l"(&p.t.att_st) : "memory");
  PROF_E(7 * layer + t, 2);
  bar_sync(BAR_GO, 256);
  const float4 zero = lds_f4(sb + OFF_ZERO);
  float l[2][2][4], o[2][2][4][4], sum[2][2][2];
#pragma unroll
  for (int h = 0; h < 2; h++) {
    if (h == 1) {
      Q[2][4] |= __float_as_uint(l[1][0][0]) & p.zero;
      Q[0][4] |= __float_as_uint(l[0][0][0]) & p.zero;
    }
    attn_scores(&Q[2][4 * h], &Q[3][4 * h], &K[1][4 * h], &K[2][4 * h], &K[3][4 * h], l[1][h], zero, early);
    attn_scores(&Q[0][4 * h], &Q[1][4 * h], &P[4 * h], &K[0][4 * h], &K[1][4 * h], l[0][h], zero, early);
  }
  const uint32_t stg = sb + OFF_STG + w * 4096, srow = stg + lane * 128 + ((lane & 7) << 4);
#pragma unroll
  for (int h = 0; h < 2; h++) {
    attn_mix(l[1][h], sc[1], off[1], rk[1], &V[1][4 * h], &V[2][4 * h], &V[3][4 * h], o[1][h], sum[1][h], mask, p.zero);
    attn_mix(l[0][h], sc[0], off[0], rk[0], &P[8 + 4 * h], &V[0][4 * h], &V[1][4 * h], o[0][h], sum[0][h], mask, p.zero);
#pragma unroll
    for (int j = 0; j < 4; j++) {
      const float(&a)[4] = o[0][h][j];
      const float(&c)[4] = o[1][h][j];
      stsm4(srow ^ ((4 * h + j) << 4), pack_bf16(a[0] * sum[0][h][0], a[1] * sum[0][h][0]), pack_bf16(a[2] * sum[0][h][1], a[3] * sum[0][h][1]),
            pack_bf16(c[0] * sum[1][h][0], c[1] * sum[1][h][0]), pack_bf16(c[2] * sum[1][h][1], c[3] * sum[1][h][1]));
    }
  }
  bar_arrive(BAR_DONE, 256);
  fence_async_smem();
  __syncwarp();
  if (lane == 0) {
    tma_st2(&p.t.att_st, stg, 128 * n + 64 * t, 128 * m + 32 * w);
    bulk_commit();
  }
}

__device__ __forceinline__ void finish_stores(uint32_t sb, int i) {
  const int t = i >= 7 ? i - 7 : i;
  if ((threadIdx.x & 31) == 0) {
    bulk_wait_all();
    mbar_arrive(sb + BAR_PUB + 8 * (t < 2 ? t : t + 1));
  }
  __syncwarp();
  if (i < 12) bar_arrive(BAR_GUARD + ((i & 1) ^ 1), 256);
}

__device__ __forceinline__ bool consumer_tile(const Params& p, float (&acc)[2][96], uint32_t sb0, int i, int mn) {
  const int layer = i >= 7, t = i - 7 * layer, wg = i & 1;
  const bool resid = t == 2 || t == 6;
  {
    if (resid) {
      const Ctx cx = make_ctx(sb0, mn);
      const uint32_t xrow = cx.sb + OFF_X + cx.w * 4096 + cx.lane * 128;
      const uint32_t sel_lo = 0x1044u | p.zero, sel_hi = 0x3244u | p.zero;
#pragma unroll
      for (int j = 0; j < 16; j++) {
        uint32_t r[4];
        ldsm4(xrow + (j >> 3) * 16384 + (((j & 7) ^ (cx.lane & 7)) << 4), r[0], r[1], r[2], r[3]);
#pragma unroll
        for (int q = 0; q < 4; q++) {
          ACC(q, j, 0) = prmt_f(r[q], sel_lo);
          ACC(q, j, 1) = prmt_f(r[q], sel_hi);
        }
      }
    }
    if (t >= 5 || i == 7) finish_stores(sb0, i - 2);
#pragma unroll 1
    for (int step = !tile_split(i);; step++) {
      if (step == 1 && (t == 1 || t == 4)) {
        const Ctx cx = make_ctx(sb0, mn);
        if (i == 1) {
          const uint32_t epoch = __ldcg(p.g->epoch + (mn & 127));
          cluster_wait();
          asm volatile("st.shared.u32 [%0], %1;" ::"r"(sb0 + OFF_TAG), "r"(epoch + 1) : "memory");
        }
        const uint32_t tag = lds_u(cx.sb + OFF_TAG);
        const int ln = (i + 1) >> 2;
#pragma unroll 1
        for (int r = 0; r < 2; r++) {
          if (i == 1) {
            if (cx.w < 3) {
              float a[8] = {0.f, 0.f, 0.f, 0.f, 0.f, 0.f, 0.f, 0.f};
              mbar_wait(sb0 + BAR_CSLD, r);
#pragma unroll 1
              for (int h = 0; h < 2; h++) sum_rows(cx.sb + OFF_STG + h * 12288 + cx.w * 4096, 4, a, cx.lane);
              publish_sums(a, p.g->csp + (cx.n * 17 + cx.m) * 224 + (3 * r + cx.w) * 32, cx.lane, tag);
            }
            PROF_E(-1, 5 + r);
          }
          if (r == 1) break;
          if (i == 1) {
            bar_sync(BAR_WG + 1, 128);
            if (cx.w == 3 && elect_one()) {
              mbar_expect_tx(sb0 + BAR_CSLD, 24576);
              tma_ld3(sb0 + OFF_STG, &p.t.wqkv, sb0 + BAR_CSLD, 128 * cx.n + 64, 64 * cx.m, 0);
              tma_ld3(sb0 + OFF_STG + 12288, &p.t.wqkv, sb0 + BAR_CSLD, 128 * cx.n + 64, 64 * cx.m + 32, 0);
            }
            mbar_wait(sb0 + BAR_XRDY, 0);
            mbar_wait(sb0 + BAR_XRDY + 8, 0);
          }
          write_partial_stats(p, cx, ln, tag);
          PROF_E(i - 2, 8);
        }
        if (i == 1) {
          bar_arrive(BAR_HLP, 160);
          bar_sync(BAR_INIT, 160);
        }
        if (i == 4) colsum_total(p, cx, 1, tag);
        PROF_E(i - 2, 9);
        if (i != 1) bar_sync(BAR_GUARD + wg, 256);
        finish_row_stats(p, cx, ln, tag);
        PROF_E(i - 2, 10);
        if (i == 4) {
          colsum_gather(p, cx, 1, tag);
          mbar_wait(sb0 + BAR_BIAS, 0);
        }
        PROF_E(i - 2, 15);
        bar_arrive(BAR_GUARD + (wg ^ 1), 256);
      }
      if (step == 2 && !resid) bar_sync(BAR_GUARD + wg, 256);
      if (step == 2 && i == 0) {
        colsum_gather(p, make_ctx(sb0, mn), 0, lds_u(sb0 + OFF_TAG));
        bar_sync(BAR_WG, 128);
      }
      if ((t + step == 2 && i != 1) || t == 6) rank1_update<0>(p, acc, make_ctx(sb0, mn), t);
      if (step == 2) break;
      if (tile_wide(t)) {
        mainloop<192>(p, acc, sb0, i, step, mn);
      } else {
        mainloop<128>(p, acc, sb0, i, step, mn);
        if (resid) return false;
      }
    }
    if (t < 2) return true;
    gelu_epilogue(p, acc, make_ctx(sb0, mn), t);
    PROF_E(i, 4);
    return false;
  }
}

template <bool BY_SMID>
__global__ void __cluster_dims__(2, 1, 1) __launch_bounds__(384, 1)
fused_layers_kernel(const Scalars scalars, const __grid_constant__ Maps maps) {
  if (threadIdx.x == 288 || threadIdx.x == 320)
    asm volatile("prefetch.tensormap [%0];" ::"l"(threadIdx.x == 288 ? &maps.xin : &maps.wqkv) : "memory");
  const Params p{scalars, maps};
  extern __shared__ __align__(1024) uint8_t smem_raw[];
  const uint32_t sb = uniform((uint32_t)__cvta_generic_to_shared(smem_raw));
  const int tid = threadIdx.x, lane = tid & 31, warp = uniform(tid >> 5), wg = warp >> 2, w = warp & 3;

  int mn;
  {
    int id = blockIdx.x;
    if (BY_SMID) asm volatile("mov.u32 %0, %%smid;" : "=r"(id));
    else if (id >= 120) id += 4;
    const int c = id >> 1;
    int g, j;
    if (c < 32) { g = c & 7; j = c >> 3; }
    else if (c < 60) { g = 1 + (c - 32) % 7; j = 4 + (c - 32) / 7; }
    else { g = 0; j = c - 58; }
    const int r = blockIdx.x & 1;
    mn = (g * 2 + r) * 8 + j;
    if (c == 60 || c == 61) {
      if (tid < 32) {
        const uint32_t tag = __ldcg(p.g->epoch + NCTA + (id & 3)) + 1;
#pragma unroll 1
        for (int mm = 0; mm < 16; mm++) poll_line(p.g->flags + mm * 32 + (lane & 7), 32 * tag, 0xffu);
        if (tid == 0) p.g->epoch[NCTA + (id & 3)] = tag;
      }
      return;
    }
  }
  const int m = mn >> 3, n = mn & 7;
  if (tid == 256) PROF_U(1);
  if (wg < 2) {
    cluster_arrive();
    asm volatile("setmaxnreg.inc.sync.aligned.u32 232;");
    if (tid == 0) PROF_U(2);
    const int id = mn | (warp << 7);
#pragma unroll 1
    for (int i = wg;; i += 2) {
      float acc[2][96];
#pragma unroll
      for (int r = 0; r < 96; r++) acc[0][r] = acc[1][r] = 0.f;
      pin_regs<96>(acc);
      if (i == 0 && threadIdx.x == 0) PROF_U(3);
#pragma unroll 1
      while (!consumer_tile(p, acc, sb, i, id)) {
        PROF_T(6 + i * 4);
        i += 2;
        if (i >= 14) goto all_done;
      }
      attn_epilogue(p, acc, make_ctx(sb, id), i >= 7, i >= 7 ? i - 7 : i, lds_u(sb + OFF_TAG));
      PROF_E(i, 4);
      finish_stores(sb, i);
      PROF_E(i, 5);
      PROF_T(6 + i * 4);
    }
  all_done:
    if (wg == 0) {
      finish_stores(sb, 12);
    } else {
      cluster_arrive();
      cluster_wait();
    }
  } else {
    asm volatile("setmaxnreg.dec.sync.aligned.u32 40;");
    if (w != 0) {
      if (w == 1 && elect_one()) {
        mbar_init(sb + BAR_FULL + 32, 2);
#pragma unroll
        for (int k = 0; k < NBAR; k++) mbar_init(sb + BAR_EMPTY + 8 * k, 8);
#pragma unroll
        for (int k = 0; k < 3; k++) mbar_init(sb + BAR_XRDY + 8 * k, 4);
#pragma unroll
        for (int k = 0; k < 9; k++) mbar_init(sb + BAR_PUB + 8 * k, 4);
#pragma unroll
        for (int k = 0; k < 4; k++) mbar_init(sb + BAR_CSLD + 8 * k, 1);
        sts_f2(sb + OFF_ZERO, 0.f, 0.f);
        sts_f2(sb + OFF_ZERO + 8, 0.f, 0.f);
        asm volatile("fence.mbarrier_init.release.cluster;" ::: "memory");
      }
      __syncwarp();
      cluster_arrive();
      if (w == 2) {
        if (lane < 28) write_run_desc(sb, lane >> 1, lane & 1);
        bar_arrive(BAR_INIT, 160);
      }
      cluster_wait();
      if (w == 1) producer<true>(p, sb, m, n, lane);
      else if (w == 3) colsum_helper(p, sb, m, n, lane);
      else if (elect_one()) publisher(p, sb, m, n);
    } else {
      const bool leader = elect_one();
      if (leader) {
#pragma unroll
        for (int k = 0; k < 4; k++) mbar_init(sb + BAR_FULL + 8 * k, 2);
        asm volatile("fence.mbarrier_init.release.cluster;" ::: "memory");
        PROF_U(4);
      }
      __syncwarp();
      bar_arrive(BAR_INIT0, 160);
      cluster_arrive();
      if (leader) {
#pragma unroll 1
        for (int k = 0; k < 4; k++) {
          const uint32_t fb = sb + BAR_FULL + 8 * k;
          mbar_expect_tx(fb, 16384);
          tma_ld_act(sb + (5 * k + 3) * UNIT, &p.t.xin, fb, 64 * k, m);
          mbar_expect_tx(fb, 3 * UNIT);
          tma_ld3(sb + 5 * k * UNIT, &p.t.wqkv, fb, 128 * n, 64 * k, 0);
          tma_ld3(sb + 5 * k * UNIT + 12288, &p.t.wqkv, fb, 128 * n, 64 * k + 32, 0);
          if (k == 0) PROF_U(6);
        }
        PROF_U(5);
      }
      __syncwarp();
      cluster_wait();
      producer<false>(p, sb, m, n, lane);
    }
  }
}

typedef CUresult (*EncodeFn)(CUtensorMap*, CUtensorMapDataType, cuuint32_t, void*, const cuuint64_t*, const cuuint64_t*,
                             const cuuint32_t*, const cuuint32_t*, CUtensorMapInterleave, CUtensorMapSwizzle,
                             CUtensorMapL2promotion, CUtensorMapFloatOOBfill);

#define PROMO2 CU_TENSOR_MAP_L2_PROMOTION_L2_128B
#define PROMO3 CU_TENSOR_MAP_L2_PROMOTION_L2_128B
void make_2d(EncodeFn enc, CUtensorMap* m, const void* ptr, uint64_t cols, uint64_t rows, uint32_t box_rows) {
  cuuint64_t d[2] = {cols, rows}, st[1] = {cols * 2};
  cuuint32_t b[2] = {64, box_rows}, e[2] = {1, 1};
  enc(m, CU_TENSOR_MAP_DATA_TYPE_BFLOAT16, 2, const_cast<void*>(ptr), d, st, b, e, CU_TENSOR_MAP_INTERLEAVE_NONE,
      CU_TENSOR_MAP_SWIZZLE_128B, PROMO2, CU_TENSOR_MAP_FLOAT_OOB_FILL_NONE);
}
void make_act(EncodeFn enc, CUtensorMap* m, const void* ptr, uint64_t cols, bool split, uint32_t box = 2) {
  const uint64_t row = cols * 2;
  cuuint64_t d[4] = {cols, 32, 2, SEQ / 64}, st[3] = {split ? 2 * row : row, split ? row : 32 * row, 64 * row};
  cuuint32_t b[4] = {64, 32, box, box}, e[4] = {1, 1, 1, 1};
  enc(m, CU_TENSOR_MAP_DATA_TYPE_BFLOAT16, 4, const_cast<void*>(ptr), d, st, b, e, CU_TENSOR_MAP_INTERLEAVE_NONE,
      CU_TENSOR_MAP_SWIZZLE_128B, PROMO2, CU_TENSOR_MAP_FLOAT_OOB_FILL_NONE);
}
void make_3d(EncodeFn enc, CUtensorMap* m, const void* ptr, uint64_t d0, uint64_t rows, uint64_t d2, uint64_t row_bytes,
             uint64_t chunk_bytes, uint32_t box_chunks) {
  cuuint64_t d[3] = {d0, rows, d2}, st[2] = {row_bytes, chunk_bytes};
  cuuint32_t b[3] = {64, 32, box_chunks}, e[3] = {1, 1, 1};
  enc(m, CU_TENSOR_MAP_DATA_TYPE_BFLOAT16, 3, const_cast<void*>(ptr), d, st, b, e, CU_TENSOR_MAP_INTERLEAVE_NONE,
      CU_TENSOR_MAP_SWIZZLE_128B, PROMO3, CU_TENSOR_MAP_FLOAT_OOB_FILL_NONE);
}

}

extern "C" void kernel_launch(void* const* d_in, const int* in_sizes, int n_in, void* d_out, int out_size) {
  (void)in_sizes; (void)n_in; (void)out_size;
  static EncodeFn enc = nullptr;
  static void *att = nullptr, *hbuf = nullptr, *scratch = nullptr;
  static int by_smid = 0;
  if (!enc) {
    void* fn = nullptr;
    cudaDriverEntryPointQueryResult q;
    cudaGetDriverEntryPoint("cuTensorMapEncodeTiled", &fn, cudaEnableDefault, &q);
    enc = (EncodeFn)fn;
    cudaGetSymbolAddress(&att, g_att);
    cudaGetSymbolAddress(&hbuf, g_h);
    cudaGetSymbolAddress(&scratch, g_scratch);
    cudaFuncSetAttribute(fused_layers_kernel<true>, cudaFuncAttributeMaxDynamicSharedMemorySize, SMEM_BYTES);
    cudaFuncSetAttribute(fused_layers_kernel<false>, cudaFuncAttributeMaxDynamicSharedMemorySize, SMEM_BYTES);
    int sms = 0, clusters = 0, dev = 0;
    cudaGetDevice(&dev);
    cudaDeviceGetAttribute(&sms, cudaDevAttrMultiProcessorCount, dev);
    cudaLaunchConfig_t cfg = {};
    cfg.gridDim = dim3(132);
    cfg.blockDim = dim3(384);
    cfg.dynamicSmemBytes = SMEM_BYTES;
    cudaLaunchAttribute at[1];
    at[0].id = cudaLaunchAttributeClusterDimension;
    at[0].val.clusterDim.x = 2; at[0].val.clusterDim.y = 1; at[0].val.clusterDim.z = 1;
    cfg.attrs = at;
    cfg.numAttrs = 1;
    if (cudaOccupancyMaxActiveClusters(&clusters, fused_layers_kernel<true>, &cfg) != cudaSuccess) (void)cudaGetLastError();
    by_smid = sms == 132 && clusters == 66;
  }
  Maps p;
  Scalars sc;
  make_act(enc, &p.xin, d_in[0], DM, true);
  make_act(enc, &p.out, d_out, DM, true);
  make_act(enc, &p.out_w, d_out, DM, true, 1);
  make_act(enc, &p.att, att, DM, false);
  make_act(enc, &p.h, hbuf, FF, false);
  make_2d(enc, &p.att_st, att, DM, SEQ, 32);
  make_2d(enc, &p.h_st, hbuf, FF, SEQ, 32);
  make_2d(enc, &p.w1c, d_in[4], FF, DM, 32);
  make_3d(enc, &p.wqkv, d_in[1], DM, DM, 3, 3 * DM * 2, DM * 2, 3);
  make_3d(enc, &p.wo, d_in[2], 64, DM, DM / 64, DM * 2, 128, 2);
  make_3d(enc, &p.w1a, d_in[4], 64, DM, FF / 64, FF * 2, 128, 3);
  make_3d(enc, &p.w1b, d_in[4], 64, DM, FF / 64, FF * 2, 128, 2);
  make_3d(enc, &p.w2, d_in[6], 64, FF, DM / 64, DM * 2, 128, 2);
  sc.b1 = (const __nv_bfloat16*)d_in[5];
  sc.b2 = (const __nv_bfloat16*)d_in[7];
  sc.g = (Scratch*)scratch;
  sc.zero = 0;
  if (by_smid) fused_layers_kernel<true><<<132, 384, SMEM_BYTES>>>(sc, p);
  else fused_layers_kernel<false><<<NCTA, 384, SMEM_BYTES>>>(sc, p);
}
```

```cpp
#include <cuda_runtime.h>
#include <cuda_bf16.h>
#include <cuda.h>
#include <stdint.h>

namespace {

constexpr int SEQ = 2048, DM = 1024, FF = 3584;
constexpr int NCTA = 128;
constexpr int NBAR = 5;

constexpr uint32_t RING_UNITS = 20, UNIT = 8192;
constexpr uint32_t OFF_X   = RING_UNITS * UNIT;
constexpr uint32_t OFF_STG = OFF_X + 32768;
constexpr uint32_t OFF_HLP = OFF_STG + 16384;
constexpr uint32_t OFF_RUN = OFF_STG + 24576;
constexpr uint32_t OFF_CSQ = OFF_RUN + 512;
constexpr uint32_t OFF_CSF = OFF_CSQ + 2048;
constexpr uint32_t OFF_ROW = OFF_CSF + 3584;
constexpr uint32_t OFF_BAR = OFF_ROW + 1024;
constexpr uint32_t SMEM_BYTES = OFF_BAR + 384;
constexpr uint32_t BAR_FULL = OFF_BAR, BAR_EMPTY = OFF_BAR + 8 * NBAR;
constexpr uint32_t BAR_XRDY = OFF_BAR + 80;
constexpr uint32_t BAR_DUMMY = OFF_BAR + 96, OFF_TAG = OFF_BAR + 104, OFF_ZERO = OFF_BAR + 112;
constexpr uint32_t BAR_PUB = OFF_BAR + 128;
constexpr uint32_t BAR_CSLD = OFF_BAR + 200;
constexpr uint32_t BAR_XGO = OFF_BAR + 224;
constexpr uint32_t BAR_BIAS = OFF_BAR + 216;

constexpr uint64_t DESC_A = (1ull << 62) | ((uint64_t)(2048 >> 4) << 32) | (1ull << 16);
constexpr uint64_t DESC_B = (1ull << 62) | ((uint64_t)(1024 >> 4) << 32) | ((uint64_t)(4096 >> 4) << 16);

constexpr int BAR_INIT = 0, BAR_ORDER = 1, BAR_GUARD = 3, BAR_WG = 5, BAR_GO = 7, BAR_DONE = 8, BAR_HLP = 9, BAR_INIT0 = 10, BAR_PAIR = 11;
#define GELU_DEP 2
#define MAP 2
#define LATE_O 1
#define HALO_NS 200
#define STG_WAIT 5
#define STAT_NS 800
#define BDELAY 400
#define STAG5 450
#define STAG4 0
#define STAG3 0
#define PACE0 0
#define PACE_M 100
#define PACE_N 300
#define CS_NS 500
#define BSPLIT 50
#define EARLY_STATS 1
#define WIN1 8
#define WIN2 2

struct Scratch {
  uint4 stats[4 * 8 * SEQ];
  uint4 halo[2 * 2 * 16 * 8 * 384];
  uint4 csp[2 * 8 * 17 * 224];
  uint32_t flags[16 * 32];
  uint32_t epoch[NCTA + 4];
};

struct Maps {
  CUtensorMap xin, out, att, h, wqkv, wo, w1a, w1b, w2, att_st, h_st, w1c, out_w;
};
struct Scalars {
  Scratch* g;
  const __nv_bfloat16 *b1, *b2;
  uint32_t zero;
};
struct Params : Scalars {
  const Maps& t;
};

__device__ __nv_bfloat16 g_att[SEQ * DM];
__device__ __nv_bfloat16 g_h[SEQ * FF];
__device__ Scratch g_scratch;
#define PROF_T(idx)
#define PROF_U(k)
#define PROF_S(g)
#define PROF_E(i, k)

__device__ __forceinline__ void mbar_init(uint32_t bar, int cnt) {
  asm volatile("mbarrier.init.shared::cta.b64 [%0], %1;" ::"r"(bar), "r"(cnt));
}
__device__ __forceinline__ void mbar_expect_tx(uint32_t bar, uint32_t bytes) {
  asm volatile("mbarrier.arrive.expect_tx.shared::cta.b64 _, [%0], %1;" ::"r"(bar), "r"(bytes) : "memory");
}
__device__ __forceinline__ void mbar_arrive(uint32_t bar) {
  asm volatile("mbarrier.arrive.shared::cta.b64 _, [%0];" ::"r"(bar) : "memory");
}
__device__ __forceinline__ bool mbar_test(uint32_t bar, uint32_t parity) {
  uint32_t ok;
  asm volatile("{\n.reg .pred p;\nmbarrier.test_wait.parity.shared::cta.b64 p, [%1], %2;\nselp.u32 %0, 1, 0, p;\n}"
               : "=r"(ok) : "r"(bar), "r"(parity) : "memory");
  return ok;
}
__device__ __forceinline__ void mbar_wait(uint32_t bar, uint32_t parity) {
  asm volatile(
      "{\n.reg .pred p;\n.reg .u32 it;\nmov.u32 it, 0;\n"
      "WAIT_LOOP:\n"
      "mbarrier.try_wait.parity.shared::cta.b64 p, [%0], %1;\n"
      "@p bra WAIT_DONE;\n"
      "add.u32 it, it, 1;\n"
      "setp.lt.u32 p, it, 0x400000;\n"
      "@p bra WAIT_LOOP;\n"
      "trap;\n"
      "WAIT_DONE:\n}"
      ::"r"(bar), "r"(parity) : "memory");
}
__device__ __forceinline__ void bar_sync(int id, int n) { asm volatile("bar.sync %0, %1;" ::"r"(id), "r"(n) : "memory"); }
__device__ __forceinline__ void bar_arrive(int id, int n) { asm volatile("bar.arrive %0, %1;" ::"r"(id), "r"(n) : "memory"); }
__device__ __forceinline__ void tma_ld2(uint32_t dst, const CUtensorMap* m, uint32_t bar, int c0, int c1) {
  asm volatile("cp.async.bulk.tensor.2d.shared::cluster.global.mbarrier::complete_tx::bytes [%0], [%1, {%3, %4}], [%2];"
               ::"r"(dst), "l"(m), "r"(bar), "r"(c0), "r"(c1) : "memory");
}
__device__ __forceinline__ void tma_ld_act(uint32_t dst, const CUtensorMap* m, uint32_t bar, int col, int blk) {
  asm volatile("cp.async.bulk.tensor.4d.shared::cluster.global.mbarrier::complete_tx::bytes [%0], [%1, {%3, %5, %5, %4}], [%2];"
               ::"r"(dst), "l"(m), "r"(bar), "r"(col), "r"(2 * blk), "r"(0) : "memory");
}
__device__ __forceinline__ void tma_st_act(const CUtensorMap* m, uint32_t src, int col, int blk) {
  asm volatile("cp.async.bulk.tensor.4d.global.shared::cta.bulk_group [%0, {%2, %4, %4, %3}], [%1];"
               ::"l"(m), "r"(src), "r"(col), "r"(2 * blk), "r"(0) : "memory");
}
__device__ __forceinline__ void tma_st_warp(const CUtensorMap* m, uint32_t src, int col, int blk, int w) {
  asm volatile("cp.async.bulk.tensor.4d.global.shared::cta.bulk_group [%0, {%2, %5, %3, %4}], [%1];"
               ::"l"(m), "r"(src), "r"(col), "r"(w & 1), "r"(2 * blk + (w >> 1)), "r"(0) : "memory");
}
__device__ __forceinline__ void tma_ld3(uint32_t dst, const CUtensorMap* m, uint32_t bar, int c0, int c1, int c2) {
  asm volatile("cp.async.bulk.tensor.3d.shared::cluster.global.mbarrier::complete_tx::bytes [%0], [%1, {%3, %4, %5}], [%2];"
               ::"r"(dst), "l"(m), "r"(bar), "r"(c0), "r"(c1), "r"(c2) : "memory");
}
__device__ __forceinline__ void tma_ld3_pair(uint32_t dst, const CUtensorMap* m, uint32_t bar, int c0, int c1, int c2) {
  asm volatile("cp.async.bulk.tensor.3d.shared::cluster.global.mbarrier::complete_tx::bytes.multicast::cluster"
               " [%0], [%1, {%3, %4, %5}], [%2], %6;"
               ::"r"(dst), "l"(m), "r"(bar), "r"(c0), "r"(c1), "r"(c2), "h"((uint16_t)3) : "memory");
}
__device__ __forceinline__ uint32_t pair_offset(uint32_t sb, uint32_t rank) {
  uint32_t r;
  asm volatile("mapa.shared::cluster.u32 %0, %1, %2;" : "=r"(r) : "r"(sb), "r"(rank));
  return r - sb;
}
__device__ __forceinline__ void mbar_arrive_cluster(uint32_t bar) {
  asm volatile("mbarrier.arrive.shared::cluster.b64 _, [%0];" ::"r"(bar) : "memory");
}
__device__ __forceinline__ void cluster_arrive() { asm volatile("barrier.cluster.arrive.relaxed;" ::: "memory"); }
__device__ __forceinline__ void cluster_wait() { asm volatile("barrier.cluster.wait.acquire;" ::: "memory"); }
__device__ __forceinline__ void tma_st2(const CUtensorMap* m, uint32_t src, int c0, int c1) {
  asm volatile("cp.async.bulk.tensor.2d.global.shared::cta.bulk_group [%0, {%2, %3}], [%1];"
               ::"l"(m), "r"(src), "r"(c0), "r"(c1) : "memory");
}
__device__ __forceinline__ void bulk_commit() { asm volatile("cp.async.bulk.commit_group;" ::: "memory"); }
__device__ __forceinline__ void bulk_wait_read() { asm volatile("cp.async.bulk.wait_group.read 0;" ::: "memory"); }
__device__ __forceinline__ void bulk_wait_all() { asm volatile("cp.async.bulk.wait_group 0;" ::: "memory"); }
__device__ __forceinline__ void fence_async_smem() { asm volatile("fence.proxy.async.shared::cta;" ::: "memory"); }
__device__ __forceinline__ void fence_async_global() { asm volatile("fence.proxy.async.global;" ::: "memory"); }
__device__ __forceinline__ void st_relaxed(uint32_t* p, uint32_t v) {
  asm volatile("st.relaxed.gpu.global.u32 [%0], %1;" ::"l"(p), "r"(v) : "memory");
}
__device__ __forceinline__ void st_msg(uint4* p, uint32_t a, uint32_t b, uint32_t c, uint32_t tag) {
  asm volatile("{\n.reg .b128 v;\nmov.b128 v, {%1, %2, %3, %4};\nst.relaxed.gpu.global.b128 [%0], v;\n}"
               ::"l"(p), "r"(a), "r"(b), "r"(c), "r"(tag) : "memory");
}
__device__ __forceinline__ void ld_msg(const uint4* p, uint32_t& a, uint32_t& b, uint32_t& c, uint32_t& tag) {
  asm volatile("{\n.reg .b128 v;\nld.relaxed.gpu.global.b128 v, [%4];\nmov.b128 {%0, %1, %2, %3}, v;\n}"
               : "=r"(a), "=r"(b), "=r"(c), "=r"(tag) : "l"(p) : "memory");
}
__device__ __forceinline__ bool elect_one() {
  uint32_t ok;
  asm volatile("{\n.reg .pred p;\nelect.sync _|p, 0xffffffff;\nselp.u32 %0, 1, 0, p;\n}" : "=r"(ok));
  return ok;
}
__device__ __forceinline__ uint32_t lanemask_lt() {
  uint32_t v;
  asm("mov.u32 %0, %%lanemask_lt;" : "=r"(v));
  return v;
}
__device__ __forceinline__ int uniform(int v) { return __shfl_sync(0xffffffffu, v, 0); }
__device__ __forceinline__ uint32_t pack_bf16(float lo, float hi) {
  uint32_t r;
  asm("cvt.rn.bf16x2.f32 %0, %1, %2;" : "=r"(r) : "f"(hi), "f"(lo));
  return r;
}
__device__ __forceinline__ float prmt_f(uint32_t a, uint32_t sel) {
  float r;
  asm("{\n.reg .b32 t;\nprmt.b32 t, %1, 0, %2;\nmov.b32 %0, t;\n}" : "=f"(r) : "r"(a), "r"(sel));
  return r;
}
__device__ __forceinline__ float bf_lo(uint32_t v) { return __uint_as_float(v << 16); }
__device__ __forceinline__ float bf_hi(uint32_t v) { return __uint_as_float(v & 0xffff0000u); }
__device__ __forceinline__ void stsm4(uint32_t addr, uint32_t r0, uint32_t r1, uint32_t r2, uint32_t r3) {
  asm volatile("stmatrix.sync.aligned.m8n8.x4.shared.b16 [%0], {%1, %2, %3, %4};"
               ::"r"(addr), "r"(r0), "r"(r1), "r"(r2), "r"(r3) : "memory");
}
__device__ __forceinline__ void ldsm4(uint32_t addr, uint32_t& r0, uint32_t& r1, uint32_t& r2, uint32_t& r3) {
  asm volatile("ldmatrix.sync.aligned.m8n8.x4.shared.b16 {%0, %1, %2, %3}, [%4];"
               : "=r"(r0), "=r"(r1), "=r"(r2), "=r"(r3) : "r"(addr) : "memory");
}
__device__ __forceinline__ uint32_t movtrans(uint32_t a) {
  uint32_t d;
  asm volatile("movmatrix.sync.aligned.m8n8.trans.b16 %0, %1;" : "=r"(d) : "r"(a));
  return d;
}
__device__ __forceinline__ void mma16816(float (&c)[4], uint32_t a0, uint32_t a1, uint32_t a2, uint32_t a3, uint32_t b0, uint32_t b1) {
  asm volatile("mma.sync.aligned.m16n8k16.row.col.f32.bf16.bf16.f32 {%0,%1,%2,%3}, {%4,%5,%6,%7}, {%8,%9}, {%0,%1,%2,%3};"
               : "+f"(c[0]), "+f"(c[1]), "+f"(c[2]), "+f"(c[3])
               : "r"(a0), "r"(a1), "r"(a2), "r"(a3), "r"(b0), "r"(b1));
}
__device__ __forceinline__ void mma1688(float (&c)[4], uint32_t a0, uint32_t a1, uint32_t b0) {
  asm volatile("mma.sync.aligned.m16n8k8.row.col.f32.bf16.bf16.f32 {%0,%1,%2,%3}, {%4,%5}, {%6}, {%0,%1,%2,%3};"
               : "+f"(c[0]), "+f"(c[1]), "+f"(c[2]), "+f"(c[3]) : "r"(a0), "r"(a1), "r"(b0));
}
__device__ __forceinline__ float2 lds_f2(uint32_t a) {
  float2 v;
  asm volatile("ld.shared.v2.f32 {%0, %1}, [%2];" : "=f"(v.x), "=f"(v.y) : "r"(a) : "memory");
  return v;
}
__device__ __forceinline__ float4 lds_f4(uint32_t a) {
  float4 v;
  asm volatile("ld.shared.v4.f32 {%0, %1, %2, %3}, [%4];" : "=f"(v.x), "=f"(v.y), "=f"(v.z), "=f"(v.w) : "r"(a) : "memory");
  return v;
}
__device__ __forceinline__ float lds_f(uint32_t a) {
  float v;
  asm volatile("ld.shared.f32 %0, [%1];" : "=f"(v) : "r"(a) : "memory");
  return v;
}
__device__ __forceinline__ uint32_t lds_u(uint32_t a) {
  uint32_t v;
  asm volatile("ld.shared.u32 %0, [%1];" : "=r"(v) : "r"(a) : "memory");
  return v;
}
__device__ __forceinline__ void sts_f2(uint32_t a, float x, float y) {
  asm volatile("st.shared.v2.f32 [%0], {%1, %2};" ::"r"(a), "f"(x), "f"(y) : "memory");
}
__device__ __forceinline__ void sts_u4(uint32_t a, uint32_t x, uint32_t y, uint32_t z, uint32_t w) {
  asm volatile("st.shared.v4.u32 [%0], {%1, %2, %3, %4};" ::"r"(a), "r"(x), "r"(y), "r"(z), "r"(w) : "memory");
}
__device__ __forceinline__ void lds_u4(uint32_t a, uint32_t& x, uint32_t& y, uint32_t& z, uint32_t& w) {
  asm volatile("ld.shared.v4.u32 {%0, %1, %2, %3}, [%4];" : "=r"(x), "=r"(y), "=r"(z), "=r"(w) : "r"(a) : "memory");
}
__device__ __forceinline__ float ex2(float x) {
  float y;
  asm("ex2.approx.ftz.f32 %0, %1;" : "=f"(y) : "f"(x));
  return y;
}
__device__ __forceinline__ float rcp_hw(float x) {
  float y;
  asm("rcp.approx.ftz.f32 %0, %1;" : "=f"(y) : "f"(x));
  return y;
}
__device__ __forceinline__ float tanh_hw(float x) {
  float y;
  asm("tanh.approx.f32 %0, %1;" : "=f"(y) : "f"(x));
  return y;
}
__device__ __forceinline__ float quad_sum(float v) {
  v += __shfl_xor_sync(0xffffffffu, v, 1);
  return v + __shfl_xor_sync(0xffffffffu, v, 2);
}
__device__ __forceinline__ float quad_max(float v) {
  v = fmaxf(v, __shfl_xor_sync(0xffffffffu, v, 1));
  return fmaxf(v, __shfl_xor_sync(0xffffffffu, v, 2));
}

template <int N> __device__ __forceinline__ void wgmma_ss(float (&d)[96], uint64_t da, uint64_t db, uint32_t keep = 1);
template <> __device__ __forceinline__ void wgmma_ss<128>(float (&d)[96], uint64_t da, uint64_t db, uint32_t keep) {
  asm volatile(
      "{\n.reg .pred p;\nsetp.ne.u32 p, %66, 0;\n"
      "wgmma.mma_async.sync.aligned.m64n128k16.f32.bf16.bf16 {%0, %1, %2, %3, %4, %5, %6, %7, %8, %9, %10, %11, %12, %13, %14, %15, %16, %17, %18, %19, %20, %21, %22, %23, %24, %25, %26, %27, %28, %29, %30, %31, %32, %33, %34, %35, %36, %37, %38, %39, %40, %41, %42, %43, %44, %45, %46, %47, %48, %49, %50, %51, %52, %53, %54, %55, %56, %57, %58, %59, %60, %61, %62, %63}, %64, %65, p, 1, 1, 0, 1;\n}"
      : "+f"(d[0]), "+f"(d[1]), "+f"(d[2]), "+f"(d[3]), "+f"(d[4]), "+f"(d[5]), "+f"(d[6]), "+f"(d[7]), "+f"(d[8]), "+f"(d[9]), "+f"(d[10]), "+f"(d[11]), "+f"(d[12]), "+f"(d[13]), "+f"(d[14]), "+f"(d[15]), "+f"(d[16]), "+f"(d[17]), "+f"(d[18]), "+f"(d[19]), "+f"(d[20]), "+f"(d[21]), "+f"(d[22]), "+f"(d[23]), "+f"(d[24]), "+f"(d[25]), "+f"(d[26]), "+f"(d[27]), "+f"(d[28]), "+f"(d[29]), "+f"(d[30]), "+f"(d[31]), "+f"(d[32]), "+f"(d[33]), "+f"(d[34]), "+f"(d[35]), "+f"(d[36]), "+f"(d[37]), "+f"(d[38]), "+f"(d[39]), "+f"(d[40]), "+f"(d[41]), "+f"(d[42]), "+f"(d[43]), "+f"(d[44]), "+f"(d[45]), "+f"(d[46]), "+f"(d[47]), "+f"(d[48]), "+f"(d[49]), "+f"(d[50]), "+f"(d[51]), "+f"(d[52]), "+f"(d[53]), "+f"(d[54]), "+f"(d[55]), "+f"(d[56]), "+f"(d[57]), "+f"(d[58]), "+f"(d[59]), "+f"(d[60]), "+f"(d[61]), "+f"(d[62]), "+f"(d[63])
      : "l"(da), "l"(db), "r"(keep));
}

template <> __device__ __forceinline__ void wgmma_ss<192>(float (&d)[96], uint64_t da, uint64_t db, uint32_t keep) {
  asm volatile(
      "{\n.reg .pred p;\nsetp.ne.u32 p, %98, 0;\n"
      "wgmma.mma_async.sync.aligned.m64n192k16.f32.bf16.bf16 {%0, %1, %2, %3, %4, %5, %6, %7, %8, %9, %10, %11, %12, %13, %14, %15, %16, %17, %18, %19, %20, %21, %22, %23, %24, %25, %26, %27, %28, %29, %30, %31, %32, %33, %34, %35, %36, %37, %38, %39, %40, %41, %42, %43, %44, %45, %46, %47, %48, %49, %50, %51, %52, %53, %54, %55, %56, %57, %58, %59, %60, %61, %62, %63, %64, %65, %66, %67, %68, %69, %70, %71, %72, %73, %74, %75, %76, %77, %78, %79, %80, %81, %82, %83, %84, %85, %86, %87, %88, %89, %90, %91, %92, %93, %94, %95}, %96, %97, p, 1, 1, 0, 1;\n}"
      : "+f"(d[0]), "+f"(d[1]), "+f"(d[2]), "+f"(d[3]), "+f"(d[4]), "+f"(d[5]), "+f"(d[6]), "+f"(d[7]), "+f"(d[8]), "+f"(d[9]), "+f"(d[10]), "+f"(d[11]), "+f"(d[12]), "+f"(d[13]), "+f"(d[14]), "+f"(d[15]), "+f"(d[16]), "+f"(d[17]), "+f"(d[18]), "+f"(d[19]), "+f"(d[20]), "+f"(d[21]), "+f"(d[22]), "+f"(d[23]), "+f"(d[24]), "+f"(d[25]), "+f"(d[26]), "+f"(d[27]), "+f"(d[28]), "+f"(d[29]), "+f"(d[30]), "+f"(d[31]), "+f"(d[32]), "+f"(d[33]), "+f"(d[34]), "+f"(d[35]), "+f"(d[36]), "+f"(d[37]), "+f"(d[38]), "+f"(d[39]), "+f"(d[40]), "+f"(d[41]), "+f"(d[42]), "+f"(d[43]), "+f"(d[44]), "+f"(d[45]), "+f"(d[46]), "+f"(d[47]), "+f"(d[48]), "+f"(d[49]), "+f"(d[50]), "+f"(d[51]), "+f"(d[52]), "+f"(d[53]), "+f"(d[54]), "+f"(d[55]), "+f"(d[56]), "+f"(d[57]), "+f"(d[58]), "+f"(d[59]), "+f"(d[60]), "+f"(d[61]), "+f"(d[62]), "+f"(d[63]), "+f"(d[64]), "+f"(d[65]), "+f"(d[66]), "+f"(d[67]), "+f"(d[68]), "+f"(d[69]), "+f"(d[70]), "+f"(d[71]), "+f"(d[72]), "+f"(d[73]), "+f"(d[74]), "+f"(d[75]), "+f"(d[76]), "+f"(d[77]), "+f"(d[78]), "+f"(d[79]), "+f"(d[80]), "+f"(d[81]), "+f"(d[82]), "+f"(d[83]), "+f"(d[84]), "+f"(d[85]), "+f"(d[86]), "+f"(d[87]), "+f"(d[88]), "+f"(d[89]), "+f"(d[90]), "+f"(d[91]), "+f"(d[92]), "+f"(d[93]), "+f"(d[94]), "+f"(d[95])
      : "l"(da), "l"(db), "r"(keep));
}

template <int R>
__device__ __forceinline__ void pin_regs(float (&a)[2][96]) {
#pragma unroll
  for (int m = 0; m < 2; m++)
#pragma unroll
    for (int i = 0; i < R; i++) asm volatile("" : "+f"(a[m][i])::"memory");
}

struct Ctx {
  uint32_t sb;
  int m, n, wg, w, lane;
};
__device__ __forceinline__ Ctx make_ctx(uint32_t sb, int id) {
  int lane;
  asm volatile("mov.u32 %0, %%laneid;" : "=r"(lane));
  asm volatile("" : "+r"(id), "+r"(sb));
  return Ctx{sb, (id >> 3) & 15, id & 7, id >> 9, (id >> 7) & 3, lane};
}
#define UNPACK_CTX(c) const uint32_t sb = c.sb; const int m = c.m, n = c.n, wg = c.wg, w = c.w, lane = c.lane

__device__ __forceinline__ uint32_t poll_line(const uint32_t* word, uint32_t target, uint32_t need) {
  uint32_t v;
  asm volatile(
      "{\n.reg .pred p;\n.reg .u32 it, m;\n.reg .s32 d;\nmov.u32 it, 0;\n"
      "POLL_LOOP:\n"
      "ld.relaxed.gpu.global.u32 %0, [%1];\n"
      "sub.s32 d, %0, %2;\n"
      "setp.ge.s32 p, d, 0;\n"
      "vote.sync.ballot.b32 m, p, 0xffffffff;\n"
      "and.b32 m, m, %3;\n"
      "setp.eq.u32 p, m, %3;\n"
      "@p bra.uni POLL_DONE;\n"
      "add.u32 it, it, 1;\n"
      "setp.lt.u32 p, it, 0x400000;\n"
      "@p bra.uni POLL_LOOP;\n"
      "trap;\n"
      "POLL_DONE:\n}"
      : "=&r"(v) : "l"(word), "r"(target), "r"(need) : "memory");
  return v;
}
__device__ __forceinline__ uint32_t ld_relaxed(const uint32_t* p) {
  uint32_t v;
  asm volatile("ld.relaxed.gpu.global.u32 %0, [%1];" : "=r"(v) : "l"(p) : "memory");
  return v;
}
__device__ __forceinline__ float chain(float x, uint32_t on, uint32_t zero) {
  return __uint_as_float(__float_as_uint(x) | (on & zero));
}
constexpr int MSG_SPINS = 1 << 20;

constexpr int STAGES_PER_LAYER = 152;
__device__ __forceinline__ int nib(uint64_t v, int i) { return (int)(v >> (4 * i)) & 15; }
__device__ __forceinline__ bool tile_wide(int t) { return (0x23 >> t) & 1; }
__device__ __forceinline__ void weight_coords(const Params& p, int t, int n, const CUtensorMap*& map, int& c0, int& c2) {
  map = &p.t.wqkv + nib(0x4233100ull, t);
  c0 = t < 2 ? 128 * n + 64 * t : 0;
  c2 = t < 2 ? 0 : (t == 2 || t == 6) ? 2 * n : 7 * n + 2 * t - 6;
}

template <bool IS_A>
__device__ __forceinline__ void producer(const Params& p, uint32_t sb, int m, int n, int lane) {
  const uint32_t low = (1u << (4 * n)) - 1, others = (0x6543210u & low) | (0x7654321u & ~low);
  const uint64_t order_x = (uint64_t)(others * 2 + 0x1111111u) << 36 | (uint64_t)others * 2 << 8 | (n * 0x22 + 0x10);
  int inflight = 4, cur = 0;
  uint32_t fb = sb + BAR_FULL + 32, rb = sb + BAR_EMPTY, rph = 0, pos = 0, tag32 = 0, seen = 0;
  const uint32_t fend = sb + BAR_FULL + 8 * NBAR, rend = sb + BAR_EMPTY + 8 * NBAR;
  const uint32_t* word = p.g->flags + m * 32 + (lane < 16 ? lane >> 1 : lane & 7);
#pragma unroll 1
  for (int sg = 1; sg < 22; sg++) {
    const int layer = sg >= 11, s = sg == 1 ? 2 : sg == 2 ? 1 : sg - 11 * layer;
    const int t = nib(0x65434321010ull, s), kind = nib(0x32110031100ull, s);
    const bool wide = tile_wide(t);
    const uint32_t bbytes = wide ? 3 * UNIT : 2 * UNIT, base = sb + (IS_A ? bbytes : (m & 1) * (bbytes / 2));
    if (IS_A && kind == 0) {
      if (sg == 2) seen = tag32 = (__ldcg(p.g->epoch + m * 8 + n) + 1) << 5;
#pragma unroll 1
      for (int k = 0; k < 2; k++) {
#pragma unroll 1
        for (; inflight > (wide ? 3 : 4); inflight--) {
          mbar_wait(rb, rph);
          rb += 8;
          if (rb == rend) { rb -= 8 * NBAR; rph ^= 1; }
        }
        if (elect_one()) mbar_arrive(fb);
        inflight++;
        fb += 8;
        if (fb == fend) fb -= 8 * NBAR;
        pos += bbytes + 2 * UNIT;
        if (pos >= RING_UNITS * UNIT) pos -= RING_UNITS * UNIT;
      }
      continue;
    }
    const int mul = t == 6 ? 448 : t == 2 ? 128 : 64, count = sg == 1 ? 12 : 2 * nib(0x4871ull, kind);
    uint64_t order0 = sg == 1 ? 0xFEDCBA987654ull : kind == 3 ? 0x76543210u : order_x >> (8 * (kind & 1));
    uint32_t special = (s == 4 || s == 10) ? 0x10 : s == 9 ? 0xF : s == 0;
    if (IS_A) special |= (kind & 1 ? 0 : 3) | (count >= 4 ? 1u << (count - 4) : 0);
    if (s >= 9) pos = (s + 6) * UNIT;
    const CUtensorMap* map;
    int c0 = 0, c2 = 0, ev = 0;
    if (IS_A) {
      map = &p.t.xin + (t == 2 ? 2 : t == 6 ? 3 : sg >= 4);
      ev = 9 * layer + (t < 2 ? 0 : t == 2 ? 1 : t < 6 ? 4 : 5);
      if (elect_one()) asm volatile("prefetch.tensormap [%0];" ::"l"(map) : "memory");
    } else {
      weight_coords(p, t, n, map, c0, c2);
    }
#pragma unroll 1
    for (int add = 0; add < mul; add += 64) {
      uint64_t order = order0;
      const int need = kind == 3 ? ev : ev - 1 + (lane & 1), sh = kind == 3 ? 16 : 0;
      uint32_t ready = IS_A ? __ballot_sync(0xffffffffu, cur >= need) >> sh : 0;
#pragma unroll 1
      for (int k = 0; k < count; k++) {
        const int code = order & 15, kc = code * mul + add;
        order >>= 4;
        if ((special >> k) & 1) {
          const int lag = wide ? (s == 9 && k == 2 ? 2 : 3) : ((s == 4 || s == 10) && add == 0 && k < 4) ? 3 : 4;
#pragma unroll 1
          for (; inflight > lag; inflight--) {
            mbar_wait(rb, rph);
            rb += 8;
            if (rb == rend) { rb -= 8 * NBAR; rph ^= 1; }
          }
          inflight++;
          if (IS_A) {
            if (kind == 3 ? t == 2 && add + k == 64 : !(kind & 1) && k < 2) {
              if (t == 2) mbar_wait(sb + BAR_PUB + 8, layer);
              if (elect_one()) mbar_arrive(fb);
              goto next_stage;
            }
            if (k == count - 4 && sg >= 3) seen = ld_relaxed(word);
          }
        } else {
          mbar_wait(rb, rph);
          rb += 8;
          if (rb == rend) { rb -= 8 * NBAR; rph ^= 1; }
        }
        if (IS_A && !((ready >> code) & 1)) {
          cur = max(cur, (int)(seen - tag32));
          ready = __ballot_sync(0xffffffffu, cur >= need) >> sh;
          if (!((ready >> code) & 1)) {
            cur = (int)(poll_line(word, tag32 + need, 1u << (code + sh)) - tag32);
            ready = __ballot_sync(0xffffffffu, cur >= need) >> sh;
          }
          asm volatile("fence.acquire.gpu;" ::: "memory");
          fence_async_global();
          seen = ld_relaxed(word);
        }
        if (elect_one()) {
          if (!IS_A) tma_ld3_pair(base + pos, map, fb, c0, kc + 32 * (m & 1), c2);
          else tma_ld_act(base + pos, map, fb, kc, m);
          mbar_expect_tx(fb, IS_A ? 16384 : bbytes);
        }
      next_stage:
        fb += 8;
        if (fb == fend) fb -= 8 * NBAR;
        pos += bbytes + 2 * UNIT;
        if (pos >= RING_UNITS * UNIT) pos -= RING_UNITS * UNIT;
      }
      special = !IS_A ? 0 : t == 2 ? 1 : add == 128 ? 0x10 : 0;
      if (t == 2) order0 = others << 4 | n;
      if (IS_A && (t == 2 || add == 64 || add == 192)) ev++;
    }
  }
}

__device__ __forceinline__ void publisher(const Params& p, uint32_t sb, int m, int n) {
  {
    const int ts = PACE0 + PACE_M * m, tx = PACE0 + PACE_N * n;
#pragma unroll 1
    for (int k = 0; k < 2; k++) {
      __nanosleep(k == 0 ? min(ts, tx) : abs(ts - tx));
      if ((ts <= tx) == (k == 0)) {
        mbar_expect_tx(sb + BAR_CSLD, 24576);
        tma_ld3(sb + OFF_STG, &p.t.wqkv, sb + BAR_CSLD, 128 * n, 64 * m, 0);
        tma_ld3(sb + OFF_STG + 12288, &p.t.wqkv, sb + BAR_CSLD, 128 * n, 64 * m + 32, 0);
      } else {
#pragma unroll 1
        for (int h = 0; h < 2; h++) {
          const uint32_t xr = sb + BAR_XRDY + 8 * h;
          mbar_expect_tx(xr, 16384);
          tma_ld_act(sb + OFF_X + h * 16384, &p.t.xin, xr, 128 * n + 64 * h, m);
          asm volatile("mbarrier.arrive.shared::cta.b64 _, [%0], 3;" ::"r"(xr) : "memory");
        }
      }
    }
  }
  const uint32_t tag = __ldcg(p.g->epoch + m * 8 + n) + 1;
  uint32_t* word = p.g->flags + m * 32 + n;
  const int mn = m * 8 + n; (void)mn;
  st_relaxed(word, 32 * tag);
#pragma unroll 1
  for (int c = 0; c < 16; c++) {
    const int e = c >= 9 ? c - 9 : c;
    if (e == 2 || e == 7) {
      asm volatile("prefetch.tensormap [%0];" ::"l"(&p.t.out) : "memory");
      mbar_wait(sb + BAR_XRDY, e == 2);
      tma_st_act(&p.t.out, sb + OFF_X, 128 * n, m);
      bulk_commit();
      mbar_wait(sb + BAR_XRDY + 8, e == 2);
      bulk_wait_all();
      mbar_arrive(sb + BAR_XGO);
      PROF_E(7 * (c >= 9) + (e < 4 ? 2 : 6), 11);
    } else {
      mbar_wait(sb + BAR_PUB + 8 * e, c >= 9);
    }
    asm volatile("fence.release.gpu;" ::: "memory");
    asm volatile("red.relaxed.gpu.global.add.u32 [%0], 1;" ::"l"(word) : "memory");
    PROF_E(7 * (c >= 9) + nib(0x665432210ull, e), (0x108 >> e) & 1 ? 14 : 12);
  }
  p.g->epoch[m * 8 + n] = tag;
}

__device__ __forceinline__ void sum_rows(uint32_t buf, int iters, float (&a)[8], int lane) {
  uint32_t addr = buf + (lane >> 3) * 128 + (((lane & 7) ^ (lane >> 3)) << 4);
#pragma unroll 1
  for (int it = 0; it < iters; it++) {
    uint32_t u[2][4];
    lds_u4(addr, u[0][0], u[0][1], u[0][2], u[0][3]);
    lds_u4((addr ^ 64) + 512, u[1][0], u[1][1], u[1][2], u[1][3]);
    addr += 1024;
#pragma unroll
    for (int e = 0; e < 8; e++) { a[2 * (e & 3)] += bf_lo(u[e >> 2][e & 3]); a[2 * (e & 3) + 1] += bf_hi(u[e >> 2][e & 3]); }
  }
}
__device__ __forceinline__ void publish_sums(const float (&a)[8], uint4* dst, int lane, uint32_t tag) {
  const bool u8 = lane & 8, u16 = lane & 16;
  float h4[4], h2[2];
#pragma unroll
  for (int e = 0; e < 4; e++) h4[e] = (u8 ? a[4 + e] : a[e]) + __shfl_xor_sync(0xffffffffu, u8 ? a[e] : a[4 + e], 8);
#pragma unroll
  for (int e = 0; e < 2; e++) h2[e] = (u16 ? h4[2 + e] : h4[e]) + __shfl_xor_sync(0xffffffffu, u16 ? h4[e] : h4[2 + e], 16);
  st_msg(dst + (lane & 7) * 4 + (u8 ? 2 : 0) + (u16 ? 1 : 0), __float_as_uint(h2[0]), __float_as_uint(h2[1]), 0u, tag);
}

__device__ __forceinline__ void colsum_helper(const Params& p, uint32_t sb, int m, int n, int lane) {
  const uint32_t tag = __ldcg(p.g->epoch + m * 8 + n) + 1;
  const int mn = m * 8 + n; (void)mn;
#pragma unroll 1
  for (int k = lane; k < 288; k += 32) {
    const uint32_t bb = __ldg(reinterpret_cast<const uint32_t*>(k < 224 ? p.b1 + 448 * n : p.b2 + 128 * n - 448) + k);
    const float sc = k < 224 ? 0.5f : 1.f;
    sts_f2(sb + (k < 224 ? OFF_CSF + k * 16 + 8 : OFF_CSQ + 1536 + (k - 224) * 8), sc * bf_lo(bb), sc * bf_hi(bb));
  }
  __syncwarp();
  if (elect_one()) mbar_arrive(sb + BAR_BIAS);
  bar_sync(BAR_HLP, 160);
  {
    uint4* base = p.g->csp + n * 17 * 224 + 12 * m + min(lane & 15, 11);
    float s0 = 0.f, s1 = 0.f;
#pragma unroll 1
    for (int g = 0; g < 2; g++) {
      uint32_t x[4], y[4];
#pragma unroll 1
      for (int it = 0; it < MSG_SPINS; it++) {
        uint32_t bad = 0, z, tg;
        if (g == 0 || it > 0) __nanosleep(CS_NS);
#pragma unroll
        for (int k = 0; k < 4; k++) { ld_msg(base + (g * 8 + (lane >> 4) * 4 + k) * 224, x[k], y[k], z, tg); bad |= tg ^ tag; }
        if (__all_sync(0xffffffffu, bad == 0)) break;
      }
#pragma unroll
      for (int k = 0; k < 4; k++) { s0 += __uint_as_float(x[k]); s1 += __uint_as_float(y[k]); }
    }
    s0 += __shfl_xor_sync(0xffffffffu, s0, 16);
    s1 += __shfl_xor_sync(0xffffffffu, s1, 16);
    if (lane < 12) st_msg(base + 16 * 224, __float_as_uint(s0), __float_as_uint(s1), 0u, tag);
    PROF_E(-1, 3);
  }
  PROF_E(-1, 1);
#pragma unroll 1
  for (int c = 0; c < 7; c++) {
    float a[8] = {0.f, 0.f, 0.f, 0.f, 0.f, 0.f, 0.f, 0.f};
#pragma unroll 1
    for (int h = 0; h < 2; h++) {
      if (elect_one()) {
        mbar_expect_tx(sb + BAR_CSLD + 8, 4096);
        tma_ld2(sb + OFF_HLP, &p.t.w1c, sb + BAR_CSLD + 8, 448 * n + 64 * c, 64 * m + 32 * h);
        if (c < 6) asm volatile("cp.async.bulk.prefetch.tensor.2d.L2.global [%0, {%1, %2}];" ::"l"(&p.t.w1c), "r"(448 * n + 64 * c + 64), "r"(64 * m + 32 * h) : "memory");
      }
      mbar_wait(sb + BAR_CSLD + 8, h);
      sum_rows(sb + OFF_HLP, 4, a, lane);
      __syncwarp();
    }
    publish_sums(a, p.g->csp + ((8 + n) * 17 + m) * 224 + c * 32, lane, tag);
  }
  PROF_E(-1, 2);
  if (elect_one()) {
#pragma unroll 1
    for (int k = 0; k < 3; k++) {
      mbar_wait(sb + BAR_XGO, k & 1);
      __nanosleep(BDELAY);
#pragma unroll 1
      for (int w = 0; w < 4; w++) {
        tma_st_warp(&p.t.out_w, sb + OFF_X + 16384 + w * 4096, 128 * n + 64, m, w);
        bulk_commit();
        bulk_wait_read();
        if (w < 3) __nanosleep(BSPLIT);
      }
      bulk_wait_all();
      asm volatile("mbarrier.arrive.shared::cta.b64 _, [%0], 4;" ::"r"(sb + BAR_PUB + (k & 1 ? 64 : 24)) : "memory");
    }
  }
}

__device__ __forceinline__ void poll_msgs2(const uint4* pa, const uint4* pb, float (&v)[4], uint32_t tag) {
#pragma unroll 1
  for (int it = 0; it < MSG_SPINS; it++) {
    uint32_t x[4], z, ta, tb;
    ld_msg(pa, x[0], x[1], z, ta);
    ld_msg(pb, x[2], x[3], z, tb);
#pragma unroll
    for (int e = 0; e < 4; e++) v[e] = __uint_as_float(x[e]);
    if (__all_sync(0xffffffffu, ta == tag && tb == tag)) break;
  }
}
__device__ __forceinline__ void colsum_total(const Params& p, const Ctx& cx, int mat, uint32_t tag) {
  uint4* base = p.g->csp + (mat * 8 + cx.n) * 17 * 224;
  const int per = 12 + 2 * mat, k = 2 * cx.w + (cx.lane >> 4), ia = per * cx.m + k, ib = per * cx.m + min(k + 8, per - 1);
  float v[4];
  poll_msgs2(base + (cx.lane & 15) * 224 + ia, base + (cx.lane & 15) * 224 + ib, v, tag);
#pragma unroll 1
  for (int d = 1; d < 16; d *= 2)
#pragma unroll
    for (int e = 0; e < 4; e++) v[e] += __shfl_xor_sync(0xffffffffu, v[e], d);
  const bool hi = cx.lane & 1;
  if ((cx.lane & 14) == 0) st_msg(base + 16 * 224 + (hi ? ib : ia), __float_as_uint(hi ? v[2] : v[0]), __float_as_uint(hi ? v[3] : v[1]), 0u, tag);
}
__device__ __forceinline__ void colsum_gather(const Params& p, const Ctx& cx, int mat, uint32_t tag) {
  const uint4* base = p.g->csp + ((mat * 8 + cx.n) * 17 + 16) * 224;
  const int ia = cx.w * 32 + cx.lane, ib = min(ia + 128, 191 + 32 * mat);
  float v[4];
  poll_msgs2(base + ia, base + ib, v, tag);
  const uint32_t tab = cx.sb + (mat ? OFF_CSF : OFF_CSQ);
  sts_f2(tab + (ia << (3 + mat)), v[0], v[1]);
  sts_f2(tab + (ib << (3 + mat)), v[2], v[3]);
}

#define ACC(q, j, e) acc[(q) & 1][4 * (j) + 2 * ((q) >> 1) + (e)]

constexpr uint32_t RING16 = RING_UNITS * (UNIT >> 4);
__device__ __forceinline__ bool tile_split(int i) { return (0xD98 >> i) & 1; }

__device__ __forceinline__ void write_run_desc(uint32_t sb, int i, int step) {
  const int layer = i >= 7, t = i - 7 * layer, part = tile_split(i) ? step : 2;
  const bool wide = tile_wide(t), own = t != 2 && t != 6 && part != 1 && i != 0, second = t == 1 || t == 4;
  const uint32_t z16 = (wide ? 5 : 4) * (UNIT >> 4), a_off = z16 - 1024 + (uint32_t)DESC_A - (uint32_t)DESC_B;
  const int gl = 16 * t + (part == 2 ? 0 : second ? 16 * part - 14 : 4 * part), g0 = layer * STAGES_PER_LAYER + gl;
  const uint32_t s16 = (sb & 0x3FFFF) >> 4, bfirst = (uint32_t)DESC_B + s16;
  const int nkb = t == 6 ? 56 : part == 0 ? 2 : 12 + 2 * part;
  const bool win1 = t == 1 && part != 0;
  const int run = win1 ? WIN1 + 1 : t == 2 ? WIN2 + 1 : nkb;
  const int rest = win1 ? 64 | (nkb - 1 - WIN1) : t == 2 ? 64 | (7 - WIN2) | (8 << 7) : 0;
  const uint32_t blo = bfirst + z16 * (wide ? (gl + (t == 5 ? 3 : 0)) & 3 : (gl + 3) % 5);
  const uint32_t alo = own ? (uint32_t)DESC_A + s16 + (OFF_X >> 4) : blo + a_off;
  const uint32_t aoff = own ? alo + 1024 - (blo == bfirst + RING16 - z16 ? bfirst : blo + z16) : a_off;
  const bool xwait = part == 0 && !second, keep = !(part == 0 || t == 5);
  sts_u4(sb + OFF_RUN + (2 * i + step) * 16, blo, alo, aoff,
         ((g0 / NBAR) & 1) | xwait << 1 | keep << 2 | 8 * (g0 % NBAR) | run << 6 | rest << 12);
}

__device__ __forceinline__ void write_partial_stats(const Params& p, const Ctx& c, int ln, uint32_t tag) {
  const uint32_t xrow = c.sb + OFF_X + c.w * 4096 + c.lane * 128;
  float s = 0.f, q = 0.f, s1 = 0.f, q1 = 0.f;
#pragma unroll 4
  for (int j = 0; j < 16; j++) {
    uint32_t u[4];
    lds_u4(xrow + (j >> 3) * 16384 + (((j & 7) ^ (c.lane & 7)) << 4), u[0], u[1], u[2], u[3]);
#pragma unroll
    for (int e = 0; e < 4; e++) {
      const float a = bf_lo(u[e]), d = bf_hi(u[e]);
      s += a; q = fmaf(a, a, q);
      s1 += d; q1 = fmaf(d, d, q1);
    }
  }
  s += s1;
  q += q1;
  st_msg(p.g->stats + (ln * 8 + c.n) * SEQ + 128 * c.m + 32 * c.w + c.lane, __float_as_uint(s),
         __float_as_uint(fmaxf(q - s * s * (1.f / 128.f), 0.f)), 0u, tag);
}

template <int N>
__device__ __forceinline__ void mainloop(const Params& p, float (&acc)[2][96], uint32_t sb, int i, int step, int mn) {
  constexpr uint32_t Z16 = (2 + N / 64) * (UNIT >> 4);
  constexpr uint32_t A_OFF = Z16 - 1024 + (uint32_t)DESC_A - (uint32_t)DESC_B;
  const int wg = i & 1;
  const uint32_t s16 = (sb & 0x3FFFF) >> 4;
  const uint32_t blast = (uint32_t)DESC_B + s16 + RING16 - Z16, flast = sb + BAR_FULL + 8 * (NBAR - 1);
  uint32_t blo = (uint32_t)DESC_B + s16, alo = blo + A_OFF, aoff = A_OFF, misc = 16 << 6;
  if (N == 128 || i > 0) lds_u4(sb + OFF_RUN + (2 * i + step) * 16, blo, alo, aoff, misc);
  uint32_t keep = misc & 4;
  int run = (misc >> 6) & 63, rest = misc >> 12;
  uint32_t fb = sb + BAR_FULL + (misc & 0x38), ph = misc & 1;
  uint32_t prev = sb + BAR_DUMMY - 8 * NBAR;
  const uint32_t lane_id = __popc(__ballot_sync(0xffffffffu, true) & lanemask_lt()), rel = pair_offset(sb, lane_id & 1) + 8 * NBAR;
  pin_regs<N / 2>(acc);
  if (N == 128 || i > 0) bar_sync(BAR_ORDER + wg, 256);
  else bar_sync(BAR_INIT0, 160);
  if (N == 192 && i == 0 && threadIdx.x == 0) PROF_U(8);
  mbar_wait(fb, ph);
  if (N == 192 && i == 0 && threadIdx.x == 0) PROF_U(9);
  if (N == 192 && i == 0) cluster_wait();
  if (misc & 2) mbar_wait(sb + BAR_XGO, N == 192);
  if (step == 0 || !tile_split(i)) PROF_T(4 + i * 4);
  if (step == 1 && tile_split(i)) PROF_E(i, 13);
#pragma unroll 1
  while (true) {
    const uint64_t da = (DESC_A & ~0xffffffffull) | alo, db = (DESC_B & ~0xffffffffull) | blo;
    asm volatile("wgmma.fence.sync.aligned;" ::: "memory");
    wgmma_ss<N>(acc[0], da, db, keep);
    wgmma_ss<N>(acc[1], da + 64, db, keep);
    keep = 4;
    wgmma_ss<N>(acc[0], da + 2, db + 128);
    wgmma_ss<N>(acc[1], da + 66, db + 128);
    asm volatile("wgmma.commit_group.sync.aligned;" ::: "memory");
    asm volatile("wgmma.wait_group.sync.aligned 1;" ::: "memory");
    PROF_S(jj++);
    if (lane_id < 2) mbar_arrive_cluster(prev + rel);
    prev = fb;
    if (fb == flast) { fb -= 8 * NBAR; ph++; }
    fb += 8;
    if (blo == blast) blo -= RING16;
    blo += Z16;
    alo = blo + aoff;
    aoff = A_OFF;
    run--;
    const bool ready = mbar_test(fb, ph) && run != 0;
    asm volatile("wgmma.fence.sync.aligned;" ::: "memory");
    wgmma_ss<N>(acc[0], da + 4, db + 4 * N);
    wgmma_ss<N>(acc[1], da + 68, db + 4 * N);
    wgmma_ss<N>(acc[0], da + 6, db + 4 * N + 128);
    wgmma_ss<N>(acc[1], da + 70, db + 4 * N + 128);
    asm volatile("wgmma.commit_group.sync.aligned;" ::: "memory");
    if (!ready) {
      bool window = false;
      if (run == 0) {
        if (rest == 0) break;
        window = rest & 64;
        if (window) bar_arrive(BAR_GO, 256);
        else alo = (uint32_t)DESC_A + s16 + (OFF_STG >> 4);
        run = rest & 63;
        rest >>= 7;
      }
      mbar_wait(fb, ph);
      if (window) bar_sync(BAR_DONE, 256);
    }
  }
  if (i < 13 && !(LATE_O && N == 192 && (misc >> 12))) bar_arrive(BAR_ORDER + (wg ^ 1), 256);
  if (N == 128 && ((0x2244 >> i) & 1)) {
    const Ctx cx = make_ctx(sb, mn);
    const uint32_t xrow = cx.sb + OFF_X + cx.w * 4096 + cx.lane * 128 + ((cx.lane & 7) << 4);
    const bool leader = elect_one();
    asm volatile("wgmma.wait_group.sync.aligned 0;" ::: "memory");
    pin_regs<64>(acc);
    PROF_T(5 + i * 4);
    PROF_E(i, 0);
#pragma unroll
    for (int h = 0; h < 2; h++) {
      if (h == 1 && p.zero != 0) break;
#pragma unroll
      for (int j = 8 * h; j < 8 * h + 8; j++)
        stsm4((xrow ^ ((j & 7) << 4)) + h * 16384, pack_bf16(ACC(0, j, 0), ACC(0, j, 1)), pack_bf16(ACC(1, j, 0), ACC(1, j, 1)),
              pack_bf16(ACC(2, j, 0), ACC(2, j, 1)), pack_bf16(ACC(3, j, 0), ACC(3, j, 1)));
      fence_async_smem();
      __syncwarp();
      if (leader) {
        mbar_arrive(sb + BAR_XRDY + 8 * h);
        if (i == 13) {
          tma_st_warp(&p.t.out_w, cx.sb + OFF_X + h * 16384 + cx.w * 4096, 128 * cx.n + 64 * h, cx.m, cx.w);
          bulk_commit();
          if (h == 1) bulk_wait_read();
        }
      }
      if (h == 0 && lane_id < 2) mbar_arrive_cluster(prev + rel);
    }
    PROF_E(i, 4);
    if (EARLY_STATS && i < 13) write_partial_stats(p, cx, (i + 3) >> 2, lds_u(sb + OFF_TAG));
    PROF_E(i, 5);
    return;
  }
  asm volatile("wgmma.wait_group.sync.aligned 0;" ::: "memory");
  pin_regs<N / 2>(acc);
  if (lane_id < 2) mbar_arrive_cluster(prev + rel);
  PROF_T(5 + i * 4);
  PROF_E(i, 0);
}

__device__ __forceinline__ void finish_row_stats(const Params& p, const Ctx& c, int ln, uint32_t tag) {
  const uint4* src = p.g->stats + ln * 8 * SEQ + 128 * c.m + 32 * c.w + c.lane;
  uint32_t ps[8], pm[8];
#pragma unroll 1
  for (int it = 0; it < MSG_SPINS; it++) {
    uint32_t bad = 0, u, tg;
    if ((!EARLY_STATS && ln > 1) || it > 0) __nanosleep(STAT_NS);
#pragma unroll
    for (int k = 0; k < 8; k++) { ld_msg(src + k * SEQ, ps[k], pm[k], u, tg); bad |= tg ^ tag; }
    if (__all_sync(0xffffffffu, bad == 0)) break;
  }
  float s = 0.f, m2 = 0.f;
#pragma unroll
  for (int k = 0; k < 8; k++) s += __uint_as_float(ps[k]);
  const float mean = s * (1.f / DM);
#pragma unroll
  for (int k = 0; k < 8; k++) {
    const float d = __uint_as_float(ps[k]) * (1.f / 128.f) - mean;
    m2 += fmaf(128.f * d, d, __uint_as_float(pm[k]));
  }
  sts_f2(c.sb + OFF_ROW + (32 * c.w + c.lane) * 8, rsqrtf(m2 * (1.f / DM) + 1e-5f), mean);
  __syncwarp();
}

__device__ __forceinline__ void attn_scores(const uint32_t* qa, const uint32_t* qb, const uint32_t* kp, const uint32_t* ka,
                                            const uint32_t* kb, float (&l)[4], const float4& zero, const bool (&early)[2]) {
  float s[3][4];
#pragma unroll
  for (int x = 0; x < 3; x++) {
    const uint32_t* kk = x == 0 ? kp : x == 1 ? ka : kb;
    asm volatile("mma.sync.aligned.m16n8k16.row.col.f32.bf16.bf16.f32 {%0,%1,%2,%3}, {%4,%5,%6,%7}, {%8,%9}, {%10,%11,%12,%13};"
                 : "=f"(s[x][0]), "=f"(s[x][1]), "=f"(s[x][2]), "=f"(s[x][3])
                 : "r"(qa[0]), "r"(qb[0]), "r"(qa[1]), "r"(qb[1]), "r"(kk[0]), "r"(kk[1]), "f"(zero.x), "f"(zero.y),
                   "f"(zero.z), "f"(zero.w));
  }
#pragma unroll
  for (int x = 0; x < 3; x++) {
    const uint32_t* kk = x == 0 ? kp : x == 1 ? ka : kb;
    mma16816(s[x], qa[2], qb[2], qa[3], qb[3], kk[2], kk[3]);
  }
#pragma unroll
  for (int e = 0; e < 2; e++) {
    l[e] = early[e] ? s[0][e] : s[1][e];
    l[2 + e] = early[e] ? s[1][2 + e] : s[2][2 + e];
  }
}

__device__ __forceinline__ void attn_mix(const float (&l)[4], const float (&sc)[4], const float (&off)[4], const float (&rk)[4],
                                         const uint32_t* vp, const uint32_t* va, const uint32_t* vb, float (&o)[4][4],
                                         float (&sum)[2], uint32_t mask, uint32_t zero) {
  float x[4];
#pragma unroll
  for (int e = 0; e < 4; e++) x[e] = fmaf(l[e], sc[e], off[e]);
  const float ml = quad_max(fmaxf(x[0], x[1])), mh = quad_max(fmaxf(x[2], x[3]));
  x[0] = ex2(x[0] - ml); x[1] = ex2(x[1] - ml);
  x[2] = ex2(x[2] - mh); x[3] = ex2(x[3] - mh);
  sum[0] = rcp_hw(quad_sum(x[0] + x[1]));
  sum[1] = rcp_hw(quad_sum(x[2] + x[3]));
  const uint32_t pl = pack_bf16(x[0] * rk[0], x[1] * rk[1]), ph = pack_bf16(x[2] * rk[2], x[3] * rk[3]);
  const uint32_t a0 = pl & ~mask, a1 = ph & mask, a2 = pl & zero, a3 = ph & ~mask, c0 = pl & mask, c1 = ph & zero;
#pragma unroll
  for (int jn = 0; jn < 4; jn++) {
    o[jn][0] = o[jn][1] = o[jn][2] = o[jn][3] = 0.f;
    mma16816(o[jn], a0, a1, a2, a3, va[jn], vb[jn]);
  }
#pragma unroll
  for (int jn = 0; jn < 4; jn++) mma1688(o[jn], c0, c1, vp[jn]);
}

__device__ __forceinline__ void gelu_epilogue(const Params& p, float (&acc)[2][96], const Ctx& cx, int t) {
  UNPACK_CTX(cx);
  (void)wg;
  float rs[4], rm[4];
#pragma unroll
  for (int q = 0; q < 4; q++) {
    const float2 v = lds_f2(sb + OFF_ROW + (32 * w + 8 * q + (lane >> 2)) * 8);
    rs[q] = 0.5f * v.x;
    rm[q] = -rs[q] * v.y;
  }
  const int col0 = 128 * (t - 3);
  const uint32_t stg = sb + OFF_STG + w * 4096;
  const uint32_t ctab = sb + OFF_CSF + (col0 / 2 + (lane & 3)) * 16, srow = stg + lane * 128 + ((lane & 7) << 4);
  __nanosleep((t == 5 ? STAG5 : t == 4 ? STAG4 : STAG3) * w);
  float4 nb = lds_f4(ctab);
#pragma unroll
  for (int c = 0; c < 3; c++) {
    if (c == 2 && t != 5) break;
    uint32_t hp[8][4];
#pragma unroll
    for (int j = 0; j < 8; j++) {
      const float4 cb = nb;
      if (8 * c + j < 23) nb = lds_f4(ctab + (8 * c + j + 1) * 64);
#pragma unroll
      for (int q = 0; q < 4; q++) {
        float y[2];
        const int k = 4 * j + q - GELU_DEP;
        const float rmq = k >= 0 ? chain(rm[q], hp[k >> 2][k & 3], p.zero) : rm[q];
#pragma unroll
        for (int e = 0; e < 2; e++) {
          const float z = fmaf(ACC(q, 8 * c + j, e), rs[q], fmaf(rmq, e ? cb.y : cb.x, e ? cb.w : cb.z));
          const float u = z * fmaf(z * z, 8.f * 0.7978845608028654f * 0.044715f, 2.f * 0.7978845608028654f);
          y[e] = fmaf(z, tanh_hw(u), z);
        }
        hp[j][q] = pack_bf16(y[0], y[1]);
      }
      if (j == STG_WAIT && c > 0) {
        if (lane == 0) bulk_wait_read();
        __syncwarp();
      }
      if (c == 0 || j > STG_WAIT) {
        stsm4(srow ^ (j << 4), hp[j][0], hp[j][1], hp[j][2], hp[j][3]);
      } else if (j == STG_WAIT) {
#pragma unroll
        for (int jj = 0; jj <= STG_WAIT; jj++) stsm4(srow ^ (jj << 4), hp[jj][0], hp[jj][1], hp[jj][2], hp[jj][3]);
      }
    }
    fence_async_smem();
    __syncwarp();
    if (lane == 0) {
      tma_st2(&p.t.h_st, stg, 448 * n + col0 + 64 * c, 128 * m + 32 * w);
      bulk_commit();
    }
  }
#pragma unroll
  for (int r = 0; r < 16; r++) acc[0][r] = acc[1][r] = 0.f;
}

template <int PART>
__device__ __forceinline__ void rank1_update(const Params& p, float (&acc)[2][96], const Ctx& cx, int t) {
  float nm[4];
#pragma unroll
  for (int q = 0; q < 4; q++) nm[q] = t == 6 ? 1.f : -lds_f(cx.sb + OFF_ROW + (32 * cx.w + 8 * q + (cx.lane >> 2)) * 8 + 4);
  const uint32_t ctab = cx.sb + OFF_CSQ + ((t & 3) * 192 + 2 * (cx.lane & 3)) * 4;
#pragma unroll
  for (int j = PART == 1 ? 8 : 0; j < 24; j++) {
    const float2 cs = lds_f2(ctab + j * 32);
#pragma unroll
    for (int q = 0; q < 4; q++) {
      if (PART != 0 && (PART == 1) != (q == 3 && j >= 8)) continue;
      const int k = 4 * j + q - 1;
      const float nq = PART == 0 && k >= 0 ? chain(nm[q], __float_as_uint(ACC(k & 3, k >> 2, 1)), p.zero) : nm[q];
      ACC(q, j, 0) = fmaf(nq, cs.x, ACC(q, j, 0));
      ACC(q, j, 1) = fmaf(nq, cs.y, ACC(q, j, 1));
    }
  }
}

__device__ __forceinline__ void attn_epilogue(const Params& p, float (&acc)[2][96], const Ctx& cx, int layer, int t, uint32_t tag) {
  UNPACK_CTX(cx);
  const uint32_t ktab = sb + OFF_ROW + (32 * w + 2 * (lane & 3)) * 8, exc = sb + OFF_STG + (w & 1) * 2048 + lane * 16;
  uint4* const halo = p.g->halo + (((layer * 2 + t) * 16 + m) * 8 + n) * 384 + (w & 1) * 192;
  const int mn = m * 8 + n; (void)mn;
  uint32_t Q[4][8], K[4][8], V[4][8], E[18], P[18];
  float kr[5][2], qr[4];
  const bool late_fold = layer == 0 && t == 1;
  if (late_fold) rank1_update<1>(p, acc, cx, 1);
  {
    const float4 r = lds_f4(ktab + 192);
    E[16] = __float_as_uint(kr[4][0] = r.x);
    E[17] = __float_as_uint(kr[4][1] = r.z);
  }
#pragma unroll
  for (int j = 0; j < 8; j++) {
    E[j] = K[3][j] = pack_bf16(ACC(3, 8 + j, 0), ACC(3, 8 + j, 1));
    E[8 + j] = V[3][j] = movtrans(pack_bf16(ACC(3, 16 + j, 0), ACC(3, 16 + j, 1)));
  }
  if (w < 2) {
#pragma unroll
    for (int k = 0; k < 4; k++) sts_u4(exc + k * 512, E[4 * k], E[4 * k + 1], E[4 * k + 2], E[4 * k + 3]);
  } else {
#pragma unroll
    for (int k = 0; k < 6; k++) st_msg(halo + k * 32 + lane, E[3 * k], E[3 * k + 1], E[3 * k + 2], tag);
  }
  bar_arrive(BAR_PAIR + w, 64);
  if (LATE_O && t == 1) bar_arrive(BAR_ORDER + (wg ^ 1), 256);
  PROF_E(7 * layer + t, 1);
  if (late_fold) rank1_update<2>(p, acc, cx, 1);
#pragma unroll
  for (int q = 0; q < 4; q++) {
    qr[q] = lds_f(sb + OFF_ROW + (32 * w + 8 * q + (lane >> 2)) * 8) * (0.17677669529663687f * 1.4426950408889634f);
#pragma unroll
    for (int j = 0; j < 8; j++) Q[q][j] = pack_bf16(ACC(q, j, 0), ACC(q, j, 1));
    if (q < 3) {
      const float4 r = lds_f4(ktab + 64 * q);
      kr[1 + q][0] = r.x;
      kr[1 + q][1] = r.z;
#pragma unroll
      for (int j = 0; j < 8; j++) {
        K[q][j] = pack_bf16(ACC(q, 8 + j, 0), ACC(q, 8 + j, 1));
        V[q][j] = movtrans(pack_bf16(ACC(q, 16 + j, 0), ACC(q, 16 + j, 1)));
      }
    }
  }
  PROF_E(7 * layer + t, 6);
  bar_sync(BAR_PAIR + (w ^ 2), 64);
  if (w >= 2 || m == 0) {
#pragma unroll
    for (int k = 0; k < 4; k++) lds_u4(exc + k * 512, P[4 * k], P[4 * k + 1], P[4 * k + 2], P[4 * k + 3]);
    const float4 r = lds_f4(ktab - (w >> 1) * 320);
    P[16] = __float_as_uint(r.x);
    P[17] = __float_as_uint(r.z);
  } else {
    if (m & 1) __nanosleep(HALO_NS);
#pragma unroll 1
    for (int it = 0; it < MSG_SPINS; it++) {
      uint32_t tg, bad = 0;
      if (it > 0 || !(m & 1)) poll_line(reinterpret_cast<const uint32_t*>(halo - 8 * 384 + 191) + 3, tag, 1u);
#pragma unroll
      for (int k = 0; k < 6; k++) {
        ld_msg(halo - 8 * 384 + k * 32 + lane, P[3 * k], P[3 * k + 1], P[3 * k + 2], tg);
        bad |= tg ^ tag;
      }
      if (__all_sync(0xffffffffu, bad == 0)) break;
    }
  }
  kr[0][0] = __uint_as_float(P[16]);
  kr[0][1] = __uint_as_float(P[17]);
  const bool early[2] = {2 * (lane & 3) > (lane >> 2), 2 * (lane & 3) + 1 > (lane >> 2)};
  const uint32_t mask = (early[0] ? 0xffffu : 0u) | (early[1] ? 0xffff0000u : 0u);
  float rk[2][4], sc[2][4], off[2][4];
#pragma unroll
  for (int g = 0; g < 2; g++) {
#pragma unroll
    for (int e = 0; e < 4; e++) {
      const int q = 2 * g + (e >> 1);
      const bool masked = q == 0 && m == 0 && w < 2 && early[e & 1];
      rk[g][e] = early[e & 1] ? kr[q][e & 1] : kr[q + 1][e & 1];
      sc[g][e] = masked ? 0.f : rk[g][e] * qr[q];
      off[g][e] = masked ? -1e30f : 0.f;
    }
  }
  if (w == 0 && elect_one()) asm volatile("prefetch.tensormap [%0];" ::"l"(&p.t.att_st) : "memory");
  PROF_E(7 * layer + t, 2);
  bar_sync(BAR_GO, 256);
  const float4 zero = lds_f4(sb + OFF_ZERO);
  float l[2][2][4], o[2][2][4][4], sum[2][2][2];
#pragma unroll
  for (int h = 0; h < 2; h++) {
    if (h == 1) {
      Q[2][4] |= __float_as_uint(l[1][0][0]) & p.zero;
      Q[0][4] |= __float_as_uint(l[0][0][0]) & p.zero;
    }
    attn_scores(&Q[2][4 * h], &Q[3][4 * h], &K[1][4 * h], &K[2][4 * h], &K[3][4 * h], l[1][h], zero, early);
    attn_scores(&Q[0][4 * h], &Q[1][4 * h], &P[4 * h], &K[0][4 * h], &K[1][4 * h], l[0][h], zero, early);
  }
  const uint32_t stg = sb + OFF_STG + w * 4096, srow = stg + lane * 128 + ((lane & 7) << 4);
#pragma unroll
  for (int h = 0; h < 2; h++) {
    attn_mix(l[1][h], sc[1], off[1], rk[1], &V[1][4 * h], &V[2][4 * h], &V[3][4 * h], o[1][h], sum[1][h], mask, p.zero);
    attn_mix(l[0][h], sc[0], off[0], rk[0], &P[8 + 4 * h], &V[0][4 * h], &V[1][4 * h], o[0][h], sum[0][h], mask, p.zero);
#pragma unroll
    for (int j = 0; j < 4; j++) {
      const float(&a)[4] = o[0][h][j];
      const float(&c)[4] = o[1][h][j];
      stsm4(srow ^ ((4 * h + j) << 4), pack_bf16(a[0] * sum[0][h][0], a[1] * sum[0][h][0]), pack_bf16(a[2] * sum[0][h][1], a[3] * sum[0][h][1]),
            pack_bf16(c[0] * sum[1][h][0], c[1] * sum[1][h][0]), pack_bf16(c[2] * sum[1][h][1], c[3] * sum[1][h][1]));
    }
  }
  bar_arrive(BAR_DONE, 256);
  fence_async_smem();
  __syncwarp();
  if (lane == 0) {
    tma_st2(&p.t.att_st, stg, 128 * n + 64 * t, 128 * m + 32 * w);
    bulk_commit();
  }
}

__device__ __forceinline__ void finish_stores(uint32_t sb, int i) {
  const int t = i >= 7 ? i - 7 : i;
  if ((threadIdx.x & 31) == 0) {
    bulk_wait_all();
    mbar_arrive(sb + BAR_PUB + 8 * (t < 2 ? t : t + 1));
  }
  __syncwarp();
  if (i < 12) bar_arrive(BAR_GUARD + ((i & 1) ^ 1), 256);
}

__device__ __forceinline__ bool consumer_tile(const Params& p, float (&acc)[2][96], uint32_t sb0, int i, int mn) {
  const int layer = i >= 7, t = i - 7 * layer, wg = i & 1;
  const bool resid = t == 2 || t == 6;
  {
    if (resid) {
      const Ctx cx = make_ctx(sb0, mn);
      const uint32_t xrow = cx.sb + OFF_X + cx.w * 4096 + cx.lane * 128;
      const uint32_t sel_lo = 0x1044u | p.zero, sel_hi = 0x3244u | p.zero;
#pragma unroll
      for (int j = 0; j < 16; j++) {
        uint32_t r[4];
        ldsm4(xrow + (j >> 3) * 16384 + (((j & 7) ^ (cx.lane & 7)) << 4), r[0], r[1], r[2], r[3]);
#pragma unroll
        for (int q = 0; q < 4; q++) {
          ACC(q, j, 0) = prmt_f(r[q], sel_lo);
          ACC(q, j, 1) = prmt_f(r[q], sel_hi);
        }
      }
    }
    if (t >= 5 || i == 7) finish_stores(sb0, i - 2);
#pragma unroll 1
    for (int step = !tile_split(i);; step++) {
      if (step == 1 && (t == 1 || t == 4)) {
        const Ctx cx = make_ctx(sb0, mn);
        if (i == 1) {
          const uint32_t epoch = __ldcg(p.g->epoch + (mn & 127));
          cluster_wait();
          asm volatile("st.shared.u32 [%0], %1;" ::"r"(sb0 + OFF_TAG), "r"(epoch + 1) : "memory");
        }
        const uint32_t tag = lds_u(cx.sb + OFF_TAG);
        const int ln = (i + 1) >> 2;
#pragma unroll 1
        for (int r = 0; r < 2; r++) {
          if (i == 1) {
            if (cx.w < 3) {
              float a[8] = {0.f, 0.f, 0.f, 0.f, 0.f, 0.f, 0.f, 0.f};
              mbar_wait(sb0 + BAR_CSLD, r);
#pragma unroll 1
              for (int h = 0; h < 2; h++) sum_rows(cx.sb + OFF_STG + h * 12288 + cx.w * 4096, 4, a, cx.lane);
              publish_sums(a, p.g->csp + (cx.n * 17 + cx.m) * 224 + (3 * r + cx.w) * 32, cx.lane, tag);
            }
            PROF_E(-1, 5 + r);
          }
          if (r == 1) break;
          if (i == 1) {
            bar_sync(BAR_WG + 1, 128);
            if (cx.w == 3 && elect_one()) {
              mbar_expect_tx(sb0 + BAR_CSLD, 24576);
              tma_ld3(sb0 + OFF_STG, &p.t.wqkv, sb0 + BAR_CSLD, 128 * cx.n + 64, 64 * cx.m, 0);
              tma_ld3(sb0 + OFF_STG + 12288, &p.t.wqkv, sb0 + BAR_CSLD, 128 * cx.n + 64, 64 * cx.m + 32, 0);
            }
            mbar_wait(sb0 + BAR_XRDY, 0);
            mbar_wait(sb0 + BAR_XRDY + 8, 0);
          }
          if (!EARLY_STATS || i == 1) write_partial_stats(p, cx, ln, tag);
          PROF_E(i - 2, 8);
        }
        if (i == 1) {
          bar_arrive(BAR_HLP, 160);
          bar_sync(BAR_INIT, 160);
        }
        if (i == 4) colsum_total(p, cx, 1, tag);
        PROF_E(i - 2, 9);
        if (i != 1) bar_sync(BAR_GUARD + wg, 256);
        finish_row_stats(p, cx, ln, tag);
        PROF_E(i - 2, 10);
        if (i == 4) {
          colsum_gather(p, cx, 1, tag);
          mbar_wait(sb0 + BAR_BIAS, 0);
        }
        PROF_E(i - 2, 15);
        bar_arrive(BAR_GUARD + (wg ^ 1), 256);
      }
      if (step == 2 && !resid) bar_sync(BAR_GUARD + wg, 256);
      if (step == 2 && i == 0) {
        colsum_gather(p, make_ctx(sb0, mn), 0, lds_u(sb0 + OFF_TAG));
        bar_sync(BAR_WG, 128);
      }
      if ((t + step == 2 && i != 1) || t == 6) rank1_update<0>(p, acc, make_ctx(sb0, mn), t);
      if (step == 2) break;
      if (tile_wide(t)) {
        mainloop<192>(p, acc, sb0, i, step, mn);
      } else {
        mainloop<128>(p, acc, sb0, i, step, mn);
        if (resid) return false;
      }
    }
    if (t < 2) return true;
    gelu_epilogue(p, acc, make_ctx(sb0, mn), t);
    PROF_E(i, 4);
    return false;
  }
}

template <bool BY_SMID>
__global__ void __cluster_dims__(2, 1, 1) __launch_bounds__(384, 1)
fused_layers_kernel(const Scalars scalars, const __grid_constant__ Maps maps) {
  if (threadIdx.x == 288 || threadIdx.x == 320)
    asm volatile("prefetch.tensormap [%0];" ::"l"(threadIdx.x == 288 ? &maps.xin : &maps.wqkv) : "memory");
  const Params p{scalars, maps};
  extern __shared__ __align__(1024) uint8_t smem_raw[];
  const uint32_t sb = uniform((uint32_t)__cvta_generic_to_shared(smem_raw));
  const int tid = threadIdx.x, lane = tid & 31, warp = uniform(tid >> 5), wg = warp >> 2, w = warp & 3;

  int mn;
  {
    int id = blockIdx.x;
    if (BY_SMID) asm volatile("mov.u32 %0, %%smid;" : "=r"(id));
    else if (id >= 120) id += 4;
    const int c = id >> 1;
    int g, j;
    if (c < 32) { g = c & 7; j = c >> 3; }
    else if (c < 60) { g = 1 + (c - 32) % 7; j = 4 + (c - 32) / 7; }
    else { g = 0; j = c - 58; }
    const int r = blockIdx.x & 1;
    mn = (g * 2 + r) * 8 + j;
    if (c == 60 || c == 61) {
      if (tid < 32) {
        const uint32_t tag = __ldcg(p.g->epoch + NCTA + (id & 3)) + 1;
#pragma unroll 1
        for (int mm = 0; mm < 16; mm++) poll_line(p.g->flags + mm * 32 + (lane & 7), 32 * tag, 0xffu);
        if (tid == 0) p.g->epoch[NCTA + (id & 3)] = tag;
      }
      return;
    }
  }
  const int m = mn >> 3, n = mn & 7;
  if (tid == 256) PROF_U(1);
  if (wg < 2) {
    cluster_arrive();
    asm volatile("setmaxnreg.inc.sync.aligned.u32 232;");
    if (tid == 0) PROF_U(2);
    const int id = mn | (warp << 7);
#pragma unroll 1
    for (int i = wg;; i += 2) {
      float acc[2][96];
#pragma unroll
      for (int r = 0; r < 96; r++) acc[0][r] = acc[1][r] = 0.f;
      pin_regs<96>(acc);
      if (i == 0 && threadIdx.x == 0) PROF_U(3);
#pragma unroll 1
      while (!consumer_tile(p, acc, sb, i, id)) {
        PROF_T(6 + i * 4);
        i += 2;
        if (i >= 14) goto all_done;
      }
      attn_epilogue(p, acc, make_ctx(sb, id), i >= 7, i >= 7 ? i - 7 : i, lds_u(sb + OFF_TAG));
      PROF_E(i, 4);
      finish_stores(sb, i);
      PROF_E(i, 5);
      PROF_T(6 + i * 4);
    }
  all_done:
    if (wg == 0) {
      finish_stores(sb, 12);
    } else {
      cluster_arrive();
      cluster_wait();
    }
  } else {
    asm volatile("setmaxnreg.dec.sync.aligned.u32 40;");
    if (w != 0) {
      if (w == 1 && elect_one()) {
        mbar_init(sb + BAR_FULL + 32, 2);
#pragma unroll
        for (int k = 0; k < NBAR; k++) mbar_init(sb + BAR_EMPTY + 8 * k, 8);
#pragma unroll
        for (int k = 0; k < 3; k++) mbar_init(sb + BAR_XRDY + 8 * k, 4);
#pragma unroll
        for (int k = 0; k < 9; k++) mbar_init(sb + BAR_PUB + 8 * k, 4);
#pragma unroll
        for (int k = 0; k < 4; k++) mbar_init(sb + BAR_CSLD + 8 * k, 1);
        sts_f2(sb + OFF_ZERO, 0.f, 0.f);
        sts_f2(sb + OFF_ZERO + 8, 0.f, 0.f);
        asm volatile("fence.mbarrier_init.release.cluster;" ::: "memory");
      }
      __syncwarp();
      cluster_arrive();
      if (w == 2) {
        if (lane < 28) write_run_desc(sb, lane >> 1, lane & 1);
        bar_arrive(BAR_INIT, 160);
      }
      cluster_wait();
      if (w == 1) producer<true>(p, sb, m, n, lane);
      else if (w == 3) colsum_helper(p, sb, m, n, lane);
      else if (elect_one()) publisher(p, sb, m, n);
    } else {
      const bool leader = elect_one();
      if (leader) {
#pragma unroll
        for (int k = 0; k < 4; k++) mbar_init(sb + BAR_FULL + 8 * k, 2);
        asm volatile("fence.mbarrier_init.release.cluster;" ::: "memory");
        PROF_U(4);
      }
      __syncwarp();
      bar_arrive(BAR_INIT0, 160);
      cluster_arrive();
      if (leader) {
#pragma unroll 1
        for (int k = 0; k < 4; k++) {
          const uint32_t fb = sb + BAR_FULL + 8 * k;
          mbar_expect_tx(fb, 16384);
          tma_ld_act(sb + (5 * k + 3) * UNIT, &p.t.xin, fb, 64 * k, m);
          mbar_expect_tx(fb, 3 * UNIT);
          tma_ld3(sb + 5 * k * UNIT, &p.t.wqkv, fb, 128 * n, 64 * k, 0);
          tma_ld3(sb + 5 * k * UNIT + 12288, &p.t.wqkv, fb, 128 * n, 64 * k + 32, 0);
          if (k == 0) PROF_U(6);
        }
        PROF_U(5);
      }
      __syncwarp();
      cluster_wait();
      producer<false>(p, sb, m, n, lane);
    }
  }
}

typedef CUresult (*EncodeFn)(CUtensorMap*, CUtensorMapDataType, cuuint32_t, void*, const cuuint64_t*, const cuuint64_t*,
                             const cuuint32_t*, const cuuint32_t*, CUtensorMapInterleave, CUtensorMapSwizzle,
                             CUtensorMapL2promotion, CUtensorMapFloatOOBfill);

#define PROMO2 CU_TENSOR_MAP_L2_PROMOTION_L2_128B
#define PROMO3 CU_TENSOR_MAP_L2_PROMOTION_L2_128B
void make_2d(EncodeFn enc, CUtensorMap* m, const void* ptr, uint64_t cols, uint64_t rows, uint32_t box_rows) {
  cuuint64_t d[2] = {cols, rows}, st[1] = {cols * 2};
  cuuint32_t b[2] = {64, box_rows}, e[2] = {1, 1};
  enc(m, CU_TENSOR_MAP_DATA_TYPE_BFLOAT16, 2, const_cast<void*>(ptr), d, st, b, e, CU_TENSOR_MAP_INTERLEAVE_NONE,
      CU_TENSOR_MAP_SWIZZLE_128B, PROMO2, CU_TENSOR_MAP_FLOAT_OOB_FILL_NONE);
}
void make_act(EncodeFn enc, CUtensorMap* m, const void* ptr, uint64_t cols, bool split, uint32_t box = 2) {
  const uint64_t row = cols * 2;
  cuuint64_t d[4] = {cols, 32, 2, SEQ / 64}, st[3] = {split ? 2 * row : row, split ? row : 32 * row, 64 * row};
  cuuint32_t b[4] = {64, 32, box, box}, e[4] = {1, 1, 1, 1};
  enc(m, CU_TENSOR_MAP_DATA_TYPE_BFLOAT16, 4, const_cast<void*>(ptr), d, st, b, e, CU_TENSOR_MAP_INTERLEAVE_NONE,
      CU_TENSOR_MAP_SWIZZLE_128B, PROMO2, CU_TENSOR_MAP_FLOAT_OOB_FILL_NONE);
}
void make_3d(EncodeFn enc, CUtensorMap* m, const void* ptr, uint64_t d0, uint64_t rows, uint64_t d2, uint64_t row_bytes,
             uint64_t chunk_bytes, uint32_t box_chunks) {
  cuuint64_t d[3] = {d0, rows, d2}, st[2] = {row_bytes, chunk_bytes};
  cuuint32_t b[3] = {64, 32, box_chunks}, e[3] = {1, 1, 1};
  enc(m, CU_TENSOR_MAP_DATA_TYPE_BFLOAT16, 3, const_cast<void*>(ptr), d, st, b, e, CU_TENSOR_MAP_INTERLEAVE_NONE,
      CU_TENSOR_MAP_SWIZZLE_128B, PROMO3, CU_TENSOR_MAP_FLOAT_OOB_FILL_NONE);
}

}

extern "C" void kernel_launch(void* const* d_in, const int* in_sizes, int n_in, void* d_out, int out_size) {
  (void)in_sizes; (void)n_in; (void)out_size;
  static EncodeFn enc = nullptr;
  static void *att = nullptr, *hbuf = nullptr, *scratch = nullptr;
  static int by_smid = 0;
  if (!enc) {
    void* fn = nullptr;
    cudaDriverEntryPointQueryResult q;
    cudaGetDriverEntryPoint("cuTensorMapEncodeTiled", &fn, cudaEnableDefault, &q);
    enc = (EncodeFn)fn;
    cudaGetSymbolAddress(&att, g_att);
    cudaGetSymbolAddress(&hbuf, g_h);
    cudaGetSymbolAddress(&scratch, g_scratch);
    cudaFuncSetAttribute(fused_layers_kernel<true>, cudaFuncAttributeMaxDynamicSharedMemorySize, SMEM_BYTES);
    cudaFuncSetAttribute(fused_layers_kernel<false>, cudaFuncAttributeMaxDynamicSharedMemorySize, SMEM_BYTES);
    int sms = 0, clusters = 0, dev = 0;
    cudaGetDevice(&dev);
    cudaDeviceGetAttribute(&sms, cudaDevAttrMultiProcessorCount, dev);
    cudaLaunchConfig_t cfg = {};
    cfg.gridDim = dim3(132);
    cfg.blockDim = dim3(384);
    cfg.dynamicSmemBytes = SMEM_BYTES;
    cudaLaunchAttribute at[1];
    at[0].id = cudaLaunchAttributeClusterDimension;
    at[0].val.clusterDim.x = 2; at[0].val.clusterDim.y = 1; at[0].val.clusterDim.z = 1;
    cfg.attrs = at;
    cfg.numAttrs = 1;
    if (cudaOccupancyMaxActiveClusters(&clusters, fused_layers_kernel<true>, &cfg) != cudaSuccess) (void)cudaGetLastError();
    by_smid = sms == 132 && clusters == 66;
  }
  Maps p;
  Scalars sc;
  make_act(enc, &p.xin, d_in[0], DM, true);
  make_act(enc, &p.out, d_out, DM, true);
  make_act(enc, &p.out_w, d_out, DM, true, 1);
  make_act(enc, &p.att, att, DM, false);
  make_act(enc, &p.h, hbuf, FF, false);
  make_2d(enc, &p.att_st, att, DM, SEQ, 32);
  make_2d(enc, &p.h_st, hbuf, FF, SEQ, 32);
  make_2d(enc, &p.w1c, d_in[4], FF, DM, 32);
  make_3d(enc, &p.wqkv, d_in[1], DM, DM, 3, 3 * DM * 2, DM * 2, 3);
  make_3d(enc, &p.wo, d_in[2], 64, DM, DM / 64, DM * 2, 128, 2);
  make_3d(enc, &p.w1a, d_in[4], 64, DM, FF / 64, FF * 2, 128, 3);
  make_3d(enc, &p.w1b, d_in[4], 64, DM, FF / 64, FF * 2, 128, 2);
  make_3d(enc, &p.w2, d_in[6], 64, FF, DM / 64, DM * 2, 128, 2);
  sc.b1 = (const __nv_bfloat16*)d_in[5];
  sc.b2 = (const __nv_bfloat16*)d_in[7];
  sc.g = (Scratch*)scratch;
  sc.zero = 0;
  if (by_smid) fused_layers_kernel<true><<<132, 384, SMEM_BYTES>>>(sc, p);
  else fused_layers_kernel<false><<<NCTA, 384, SMEM_BYTES>>>(sc, p);
}
```

```cpp
#include <cuda_runtime.h>
#include <cuda_bf16.h>
#include <cuda.h>
#include <stdint.h>

namespace {

constexpr int SEQ = 2048, DM = 1024, FF = 3584;
constexpr int NCTA = 128;
constexpr int NBAR = 5;

constexpr uint32_t RING_UNITS = 20, UNIT = 8192;
constexpr uint32_t OFF_X   = RING_UNITS * UNIT;
constexpr uint32_t OFF_STG = OFF_X + 32768;
constexpr uint32_t OFF_HLP = OFF_STG + 16384;
constexpr uint32_t OFF_RUN = OFF_STG + 24576;
constexpr uint32_t OFF_CSQ = OFF_RUN + 512;
constexpr uint32_t OFF_CSF = OFF_CSQ + 2048;
constexpr uint32_t OFF_ROW = OFF_CSF + 3584;
constexpr uint32_t OFF_BAR = OFF_ROW + 1024;
constexpr uint32_t SMEM_BYTES = OFF_BAR + 384;
constexpr uint32_t BAR_FULL = OFF_BAR, BAR_EMPTY = OFF_BAR + 8 * NBAR;
constexpr uint32_t BAR_XRDY = OFF_BAR + 80;
constexpr uint32_t BAR_DUMMY = OFF_BAR + 96, OFF_TAG = OFF_BAR + 104, OFF_ZERO = OFF_BAR + 112;
constexpr uint32_t BAR_PUB = OFF_BAR + 128;
constexpr uint32_t BAR_CSLD = OFF_BAR + 200;
constexpr uint32_t BAR_XGO = OFF_BAR + 224;
constexpr uint32_t BAR_BIAS = OFF_BAR + 216;

constexpr uint64_t DESC_A = (1ull << 62) | ((uint64_t)(2048 >> 4) << 32) | (1ull << 16);
constexpr uint64_t DESC_B = (1ull << 62) | ((uint64_t)(1024 >> 4) << 32) | ((uint64_t)(4096 >> 4) << 16);

constexpr int BAR_INIT = 0, BAR_ORDER = 1, BAR_GUARD = 3, BAR_WG = 5, BAR_GO = 7, BAR_DONE = 8, BAR_HLP = 9, BAR_INIT0 = 10, BAR_PAIR = 11;
#define GELU_DEP 2
#define MAP 2
#define LATE_O 1
#define HALO_NS 200
#define STG_WAIT 5
#define STAT_NS 800
#define BDELAY 400
#define STAG5 450
#define STAG4 0
#define STAG3 0
#define PACE0 0
#define PACE_M 100
#define PACE_N 300
#define CS_NS 500
#define BSPLIT 50
#define EARLY_STATS 2
#define WIN1 8
#define WIN2 2

struct Scratch {
  uint4 stats[4 * 8 * SEQ];
  uint4 halo[2 * 2 * 16 * 8 * 384];
  uint4 csp[2 * 8 * 17 * 224];
  uint32_t flags[16 * 32];
  uint32_t epoch[NCTA + 4];
};

struct Maps {
  CUtensorMap xin, out, att, h, wqkv, wo, w1a, w1b, w2, att_st, h_st, w1c, out_w;
};
struct Scalars {
  Scratch* g;
  const __nv_bfloat16 *b1, *b2;
  uint32_t zero;
};
struct Params : Scalars {
  const Maps& t;
};

__device__ __nv_bfloat16 g_att[SEQ * DM];
__device__ __nv_bfloat16 g_h[SEQ * FF];
__device__ Scratch g_scratch;
#define PROF_T(idx)
#define PROF_U(k)
#define PROF_S(g)
#define PROF_E(i, k)

__device__ __forceinline__ void mbar_init(uint32_t bar, int cnt) {
  asm volatile("mbarrier.init.shared::cta.b64 [%0], %1;" ::"r"(bar), "r"(cnt));
}
__device__ __forceinline__ void mbar_expect_tx(uint32_t bar, uint32_t bytes) {
  asm volatile("mbarrier.arrive.expect_tx.shared::cta.b64 _, [%0], %1;" ::"r"(bar), "r"(bytes) : "memory");
}
__device__ __forceinline__ void mbar_arrive(uint32_t bar) {
  asm volatile("mbarrier.arrive.shared::cta.b64 _, [%0];" ::"r"(bar) : "memory");
}
__device__ __forceinline__ bool mbar_test(uint32_t bar, uint32_t parity) {
  uint32_t ok;
  asm volatile("{\n.reg .pred p;\nmbarrier.test_wait.parity.shared::cta.b64 p, [%1], %2;\nselp.u32 %0, 1, 0, p;\n}"
               : "=r"(ok) : "r"(bar), "r"(parity) : "memory");
  return ok;
}
__device__ __forceinline__ void mbar_wait(uint32_t bar, uint32_t parity) {
  asm volatile(
      "{\n.reg .pred p;\n.reg .u32 it;\nmov.u32 it, 0;\n"
      "WAIT_LOOP:\n"
      "mbarrier.try_wait.parity.shared::cta.b64 p, [%0], %1;\n"
      "@p bra WAIT_DONE;\n"
      "add.u32 it, it, 1;\n"
      "setp.lt.u32 p, it, 0x400000;\n"
      "@p bra WAIT_LOOP;\n"
      "trap;\n"
      "WAIT_DONE:\n}"
      ::"r"(bar), "r"(parity) : "memory");
}
__device__ __forceinline__ void bar_sync(int id, int n) { asm volatile("bar.sync %0, %1;" ::"r"(id), "r"(n) : "memory"); }
__device__ __forceinline__ void bar_arrive(int id, int n) { asm volatile("bar.arrive %0, %1;" ::"r"(id), "r"(n) : "memory"); }
__device__ __forceinline__ void tma_ld2(uint32_t dst, const CUtensorMap* m, uint32_t bar, int c0, int c1) {
  asm volatile("cp.async.bulk.tensor.2d.shared::cluster.global.mbarrier::complete_tx::bytes [%0], [%1, {%3, %4}], [%2];"
               ::"r"(dst), "l"(m), "r"(bar), "r"(c0), "r"(c1) : "memory");
}
__device__ __forceinline__ void tma_ld_act(uint32_t dst, const CUtensorMap* m, uint32_t bar, int col, int blk) {
  asm volatile("cp.async.bulk.tensor.4d.shared::cluster.global.mbarrier::complete_tx::bytes [%0], [%1, {%3, %5, %5, %4}], [%2];"
               ::"r"(dst), "l"(m), "r"(bar), "r"(col), "r"(2 * blk), "r"(0) : "memory");
}
__device__ __forceinline__ void tma_st_act(const CUtensorMap* m, uint32_t src, int col, int blk) {
  asm volatile("cp.async.bulk.tensor.4d.global.shared::cta.bulk_group [%0, {%2, %4, %4, %3}], [%1];"
               ::"l"(m), "r"(src), "r"(col), "r"(2 * blk), "r"(0) : "memory");
}
__device__ __forceinline__ void tma_st_warp(const CUtensorMap* m, uint32_t src, int col, int blk, int w) {
  asm volatile("cp.async.bulk.tensor.4d.global.shared::cta.bulk_group [%0, {%2, %5, %3, %4}], [%1];"
               ::"l"(m), "r"(src), "r"(col), "r"(w & 1), "r"(2 * blk + (w >> 1)), "r"(0) : "memory");
}
__device__ __forceinline__ void tma_ld3(uint32_t dst, const CUtensorMap* m, uint32_t bar, int c0, int c1, int c2) {
  asm volatile("cp.async.bulk.tensor.3d.shared::cluster.global.mbarrier::complete_tx::bytes [%0], [%1, {%3, %4, %5}], [%2];"
               ::"r"(dst), "l"(m), "r"(bar), "r"(c0), "r"(c1), "r"(c2) : "memory");
}
__device__ __forceinline__ void tma_ld3_pair(uint32_t dst, const CUtensorMap* m, uint32_t bar, int c0, int c1, int c2) {
  asm volatile("cp.async.bulk.tensor.3d.shared::cluster.global.mbarrier::complete_tx::bytes.multicast::cluster"
               " [%0], [%1, {%3, %4, %5}], [%2], %6;"
               ::"r"(dst), "l"(m), "r"(bar), "r"(c0), "r"(c1), "r"(c2), "h"((uint16_t)3) : "memory");
}
__device__ __forceinline__ uint32_t pair_offset(uint32_t sb, uint32_t rank) {
  uint32_t r;
  asm volatile("mapa.shared::cluster.u32 %0, %1, %2;" : "=r"(r) : "r"(sb), "r"(rank));
  return r - sb;
}
__device__ __forceinline__ void mbar_arrive_cluster(uint32_t bar) {
  asm volatile("mbarrier.arrive.shared::cluster.b64 _, [%0];" ::"r"(bar) : "memory");
}
__device__ __forceinline__ void cluster_arrive() { asm volatile("barrier.cluster.arrive.relaxed;" ::: "memory"); }
__device__ __forceinline__ void cluster_wait() { asm volatile("barrier.cluster.wait.acquire;" ::: "memory"); }
__device__ __forceinline__ void tma_st2(const CUtensorMap* m, uint32_t src, int c0, int c1) {
  asm volatile("cp.async.bulk.tensor.2d.global.shared::cta.bulk_group [%0, {%2, %3}], [%1];"
               ::"l"(m), "r"(src), "r"(c0), "r"(c1) : "memory");
}
__device__ __forceinline__ void bulk_commit() { asm volatile("cp.async.bulk.commit_group;" ::: "memory"); }
__device__ __forceinline__ void bulk_wait_read() { asm volatile("cp.async.bulk.wait_group.read 0;" ::: "memory"); }
__device__ __forceinline__ void bulk_wait_all() { asm volatile("cp.async.bulk.wait_group 0;" ::: "memory"); }
__device__ __forceinline__ void fence_async_smem() { asm volatile("fence.proxy.async.shared::cta;" ::: "memory"); }
__device__ __forceinline__ void fence_async_global() { asm volatile("fence.proxy.async.global;" ::: "memory"); }
__device__ __forceinline__ void st_relaxed(uint32_t* p, uint32_t v) {
  asm volatile("st.relaxed.gpu.global.u32 [%0], %1;" ::"l"(p), "r"(v) : "memory");
}
__device__ __forceinline__ void st_msg(uint4* p, uint32_t a, uint32_t b, uint32_t c, uint32_t tag) {
  asm volatile("{\n.reg .b128 v;\nmov.b128 v, {%1, %2, %3, %4};\nst.relaxed.gpu.global.b128 [%0], v;\n}"
               ::"l"(p), "r"(a), "r"(b), "r"(c), "r"(tag) : "memory");
}
__device__ __forceinline__ void ld_msg(const uint4* p, uint32_t& a, uint32_t& b, uint32_t& c, uint32_t& tag) {
  asm volatile("{\n.reg .b128 v;\nld.relaxed.gpu.global.b128 v, [%4];\nmov.b128 {%0, %1, %2, %3}, v;\n}"
               : "=r"(a), "=r"(b), "=r"(c), "=r"(tag) : "l"(p) : "memory");
}
__device__ __forceinline__ bool elect_one() {
  uint32_t ok;
  asm volatile("{\n.reg .pred p;\nelect.sync _|p, 0xffffffff;\nselp.u32 %0, 1, 0, p;\n}" : "=r"(ok));
  return ok;
}
__device__ __forceinline__ uint32_t lanemask_lt() {
  uint32_t v;
  asm("mov.u32 %0, %%lanemask_lt;" : "=r"(v));
  return v;
}
__device__ __forceinline__ int uniform(int v) { return __shfl_sync(0xffffffffu, v, 0); }
__device__ __forceinline__ uint32_t pack_bf16(float lo, float hi) {
  uint32_t r;
  asm("cvt.rn.bf16x2.f32 %0, %1, %2;" : "=r"(r) : "f"(hi), "f"(lo));
  return r;
}
__device__ __forceinline__ float prmt_f(uint32_t a, uint32_t sel) {
  float r;
  asm("{\n.reg .b32 t;\nprmt.b32 t, %1, 0, %2;\nmov.b32 %0, t;\n}" : "=f"(r) : "r"(a), "r"(sel));
  return r;
}
__device__ __forceinline__ float bf_lo(uint32_t v) { return __uint_as_float(v << 16); }
__device__ __forceinline__ float bf_hi(uint32_t v) { return __uint_as_float(v & 0xffff0000u); }
__device__ __forceinline__ void stsm4(uint32_t addr, uint32_t r0, uint32_t r1, uint32_t r2, uint32_t r3) {
  asm volatile("stmatrix.sync.aligned.m8n8.x4.shared.b16 [%0], {%1, %2, %3, %4};"
               ::"r"(addr), "r"(r0), "r"(r1), "r"(r2), "r"(r3) : "memory");
}
__device__ __forceinline__ void ldsm4(uint32_t addr, uint32_t& r0, uint32_t& r1, uint32_t& r2, uint32_t& r3) {
  asm volatile("ldmatrix.sync.aligned.m8n8.x4.shared.b16 {%0, %1, %2, %3}, [%4];"
               : "=r"(r0), "=r"(r1), "=r"(r2), "=r"(r3) : "r"(addr) : "memory");
}
__device__ __forceinline__ uint32_t movtrans(uint32_t a) {
  uint32_t d;
  asm volatile("movmatrix.sync.aligned.m8n8.trans.b16 %0, %1;" : "=r"(d) : "r"(a));
  return d;
}
__device__ __forceinline__ void mma16816(float (&c)[4], uint32_t a0, uint32_t a1, uint32_t a2, uint32_t a3, uint32_t b0, uint32_t b1) {
  asm volatile("mma.sync.aligned.m16n8k16.row.col.f32.bf16.bf16.f32 {%0,%1,%2,%3}, {%4,%5,%6,%7}, {%8,%9}, {%0,%1,%2,%3};"
               : "+f"(c[0]), "+f"(c[1]), "+f"(c[2]), "+f"(c[3])
               : "r"(a0), "r"(a1), "r"(a2), "r"(a3), "r"(b0), "r"(b1));
}
__device__ __forceinline__ void mma1688(float (&c)[4], uint32_t a0, uint32_t a1, uint32_t b0) {
  asm volatile("mma.sync.aligned.m16n8k8.row.col.f32.bf16.bf16.f32 {%0,%1,%2,%3}, {%4,%5}, {%6}, {%0,%1,%2,%3};"
               : "+f"(c[0]), "+f"(c[1]), "+f"(c[2]), "+f"(c[3]) : "r"(a0), "r"(a1), "r"(b0));
}
__device__ __forceinline__ float2 lds_f2(uint32_t a) {
  float2 v;
  asm volatile("ld.shared.v2.f32 {%0, %1}, [%2];" : "=f"(v.x), "=f"(v.y) : "r"(a) : "memory");
  return v;
}
__device__ __forceinline__ float4 lds_f4(uint32_t a) {
  float4 v;
  asm volatile("ld.shared.v4.f32 {%0, %1, %2, %3}, [%4];" : "=f"(v.x), "=f"(v.y), "=f"(v.z), "=f"(v.w) : "r"(a) : "memory");
  return v;
}
__device__ __forceinline__ float lds_f(uint32_t a) {
  float v;
  asm volatile("ld.shared.f32 %0, [%1];" : "=f"(v) : "r"(a) : "memory");
  return v;
}
__device__ __forceinline__ uint32_t lds_u(uint32_t a) {
  uint32_t v;
  asm volatile("ld.shared.u32 %0, [%1];" : "=r"(v) : "r"(a) : "memory");
  return v;
}
__device__ __forceinline__ void sts_f2(uint32_t a, float x, float y) {
  asm volatile("st.shared.v2.f32 [%0], {%1, %2};" ::"r"(a), "f"(x), "f"(y) : "memory");
}
__device__ __forceinline__ void sts_u4(uint32_t a, uint32_t x, uint32_t y, uint32_t z, uint32_t w) {
  asm volatile("st.shared.v4.u32 [%0], {%1, %2, %3, %4};" ::"r"(a), "r"(x), "r"(y), "r"(z), "r"(w) : "memory");
}
__device__ __forceinline__ void lds_u4(uint32_t a, uint32_t& x, uint32_t& y, uint32_t& z, uint32_t& w) {
  asm volatile("ld.shared.v4.u32 {%0, %1, %2, %3}, [%4];" : "=r"(x), "=r"(y), "=r"(z), "=r"(w) : "r"(a) : "memory");
}
__device__ __forceinline__ float ex2(float x) {
  float y;
  asm("ex2.approx.ftz.f32 %0, %1;" : "=f"(y) : "f"(x));
  return y;
}
__device__ __forceinline__ float rcp_hw(float x) {
  float y;
  asm("rcp.approx.ftz.f32 %0, %1;" : "=f"(y) : "f"(x));
  return y;
}
__device__ __forceinline__ float tanh_hw(float x) {
  float y;
  asm("tanh.approx.f32 %0, %1;" : "=f"(y) : "f"(x));
  return y;
}
__device__ __forceinline__ float quad_sum(float v) {
  v += __shfl_xor_sync(0xffffffffu, v, 1);
  return v + __shfl_xor_sync(0xffffffffu, v, 2);
}
__device__ __forceinline__ float quad_max(float v) {
  v = fmaxf(v, __shfl_xor_sync(0xffffffffu, v, 1));
  return fmaxf(v, __shfl_xor_sync(0xffffffffu, v, 2));
}

template <int N> __device__ __forceinline__ void wgmma_ss(float (&d)[96], uint64_t da, uint64_t db, uint32_t keep = 1);
template <> __device__ __forceinline__ void wgmma_ss<128>(float (&d)[96], uint64_t da, uint64_t db, uint32_t keep) {
  asm volatile(
      "{\n.reg .pred p;\nsetp.ne.u32 p, %66, 0;\n"
      "wgmma.mma_async.sync.aligned.m64n128k16.f32.bf16.bf16 {%0, %1, %2, %3, %4, %5, %6, %7, %8, %9, %10, %11, %12, %13, %14, %15, %16, %17, %18, %19, %20, %21, %22, %23, %24, %25, %26, %27, %28, %29, %30, %31, %32, %33, %34, %35, %36, %37, %38, %39, %40, %41, %42, %43, %44, %45, %46, %47, %48, %49, %50, %51, %52, %53, %54, %55, %56, %57, %58, %59, %60, %61, %62, %63}, %64, %65, p, 1, 1, 0, 1;\n}"
      : "+f"(d[0]), "+f"(d[1]), "+f"(d[2]), "+f"(d[3]), "+f"(d[4]), "+f"(d[5]), "+f"(d[6]), "+f"(d[7]), "+f"(d[8]), "+f"(d[9]), "+f"(d[10]), "+f"(d[11]), "+f"(d[12]), "+f"(d[13]), "+f"(d[14]), "+f"(d[15]), "+f"(d[16]), "+f"(d[17]), "+f"(d[18]), "+f"(d[19]), "+f"(d[20]), "+f"(d[21]), "+f"(d[22]), "+f"(d[23]), "+f"(d[24]), "+f"(d[25]), "+f"(d[26]), "+f"(d[27]), "+f"(d[28]), "+f"(d[29]), "+f"(d[30]), "+f"(d[31]), "+f"(d[32]), "+f"(d[33]), "+f"(d[34]), "+f"(d[35]), "+f"(d[36]), "+f"(d[37]), "+f"(d[38]), "+f"(d[39]), "+f"(d[40]), "+f"(d[41]), "+f"(d[42]), "+f"(d[43]), "+f"(d[44]), "+f"(d[45]), "+f"(d[46]), "+f"(d[47]), "+f"(d[48]), "+f"(d[49]), "+f"(d[50]), "+f"(d[51]), "+f"(d[52]), "+f"(d[53]), "+f"(d[54]), "+f"(d[55]), "+f"(d[56]), "+f"(d[57]), "+f"(d[58]), "+f"(d[59]), "+f"(d[60]), "+f"(d[61]), "+f"(d[62]), "+f"(d[63])
      : "l"(da), "l"(db), "r"(keep));
}

template <> __device__ __forceinline__ void wgmma_ss<192>(float (&d)[96], uint64_t da, uint64_t db, uint32_t keep) {
  asm volatile(
      "{\n.reg .pred p;\nsetp.ne.u32 p, %98, 0;\n"
      "wgmma.mma_async.sync.aligned.m64n192k16.f32.bf16.bf16 {%0, %1, %2, %3, %4, %5, %6, %7, %8, %9, %10, %11, %12, %13, %14, %15, %16, %17, %18, %19, %20, %21, %22, %23, %24, %25, %26, %27, %28, %29, %30, %31, %32, %33, %34, %35, %36, %37, %38, %39, %40, %41, %42, %43, %44, %45, %46, %47, %48, %49, %50, %51, %52, %53, %54, %55, %56, %57, %58, %59, %60, %61, %62, %63, %64, %65, %66, %67, %68, %69, %70, %71, %72, %73, %74, %75, %76, %77, %78, %79, %80, %81, %82, %83, %84, %85, %86, %87, %88, %89, %90, %91, %92, %93, %94, %95}, %96, %97, p, 1, 1, 0, 1;\n}"
      : "+f"(d[0]), "+f"(d[1]), "+f"(d[2]), "+f"(d[3]), "+f"(d[4]), "+f"(d[5]), "+f"(d[6]), "+f"(d[7]), "+f"(d[8]), "+f"(d[9]), "+f"(d[10]), "+f"(d[11]), "+f"(d[12]), "+f"(d[13]), "+f"(d[14]), "+f"(d[15]), "+f"(d[16]), "+f"(d[17]), "+f"(d[18]), "+f"(d[19]), "+f"(d[20]), "+f"(d[21]), "+f"(d[22]), "+f"(d[23]), "+f"(d[24]), "+f"(d[25]), "+f"(d[26]), "+f"(d[27]), "+f"(d[28]), "+f"(d[29]), "+f"(d[30]), "+f"(d[31]), "+f"(d[32]), "+f"(d[33]), "+f"(d[34]), "+f"(d[35]), "+f"(d[36]), "+f"(d[37]), "+f"(d[38]), "+f"(d[39]), "+f"(d[40]), "+f"(d[41]), "+f"(d[42]), "+f"(d[43]), "+f"(d[44]), "+f"(d[45]), "+f"(d[46]), "+f"(d[47]), "+f"(d[48]), "+f"(d[49]), "+f"(d[50]), "+f"(d[51]), "+f"(d[52]), "+f"(d[53]), "+f"(d[54]), "+f"(d[55]), "+f"(d[56]), "+f"(d[57]), "+f"(d[58]), "+f"(d[59]), "+f"(d[60]), "+f"(d[61]), "+f"(d[62]), "+f"(d[63]), "+f"(d[64]), "+f"(d[65]), "+f"(d[66]), "+f"(d[67]), "+f"(d[68]), "+f"(d[69]), "+f"(d[70]), "+f"(d[71]), "+f"(d[72]), "+f"(d[73]), "+f"(d[74]), "+f"(d[75]), "+f"(d[76]), "+f"(d[77]), "+f"(d[78]), "+f"(d[79]), "+f"(d[80]), "+f"(d[81]), "+f"(d[82]), "+f"(d[83]), "+f"(d[84]), "+f"(d[85]), "+f"(d[86]), "+f"(d[87]), "+f"(d[88]), "+f"(d[89]), "+f"(d[90]), "+f"(d[91]), "+f"(d[92]), "+f"(d[93]), "+f"(d[94]), "+f"(d[95])
      : "l"(da), "l"(db), "r"(keep));
}

template <int R>
__device__ __forceinline__ void pin_regs(float (&a)[2][96]) {
#pragma unroll
  for (int m = 0; m < 2; m++)
#pragma unroll
    for (int i = 0; i < R; i++) asm volatile("" : "+f"(a[m][i])::"memory");
}

struct Ctx {
  uint32_t sb;
  int m, n, wg, w, lane;
};
__device__ __forceinline__ Ctx make_ctx(uint32_t sb, int id) {
  int lane;
  asm volatile("mov.u32 %0, %%laneid;" : "=r"(lane));
  asm volatile("" : "+r"(id), "+r"(sb));
  return Ctx{sb, (id >> 3) & 15, id & 7, id >> 9, (id >> 7) & 3, lane};
}
#define UNPACK_CTX(c) const uint32_t sb = c.sb; const int m = c.m, n = c.n, wg = c.wg, w = c.w, lane = c.lane

__device__ __forceinline__ uint32_t poll_line(const uint32_t* word, uint32_t target, uint32_t need) {
  uint32_t v;
  asm volatile(
      "{\n.reg .pred p;\n.reg .u32 it, m;\n.reg .s32 d;\nmov.u32 it, 0;\n"
      "POLL_LOOP:\n"
      "ld.relaxed.gpu.global.u32 %0, [%1];\n"
      "sub.s32 d, %0, %2;\n"
      "setp.ge.s32 p, d, 0;\n"
      "vote.sync.ballot.b32 m, p, 0xffffffff;\n"
      "and.b32 m, m, %3;\n"
      "setp.eq.u32 p, m, %3;\n"
      "@p bra.uni POLL_DONE;\n"
      "add.u32 it, it, 1;\n"
      "setp.lt.u32 p, it, 0x400000;\n"
      "@p bra.uni POLL_LOOP;\n"
      "trap;\n"
      "POLL_DONE:\n}"
      : "=&r"(v) : "l"(word), "r"(target), "r"(need) : "memory");
  return v;
}
__device__ __forceinline__ uint32_t ld_relaxed(const uint32_t* p) {
  uint32_t v;
  asm volatile("ld.relaxed.gpu.global.u32 %0, [%1];" : "=r"(v) : "l"(p) : "memory");
  return v;
}
__device__ __forceinline__ float chain(float x, uint32_t on, uint32_t zero) {
  return __uint_as_float(__float_as_uint(x) | (on & zero));
}
constexpr int MSG_SPINS = 1 << 20;

constexpr int STAGES_PER_LAYER = 152;
__device__ __forceinline__ int nib(uint64_t v, int i) { return (int)(v >> (4 * i)) & 15; }
__device__ __forceinline__ bool tile_wide(int t) { return (0x23 >> t) & 1; }
__device__ __forceinline__ void weight_coords(const Params& p, int t, int n, const CUtensorMap*& map, int& c0, int& c2) {
  map = &p.t.wqkv + nib(0x4233100ull, t);
  c0 = t < 2 ? 128 * n + 64 * t : 0;
  c2 = t < 2 ? 0 : (t == 2 || t == 6) ? 2 * n : 7 * n + 2 * t - 6;
}

template <bool IS_A>
__device__ __forceinline__ void producer(const Params& p, uint32_t sb, int m, int n, int lane) {
  const uint32_t low = (1u << (4 * n)) - 1, others = (0x6543210u & low) | (0x7654321u & ~low);
  const uint64_t order_x = (uint64_t)(others * 2 + 0x1111111u) << 36 | (uint64_t)others * 2 << 8 | (n * 0x22 + 0x10);
  int inflight = 4, cur = 0;
  uint32_t fb = sb + BAR_FULL + 32, rb = sb + BAR_EMPTY, rph = 0, pos = 0, tag32 = 0, seen = 0;
  const uint32_t fend = sb + BAR_FULL + 8 * NBAR, rend = sb + BAR_EMPTY + 8 * NBAR;
  const uint32_t* word = p.g->flags + m * 32 + (lane < 16 ? lane >> 1 : lane & 7);
#pragma unroll 1
  for (int sg = 1; sg < 22; sg++) {
    const int layer = sg >= 11, s = sg == 1 ? 2 : sg == 2 ? 1 : sg - 11 * layer;
    const int t = nib(0x65434321010ull, s), kind = nib(0x32110031100ull, s);
    const bool wide = tile_wide(t);
    const uint32_t bbytes = wide ? 3 * UNIT : 2 * UNIT, base = sb + (IS_A ? bbytes : (m & 1) * (bbytes / 2));
    if (IS_A && kind == 0) {
      if (sg == 2) seen = tag32 = (__ldcg(p.g->epoch + m * 8 + n) + 1) << 5;
#pragma unroll 1
      for (int k = 0; k < 2; k++) {
#pragma unroll 1
        for (; inflight > (wide ? 3 : 4); inflight--) {
          mbar_wait(rb, rph);
          rb += 8;
          if (rb == rend) { rb -= 8 * NBAR; rph ^= 1; }
        }
        if (elect_one()) mbar_arrive(fb);
        inflight++;
        fb += 8;
        if (fb == fend) fb -= 8 * NBAR;
        pos += bbytes + 2 * UNIT;
        if (pos >= RING_UNITS * UNIT) pos -= RING_UNITS * UNIT;
      }
      continue;
    }
    const int mul = t == 6 ? 448 : t == 2 ? 128 : 64, count = sg == 1 ? 12 : 2 * nib(0x4871ull, kind);
    uint64_t order0 = sg == 1 ? 0xFEDCBA987654ull : kind == 3 ? 0x76543210u : order_x >> (8 * (kind & 1));
    uint32_t special = (s == 4 || s == 10) ? 0x10 : s == 9 ? 0xF : s == 0;
    if (IS_A) special |= (kind & 1 ? 0 : 3) | (count >= 4 ? 1u << (count - 4) : 0);
    if (s >= 9) pos = (s + 6) * UNIT;
    const CUtensorMap* map;
    int c0 = 0, c2 = 0, ev = 0;
    if (IS_A) {
      map = &p.t.xin + (t == 2 ? 2 : t == 6 ? 3 : sg >= 4);
      ev = 9 * layer + (t < 2 ? 0 : t == 2 ? 1 : t < 6 ? 4 : 5);
      if (elect_one()) asm volatile("prefetch.tensormap [%0];" ::"l"(map) : "memory");
    } else {
      weight_coords(p, t, n, map, c0, c2);
    }
#pragma unroll 1
    for (int add = 0; add < mul; add += 64) {
      uint64_t order = order0;
      const int need = kind == 3 ? ev : ev - 1 + (lane & 1), sh = kind == 3 ? 16 : 0;
      uint32_t ready = IS_A ? __ballot_sync(0xffffffffu, cur >= need) >> sh : 0;
#pragma unroll 1
      for (int k = 0; k < count; k++) {
        const int code = order & 15, kc = code * mul + add;
        order >>= 4;
        if ((special >> k) & 1) {
          const int lag = wide ? (s == 9 && k == 2 ? 2 : 3) : ((s == 4 || s == 10) && add == 0 && k < 4) ? 3 : 4;
#pragma unroll 1
          for (; inflight > lag; inflight--) {
            mbar_wait(rb, rph);
            rb += 8;
            if (rb == rend) { rb -= 8 * NBAR; rph ^= 1; }
          }
          inflight++;
          if (IS_A) {
            if (kind == 3 ? t == 2 && add + k == 64 : !(kind & 1) && k < 2) {
              if (t == 2) mbar_wait(sb + BAR_PUB + 8, layer);
              if (elect_one()) mbar_arrive(fb);
              goto next_stage;
            }
            if (k == count - 4 && sg >= 3) seen = ld_relaxed(word);
          }
        } else {
          mbar_wait(rb, rph);
          rb += 8;
          if (rb == rend) { rb -= 8 * NBAR; rph ^= 1; }
        }
        if (IS_A && !((ready >> code) & 1)) {
          cur = max(cur, (int)(seen - tag32));
          ready = __ballot_sync(0xffffffffu, cur >= need) >> sh;
          if (!((ready >> code) & 1)) {
            cur = (int)(poll_line(word, tag32 + need, 1u << (code + sh)) - tag32);
            ready = __ballot_sync(0xffffffffu, cur >= need) >> sh;
          }
          asm volatile("fence.acquire.gpu;" ::: "memory");
          fence_async_global();
          seen = ld_relaxed(word);
        }
        if (elect_one()) {
          if (!IS_A) tma_ld3_pair(base + pos, map, fb, c0, kc + 32 * (m & 1), c2);
          else tma_ld_act(base + pos, map, fb, kc, m);
          mbar_expect_tx(fb, IS_A ? 16384 : bbytes);
        }
      next_stage:
        fb += 8;
        if (fb == fend) fb -= 8 * NBAR;
        pos += bbytes + 2 * UNIT;
        if (pos >= RING_UNITS * UNIT) pos -= RING_UNITS * UNIT;
      }
      special = !IS_A ? 0 : t == 2 ? 1 : add == 128 ? 0x10 : 0;
      if (t == 2) order0 = others << 4 | n;
      if (IS_A && (t == 2 || add == 64 || add == 192)) ev++;
    }
  }
}

__device__ __forceinline__ void publisher(const Params& p, uint32_t sb, int m, int n) {
  {
    const int ts = PACE0 + PACE_M * m, tx = PACE0 + PACE_N * n;
#pragma unroll 1
    for (int k = 0; k < 2; k++) {
      __nanosleep(k == 0 ? min(ts, tx) : abs(ts - tx));
      if ((ts <= tx) == (k == 0)) {
        mbar_expect_tx(sb + BAR_CSLD, 24576);
        tma_ld3(sb + OFF_STG, &p.t.wqkv, sb + BAR_CSLD, 128 * n, 64 * m, 0);
        tma_ld3(sb + OFF_STG + 12288, &p.t.wqkv, sb + BAR_CSLD, 128 * n, 64 * m + 32, 0);
      } else {
#pragma unroll 1
        for (int h = 0; h < 2; h++) {
          const uint32_t xr = sb + BAR_XRDY + 8 * h;
          mbar_expect_tx(xr, 16384);
          tma_ld_act(sb + OFF_X + h * 16384, &p.t.xin, xr, 128 * n + 64 * h, m);
          asm volatile("mbarrier.arrive.shared::cta.b64 _, [%0], 3;" ::"r"(xr) : "memory");
        }
      }
    }
  }
  const uint32_t tag = __ldcg(p.g->epoch + m * 8 + n) + 1;
  uint32_t* word = p.g->flags + m * 32 + n;
  const int mn = m * 8 + n; (void)mn;
  st_relaxed(word, 32 * tag);
#pragma unroll 1
  for (int c = 0; c < 16; c++) {
    const int e = c >= 9 ? c - 9 : c;
    if (e == 2 || e == 7) {
      asm volatile("prefetch.tensormap [%0];" ::"l"(&p.t.out) : "memory");
      mbar_wait(sb + BAR_XRDY, e == 2);
      tma_st_act(&p.t.out, sb + OFF_X, 128 * n, m);
      bulk_commit();
      mbar_wait(sb + BAR_XRDY + 8, e == 2);
      bulk_wait_all();
      mbar_arrive(sb + BAR_XGO);
      PROF_E(7 * (c >= 9) + (e < 4 ? 2 : 6), 11);
    } else {
      mbar_wait(sb + BAR_PUB + 8 * e, c >= 9);
    }
    asm volatile("fence.release.gpu;" ::: "memory");
    asm volatile("red.relaxed.gpu.global.add.u32 [%0], 1;" ::"l"(word) : "memory");
    PROF_E(7 * (c >= 9) + nib(0x665432210ull, e), (0x108 >> e) & 1 ? 14 : 12);
  }
  p.g->epoch[m * 8 + n] = tag;
}

__device__ __forceinline__ void sum_rows(uint32_t buf, int iters, float (&a)[8], int lane) {
  uint32_t addr = buf + (lane >> 3) * 128 + (((lane & 7) ^ (lane >> 3)) << 4);
#pragma unroll 1
  for (int it = 0; it < iters; it++) {
    uint32_t u[2][4];
    lds_u4(addr, u[0][0], u[0][1], u[0][2], u[0][3]);
    lds_u4((addr ^ 64) + 512, u[1][0], u[1][1], u[1][2], u[1][3]);
    addr += 1024;
#pragma unroll
    for (int e = 0; e < 8; e++) { a[2 * (e & 3)] += bf_lo(u[e >> 2][e & 3]); a[2 * (e & 3) + 1] += bf_hi(u[e >> 2][e & 3]); }
  }
}
__device__ __forceinline__ void publish_sums(const float (&a)[8], uint4* dst, int lane, uint32_t tag) {
  const bool u8 = lane & 8, u16 = lane & 16;
  float h4[4], h2[2];
#pragma unroll
  for (int e = 0; e < 4; e++) h4[e] = (u8 ? a[4 + e] : a[e]) + __shfl_xor_sync(0xffffffffu, u8 ? a[e] : a[4 + e], 8);
#pragma unroll
  for (int e = 0; e < 2; e++) h2[e] = (u16 ? h4[2 + e] : h4[e]) + __shfl_xor_sync(0xffffffffu, u16 ? h4[e] : h4[2 + e], 16);
  st_msg(dst + (lane & 7) * 4 + (u8 ? 2 : 0) + (u16 ? 1 : 0), __float_as_uint(h2[0]), __float_as_uint(h2[1]), 0u, tag);
}

__device__ __forceinline__ void colsum_helper(const Params& p, uint32_t sb, int m, int n, int lane) {
  const uint32_t tag = __ldcg(p.g->epoch + m * 8 + n) + 1;
  const int mn = m * 8 + n; (void)mn;
#pragma unroll 1
  for (int k = lane; k < 288; k += 32) {
    const uint32_t bb = __ldg(reinterpret_cast<const uint32_t*>(k < 224 ? p.b1 + 448 * n : p.b2 + 128 * n - 448) + k);
    const float sc = k < 224 ? 0.5f : 1.f;
    sts_f2(sb + (k < 224 ? OFF_CSF + k * 16 + 8 : OFF_CSQ + 1536 + (k - 224) * 8), sc * bf_lo(bb), sc * bf_hi(bb));
  }
  __syncwarp();
  if (elect_one()) mbar_arrive(sb + BAR_BIAS);
  bar_sync(BAR_HLP, 160);
  {
    uint4* base = p.g->csp + n * 17 * 224 + 12 * m + min(lane & 15, 11);
    float s0 = 0.f, s1 = 0.f;
#pragma unroll 1
    for (int g = 0; g < 2; g++) {
      uint32_t x[4], y[4];
#pragma unroll 1
      for (int it = 0; it < MSG_SPINS; it++) {
        uint32_t bad = 0, z, tg;
        if (g == 0 || it > 0) __nanosleep(CS_NS);
#pragma unroll
        for (int k = 0; k < 4; k++) { ld_msg(base + (g * 8 + (lane >> 4) * 4 + k) * 224, x[k], y[k], z, tg); bad |= tg ^ tag; }
        if (__all_sync(0xffffffffu, bad == 0)) break;
      }
#pragma unroll
      for (int k = 0; k < 4; k++) { s0 += __uint_as_float(x[k]); s1 += __uint_as_float(y[k]); }
    }
    s0 += __shfl_xor_sync(0xffffffffu, s0, 16);
    s1 += __shfl_xor_sync(0xffffffffu, s1, 16);
    if (lane < 12) st_msg(base + 16 * 224, __float_as_uint(s0), __float_as_uint(s1), 0u, tag);
    PROF_E(-1, 3);
  }
  PROF_E(-1, 1);
#pragma unroll 1
  for (int c = 0; c < 7; c++) {
    float a[8] = {0.f, 0.f, 0.f, 0.f, 0.f, 0.f, 0.f, 0.f};
#pragma unroll 1
    for (int h = 0; h < 2; h++) {
      if (elect_one()) {
        mbar_expect_tx(sb + BAR_CSLD + 8, 4096);
        tma_ld2(sb + OFF_HLP, &p.t.w1c, sb + BAR_CSLD + 8, 448 * n + 64 * c, 64 * m + 32 * h);
        if (c < 6) asm volatile("cp.async.bulk.prefetch.tensor.2d.L2.global [%0, {%1, %2}];" ::"l"(&p.t.w1c), "r"(448 * n + 64 * c + 64), "r"(64 * m + 32 * h) : "memory");
      }
      mbar_wait(sb + BAR_CSLD + 8, h);
      sum_rows(sb + OFF_HLP, 4, a, lane);
      __syncwarp();
    }
    publish_sums(a, p.g->csp + ((8 + n) * 17 + m) * 224 + c * 32, lane, tag);
  }
  PROF_E(-1, 2);
  if (elect_one()) {
#pragma unroll 1
    for (int k = 0; k < 3; k++) {
      mbar_wait(sb + BAR_XGO, k & 1);
      __nanosleep(BDELAY);
#pragma unroll 1
      for (int w = 0; w < 4; w++) {
        tma_st_warp(&p.t.out_w, sb + OFF_X + 16384 + w * 4096, 128 * n + 64, m, w);
        bulk_commit();
        bulk_wait_read();
        if (w < 3) __nanosleep(BSPLIT);
      }
      bulk_wait_all();
      asm volatile("mbarrier.arrive.shared::cta.b64 _, [%0], 4;" ::"r"(sb + BAR_PUB + (k & 1 ? 64 : 24)) : "memory");
    }
  }
}

__device__ __forceinline__ void poll_msgs2(const uint4* pa, const uint4* pb, float (&v)[4], uint32_t tag) {
#pragma unroll 1
  for (int it = 0; it < MSG_SPINS; it++) {
    uint32_t x[4], z, ta, tb;
    ld_msg(pa, x[0], x[1], z, ta);
    ld_msg(pb, x[2], x[3], z, tb);
#pragma unroll
    for (int e = 0; e < 4; e++) v[e] = __uint_as_float(x[e]);
    if (__all_sync(0xffffffffu, ta == tag && tb == tag)) break;
  }
}
__device__ __forceinline__ void colsum_total(const Params& p, const Ctx& cx, int mat, uint32_t tag) {
  uint4* base = p.g->csp + (mat * 8 + cx.n) * 17 * 224;
  const int per = 12 + 2 * mat, k = 2 * cx.w + (cx.lane >> 4), ia = per * cx.m + k, ib = per * cx.m + min(k + 8, per - 1);
  float v[4];
  poll_msgs2(base + (cx.lane & 15) * 224 + ia, base + (cx.lane & 15) * 224 + ib, v, tag);
#pragma unroll 1
  for (int d = 1; d < 16; d *= 2)
#pragma unroll
    for (int e = 0; e < 4; e++) v[e] += __shfl_xor_sync(0xffffffffu, v[e], d);
  const bool hi = cx.lane & 1;
  if ((cx.lane & 14) == 0) st_msg(base + 16 * 224 + (hi ? ib : ia), __float_as_uint(hi ? v[2] : v[0]), __float_as_uint(hi ? v[3] : v[1]), 0u, tag);
}
__device__ __forceinline__ void colsum_gather(const Params& p, const Ctx& cx, int mat, uint32_t tag) {
  const uint4* base = p.g->csp + ((mat * 8 + cx.n) * 17 + 16) * 224;
  const int ia = cx.w * 32 + cx.lane, ib = min(ia + 128, 191 + 32 * mat);
  float v[4];
  poll_msgs2(base + ia, base + ib, v, tag);
  const uint32_t tab = cx.sb + (mat ? OFF_CSF : OFF_CSQ);
  sts_f2(tab + (ia << (3 + mat)), v[0], v[1]);
  sts_f2(tab + (ib << (3 + mat)), v[2], v[3]);
}

#define ACC(q, j, e) acc[(q) & 1][4 * (j) + 2 * ((q) >> 1) + (e)]

constexpr uint32_t RING16 = RING_UNITS * (UNIT >> 4);
__device__ __forceinline__ bool tile_split(int i) { return (0xD98 >> i) & 1; }

__device__ __forceinline__ void write_run_desc(uint32_t sb, int i, int step) {
  const int layer = i >= 7, t = i - 7 * layer, part = tile_split(i) ? step : 2;
  const bool wide = tile_wide(t), own = t != 2 && t != 6 && part != 1 && i != 0, second = t == 1 || t == 4;
  const uint32_t z16 = (wide ? 5 : 4) * (UNIT >> 4), a_off = z16 - 1024 + (uint32_t)DESC_A - (uint32_t)DESC_B;
  const int gl = 16 * t + (part == 2 ? 0 : second ? 16 * part - 14 : 4 * part), g0 = layer * STAGES_PER_LAYER + gl;
  const uint32_t s16 = (sb & 0x3FFFF) >> 4, bfirst = (uint32_t)DESC_B + s16;
  const int nkb = t == 6 ? 56 : part == 0 ? 2 : 12 + 2 * part;
  const bool win1 = t == 1 && part != 0;
  const int run = win1 ? WIN1 + 1 : t == 2 ? WIN2 + 1 : nkb;
  const int rest = win1 ? 64 | (nkb - 1 - WIN1) : t == 2 ? 64 | (7 - WIN2) | (8 << 7) : 0;
  const uint32_t blo = bfirst + z16 * (wide ? (gl + (t == 5 ? 3 : 0)) & 3 : (gl + 3) % 5);
  const uint32_t alo = own ? (uint32_t)DESC_A + s16 + (OFF_X >> 4) : blo + a_off;
  const uint32_t aoff = own ? alo + 1024 - (blo == bfirst + RING16 - z16 ? bfirst : blo + z16) : a_off;
  const bool xwait = part == 0 && !second, keep = !(part == 0 || t == 5);
  sts_u4(sb + OFF_RUN + (2 * i + step) * 16, blo, alo, aoff,
         ((g0 / NBAR) & 1) | xwait << 1 | keep << 2 | 8 * (g0 % NBAR) | run << 6 | rest << 12);
}

__device__ __forceinline__ void write_partial_stats(const Params& p, const Ctx& c, int ln, uint32_t tag) {
  const uint32_t xrow = c.sb + OFF_X + c.w * 4096 + c.lane * 128;
  float s = 0.f, q = 0.f, s1 = 0.f, q1 = 0.f;
#pragma unroll 4
  for (int j = 0; j < 16; j++) {
    uint32_t u[4];
    lds_u4(xrow + (j >> 3) * 16384 + (((j & 7) ^ (c.lane & 7)) << 4), u[0], u[1], u[2], u[3]);
#pragma unroll
    for (int e = 0; e < 4; e++) {
      const float a = bf_lo(u[e]), d = bf_hi(u[e]);
      s += a; q = fmaf(a, a, q);
      s1 += d; q1 = fmaf(d, d, q1);
    }
  }
  s += s1;
  q += q1;
  st_msg(p.g->stats + (ln * 8 + c.n) * SEQ + 128 * c.m + 32 * c.w + c.lane, __float_as_uint(s),
         __float_as_uint(fmaxf(q - s * s * (1.f / 128.f), 0.f)), 0u, tag);
}

template <int N>
__device__ __forceinline__ void mainloop(const Params& p, float (&acc)[2][96], uint32_t sb, int i, int step, int mn) {
  constexpr uint32_t Z16 = (2 + N / 64) * (UNIT >> 4);
  constexpr uint32_t A_OFF = Z16 - 1024 + (uint32_t)DESC_A - (uint32_t)DESC_B;
  const int wg = i & 1;
  const uint32_t s16 = (sb & 0x3FFFF) >> 4;
  const uint32_t blast = (uint32_t)DESC_B + s16 + RING16 - Z16, flast = sb + BAR_FULL + 8 * (NBAR - 1);
  uint32_t blo = (uint32_t)DESC_B + s16, alo = blo + A_OFF, aoff = A_OFF, misc = 16 << 6;
  if (N == 128 || i > 0) lds_u4(sb + OFF_RUN + (2 * i + step) * 16, blo, alo, aoff, misc);
  uint32_t keep = misc & 4;
  int run = (misc >> 6) & 63, rest = misc >> 12;
  uint32_t fb = sb + BAR_FULL + (misc & 0x38), ph = misc & 1;
  uint32_t prev = sb + BAR_DUMMY - 8 * NBAR;
  const uint32_t lane_id = __popc(__ballot_sync(0xffffffffu, true) & lanemask_lt()), rel = pair_offset(sb, lane_id & 1) + 8 * NBAR;
  pin_regs<N / 2>(acc);
  if (N == 128 || i > 0) bar_sync(BAR_ORDER + wg, 256);
  else bar_sync(BAR_INIT0, 160);
  if (N == 192 && i == 0 && threadIdx.x == 0) PROF_U(8);
  mbar_wait(fb, ph);
  if (N == 192 && i == 0 && threadIdx.x == 0) PROF_U(9);
  if (N == 192 && i == 0) cluster_wait();
  if (misc & 2) mbar_wait(sb + BAR_XGO, N == 192);
  if (step == 0 || !tile_split(i)) PROF_T(4 + i * 4);
  if (step == 1 && tile_split(i)) PROF_E(i, 13);
#pragma unroll 1
  while (true) {
    const uint64_t da = (DESC_A & ~0xffffffffull) | alo, db = (DESC_B & ~0xffffffffull) | blo;
    asm volatile("wgmma.fence.sync.aligned;" ::: "memory");
    wgmma_ss<N>(acc[0], da, db, keep);
    wgmma_ss<N>(acc[1], da + 64, db, keep);
    keep = 4;
    wgmma_ss<N>(acc[0], da + 2, db + 128);
    wgmma_ss<N>(acc[1], da + 66, db + 128);
    asm volatile("wgmma.commit_group.sync.aligned;" ::: "memory");
    asm volatile("wgmma.wait_group.sync.aligned 1;" ::: "memory");
    PROF_S(jj++);
    if (lane_id < 2) mbar_arrive_cluster(prev + rel);
    prev = fb;
    if (fb == flast) { fb -= 8 * NBAR; ph++; }
    fb += 8;
    if (blo == blast) blo -= RING16;
    blo += Z16;
    alo = blo + aoff;
    aoff = A_OFF;
    run--;
    const bool ready = mbar_test(fb, ph) && run != 0;
    asm volatile("wgmma.fence.sync.aligned;" ::: "memory");
    wgmma_ss<N>(acc[0], da + 4, db + 4 * N);
    wgmma_ss<N>(acc[1], da + 68, db + 4 * N);
    wgmma_ss<N>(acc[0], da + 6, db + 4 * N + 128);
    wgmma_ss<N>(acc[1], da + 70, db + 4 * N + 128);
    asm volatile("wgmma.commit_group.sync.aligned;" ::: "memory");
    if (!ready) {
      bool window = false;
      if (run == 0) {
        if (rest == 0) break;
        window = rest & 64;
        if (window) bar_arrive(BAR_GO, 256);
        else alo = (uint32_t)DESC_A + s16 + (OFF_STG >> 4);
        run = rest & 63;
        rest >>= 7;
      }
      mbar_wait(fb, ph);
      if (window) bar_sync(BAR_DONE, 256);
    }
  }
  if (i < 13 && !(LATE_O && N == 192 && (misc >> 12))) bar_arrive(BAR_ORDER + (wg ^ 1), 256);
  if (N == 128 && ((0x2244 >> i) & 1)) {
    const Ctx cx = make_ctx(sb, mn);
    const uint32_t xrow = cx.sb + OFF_X + cx.w * 4096 + cx.lane * 128 + ((cx.lane & 7) << 4);
    const bool leader = elect_one();
    asm volatile("wgmma.wait_group.sync.aligned 0;" ::: "memory");
    pin_regs<64>(acc);
    PROF_T(5 + i * 4);
    PROF_E(i, 0);
#pragma unroll
    for (int h = 0; h < 2; h++) {
      if (h == 1 && p.zero != 0) break;
#pragma unroll
      for (int j = 8 * h; j < 8 * h + 8; j++)
        stsm4((xrow ^ ((j & 7) << 4)) + h * 16384, pack_bf16(ACC(0, j, 0), ACC(0, j, 1)), pack_bf16(ACC(1, j, 0), ACC(1, j, 1)),
              pack_bf16(ACC(2, j, 0), ACC(2, j, 1)), pack_bf16(ACC(3, j, 0), ACC(3, j, 1)));
      fence_async_smem();
      __syncwarp();
      if (leader) {
        mbar_arrive(sb + BAR_XRDY + 8 * h);
        if (i == 13) {
          tma_st_warp(&p.t.out_w, cx.sb + OFF_X + h * 16384 + cx.w * 4096, 128 * cx.n + 64 * h, cx.m, cx.w);
          bulk_commit();
          if (h == 1) bulk_wait_read();
        }
      }
      if (h == 0 && lane_id < 2) mbar_arrive_cluster(prev + rel);
    }
    PROF_E(i, 4);
    if (EARLY_STATS == 1 ? i < 13 : i == 2 || i == 9) write_partial_stats(p, cx, (i + 3) >> 2, lds_u(sb + OFF_TAG));
    PROF_E(i, 5);
    return;
  }
  asm volatile("wgmma.wait_group.sync.aligned 0;" ::: "memory");
  pin_regs<N / 2>(acc);
  if (lane_id < 2) mbar_arrive_cluster(prev + rel);
  PROF_T(5 + i * 4);
  PROF_E(i, 0);
}

__device__ __forceinline__ void finish_row_stats(const Params& p, const Ctx& c, int ln, uint32_t tag) {
  const uint4* src = p.g->stats + ln * 8 * SEQ + 128 * c.m + 32 * c.w + c.lane;
  uint32_t ps[8], pm[8];
#pragma unroll 1
  for (int it = 0; it < MSG_SPINS; it++) {
    uint32_t bad = 0, u, tg;
    if ((EARLY_STATS == 2 && ln == 2) || it > 0) __nanosleep(STAT_NS);
#pragma unroll
    for (int k = 0; k < 8; k++) { ld_msg(src + k * SEQ, ps[k], pm[k], u, tg); bad |= tg ^ tag; }
    if (__all_sync(0xffffffffu, bad == 0)) break;
  }
  float s = 0.f, m2 = 0.f;
#pragma unroll
  for (int k = 0; k < 8; k++) s += __uint_as_float(ps[k]);
  const float mean = s * (1.f / DM);
#pragma unroll
  for (int k = 0; k < 8; k++) {
    const float d = __uint_as_float(ps[k]) * (1.f / 128.f) - mean;
    m2 += fmaf(128.f * d, d, __uint_as_float(pm[k]));
  }
  sts_f2(c.sb + OFF_ROW + (32 * c.w + c.lane) * 8, rsqrtf(m2 * (1.f / DM) + 1e-5f), mean);
  __syncwarp();
}

__device__ __forceinline__ void attn_scores(const uint32_t* qa, const uint32_t* qb, const uint32_t* kp, const uint32_t* ka,
                                            const uint32_t* kb, float (&l)[4], const float4& zero, const bool (&early)[2]) {
  float s[3][4];
#pragma unroll
  for (int x = 0; x < 3; x++) {
    const uint32_t* kk = x == 0 ? kp : x == 1 ? ka : kb;
    asm volatile("mma.sync.aligned.m16n8k16.row.col.f32.bf16.bf16.f32 {%0,%1,%2,%3}, {%4,%5,%6,%7}, {%8,%9}, {%10,%11,%12,%13};"
                 : "=f"(s[x][0]), "=f"(s[x][1]), "=f"(s[x][2]), "=f"(s[x][3])
                 : "r"(qa[0]), "r"(qb[0]), "r"(qa[1]), "r"(qb[1]), "r"(kk[0]), "r"(kk[1]), "f"(zero.x), "f"(zero.y),
                   "f"(zero.z), "f"(zero.w));
  }
#pragma unroll
  for (int x = 0; x < 3; x++) {
    const uint32_t* kk = x == 0 ? kp : x == 1 ? ka : kb;
    mma16816(s[x], qa[2], qb[2], qa[3], qb[3], kk[2], kk[3]);
  }
#pragma unroll
  for (int e = 0; e < 2; e++) {
    l[e] = early[e] ? s[0][e] : s[1][e];
    l[2 + e] = early[e] ? s[1][2 + e] : s[2][2 + e];
  }
}

__device__ __forceinline__ void attn_mix(const float (&l)[4], const float (&sc)[4], const float (&off)[4], const float (&rk)[4],
                                         const uint32_t* vp, const uint32_t* va, const uint32_t* vb, float (&o)[4][4],
                                         float (&sum)[2], uint32_t mask, uint32_t zero) {
  float x[4];
#pragma unroll
  for (int e = 0; e < 4; e++) x[e] = fmaf(l[e], sc[e], off[e]);
  const float ml = quad_max(fmaxf(x[0], x[1])), mh = quad_max(fmaxf(x[2], x[3]));
  x[0] = ex2(x[0] - ml); x[1] = ex2(x[1] - ml);
  x[2] = ex2(x[2] - mh); x[3] = ex2(x[3] - mh);
  sum[0] = rcp_hw(quad_sum(x[0] + x[1]));
  sum[1] = rcp_hw(quad_sum(x[2] + x[3]));
  const uint32_t pl = pack_bf16(x[0] * rk[0], x[1] * rk[1]), ph = pack_bf16(x[2] * rk[2], x[3] * rk[3]);
  const uint32_t a0 = pl & ~mask, a1 = ph & mask, a2 = pl & zero, a3 = ph & ~mask, c0 = pl & mask, c1 = ph & zero;
#pragma unroll
  for (int jn = 0; jn < 4; jn++) {
    o[jn][0] = o[jn][1] = o[jn][2] = o[jn][3] = 0.f;
    mma16816(o[jn], a0, a1, a2, a3, va[jn], vb[jn]);
  }
#pragma unroll
  for (int jn = 0; jn < 4; jn++) mma1688(o[jn], c0, c1, vp[jn]);
}

__device__ __forceinline__ void gelu_epilogue(const Params& p, float (&acc)[2][96], const Ctx& cx, int t) {
  UNPACK_CTX(cx);
  (void)wg;
  float rs[4], rm[4];
#pragma unroll
  for (int q = 0; q < 4; q++) {
    const float2 v = lds_f2(sb + OFF_ROW + (32 * w + 8 * q + (lane >> 2)) * 8);
    rs[q] = 0.5f * v.x;
    rm[q] = -rs[q] * v.y;
  }
  const int col0 = 128 * (t - 3);
  const uint32_t stg = sb + OFF_STG + w * 4096;
  const uint32_t ctab = sb + OFF_CSF + (col0 / 2 + (lane & 3)) * 16, srow = stg + lane * 128 + ((lane & 7) << 4);
  __nanosleep((t == 5 ? STAG5 : t == 4 ? STAG4 : STAG3) * w);
  float4 nb = lds_f4(ctab);
#pragma unroll
  for (int c = 0; c < 3; c++) {
    if (c == 2 && t != 5) break;
    uint32_t hp[8][4];
#pragma unroll
    for (int j = 0; j < 8; j++) {
      const float4 cb = nb;
      if (8 * c + j < 23) nb = lds_f4(ctab + (8 * c + j + 1) * 64);
#pragma unroll
      for (int q = 0; q < 4; q++) {
        float y[2];
        const int k = 4 * j + q - GELU_DEP;
        const float rmq = k >= 0 ? chain(rm[q], hp[k >> 2][k & 3], p.zero) : rm[q];
#pragma unroll
        for (int e = 0; e < 2; e++) {
          const float z = fmaf(ACC(q, 8 * c + j, e), rs[q], fmaf(rmq, e ? cb.y : cb.x, e ? cb.w : cb.z));
          const float u = z * fmaf(z * z, 8.f * 0.7978845608028654f * 0.044715f, 2.f * 0.7978845608028654f);
          y[e] = fmaf(z, tanh_hw(u), z);
        }
        hp[j][q] = pack_bf16(y[0], y[1]);
      }
      if (j == STG_WAIT && c > 0) {
        if (lane == 0) bulk_wait_read();
        __syncwarp();
      }
      if (c == 0 || j > STG_WAIT) {
        stsm4(srow ^ (j << 4), hp[j][0], hp[j][1], hp[j][2], hp[j][3]);
      } else if (j == STG_WAIT) {
#pragma unroll
        for (int jj = 0; jj <= STG_WAIT; jj++) stsm4(srow ^ (jj << 4), hp[jj][0], hp[jj][1], hp[jj][2], hp[jj][3]);
      }
    }
    fence_async_smem();
    __syncwarp();
    if (lane == 0) {
      tma_st2(&p.t.h_st, stg, 448 * n + col0 + 64 * c, 128 * m + 32 * w);
      bulk_commit();
    }
  }
#pragma unroll
  for (int r = 0; r < 16; r++) acc[0][r] = acc[1][r] = 0.f;
}

template <int PART>
__device__ __forceinline__ void rank1_update(const Params& p, float (&acc)[2][96], const Ctx& cx, int t) {
  float nm[4];
#pragma unroll
  for (int q = 0; q < 4; q++) nm[q] = t == 6 ? 1.f : -lds_f(cx.sb + OFF_ROW + (32 * cx.w + 8 * q + (cx.lane >> 2)) * 8 + 4);
  const uint32_t ctab = cx.sb + OFF_CSQ + ((t & 3) * 192 + 2 * (cx.lane & 3)) * 4;
#pragma unroll
  for (int j = PART == 1 ? 8 : 0; j < 24; j++) {
    const float2 cs = lds_f2(ctab + j * 32);
#pragma unroll
    for (int q = 0; q < 4; q++) {
      if (PART != 0 && (PART == 1) != (q == 3 && j >= 8)) continue;
      const int k = 4 * j + q - 1;
      const float nq = PART == 0 && k >= 0 ? chain(nm[q], __float_as_uint(ACC(k & 3, k >> 2, 1)), p.zero) : nm[q];
      ACC(q, j, 0) = fmaf(nq, cs.x, ACC(q, j, 0));
      ACC(q, j, 1) = fmaf(nq, cs.y, ACC(q, j, 1));
    }
  }
}

__device__ __forceinline__ void attn_epilogue(const Params& p, float (&acc)[2][96], const Ctx& cx, int layer, int t, uint32_t tag) {
  UNPACK_CTX(cx);
  const uint32_t ktab = sb + OFF_ROW + (32 * w + 2 * (lane & 3)) * 8, exc = sb + OFF_STG + (w & 1) * 2048 + lane * 16;
  uint4* const halo = p.g->halo + (((layer * 2 + t) * 16 + m) * 8 + n) * 384 + (w & 1) * 192;
  const int mn = m * 8 + n; (void)mn;
  uint32_t Q[4][8], K[4][8], V[4][8], E[18], P[18];
  float kr[5][2], qr[4];
  const bool late_fold = layer == 0 && t == 1;
  if (late_fold) rank1_update<1>(p, acc, cx, 1);
  {
    const float4 r = lds_f4(ktab + 192);
    E[16] = __float_as_uint(kr[4][0] = r.x);
    E[17] = __float_as_uint(kr[4][1] = r.z);
  }
#pragma unroll
  for (int j = 0; j < 8; j++) {
    E[j] = K[3][j] = pack_bf16(ACC(3, 8 + j, 0), ACC(3, 8 + j, 1));
    E[8 + j] = V[3][j] = movtrans(pack_bf16(ACC(3, 16 + j, 0), ACC(3, 16 + j, 1)));
  }
  if (w < 2) {
#pragma unroll
    for (int k = 0; k < 4; k++) sts_u4(exc + k * 512, E[4 * k], E[4 * k + 1], E[4 * k + 2], E[4 * k + 3]);
  } else {
#pragma unroll
    for (int k = 0; k < 6; k++) st_msg(halo + k * 32 + lane, E[3 * k], E[3 * k + 1], E[3 * k + 2], tag);
  }
  bar_arrive(BAR_PAIR + w, 64);
  if (LATE_O && t == 1) bar_arrive(BAR_ORDER + (wg ^ 1), 256);
  PROF_E(7 * layer + t, 1);
  if (late_fold) rank1_update<2>(p, acc, cx, 1);
#pragma unroll
  for (int q = 0; q < 4; q++) {
    qr[q] = lds_f(sb + OFF_ROW + (32 * w + 8 * q + (lane >> 2)) * 8) * (0.17677669529663687f * 1.4426950408889634f);
#pragma unroll
    for (int j = 0; j < 8; j++) Q[q][j] = pack_bf16(ACC(q, j, 0), ACC(q, j, 1));
    if (q < 3) {
      const float4 r = lds_f4(ktab + 64 * q);
      kr[1 + q][0] = r.x;
      kr[1 + q][1] = r.z;
#pragma unroll
      for (int j = 0; j < 8; j++) {
        K[q][j] = pack_bf16(ACC(q, 8 + j, 0), ACC(q, 8 + j, 1));
        V[q][j] = movtrans(pack_bf16(ACC(q, 16 + j, 0), ACC(q, 16 + j, 1)));
      }
    }
  }
  PROF_E(7 * layer + t, 6);
  bar_sync(BAR_PAIR + (w ^ 2), 64);
  if (w >= 2 || m == 0) {
#pragma unroll
    for (int k = 0; k < 4; k++) lds_u4(exc + k * 512, P[4 * k], P[4 * k + 1], P[4 * k + 2], P[4 * k + 3]);
    const float4 r = lds_f4(ktab - (w >> 1) * 320);
    P[16] = __float_as_uint(r.x);
    P[17] = __float_as_uint(r.z);
  } else {
    if (m & 1) __nanosleep(HALO_NS);
#pragma unroll 1
    for (int it = 0; it < MSG_SPINS; it++) {
      uint32_t tg, bad = 0;
      if (it > 0 || !(m & 1)) poll_line(reinterpret_cast<const uint32_t*>(halo - 8 * 384 + 191) + 3, tag, 1u);
#pragma unroll
      for (int k = 0; k < 6; k++) {
        ld_msg(halo - 8 * 384 + k * 32 + lane, P[3 * k], P[3 * k + 1], P[3 * k + 2], tg);
        bad |= tg ^ tag;
      }
      if (__all_sync(0xffffffffu, bad == 0)) break;
    }
  }
  kr[0][0] = __uint_as_float(P[16]);
  kr[0][1] = __uint_as_float(P[17]);
  const bool early[2] = {2 * (lane & 3) > (lane >> 2), 2 * (lane & 3) + 1 > (lane >> 2)};
  const uint32_t mask = (early[0] ? 0xffffu : 0u) | (early[1] ? 0xffff0000u : 0u);
  float rk[2][4], sc[2][4], off[2][4];
#pragma unroll
  for (int g = 0; g < 2; g++) {
#pragma unroll
    for (int e = 0; e < 4; e++) {
      const int q = 2 * g + (e >> 1);
      const bool masked = q == 0 && m == 0 && w < 2 && early[e & 1];
      rk[g][e] = early[e & 1] ? kr[q][e & 1] : kr[q + 1][e & 1];
      sc[g][e] = masked ? 0.f : rk[g][e] * qr[q];
      off[g][e] = masked ? -1e30f : 0.f;
    }
  }
  if (w == 0 && elect_one()) asm volatile("prefetch.tensormap [%0];" ::"l"(&p.t.att_st) : "memory");
  PROF_E(7 * layer + t, 2);
  bar_sync(BAR_GO, 256);
  const float4 zero = lds_f4(sb + OFF_ZERO);
  float l[2][2][4], o[2][2][4][4], sum[2][2][2];
#pragma unroll
  for (int h = 0; h < 2; h++) {
    if (h == 1) {
      Q[2][4] |= __float_as_uint(l[1][0][0]) & p.zero;
      Q[0][4] |= __float_as_uint(l[0][0][0]) & p.zero;
    }
    attn_scores(&Q[2][4 * h], &Q[3][4 * h], &K[1][4 * h], &K[2][4 * h], &K[3][4 * h], l[1][h], zero, early);
    attn_scores(&Q[0][4 * h], &Q[1][4 * h], &P[4 * h], &K[0][4 * h], &K[1][4 * h], l[0][h], zero, early);
  }
  const uint32_t stg = sb + OFF_STG + w * 4096, srow = stg + lane * 128 + ((lane & 7) << 4);
#pragma unroll
  for (int h = 0; h < 2; h++) {
    attn_mix(l[1][h], sc[1], off[1], rk[1], &V[1][4 * h], &V[2][4 * h], &V[3][4 * h], o[1][h], sum[1][h], mask, p.zero);
    attn_mix(l[0][h], sc[0], off[0], rk[0], &P[8 + 4 * h], &V[0][4 * h], &V[1][4 * h], o[0][h], sum[0][h], mask, p.zero);
#pragma unroll
    for (int j = 0; j < 4; j++) {
      const float(&a)[4] = o[0][h][j];
      const float(&c)[4] = o[1][h][j];
      stsm4(srow ^ ((4 * h + j) << 4), pack_bf16(a[0] * sum[0][h][0], a[1] * sum[0][h][0]), pack_bf16(a[2] * sum[0][h][1], a[3] * sum[0][h][1]),
            pack_bf16(c[0] * sum[1][h][0], c[1] * sum[1][h][0]), pack_bf16(c[2] * sum[1][h][1], c[3] * sum[1][h][1]));
    }
  }
  bar_arrive(BAR_DONE, 256);
  fence_async_smem();
  __syncwarp();
  if (lane == 0) {
    tma_st2(&p.t.att_st, stg, 128 * n + 64 * t, 128 * m + 32 * w);
    bulk_commit();
  }
}

__device__ __forceinline__ void finish_stores(uint32_t sb, int i) {
  const int t = i >= 7 ? i - 7 : i;
  if ((threadIdx.x & 31) == 0) {
    bulk_wait_all();
    mbar_arrive(sb + BAR_PUB + 8 * (t < 2 ? t : t + 1));
  }
  __syncwarp();
  if (i < 12) bar_arrive(BAR_GUARD + ((i & 1) ^ 1), 256);
}

__device__ __forceinline__ bool consumer_tile(const Params& p, float (&acc)[2][96], uint32_t sb0, int i, int mn) {
  const int layer = i >= 7, t = i - 7 * layer, wg = i & 1;
  const bool resid = t == 2 || t == 6;
  {
    if (resid) {
      const Ctx cx = make_ctx(sb0, mn);
      const uint32_t xrow = cx.sb + OFF_X + cx.w * 4096 + cx.lane * 128;
      const uint32_t sel_lo = 0x1044u | p.zero, sel_hi = 0x3244u | p.zero;
#pragma unroll
      for (int j = 0; j < 16; j++) {
        uint32_t r[4];
        ldsm4(xrow + (j >> 3) * 16384 + (((j & 7) ^ (cx.lane & 7)) << 4), r[0], r[1], r[2], r[3]);
#pragma unroll
        for (int q = 0; q < 4; q++) {
          ACC(q, j, 0) = prmt_f(r[q], sel_lo);
          ACC(q, j, 1) = prmt_f(r[q], sel_hi);
        }
      }
    }
    if (t >= 5 || i == 7) finish_stores(sb0, i - 2);
#pragma unroll 1
    for (int step = !tile_split(i);; step++) {
      if (step == 1 && (t == 1 || t == 4)) {
        const Ctx cx = make_ctx(sb0, mn);
        if (i == 1) {
          const uint32_t epoch = __ldcg(p.g->epoch + (mn & 127));
          cluster_wait();
          asm volatile("st.shared.u32 [%0], %1;" ::"r"(sb0 + OFF_TAG), "r"(epoch + 1) : "memory");
        }
        const uint32_t tag = lds_u(cx.sb + OFF_TAG);
        const int ln = (i + 1) >> 2;
#pragma unroll 1
        for (int r = 0; r < 2; r++) {
          if (i == 1) {
            if (cx.w < 3) {
              float a[8] = {0.f, 0.f, 0.f, 0.f, 0.f, 0.f, 0.f, 0.f};
              mbar_wait(sb0 + BAR_CSLD, r);
#pragma unroll 1
              for (int h = 0; h < 2; h++) sum_rows(cx.sb + OFF_STG + h * 12288 + cx.w * 4096, 4, a, cx.lane);
              publish_sums(a, p.g->csp + (cx.n * 17 + cx.m) * 224 + (3 * r + cx.w) * 32, cx.lane, tag);
            }
            PROF_E(-1, 5 + r);
          }
          if (r == 1) break;
          if (i == 1) {
            bar_sync(BAR_WG + 1, 128);
            if (cx.w == 3 && elect_one()) {
              mbar_expect_tx(sb0 + BAR_CSLD, 24576);
              tma_ld3(sb0 + OFF_STG, &p.t.wqkv, sb0 + BAR_CSLD, 128 * cx.n + 64, 64 * cx.m, 0);
              tma_ld3(sb0 + OFF_STG + 12288, &p.t.wqkv, sb0 + BAR_CSLD, 128 * cx.n + 64, 64 * cx.m + 32, 0);
            }
            mbar_wait(sb0 + BAR_XRDY, 0);
            mbar_wait(sb0 + BAR_XRDY + 8, 0);
          }
          if (EARLY_STATS == 1 ? i == 1 : t == 1) write_partial_stats(p, cx, ln, tag);
          PROF_E(i - 2, 8);
        }
        if (i == 1) {
          bar_arrive(BAR_HLP, 160);
          bar_sync(BAR_INIT, 160);
        }
        if (i == 4) colsum_total(p, cx, 1, tag);
        PROF_E(i - 2, 9);
        if (i != 1) bar_sync(BAR_GUARD + wg, 256);
        finish_row_stats(p, cx, ln, tag);
        PROF_E(i - 2, 10);
        if (i == 4) {
          colsum_gather(p, cx, 1, tag);
          mbar_wait(sb0 + BAR_BIAS, 0);
        }
        PROF_E(i - 2, 15);
        bar_arrive(BAR_GUARD + (wg ^ 1), 256);
      }
      if (step == 2 && !resid) bar_sync(BAR_GUARD + wg, 256);
      if (step == 2 && i == 0) {
        colsum_gather(p, make_ctx(sb0, mn), 0, lds_u(sb0 + OFF_TAG));
        bar_sync(BAR_WG, 128);
      }
      if ((t + step == 2 && i != 1) || t == 6) rank1_update<0>(p, acc, make_ctx(sb0, mn), t);
      if (step == 2) break;
      if (tile_wide(t)) {
        mainloop<192>(p, acc, sb0, i, step, mn);
      } else {
        mainloop<128>(p, acc, sb0, i, step, mn);
        if (resid) return false;
      }
    }
    if (t < 2) return true;
    gelu_epilogue(p, acc, make_ctx(sb0, mn), t);
    PROF_E(i, 4);
    return false;
  }
}

template <bool BY_SMID>
__global__ void __cluster_dims__(2, 1, 1) __launch_bounds__(384, 1)
fused_layers_kernel(const Scalars scalars, const __grid_constant__ Maps maps) {
  if (threadIdx.x == 288 || threadIdx.x == 320)
    asm volatile("prefetch.tensormap [%0];" ::"l"(threadIdx.x == 288 ? &maps.xin : &maps.wqkv) : "memory");
  const Params p{scalars, maps};
  extern __shared__ __align__(1024) uint8_t smem_raw[];
  const uint32_t sb = uniform((uint32_t)__cvta_generic_to_shared(smem_raw));
  const int tid = threadIdx.x, lane = tid & 31, warp = uniform(tid >> 5), wg = warp >> 2, w = warp & 3;

  int mn;
  {
    int id = blockIdx.x;
    if (BY_SMID) asm volatile("mov.u32 %0, %%smid;" : "=r"(id));
    else if (id >= 120) id += 4;
    const int c = id >> 1;
    int g, j;
    if (c < 32) { g = c & 7; j = c >> 3; }
    else if (c < 60) { g = 1 + (c - 32) % 7; j = 4 + (c - 32) / 7; }
    else { g = 0; j = c - 58; }
    const int r = blockIdx.x & 1;
    mn = (g * 2 + r) * 8 + j;
    if (c == 60 || c == 61) {
      if (tid < 32) {
        const uint32_t tag = __ldcg(p.g->epoch + NCTA + (id & 3)) + 1;
#pragma unroll 1
        for (int mm = 0; mm < 16; mm++) poll_line(p.g->flags + mm * 32 + (lane & 7), 32 * tag, 0xffu);
        if (tid == 0) p.g->epoch[NCTA + (id & 3)] = tag;
      }
      return;
    }
  }
  const int m = mn >> 3, n = mn & 7;
  if (tid == 256) PROF_U(1);
  if (wg < 2) {
    cluster_arrive();
    asm volatile("setmaxnreg.inc.sync.aligned.u32 232;");
    if (tid == 0) PROF_U(2);
    const int id = mn | (warp << 7);
#pragma unroll 1
    for (int i = wg;; i += 2) {
      float acc[2][96];
#pragma unroll
      for (int r = 0; r < 96; r++) acc[0][r] = acc[1][r] = 0.f;
      pin_regs<96>(acc);
      if (i == 0 && threadIdx.x == 0) PROF_U(3);
#pragma unroll 1
      while (!consumer_tile(p, acc, sb, i, id)) {
        PROF_T(6 + i * 4);
        i += 2;
        if (i >= 14) goto all_done;
      }
      attn_epilogue(p, acc, make_ctx(sb, id), i >= 7, i >= 7 ? i - 7 : i, lds_u(sb + OFF_TAG));
      PROF_E(i, 4);
      finish_stores(sb, i);
      PROF_E(i, 5);
      PROF_T(6 + i * 4);
    }
  all_done:
    if (wg == 0) {
      finish_stores(sb, 12);
    } else {
      cluster_arrive();
      cluster_wait();
    }
  } else {
    asm volatile("setmaxnreg.dec.sync.aligned.u32 40;");
    if (w != 0) {
      if (w == 1 && elect_one()) {
        mbar_init(sb + BAR_FULL + 32, 2);
#pragma unroll
        for (int k = 0; k < NBAR; k++) mbar_init(sb + BAR_EMPTY + 8 * k, 8);
#pragma unroll
        for (int k = 0; k < 3; k++) mbar_init(sb + BAR_XRDY + 8 * k, 4);
#pragma unroll
        for (int k = 0; k < 9; k++) mbar_init(sb + BAR_PUB + 8 * k, 4);
#pragma unroll
        for (int k = 0; k < 4; k++) mbar_init(sb + BAR_CSLD + 8 * k, 1);
        sts_f2(sb + OFF_ZERO, 0.f, 0.f);
        sts_f2(sb + OFF_ZERO + 8, 0.f, 0.f);
        asm volatile("fence.mbarrier_init.release.cluster;" ::: "memory");
      }
      __syncwarp();
      cluster_arrive();
      if (w == 2) {
        if (lane < 28) write_run_desc(sb, lane >> 1, lane & 1);
        bar_arrive(BAR_INIT, 160);
      }
      cluster_wait();
      if (w == 1) producer<true>(p, sb, m, n, lane);
      else if (w == 3) colsum_helper(p, sb, m, n, lane);
      else if (elect_one()) publisher(p, sb, m, n);
    } else {
      const bool leader = elect_one();
      if (leader) {
#pragma unroll
        for (int k = 0; k < 4; k++) mbar_init(sb + BAR_FULL + 8 * k, 2);
        asm volatile("fence.mbarrier_init.release.cluster;" ::: "memory");
        PROF_U(4);
      }
      __syncwarp();
      bar_arrive(BAR_INIT0, 160);
      cluster_arrive();
      if (leader) {
#pragma unroll 1
        for (int k = 0; k < 4; k++) {
          const uint32_t fb = sb + BAR_FULL + 8 * k;
          mbar_expect_tx(fb, 16384);
          tma_ld_act(sb + (5 * k + 3) * UNIT, &p.t.xin, fb, 64 * k, m);
          mbar_expect_tx(fb, 3 * UNIT);
          tma_ld3(sb + 5 * k * UNIT, &p.t.wqkv, fb, 128 * n, 64 * k, 0);
          tma_ld3(sb + 5 * k * UNIT + 12288, &p.t.wqkv, fb, 128 * n, 64 * k + 32, 0);
          if (k == 0) PROF_U(6);
        }
        PROF_U(5);
      }
      __syncwarp();
      cluster_wait();
      producer<false>(p, sb, m, n, lane);
    }
  }
}

typedef CUresult (*EncodeFn)(CUtensorMap*, CUtensorMapDataType, cuuint32_t, void*, const cuuint64_t*, const cuuint64_t*,
                             const cuuint32_t*, const cuuint32_t*, CUtensorMapInterleave, CUtensorMapSwizzle,
                             CUtensorMapL2promotion, CUtensorMapFloatOOBfill);

#define PROMO2 CU_TENSOR_MAP_L2_PROMOTION_L2_128B
#define PROMO3 CU_TENSOR_MAP_L2_PROMOTION_L2_128B
void make_2d(EncodeFn enc, CUtensorMap* m, const void* ptr, uint64_t cols, uint64_t rows, uint32_t box_rows) {
  cuuint64_t d[2] = {cols, rows}, st[1] = {cols * 2};
  cuuint32_t b[2] = {64, box_rows}, e[2] = {1, 1};
  enc(m, CU_TENSOR_MAP_DATA_TYPE_BFLOAT16, 2, const_cast<void*>(ptr), d, st, b, e, CU_TENSOR_MAP_INTERLEAVE_NONE,
      CU_TENSOR_MAP_SWIZZLE_128B, PROMO2, CU_TENSOR_MAP_FLOAT_OOB_FILL_NONE);
}
void make_act(EncodeFn enc, CUtensorMap* m, const void* ptr, uint64_t cols, bool split, uint32_t box = 2) {
  const uint64_t row = cols * 2;
  cuuint64_t d[4] = {cols, 32, 2, SEQ / 64}, st[3] = {split ? 2 * row : row, split ? row : 32 * row, 64 * row};
  cuuint32_t b[4] = {64, 32, box, box}, e[4] = {1, 1, 1, 1};
  enc(m, CU_TENSOR_MAP_DATA_TYPE_BFLOAT16, 4, const_cast<void*>(ptr), d, st, b, e, CU_TENSOR_MAP_INTERLEAVE_NONE,
      CU_TENSOR_MAP_SWIZZLE_128B, PROMO2, CU_TENSOR_MAP_FLOAT_OOB_FILL_NONE);
}
void make_3d(EncodeFn enc, CUtensorMap* m, const void* ptr, uint64_t d0, uint64_t rows, uint64_t d2, uint64_t row_bytes,
             uint64_t chunk_bytes, uint32_t box_chunks) {
  cuuint64_t d[3] = {d0, rows, d2}, st[2] = {row_bytes, chunk_bytes};
  cuuint32_t b[3] = {64, 32, box_chunks}, e[3] = {1, 1, 1};
  enc(m, CU_TENSOR_MAP_DATA_TYPE_BFLOAT16, 3, const_cast<void*>(ptr), d, st, b, e, CU_TENSOR_MAP_INTERLEAVE_NONE,
      CU_TENSOR_MAP_SWIZZLE_128B, PROMO3, CU_TENSOR_MAP_FLOAT_OOB_FILL_NONE);
}

}

extern "C" void kernel_launch(void* const* d_in, const int* in_sizes, int n_in, void* d_out, int out_size) {
  (void)in_sizes; (void)n_in; (void)out_size;
  static EncodeFn enc = nullptr;
  static void *att = nullptr, *hbuf = nullptr, *scratch = nullptr;
  static int by_smid = 0;
  if (!enc) {
    void* fn = nullptr;
    cudaDriverEntryPointQueryResult q;
    cudaGetDriverEntryPoint("cuTensorMapEncodeTiled", &fn, cudaEnableDefault, &q);
    enc = (EncodeFn)fn;
    cudaGetSymbolAddress(&att, g_att);
    cudaGetSymbolAddress(&hbuf, g_h);
    cudaGetSymbolAddress(&scratch, g_scratch);
    cudaFuncSetAttribute(fused_layers_kernel<true>, cudaFuncAttributeMaxDynamicSharedMemorySize, SMEM_BYTES);
    cudaFuncSetAttribute(fused_layers_kernel<false>, cudaFuncAttributeMaxDynamicSharedMemorySize, SMEM_BYTES);
    int sms = 0, clusters = 0, dev = 0;
    cudaGetDevice(&dev);
    cudaDeviceGetAttribute(&sms, cudaDevAttrMultiProcessorCount, dev);
    cudaLaunchConfig_t cfg = {};
    cfg.gridDim = dim3(132);
    cfg.blockDim = dim3(384);
    cfg.dynamicSmemBytes = SMEM_BYTES;
    cudaLaunchAttribute at[1];
    at[0].id = cudaLaunchAttributeClusterDimension;
    at[0].val.clusterDim.x = 2; at[0].val.clusterDim.y = 1; at[0].val.clusterDim.z = 1;
    cfg.attrs = at;
    cfg.numAttrs = 1;
    if (cudaOccupancyMaxActiveClusters(&clusters, fused_layers_kernel<true>, &cfg) != cudaSuccess) (void)cudaGetLastError();
    by_smid = sms == 132 && clusters == 66;
  }
  Maps p;
  Scalars sc;
  make_act(enc, &p.xin, d_in[0], DM, true);
  make_act(enc, &p.out, d_out, DM, true);
  make_act(enc, &p.out_w, d_out, DM, true, 1);
  make_act(enc, &p.att, att, DM, false);
  make_act(enc, &p.h, hbuf, FF, false);
  make_2d(enc, &p.att_st, att, DM, SEQ, 32);
  make_2d(enc, &p.h_st, hbuf, FF, SEQ, 32);
  make_2d(enc, &p.w1c, d_in[4], FF, DM, 32);
  make_3d(enc, &p.wqkv, d_in[1], DM, DM, 3, 3 * DM * 2, DM * 2, 3);
  make_3d(enc, &p.wo, d_in[2], 64, DM, DM / 64, DM * 2, 128, 2);
  make_3d(enc, &p.w1a, d_in[4], 64, DM, FF / 64, FF * 2, 128, 3);
  make_3d(enc, &p.w1b, d_in[4], 64, DM, FF / 64, FF * 2, 128, 2);
  make_3d(enc, &p.w2, d_in[6], 64, FF, DM / 64, DM * 2, 128, 2);
  sc.b1 = (const __nv_bfloat16*)d_in[5];
  sc.b2 = (const __nv_bfloat16*)d_in[7];
  sc.g = (Scratch*)scratch;
  sc.zero = 0;
  if (by_smid) fused_layers_kernel<true><<<132, 384, SMEM_BYTES>>>(sc, p);
  else fused_layers_kernel<false><<<NCTA, 384, SMEM_BYTES>>>(sc, p);
}
```

```cpp
#include <cuda_runtime.h>
#include <cuda_bf16.h>
#include <cuda.h>
#include <stdint.h>

namespace {

constexpr int SEQ = 2048, DM = 1024, FF = 3584;
constexpr int NCTA = 128;
constexpr int NBAR = 5;

constexpr uint32_t RING_UNITS = 20, UNIT = 8192;
constexpr uint32_t OFF_X   = RING_UNITS * UNIT;
constexpr uint32_t OFF_STG = OFF_X + 32768;
constexpr uint32_t OFF_HLP = OFF_STG + 16384;
constexpr uint32_t OFF_RUN = OFF_STG + 24576;
constexpr uint32_t OFF_CSQ = OFF_RUN + 512;
constexpr uint32_t OFF_CSF = OFF_CSQ + 2048;
constexpr uint32_t OFF_ROW = OFF_CSF + 3584;
constexpr uint32_t OFF_BAR = OFF_ROW + 1024;
constexpr uint32_t SMEM_BYTES = OFF_BAR + 384;
constexpr uint32_t BAR_FULL = OFF_BAR, BAR_EMPTY = OFF_BAR + 8 * NBAR;
constexpr uint32_t BAR_XRDY = OFF_BAR + 80;
constexpr uint32_t BAR_DUMMY = OFF_BAR + 96, OFF_TAG = OFF_BAR + 104, OFF_ZERO = OFF_BAR + 112;
constexpr uint32_t BAR_PUB = OFF_BAR + 128;
constexpr uint32_t BAR_CSLD = OFF_BAR + 200;
constexpr uint32_t BAR_BIAS = OFF_BAR + 216;
constexpr uint32_t BAR_XGO = OFF_BAR + 224;

constexpr uint64_t DESC_A = (1ull << 62) | ((uint64_t)(2048 >> 4) << 32) | (1ull << 16);
constexpr uint64_t DESC_B = (1ull << 62) | ((uint64_t)(1024 >> 4) << 32) | ((uint64_t)(4096 >> 4) << 16);

constexpr int BAR_INIT = 0, BAR_ORDER = 1, BAR_GUARD = 3, BAR_WG = 5, BAR_GO = 7, BAR_DONE = 8, BAR_HLP = 9;
constexpr int BAR_INIT0 = 10, BAR_PAIR = 11;

constexpr int WIN1 = 8;
constexpr int WIN2 = 2;
constexpr int GELU_DEP = 2;
constexpr int STG_WAIT = 5;
constexpr int HALO_NS = 200;
constexpr int STAT_NS = 800;
constexpr int CS_NS = 500;
constexpr int XB_NS = 400;
constexpr int XB_GAP_NS = 50;
constexpr int STAG_NS = 450;
constexpr int PACE_M = 100;
constexpr int PACE_N = 300;

struct Scratch {
  uint4 stats[4 * 8 * SEQ];
  uint4 halo[2 * 2 * 16 * 8 * 384];
  uint4 csp[2 * 8 * 17 * 224];
  uint32_t flags[16 * 32];
  uint32_t epoch[NCTA + 4];
};

struct Maps {
  CUtensorMap xin, out, att, h, wqkv, wo, w1a, w1b, w2, att_st, h_st, w1c, out_w;
};
struct Scalars {
  Scratch* g;
  const __nv_bfloat16 *b1, *b2;
  uint32_t zero;
};
struct Params : Scalars {
  const Maps& t;
};

__device__ __nv_bfloat16 g_att[SEQ * DM];
__device__ __nv_bfloat16 g_h[SEQ * FF];
__device__ Scratch g_scratch;

__device__ __forceinline__ void mbar_init(uint32_t bar, int cnt) {
  asm volatile("mbarrier.init.shared::cta.b64 [%0], %1;" ::"r"(bar), "r"(cnt));
}
__device__ __forceinline__ void mbar_expect_tx(uint32_t bar, uint32_t bytes) {
  asm volatile("mbarrier.arrive.expect_tx.shared::cta.b64 _, [%0], %1;" ::"r"(bar), "r"(bytes) : "memory");
}
__device__ __forceinline__ void mbar_arrive(uint32_t bar) {
  asm volatile("mbarrier.arrive.shared::cta.b64 _, [%0];" ::"r"(bar) : "memory");
}
__device__ __forceinline__ bool mbar_test(uint32_t bar, uint32_t parity) {
  uint32_t ok;
  asm volatile("{\n.reg .pred p;\nmbarrier.test_wait.parity.shared::cta.b64 p, [%1], %2;\nselp.u32 %0, 1, 0, p;\n}"
               : "=r"(ok) : "r"(bar), "r"(parity) : "memory");
  return ok;
}
__device__ __forceinline__ void mbar_wait(uint32_t bar, uint32_t parity) {
  asm volatile(
      "{\n.reg .pred p;\n.reg .u32 it;\nmov.u32 it, 0;\n"
      "WAIT_LOOP:\n"
      "mbarrier.try_wait.parity.shared::cta.b64 p, [%0], %1;\n"
      "@p bra WAIT_DONE;\n"
      "add.u32 it, it, 1;\n"
      "setp.lt.u32 p, it, 0x400000;\n"
      "@p bra WAIT_LOOP;\n"
      "trap;\n"
      "WAIT_DONE:\n}"
      ::"r"(bar), "r"(parity) : "memory");
}
__device__ __forceinline__ void bar_sync(int id, int n) { asm volatile("bar.sync %0, %1;" ::"r"(id), "r"(n) : "memory"); }
__device__ __forceinline__ void bar_arrive(int id, int n) { asm volatile("bar.arrive %0, %1;" ::"r"(id), "r"(n) : "memory"); }
__device__ __forceinline__ void tma_ld2(uint32_t dst, const CUtensorMap* m, uint32_t bar, int c0, int c1) {
  asm volatile("cp.async.bulk.tensor.2d.shared::cluster.global.mbarrier::complete_tx::bytes [%0], [%1, {%3, %4}], [%2];"
               ::"r"(dst), "l"(m), "r"(bar), "r"(c0), "r"(c1) : "memory");
}
__device__ __forceinline__ void tma_ld_act(uint32_t dst, const CUtensorMap* m, uint32_t bar, int col, int blk) {
  asm volatile("cp.async.bulk.tensor.4d.shared::cluster.global.mbarrier::complete_tx::bytes [%0], [%1, {%3, %5, %5, %4}], [%2];"
               ::"r"(dst), "l"(m), "r"(bar), "r"(col), "r"(2 * blk), "r"(0) : "memory");
}
__device__ __forceinline__ void tma_st_act(const CUtensorMap* m, uint32_t src, int col, int blk) {
  asm volatile("cp.async.bulk.tensor.4d.global.shared::cta.bulk_group [%0, {%2, %4, %4, %3}], [%1];"
               ::"l"(m), "r"(src), "r"(col), "r"(2 * blk), "r"(0) : "memory");
}
__device__ __forceinline__ void tma_st_warp(const CUtensorMap* m, uint32_t src, int col, int blk, int w) {
  asm volatile("cp.async.bulk.tensor.4d.global.shared::cta.bulk_group [%0, {%2, %5, %3, %4}], [%1];"
               ::"l"(m), "r"(src), "r"(col), "r"(w & 1), "r"(2 * blk + (w >> 1)), "r"(0) : "memory");
}
__device__ __forceinline__ void tma_ld3(uint32_t dst, const CUtensorMap* m, uint32_t bar, int c0, int c1, int c2) {
  asm volatile("cp.async.bulk.tensor.3d.shared::cluster.global.mbarrier::complete_tx::bytes [%0], [%1, {%3, %4, %5}], [%2];"
               ::"r"(dst), "l"(m), "r"(bar), "r"(c0), "r"(c1), "r"(c2) : "memory");
}
__device__ __forceinline__ void tma_ld3_pair(uint32_t dst, const CUtensorMap* m, uint32_t bar, int c0, int c1, int c2) {
  asm volatile("cp.async.bulk.tensor.3d.shared::cluster.global.mbarrier::complete_tx::bytes.multicast::cluster"
               " [%0], [%1, {%3, %4, %5}], [%2], %6;"
               ::"r"(dst), "l"(m), "r"(bar), "r"(c0), "r"(c1), "r"(c2), "h"((uint16_t)3) : "memory");
}
__device__ __forceinline__ uint32_t pair_offset(uint32_t sb, uint32_t rank) {
  uint32_t r;
  asm volatile("mapa.shared::cluster.u32 %0, %1, %2;" : "=r"(r) : "r"(sb), "r"(rank));
  return r - sb;
}
__device__ __forceinline__ void mbar_arrive_cluster(uint32_t bar) {
  asm volatile("mbarrier.arrive.shared::cluster.b64 _, [%0];" ::"r"(bar) : "memory");
}
__device__ __forceinline__ void cluster_arrive() { asm volatile("barrier.cluster.arrive.relaxed;" ::: "memory"); }
__device__ __forceinline__ void cluster_wait() { asm volatile("barrier.cluster.wait.acquire;" ::: "memory"); }
__device__ __forceinline__ void tma_st2(const CUtensorMap* m, uint32_t src, int c0, int c1) {
  asm volatile("cp.async.bulk.tensor.2d.global.shared::cta.bulk_group [%0, {%2, %3}], [%1];"
               ::"l"(m), "r"(src), "r"(c0), "r"(c1) : "memory");
}
__device__ __forceinline__ void bulk_commit() { asm volatile("cp.async.bulk.commit_group;" ::: "memory"); }
__device__ __forceinline__ void bulk_wait_read() { asm volatile("cp.async.bulk.wait_group.read 0;" ::: "memory"); }
__device__ __forceinline__ void bulk_wait_all() { asm volatile("cp.async.bulk.wait_group 0;" ::: "memory"); }
__device__ __forceinline__ void fence_async_smem() { asm volatile("fence.proxy.async.shared::cta;" ::: "memory"); }
__device__ __forceinline__ void fence_async_global() { asm volatile("fence.proxy.async.global;" ::: "memory"); }
__device__ __forceinline__ void st_relaxed(uint32_t* p, uint32_t v) {
  asm volatile("st.relaxed.gpu.global.u32 [%0], %1;" ::"l"(p), "r"(v) : "memory");
}
__device__ __forceinline__ void st_msg(uint4* p, uint32_t a, uint32_t b, uint32_t c, uint32_t tag) {
  asm volatile("{\n.reg .b128 v;\nmov.b128 v, {%1, %2, %3, %4};\nst.relaxed.gpu.global.b128 [%0], v;\n}"
               ::"l"(p), "r"(a), "r"(b), "r"(c), "r"(tag) : "memory");
}
__device__ __forceinline__ void ld_msg(const uint4* p, uint32_t& a, uint32_t& b, uint32_t& c, uint32_t& tag) {
  asm volatile("{\n.reg .b128 v;\nld.relaxed.gpu.global.b128 v, [%4];\nmov.b128 {%0, %1, %2, %3}, v;\n}"
               : "=r"(a), "=r"(b), "=r"(c), "=r"(tag) : "l"(p) : "memory");
}
__device__ __forceinline__ bool elect_one() {
  uint32_t ok;
  asm volatile("{\n.reg .pred p;\nelect.sync _|p, 0xffffffff;\nselp.u32 %0, 1, 0, p;\n}" : "=r"(ok));
  return ok;
}
__device__ __forceinline__ uint32_t lanemask_lt() {
  uint32_t v;
  asm("mov.u32 %0, %%lanemask_lt;" : "=r"(v));
  return v;
}
__device__ __forceinline__ int uniform(int v) { return __shfl_sync(0xffffffffu, v, 0); }
__device__ __forceinline__ uint32_t pack_bf16(float lo, float hi) {
  uint32_t r;
  asm("cvt.rn.bf16x2.f32 %0, %1, %2;" : "=r"(r) : "f"(hi), "f"(lo));
  return r;
}
__device__ __forceinline__ float prmt_f(uint32_t a, uint32_t sel) {
  float r;
  asm("{\n.reg .b32 t;\nprmt.b32 t, %1, 0, %2;\nmov.b32 %0, t;\n}" : "=f"(r) : "r"(a), "r"(sel));
  return r;
}
__device__ __forceinline__ float bf_lo(uint32_t v) { return __uint_as_float(v << 16); }
__device__ __forceinline__ float bf_hi(uint32_t v) { return __uint_as_float(v & 0xffff0000u); }
__device__ __forceinline__ void stsm4(uint32_t addr, uint32_t r0, uint32_t r1, uint32_t r2, uint32_t r3) {
  asm volatile("stmatrix.sync.aligned.m8n8.x4.shared.b16 [%0], {%1, %2, %3, %4};"
               ::"r"(addr), "r"(r0), "r"(r1), "r"(r2), "r"(r3) : "memory");
}
__device__ __forceinline__ void ldsm4(uint32_t addr, uint32_t& r0, uint32_t& r1, uint32_t& r2, uint32_t& r3) {
  asm volatile("ldmatrix.sync.aligned.m8n8.x4.shared.b16 {%0, %1, %2, %3}, [%4];"
               : "=r"(r0), "=r"(r1), "=r"(r2), "=r"(r3) : "r"(addr) : "memory");
}
__device__ __forceinline__ uint32_t movtrans(uint32_t a) {
  uint32_t d;
  asm volatile("movmatrix.sync.aligned.m8n8.trans.b16 %0, %1;" : "=r"(d) : "r"(a));
  return d;
}
__device__ __forceinline__ void mma16816(float (&c)[4], uint32_t a0, uint32_t a1, uint32_t a2, uint32_t a3, uint32_t b0, uint32_t b1) {
  asm volatile("mma.sync.aligned.m16n8k16.row.col.f32.bf16.bf16.f32 {%0,%1,%2,%3}, {%4,%5,%6,%7}, {%8,%9}, {%0,%1,%2,%3};"
               : "+f"(c[0]), "+f"(c[1]), "+f"(c[2]), "+f"(c[3])
               : "r"(a0), "r"(a1), "r"(a2), "r"(a3), "r"(b0), "r"(b1));
}
__device__ __forceinline__ void mma1688(float (&c)[4], uint32_t a0, uint32_t a1, uint32_t b0) {
  asm volatile("mma.sync.aligned.m16n8k8.row.col.f32.bf16.bf16.f32 {%0,%1,%2,%3}, {%4,%5}, {%6}, {%0,%1,%2,%3};"
               : "+f"(c[0]), "+f"(c[1]), "+f"(c[2]), "+f"(c[3]) : "r"(a0), "r"(a1), "r"(b0));
}
__device__ __forceinline__ float2 lds_f2(uint32_t a) {
  float2 v;
  asm volatile("ld.shared.v2.f32 {%0, %1}, [%2];" : "=f"(v.x), "=f"(v.y) : "r"(a) : "memory");
  return v;
}
__device__ __forceinline__ float4 lds_f4(uint32_t a) {
  float4 v;
  asm volatile("ld.shared.v4.f32 {%0, %1, %2, %3}, [%4];" : "=f"(v.x), "=f"(v.y), "=f"(v.z), "=f"(v.w) : "r"(a) : "memory");
  return v;
}
__device__ __forceinline__ float lds_f(uint32_t a) {
  float v;
  asm volatile("ld.shared.f32 %0, [%1];" : "=f"(v) : "r"(a) : "memory");
  return v;
}
__device__ __forceinline__ uint32_t lds_u(uint32_t a) {
  uint32_t v;
  asm volatile("ld.shared.u32 %0, [%1];" : "=r"(v) : "r"(a) : "memory");
  return v;
}
__device__ __forceinline__ void sts_f2(uint32_t a, float x, float y) {
  asm volatile("st.shared.v2.f32 [%0], {%1, %2};" ::"r"(a), "f"(x), "f"(y) : "memory");
}
__device__ __forceinline__ void sts_u4(uint32_t a, uint32_t x, uint32_t y, uint32_t z, uint32_t w) {
  asm volatile("st.shared.v4.u32 [%0], {%1, %2, %3, %4};" ::"r"(a), "r"(x), "r"(y), "r"(z), "r"(w) : "memory");
}
__device__ __forceinline__ void lds_u4(uint32_t a, uint32_t& x, uint32_t& y, uint32_t& z, uint32_t& w) {
  asm volatile("ld.shared.v4.u32 {%0, %1, %2, %3}, [%4];" : "=r"(x), "=r"(y), "=r"(z), "=r"(w) : "r"(a) : "memory");
}
__device__ __forceinline__ float ex2(float x) {
  float y;
  asm("ex2.approx.ftz.f32 %0, %1;" : "=f"(y) : "f"(x));
  return y;
}
__device__ __forceinline__ float rcp_hw(float x) {
  float y;
  asm("rcp.approx.ftz.f32 %0, %1;" : "=f"(y) : "f"(x));
  return y;
}
__device__ __forceinline__ float tanh_hw(float x) {
  float y;
  asm("tanh.approx.f32 %0, %1;" : "=f"(y) : "f"(x));
  return y;
}
__device__ __forceinline__ float quad_sum(float v) {
  v += __shfl_xor_sync(0xffffffffu, v, 1);
  return v + __shfl_xor_sync(0xffffffffu, v, 2);
}
__device__ __forceinline__ float quad_max(float v) {
  v = fmaxf(v, __shfl_xor_sync(0xffffffffu, v, 1));
  return fmaxf(v, __shfl_xor_sync(0xffffffffu, v, 2));
}

template <int N> __device__ __forceinline__ void wgmma_ss(float (&d)[96], uint64_t da, uint64_t db, uint32_t keep = 1);
template <> __device__ __forceinline__ void wgmma_ss<128>(float (&d)[96], uint64_t da, uint64_t db, uint32_t keep) {
  asm volatile(
      "{\n.reg .pred p;\nsetp.ne.u32 p, %66, 0;\n"
      "wgmma.mma_async.sync.aligned.m64n128k16.f32.bf16.bf16 {%0, %1, %2, %3, %4, %5, %6, %7, %8, %9, %10, %11, %12, %13, %14, %15, %16, %17, %18, %19, %20, %21, %22, %23, %24, %25, %26, %27, %28, %29, %30, %31, %32, %33, %34, %35, %36, %37, %38, %39, %40, %41, %42, %43, %44, %45, %46, %47, %48, %49, %50, %51, %52, %53, %54, %55, %56, %57, %58, %59, %60, %61, %62, %63}, %64, %65, p, 1, 1, 0, 1;\n}"
      : "+f"(d[0]), "+f"(d[1]), "+f"(d[2]), "+f"(d[3]), "+f"(d[4]), "+f"(d[5]), "+f"(d[6]), "+f"(d[7]), "+f"(d[8]), "+f"(d[9]), "+f"(d[10]), "+f"(d[11]), "+f"(d[12]), "+f"(d[13]), "+f"(d[14]), "+f"(d[15]), "+f"(d[16]), "+f"(d[17]), "+f"(d[18]), "+f"(d[19]), "+f"(d[20]), "+f"(d[21]), "+f"(d[22]), "+f"(d[23]), "+f"(d[24]), "+f"(d[25]), "+f"(d[26]), "+f"(d[27]), "+f"(d[28]), "+f"(d[29]), "+f"(d[30]), "+f"(d[31]), "+f"(d[32]), "+f"(d[33]), "+f"(d[34]), "+f"(d[35]), "+f"(d[36]), "+f"(d[37]), "+f"(d[38]), "+f"(d[39]), "+f"(d[40]), "+f"(d[41]), "+f"(d[42]), "+f"(d[43]), "+f"(d[44]), "+f"(d[45]), "+f"(d[46]), "+f"(d[47]), "+f"(d[48]), "+f"(d[49]), "+f"(d[50]), "+f"(d[51]), "+f"(d[52]), "+f"(d[53]), "+f"(d[54]), "+f"(d[55]), "+f"(d[56]), "+f"(d[57]), "+f"(d[58]), "+f"(d[59]), "+f"(d[60]), "+f"(d[61]), "+f"(d[62]), "+f"(d[63])
      : "l"(da), "l"(db), "r"(keep));
}

template <> __device__ __forceinline__ void wgmma_ss<192>(float (&d)[96], uint64_t da, uint64_t db, uint32_t keep) {
  asm volatile(
      "{\n.reg .pred p;\nsetp.ne.u32 p, %98, 0;\n"
      "wgmma.mma_async.sync.aligned.m64n192k16.f32.bf16.bf16 {%0, %1, %2, %3, %4, %5, %6, %7, %8, %9, %10, %11, %12, %13, %14, %15, %16, %17, %18, %19, %20, %21, %22, %23, %24, %25, %26, %27, %28, %29, %30, %31, %32, %33, %34, %35, %36, %37, %38, %39, %40, %41, %42, %43, %44, %45, %46, %47, %48, %49, %50, %51, %52, %53, %54, %55, %56, %57, %58, %59, %60, %61, %62, %63, %64, %65, %66, %67, %68, %69, %70, %71, %72, %73, %74, %75, %76, %77, %78, %79, %80, %81, %82, %83, %84, %85, %86, %87, %88, %89, %90, %91, %92, %93, %94, %95}, %96, %97, p, 1, 1, 0, 1;\n}"
      : "+f"(d[0]), "+f"(d[1]), "+f"(d[2]), "+f"(d[3]), "+f"(d[4]), "+f"(d[5]), "+f"(d[6]), "+f"(d[7]), "+f"(d[8]), "+f"(d[9]), "+f"(d[10]), "+f"(d[11]), "+f"(d[12]), "+f"(d[13]), "+f"(d[14]), "+f"(d[15]), "+f"(d[16]), "+f"(d[17]), "+f"(d[18]), "+f"(d[19]), "+f"(d[20]), "+f"(d[21]), "+f"(d[22]), "+f"(d[23]), "+f"(d[24]), "+f"(d[25]), "+f"(d[26]), "+f"(d[27]), "+f"(d[28]), "+f"(d[29]), "+f"(d[30]), "+f"(d[31]), "+f"(d[32]), "+f"(d[33]), "+f"(d[34]), "+f"(d[35]), "+f"(d[36]), "+f"(d[37]), "+f"(d[38]), "+f"(d[39]), "+f"(d[40]), "+f"(d[41]), "+f"(d[42]), "+f"(d[43]), "+f"(d[44]), "+f"(d[45]), "+f"(d[46]), "+f"(d[47]), "+f"(d[48]), "+f"(d[49]), "+f"(d[50]), "+f"(d[51]), "+f"(d[52]), "+f"(d[53]), "+f"(d[54]), "+f"(d[55]), "+f"(d[56]), "+f"(d[57]), "+f"(d[58]), "+f"(d[59]), "+f"(d[60]), "+f"(d[61]), "+f"(d[62]), "+f"(d[63]), "+f"(d[64]), "+f"(d[65]), "+f"(d[66]), "+f"(d[67]), "+f"(d[68]), "+f"(d[69]), "+f"(d[70]), "+f"(d[71]), "+f"(d[72]), "+f"(d[73]), "+f"(d[74]), "+f"(d[75]), "+f"(d[76]), "+f"(d[77]), "+f"(d[78]), "+f"(d[79]), "+f"(d[80]), "+f"(d[81]), "+f"(d[82]), "+f"(d[83]), "+f"(d[84]), "+f"(d[85]), "+f"(d[86]), "+f"(d[87]), "+f"(d[88]), "+f"(d[89]), "+f"(d[90]), "+f"(d[91]), "+f"(d[92]), "+f"(d[93]), "+f"(d[94]), "+f"(d[95])
      : "l"(da), "l"(db), "r"(keep));
}

template <int R>
__device__ __forceinline__ void pin_regs(float (&a)[2][96]) {
#pragma unroll
  for (int m = 0; m < 2; m++)
#pragma unroll
    for (int i = 0; i < R; i++) asm volatile("" : "+f"(a[m][i])::"memory");
}

struct Ctx {
  uint32_t sb;
  int m, n, wg, w, lane;
};
__device__ __forceinline__ Ctx make_ctx(uint32_t sb, int id) {
  int lane;
  asm volatile("mov.u32 %0, %%laneid;" : "=r"(lane));
  asm volatile("" : "+r"(id), "+r"(sb));
  return Ctx{sb, (id >> 3) & 15, id & 7, id >> 9, (id >> 7) & 3, lane};
}
#define UNPACK_CTX(c) const uint32_t sb = c.sb; const int m = c.m, n = c.n, wg = c.wg, w = c.w, lane = c.lane

__device__ __forceinline__ uint32_t poll_line(const uint32_t* word, uint32_t target, uint32_t need) {
  uint32_t v;
  asm volatile(
      "{\n.reg .pred p;\n.reg .u32 it, m;\n.reg .s32 d;\nmov.u32 it, 0;\n"
      "POLL_LOOP:\n"
      "ld.relaxed.gpu.global.u32 %0, [%1];\n"
      "sub.s32 d, %0, %2;\n"
      "setp.ge.s32 p, d, 0;\n"
      "vote.sync.ballot.b32 m, p, 0xffffffff;\n"
      "and.b32 m, m, %3;\n"
      "setp.eq.u32 p, m, %3;\n"
      "@p bra.uni POLL_DONE;\n"
      "add.u32 it, it, 1;\n"
      "setp.lt.u32 p, it, 0x400000;\n"
      "@p bra.uni POLL_LOOP;\n"
      "trap;\n"
      "POLL_DONE:\n}"
      : "=&r"(v) : "l"(word), "r"(target), "r"(need) : "memory");
  return v;
}
__device__ __forceinline__ uint32_t ld_relaxed(const uint32_t* p) {
  uint32_t v;
  asm volatile("ld.relaxed.gpu.global.u32 %0, [%1];" : "=r"(v) : "l"(p) : "memory");
  return v;
}
__device__ __forceinline__ float chain(float x, uint32_t on, uint32_t zero) {
  return __uint_as_float(__float_as_uint(x) | (on & zero));
}
constexpr int MSG_SPINS = 1 << 20;

constexpr int STAGES_PER_LAYER = 152;
__device__ __forceinline__ int nib(uint64_t v, int i) { return (int)(v >> (4 * i)) & 15; }
__device__ __forceinline__ bool tile_wide(int t) { return (0x23 >> t) & 1; }
__device__ __forceinline__ void weight_coords(const Params& p, int t, int n, const CUtensorMap*& map, int& c0, int& c2) {
  map = &p.t.wqkv + nib(0x4233100ull, t);
  c0 = t < 2 ? 128 * n + 64 * t : 0;
  c2 = t < 2 ? 0 : (t == 2 || t == 6) ? 2 * n : 7 * n + 2 * t - 6;
}

template <bool IS_A>
__device__ __forceinline__ void producer(const Params& p, uint32_t sb, int m, int n, int lane) {
  const uint32_t low = (1u << (4 * n)) - 1, others = (0x6543210u & low) | (0x7654321u & ~low);
  const uint64_t order_x = (uint64_t)(others * 2 + 0x1111111u) << 36 | (uint64_t)others * 2 << 8 | (n * 0x22 + 0x10);
  int inflight = 4, cur = 0;
  uint32_t fb = sb + BAR_FULL + 32, rb = sb + BAR_EMPTY, rph = 0, pos = 0, tag32 = 0, seen = 0;
  const uint32_t fend = sb + BAR_FULL + 8 * NBAR, rend = sb + BAR_EMPTY + 8 * NBAR;
  const uint32_t* word = p.g->flags + m * 32 + (lane < 16 ? lane >> 1 : lane & 7);
#pragma unroll 1
  for (int sg = 1; sg < 22; sg++) {
    const int layer = sg >= 11, s = sg == 1 ? 2 : sg == 2 ? 1 : sg - 11 * layer;
    const int t = nib(0x65434321010ull, s), kind = nib(0x32110031100ull, s);
    const bool wide = tile_wide(t);
    const uint32_t bbytes = wide ? 3 * UNIT : 2 * UNIT, base = sb + (IS_A ? bbytes : (m & 1) * (bbytes / 2));
    if (IS_A && kind == 0) {
      if (sg == 2) seen = tag32 = (__ldcg(p.g->epoch + m * 8 + n) + 1) << 5;
#pragma unroll 1
      for (int k = 0; k < 2; k++) {
#pragma unroll 1
        for (; inflight > (wide ? 3 : 4); inflight--) {
          mbar_wait(rb, rph);
          rb += 8;
          if (rb == rend) { rb -= 8 * NBAR; rph ^= 1; }
        }
        if (elect_one()) mbar_arrive(fb);
        inflight++;
        fb += 8;
        if (fb == fend) fb -= 8 * NBAR;
        pos += bbytes + 2 * UNIT;
        if (pos >= RING_UNITS * UNIT) pos -= RING_UNITS * UNIT;
      }
      continue;
    }
    const int mul = t == 6 ? 448 : t == 2 ? 128 : 64, count = sg == 1 ? 12 : 2 * nib(0x4871ull, kind);
    uint64_t order0 = sg == 1 ? 0xFEDCBA987654ull : kind == 3 ? 0x76543210u : order_x >> (8 * (kind & 1));
    uint32_t special = (s == 4 || s == 10) ? 0x10 : s == 9 ? 0xF : s == 0;
    if (IS_A) special |= (kind & 1 ? 0 : 3) | (count >= 4 ? 1u << (count - 4) : 0);
    if (s >= 9) pos = (s + 6) * UNIT;
    const CUtensorMap* map;
    int c0 = 0, c2 = 0, ev = 0;
    if (IS_A) {
      map = &p.t.xin + (t == 2 ? 2 : t == 6 ? 3 : sg >= 4);
      ev = 9 * layer + (t < 2 ? 0 : t == 2 ? 1 : t < 6 ? 4 : 5);
      if (elect_one()) asm volatile("prefetch.tensormap [%0];" ::"l"(map) : "memory");
    } else {
      weight_coords(p, t, n, map, c0, c2);
    }
#pragma unroll 1
    for (int add = 0; add < mul; add += 64) {
      uint64_t order = order0;
      const int need = kind == 3 ? ev : ev - 1 + (lane & 1), sh = kind == 3 ? 16 : 0;
      uint32_t ready = IS_A ? __ballot_sync(0xffffffffu, cur >= need) >> sh : 0;
#pragma unroll 1
      for (int k = 0; k < count; k++) {
        const int code = order & 15, kc = code * mul + add;
        order >>= 4;
        if ((special >> k) & 1) {
          const int lag = wide ? (s == 9 && k == 2 ? 2 : 3) : ((s == 4 || s == 10) && add == 0 && k < 4) ? 3 : 4;
#pragma unroll 1
          for (; inflight > lag; inflight--) {
            mbar_wait(rb, rph);
            rb += 8;
            if (rb == rend) { rb -= 8 * NBAR; rph ^= 1; }
          }
          inflight++;
          if (IS_A) {
            if (kind == 3 ? t == 2 && add + k == 64 : !(kind & 1) && k < 2) {
              if (t == 2) mbar_wait(sb + BAR_PUB + 8, layer);
              if (elect_one()) mbar_arrive(fb);
              goto next_stage;
            }
            if (k == count - 4 && sg >= 3) seen = ld_relaxed(word);
          }
        } else {
          mbar_wait(rb, rph);
          rb += 8;
          if (rb == rend) { rb -= 8 * NBAR; rph ^= 1; }
        }
        if (IS_A && !((ready >> code) & 1)) {
          cur = max(cur, (int)(seen - tag32));
          ready = __ballot_sync(0xffffffffu, cur >= need) >> sh;
          if (!((ready >> code) & 1)) {
            cur = (int)(poll_line(word, tag32 + need, 1u << (code + sh)) - tag32);
            ready = __ballot_sync(0xffffffffu, cur >= need) >> sh;
          }
          asm volatile("fence.acquire.gpu;" ::: "memory");
          fence_async_global();
          seen = ld_relaxed(word);
        }
        if (elect_one()) {
          if (!IS_A) tma_ld3_pair(base + pos, map, fb, c0, kc + 32 * (m & 1), c2);
          else tma_ld_act(base + pos, map, fb, kc, m);
          mbar_expect_tx(fb, IS_A ? 16384 : bbytes);
        }
      next_stage:
        fb += 8;
        if (fb == fend) fb -= 8 * NBAR;
        pos += bbytes + 2 * UNIT;
        if (pos >= RING_UNITS * UNIT) pos -= RING_UNITS * UNIT;
      }
      special = !IS_A ? 0 : t == 2 ? 1 : add == 128 ? 0x10 : 0;
      if (t == 2) order0 = others << 4 | n;
      if (IS_A && (t == 2 || add == 64 || add == 192)) ev++;
    }
  }
}

__device__ __forceinline__ void publisher(const Params& p, uint32_t sb, int m, int n) {
  {
    const int ts = PACE_M * m, tx = PACE_N * n;
#pragma unroll 1
    for (int k = 0; k < 2; k++) {
      __nanosleep(k == 0 ? min(ts, tx) : abs(ts - tx));
      if ((ts <= tx) == (k == 0)) {
        mbar_expect_tx(sb + BAR_CSLD, 24576);
        tma_ld3(sb + OFF_STG, &p.t.wqkv, sb + BAR_CSLD, 128 * n, 64 * m, 0);
        tma_ld3(sb + OFF_STG + 12288, &p.t.wqkv, sb + BAR_CSLD, 128 * n, 64 * m + 32, 0);
      } else {
#pragma unroll 1
        for (int h = 0; h < 2; h++) {
          const uint32_t xr = sb + BAR_XRDY + 8 * h;
          mbar_expect_tx(xr, 16384);
          tma_ld_act(sb + OFF_X + h * 16384, &p.t.xin, xr, 128 * n + 64 * h, m);
          asm volatile("mbarrier.arrive.shared::cta.b64 _, [%0], 3;" ::"r"(xr) : "memory");
        }
      }
    }
  }
  const uint32_t tag = __ldcg(p.g->epoch + m * 8 + n) + 1;
  uint32_t* word = p.g->flags + m * 32 + n;
  st_relaxed(word, 32 * tag);
#pragma unroll 1
  for (int c = 0; c < 16; c++) {
    const int e = c >= 9 ? c - 9 : c;
    if (e == 2 || e == 7) {
      asm volatile("prefetch.tensormap [%0];" ::"l"(&p.t.out) : "memory");
      mbar_wait(sb + BAR_XRDY, e == 2);
      tma_st_act(&p.t.out, sb + OFF_X, 128 * n, m);
      bulk_commit();
      mbar_wait(sb + BAR_XRDY + 8, e == 2);
      bulk_wait_all();
      mbar_arrive(sb + BAR_XGO);
    } else {
      mbar_wait(sb + BAR_PUB + 8 * e, c >= 9);
    }
    asm volatile("fence.release.gpu;" ::: "memory");
    asm volatile("red.relaxed.gpu.global.add.u32 [%0], 1;" ::"l"(word) : "memory");
  }
  p.g->epoch[m * 8 + n] = tag;
}

__device__ __forceinline__ void sum_rows(uint32_t buf, int iters, float (&a)[8], int lane) {
  uint32_t addr = buf + (lane >> 3) * 128 + (((lane & 7) ^ (lane >> 3)) << 4);
#pragma unroll 1
  for (int it = 0; it < iters; it++) {
    uint32_t u[2][4];
    lds_u4(addr, u[0][0], u[0][1], u[0][2], u[0][3]);
    lds_u4((addr ^ 64) + 512, u[1][0], u[1][1], u[1][2], u[1][3]);
    addr += 1024;
#pragma unroll
    for (int e = 0; e < 8; e++) { a[2 * (e & 3)] += bf_lo(u[e >> 2][e & 3]); a[2 * (e & 3) + 1] += bf_hi(u[e >> 2][e & 3]); }
  }
}
__device__ __forceinline__ void publish_sums(const float (&a)[8], uint4* dst, int lane, uint32_t tag) {
  const bool u8 = lane & 8, u16 = lane & 16;
  float h4[4], h2[2];
#pragma unroll
  for (int e = 0; e < 4; e++) h4[e] = (u8 ? a[4 + e] : a[e]) + __shfl_xor_sync(0xffffffffu, u8 ? a[e] : a[4 + e], 8);
#pragma unroll
  for (int e = 0; e < 2; e++) h2[e] = (u16 ? h4[2 + e] : h4[e]) + __shfl_xor_sync(0xffffffffu, u16 ? h4[e] : h4[2 + e], 16);
  st_msg(dst + (lane & 7) * 4 + (u8 ? 2 : 0) + (u16 ? 1 : 0), __float_as_uint(h2[0]), __float_as_uint(h2[1]), 0u, tag);
}

__device__ __forceinline__ void colsum_helper(const Params& p, uint32_t sb, int m, int n, int lane) {
  const uint32_t tag = __ldcg(p.g->epoch + m * 8 + n) + 1;
#pragma unroll 1
  for (int k = lane; k < 288; k += 32) {
    const uint32_t bb = __ldg(reinterpret_cast<const uint32_t*>(k < 224 ? p.b1 + 448 * n : p.b2 + 128 * n - 448) + k);
    const float sc = k < 224 ? 0.5f : 1.f;
    sts_f2(sb + (k < 224 ? OFF_CSF + k * 16 + 8 : OFF_CSQ + 1536 + (k - 224) * 8), sc * bf_lo(bb), sc * bf_hi(bb));
  }
  __syncwarp();
  if (elect_one()) mbar_arrive(sb + BAR_BIAS);
  bar_sync(BAR_HLP, 160);
  {
    uint4* base = p.g->csp + n * 17 * 224 + 12 * m + min(lane & 15, 11);
    float s0 = 0.f, s1 = 0.f;
#pragma unroll 1
    for (int g = 0; g < 2; g++) {
      uint32_t x[4], y[4];
#pragma unroll 1
      for (int it = 0; it < MSG_SPINS; it++) {
        uint32_t bad = 0, z, tg;
        if (g == 0 || it > 0) __nanosleep(CS_NS);
#pragma unroll
        for (int k = 0; k < 4; k++) { ld_msg(base + (g * 8 + (lane >> 4) * 4 + k) * 224, x[k], y[k], z, tg); bad |= tg ^ tag; }
        if (__all_sync(0xffffffffu, bad == 0)) break;
      }
#pragma unroll
      for (int k = 0; k < 4; k++) { s0 += __uint_as_float(x[k]); s1 += __uint_as_float(y[k]); }
    }
    s0 += __shfl_xor_sync(0xffffffffu, s0, 16);
    s1 += __shfl_xor_sync(0xffffffffu, s1, 16);
    if (lane < 12) st_msg(base + 16 * 224, __float_as_uint(s0), __float_as_uint(s1), 0u, tag);
  }
#pragma unroll 1
  for (int c = 0; c < 7; c++) {
    float a[8] = {0.f, 0.f, 0.f, 0.f, 0.f, 0.f, 0.f, 0.f};
#pragma unroll 1
    for (int h = 0; h < 2; h++) {
      if (elect_one()) {
        mbar_expect_tx(sb + BAR_CSLD + 8, 4096);
        tma_ld2(sb + OFF_HLP, &p.t.w1c, sb + BAR_CSLD + 8, 448 * n + 64 * c, 64 * m + 32 * h);
        if (c < 6) asm volatile("cp.async.bulk.prefetch.tensor.2d.L2.global [%0, {%1, %2}];" ::"l"(&p.t.w1c), "r"(448 * n + 64 * c + 64), "r"(64 * m + 32 * h) : "memory");
      }
      mbar_wait(sb + BAR_CSLD + 8, h);
      sum_rows(sb + OFF_HLP, 4, a, lane);
      __syncwarp();
    }
    publish_sums(a, p.g->csp + ((8 + n) * 17 + m) * 224 + c * 32, lane, tag);
  }
  if (elect_one()) {
#pragma unroll 1
    for (int k = 0; k < 3; k++) {
      mbar_wait(sb + BAR_XGO, k & 1);
      __nanosleep(XB_NS);
#pragma unroll 1
      for (int w = 0; w < 4; w++) {
        tma_st_warp(&p.t.out_w, sb + OFF_X + 16384 + w * 4096, 128 * n + 64, m, w);
        bulk_commit();
        bulk_wait_read();
        if (w < 3) __nanosleep(XB_GAP_NS);
      }
      bulk_wait_all();
      asm volatile("mbarrier.arrive.shared::cta.b64 _, [%0], 4;" ::"r"(sb + BAR_PUB + (k & 1 ? 64 : 24)) : "memory");
    }
  }
}

__device__ __forceinline__ void poll_msgs2(const uint4* pa, const uint4* pb, float (&v)[4], uint32_t tag) {
#pragma unroll 1
  for (int it = 0; it < MSG_SPINS; it++) {
    uint32_t x[4], z, ta, tb;
    ld_msg(pa, x[0], x[1], z, ta);
    ld_msg(pb, x[2], x[3], z, tb);
#pragma unroll
    for (int e = 0; e < 4; e++) v[e] = __uint_as_float(x[e]);
    if (__all_sync(0xffffffffu, ta == tag && tb == tag)) break;
  }
}
__device__ __forceinline__ void colsum_total(const Params& p, const Ctx& cx, int mat, uint32_t tag) {
  uint4* base = p.g->csp + (mat * 8 + cx.n) * 17 * 224;
  const int per = 12 + 2 * mat, k = 2 * cx.w + (cx.lane >> 4), ia = per * cx.m + k, ib = per * cx.m + min(k + 8, per - 1);
  float v[4];
  poll_msgs2(base + (cx.lane & 15) * 224 + ia, base + (cx.lane & 15) * 224 + ib, v, tag);
#pragma unroll 1
  for (int d = 1; d < 16; d *= 2)
#pragma unroll
    for (int e = 0; e < 4; e++) v[e] += __shfl_xor_sync(0xffffffffu, v[e], d);
  const bool hi = cx.lane & 1;
  if ((cx.lane & 14) == 0) st_msg(base + 16 * 224 + (hi ? ib : ia), __float_as_uint(hi ? v[2] : v[0]), __float_as_uint(hi ? v[3] : v[1]), 0u, tag);
}
__device__ __forceinline__ void colsum_gather(const Params& p, const Ctx& cx, int mat, uint32_t tag) {
  const uint4* base = p.g->csp + ((mat * 8 + cx.n) * 17 + 16) * 224;
  const int ia = cx.w * 32 + cx.lane, ib = min(ia + 128, 191 + 32 * mat);
  float v[4];
  poll_msgs2(base + ia, base + ib, v, tag);
  const uint32_t tab = cx.sb + (mat ? OFF_CSF : OFF_CSQ);
  sts_f2(tab + (ia << (3 + mat)), v[0], v[1]);
  sts_f2(tab + (ib << (3 + mat)), v[2], v[3]);
}

#define ACC(q, j, e) acc[(q) & 1][4 * (j) + 2 * ((q) >> 1) + (e)]

constexpr uint32_t RING16 = RING_UNITS * (UNIT >> 4);
__device__ __forceinline__ bool tile_split(int i) { return (0xD98 >> i) & 1; }

__device__ __forceinline__ void write_run_desc(uint32_t sb, int i, int step) {
  const int layer = i >= 7, t = i - 7 * layer, part = tile_split(i) ? step : 2;
  const bool wide = tile_wide(t), own = t != 2 && t != 6 && part != 1 && i != 0, second = t == 1 || t == 4;
  const uint32_t z16 = (wide ? 5 : 4) * (UNIT >> 4), a_off = z16 - 1024 + (uint32_t)DESC_A - (uint32_t)DESC_B;
  const int gl = 16 * t + (part == 2 ? 0 : second ? 16 * part - 14 : 4 * part), g0 = layer * STAGES_PER_LAYER + gl;
  const uint32_t s16 = (sb & 0x3FFFF) >> 4, bfirst = (uint32_t)DESC_B + s16;
  const int nkb = t == 6 ? 56 : part == 0 ? 2 : 12 + 2 * part;
  const bool win1 = t == 1 && part != 0;
  const int run = win1 ? WIN1 + 1 : t == 2 ? WIN2 + 1 : nkb;
  const int rest = win1 ? 64 | (nkb - 1 - WIN1) : t == 2 ? 64 | (7 - WIN2) | (8 << 7) : 0;
  const uint32_t blo = bfirst + z16 * (wide ? (gl + (t == 5 ? 3 : 0)) & 3 : (gl + 3) % 5);
  const uint32_t alo = own ? (uint32_t)DESC_A + s16 + (OFF_X >> 4) : blo + a_off;
  const uint32_t aoff = own ? alo + 1024 - (blo == bfirst + RING16 - z16 ? bfirst : blo + z16) : a_off;
  const bool xwait = part == 0 && !second, keep = !(part == 0 || t == 5);
  sts_u4(sb + OFF_RUN + (2 * i + step) * 16, blo, alo, aoff,
         ((g0 / NBAR) & 1) | xwait << 1 | keep << 2 | 8 * (g0 % NBAR) | run << 6 | rest << 12);
}

__device__ __forceinline__ void write_partial_stats(const Params& p, const Ctx& c, int ln, uint32_t tag) {
  const uint32_t xrow = c.sb + OFF_X + c.w * 4096 + c.lane * 128;
  float s = 0.f, q = 0.f, s1 = 0.f, q1 = 0.f;
#pragma unroll 4
  for (int j = 0; j < 16; j++) {
    uint32_t u[4];
    lds_u4(xrow + (j >> 3) * 16384 + (((j & 7) ^ (c.lane & 7)) << 4), u[0], u[1], u[2], u[3]);
#pragma unroll
    for (int e = 0; e < 4; e++) {
      const float a = bf_lo(u[e]), d = bf_hi(u[e]);
      s += a; q = fmaf(a, a, q);
      s1 += d; q1 = fmaf(d, d, q1);
    }
  }
  s += s1;
  q += q1;
  st_msg(p.g->stats + (ln * 8 + c.n) * SEQ + 128 * c.m + 32 * c.w + c.lane, __float_as_uint(s),
         __float_as_uint(fmaxf(q - s * s * (1.f / 128.f), 0.f)), 0u, tag);
}

template <int N>
__device__ __forceinline__ void mainloop(const Params& p, float (&acc)[2][96], uint32_t sb, int i, int step, int mn) {
  constexpr uint32_t Z16 = (2 + N / 64) * (UNIT >> 4);
  constexpr uint32_t A_OFF = Z16 - 1024 + (uint32_t)DESC_A - (uint32_t)DESC_B;
  const int wg = i & 1;
  const uint32_t s16 = (sb & 0x3FFFF) >> 4;
  const uint32_t blast = (uint32_t)DESC_B + s16 + RING16 - Z16, flast = sb + BAR_FULL + 8 * (NBAR - 1);
  uint32_t blo = (uint32_t)DESC_B + s16, alo = blo + A_OFF, aoff = A_OFF, misc = 16 << 6;
  if (N == 128 || i > 0) lds_u4(sb + OFF_RUN + (2 * i + step) * 16, blo, alo, aoff, misc);
  uint32_t keep = misc & 4;
  int run = (misc >> 6) & 63, rest = misc >> 12;
  uint32_t fb = sb + BAR_FULL + (misc & 0x38), ph = misc & 1;
  uint32_t prev = sb + BAR_DUMMY - 8 * NBAR;
  const uint32_t lane_id = __popc(__ballot_sync(0xffffffffu, true) & lanemask_lt()), rel = pair_offset(sb, lane_id & 1) + 8 * NBAR;
  pin_regs<N / 2>(acc);
  if (N == 128 || i > 0) bar_sync(BAR_ORDER + wg, 256);
  else bar_sync(BAR_INIT0, 160);
  mbar_wait(fb, ph);
  if (N == 192 && i == 0) cluster_wait();
  if (misc & 2) mbar_wait(sb + BAR_XGO, N == 192);
#pragma unroll 1
  while (true) {
    const uint64_t da = (DESC_A & ~0xffffffffull) | alo, db = (DESC_B & ~0xffffffffull) | blo;
    asm volatile("wgmma.fence.sync.aligned;" ::: "memory");
    wgmma_ss<N>(acc[0], da, db, keep);
    wgmma_ss<N>(acc[1], da + 64, db, keep);
    keep = 4;
    wgmma_ss<N>(acc[0], da + 2, db + 128);
    wgmma_ss<N>(acc[1], da + 66, db + 128);
    asm volatile("wgmma.commit_group.sync.aligned;" ::: "memory");
    asm volatile("wgmma.wait_group.sync.aligned 1;" ::: "memory");
    if (lane_id < 2) mbar_arrive_cluster(prev + rel);
    prev = fb;
    if (fb == flast) { fb -= 8 * NBAR; ph++; }
    fb += 8;
    if (blo == blast) blo -= RING16;
    blo += Z16;
    alo = blo + aoff;
    aoff = A_OFF;
    run--;
    const bool ready = mbar_test(fb, ph) && run != 0;
    asm volatile("wgmma.fence.sync.aligned;" ::: "memory");
    wgmma_ss<N>(acc[0], da + 4, db + 4 * N);
    wgmma_ss<N>(acc[1], da + 68, db + 4 * N);
    wgmma_ss<N>(acc[0], da + 6, db + 4 * N + 128);
    wgmma_ss<N>(acc[1], da + 70, db + 4 * N + 128);
    asm volatile("wgmma.commit_group.sync.aligned;" ::: "memory");
    if (!ready) {
      bool window = false;
      if (run == 0) {
        if (rest == 0) break;
        window = rest & 64;
        if (window) bar_arrive(BAR_GO, 256);
        else alo = (uint32_t)DESC_A + s16 + (OFF_STG >> 4);
        run = rest & 63;
        rest >>= 7;
      }
      mbar_wait(fb, ph);
      if (window) bar_sync(BAR_DONE, 256);
    }
  }
  if (i < 13 && !(N == 192 && (misc >> 12))) bar_arrive(BAR_ORDER + (wg ^ 1), 256);
  if (N == 128 && ((0x2244 >> i) & 1)) {
    const Ctx cx = make_ctx(sb, mn);
    const uint32_t xrow = cx.sb + OFF_X + cx.w * 4096 + cx.lane * 128 + ((cx.lane & 7) << 4);
    const bool leader = elect_one();
    asm volatile("wgmma.wait_group.sync.aligned 0;" ::: "memory");
    pin_regs<64>(acc);
#pragma unroll
    for (int h = 0; h < 2; h++) {
      if (h == 1 && p.zero != 0) break;
#pragma unroll
      for (int j = 8 * h; j < 8 * h + 8; j++)
        stsm4((xrow ^ ((j & 7) << 4)) + h * 16384, pack_bf16(ACC(0, j, 0), ACC(0, j, 1)), pack_bf16(ACC(1, j, 0), ACC(1, j, 1)),
              pack_bf16(ACC(2, j, 0), ACC(2, j, 1)), pack_bf16(ACC(3, j, 0), ACC(3, j, 1)));
      fence_async_smem();
      __syncwarp();
      if (leader) {
        mbar_arrive(sb + BAR_XRDY + 8 * h);
        if (i == 13) {
          tma_st_warp(&p.t.out_w, cx.sb + OFF_X + h * 16384 + cx.w * 4096, 128 * cx.n + 64 * h, cx.m, cx.w);
          bulk_commit();
          if (h == 1) bulk_wait_read();
        }
      }
      if (h == 0 && lane_id < 2 && i < 13) mbar_arrive_cluster(prev + rel);
    }
    if (i == 2 || i == 9) write_partial_stats(p, cx, (i + 3) >> 2, lds_u(sb + OFF_TAG));
    return;
  }
  asm volatile("wgmma.wait_group.sync.aligned 0;" ::: "memory");
  pin_regs<N / 2>(acc);
  if (lane_id < 2) mbar_arrive_cluster(prev + rel);
}

__device__ __forceinline__ void finish_row_stats(const Params& p, const Ctx& c, int ln, uint32_t tag) {
  const uint4* src = p.g->stats + ln * 8 * SEQ + 128 * c.m + 32 * c.w + c.lane;
  uint32_t ps[8], pm[8];
#pragma unroll 1
  for (int it = 0; it < MSG_SPINS; it++) {
    uint32_t bad = 0, u, tg;
    if (ln == 2 || it > 0) __nanosleep(STAT_NS);
#pragma unroll
    for (int k = 0; k < 8; k++) { ld_msg(src + k * SEQ, ps[k], pm[k], u, tg); bad |= tg ^ tag; }
    if (__all_sync(0xffffffffu, bad == 0)) break;
  }
  float s = 0.f, m2 = 0.f;
#pragma unroll
  for (int k = 0; k < 8; k++) s += __uint_as_float(ps[k]);
  const float mean = s * (1.f / DM);
#pragma unroll
  for (int k = 0; k < 8; k++) {
    const float d = __uint_as_float(ps[k]) * (1.f / 128.f) - mean;
    m2 += fmaf(128.f * d, d, __uint_as_float(pm[k]));
  }
  sts_f2(c.sb + OFF_ROW + (32 * c.w + c.lane) * 8, rsqrtf(m2 * (1.f / DM) + 1e-5f), mean);
  __syncwarp();
}

__device__ __forceinline__ void attn_scores(const uint32_t* qa, const uint32_t* qb, const uint32_t* kp, const uint32_t* ka,
                                            const uint32_t* kb, float (&l)[4], const float4& zero, const bool (&early)[2]) {
  float s[3][4];
#pragma unroll
  for (int x = 0; x < 3; x++) {
    const uint32_t* kk = x == 0 ? kp : x == 1 ? ka : kb;
    asm volatile("mma.sync.aligned.m16n8k16.row.col.f32.bf16.bf16.f32 {%0,%1,%2,%3}, {%4,%5,%6,%7}, {%8,%9}, {%10,%11,%12,%13};"
                 : "=f"(s[x][0]), "=f"(s[x][1]), "=f"(s[x][2]), "=f"(s[x][3])
                 : "r"(qa[0]), "r"(qb[0]), "r"(qa[1]), "r"(qb[1]), "r"(kk[0]), "r"(kk[1]), "f"(zero.x), "f"(zero.y),
                   "f"(zero.z), "f"(zero.w));
  }
#pragma unroll
  for (int x = 0; x < 3; x++) {
    const uint32_t* kk = x == 0 ? kp : x == 1 ? ka : kb;
    mma16816(s[x], qa[2], qb[2], qa[3], qb[3], kk[2], kk[3]);
  }
#pragma unroll
  for (int e = 0; e < 2; e++) {
    l[e] = early[e] ? s[0][e] : s[1][e];
    l[2 + e] = early[e] ? s[1][2 + e] : s[2][2 + e];
  }
}

__device__ __forceinline__ void attn_mix(const float (&l)[4], const float (&sc)[4], const float (&off)[4], const float (&rk)[4],
                                         const uint32_t* vp, const uint32_t* va, const uint32_t* vb, float (&o)[4][4],
                                         float (&sum)[2], uint32_t mask, uint32_t zero) {
  float x[4];
#pragma unroll
  for (int e = 0; e < 4; e++) x[e] = fmaf(l[e], sc[e], off[e]);
  const float ml = quad_max(fmaxf(x[0], x[1])), mh = quad_max(fmaxf(x[2], x[3]));
  x[0] = ex2(x[0] - ml); x[1] = ex2(x[1] - ml);
  x[2] = ex2(x[2] - mh); x[3] = ex2(x[3] - mh);
  sum[0] = rcp_hw(quad_sum(x[0] + x[1]));
  sum[1] = rcp_hw(quad_sum(x[2] + x[3]));
  const uint32_t pl = pack_bf16(x[0] * rk[0], x[1] * rk[1]), ph = pack_bf16(x[2] * rk[2], x[3] * rk[3]);
  const uint32_t a0 = pl & ~mask, a1 = ph & mask, a2 = pl & zero, a3 = ph & ~mask, c0 = pl & mask, c1 = ph & zero;
#pragma unroll
  for (int jn = 0; jn < 4; jn++) {
    o[jn][0] = o[jn][1] = o[jn][2] = o[jn][3] = 0.f;
    mma16816(o[jn], a0, a1, a2, a3, va[jn], vb[jn]);
  }
#pragma unroll
  for (int jn = 0; jn < 4; jn++) mma1688(o[jn], c0, c1, vp[jn]);
}

__device__ __forceinline__ void gelu_epilogue(const Params& p, float (&acc)[2][96], const Ctx& cx, int t) {
  UNPACK_CTX(cx);
  (void)wg;
  float rs[4], rm[4];
#pragma unroll
  for (int q = 0; q < 4; q++) {
    const float2 v = lds_f2(sb + OFF_ROW + (32 * w + 8 * q + (lane >> 2)) * 8);
    rs[q] = 0.5f * v.x;
    rm[q] = -rs[q] * v.y;
  }
  const int col0 = 128 * (t - 3);
  const uint32_t stg = sb + OFF_STG + w * 4096;
  const uint32_t ctab = sb + OFF_CSF + (col0 / 2 + (lane & 3)) * 16, srow = stg + lane * 128 + ((lane & 7) << 4);
  if (t == 5) __nanosleep(STAG_NS * w);
  float4 nb = lds_f4(ctab);
#pragma unroll
  for (int c = 0; c < 3; c++) {
    if (c == 2 && t != 5) break;
    uint32_t hp[8][4];
#pragma unroll
    for (int j = 0; j < 8; j++) {
      const float4 cb = nb;
      if (8 * c + j < 23) nb = lds_f4(ctab + (8 * c + j + 1) * 64);
#pragma unroll
      for (int q = 0; q < 4; q++) {
        float y[2];
        const int k = 4 * j + q - GELU_DEP;
        const float rmq = k >= 0 ? chain(rm[q], hp[k >> 2][k & 3], p.zero) : rm[q];
#pragma unroll
        for (int e = 0; e < 2; e++) {
          const float z = fmaf(ACC(q, 8 * c + j, e), rs[q], fmaf(rmq, e ? cb.y : cb.x, e ? cb.w : cb.z));
          const float u = z * fmaf(z * z, 8.f * 0.7978845608028654f * 0.044715f, 2.f * 0.7978845608028654f);
          y[e] = fmaf(z, tanh_hw(u), z);
        }
        hp[j][q] = pack_bf16(y[0], y[1]);
      }
      if (j == STG_WAIT && c > 0) {
        if (lane == 0) bulk_wait_read();
        __syncwarp();
      }
      if (c == 0 || j > STG_WAIT) {
        stsm4(srow ^ (j << 4), hp[j][0], hp[j][1], hp[j][2], hp[j][3]);
      } else if (j == STG_WAIT) {
#pragma unroll
        for (int jj = 0; jj <= STG_WAIT; jj++) stsm4(srow ^ (jj << 4), hp[jj][0], hp[jj][1], hp[jj][2], hp[jj][3]);
      }
    }
    fence_async_smem();
    __syncwarp();
    if (lane == 0) {
      tma_st2(&p.t.h_st, stg, 448 * n + col0 + 64 * c, 128 * m + 32 * w);
      bulk_commit();
    }
  }
#pragma unroll
  for (int r = 0; r < 16; r++) acc[0][r] = acc[1][r] = 0.f;
}

template <int PART>
__device__ __forceinline__ void rank1_update(const Params& p, float (&acc)[2][96], const Ctx& cx, int t) {
  float nm[4];
#pragma unroll
  for (int q = 0; q < 4; q++) nm[q] = t == 6 ? 1.f : -lds_f(cx.sb + OFF_ROW + (32 * cx.w + 8 * q + (cx.lane >> 2)) * 8 + 4);
  const uint32_t ctab = cx.sb + OFF_CSQ + ((t & 3) * 192 + 2 * (cx.lane & 3)) * 4;
#pragma unroll
  for (int j = PART == 1 ? 8 : 0; j < 24; j++) {
    const float2 cs = lds_f2(ctab + j * 32);
#pragma unroll
    for (int q = 0; q < 4; q++) {
      if (PART != 0 && (PART == 1) != (q == 3 && j >= 8)) continue;
      const int k = 4 * j + q - 1;
      const float nq = PART == 0 && k >= 0 ? chain(nm[q], __float_as_uint(ACC(k & 3, k >> 2, 1)), p.zero) : nm[q];
      ACC(q, j, 0) = fmaf(nq, cs.x, ACC(q, j, 0));
      ACC(q, j, 1) = fmaf(nq, cs.y, ACC(q, j, 1));
    }
  }
}

__device__ __forceinline__ void attn_epilogue(const Params& p, float (&acc)[2][96], const Ctx& cx, int layer, int t, uint32_t tag) {
  UNPACK_CTX(cx);
  const uint32_t ktab = sb + OFF_ROW + (32 * w + 2 * (lane & 3)) * 8, exc = sb + OFF_STG + (w & 1) * 2048 + lane * 16;
  uint4* const halo = p.g->halo + (((layer * 2 + t) * 16 + m) * 8 + n) * 384 + (w & 1) * 192;
  uint32_t Q[4][8], K[4][8], V[4][8], E[18], P[18];
  float kr[5][2], qr[4];
  const bool late_fold = layer == 0 && t == 1;
  if (late_fold) rank1_update<1>(p, acc, cx, 1);
  {
    const float4 r = lds_f4(ktab + 192);
    E[16] = __float_as_uint(kr[4][0] = r.x);
    E[17] = __float_as_uint(kr[4][1] = r.z);
  }
#pragma unroll
  for (int j = 0; j < 8; j++) {
    E[j] = K[3][j] = pack_bf16(ACC(3, 8 + j, 0), ACC(3, 8 + j, 1));
    E[8 + j] = V[3][j] = movtrans(pack_bf16(ACC(3, 16 + j, 0), ACC(3, 16 + j, 1)));
  }
  if (w < 2) {
#pragma unroll
    for (int k = 0; k < 4; k++) sts_u4(exc + k * 512, E[4 * k], E[4 * k + 1], E[4 * k + 2], E[4 * k + 3]);
  } else {
#pragma unroll
    for (int k = 0; k < 6; k++) st_msg(halo + k * 32 + lane, E[3 * k], E[3 * k + 1], E[3 * k + 2], tag);
  }
  bar_arrive(BAR_PAIR + w, 64);
  if (t == 1) bar_arrive(BAR_ORDER + (wg ^ 1), 256);
  if (late_fold) rank1_update<2>(p, acc, cx, 1);
#pragma unroll
  for (int q = 0; q < 4; q++) {
    qr[q] = lds_f(sb + OFF_ROW + (32 * w + 8 * q + (lane >> 2)) * 8) * (0.17677669529663687f * 1.4426950408889634f);
#pragma unroll
    for (int j = 0; j < 8; j++) Q[q][j] = pack_bf16(ACC(q, j, 0), ACC(q, j, 1));
    if (q < 3) {
      const float4 r = lds_f4(ktab + 64 * q);
      kr[1 + q][0] = r.x;
      kr[1 + q][1] = r.z;
#pragma unroll
      for (int j = 0; j < 8; j++) {
        K[q][j] = pack_bf16(ACC(q, 8 + j, 0), ACC(q, 8 + j, 1));
        V[q][j] = movtrans(pack_bf16(ACC(q, 16 + j, 0), ACC(q, 16 + j, 1)));
      }
    }
  }
  bar_sync(BAR_PAIR + (w ^ 2), 64);
  if (w >= 2 || m == 0) {
#pragma unroll
    for (int k = 0; k < 4; k++) lds_u4(exc + k * 512, P[4 * k], P[4 * k + 1], P[4 * k + 2], P[4 * k + 3]);
    const float4 r = lds_f4(ktab - (w >> 1) * 320);
    P[16] = __float_as_uint(r.x);
    P[17] = __float_as_uint(r.z);
  } else {
    if (m & 1) __nanosleep(HALO_NS);
#pragma unroll 1
    for (int it = 0; it < MSG_SPINS; it++) {
      uint32_t tg, bad = 0;
      if (it > 0 || !(m & 1)) poll_line(reinterpret_cast<const uint32_t*>(halo - 8 * 384 + 191) + 3, tag, 1u);
#pragma unroll
      for (int k = 0; k < 6; k++) {
        ld_msg(halo - 8 * 384 + k * 32 + lane, P[3 * k], P[3 * k + 1], P[3 * k + 2], tg);
        bad |= tg ^ tag;
      }
      if (__all_sync(0xffffffffu, bad == 0)) break;
    }
  }
  kr[0][0] = __uint_as_float(P[16]);
  kr[0][1] = __uint_as_float(P[17]);
  const bool early[2] = {2 * (lane & 3) > (lane >> 2), 2 * (lane & 3) + 1 > (lane >> 2)};
  const uint32_t mask = (early[0] ? 0xffffu : 0u) | (early[1] ? 0xffff0000u : 0u);
  float rk[2][4], sc[2][4], off[2][4];
#pragma unroll
  for (int g = 0; g < 2; g++) {
#pragma unroll
    for (int e = 0; e < 4; e++) {
      const int q = 2 * g + (e >> 1);
      const bool masked = q == 0 && m == 0 && w < 2 && early[e & 1];
      rk[g][e] = early[e & 1] ? kr[q][e & 1] : kr[q + 1][e & 1];
      sc[g][e] = masked ? 0.f : rk[g][e] * qr[q];
      off[g][e] = masked ? -1e30f : 0.f;
    }
  }
  if (w == 0 && elect_one()) asm volatile("prefetch.tensormap [%0];" ::"l"(&p.t.att_st) : "memory");
  bar_sync(BAR_GO, 256);
  const float4 zero = lds_f4(sb + OFF_ZERO);
  float l[2][2][4], o[2][2][4][4], sum[2][2][2];
#pragma unroll
  for (int h = 0; h < 2; h++) {
    if (h == 1) {
      Q[2][4] |= __float_as_uint(l[1][0][0]) & p.zero;
      Q[0][4] |= __float_as_uint(l[0][0][0]) & p.zero;
    }
    attn_scores(&Q[2][4 * h], &Q[3][4 * h], &K[1][4 * h], &K[2][4 * h], &K[3][4 * h], l[1][h], zero, early);
    attn_scores(&Q[0][4 * h], &Q[1][4 * h], &P[4 * h], &K[0][4 * h], &K[1][4 * h], l[0][h], zero, early);
  }
  const uint32_t stg = sb + OFF_STG + w * 4096, srow = stg + lane * 128 + ((lane & 7) << 4);
#pragma unroll
  for (int h = 0; h < 2; h++) {
    attn_mix(l[1][h], sc[1], off[1], rk[1], &V[1][4 * h], &V[2][4 * h], &V[3][4 * h], o[1][h], sum[1][h], mask, p.zero);
    attn_mix(l[0][h], sc[0], off[0], rk[0], &P[8 + 4 * h], &V[0][4 * h], &V[1][4 * h], o[0][h], sum[0][h], mask, p.zero);
#pragma unroll
    for (int j = 0; j < 4; j++) {
      const float(&a)[4] = o[0][h][j];
      const float(&c)[4] = o[1][h][j];
      stsm4(srow ^ ((4 * h + j) << 4), pack_bf16(a[0] * sum[0][h][0], a[1] * sum[0][h][0]), pack_bf16(a[2] * sum[0][h][1], a[3] * sum[0][h][1]),
            pack_bf16(c[0] * sum[1][h][0], c[1] * sum[1][h][0]), pack_bf16(c[2] * sum[1][h][1], c[3] * sum[1][h][1]));
    }
  }
  bar_arrive(BAR_DONE, 256);
  fence_async_smem();
  __syncwarp();
  if (lane == 0) {
    tma_st2(&p.t.att_st, stg, 128 * n + 64 * t, 128 * m + 32 * w);
    bulk_commit();
  }
}

__device__ __forceinline__ void finish_stores(uint32_t sb, int i) {
  const int t = i >= 7 ? i - 7 : i;
  if ((threadIdx.x & 31) == 0) {
    bulk_wait_all();
    mbar_arrive(sb + BAR_PUB + 8 * (t < 2 ? t : t + 1));
  }
  __syncwarp();
  if (i < 12) bar_arrive(BAR_GUARD + ((i & 1) ^ 1), 256);
}

__device__ __forceinline__ bool consumer_tile(const Params& p, float (&acc)[2][96], uint32_t sb0, int i, int mn) {
  const int layer = i >= 7, t = i - 7 * layer, wg = i & 1;
  const bool resid = t == 2 || t == 6;
  {
    if (resid) {
      const Ctx cx = make_ctx(sb0, mn);
      const uint32_t xrow = cx.sb + OFF_X + cx.w * 4096 + cx.lane * 128;
      const uint32_t sel_lo = 0x1044u | p.zero, sel_hi = 0x3244u | p.zero;
#pragma unroll
      for (int j = 0; j < 16; j++) {
        uint32_t r[4];
        ldsm4(xrow + (j >> 3) * 16384 + (((j & 7) ^ (cx.lane & 7)) << 4), r[0], r[1], r[2], r[3]);
#pragma unroll
        for (int q = 0; q < 4; q++) {
          ACC(q, j, 0) = prmt_f(r[q], sel_lo);
          ACC(q, j, 1) = prmt_f(r[q], sel_hi);
        }
      }
    }
    if (t >= 5 || i == 7) finish_stores(sb0, i - 2);
#pragma unroll 1
    for (int step = !tile_split(i);; step++) {
      if (step == 1 && (t == 1 || t == 4)) {
        const Ctx cx = make_ctx(sb0, mn);
        if (i == 1) {
          const uint32_t epoch = __ldcg(p.g->epoch + (mn & 127));
          cluster_wait();
          asm volatile("st.shared.u32 [%0], %1;" ::"r"(sb0 + OFF_TAG), "r"(epoch + 1) : "memory");
        }
        const uint32_t tag = lds_u(cx.sb + OFF_TAG);
        const int ln = (i + 1) >> 2;
#pragma unroll 1
        for (int r = 0; r < 2; r++) {
          if (i == 1) {
            if (cx.w < 3) {
              float a[8] = {0.f, 0.f, 0.f, 0.f, 0.f, 0.f, 0.f, 0.f};
              mbar_wait(sb0 + BAR_CSLD, r);
#pragma unroll 1
              for (int h = 0; h < 2; h++) sum_rows(cx.sb + OFF_STG + h * 12288 + cx.w * 4096, 4, a, cx.lane);
              publish_sums(a, p.g->csp + (cx.n * 17 + cx.m) * 224 + (3 * r + cx.w) * 32, cx.lane, tag);
            }
          }
          if (r == 1) break;
          if (i == 1) {
            bar_sync(BAR_WG + 1, 128);
            if (cx.w == 3 && elect_one()) {
              mbar_expect_tx(sb0 + BAR_CSLD, 24576);
              tma_ld3(sb0 + OFF_STG, &p.t.wqkv, sb0 + BAR_CSLD, 128 * cx.n + 64, 64 * cx.m, 0);
              tma_ld3(sb0 + OFF_STG + 12288, &p.t.wqkv, sb0 + BAR_CSLD, 128 * cx.n + 64, 64 * cx.m + 32, 0);
            }
            mbar_wait(sb0 + BAR_XRDY, 0);
            mbar_wait(sb0 + BAR_XRDY + 8, 0);
          }
          if (t == 1) write_partial_stats(p, cx, ln, tag);
        }
        if (i == 1) {
          bar_arrive(BAR_HLP, 160);
          bar_sync(BAR_INIT, 160);
        }
        if (i == 4) colsum_total(p, cx, 1, tag);
        if (i != 1) bar_sync(BAR_GUARD + wg, 256);
        finish_row_stats(p, cx, ln, tag);
        if (i == 4) {
          colsum_gather(p, cx, 1, tag);
          mbar_wait(sb0 + BAR_BIAS, 0);
        }
        bar_arrive(BAR_GUARD + (wg ^ 1), 256);
      }
      if (step == 2 && !resid) bar_sync(BAR_GUARD + wg, 256);
      if (step == 2 && i == 0) {
        colsum_gather(p, make_ctx(sb0, mn), 0, lds_u(sb0 + OFF_TAG));
        bar_sync(BAR_WG, 128);
      }
      if ((t + step == 2 && i != 1) || t == 6) rank1_update<0>(p, acc, make_ctx(sb0, mn), t);
      if (step == 2) break;
      if (tile_wide(t)) {
        mainloop<192>(p, acc, sb0, i, step, mn);
      } else {
        mainloop<128>(p, acc, sb0, i, step, mn);
        if (resid) return false;
      }
    }
    if (t < 2) return true;
    gelu_epilogue(p, acc, make_ctx(sb0, mn), t);
    return false;
  }
}

template <bool BY_SMID>
__global__ void __cluster_dims__(2, 1, 1) __launch_bounds__(384, 1)
fused_layers_kernel(const Scalars scalars, const __grid_constant__ Maps maps) {
  if (threadIdx.x == 288 || threadIdx.x == 320)
    asm volatile("prefetch.tensormap [%0];" ::"l"(threadIdx.x == 288 ? &maps.xin : &maps.wqkv) : "memory");
  const Params p{scalars, maps};
  extern __shared__ __align__(1024) uint8_t smem_raw[];
  const uint32_t sb = uniform((uint32_t)__cvta_generic_to_shared(smem_raw));
  const int tid = threadIdx.x, lane = tid & 31, warp = uniform(tid >> 5), wg = warp >> 2, w = warp & 3;

  int mn;
  {
    int id = blockIdx.x;
    if (BY_SMID) asm volatile("mov.u32 %0, %%smid;" : "=r"(id));
    else if (id >= 120) id += 4;
    const int c = id >> 1;
    int g, j;
    if (c < 32) { g = c & 7; j = c >> 3; }
    else if (c < 60) { g = 1 + (c - 32) % 7; j = 4 + (c - 32) / 7; }
    else { g = 0; j = c - 58; }
    mn = (g * 2 + (blockIdx.x & 1)) * 8 + j;
    if (c == 60 || c == 61) {
      if (tid < 32) {
        const uint32_t tag = __ldcg(p.g->epoch + NCTA + (id & 3)) + 1;
#pragma unroll 1
        for (int mm = 0; mm < 16; mm++) poll_line(p.g->flags + mm * 32 + (lane & 7), 32 * tag, 0xffu);
        if (tid == 0) p.g->epoch[NCTA + (id & 3)] = tag;
      }
      return;
    }
  }
  const int m = mn >> 3, n = mn & 7;
  if (wg < 2) {
    cluster_arrive();
    asm volatile("setmaxnreg.inc.sync.aligned.u32 232;");
    const int id = mn | (warp << 7);
#pragma unroll 1
    for (int i = wg;; i += 2) {
      float acc[2][96];
#pragma unroll
      for (int r = 0; r < 96; r++) acc[0][r] = acc[1][r] = 0.f;
      pin_regs<96>(acc);
#pragma unroll 1
      while (!consumer_tile(p, acc, sb, i, id)) {
        i += 2;
        if (i >= 14) goto all_done;
      }
      attn_epilogue(p, acc, make_ctx(sb, id), i >= 7, i >= 7 ? i - 7 : i, lds_u(sb + OFF_TAG));
      finish_stores(sb, i);
    }
  all_done:
    if (wg == 0) {
      finish_stores(sb, 12);
    } else {
      cluster_arrive();
      cluster_wait();
    }
  } else {
    asm volatile("setmaxnreg.dec.sync.aligned.u32 40;");
    if (w != 0) {
      if (w == 1 && elect_one()) {
        mbar_init(sb + BAR_FULL + 32, 2);
#pragma unroll
        for (int k = 0; k < NBAR; k++) mbar_init(sb + BAR_EMPTY + 8 * k, 8);
#pragma unroll
        for (int k = 0; k < 3; k++) mbar_init(sb + BAR_XRDY + 8 * k, 4);
#pragma unroll
        for (int k = 0; k < 9; k++) mbar_init(sb + BAR_PUB + 8 * k, 4);
#pragma unroll
        for (int k = 0; k < 4; k++) mbar_init(sb + BAR_CSLD + 8 * k, 1);
        sts_f2(sb + OFF_ZERO, 0.f, 0.f);
        sts_f2(sb + OFF_ZERO + 8, 0.f, 0.f);
        asm volatile("fence.mbarrier_init.release.cluster;" ::: "memory");
      }
      __syncwarp();
      cluster_arrive();
      if (w == 2) {
        if (lane < 28) write_run_desc(sb, lane >> 1, lane & 1);
        bar_arrive(BAR_INIT, 160);
      }
      cluster_wait();
      if (w == 1) producer<true>(p, sb, m, n, lane);
      else if (w == 3) colsum_helper(p, sb, m, n, lane);
      else if (elect_one()) publisher(p, sb, m, n);
    } else {
      const bool leader = elect_one();
      if (leader) {
#pragma unroll
        for (int k = 0; k < 4; k++) mbar_init(sb + BAR_FULL + 8 * k, 2);
        asm volatile("fence.mbarrier_init.release.cluster;" ::: "memory");
      }
      __syncwarp();
      bar_arrive(BAR_INIT0, 160);
      cluster_arrive();
      if (leader) {
#pragma unroll 1
        for (int k = 0; k < 4; k++) {
          const uint32_t fb = sb + BAR_FULL + 8 * k;
          mbar_expect_tx(fb, 16384);
          tma_ld_act(sb + (5 * k + 3) * UNIT, &p.t.xin, fb, 64 * k, m);
          mbar_expect_tx(fb, 3 * UNIT);
          tma_ld3(sb + 5 * k * UNIT, &p.t.wqkv, fb, 128 * n, 64 * k, 0);
          tma_ld3(sb + 5 * k * UNIT + 12288, &p.t.wqkv, fb, 128 * n, 64 * k + 32, 0);
        }
      }
      __syncwarp();
      cluster_wait();
      producer<false>(p, sb, m, n, lane);
    }
  }
}

typedef CUresult (*EncodeFn)(CUtensorMap*, CUtensorMapDataType, cuuint32_t, void*, const cuuint64_t*, const cuuint64_t*,
                             const cuuint32_t*, const cuuint32_t*, CUtensorMapInterleave, CUtensorMapSwizzle,
                             CUtensorMapL2promotion, CUtensorMapFloatOOBfill);

void make_2d(EncodeFn enc, CUtensorMap* m, const void* ptr, uint64_t cols, uint64_t rows, uint32_t box_rows) {
  cuuint64_t d[2] = {cols, rows}, st[1] = {cols * 2};
  cuuint32_t b[2] = {64, box_rows}, e[2] = {1, 1};
  enc(m, CU_TENSOR_MAP_DATA_TYPE_BFLOAT16, 2, const_cast<void*>(ptr), d, st, b, e, CU_TENSOR_MAP_INTERLEAVE_NONE,
      CU_TENSOR_MAP_SWIZZLE_128B, CU_TENSOR_MAP_L2_PROMOTION_L2_128B, CU_TENSOR_MAP_FLOAT_OOB_FILL_NONE);
}
void make_act(EncodeFn enc, CUtensorMap* m, const void* ptr, uint64_t cols, bool split, uint32_t box = 2) {
  const uint64_t row = cols * 2;
  cuuint64_t d[4] = {cols, 32, 2, SEQ / 64}, st[3] = {split ? 2 * row : row, split ? row : 32 * row, 64 * row};
  cuuint32_t b[4] = {64, 32, box, box}, e[4] = {1, 1, 1, 1};
  enc(m, CU_TENSOR_MAP_DATA_TYPE_BFLOAT16, 4, const_cast<void*>(ptr), d, st, b, e, CU_TENSOR_MAP_INTERLEAVE_NONE,
      CU_TENSOR_MAP_SWIZZLE_128B, CU_TENSOR_MAP_L2_PROMOTION_L2_128B, CU_TENSOR_MAP_FLOAT_OOB_FILL_NONE);
}
void make_3d(EncodeFn enc, CUtensorMap* m, const void* ptr, uint64_t d0, uint64_t rows, uint64_t d2, uint64_t row_bytes,
             uint64_t chunk_bytes, uint32_t box_chunks) {
  cuuint64_t d[3] = {d0, rows, d2}, st[2] = {row_bytes, chunk_bytes};
  cuuint32_t b[3] = {64, 32, box_chunks}, e[3] = {1, 1, 1};
  enc(m, CU_TENSOR_MAP_DATA_TYPE_BFLOAT16, 3, const_cast<void*>(ptr), d, st, b, e, CU_TENSOR_MAP_INTERLEAVE_NONE,
      CU_TENSOR_MAP_SWIZZLE_128B, CU_TENSOR_MAP_L2_PROMOTION_L2_128B, CU_TENSOR_MAP_FLOAT_OOB_FILL_NONE);
}

}

extern "C" void kernel_launch(void* const* d_in, const int* in_sizes, int n_in, void* d_out, int out_size) {
  (void)in_sizes; (void)n_in; (void)out_size;
  static EncodeFn enc = nullptr;
  static void *att = nullptr, *hbuf = nullptr, *scratch = nullptr;
  static int by_smid = 0;
  if (!enc) {
    void* fn = nullptr;
    cudaDriverEntryPointQueryResult q;
    cudaGetDriverEntryPoint("cuTensorMapEncodeTiled", &fn, cudaEnableDefault, &q);
    enc = (EncodeFn)fn;
    cudaGetSymbolAddress(&att, g_att);
    cudaGetSymbolAddress(&hbuf, g_h);
    cudaGetSymbolAddress(&scratch, g_scratch);
    cudaFuncSetAttribute(fused_layers_kernel<true>, cudaFuncAttributeMaxDynamicSharedMemorySize, SMEM_BYTES);
    cudaFuncSetAttribute(fused_layers_kernel<false>, cudaFuncAttributeMaxDynamicSharedMemorySize, SMEM_BYTES);
    int sms = 0, clusters = 0, dev = 0;
    cudaGetDevice(&dev);
    cudaDeviceGetAttribute(&sms, cudaDevAttrMultiProcessorCount, dev);
    cudaLaunchConfig_t cfg = {};
    cfg.gridDim = dim3(132);
    cfg.blockDim = dim3(384);
    cfg.dynamicSmemBytes = SMEM_BYTES;
    cudaLaunchAttribute at[1];
    at[0].id = cudaLaunchAttributeClusterDimension;
    at[0].val.clusterDim.x = 2; at[0].val.clusterDim.y = 1; at[0].val.clusterDim.z = 1;
    cfg.attrs = at;
    cfg.numAttrs = 1;
    if (cudaOccupancyMaxActiveClusters(&clusters, fused_layers_kernel<true>, &cfg) != cudaSuccess) (void)cudaGetLastError();
    by_smid = sms == 132 && clusters == 66;
  }
  Maps p;
  Scalars sc;
  make_act(enc, &p.xin, d_in[0], DM, true);
  make_act(enc, &p.out, d_out, DM, true);
  make_act(enc, &p.out_w, d_out, DM, true, 1);
  make_act(enc, &p.att, att, DM, false);
  make_act(enc, &p.h, hbuf, FF, false);
  make_2d(enc, &p.att_st, att, DM, SEQ, 32);
  make_2d(enc, &p.h_st, hbuf, FF, SEQ, 32);
  make_2d(enc, &p.w1c, d_in[4], FF, DM, 32);
  make_3d(enc, &p.wqkv, d_in[1], DM, DM, 3, 3 * DM * 2, DM * 2, 3);
  make_3d(enc, &p.wo, d_in[2], 64, DM, DM / 64, DM * 2, 128, 2);
  make_3d(enc, &p.w1a, d_in[4], 64, DM, FF / 64, FF * 2, 128, 3);
  make_3d(enc, &p.w1b, d_in[4], 64, DM, FF / 64, FF * 2, 128, 2);
  make_3d(enc, &p.w2, d_in[6], 64, FF, DM / 64, DM * 2, 128, 2);
  sc.b1 = (const __nv_bfloat16*)d_in[5];
  sc.b2 = (const __nv_bfloat16*)d_in[7];
  sc.g = (Scratch*)scratch;
  sc.zero = 0;
  if (by_smid) fused_layers_kernel<true><<<132, 384, SMEM_BYTES>>>(sc, p);
  else fused_layers_kernel<false><<<NCTA, 384, SMEM_BYTES>>>(sc, p);
}
```

```cpp
#include <cuda_runtime.h>
#include <cuda_bf16.h>
#include <cuda.h>
#include <stdint.h>

namespace {

constexpr int SEQ = 2048, DM = 1024, FF = 3584;
constexpr int NCTA = 128;
constexpr int NBAR = 5;

constexpr uint32_t RING_UNITS = 20, UNIT = 8192;
constexpr uint32_t OFF_X   = RING_UNITS * UNIT;
constexpr uint32_t OFF_STG = OFF_X + 32768;
constexpr uint32_t OFF_HLP = OFF_STG + 16384;
constexpr uint32_t OFF_RUN = OFF_STG + 24576;
constexpr uint32_t OFF_CSQ = OFF_RUN + 512;
constexpr uint32_t OFF_CSF = OFF_CSQ + 2048;
constexpr uint32_t OFF_ROW = OFF_CSF + 3584;
constexpr uint32_t OFF_BAR = OFF_ROW + 1024;
constexpr uint32_t SMEM_BYTES = OFF_BAR + 384;
constexpr uint32_t BAR_FULL = OFF_BAR, BAR_EMPTY = OFF_BAR + 8 * NBAR;
constexpr uint32_t BAR_XRDY = OFF_BAR + 80;
constexpr uint32_t BAR_DUMMY = OFF_BAR + 96, OFF_TAG = OFF_BAR + 104, OFF_ZERO = OFF_BAR + 112;
constexpr uint32_t BAR_PUB = OFF_BAR + 128;
constexpr uint32_t BAR_CSLD = OFF_BAR + 200;
constexpr uint32_t BAR_BIAS = OFF_BAR + 216;
constexpr uint32_t BAR_XGO = OFF_BAR + 224;

constexpr uint64_t DESC_A = (1ull << 62) | ((uint64_t)(2048 >> 4) << 32) | (1ull << 16);
constexpr uint64_t DESC_B = (1ull << 62) | ((uint64_t)(1024 >> 4) << 32) | ((uint64_t)(4096 >> 4) << 16);

constexpr int BAR_INIT = 0, BAR_ORDER = 1, BAR_GUARD = 3, BAR_WG = 5, BAR_GO = 7, BAR_DONE = 8, BAR_HLP = 9;
constexpr int BAR_INIT0 = 10, BAR_PAIR = 11;

constexpr int WIN1 = 7;
constexpr int WIN0 = 9;
constexpr int SLICE = 0;
constexpr int SKEW = 3;
constexpr int WIN2 = 1;
constexpr int GELU_DEP = 2;
constexpr int STG_WAIT = 5;
constexpr int HALO_NS = 200;
constexpr int STAT_NS = 800;
constexpr int CS_NS = 500;
constexpr int XB_NS = 400;
constexpr int XB_GAP_NS = 50;
constexpr int STAG_NS = 450;
constexpr int PACE_M = 100;
constexpr int PACE_N = 300;

struct Scratch {
  uint4 stats[4 * 8 * SEQ];
  uint4 halo[2 * 2 * 16 * 8 * 384];
  uint4 csp[2 * 8 * 17 * 224];
  uint32_t flags[16 * 32];
  uint32_t epoch[NCTA + 4];
};

struct Maps {
  CUtensorMap xin, out, att, h, wqkv, wo, w1a, w1b, w2, att_st, h_st, w1c, out_w;
};
struct Scalars {
  Scratch* g;
  const __nv_bfloat16 *b1, *b2;
  uint32_t zero;
};
struct Params : Scalars {
  const Maps& t;
};

__device__ __nv_bfloat16 g_att[SEQ * DM];
__device__ __nv_bfloat16 g_h[SEQ * FF];
__device__ Scratch g_scratch;

__device__ __forceinline__ void mbar_init(uint32_t bar, int cnt) {
  asm volatile("mbarrier.init.shared::cta.b64 [%0], %1;" ::"r"(bar), "r"(cnt));
}
__device__ __forceinline__ void mbar_expect_tx(uint32_t bar, uint32_t bytes) {
  asm volatile("mbarrier.arrive.expect_tx.shared::cta.b64 _, [%0], %1;" ::"r"(bar), "r"(bytes) : "memory");
}
__device__ __forceinline__ void mbar_arrive(uint32_t bar) {
  asm volatile("mbarrier.arrive.shared::cta.b64 _, [%0];" ::"r"(bar) : "memory");
}
__device__ __forceinline__ bool mbar_test(uint32_t bar, uint32_t parity) {
  uint32_t ok;
  asm volatile("{\n.reg .pred p;\nmbarrier.test_wait.parity.shared::cta.b64 p, [%1], %2;\nselp.u32 %0, 1, 0, p;\n}"
               : "=r"(ok) : "r"(bar), "r"(parity) : "memory");
  return ok;
}
__device__ __forceinline__ void mbar_wait(uint32_t bar, uint32_t parity) {
  asm volatile(
      "{\n.reg .pred p;\n.reg .u32 it;\nmov.u32 it, 0;\n"
      "WAIT_LOOP:\n"
      "mbarrier.try_wait.parity.shared::cta.b64 p, [%0], %1;\n"
      "@p bra WAIT_DONE;\n"
      "add.u32 it, it, 1;\n"
      "setp.lt.u32 p, it, 0x400000;\n"
      "@p bra WAIT_LOOP;\n"
      "trap;\n"
      "WAIT_DONE:\n}"
      ::"r"(bar), "r"(parity) : "memory");
}
__device__ __forceinline__ void bar_sync(int id, int n) { asm volatile("bar.sync %0, %1;" ::"r"(id), "r"(n) : "memory"); }
__device__ __forceinline__ void bar_arrive(int id, int n) { asm volatile("bar.arrive %0, %1;" ::"r"(id), "r"(n) : "memory"); }
__device__ __forceinline__ void tma_ld2(uint32_t dst, const CUtensorMap* m, uint32_t bar, int c0, int c1) {
  asm volatile("cp.async.bulk.tensor.2d.shared::cluster.global.mbarrier::complete_tx::bytes [%0], [%1, {%3, %4}], [%2];"
               ::"r"(dst), "l"(m), "r"(bar), "r"(c0), "r"(c1) : "memory");
}
__device__ __forceinline__ void tma_ld_act(uint32_t dst, const CUtensorMap* m, uint32_t bar, int col, int blk) {
  asm volatile("cp.async.bulk.tensor.4d.shared::cluster.global.mbarrier::complete_tx::bytes [%0], [%1, {%3, %5, %5, %4}], [%2];"
               ::"r"(dst), "l"(m), "r"(bar), "r"(col), "r"(2 * blk), "r"(0) : "memory");
}
__device__ __forceinline__ void tma_st_act(const CUtensorMap* m, uint32_t src, int col, int blk) {
  asm volatile("cp.async.bulk.tensor.4d.global.shared::cta.bulk_group [%0, {%2, %4, %4, %3}], [%1];"
               ::"l"(m), "r"(src), "r"(col), "r"(2 * blk), "r"(0) : "memory");
}
__device__ __forceinline__ void tma_st_warp(const CUtensorMap* m, uint32_t src, int col, int blk, int w) {
  asm volatile("cp.async.bulk.tensor.4d.global.shared::cta.bulk_group [%0, {%2, %5, %3, %4}], [%1];"
               ::"l"(m), "r"(src), "r"(col), "r"(w & 1), "r"(2 * blk + (w >> 1)), "r"(0) : "memory");
}
__device__ __forceinline__ void tma_ld3(uint32_t dst, const CUtensorMap* m, uint32_t bar, int c0, int c1, int c2) {
  asm volatile("cp.async.bulk.tensor.3d.shared::cluster.global.mbarrier::complete_tx::bytes [%0], [%1, {%3, %4, %5}], [%2];"
               ::"r"(dst), "l"(m), "r"(bar), "r"(c0), "r"(c1), "r"(c2) : "memory");
}
__device__ __forceinline__ void tma_ld3_pair(uint32_t dst, const CUtensorMap* m, uint32_t bar, int c0, int c1, int c2) {
  asm volatile("cp.async.bulk.tensor.3d.shared::cluster.global.mbarrier::complete_tx::bytes.multicast::cluster"
               " [%0], [%1, {%3, %4, %5}], [%2], %6;"
               ::"r"(dst), "l"(m), "r"(bar), "r"(c0), "r"(c1), "r"(c2), "h"((uint16_t)3) : "memory");
}
__device__ __forceinline__ uint32_t pair_offset(uint32_t sb, uint32_t rank) {
  uint32_t r;
  asm volatile("mapa.shared::cluster.u32 %0, %1, %2;" : "=r"(r) : "r"(sb), "r"(rank));
  return r - sb;
}
__device__ __forceinline__ void mbar_arrive_cluster(uint32_t bar) {
  asm volatile("mbarrier.arrive.shared::cluster.b64 _, [%0];" ::"r"(bar) : "memory");
}
__device__ __forceinline__ void cluster_arrive() { asm volatile("barrier.cluster.arrive.relaxed;" ::: "memory"); }
__device__ __forceinline__ void cluster_wait() { asm volatile("barrier.cluster.wait.acquire;" ::: "memory"); }
__device__ __forceinline__ void tma_st2(const CUtensorMap* m, uint32_t src, int c0, int c1) {
  asm volatile("cp.async.bulk.tensor.2d.global.shared::cta.bulk_group [%0, {%2, %3}], [%1];"
               ::"l"(m), "r"(src), "r"(c0), "r"(c1) : "memory");
}
__device__ __forceinline__ void bulk_commit() { asm volatile("cp.async.bulk.commit_group;" ::: "memory"); }
__device__ __forceinline__ void bulk_wait_read() { asm volatile("cp.async.bulk.wait_group.read 0;" ::: "memory"); }
__device__ __forceinline__ void bulk_wait_all() { asm volatile("cp.async.bulk.wait_group 0;" ::: "memory"); }
__device__ __forceinline__ void fence_async_smem() { asm volatile("fence.proxy.async.shared::cta;" ::: "memory"); }
__device__ __forceinline__ void fence_async_global() { asm volatile("fence.proxy.async.global;" ::: "memory"); }
__device__ __forceinline__ void st_relaxed(uint32_t* p, uint32_t v) {
  asm volatile("st.relaxed.gpu.global.u32 [%0], %1;" ::"l"(p), "r"(v) : "memory");
}
__device__ __forceinline__ void st_msg(uint4* p, uint32_t a, uint32_t b, uint32_t c, uint32_t tag) {
  asm volatile("{\n.reg .b128 v;\nmov.b128 v, {%1, %2, %3, %4};\nst.relaxed.gpu.global.b128 [%0], v;\n}"
               ::"l"(p), "r"(a), "r"(b), "r"(c), "r"(tag) : "memory");
}
__device__ __forceinline__ void ld_msg(const uint4* p, uint32_t& a, uint32_t& b, uint32_t& c, uint32_t& tag) {
  asm volatile("{\n.reg .b128 v;\nld.relaxed.gpu.global.b128 v, [%4];\nmov.b128 {%0, %1, %2, %3}, v;\n}"
               : "=r"(a), "=r"(b), "=r"(c), "=r"(tag) : "l"(p) : "memory");
}
__device__ __forceinline__ bool elect_one() {
  uint32_t ok;
  asm volatile("{\n.reg .pred p;\nelect.sync _|p, 0xffffffff;\nselp.u32 %0, 1, 0, p;\n}" : "=r"(ok));
  return ok;
}
__device__ __forceinline__ uint32_t lanemask_lt() {
  uint32_t v;
  asm("mov.u32 %0, %%lanemask_lt;" : "=r"(v));
  return v;
}
__device__ __forceinline__ int uniform(int v) { return __shfl_sync(0xffffffffu, v, 0); }
__device__ __forceinline__ uint32_t pack_bf16(float lo, float hi) {
  uint32_t r;
  asm("cvt.rn.bf16x2.f32 %0, %1, %2;" : "=r"(r) : "f"(hi), "f"(lo));
  return r;
}
__device__ __forceinline__ float prmt_f(uint32_t a, uint32_t sel) {
  float r;
  asm("{\n.reg .b32 t;\nprmt.b32 t, %1, 0, %2;\nmov.b32 %0, t;\n}" : "=f"(r) : "r"(a), "r"(sel));
  return r;
}
__device__ __forceinline__ float bf_lo(uint32_t v) { return __uint_as_float(v << 16); }
__device__ __forceinline__ float bf_hi(uint32_t v) { return __uint_as_float(v & 0xffff0000u); }
__device__ __forceinline__ void stsm4(uint32_t addr, uint32_t r0, uint32_t r1, uint32_t r2, uint32_t r3) {
  asm volatile("stmatrix.sync.aligned.m8n8.x4.shared.b16 [%0], {%1, %2, %3, %4};"
               ::"r"(addr), "r"(r0), "r"(r1), "r"(r2), "r"(r3) : "memory");
}
__device__ __forceinline__ void ldsm4(uint32_t addr, uint32_t& r0, uint32_t& r1, uint32_t& r2, uint32_t& r3) {
  asm volatile("ldmatrix.sync.aligned.m8n8.x4.shared.b16 {%0, %1, %2, %3}, [%4];"
               : "=r"(r0), "=r"(r1), "=r"(r2), "=r"(r3) : "r"(addr) : "memory");
}
__device__ __forceinline__ uint32_t movtrans(uint32_t a) {
  uint32_t d;
  asm volatile("movmatrix.sync.aligned.m8n8.trans.b16 %0, %1;" : "=r"(d) : "r"(a));
  return d;
}
__device__ __forceinline__ void mma16816(float (&c)[4], uint32_t a0, uint32_t a1, uint32_t a2, uint32_t a3, uint32_t b0, uint32_t b1) {
  asm volatile("mma.sync.aligned.m16n8k16.row.col.f32.bf16.bf16.f32 {%0,%1,%2,%3}, {%4,%5,%6,%7}, {%8,%9}, {%0,%1,%2,%3};"
               : "+f"(c[0]), "+f"(c[1]), "+f"(c[2]), "+f"(c[3])
               : "r"(a0), "r"(a1), "r"(a2), "r"(a3), "r"(b0), "r"(b1));
}
__device__ __forceinline__ void mma1688(float (&c)[4], uint32_t a0, uint32_t a1, uint32_t b0) {
  asm volatile("mma.sync.aligned.m16n8k8.row.col.f32.bf16.bf16.f32 {%0,%1,%2,%3}, {%4,%5}, {%6}, {%0,%1,%2,%3};"
               : "+f"(c[0]), "+f"(c[1]), "+f"(c[2]), "+f"(c[3]) : "r"(a0), "r"(a1), "r"(b0));
}
__device__ __forceinline__ float2 lds_f2(uint32_t a) {
  float2 v;
  asm volatile("ld.shared.v2.f32 {%0, %1}, [%2];" : "=f"(v.x), "=f"(v.y) : "r"(a) : "memory");
  return v;
}
__device__ __forceinline__ float4 lds_f4(uint32_t a) {
  float4 v;
  asm volatile("ld.shared.v4.f32 {%0, %1, %2, %3}, [%4];" : "=f"(v.x), "=f"(v.y), "=f"(v.z), "=f"(v.w) : "r"(a) : "memory");
  return v;
}
__device__ __forceinline__ float lds_f(uint32_t a) {
  float v;
  asm volatile("ld.shared.f32 %0, [%1];" : "=f"(v) : "r"(a) : "memory");
  return v;
}
__device__ __forceinline__ uint32_t lds_u(uint32_t a) {
  uint32_t v;
  asm volatile("ld.shared.u32 %0, [%1];" : "=r"(v) : "r"(a) : "memory");
  return v;
}
__device__ __forceinline__ void sts_f2(uint32_t a, float x, float y) {
  asm volatile("st.shared.v2.f32 [%0], {%1, %2};" ::"r"(a), "f"(x), "f"(y) : "memory");
}
__device__ __forceinline__ void sts_u4(uint32_t a, uint32_t x, uint32_t y, uint32_t z, uint32_t w) {
  asm volatile("st.shared.v4.u32 [%0], {%1, %2, %3, %4};" ::"r"(a), "r"(x), "r"(y), "r"(z), "r"(w) : "memory");
}
__device__ __forceinline__ void lds_u4(uint32_t a, uint32_t& x, uint32_t& y, uint32_t& z, uint32_t& w) {
  asm volatile("ld.shared.v4.u32 {%0, %1, %2, %3}, [%4];" : "=r"(x), "=r"(y), "=r"(z), "=r"(w) : "r"(a) : "memory");
}
__device__ __forceinline__ float ex2(float x) {
  float y;
  asm("ex2.approx.ftz.f32 %0, %1;" : "=f"(y) : "f"(x));
  return y;
}
__device__ __forceinline__ float rcp_hw(float x) {
  float y;
  asm("rcp.approx.ftz.f32 %0, %1;" : "=f"(y) : "f"(x));
  return y;
}
__device__ __forceinline__ float tanh_hw(float x) {
  float y;
  asm("tanh.approx.f32 %0, %1;" : "=f"(y) : "f"(x));
  return y;
}
__device__ __forceinline__ float quad_sum(float v) {
  v += __shfl_xor_sync(0xffffffffu, v, 1);
  return v + __shfl_xor_sync(0xffffffffu, v, 2);
}
__device__ __forceinline__ float quad_max(float v) {
  v = fmaxf(v, __shfl_xor_sync(0xffffffffu, v, 1));
  return fmaxf(v, __shfl_xor_sync(0xffffffffu, v, 2));
}

template <int N> __device__ __forceinline__ void wgmma_ss(float (&d)[96], uint64_t da, uint64_t db, uint32_t keep = 1);
template <> __device__ __forceinline__ void wgmma_ss<128>(float (&d)[96], uint64_t da, uint64_t db, uint32_t keep) {
  asm volatile(
      "{\n.reg .pred p;\nsetp.ne.u32 p, %66, 0;\n"
      "wgmma.mma_async.sync.aligned.m64n128k16.f32.bf16.bf16 {%0, %1, %2, %3, %4, %5, %6, %7, %8, %9, %10, %11, %12, %13, %14, %15, %16, %17, %18, %19, %20, %21, %22, %23, %24, %25, %26, %27, %28, %29, %30, %31, %32, %33, %34, %35, %36, %37, %38, %39, %40, %41, %42, %43, %44, %45, %46, %47, %48, %49, %50, %51, %52, %53, %54, %55, %56, %57, %58, %59, %60, %61, %62, %63}, %64, %65, p, 1, 1, 0, 1;\n}"
      : "+f"(d[0]), "+f"(d[1]), "+f"(d[2]), "+f"(d[3]), "+f"(d[4]), "+f"(d[5]), "+f"(d[6]), "+f"(d[7]), "+f"(d[8]), "+f"(d[9]), "+f"(d[10]), "+f"(d[11]), "+f"(d[12]), "+f"(d[13]), "+f"(d[14]), "+f"(d[15]), "+f"(d[16]), "+f"(d[17]), "+f"(d[18]), "+f"(d[19]), "+f"(d[20]), "+f"(d[21]), "+f"(d[22]), "+f"(d[23]), "+f"(d[24]), "+f"(d[25]), "+f"(d[26]), "+f"(d[27]), "+f"(d[28]), "+f"(d[29]), "+f"(d[30]), "+f"(d[31]), "+f"(d[32]), "+f"(d[33]), "+f"(d[34]), "+f"(d[35]), "+f"(d[36]), "+f"(d[37]), "+f"(d[38]), "+f"(d[39]), "+f"(d[40]), "+f"(d[41]), "+f"(d[42]), "+f"(d[43]), "+f"(d[44]), "+f"(d[45]), "+f"(d[46]), "+f"(d[47]), "+f"(d[48]), "+f"(d[49]), "+f"(d[50]), "+f"(d[51]), "+f"(d[52]), "+f"(d[53]), "+f"(d[54]), "+f"(d[55]), "+f"(d[56]), "+f"(d[57]), "+f"(d[58]), "+f"(d[59]), "+f"(d[60]), "+f"(d[61]), "+f"(d[62]), "+f"(d[63])
      : "l"(da), "l"(db), "r"(keep));
}

template <> __device__ __forceinline__ void wgmma_ss<192>(float (&d)[96], uint64_t da, uint64_t db, uint32_t keep) {
  asm volatile(
      "{\n.reg .pred p;\nsetp.ne.u32 p, %98, 0;\n"
      "wgmma.mma_async.sync.aligned.m64n192k16.f32.bf16.bf16 {%0, %1, %2, %3, %4, %5, %6, %7, %8, %9, %10, %11, %12, %13, %14, %15, %16, %17, %18, %19, %20, %21, %22, %23, %24, %25, %26, %27, %28, %29, %30, %31, %32, %33, %34, %35, %36, %37, %38, %39, %40, %41, %42, %43, %44, %45, %46, %47, %48, %49, %50, %51, %52, %53, %54, %55, %56, %57, %58, %59, %60, %61, %62, %63, %64, %65, %66, %67, %68, %69, %70, %71, %72, %73, %74, %75, %76, %77, %78, %79, %80, %81, %82, %83, %84, %85, %86, %87, %88, %89, %90, %91, %92, %93, %94, %95}, %96, %97, p, 1, 1, 0, 1;\n}"
      : "+f"(d[0]), "+f"(d[1]), "+f"(d[2]), "+f"(d[3]), "+f"(d[4]), "+f"(d[5]), "+f"(d[6]), "+f"(d[7]), "+f"(d[8]), "+f"(d[9]), "+f"(d[10]), "+f"(d[11]), "+f"(d[12]), "+f"(d[13]), "+f"(d[14]), "+f"(d[15]), "+f"(d[16]), "+f"(d[17]), "+f"(d[18]), "+f"(d[19]), "+f"(d[20]), "+f"(d[21]), "+f"(d[22]), "+f"(d[23]), "+f"(d[24]), "+f"(d[25]), "+f"(d[26]), "+f"(d[27]), "+f"(d[28]), "+f"(d[29]), "+f"(d[30]), "+f"(d[31]), "+f"(d[32]), "+f"(d[33]), "+f"(d[34]), "+f"(d[35]), "+f"(d[36]), "+f"(d[37]), "+f"(d[38]), "+f"(d[39]), "+f"(d[40]), "+f"(d[41]), "+f"(d[42]), "+f"(d[43]), "+f"(d[44]), "+f"(d[45]), "+f"(d[46]), "+f"(d[47]), "+f"(d[48]), "+f"(d[49]), "+f"(d[50]), "+f"(d[51]), "+f"(d[52]), "+f"(d[53]), "+f"(d[54]), "+f"(d[55]), "+f"(d[56]), "+f"(d[57]), "+f"(d[58]), "+f"(d[59]), "+f"(d[60]), "+f"(d[61]), "+f"(d[62]), "+f"(d[63]), "+f"(d[64]), "+f"(d[65]), "+f"(d[66]), "+f"(d[67]), "+f"(d[68]), "+f"(d[69]), "+f"(d[70]), "+f"(d[71]), "+f"(d[72]), "+f"(d[73]), "+f"(d[74]), "+f"(d[75]), "+f"(d[76]), "+f"(d[77]), "+f"(d[78]), "+f"(d[79]), "+f"(d[80]), "+f"(d[81]), "+f"(d[82]), "+f"(d[83]), "+f"(d[84]), "+f"(d[85]), "+f"(d[86]), "+f"(d[87]), "+f"(d[88]), "+f"(d[89]), "+f"(d[90]), "+f"(d[91]), "+f"(d[92]), "+f"(d[93]), "+f"(d[94]), "+f"(d[95])
      : "l"(da), "l"(db), "r"(keep));
}

template <int R>
__device__ __forceinline__ void pin_regs(float (&a)[2][96]) {
#pragma unroll
  for (int m = 0; m < 2; m++)
#pragma unroll
    for (int i = 0; i < R; i++) asm volatile("" : "+f"(a[m][i])::"memory");
}

struct Ctx {
  uint32_t sb;
  int m, n, wg, w, lane;
};
__device__ __forceinline__ Ctx make_ctx(uint32_t sb, int id) {
  int lane;
  asm volatile("mov.u32 %0, %%laneid;" : "=r"(lane));
  asm volatile("" : "+r"(id), "+r"(sb));
  return Ctx{sb, (id >> 3) & 15, id & 7, id >> 9, (id >> 7) & 3, lane};
}
#define UNPACK_CTX(c) const uint32_t sb = c.sb; const int m = c.m, n = c.n, wg = c.wg, w = c.w, lane = c.lane

__device__ __forceinline__ uint32_t poll_line(const uint32_t* word, uint32_t target, uint32_t need) {
  uint32_t v;
  asm volatile(
      "{\n.reg .pred p;\n.reg .u32 it, m;\n.reg .s32 d;\nmov.u32 it, 0;\n"
      "POLL_LOOP:\n"
      "ld.relaxed.gpu.global.u32 %0, [%1];\n"
      "sub.s32 d, %0, %2;\n"
      "setp.ge.s32 p, d, 0;\n"
      "vote.sync.ballot.b32 m, p, 0xffffffff;\n"
      "and.b32 m, m, %3;\n"
      "setp.eq.u32 p, m, %3;\n"
      "@p bra.uni POLL_DONE;\n"
      "add.u32 it, it, 1;\n"
      "setp.lt.u32 p, it, 0x400000;\n"
      "@p bra.uni POLL_LOOP;\n"
      "trap;\n"
      "POLL_DONE:\n}"
      : "=&r"(v) : "l"(word), "r"(target), "r"(need) : "memory");
  return v;
}
__device__ __forceinline__ uint32_t ld_relaxed(const uint32_t* p) {
  uint32_t v;
  asm volatile("ld.relaxed.gpu.global.u32 %0, [%1];" : "=r"(v) : "l"(p) : "memory");
  return v;
}
__device__ __forceinline__ float chain(float x, uint32_t on, uint32_t zero) {
  return __uint_as_float(__float_as_uint(x) | (on & zero));
}
constexpr int MSG_SPINS = 1 << 20;

constexpr int STAGES_PER_LAYER = 152;
__device__ __forceinline__ int nib(uint64_t v, int i) { return (int)(v >> (4 * i)) & 15; }
__device__ __forceinline__ bool tile_wide(int t) { return (0x23 >> t) & 1; }
__device__ __forceinline__ void weight_coords(const Params& p, int t, int n, const CUtensorMap*& map, int& c0, int& c2) {
  map = &p.t.wqkv + nib(0x4233100ull, t);
  c0 = t < 2 ? 128 * n + 64 * t : 0;
  c2 = t < 2 ? 0 : (t == 2 || t == 6) ? 2 * n : 7 * n + 2 * t - 6;
}

template <bool IS_A>
__device__ __forceinline__ void producer(const Params& p, uint32_t sb, int m, int n, int lane) {
  const uint32_t low = (1u << (4 * n)) - 1, others = (0x6543210u & low) | (0x7654321u & ~low);
  const uint64_t order_x = (uint64_t)(others * 2 + 0x1111111u) << 36 | (uint64_t)others * 2 << 8 | (n * 0x22 + 0x10);
  int inflight = 4, cur = 0;
  uint32_t fb = sb + BAR_FULL + 32, rb = sb + BAR_EMPTY, rph = 0, pos = 0, tag32 = 0, seen = 0;
  const uint32_t fend = sb + BAR_FULL + 8 * NBAR, rend = sb + BAR_EMPTY + 8 * NBAR;
  const uint32_t* word = p.g->flags + m * 32 + (lane < 16 ? lane >> 1 : lane & 7);
#pragma unroll 1
  for (int sg = 1; sg < 22; sg++) {
    const int layer = sg >= 11, s = sg == 1 ? 2 : sg == 2 ? 1 : sg - 11 * layer;
    const int t = nib(0x65434321010ull, s), kind = nib(0x32110031100ull, s);
    const bool wide = tile_wide(t);
    const uint32_t bbytes = wide ? 3 * UNIT : 2 * UNIT, base = sb + (IS_A ? bbytes : (m & 1) * (bbytes / 2));
    if (IS_A && kind == 0) {
      if (sg == 2) seen = tag32 = (__ldcg(p.g->epoch + m * 8 + n) + 1) << 5;
#pragma unroll 1
      for (int k = 0; k < 2; k++) {
#pragma unroll 1
        for (; inflight > (wide ? 3 : 4); inflight--) {
          mbar_wait(rb, rph);
          rb += 8;
          if (rb == rend) { rb -= 8 * NBAR; rph ^= 1; }
        }
        if (elect_one()) mbar_arrive(fb);
        inflight++;
        fb += 8;
        if (fb == fend) fb -= 8 * NBAR;
        pos += bbytes + 2 * UNIT;
        if (pos >= RING_UNITS * UNIT) pos -= RING_UNITS * UNIT;
      }
      continue;
    }
    const int mul = t == 6 ? 448 : t == 2 ? 128 : 64, count = sg == 1 ? 12 : 2 * nib(0x4871ull, kind);
    uint64_t order0 = sg == 1 ? 0xFEDCBA987654ull : kind == 3 ? 0x76543210u : order_x >> (8 * (kind & 1));
    uint32_t special = (s == 4 || s == 10) ? 0x10 : s == 9 ? 0xF : s == 0;
    if (IS_A) special |= (kind & 1 ? 0 : 3) | (count >= 4 ? 1u << (count - 4) : 0);
    if (s >= 9) pos = (s + 6) * UNIT;
    const CUtensorMap* map;
    int c0 = 0, c2 = 0, ev = 0;
    if (IS_A) {
      map = &p.t.xin + (t == 2 ? 2 : t == 6 ? 3 : sg >= 4);
      ev = 9 * layer + (t < 2 ? 0 : t == 2 ? 1 : t < 6 ? 4 : 5);
      if (elect_one()) asm volatile("prefetch.tensormap [%0];" ::"l"(map) : "memory");
    } else {
      weight_coords(p, t, n, map, c0, c2);
    }
#pragma unroll 1
    for (int add = 0; add < mul; add += 64) {
      uint64_t order = order0;
      const int need = kind == 3 ? ev : ev - 1 + (lane & 1), sh = kind == 3 ? 16 : 0;
      uint32_t ready = IS_A ? __ballot_sync(0xffffffffu, cur >= need) >> sh : 0;
#pragma unroll 1
      for (int k = 0; k < count; k++) {
        const int code = order & 15, kc = code * mul + add;
        order >>= 4;
        if ((special >> k) & 1) {
          const int lag = wide ? (s == 9 && k == 2 ? 2 : 3) : ((s == 4 || s == 10) && add == 0 && k < 4) ? 3 : 4;
#pragma unroll 1
          for (; inflight > lag; inflight--) {
            mbar_wait(rb, rph);
            rb += 8;
            if (rb == rend) { rb -= 8 * NBAR; rph ^= 1; }
          }
          inflight++;
          if (IS_A) {
            if (kind == 3 ? t == 2 && add + k == 64 : !(kind & 1) && k < 2) {
              if (t == 2) mbar_wait(sb + BAR_PUB + 8, layer);
              if (elect_one()) mbar_arrive(fb);
              goto next_stage;
            }
            if (k == count - 4 && sg >= 3) seen = ld_relaxed(word);
          }
        } else {
          mbar_wait(rb, rph);
          rb += 8;
          if (rb == rend) { rb -= 8 * NBAR; rph ^= 1; }
        }
        if (IS_A && !((ready >> code) & 1)) {
          cur = max(cur, (int)(seen - tag32));
          ready = __ballot_sync(0xffffffffu, cur >= need) >> sh;
          if (!((ready >> code) & 1)) {
            cur = (int)(poll_line(word, tag32 + need, 1u << (code + sh)) - tag32);
            ready = __ballot_sync(0xffffffffu, cur >= need) >> sh;
          }
          asm volatile("fence.acquire.gpu;" ::: "memory");
          fence_async_global();
          seen = ld_relaxed(word);
        }
        if (elect_one()) {
          if (!IS_A) tma_ld3_pair(base + pos, map, fb, c0, kc + 32 * (m & 1), c2);
          else tma_ld_act(base + pos, map, fb, kc, m);
          mbar_expect_tx(fb, IS_A ? 16384 : bbytes);
        }
      next_stage:
        fb += 8;
        if (fb == fend) fb -= 8 * NBAR;
        pos += bbytes + 2 * UNIT;
        if (pos >= RING_UNITS * UNIT) pos -= RING_UNITS * UNIT;
      }
      special = !IS_A ? 0 : t == 2 ? 1 : add == 128 ? 0x10 : 0;
      if (t == 2) order0 = others << 4 | n;
      if (IS_A && (t == 2 || add == 64 || add == 192)) ev++;
    }
  }
}

__device__ __forceinline__ void publisher(const Params& p, uint32_t sb, int m, int n) {
  {
    const int ts = PACE_M * m, tx = PACE_N * n;
#pragma unroll 1
    for (int k = 0; k < 2; k++) {
      __nanosleep(k == 0 ? min(ts, tx) : abs(ts - tx));
      if ((ts <= tx) == (k == 0)) {
        mbar_expect_tx(sb + BAR_CSLD, 24576);
        tma_ld3(sb + OFF_STG, &p.t.wqkv, sb + BAR_CSLD, 128 * n, 64 * m, 0);
        tma_ld3(sb + OFF_STG + 12288, &p.t.wqkv, sb + BAR_CSLD, 128 * n, 64 * m + 32, 0);
      } else {
#pragma unroll 1
        for (int h = 0; h < 2; h++) {
          const uint32_t xr = sb + BAR_XRDY + 8 * h;
          mbar_expect_tx(xr, 16384);
          tma_ld_act(sb + OFF_X + h * 16384, &p.t.xin, xr, 128 * n + 64 * h, m);
          asm volatile("mbarrier.arrive.shared::cta.b64 _, [%0], 3;" ::"r"(xr) : "memory");
        }
      }
    }
  }
  const uint32_t tag = __ldcg(p.g->epoch + m * 8 + n) + 1;
  uint32_t* word = p.g->flags + m * 32 + n;
  st_relaxed(word, 32 * tag);
#pragma unroll 1
  for (int c = 0; c < 16; c++) {
    const int e = c >= 9 ? c - 9 : c;
    if (e == 2 || e == 7) {
      asm volatile("prefetch.tensormap [%0];" ::"l"(&p.t.out) : "memory");
      mbar_wait(sb + BAR_XRDY, e == 2);
      tma_st_act(&p.t.out, sb + OFF_X, 128 * n, m);
      bulk_commit();
      mbar_wait(sb + BAR_XRDY + 8, e == 2);
      bulk_wait_all();
      mbar_arrive(sb + BAR_XGO);
    } else {
      mbar_wait(sb + BAR_PUB + 8 * e, c >= 9);
    }
    asm volatile("fence.release.gpu;" ::: "memory");
    asm volatile("red.relaxed.gpu.global.add.u32 [%0], 1;" ::"l"(word) : "memory");
  }
  p.g->epoch[m * 8 + n] = tag;
}

__device__ __forceinline__ void sum_rows(uint32_t buf, int iters, float (&a)[8], int lane) {
  uint32_t addr = buf + (lane >> 3) * 128 + (((lane & 7) ^ (lane >> 3)) << 4);
#pragma unroll 1
  for (int it = 0; it < iters; it++) {
    uint32_t u[2][4];
    lds_u4(addr, u[0][0], u[0][1], u[0][2], u[0][3]);
    lds_u4((addr ^ 64) + 512, u[1][0], u[1][1], u[1][2], u[1][3]);
    addr += 1024;
#pragma unroll
    for (int e = 0; e < 8; e++) { a[2 * (e & 3)] += bf_lo(u[e >> 2][e & 3]); a[2 * (e & 3) + 1] += bf_hi(u[e >> 2][e & 3]); }
  }
}
__device__ __forceinline__ void publish_sums(const float (&a)[8], uint4* dst, int lane, uint32_t tag) {
  const bool u8 = lane & 8, u16 = lane & 16;
  float h4[4], h2[2];
#pragma unroll
  for (int e = 0; e < 4; e++) h4[e] = (u8 ? a[4 + e] : a[e]) + __shfl_xor_sync(0xffffffffu, u8 ? a[e] : a[4 + e], 8);
#pragma unroll
  for (int e = 0; e < 2; e++) h2[e] = (u16 ? h4[2 + e] : h4[e]) + __shfl_xor_sync(0xffffffffu, u16 ? h4[e] : h4[2 + e], 16);
  st_msg(dst + (lane & 7) * 4 + (u8 ? 2 : 0) + (u16 ? 1 : 0), __float_as_uint(h2[0]), __float_as_uint(h2[1]), 0u, tag);
}

__device__ __forceinline__ void colsum_helper(const Params& p, uint32_t sb, int m, int n, int lane) {
  const uint32_t tag = __ldcg(p.g->epoch + m * 8 + n) + 1;
#pragma unroll 1
  for (int k = lane; k < 288; k += 32) {
    const uint32_t bb = __ldg(reinterpret_cast<const uint32_t*>(k < 224 ? p.b1 + 448 * n : p.b2 + 128 * n - 448) + k);
    const float sc = k < 224 ? 0.5f : 1.f;
    sts_f2(sb + (k < 224 ? OFF_CSF + k * 16 + 8 : OFF_CSQ + 1536 + (k - 224) * 8), sc * bf_lo(bb), sc * bf_hi(bb));
  }
  __syncwarp();
  if (elect_one()) mbar_arrive(sb + BAR_BIAS);
  bar_sync(BAR_HLP, 160);
  {
    uint4* base = p.g->csp + n * 17 * 224 + 12 * m + min(lane & 15, 11);
    float s0 = 0.f, s1 = 0.f;
#pragma unroll 1
    for (int g = 0; g < 2; g++) {
      uint32_t x[4], y[4];
#pragma unroll 1
      for (int it = 0; it < MSG_SPINS; it++) {
        uint32_t bad = 0, z, tg;
        if (g == 0 || it > 0) __nanosleep(CS_NS);
#pragma unroll
        for (int k = 0; k < 4; k++) { ld_msg(base + (g * 8 + (lane >> 4) * 4 + k) * 224, x[k], y[k], z, tg); bad |= tg ^ tag; }
        if (__all_sync(0xffffffffu, bad == 0)) break;
      }
#pragma unroll
      for (int k = 0; k < 4; k++) { s0 += __uint_as_float(x[k]); s1 += __uint_as_float(y[k]); }
    }
    s0 += __shfl_xor_sync(0xffffffffu, s0, 16);
    s1 += __shfl_xor_sync(0xffffffffu, s1, 16);
    if (lane < 12) st_msg(base + 16 * 224, __float_as_uint(s0), __float_as_uint(s1), 0u, tag);
  }
#pragma unroll 1
  for (int c = 0; c < 7; c++) {
    float a[8] = {0.f, 0.f, 0.f, 0.f, 0.f, 0.f, 0.f, 0.f};
#pragma unroll 1
    for (int h = 0; h < 2; h++) {
      if (elect_one()) {
        mbar_expect_tx(sb + BAR_CSLD + 8, 4096);
        tma_ld2(sb + OFF_HLP, &p.t.w1c, sb + BAR_CSLD + 8, 448 * n + 64 * c, 64 * m + 32 * h);
        if (c < 6) asm volatile("cp.async.bulk.prefetch.tensor.2d.L2.global [%0, {%1, %2}];" ::"l"(&p.t.w1c), "r"(448 * n + 64 * c + 64), "r"(64 * m + 32 * h) : "memory");
      }
      mbar_wait(sb + BAR_CSLD + 8, h);
      sum_rows(sb + OFF_HLP, 4, a, lane);
      __syncwarp();
    }
    publish_sums(a, p.g->csp + ((8 + n) * 17 + m) * 224 + c * 32, lane, tag);
  }
  if (elect_one()) {
#pragma unroll 1
    for (int k = 0; k < 3; k++) {
      mbar_wait(sb + BAR_XGO, k & 1);
      __nanosleep(XB_NS);
#pragma unroll 1
      for (int w = 0; w < 4; w++) {
        tma_st_warp(&p.t.out_w, sb + OFF_X + 16384 + w * 4096, 128 * n + 64, m, w);
        bulk_commit();
        bulk_wait_read();
        if (w < 3) __nanosleep(XB_GAP_NS);
      }
      bulk_wait_all();
      asm volatile("mbarrier.arrive.shared::cta.b64 _, [%0], 4;" ::"r"(sb + BAR_PUB + (k & 1 ? 64 : 24)) : "memory");
    }
  }
}

__device__ __forceinline__ void poll_msgs2(const uint4* pa, const uint4* pb, float (&v)[4], uint32_t tag) {
#pragma unroll 1
  for (int it = 0; it < MSG_SPINS; it++) {
    uint32_t x[4], z, ta, tb;
    ld_msg(pa, x[0], x[1], z, ta);
    ld_msg(pb, x[2], x[3], z, tb);
#pragma unroll
    for (int e = 0; e < 4; e++) v[e] = __uint_as_float(x[e]);
    if (__all_sync(0xffffffffu, ta == tag && tb == tag)) break;
  }
}
__device__ __forceinline__ void colsum_total(const Params& p, const Ctx& cx, int mat, uint32_t tag) {
  uint4* base = p.g->csp + (mat * 8 + cx.n) * 17 * 224;
  const int per = 12 + 2 * mat, k = 2 * cx.w + (cx.lane >> 4), ia = per * cx.m + k, ib = per * cx.m + min(k + 8, per - 1);
  float v[4];
  poll_msgs2(base + (cx.lane & 15) * 224 + ia, base + (cx.lane & 15) * 224 + ib, v, tag);
#pragma unroll 1
  for (int d = 1; d < 16; d *= 2)
#pragma unroll
    for (int e = 0; e < 4; e++) v[e] += __shfl_xor_sync(0xffffffffu, v[e], d);
  const bool hi = cx.lane & 1;
  if ((cx.lane & 14) == 0) st_msg(base + 16 * 224 + (hi ? ib : ia), __float_as_uint(hi ? v[2] : v[0]), __float_as_uint(hi ? v[3] : v[1]), 0u, tag);
}
__device__ __forceinline__ void colsum_gather(const Params& p, const Ctx& cx, int mat, uint32_t tag) {
  const uint4* base = p.g->csp + ((mat * 8 + cx.n) * 17 + 16) * 224;
  const int ia = cx.w * 32 + cx.lane, ib = min(ia + 128, 191 + 32 * mat);
  float v[4];
  poll_msgs2(base + ia, base + ib, v, tag);
  const uint32_t tab = cx.sb + (mat ? OFF_CSF : OFF_CSQ);
  sts_f2(tab + (ia << (3 + mat)), v[0], v[1]);
  sts_f2(tab + (ib << (3 + mat)), v[2], v[3]);
}

#define ACC(q, j, e) acc[(q) & 1][4 * (j) + 2 * ((q) >> 1) + (e)]

constexpr uint32_t RING16 = RING_UNITS * (UNIT >> 4);
__device__ __forceinline__ bool tile_split(int i) { return (0xD98 >> i) & 1; }

__device__ __forceinline__ void write_run_desc(uint32_t sb, int i, int step) {
  const int layer = i >= 7, t = i - 7 * layer, part = tile_split(i) ? step : 2;
  const bool wide = tile_wide(t), own = t != 2 && t != 6 && part != 1 && i != 0, second = t == 1 || t == 4;
  const uint32_t z16 = (wide ? 5 : 4) * (UNIT >> 4), a_off = z16 - 1024 + (uint32_t)DESC_A - (uint32_t)DESC_B;
  const int gl = 16 * t + (part == 2 ? 0 : second ? 16 * part - 14 : 4 * part), g0 = layer * STAGES_PER_LAYER + gl;
  const uint32_t s16 = (sb & 0x3FFFF) >> 4, bfirst = (uint32_t)DESC_B + s16;
  const int nkb = t == 6 ? 56 : part == 0 ? 2 : 12 + 2 * part;
  const bool win1 = t == 1 && part != 0;
  const int win = layer ? WIN1 : WIN0;
  const int run = win1 ? win + 1 : t == 2 ? WIN2 + 1 : nkb;
  const int rest = win1 ? 64 | (nkb - 1 - SKEW - win) : t == 2 ? 64 | (7 - WIN2) | (8 << 7) : 0;
  const uint32_t blo = bfirst + z16 * (wide ? (gl + (t == 5 ? 3 : 0)) & 3 : (gl + 3) % 5);
  const uint32_t alo = own ? (uint32_t)DESC_A + s16 + (OFF_X >> 4) : blo + a_off;
  const uint32_t aoff = own ? alo + 1024 - (blo == bfirst + RING16 - z16 ? bfirst : blo + z16) : a_off;
  const bool xwait = part == 0 && !second, keep = !(part == 0 || t == 5);
  sts_u4(sb + OFF_RUN + (2 * i + step) * 16, blo, alo, aoff,
         ((g0 / NBAR) & 1) | xwait << 1 | keep << 2 | 8 * (g0 % NBAR) | run << 6 | rest << 12);
}

__device__ __forceinline__ void write_partial_stats(const Params& p, const Ctx& c, int ln, uint32_t tag) {
  const uint32_t xrow = c.sb + OFF_X + c.w * 4096 + c.lane * 128;
  float s = 0.f, q = 0.f, s1 = 0.f, q1 = 0.f;
#pragma unroll 4
  for (int j = 0; j < 16; j++) {
    uint32_t u[4];
    lds_u4(xrow + (j >> 3) * 16384 + (((j & 7) ^ (c.lane & 7)) << 4), u[0], u[1], u[2], u[3]);
#pragma unroll
    for (int e = 0; e < 4; e++) {
      const float a = bf_lo(u[e]), d = bf_hi(u[e]);
      s += a; q = fmaf(a, a, q);
      s1 += d; q1 = fmaf(d, d, q1);
    }
  }
  s += s1;
  q += q1;
  st_msg(p.g->stats + (ln * 8 + c.n) * SEQ + 128 * c.m + 32 * c.w + c.lane, __float_as_uint(s),
         __float_as_uint(fmaxf(q - s * s * (1.f / 128.f), 0.f)), 0u, tag);
}

template <int QMASK, int J0 = 0, int J1 = 24>
__device__ __forceinline__ void rank1_update(const Params& p, float (&acc)[2][96], const Ctx& cx, int t) {
  float nm[4];
#pragma unroll
  for (int q = 0; q < 4; q++)
    if ((QMASK >> q) & 1) nm[q] = t == 6 ? 1.f : -lds_f(cx.sb + OFF_ROW + (32 * cx.w + 8 * q + (cx.lane >> 2)) * 8 + 4);
  const uint32_t ctab = cx.sb + OFF_CSQ + ((t & 3) * 192 + 2 * (cx.lane & 3)) * 4;
#pragma unroll
  for (int j = J0; j < J1; j++) {
    const float2 cs = lds_f2(ctab + j * 32);
#pragma unroll
    for (int q = 0; q < 4; q++) {
      if (!((QMASK >> q) & 1)) continue;
      const int k = 4 * j + q - 1;
      const float nq = QMASK == 15 && k >= 0 ? chain(nm[q], __float_as_uint(ACC(k & 3, k >> 2, 1)), p.zero) : nm[q];
      ACC(q, j, 0) = fmaf(nq, cs.x, ACC(q, j, 0));
      ACC(q, j, 1) = fmaf(nq, cs.y, ACC(q, j, 1));
    }
  }
}

template <int QMASK, int SEC>
__device__ __forceinline__ void pack_qkv(const float (&acc)[2][96], uint32_t (&F)[3][4][8]) {
#pragma unroll
  for (int q = 3; q >= 0; q--)
#pragma unroll
    for (int j = 0; j < 8; j++) {
      if (!((QMASK >> q) & 1)) continue;
      const uint32_t u = pack_bf16(ACC(q, 8 * SEC + j, 0), ACC(q, 8 * SEC + j, 1));
      F[SEC][q][j] = SEC == 2 ? movtrans(u) : u;
    }
}
template <int K0, int K1>
__device__ __forceinline__ void send_halo(const Params& p, const uint32_t (&F)[3][4][8], const Ctx& cx, int layer, int t) {
  uint32_t E[18];
#pragma unroll
  for (int j = 0; j < 8; j++) { E[j] = F[1][3][j]; E[8 + j] = F[2][3][j]; }
  if (cx.w < 2) {
#pragma unroll
    for (int k = K0; k < K1; k++)
      if (k < 4) sts_u4(cx.sb + OFF_STG + cx.w * 2048 + cx.lane * 16 + k * 512, E[4 * k], E[4 * k + 1], E[4 * k + 2], E[4 * k + 3]);
  } else {
    uint4* dst = p.g->halo + (((layer * 2 + t) * 16 + cx.m) * 8 + cx.n) * 384 + (cx.w & 1) * 192 + cx.lane;
    const uint32_t tag = lds_u(cx.sb + OFF_TAG);
    if (K1 == 6) {
      const float4 r = lds_f4(cx.sb + OFF_ROW + (32 * cx.w + 24 + 2 * (cx.lane & 3)) * 8);
      E[16] = __float_as_uint(r.x);
      E[17] = __float_as_uint(r.z);
    }
#pragma unroll
    for (int k = K0; k < K1; k++) st_msg(dst + k * 32, E[3 * k], E[3 * k + 1], E[3 * k + 2], tag);
  }
}

__device__ __forceinline__ void attn_scores(const uint32_t* qa, const uint32_t* qb, const uint32_t* kp, const uint32_t* ka,
                                            const uint32_t* kb, float (&l)[4], const float4& zero, const bool (&early)[2]) {
  float s[3][4];
#pragma unroll
  for (int x = 0; x < 3; x++) {
    const uint32_t* kk = x == 0 ? kp : x == 1 ? ka : kb;
    asm volatile("mma.sync.aligned.m16n8k16.row.col.f32.bf16.bf16.f32 {%0,%1,%2,%3}, {%4,%5,%6,%7}, {%8,%9}, {%10,%11,%12,%13};"
                 : "=f"(s[x][0]), "=f"(s[x][1]), "=f"(s[x][2]), "=f"(s[x][3])
                 : "r"(qa[0]), "r"(qb[0]), "r"(qa[1]), "r"(qb[1]), "r"(kk[0]), "r"(kk[1]), "f"(zero.x), "f"(zero.y),
                   "f"(zero.z), "f"(zero.w));
  }
#pragma unroll
  for (int x = 0; x < 3; x++) {
    const uint32_t* kk = x == 0 ? kp : x == 1 ? ka : kb;
    mma16816(s[x], qa[2], qb[2], qa[3], qb[3], kk[2], kk[3]);
  }
#pragma unroll
  for (int e = 0; e < 2; e++) {
    l[e] = early[e] ? s[0][e] : s[1][e];
    l[2 + e] = early[e] ? s[1][2 + e] : s[2][2 + e];
  }
}

__device__ __forceinline__ void attn_mix(const float (&l)[4], const float (&sc)[4], const float (&off)[4], const float (&rk)[4],
                                         const uint32_t* vp, const uint32_t* va, const uint32_t* vb, float (&o)[4][4],
                                         float (&sum)[2], uint32_t mask, uint32_t zero) {
  float x[4];
#pragma unroll
  for (int e = 0; e < 4; e++) x[e] = fmaf(l[e], sc[e], off[e]);
  const float ml = quad_max(fmaxf(x[0], x[1])), mh = quad_max(fmaxf(x[2], x[3]));
  x[0] = ex2(x[0] - ml); x[1] = ex2(x[1] - ml);
  x[2] = ex2(x[2] - mh); x[3] = ex2(x[3] - mh);
  sum[0] = rcp_hw(quad_sum(x[0] + x[1]));
  sum[1] = rcp_hw(quad_sum(x[2] + x[3]));
  const uint32_t pl = pack_bf16(x[0] * rk[0], x[1] * rk[1]), ph = pack_bf16(x[2] * rk[2], x[3] * rk[3]);
  const uint32_t a0 = pl & ~mask, a1 = ph & mask, a2 = pl & zero, a3 = ph & ~mask, c0 = pl & mask, c1 = ph & zero;
#pragma unroll
  for (int jn = 0; jn < 4; jn++) {
    o[jn][0] = o[jn][1] = o[jn][2] = o[jn][3] = 0.f;
    mma16816(o[jn], a0, a1, a2, a3, va[jn], vb[jn]);
  }
#pragma unroll
  for (int jn = 0; jn < 4; jn++) mma1688(o[jn], c0, c1, vp[jn]);
}

template <int t>
__device__ __forceinline__ void attn_epilogue(const Params& p, float (&acc)[2][96], uint32_t (&F)[3][4][8], const Ctx& cx, int layer, uint32_t tag) {
  UNPACK_CTX(cx);
  const uint32_t ktab = sb + OFF_ROW + (32 * w + 2 * (lane & 3)) * 8, exc = sb + OFF_STG + (w & 1) * 2048 + lane * 16;
  uint4* const halo = p.g->halo + (((layer * 2 + t) * 16 + m) * 8 + n) * 384 + (w & 1) * 192;
  (void)wg;
  uint32_t(&Q)[4][8] = F[0], (&K)[4][8] = F[1], (&V)[4][8] = F[2], P[18];
  float kr[5][2], qr[4];
  bar_arrive(BAR_PAIR + w, 64);
  if (layer == 0 && t == 1) {
    rank1_update<7, 8, 24>(p, acc, cx, 1);
    rank1_update<31, 0, 8>(p, acc, cx, 1);
  }
#pragma unroll
  for (int q = 0; q < 4; q++) {
    qr[q] = lds_f(sb + OFF_ROW + (32 * w + 8 * q + (lane >> 2)) * 8) * (0.17677669529663687f * 1.4426950408889634f);
    const float4 r = lds_f4(ktab + 64 * q);
    kr[1 + q][0] = r.x;
    kr[1 + q][1] = r.z;
  }
  pack_qkv<7, 1>(acc, F);
  uint32_t tg[6];
#pragma unroll
  for (int k = 0; k < 6; k++) {
    tg[k] = ~tag;
    if (t == 1)
      asm volatile("{\n.reg .b128 v;\n.reg .pred g;\nsetp.ne.u32 g, %5, 0;\nmov.b128 v, {%6, %6, %6, %6};\n"
                   "@g ld.relaxed.gpu.global.b128 v, [%4];\nmov.b128 {%0, %1, %2, %3}, v;\n}"
                   : "=r"(P[3 * k]), "=r"(P[3 * k + 1]), "=r"(P[3 * k + 2]), "=r"(tg[k])
                   : "l"(halo - 8 * 384 + k * 32 + lane), "r"((uint32_t)(w < 2 && m > 0) | ((K[0][7] | K[1][7] | K[2][7]) & p.zero)), "r"(~tag) : "memory");
  }
  pack_qkv<7, 2>(acc, F);
  pack_qkv<15, 0>(acc, F);
  bar_sync(BAR_PAIR + (w ^ 2), 64);
  if (w >= 2 || m == 0) {
#pragma unroll
    for (int k = 0; k < 4; k++) lds_u4(exc + k * 512, P[4 * k], P[4 * k + 1], P[4 * k + 2], P[4 * k + 3]);
    const float4 r = lds_f4(ktab - (w >> 1) * 320);
    P[16] = __float_as_uint(r.x);
    P[17] = __float_as_uint(r.z);
  } else {
    if ((m & 1) && t == 0) __nanosleep(HALO_NS);
#pragma unroll 1
    for (int it = 0; it < MSG_SPINS; it++) {
      if (t == 0 || it > 0) {
        if (it > 0 || !(m & 1)) poll_line(reinterpret_cast<const uint32_t*>(halo - 8 * 384 + 191) + 3, tag, 1u);
#pragma unroll
        for (int k = 0; k < 6; k++) ld_msg(halo - 8 * 384 + k * 32 + lane, P[3 * k], P[3 * k + 1], P[3 * k + 2], tg[k]);
      }
      uint32_t bad = 0;
#pragma unroll
      for (int k = 0; k < 6; k++) bad |= tg[k] ^ tag;
      if (__all_sync(0xffffffffu, bad == 0)) break;
    }
  }
  kr[0][0] = __uint_as_float(P[16]);
  kr[0][1] = __uint_as_float(P[17]);
  const bool early[2] = {2 * (lane & 3) > (lane >> 2), 2 * (lane & 3) + 1 > (lane >> 2)};
  const uint32_t mask = (early[0] ? 0xffffu : 0u) | (early[1] ? 0xffff0000u : 0u);
  float rk[2][4], sc[2][4], off[2][4];
#pragma unroll
  for (int g = 0; g < 2; g++) {
#pragma unroll
    for (int e = 0; e < 4; e++) {
      const int q = 2 * g + (e >> 1);
      const bool masked = q == 0 && m == 0 && w < 2 && early[e & 1];
      rk[g][e] = early[e & 1] ? kr[q][e & 1] : kr[q + 1][e & 1];
      sc[g][e] = masked ? 0.f : rk[g][e] * qr[q];
      off[g][e] = masked ? -1e30f : 0.f;
    }
  }
  if (w == 0 && elect_one()) asm volatile("prefetch.tensormap [%0];" ::"l"(&p.t.att_st) : "memory");
  bar_sync(BAR_GO, 256);
  const float4 zero = lds_f4(sb + OFF_ZERO);
  float l[2][2][4], o[2][2][4][4], sum[2][2][2];
#pragma unroll
  for (int h = 0; h < 2; h++) {
    if (h == 1) {
      Q[2][4] |= __float_as_uint(l[1][0][0]) & p.zero;
      Q[0][4] |= __float_as_uint(l[0][0][0]) & p.zero;
    }
    attn_scores(&Q[2][4 * h], &Q[3][4 * h], &K[1][4 * h], &K[2][4 * h], &K[3][4 * h], l[1][h], zero, early);
    attn_scores(&Q[0][4 * h], &Q[1][4 * h], &P[4 * h], &K[0][4 * h], &K[1][4 * h], l[0][h], zero, early);
  }
  const uint32_t stg = sb + OFF_STG + w * 4096, srow = stg + lane * 128 + ((lane & 7) << 4);
#pragma unroll
  for (int h = 0; h < 2; h++) {
    attn_mix(l[1][h], sc[1], off[1], rk[1], &V[1][4 * h], &V[2][4 * h], &V[3][4 * h], o[1][h], sum[1][h], mask, p.zero);
    attn_mix(l[0][h], sc[0], off[0], rk[0], &P[8 + 4 * h], &V[0][4 * h], &V[1][4 * h], o[0][h], sum[0][h], mask, p.zero);
#pragma unroll
    for (int j = 0; j < 4; j++) {
      const float(&a)[4] = o[0][h][j];
      const float(&c)[4] = o[1][h][j];
      stsm4(srow ^ ((4 * h + j) << 4), pack_bf16(a[0] * sum[0][h][0], a[1] * sum[0][h][0]), pack_bf16(a[2] * sum[0][h][1], a[3] * sum[0][h][1]),
            pack_bf16(c[0] * sum[1][h][0], c[1] * sum[1][h][0]), pack_bf16(c[2] * sum[1][h][1], c[3] * sum[1][h][1]));
    }
  }
  bar_arrive(BAR_DONE, 256);
  fence_async_smem();
  __syncwarp();
  if (lane == 0) {
    tma_st2(&p.t.att_st, stg, 128 * n + 64 * t, 128 * m + 32 * w);
    bulk_commit();
  }
}

__device__ __forceinline__ void finish_stores(uint32_t sb, int i) {
  const int t = i >= 7 ? i - 7 : i;
  if ((threadIdx.x & 31) == 0) {
    bulk_wait_all();
    mbar_arrive(sb + BAR_PUB + 8 * (t < 2 ? t : t + 1));
  }
  __syncwarp();
  if (i < 12) bar_arrive(BAR_GUARD + ((i & 1) ^ 1), 256);
}

template <int N>
__device__ __forceinline__ bool mainloop(const Params& p, float (&acc)[2][96], uint32_t sb, int i, int step, int mn) {
  constexpr uint32_t Z16 = (2 + N / 64) * (UNIT >> 4);
  constexpr uint32_t A_OFF = Z16 - 1024 + (uint32_t)DESC_A - (uint32_t)DESC_B;
  const int wg = i & 1;
  const uint32_t s16 = (sb & 0x3FFFF) >> 4;
  const uint32_t blast = (uint32_t)DESC_B + s16 + RING16 - Z16, flast = sb + BAR_FULL + 8 * (NBAR - 1);
  uint32_t blo = (uint32_t)DESC_B + s16, alo = blo + A_OFF, aoff = A_OFF, misc = 16 << 6;
  if (N == 128 || i > 0) lds_u4(sb + OFF_RUN + (2 * i + step) * 16, blo, alo, aoff, misc);
  uint32_t keep = misc & 4;
  int run = (misc >> 6) & 63, rest = misc >> 12;
  uint32_t fb = sb + BAR_FULL + (misc & 0x38), ph = misc & 1;
  uint32_t prev = sb + BAR_DUMMY - 8 * NBAR;
  const uint32_t lane_id = __popc(__ballot_sync(0xffffffffu, true) & lanemask_lt()), rel = pair_offset(sb, lane_id & 1) + 8 * NBAR;
  pin_regs<N / 2>(acc);
  if (N == 128 || i > 0) bar_sync(BAR_ORDER + wg, 256);
  else bar_sync(BAR_INIT0, 160);
  mbar_wait(fb, ph);
  if (N == 192 && i == 0) cluster_wait();
  if (misc & 2) mbar_wait(sb + BAR_XGO, N == 192);
#pragma unroll 1
  while (true) {
    const uint64_t da = (DESC_A & ~0xffffffffull) | alo, db = (DESC_B & ~0xffffffffull) | blo;
    asm volatile("wgmma.fence.sync.aligned;" ::: "memory");
    wgmma_ss<N>(acc[0], da, db, keep);
    wgmma_ss<N>(acc[1], da + 64, db, keep);
    keep = 4;
    wgmma_ss<N>(acc[0], da + 2, db + 128);
    wgmma_ss<N>(acc[1], da + 66, db + 128);
    asm volatile("wgmma.commit_group.sync.aligned;" ::: "memory");
    asm volatile("wgmma.wait_group.sync.aligned 1;" ::: "memory");
    if (lane_id < 2) mbar_arrive_cluster(prev + rel);
    prev = fb;
    if (fb == flast) { fb -= 8 * NBAR; ph++; }
    fb += 8;
    if (blo == blast) blo -= RING16;
    blo += Z16;
    alo = blo + aoff;
    aoff = A_OFF;
    run--;
    const bool ready = mbar_test(fb, ph) && run != 0;
    asm volatile("wgmma.fence.sync.aligned;" ::: "memory");
    wgmma_ss<N>(acc[0], da + 4, db + 4 * N);
    wgmma_ss<N>(acc[1], da + 68, db + 4 * N);
    wgmma_ss<N>(acc[0], da + 6, db + 4 * N + 128);
    wgmma_ss<N>(acc[1], da + 70, db + 4 * N + 128);
    asm volatile("wgmma.commit_group.sync.aligned;" ::: "memory");
    if (!ready) {
      bool window = false;
      if (run == 0) {
        if (rest == 0) break;
        window = rest & 64;
        if (window) bar_arrive(BAR_GO, 256);
        else alo = (uint32_t)DESC_A + s16 + (OFF_STG >> 4);
        run = rest & 63;
        rest >>= 7;
      }
      mbar_wait(fb, ph);
      if (window) bar_sync(BAR_DONE, 256);
    }
  }
  if constexpr (N == 192) {
    if (misc >> 12) {
      const Ctx cx = make_ctx(sb, mn);
      uint32_t F[3][4][8];
      const uint32_t fb0 = fb, blo0 = blo;
#pragma unroll 1
      for (int x = 0; x < SKEW; x++) {
        const uint64_t da = (DESC_A & ~0xffffffffull) | (blo + A_OFF + 64), db = (DESC_B & ~0xffffffffull) | blo;
        mbar_wait(fb, ph);
        asm volatile("wgmma.fence.sync.aligned;" ::: "memory");
#pragma unroll
        for (int k = 0; k < 4; k++) wgmma_ss<N>(acc[1], da + 2 * k, db + (k >> 1) * 4 * N + (k & 1) * 128);
        asm volatile("wgmma.commit_group.sync.aligned;" ::: "memory");
        asm volatile("wgmma.wait_group.sync.aligned 1;" ::: "memory");
        if (x == 0) {
          if (lane_id < 2) mbar_arrive_cluster(prev + rel);
          bar_sync(BAR_GUARD + wg, 256);
        }
        if (fb == flast) { fb -= 8 * NBAR; ph++; }
        fb += 8;
        blo += Z16;
      }
      fb = fb0;
#pragma unroll
      for (int u = 0; u < 2 * SKEW; u++) {
        const uint64_t da = (DESC_A & ~0xffffffffull) | (blo0 + (u >> 1) * Z16 + A_OFF + 4 * (u & 1));
        const uint64_t db = (DESC_B & ~0xffffffffull) | (blo0 + (u >> 1) * Z16 + 4 * N * (u & 1));
        asm volatile("wgmma.fence.sync.aligned;" ::: "memory");
        wgmma_ss<N>(acc[0], da, db);
        wgmma_ss<N>(acc[0], da + 2, db + 128);
        asm volatile("wgmma.commit_group.sync.aligned;" ::: "memory");
        if (u == 2 * SKEW - 1) break;
        asm volatile("wgmma.wait_group.sync.aligned 1;" ::: "memory");
        if (u == 0) {
#pragma unroll
          for (int r = 0; r < 96; r++) asm volatile("" : "+f"(acc[1][r])::"memory");
        }
        if (u == 2 || u == 4) {
          if (lane_id < 2) mbar_arrive_cluster(fb + rel);
          fb = fb == flast ? fb - 8 * (NBAR - 1) : fb + 8;
        }
        if (SLICE == 0) {
          if (u == 0) { if (i == 1) rank1_update<8, 8, 24>(p, acc, cx, 1); pack_qkv<8, 2>(acc, F); pack_qkv<8, 1>(acc, F); }
          if (u == 1) send_halo<0, 3>(p, F, cx, i >= 7, 1);
          if (u == 2) send_halo<3, 6>(p, F, cx, i >= 7, 1);
        } else {
          if (u == 0) { if (i == 1) rank1_update<8, 16, 24>(p, acc, cx, 1); pack_qkv<8, 2>(acc, F); }
          if (u == 1) { if (i == 1) rank1_update<8, 8, 16>(p, acc, cx, 1); pack_qkv<8, 1>(acc, F); }
          if (u == 2) send_halo<0, 2>(p, F, cx, i >= 7, 1);
          if (u == 3) send_halo<2, 4>(p, F, cx, i >= 7, 1);
          if (u == 4) send_halo<4, 6>(p, F, cx, i >= 7, 1);
        }
      }
      bar_arrive(BAR_ORDER + (wg ^ 1), 256);
      asm volatile("wgmma.wait_group.sync.aligned 0;" ::: "memory");
#pragma unroll
      for (int r = 0; r < 96; r++) asm volatile("" : "+f"(acc[0][r])::"memory");
      if (lane_id < 2) mbar_arrive_cluster(fb + rel);
      attn_epilogue<1>(p, acc, F, cx, i >= 7, lds_u(sb + OFF_TAG));
      finish_stores(sb, i);
#pragma unroll
      for (int r = 0; r < 192; r++)
        asm volatile("{\n.reg .b32 t;\nxor.b32 t, %1, %2;\nmov.b32 %0, t;\n}" : "=f"(acc[r & 1][r >> 1]) : "r"(lane_id), "r"(r + 64));
      return true;
    }
  }
  if (i < 13) bar_arrive(BAR_ORDER + (wg ^ 1), 256);
  if (N == 128 && ((0x2244 >> i) & 1)) {
    const Ctx cx = make_ctx(sb, mn);
    const uint32_t xrow = cx.sb + OFF_X + cx.w * 4096 + cx.lane * 128 + ((cx.lane & 7) << 4);
    const bool leader = elect_one();
    asm volatile("wgmma.wait_group.sync.aligned 0;" ::: "memory");
    pin_regs<64>(acc);
#pragma unroll
    for (int h = 0; h < 2; h++) {
      if (h == 1 && p.zero != 0) break;
#pragma unroll
      for (int j = 8 * h; j < 8 * h + 8; j++)
        stsm4((xrow ^ ((j & 7) << 4)) + h * 16384, pack_bf16(ACC(0, j, 0), ACC(0, j, 1)), pack_bf16(ACC(1, j, 0), ACC(1, j, 1)),
              pack_bf16(ACC(2, j, 0), ACC(2, j, 1)), pack_bf16(ACC(3, j, 0), ACC(3, j, 1)));
      fence_async_smem();
      __syncwarp();
      if (leader) {
        mbar_arrive(sb + BAR_XRDY + 8 * h);
        if (i == 13) {
          tma_st_warp(&p.t.out_w, cx.sb + OFF_X + h * 16384 + cx.w * 4096, 128 * cx.n + 64 * h, cx.m, cx.w);
          bulk_commit();
          if (h == 1) bulk_wait_read();
        }
      }
      if (h == 0 && lane_id < 2 && i < 13) mbar_arrive_cluster(prev + rel);
    }
    if (i == 2 || i == 9) write_partial_stats(p, cx, (i + 3) >> 2, lds_u(sb + OFF_TAG));
    return true;
  }
  asm volatile("wgmma.wait_group.sync.aligned 0;" ::: "memory");
  pin_regs<N / 2>(acc);
  if (lane_id < 2) mbar_arrive_cluster(prev + rel);
  return false;
}

__device__ __forceinline__ void finish_row_stats(const Params& p, const Ctx& c, int ln, uint32_t tag) {
  const uint4* src = p.g->stats + ln * 8 * SEQ + 128 * c.m + 32 * c.w + c.lane;
  uint32_t ps[8], pm[8];
#pragma unroll 1
  for (int it = 0; it < MSG_SPINS; it++) {
    uint32_t bad = 0, u, tg;
    if (ln == 2 || it > 0) __nanosleep(STAT_NS);
#pragma unroll
    for (int k = 0; k < 8; k++) { ld_msg(src + k * SEQ, ps[k], pm[k], u, tg); bad |= tg ^ tag; }
    if (__all_sync(0xffffffffu, bad == 0)) break;
  }
  float s = 0.f, m2 = 0.f;
#pragma unroll
  for (int k = 0; k < 8; k++) s += __uint_as_float(ps[k]);
  const float mean = s * (1.f / DM);
#pragma unroll
  for (int k = 0; k < 8; k++) {
    const float d = __uint_as_float(ps[k]) * (1.f / 128.f) - mean;
    m2 += fmaf(128.f * d, d, __uint_as_float(pm[k]));
  }
  sts_f2(c.sb + OFF_ROW + (32 * c.w + c.lane) * 8, rsqrtf(m2 * (1.f / DM) + 1e-5f), mean);
  __syncwarp();
}

__device__ __forceinline__ void gelu_epilogue(const Params& p, float (&acc)[2][96], const Ctx& cx, int t) {
  UNPACK_CTX(cx);
  (void)wg;
  float rs[4], rm[4];
#pragma unroll
  for (int q = 0; q < 4; q++) {
    const float2 v = lds_f2(sb + OFF_ROW + (32 * w + 8 * q + (lane >> 2)) * 8);
    rs[q] = 0.5f * v.x;
    rm[q] = -rs[q] * v.y;
  }
  const int col0 = 128 * (t - 3);
  const uint32_t stg = sb + OFF_STG + w * 4096;
  const uint32_t ctab = sb + OFF_CSF + (col0 / 2 + (lane & 3)) * 16, srow = stg + lane * 128 + ((lane & 7) << 4);
  if (t == 5) __nanosleep(STAG_NS * w);
  float4 nb = lds_f4(ctab);
#pragma unroll
  for (int c = 0; c < 3; c++) {
    if (c == 2 && t != 5) break;
    uint32_t hp[8][4];
#pragma unroll
    for (int j = 0; j < 8; j++) {
      const float4 cb = nb;
      if (8 * c + j < 23) nb = lds_f4(ctab + (8 * c + j + 1) * 64);
#pragma unroll
      for (int q = 0; q < 4; q++) {
        float y[2];
        const int k = 4 * j + q - GELU_DEP;
        const float rmq = k >= 0 ? chain(rm[q], hp[k >> 2][k & 3], p.zero) : rm[q];
#pragma unroll
        for (int e = 0; e < 2; e++) {
          const float z = fmaf(ACC(q, 8 * c + j, e), rs[q], fmaf(rmq, e ? cb.y : cb.x, e ? cb.w : cb.z));
          const float u = z * fmaf(z * z, 8.f * 0.7978845608028654f * 0.044715f, 2.f * 0.7978845608028654f);
          y[e] = fmaf(z, tanh_hw(u), z);
        }
        hp[j][q] = pack_bf16(y[0], y[1]);
      }
      if (j == STG_WAIT && c > 0) {
        if (lane == 0) bulk_wait_read();
        __syncwarp();
      }
      if (c == 0 || j > STG_WAIT) {
        stsm4(srow ^ (j << 4), hp[j][0], hp[j][1], hp[j][2], hp[j][3]);
      } else if (j == STG_WAIT) {
#pragma unroll
        for (int jj = 0; jj <= STG_WAIT; jj++) stsm4(srow ^ (jj << 4), hp[jj][0], hp[jj][1], hp[jj][2], hp[jj][3]);
      }
    }
    fence_async_smem();
    __syncwarp();
    if (lane == 0) {
      tma_st2(&p.t.h_st, stg, 448 * n + col0 + 64 * c, 128 * m + 32 * w);
      bulk_commit();
    }
  }
#pragma unroll
  for (int r = 0; r < 16; r++) acc[0][r] = acc[1][r] = 0.f;
}

__device__ __forceinline__ bool consumer_tile(const Params& p, float (&acc)[2][96], uint32_t sb0, int i, int mn) {
  const int layer = i >= 7, t = i - 7 * layer, wg = i & 1;
  const bool resid = t == 2 || t == 6;
  {
    if (resid) {
      const Ctx cx = make_ctx(sb0, mn);
      const uint32_t xrow = cx.sb + OFF_X + cx.w * 4096 + cx.lane * 128;
      const uint32_t sel_lo = 0x1044u | p.zero, sel_hi = 0x3244u | p.zero;
#pragma unroll
      for (int j = 0; j < 16; j++) {
        uint32_t r[4];
        ldsm4(xrow + (j >> 3) * 16384 + (((j & 7) ^ (cx.lane & 7)) << 4), r[0], r[1], r[2], r[3]);
#pragma unroll
        for (int q = 0; q < 4; q++) {
          ACC(q, j, 0) = prmt_f(r[q], sel_lo);
          ACC(q, j, 1) = prmt_f(r[q], sel_hi);
        }
      }
    }
    if (t >= 5 || i == 7) finish_stores(sb0, i - 2);
#pragma unroll 1
    for (int step = !tile_split(i);; step++) {
      if (step == 1 && (t == 1 || t == 4)) {
        const Ctx cx = make_ctx(sb0, mn);
        if (i == 1) {
          const uint32_t epoch = __ldcg(p.g->epoch + (mn & 127));
          cluster_wait();
          asm volatile("st.shared.u32 [%0], %1;" ::"r"(sb0 + OFF_TAG), "r"(epoch + 1) : "memory");
        }
        const uint32_t tag = lds_u(cx.sb + OFF_TAG);
        const int ln = (i + 1) >> 2;
#pragma unroll 1
        for (int r = 0; r < 2; r++) {
          if (i == 1) {
            if (cx.w < 3) {
              float a[8] = {0.f, 0.f, 0.f, 0.f, 0.f, 0.f, 0.f, 0.f};
              mbar_wait(sb0 + BAR_CSLD, r);
#pragma unroll 1
              for (int h = 0; h < 2; h++) sum_rows(cx.sb + OFF_STG + h * 12288 + cx.w * 4096, 4, a, cx.lane);
              publish_sums(a, p.g->csp + (cx.n * 17 + cx.m) * 224 + (3 * r + cx.w) * 32, cx.lane, tag);
            }
          }
          if (r == 1) break;
          if (i == 1) {
            bar_sync(BAR_WG + 1, 128);
            if (cx.w == 3 && elect_one()) {
              mbar_expect_tx(sb0 + BAR_CSLD, 24576);
              tma_ld3(sb0 + OFF_STG, &p.t.wqkv, sb0 + BAR_CSLD, 128 * cx.n + 64, 64 * cx.m, 0);
              tma_ld3(sb0 + OFF_STG + 12288, &p.t.wqkv, sb0 + BAR_CSLD, 128 * cx.n + 64, 64 * cx.m + 32, 0);
            }
            mbar_wait(sb0 + BAR_XRDY, 0);
            mbar_wait(sb0 + BAR_XRDY + 8, 0);
          }
          if (t == 1) write_partial_stats(p, cx, ln, tag);
        }
        if (i == 1) {
          bar_arrive(BAR_HLP, 160);
          bar_sync(BAR_INIT, 160);
        }
        if (i == 4) colsum_total(p, cx, 1, tag);
        if (i != 1) bar_sync(BAR_GUARD + wg, 256);
        finish_row_stats(p, cx, ln, tag);
        if (i == 4) {
          colsum_gather(p, cx, 1, tag);
          mbar_wait(sb0 + BAR_BIAS, 0);
        }
        bar_arrive(BAR_GUARD + (wg ^ 1), 256);
      }
      if (step == 2) bar_sync(BAR_GUARD + wg, 256);
      if (step == 2 && i == 0) {
        colsum_gather(p, make_ctx(sb0, mn), 0, lds_u(sb0 + OFF_TAG));
        bar_sync(BAR_WG, 128);
      }
      if ((t + step == 2 && i != 1) || t == 6) rank1_update<15>(p, acc, make_ctx(sb0, mn), t);
      if (step == 2) break;
      if (tile_wide(t)) {
        if (mainloop<192>(p, acc, sb0, i, step, mn)) return false;
      } else {
        if (mainloop<128>(p, acc, sb0, i, step, mn)) return false;
      }
    }
    if (t < 2) return true;
    gelu_epilogue(p, acc, make_ctx(sb0, mn), t);
    return false;
  }
}

template <bool BY_SMID>
__global__ void __cluster_dims__(2, 1, 1) __launch_bounds__(384, 1)
fused_layers_kernel(const Scalars scalars, const __grid_constant__ Maps maps) {
  if (threadIdx.x == 288 || threadIdx.x == 320)
    asm volatile("prefetch.tensormap [%0];" ::"l"(threadIdx.x == 288 ? &maps.xin : &maps.wqkv) : "memory");
  const Params p{scalars, maps};
  extern __shared__ __align__(1024) uint8_t smem_raw[];
  const uint32_t sb = uniform((uint32_t)__cvta_generic_to_shared(smem_raw));
  const int tid = threadIdx.x, lane = tid & 31, warp = uniform(tid >> 5), wg = warp >> 2, w = warp & 3;

  int mn;
  {
    int id = blockIdx.x;
    if (BY_SMID) asm volatile("mov.u32 %0, %%smid;" : "=r"(id));
    else if (id >= 120) id += 4;
    const int c = id >> 1;
    int g, j;
    if (c < 32) { g = c & 7; j = c >> 3; }
    else if (c < 60) { g = 1 + (c - 32) % 7; j = 4 + (c - 32) / 7; }
    else { g = 0; j = c - 58; }
    mn = (g * 2 + (blockIdx.x & 1)) * 8 + j;
    if (c == 60 || c == 61) {
      if (tid < 32) {
        const uint32_t tag = __ldcg(p.g->epoch + NCTA + (id & 3)) + 1;
#pragma unroll 1
        for (int mm = 0; mm < 16; mm++) poll_line(p.g->flags + mm * 32 + (lane & 7), 32 * tag, 0xffu);
        if (tid == 0) p.g->epoch[NCTA + (id & 3)] = tag;
      }
      return;
    }
  }
  const int m = mn >> 3, n = mn & 7;
  if (wg < 2) {
    cluster_arrive();
    asm volatile("setmaxnreg.inc.sync.aligned.u32 232;");
    const int id = mn | (warp << 7);
#pragma unroll 1
    for (int i = wg;; i += 2) {
      float acc[2][96];
#pragma unroll
      for (int r = 0; r < 96; r++) acc[0][r] = acc[1][r] = 0.f;
      pin_regs<96>(acc);
#pragma unroll 1
      while (!consumer_tile(p, acc, sb, i, id)) {
        i += 2;
        if (i >= 14) goto all_done;
      }
      const Ctx cx = make_ctx(sb, id);
      uint32_t F[3][4][8];
      pack_qkv<8, 2>(acc, F);
      pack_qkv<8, 1>(acc, F);
      send_halo<0, 6>(p, F, cx, i >= 7, 0);
      attn_epilogue<0>(p, acc, F, cx, i >= 7, lds_u(sb + OFF_TAG));
      finish_stores(sb, i);
    }
  all_done:
    if (wg == 0) {
      finish_stores(sb, 12);
    } else {
      cluster_arrive();
      cluster_wait();
    }
  } else {
    asm volatile("setmaxnreg.dec.sync.aligned.u32 40;");
    if (w != 0) {
      if (w == 1 && elect_one()) {
        mbar_init(sb + BAR_FULL + 32, 2);
#pragma unroll
        for (int k = 0; k < NBAR; k++) mbar_init(sb + BAR_EMPTY + 8 * k, 8);
#pragma unroll
        for (int k = 0; k < 3; k++) mbar_init(sb + BAR_XRDY + 8 * k, 4);
#pragma unroll
        for (int k = 0; k < 9; k++) mbar_init(sb + BAR_PUB + 8 * k, 4);
#pragma unroll
        for (int k = 0; k < 4; k++) mbar_init(sb + BAR_CSLD + 8 * k, 1);
        sts_f2(sb + OFF_ZERO, 0.f, 0.f);
        sts_f2(sb + OFF_ZERO + 8, 0.f, 0.f);
        asm volatile("fence.mbarrier_init.release.cluster;" ::: "memory");
      }
      __syncwarp();
      cluster_arrive();
      if (w == 2) {
        if (lane < 28) write_run_desc(sb, lane >> 1, lane & 1);
        bar_arrive(BAR_INIT, 160);
      }
      cluster_wait();
      if (w == 1) producer<true>(p, sb, m, n, lane);
      else if (w == 3) colsum_helper(p, sb, m, n, lane);
      else if (elect_one()) publisher(p, sb, m, n);
    } else {
      const bool leader = elect_one();
      if (leader) {
#pragma unroll
        for (int k = 0; k < 4; k++) mbar_init(sb + BAR_FULL + 8 * k, 2);
        asm volatile("fence.mbarrier_init.release.cluster;" ::: "memory");
      }
      __syncwarp();
      bar_arrive(BAR_INIT0, 160);
      cluster_arrive();
      if (leader) {
#pragma unroll 1
        for (int k = 0; k < 4; k++) {
          const uint32_t fb = sb + BAR_FULL + 8 * k;
          mbar_expect_tx(fb, 16384);
          tma_ld_act(sb + (5 * k + 3) * UNIT, &p.t.xin, fb, 64 * k, m);
          mbar_expect_tx(fb, 3 * UNIT);
          tma_ld3(sb + 5 * k * UNIT, &p.t.wqkv, fb, 128 * n, 64 * k, 0);
          tma_ld3(sb + 5 * k * UNIT + 12288, &p.t.wqkv, fb, 128 * n, 64 * k + 32, 0);
        }
      }
      __syncwarp();
      cluster_wait();
      producer<false>(p, sb, m, n, lane);
    }
  }
}

typedef CUresult (*EncodeFn)(CUtensorMap*, CUtensorMapDataType, cuuint32_t, void*, const cuuint64_t*, const cuuint64_t*,
                             const cuuint32_t*, const cuuint32_t*, CUtensorMapInterleave, CUtensorMapSwizzle,
                             CUtensorMapL2promotion, CUtensorMapFloatOOBfill);

void make_2d(EncodeFn enc, CUtensorMap* m, const void* ptr, uint64_t cols, uint64_t rows, uint32_t box_rows) {
  cuuint64_t d[2] = {cols, rows}, st[1] = {cols * 2};
  cuuint32_t b[2] = {64, box_rows}, e[2] = {1, 1};
  enc(m, CU_TENSOR_MAP_DATA_TYPE_BFLOAT16, 2, const_cast<void*>(ptr), d, st, b, e, CU_TENSOR_MAP_INTERLEAVE_NONE,
      CU_TENSOR_MAP_SWIZZLE_128B, CU_TENSOR_MAP_L2_PROMOTION_L2_128B, CU_TENSOR_MAP_FLOAT_OOB_FILL_NONE);
}
void make_act(EncodeFn enc, CUtensorMap* m, const void* ptr, uint64_t cols, bool split, uint32_t box = 2) {
  const uint64_t row = cols * 2;
  cuuint64_t d[4] = {cols, 32, 2, SEQ / 64}, st[3] = {split ? 2 * row : row, split ? row : 32 * row, 64 * row};
  cuuint32_t b[4] = {64, 32, box, box}, e[4] = {1, 1, 1, 1};
  enc(m, CU_TENSOR_MAP_DATA_TYPE_BFLOAT16, 4, const_cast<void*>(ptr), d, st, b, e, CU_TENSOR_MAP_INTERLEAVE_NONE,
      CU_TENSOR_MAP_SWIZZLE_128B, CU_TENSOR_MAP_L2_PROMOTION_L2_128B, CU_TENSOR_MAP_FLOAT_OOB_FILL_NONE);
}
void make_3d(EncodeFn enc, CUtensorMap* m, const void* ptr, uint64_t d0, uint64_t rows, uint64_t d2, uint64_t row_bytes,
             uint64_t chunk_bytes, uint32_t box_chunks) {
  cuuint64_t d[3] = {d0, rows, d2}, st[2] = {row_bytes, chunk_bytes};
  cuuint32_t b[3] = {64, 32, box_chunks}, e[3] = {1, 1, 1};
  enc(m, CU_TENSOR_MAP_DATA_TYPE_BFLOAT16, 3, const_cast<void*>(ptr), d, st, b, e, CU_TENSOR_MAP_INTERLEAVE_NONE,
      CU_TENSOR_MAP_SWIZZLE_128B, CU_TENSOR_MAP_L2_PROMOTION_L2_128B, CU_TENSOR_MAP_FLOAT_OOB_FILL_NONE);
}

}

extern "C" void kernel_launch(void* const* d_in, const int* in_sizes, int n_in, void* d_out, int out_size) {
  (void)in_sizes; (void)n_in; (void)out_size;
  static EncodeFn enc = nullptr;
  static void *att = nullptr, *hbuf = nullptr, *scratch = nullptr;
  static int by_smid = 0;
  if (!enc) {
    void* fn = nullptr;
    cudaDriverEntryPointQueryResult q;
    cudaGetDriverEntryPoint("cuTensorMapEncodeTiled", &fn, cudaEnableDefault, &q);
    enc = (EncodeFn)fn;
    cudaGetSymbolAddress(&att, g_att);
    cudaGetSymbolAddress(&hbuf, g_h);
    cudaGetSymbolAddress(&scratch, g_scratch);
    cudaFuncSetAttribute(fused_layers_kernel<true>, cudaFuncAttributeMaxDynamicSharedMemorySize, SMEM_BYTES);
    cudaFuncSetAttribute(fused_layers_kernel<false>, cudaFuncAttributeMaxDynamicSharedMemorySize, SMEM_BYTES);
    int sms = 0, clusters = 0, dev = 0;
    cudaGetDevice(&dev);
    cudaDeviceGetAttribute(&sms, cudaDevAttrMultiProcessorCount, dev);
    cudaLaunchConfig_t cfg = {};
    cfg.gridDim = dim3(132);
    cfg.blockDim = dim3(384);
    cfg.dynamicSmemBytes = SMEM_BYTES;
    cudaLaunchAttribute at[1];
    at[0].id = cudaLaunchAttributeClusterDimension;
    at[0].val.clusterDim.x = 2; at[0].val.clusterDim.y = 1; at[0].val.clusterDim.z = 1;
    cfg.attrs = at;
    cfg.numAttrs = 1;
    if (cudaOccupancyMaxActiveClusters(&clusters, fused_layers_kernel<true>, &cfg) != cudaSuccess) (void)cudaGetLastError();
    by_smid = sms == 132 && clusters == 66;
  }
  Maps p;
  Scalars sc;
  make_act(enc, &p.xin, d_in[0], DM, true);
  make_act(enc, &p.out, d_out, DM, true);
  make_act(enc, &p.out_w, d_out, DM, true, 1);
  make_act(enc, &p.att, att, DM, false);
  make_act(enc, &p.h, hbuf, FF, false);
  make_2d(enc, &p.att_st, att, DM, SEQ, 32);
  make_2d(enc, &p.h_st, hbuf, FF, SEQ, 32);
  make_2d(enc, &p.w1c, d_in[4], FF, DM, 32);
  make_3d(enc, &p.wqkv, d_in[1], DM, DM, 3, 3 * DM * 2, DM * 2, 3);
  make_3d(enc, &p.wo, d_in[2], 64, DM, DM / 64, DM * 2, 128, 2);
  make_3d(enc, &p.w1a, d_in[4], 64, DM, FF / 64, FF * 2, 128, 3);
  make_3d(enc, &p.w1b, d_in[4], 64, DM, FF / 64, FF * 2, 128, 2);
  make_3d(enc, &p.w2, d_in[6], 64, FF, DM / 64, DM * 2, 128, 2);
  sc.b1 = (const __nv_bfloat16*)d_in[5];
  sc.b2 = (const __nv_bfloat16*)d_in[7];
  sc.g = (Scratch*)scratch;
  sc.zero = 0;
  if (by_smid) fused_layers_kernel<true><<<132, 384, SMEM_BYTES>>>(sc, p);
  else fused_layers_kernel<false><<<NCTA, 384, SMEM_BYTES>>>(sc, p);
}
```

```cpp
#include <cuda_runtime.h>
#include <cuda_bf16.h>
#include <cuda.h>
#include <stdint.h>

namespace {

constexpr int SEQ = 2048, DM = 1024, FF = 3584;
constexpr int NCTA = 128;
constexpr int NBAR = 5;

constexpr uint32_t RING_UNITS = 20, UNIT = 8192;
constexpr uint32_t OFF_X   = RING_UNITS * UNIT;
constexpr uint32_t OFF_STG = OFF_X + 32768;
constexpr uint32_t OFF_HLP = OFF_STG + 16384;
constexpr uint32_t OFF_RUN = OFF_STG + 24576;
constexpr uint32_t OFF_CSQ = OFF_RUN + 512;
constexpr uint32_t OFF_CSF = OFF_CSQ + 2048;
constexpr uint32_t OFF_ROW = OFF_CSF + 3584;
constexpr uint32_t OFF_BAR = OFF_ROW + 1024;
constexpr uint32_t SMEM_BYTES = OFF_BAR + 384;
constexpr uint32_t BAR_FULL = OFF_BAR, BAR_EMPTY = OFF_BAR + 8 * NBAR;
constexpr uint32_t BAR_XRDY = OFF_BAR + 80;
constexpr uint32_t BAR_DUMMY = OFF_BAR + 96, OFF_TAG = OFF_BAR + 104, OFF_ZERO = OFF_BAR + 112;
constexpr uint32_t BAR_PUB = OFF_BAR + 128;
constexpr uint32_t BAR_CSLD = OFF_BAR + 200;
constexpr uint32_t BAR_BIAS = OFF_BAR + 216;
constexpr uint32_t BAR_XGO = OFF_BAR + 224;

constexpr uint64_t DESC_A = (1ull << 62) | ((uint64_t)(2048 >> 4) << 32) | (1ull << 16);
constexpr uint64_t DESC_B = (1ull << 62) | ((uint64_t)(1024 >> 4) << 32) | ((uint64_t)(4096 >> 4) << 16);

constexpr int BAR_INIT = 0, BAR_ORDER = 1, BAR_GUARD = 3, BAR_WG = 5, BAR_GO = 7, BAR_DONE = 8, BAR_HLP = 9;
constexpr int BAR_INIT0 = 10, BAR_PAIR = 11;

constexpr int WIN1 = 5;
constexpr int WIN0 = 7;
constexpr int SKEW = 3;
constexpr int WIN2 = 1;
constexpr int GELU_DEP = 2;
constexpr int STG_WAIT = 5;
constexpr int HALO_NS = 200;
constexpr int STAT_NS = 800;
constexpr int CS_NS = 500;
constexpr int XB_NS = 400;
constexpr int XB_GAP_NS = 50;
constexpr int STAG_NS = 450;
constexpr int PACE_M = 100;
constexpr int PACE_N = 300;

struct Scratch {
  uint4 stats[4 * 8 * SEQ];
  uint4 halo[2 * 2 * 16 * 8 * 384];
  uint4 csp[2 * 8 * 17 * 224];
  uint32_t flags[16 * 32];
  uint32_t epoch[NCTA + 4];
};

struct Maps {
  CUtensorMap xin, out, att, h, wqkv, wo, w1a, w1b, w2, att_st, h_st, w1c, out_w;
};
struct Scalars {
  Scratch* g;
  const __nv_bfloat16 *b1, *b2;
  uint32_t zero;
};
struct Params : Scalars {
  const Maps& t;
};

__device__ __nv_bfloat16 g_att[SEQ * DM];
__device__ __nv_bfloat16 g_h[SEQ * FF];
__device__ Scratch g_scratch;

__device__ __forceinline__ void mbar_init(uint32_t bar, int cnt) {
  asm volatile("mbarrier.init.shared::cta.b64 [%0], %1;" ::"r"(bar), "r"(cnt));
}
__device__ __forceinline__ void mbar_expect_tx(uint32_t bar, uint32_t bytes) {
  asm volatile("mbarrier.arrive.expect_tx.shared::cta.b64 _, [%0], %1;" ::"r"(bar), "r"(bytes) : "memory");
}
__device__ __forceinline__ void mbar_arrive(uint32_t bar) {
  asm volatile("mbarrier.arrive.shared::cta.b64 _, [%0];" ::"r"(bar) : "memory");
}
__device__ __forceinline__ bool mbar_test(uint32_t bar, uint32_t parity) {
  uint32_t ok;
  asm volatile("{\n.reg .pred p;\nmbarrier.test_wait.parity.shared::cta.b64 p, [%1], %2;\nselp.u32 %0, 1, 0, p;\n}"
               : "=r"(ok) : "r"(bar), "r"(parity) : "memory");
  return ok;
}
__device__ __forceinline__ void mbar_wait(uint32_t bar, uint32_t parity) {
  asm volatile(
      "{\n.reg .pred p;\n.reg .u32 it;\nmov.u32 it, 0;\n"
      "WAIT_LOOP:\n"
      "mbarrier.try_wait.parity.shared::cta.b64 p, [%0], %1;\n"
      "@p bra WAIT_DONE;\n"
      "add.u32 it, it, 1;\n"
      "setp.lt.u32 p, it, 0x400000;\n"
      "@p bra WAIT_LOOP;\n"
      "trap;\n"
      "WAIT_DONE:\n}"
      ::"r"(bar), "r"(parity) : "memory");
}
__device__ __forceinline__ void bar_sync(int id, int n) { asm volatile("bar.sync %0, %1;" ::"r"(id), "r"(n) : "memory"); }
__device__ __forceinline__ void bar_arrive(int id, int n) { asm volatile("bar.arrive %0, %1;" ::"r"(id), "r"(n) : "memory"); }
__device__ __forceinline__ void tma_ld2(uint32_t dst, const CUtensorMap* m, uint32_t bar, int c0, int c1) {
  asm volatile("cp.async.bulk.tensor.2d.shared::cluster.global.mbarrier::complete_tx::bytes [%0], [%1, {%3, %4}], [%2];"
               ::"r"(dst), "l"(m), "r"(bar), "r"(c0), "r"(c1) : "memory");
}
__device__ __forceinline__ void tma_ld_act(uint32_t dst, const CUtensorMap* m, uint32_t bar, int col, int blk) {
  asm volatile("cp.async.bulk.tensor.4d.shared::cluster.global.mbarrier::complete_tx::bytes [%0], [%1, {%3, %5, %5, %4}], [%2];"
               ::"r"(dst), "l"(m), "r"(bar), "r"(col), "r"(2 * blk), "r"(0) : "memory");
}
__device__ __forceinline__ void tma_st_act(const CUtensorMap* m, uint32_t src, int col, int blk) {
  asm volatile("cp.async.bulk.tensor.4d.global.shared::cta.bulk_group [%0, {%2, %4, %4, %3}], [%1];"
               ::"l"(m), "r"(src), "r"(col), "r"(2 * blk), "r"(0) : "memory");
}
__device__ __forceinline__ void tma_st_warp(const CUtensorMap* m, uint32_t src, int col, int blk, int w) {
  asm volatile("cp.async.bulk.tensor.4d.global.shared::cta.bulk_group [%0, {%2, %5, %3, %4}], [%1];"
               ::"l"(m), "r"(src), "r"(col), "r"(w & 1), "r"(2 * blk + (w >> 1)), "r"(0) : "memory");
}
__device__ __forceinline__ void tma_ld3(uint32_t dst, const CUtensorMap* m, uint32_t bar, int c0, int c1, int c2) {
  asm volatile("cp.async.bulk.tensor.3d.shared::cluster.global.mbarrier::complete_tx::bytes [%0], [%1, {%3, %4, %5}], [%2];"
               ::"r"(dst), "l"(m), "r"(bar), "r"(c0), "r"(c1), "r"(c2) : "memory");
}
__device__ __forceinline__ void tma_ld3_pair(uint32_t dst, const CUtensorMap* m, uint32_t bar, int c0, int c1, int c2) {
  asm volatile("cp.async.bulk.tensor.3d.shared::cluster.global.mbarrier::complete_tx::bytes.multicast::cluster"
               " [%0], [%1, {%3, %4, %5}], [%2], %6;"
               ::"r"(dst), "l"(m), "r"(bar), "r"(c0), "r"(c1), "r"(c2), "h"((uint16_t)3) : "memory");
}
__device__ __forceinline__ uint32_t pair_offset(uint32_t sb, uint32_t rank) {
  uint32_t r;
  asm volatile("mapa.shared::cluster.u32 %0, %1, %2;" : "=r"(r) : "r"(sb), "r"(rank));
  return r - sb;
}
__device__ __forceinline__ void mbar_arrive_cluster(uint32_t bar) {
  asm volatile("mbarrier.arrive.shared::cluster.b64 _, [%0];" ::"r"(bar) : "memory");
}
__device__ __forceinline__ void cluster_arrive() { asm volatile("barrier.cluster.arrive.relaxed;" ::: "memory"); }
__device__ __forceinline__ void cluster_wait() { asm volatile("barrier.cluster.wait.acquire;" ::: "memory"); }
__device__ __forceinline__ void tma_st2(const CUtensorMap* m, uint32_t src, int c0, int c1) {
  asm volatile("cp.async.bulk.tensor.2d.global.shared::cta.bulk_group [%0, {%2, %3}], [%1];"
               ::"l"(m), "r"(src), "r"(c0), "r"(c1) : "memory");
}
__device__ __forceinline__ void bulk_commit() { asm volatile("cp.async.bulk.commit_group;" ::: "memory"); }
__device__ __forceinline__ void bulk_wait_read() { asm volatile("cp.async.bulk.wait_group.read 0;" ::: "memory"); }
__device__ __forceinline__ void bulk_wait_all() { asm volatile("cp.async.bulk.wait_group 0;" ::: "memory"); }
__device__ __forceinline__ void fence_async_smem() { asm volatile("fence.proxy.async.shared::cta;" ::: "memory"); }
__device__ __forceinline__ void fence_async_global() { asm volatile("fence.proxy.async.global;" ::: "memory"); }
__device__ __forceinline__ void st_relaxed(uint32_t* p, uint32_t v) {
  asm volatile("st.relaxed.gpu.global.u32 [%0], %1;" ::"l"(p), "r"(v) : "memory");
}
__device__ __forceinline__ void st_msg(uint4* p, uint32_t a, uint32_t b, uint32_t c, uint32_t tag) {
  asm volatile("{\n.reg .b128 v;\nmov.b128 v, {%1, %2, %3, %4};\nst.relaxed.gpu.global.b128 [%0], v;\n}"
               ::"l"(p), "r"(a), "r"(b), "r"(c), "r"(tag) : "memory");
}
__device__ __forceinline__ void ld_msg(const uint4* p, uint32_t& a, uint32_t& b, uint32_t& c, uint32_t& tag) {
  asm volatile("{\n.reg .b128 v;\nld.relaxed.gpu.global.b128 v, [%4];\nmov.b128 {%0, %1, %2, %3}, v;\n}"
               : "=r"(a), "=r"(b), "=r"(c), "=r"(tag) : "l"(p) : "memory");
}
__device__ __forceinline__ bool elect_one() {
  uint32_t ok;
  asm volatile("{\n.reg .pred p;\nelect.sync _|p, 0xffffffff;\nselp.u32 %0, 1, 0, p;\n}" : "=r"(ok));
  return ok;
}
__device__ __forceinline__ uint32_t lanemask_lt() {
  uint32_t v;
  asm("mov.u32 %0, %%lanemask_lt;" : "=r"(v));
  return v;
}
__device__ __forceinline__ int uniform(int v) { return __shfl_sync(0xffffffffu, v, 0); }
__device__ __forceinline__ uint32_t pack_bf16(float lo, float hi) {
  uint32_t r;
  asm("cvt.rn.bf16x2.f32 %0, %1, %2;" : "=r"(r) : "f"(hi), "f"(lo));
  return r;
}
__device__ __forceinline__ float prmt_f(uint32_t a, uint32_t sel) {
  float r;
  asm("{\n.reg .b32 t;\nprmt.b32 t, %1, 0, %2;\nmov.b32 %0, t;\n}" : "=f"(r) : "r"(a), "r"(sel));
  return r;
}
__device__ __forceinline__ float bf_lo(uint32_t v) { return __uint_as_float(v << 16); }
__device__ __forceinline__ float bf_hi(uint32_t v) { return __uint_as_float(v & 0xffff0000u); }
__device__ __forceinline__ void stsm4(uint32_t addr, uint32_t r0, uint32_t r1, uint32_t r2, uint32_t r3) {
  asm volatile("stmatrix.sync.aligned.m8n8.x4.shared.b16 [%0], {%1, %2, %3, %4};"
               ::"r"(addr), "r"(r0), "r"(r1), "r"(r2), "r"(r3) : "memory");
}
__device__ __forceinline__ void ldsm4(uint32_t addr, uint32_t& r0, uint32_t& r1, uint32_t& r2, uint32_t& r3) {
  asm volatile("ldmatrix.sync.aligned.m8n8.x4.shared.b16 {%0, %1, %2, %3}, [%4];"
               : "=r"(r0), "=r"(r1), "=r"(r2), "=r"(r3) : "r"(addr) : "memory");
}
__device__ __forceinline__ uint32_t movtrans(uint32_t a) {
  uint32_t d;
  asm volatile("movmatrix.sync.aligned.m8n8.trans.b16 %0, %1;" : "=r"(d) : "r"(a));
  return d;
}
__device__ __forceinline__ void mma16816(float (&c)[4], uint32_t a0, uint32_t a1, uint32_t a2, uint32_t a3, uint32_t b0, uint32_t b1) {
  asm volatile("mma.sync.aligned.m16n8k16.row.col.f32.bf16.bf16.f32 {%0,%1,%2,%3}, {%4,%5,%6,%7}, {%8,%9}, {%0,%1,%2,%3};"
               : "+f"(c[0]), "+f"(c[1]), "+f"(c[2]), "+f"(c[3])
               : "r"(a0), "r"(a1), "r"(a2), "r"(a3), "r"(b0), "r"(b1));
}
__device__ __forceinline__ void mma1688(float (&c)[4], uint32_t a0, uint32_t a1, uint32_t b0) {
  asm volatile("mma.sync.aligned.m16n8k8.row.col.f32.bf16.bf16.f32 {%0,%1,%2,%3}, {%4,%5}, {%6}, {%0,%1,%2,%3};"
               : "+f"(c[0]), "+f"(c[1]), "+f"(c[2]), "+f"(c[3]) : "r"(a0), "r"(a1), "r"(b0));
}
__device__ __forceinline__ float2 lds_f2(uint32_t a) {
  float2 v;
  asm volatile("ld.shared.v2.f32 {%0, %1}, [%2];" : "=f"(v.x), "=f"(v.y) : "r"(a) : "memory");
  return v;
}
__device__ __forceinline__ float4 lds_f4(uint32_t a) {
  float4 v;
  asm volatile("ld.shared.v4.f32 {%0, %1, %2, %3}, [%4];" : "=f"(v.x), "=f"(v.y), "=f"(v.z), "=f"(v.w) : "r"(a) : "memory");
  return v;
}
__device__ __forceinline__ float lds_f(uint32_t a) {
  float v;
  asm volatile("ld.shared.f32 %0, [%1];" : "=f"(v) : "r"(a) : "memory");
  return v;
}
__device__ __forceinline__ uint32_t lds_u(uint32_t a) {
  uint32_t v;
  asm volatile("ld.shared.u32 %0, [%1];" : "=r"(v) : "r"(a) : "memory");
  return v;
}
__device__ __forceinline__ void sts_f2(uint32_t a, float x, float y) {
  asm volatile("st.shared.v2.f32 [%0], {%1, %2};" ::"r"(a), "f"(x), "f"(y) : "memory");
}
__device__ __forceinline__ void sts_u4(uint32_t a, uint32_t x, uint32_t y, uint32_t z, uint32_t w) {
  asm volatile("st.shared.v4.u32 [%0], {%1, %2, %3, %4};" ::"r"(a), "r"(x), "r"(y), "r"(z), "r"(w) : "memory");
}
__device__ __forceinline__ void lds_u4(uint32_t a, uint32_t& x, uint32_t& y, uint32_t& z, uint32_t& w) {
  asm volatile("ld.shared.v4.u32 {%0, %1, %2, %3}, [%4];" : "=r"(x), "=r"(y), "=r"(z), "=r"(w) : "r"(a) : "memory");
}
__device__ __forceinline__ float ex2(float x) {
  float y;
  asm("ex2.approx.ftz.f32 %0, %1;" : "=f"(y) : "f"(x));
  return y;
}
__device__ __forceinline__ float rcp_hw(float x) {
  float y;
  asm("rcp.approx.ftz.f32 %0, %1;" : "=f"(y) : "f"(x));
  return y;
}
__device__ __forceinline__ float tanh_hw(float x) {
  float y;
  asm("tanh.approx.f32 %0, %1;" : "=f"(y) : "f"(x));
  return y;
}
__device__ __forceinline__ float quad_sum(float v) {
  v += __shfl_xor_sync(0xffffffffu, v, 1);
  return v + __shfl_xor_sync(0xffffffffu, v, 2);
}
__device__ __forceinline__ float quad_max(float v) {
  v = fmaxf(v, __shfl_xor_sync(0xffffffffu, v, 1));
  return fmaxf(v, __shfl_xor_sync(0xffffffffu, v, 2));
}

template <int N> __device__ __forceinline__ void wgmma_ss(float (&d)[96], uint64_t da, uint64_t db, uint32_t keep = 1);
template <> __device__ __forceinline__ void wgmma_ss<128>(float (&d)[96], uint64_t da, uint64_t db, uint32_t keep) {
  asm volatile(
      "{\n.reg .pred p;\nsetp.ne.u32 p, %66, 0;\n"
      "wgmma.mma_async.sync.aligned.m64n128k16.f32.bf16.bf16 {%0, %1, %2, %3, %4, %5, %6, %7, %8, %9, %10, %11, %12, %13, %14, %15, %16, %17, %18, %19, %20, %21, %22, %23, %24, %25, %26, %27, %28, %29, %30, %31, %32, %33, %34, %35, %36, %37, %38, %39, %40, %41, %42, %43, %44, %45, %46, %47, %48, %49, %50, %51, %52, %53, %54, %55, %56, %57, %58, %59, %60, %61, %62, %63}, %64, %65, p, 1, 1, 0, 1;\n}"
      : "+f"(d[0]), "+f"(d[1]), "+f"(d[2]), "+f"(d[3]), "+f"(d[4]), "+f"(d[5]), "+f"(d[6]), "+f"(d[7]), "+f"(d[8]), "+f"(d[9]), "+f"(d[10]), "+f"(d[11]), "+f"(d[12]), "+f"(d[13]), "+f"(d[14]), "+f"(d[15]), "+f"(d[16]), "+f"(d[17]), "+f"(d[18]), "+f"(d[19]), "+f"(d[20]), "+f"(d[21]), "+f"(d[22]), "+f"(d[23]), "+f"(d[24]), "+f"(d[25]), "+f"(d[26]), "+f"(d[27]), "+f"(d[28]), "+f"(d[29]), "+f"(d[30]), "+f"(d[31]), "+f"(d[32]), "+f"(d[33]), "+f"(d[34]), "+f"(d[35]), "+f"(d[36]), "+f"(d[37]), "+f"(d[38]), "+f"(d[39]), "+f"(d[40]), "+f"(d[41]), "+f"(d[42]), "+f"(d[43]), "+f"(d[44]), "+f"(d[45]), "+f"(d[46]), "+f"(d[47]), "+f"(d[48]), "+f"(d[49]), "+f"(d[50]), "+f"(d[51]), "+f"(d[52]), "+f"(d[53]), "+f"(d[54]), "+f"(d[55]), "+f"(d[56]), "+f"(d[57]), "+f"(d[58]), "+f"(d[59]), "+f"(d[60]), "+f"(d[61]), "+f"(d[62]), "+f"(d[63])
      : "l"(da), "l"(db), "r"(keep));
}

template <> __device__ __forceinline__ void wgmma_ss<192>(float (&d)[96], uint64_t da, uint64_t db, uint32_t keep) {
  asm volatile(
      "{\n.reg .pred p;\nsetp.ne.u32 p, %98, 0;\n"
      "wgmma.mma_async.sync.aligned.m64n192k16.f32.bf16.bf16 {%0, %1, %2, %3, %4, %5, %6, %7, %8, %9, %10, %11, %12, %13, %14, %15, %16, %17, %18, %19, %20, %21, %22, %23, %24, %25, %26, %27, %28, %29, %30, %31, %32, %33, %34, %35, %36, %37, %38, %39, %40, %41, %42, %43, %44, %45, %46, %47, %48, %49, %50, %51, %52, %53, %54, %55, %56, %57, %58, %59, %60, %61, %62, %63, %64, %65, %66, %67, %68, %69, %70, %71, %72, %73, %74, %75, %76, %77, %78, %79, %80, %81, %82, %83, %84, %85, %86, %87, %88, %89, %90, %91, %92, %93, %94, %95}, %96, %97, p, 1, 1, 0, 1;\n}"
      : "+f"(d[0]), "+f"(d[1]), "+f"(d[2]), "+f"(d[3]), "+f"(d[4]), "+f"(d[5]), "+f"(d[6]), "+f"(d[7]), "+f"(d[8]), "+f"(d[9]), "+f"(d[10]), "+f"(d[11]), "+f"(d[12]), "+f"(d[13]), "+f"(d[14]), "+f"(d[15]), "+f"(d[16]), "+f"(d[17]), "+f"(d[18]), "+f"(d[19]), "+f"(d[20]), "+f"(d[21]), "+f"(d[22]), "+f"(d[23]), "+f"(d[24]), "+f"(d[25]), "+f"(d[26]), "+f"(d[27]), "+f"(d[28]), "+f"(d[29]), "+f"(d[30]), "+f"(d[31]), "+f"(d[32]), "+f"(d[33]), "+f"(d[34]), "+f"(d[35]), "+f"(d[36]), "+f"(d[37]), "+f"(d[38]), "+f"(d[39]), "+f"(d[40]), "+f"(d[41]), "+f"(d[42]), "+f"(d[43]), "+f"(d[44]), "+f"(d[45]), "+f"(d[46]), "+f"(d[47]), "+f"(d[48]), "+f"(d[49]), "+f"(d[50]), "+f"(d[51]), "+f"(d[52]), "+f"(d[53]), "+f"(d[54]), "+f"(d[55]), "+f"(d[56]), "+f"(d[57]), "+f"(d[58]), "+f"(d[59]), "+f"(d[60]), "+f"(d[61]), "+f"(d[62]), "+f"(d[63]), "+f"(d[64]), "+f"(d[65]), "+f"(d[66]), "+f"(d[67]), "+f"(d[68]), "+f"(d[69]), "+f"(d[70]), "+f"(d[71]), "+f"(d[72]), "+f"(d[73]), "+f"(d[74]), "+f"(d[75]), "+f"(d[76]), "+f"(d[77]), "+f"(d[78]), "+f"(d[79]), "+f"(d[80]), "+f"(d[81]), "+f"(d[82]), "+f"(d[83]), "+f"(d[84]), "+f"(d[85]), "+f"(d[86]), "+f"(d[87]), "+f"(d[88]), "+f"(d[89]), "+f"(d[90]), "+f"(d[91]), "+f"(d[92]), "+f"(d[93]), "+f"(d[94]), "+f"(d[95])
      : "l"(da), "l"(db), "r"(keep));
}

template <int R>
__device__ __forceinline__ void pin_regs(float (&a)[2][96]) {
#pragma unroll
  for (int m = 0; m < 2; m++)
#pragma unroll
    for (int i = 0; i < R; i++) asm volatile("" : "+f"(a[m][i])::"memory");
}

struct Ctx {
  uint32_t sb;
  int m, n, wg, w, lane;
};
__device__ __forceinline__ Ctx make_ctx(uint32_t sb, int id) {
  int lane;
  asm volatile("mov.u32 %0, %%laneid;" : "=r"(lane));
  asm volatile("" : "+r"(id), "+r"(sb));
  return Ctx{sb, (id >> 3) & 15, id & 7, id >> 9, (id >> 7) & 3, lane};
}
#define UNPACK_CTX(c) const uint32_t sb = c.sb; const int m = c.m, n = c.n, wg = c.wg, w = c.w, lane = c.lane

__device__ __forceinline__ uint32_t poll_line(const uint32_t* word, uint32_t target, uint32_t need) {
  uint32_t v;
  asm volatile(
      "{\n.reg .pred p;\n.reg .u32 it, m;\n.reg .s32 d;\nmov.u32 it, 0;\n"
      "POLL_LOOP:\n"
      "ld.relaxed.gpu.global.u32 %0, [%1];\n"
      "sub.s32 d, %0, %2;\n"
      "setp.ge.s32 p, d, 0;\n"
      "vote.sync.ballot.b32 m, p, 0xffffffff;\n"
      "and.b32 m, m, %3;\n"
      "setp.eq.u32 p, m, %3;\n"
      "@p bra.uni POLL_DONE;\n"
      "add.u32 it, it, 1;\n"
      "setp.lt.u32 p, it, 0x400000;\n"
      "@p bra.uni POLL_LOOP;\n"
      "trap;\n"
      "POLL_DONE:\n}"
      : "=&r"(v) : "l"(word), "r"(target), "r"(need) : "memory");
  return v;
}
__device__ __forceinline__ uint32_t ld_relaxed(const uint32_t* p) {
  uint32_t v;
  asm volatile("ld.relaxed.gpu.global.u32 %0, [%1];" : "=r"(v) : "l"(p) : "memory");
  return v;
}
__device__ __forceinline__ float chain(float x, uint32_t on, uint32_t zero) {
  return __uint_as_float(__float_as_uint(x) | (on & zero));
}
constexpr int MSG_SPINS = 1 << 20;

constexpr int STAGES_PER_LAYER = 152;
__device__ __forceinline__ int nib(uint64_t v, int i) { return (int)(v >> (4 * i)) & 15; }
__device__ __forceinline__ bool tile_wide(int t) { return (0x23 >> t) & 1; }
__device__ __forceinline__ void weight_coords(const Params& p, int t, int n, const CUtensorMap*& map, int& c0, int& c2) {
  map = &p.t.wqkv + nib(0x4233100ull, t);
  c0 = t < 2 ? 128 * n + 64 * t : 0;
  c2 = t < 2 ? 0 : (t == 2 || t == 6) ? 2 * n : 7 * n + 2 * t - 6;
}

template <bool IS_A>
__device__ __forceinline__ void producer(const Params& p, uint32_t sb, int m, int n, int lane) {
  const uint32_t low = (1u << (4 * n)) - 1, others = (0x6543210u & low) | (0x7654321u & ~low);
  const uint64_t order_x = (uint64_t)(others * 2 + 0x1111111u) << 36 | (uint64_t)others * 2 << 8 | (n * 0x22 + 0x10);
  int inflight = 4, cur = 0;
  uint32_t fb = sb + BAR_FULL + 32, rb = sb + BAR_EMPTY, rph = 0, pos = 0, tag32 = 0, seen = 0;
  const uint32_t fend = sb + BAR_FULL + 8 * NBAR, rend = sb + BAR_EMPTY + 8 * NBAR;
  const uint32_t* word = p.g->flags + m * 32 + (lane < 16 ? lane >> 1 : lane & 7);
#pragma unroll 1
  for (int sg = 1; sg < 22; sg++) {
    const int layer = sg >= 11, s = sg == 1 ? 2 : sg == 2 ? 1 : sg - 11 * layer;
    const int t = nib(0x65434321010ull, s), kind = nib(0x32110031100ull, s);
    const bool wide = tile_wide(t);
    const uint32_t bbytes = wide ? 3 * UNIT : 2 * UNIT, base = sb + (IS_A ? bbytes : (m & 1) * (bbytes / 2));
    if (IS_A && kind == 0) {
      if (sg == 2) seen = tag32 = (__ldcg(p.g->epoch + m * 8 + n) + 1) << 5;
#pragma unroll 1
      for (int k = 0; k < 2; k++) {
#pragma unroll 1
        for (; inflight > (wide ? 3 : 4); inflight--) {
          mbar_wait(rb, rph);
          rb += 8;
          if (rb == rend) { rb -= 8 * NBAR; rph ^= 1; }
        }
        if (elect_one()) mbar_arrive(fb);
        inflight++;
        fb += 8;
        if (fb == fend) fb -= 8 * NBAR;
        pos += bbytes + 2 * UNIT;
        if (pos >= RING_UNITS * UNIT) pos -= RING_UNITS * UNIT;
      }
      continue;
    }
    const int mul = t == 6 ? 448 : t == 2 ? 128 : 64, count = sg == 1 ? 12 : 2 * nib(0x4871ull, kind);
    uint64_t order0 = sg == 1 ? 0xFEDCBA987654ull : kind == 3 ? 0x76543210u : order_x >> (8 * (kind & 1));
    uint32_t special = (s == 4 || s == 10) ? 0x10 : s == 9 ? 0xF : s == 0;
    if (IS_A) special |= (kind & 1 ? 0 : 3) | (count >= 4 ? 1u << (count - 4) : 0);
    if (s >= 9) pos = (s + 6) * UNIT;
    const CUtensorMap* map;
    int c0 = 0, c2 = 0, ev = 0;
    if (IS_A) {
      map = &p.t.xin + (t == 2 ? 2 : t == 6 ? 3 : sg >= 4);
      ev = 9 * layer + (t < 2 ? 0 : t == 2 ? 1 : t < 6 ? 4 : 5);
      if (elect_one()) asm volatile("prefetch.tensormap [%0];" ::"l"(map) : "memory");
    } else {
      weight_coords(p, t, n, map, c0, c2);
    }
#pragma unroll 1
    for (int add = 0; add < mul; add += 64) {
      uint64_t order = order0;
      const int need = kind == 3 ? ev : ev - 1 + (lane & 1), sh = kind == 3 ? 16 : 0;
      uint32_t ready = IS_A ? __ballot_sync(0xffffffffu, cur >= need) >> sh : 0;
#pragma unroll 1
      for (int k = 0; k < count; k++) {
        const int code = order & 15, kc = code * mul + add;
        order >>= 4;
        if ((special >> k) & 1) {
          const int lag = wide ? (s == 9 && k == 2 ? 2 : 3) : ((s == 4 || s == 10) && add == 0 && k < 4) ? 3 : 4;
#pragma unroll 1
          for (; inflight > lag; inflight--) {
            mbar_wait(rb, rph);
            rb += 8;
            if (rb == rend) { rb -= 8 * NBAR; rph ^= 1; }
          }
          inflight++;
          if (IS_A) {
            if (kind == 3 ? t == 2 && add + k == 64 : !(kind & 1) && k < 2) {
              if (t == 2) mbar_wait(sb + BAR_PUB + 8, layer);
              if (elect_one()) mbar_arrive(fb);
              goto next_stage;
            }
            if (k == count - 4 && sg >= 3) seen = ld_relaxed(word);
          }
        } else {
          mbar_wait(rb, rph);
          rb += 8;
          if (rb == rend) { rb -= 8 * NBAR; rph ^= 1; }
        }
        if (IS_A && !((ready >> code) & 1)) {
          cur = max(cur, (int)(seen - tag32));
          ready = __ballot_sync(0xffffffffu, cur >= need) >> sh;
          if (!((ready >> code) & 1)) {
            cur = (int)(poll_line(word, tag32 + need, 1u << (code + sh)) - tag32);
            ready = __ballot_sync(0xffffffffu, cur >= need) >> sh;
          }
          asm volatile("fence.acquire.gpu;" ::: "memory");
          fence_async_global();
          seen = ld_relaxed(word);
        }
        if (elect_one()) {
          if (!IS_A) tma_ld3_pair(base + pos, map, fb, c0, kc + 32 * (m & 1), c2);
          else tma_ld_act(base + pos, map, fb, kc, m);
          mbar_expect_tx(fb, IS_A ? 16384 : bbytes);
        }
      next_stage:
        fb += 8;
        if (fb == fend) fb -= 8 * NBAR;
        pos += bbytes + 2 * UNIT;
        if (pos >= RING_UNITS * UNIT) pos -= RING_UNITS * UNIT;
      }
      special = !IS_A ? 0 : t == 2 ? 1 : add == 128 ? 0x10 : 0;
      if (t == 2) order0 = others << 4 | n;
      if (IS_A && (t == 2 || add == 64 || add == 192)) ev++;
    }
  }
}

__device__ __forceinline__ void publisher(const Params& p, uint32_t sb, int m, int n) {
  {
    const int ts = PACE_M * m, tx = PACE_N * n;
#pragma unroll 1
    for (int k = 0; k < 2; k++) {
      __nanosleep(k == 0 ? min(ts, tx) : abs(ts - tx));
      if ((ts <= tx) == (k == 0)) {
        mbar_expect_tx(sb + BAR_CSLD, 24576);
        tma_ld3(sb + OFF_STG, &p.t.wqkv, sb + BAR_CSLD, 128 * n, 64 * m, 0);
        tma_ld3(sb + OFF_STG + 12288, &p.t.wqkv, sb + BAR_CSLD, 128 * n, 64 * m + 32, 0);
      } else {
#pragma unroll 1
        for (int h = 0; h < 2; h++) {
          const uint32_t xr = sb + BAR_XRDY + 8 * h;
          mbar_expect_tx(xr, 16384);
          tma_ld_act(sb + OFF_X + h * 16384, &p.t.xin, xr, 128 * n + 64 * h, m);
          asm volatile("mbarrier.arrive.shared::cta.b64 _, [%0], 3;" ::"r"(xr) : "memory");
        }
      }
    }
  }
  const uint32_t tag = __ldcg(p.g->epoch + m * 8 + n) + 1;
  uint32_t* word = p.g->flags + m * 32 + n;
  st_relaxed(word, 32 * tag);
#pragma unroll 1
  for (int c = 0; c < 16; c++) {
    const int e = c >= 9 ? c - 9 : c;
    if (e == 2 || e == 7) {
      asm volatile("prefetch.tensormap [%0];" ::"l"(&p.t.out) : "memory");
      mbar_wait(sb + BAR_XRDY, e == 2);
      tma_st_act(&p.t.out, sb + OFF_X, 128 * n, m);
      bulk_commit();
      mbar_wait(sb + BAR_XRDY + 8, e == 2);
      bulk_wait_all();
      mbar_arrive(sb + BAR_XGO);
    } else {
      mbar_wait(sb + BAR_PUB + 8 * e, c >= 9);
    }
    asm volatile("fence.release.gpu;" ::: "memory");
    asm volatile("red.relaxed.gpu.global.add.u32 [%0], 1;" ::"l"(word) : "memory");
  }
  p.g->epoch[m * 8 + n] = tag;
}

__device__ __forceinline__ void sum_rows(uint32_t buf, int iters, float (&a)[8], int lane) {
  uint32_t addr = buf + (lane >> 3) * 128 + (((lane & 7) ^ (lane >> 3)) << 4);
#pragma unroll 1
  for (int it = 0; it < iters; it++) {
    uint32_t u[2][4];
    lds_u4(addr, u[0][0], u[0][1], u[0][2], u[0][3]);
    lds_u4((addr ^ 64) + 512, u[1][0], u[1][1], u[1][2], u[1][3]);
    addr += 1024;
#pragma unroll
    for (int e = 0; e < 8; e++) { a[2 * (e & 3)] += bf_lo(u[e >> 2][e & 3]); a[2 * (e & 3) + 1] += bf_hi(u[e >> 2][e & 3]); }
  }
}
__device__ __forceinline__ void publish_sums(const float (&a)[8], uint4* dst, int lane, uint32_t tag) {
  const bool u8 = lane & 8, u16 = lane & 16;
  float h4[4], h2[2];
#pragma unroll
  for (int e = 0; e < 4; e++) h4[e] = (u8 ? a[4 + e] : a[e]) + __shfl_xor_sync(0xffffffffu, u8 ? a[e] : a[4 + e], 8);
#pragma unroll
  for (int e = 0; e < 2; e++) h2[e] = (u16 ? h4[2 + e] : h4[e]) + __shfl_xor_sync(0xffffffffu, u16 ? h4[e] : h4[2 + e], 16);
  st_msg(dst + (lane & 7) * 4 + (u8 ? 2 : 0) + (u16 ? 1 : 0), __float_as_uint(h2[0]), __float_as_uint(h2[1]), 0u, tag);
}

__device__ __forceinline__ void colsum_helper(const Params& p, uint32_t sb, int m, int n, int lane) {
  const uint32_t tag = __ldcg(p.g->epoch + m * 8 + n) + 1;
#pragma unroll 1
  for (int k = lane; k < 288; k += 32) {
    const uint32_t bb = __ldg(reinterpret_cast<const uint32_t*>(k < 224 ? p.b1 + 448 * n : p.b2 + 128 * n - 448) + k);
    const float sc = k < 224 ? 0.5f : 1.f;
    sts_f2(sb + (k < 224 ? OFF_CSF + k * 16 + 8 : OFF_CSQ + 1536 + (k - 224) * 8), sc * bf_lo(bb), sc * bf_hi(bb));
  }
  __syncwarp();
  if (elect_one()) mbar_arrive(sb + BAR_BIAS);
  bar_sync(BAR_HLP, 160);
  {
    uint4* base = p.g->csp + n * 17 * 224 + 12 * m + min(lane & 15, 11);
    float s0 = 0.f, s1 = 0.f;
#pragma unroll 1
    for (int g = 0; g < 2; g++) {
      uint32_t x[4], y[4];
#pragma unroll 1
      for (int it = 0; it < MSG_SPINS; it++) {
        uint32_t bad = 0, z, tg;
        if (g == 0 || it > 0) __nanosleep(CS_NS);
#pragma unroll
        for (int k = 0; k < 4; k++) { ld_msg(base + (g * 8 + (lane >> 4) * 4 + k) * 224, x[k], y[k], z, tg); bad |= tg ^ tag; }
        if (__all_sync(0xffffffffu, bad == 0)) break;
      }
#pragma unroll
      for (int k = 0; k < 4; k++) { s0 += __uint_as_float(x[k]); s1 += __uint_as_float(y[k]); }
    }
    s0 += __shfl_xor_sync(0xffffffffu, s0, 16);
    s1 += __shfl_xor_sync(0xffffffffu, s1, 16);
    if (lane < 12) st_msg(base + 16 * 224, __float_as_uint(s0), __float_as_uint(s1), 0u, tag);
  }
#pragma unroll 1
  for (int c = 0; c < 7; c++) {
    float a[8] = {0.f, 0.f, 0.f, 0.f, 0.f, 0.f, 0.f, 0.f};
#pragma unroll 1
    for (int h = 0; h < 2; h++) {
      if (elect_one()) {
        mbar_expect_tx(sb + BAR_CSLD + 8, 4096);
        tma_ld2(sb + OFF_HLP, &p.t.w1c, sb + BAR_CSLD + 8, 448 * n + 64 * c, 64 * m + 32 * h);
        if (c < 6) asm volatile("cp.async.bulk.prefetch.tensor.2d.L2.global [%0, {%1, %2}];" ::"l"(&p.t.w1c), "r"(448 * n + 64 * c + 64), "r"(64 * m + 32 * h) : "memory");
      }
      mbar_wait(sb + BAR_CSLD + 8, h);
      sum_rows(sb + OFF_HLP, 4, a, lane);
      __syncwarp();
    }
    publish_sums(a, p.g->csp + ((8 + n) * 17 + m) * 224 + c * 32, lane, tag);
  }
  if (elect_one()) {
#pragma unroll 1
    for (int k = 0; k < 3; k++) {
      mbar_wait(sb + BAR_XGO, k & 1);
      __nanosleep(XB_NS);
#pragma unroll 1
      for (int w = 0; w < 4; w++) {
        tma_st_warp(&p.t.out_w, sb + OFF_X + 16384 + w * 4096, 128 * n + 64, m, w);
        bulk_commit();
        bulk_wait_read();
        if (w < 3) __nanosleep(XB_GAP_NS);
      }
      bulk_wait_all();
      asm volatile("mbarrier.arrive.shared::cta.b64 _, [%0], 4;" ::"r"(sb + BAR_PUB + (k & 1 ? 64 : 24)) : "memory");
    }
  }
}

__device__ __forceinline__ void poll_msgs2(const uint4* pa, const uint4* pb, float (&v)[4], uint32_t tag) {
#pragma unroll 1
  for (int it = 0; it < MSG_SPINS; it++) {
    uint32_t x[4], z, ta, tb;
    ld_msg(pa, x[0], x[1], z, ta);
    ld_msg(pb, x[2], x[3], z, tb);
#pragma unroll
    for (int e = 0; e < 4; e++) v[e] = __uint_as_float(x[e]);
    if (__all_sync(0xffffffffu, ta == tag && tb == tag)) break;
  }
}
__device__ __forceinline__ void colsum_total(const Params& p, const Ctx& cx, int mat, uint32_t tag) {
  uint4* base = p.g->csp + (mat * 8 + cx.n) * 17 * 224;
  const int per = 12 + 2 * mat, k = 2 * cx.w + (cx.lane >> 4), ia = per * cx.m + k, ib = per * cx.m + min(k + 8, per - 1);
  float v[4];
  poll_msgs2(base + (cx.lane & 15) * 224 + ia, base + (cx.lane & 15) * 224 + ib, v, tag);
#pragma unroll 1
  for (int d = 1; d < 16; d *= 2)
#pragma unroll
    for (int e = 0; e < 4; e++) v[e] += __shfl_xor_sync(0xffffffffu, v[e], d);
  const bool hi = cx.lane & 1;
  if ((cx.lane & 14) == 0) st_msg(base + 16 * 224 + (hi ? ib : ia), __float_as_uint(hi ? v[2] : v[0]), __float_as_uint(hi ? v[3] : v[1]), 0u, tag);
}
__device__ __forceinline__ void colsum_gather(const Params& p, const Ctx& cx, int mat, uint32_t tag) {
  const uint4* base = p.g->csp + ((mat * 8 + cx.n) * 17 + 16) * 224;
  const int ia = cx.w * 32 + cx.lane, ib = min(ia + 128, 191 + 32 * mat);
  float v[4];
  poll_msgs2(base + ia, base + ib, v, tag);
  const uint32_t tab = cx.sb + (mat ? OFF_CSF : OFF_CSQ);
  sts_f2(tab + (ia << (3 + mat)), v[0], v[1]);
  sts_f2(tab + (ib << (3 + mat)), v[2], v[3]);
}

#define ACC(q, j, e) acc[(q) & 1][4 * (j) + 2 * ((q) >> 1) + (e)]

constexpr uint32_t RING16 = RING_UNITS * (UNIT >> 4);
__device__ __forceinline__ bool tile_split(int i) { return (0xD98 >> i) & 1; }

__device__ __forceinline__ void write_run_desc(uint32_t sb, int i, int step) {
  const int layer = i >= 7, t = i - 7 * layer, part = tile_split(i) ? step : 2;
  const bool wide = tile_wide(t), own = t != 2 && t != 6 && part != 1 && i != 0, second = t == 1 || t == 4;
  const uint32_t z16 = (wide ? 5 : 4) * (UNIT >> 4), a_off = z16 - 1024 + (uint32_t)DESC_A - (uint32_t)DESC_B;
  const int gl = 16 * t + (part == 2 ? 0 : second ? 16 * part - 14 : 4 * part), g0 = layer * STAGES_PER_LAYER + gl;
  const uint32_t s16 = (sb & 0x3FFFF) >> 4, bfirst = (uint32_t)DESC_B + s16;
  const int nkb = t == 6 ? 56 : part == 0 ? 2 : 12 + 2 * part;
  const bool win1 = t == 1 && part != 0;
  const int win = layer ? WIN1 : WIN0;
  const int run = win1 ? win + 1 : t == 2 ? WIN2 + 1 : nkb;
  const int rest = win1 ? 64 | (nkb - 1 - SKEW - win) : t == 2 ? 64 | (7 - WIN2) | (8 << 7) : 0;
  const uint32_t blo = bfirst + z16 * (wide ? (gl + (t == 5 ? 3 : 0)) & 3 : (gl + 3) % 5);
  const uint32_t alo = own ? (uint32_t)DESC_A + s16 + (OFF_X >> 4) : blo + a_off;
  const uint32_t aoff = own ? alo + 1024 - (blo == bfirst + RING16 - z16 ? bfirst : blo + z16) : a_off;
  const bool xwait = part == 0 && !second, keep = !(part == 0 || t == 5);
  sts_u4(sb + OFF_RUN + (2 * i + step) * 16, blo, alo, aoff,
         ((g0 / NBAR) & 1) | xwait << 1 | keep << 2 | 8 * (g0 % NBAR) | run << 6 | rest << 12);
}

__device__ __forceinline__ void write_partial_stats(const Params& p, const Ctx& c, int ln, uint32_t tag) {
  const uint32_t xrow = c.sb + OFF_X + c.w * 4096 + c.lane * 128;
  float s = 0.f, q = 0.f, s1 = 0.f, q1 = 0.f;
#pragma unroll 4
  for (int j = 0; j < 16; j++) {
    uint32_t u[4];
    lds_u4(xrow + (j >> 3) * 16384 + (((j & 7) ^ (c.lane & 7)) << 4), u[0], u[1], u[2], u[3]);
#pragma unroll
    for (int e = 0; e < 4; e++) {
      const float a = bf_lo(u[e]), d = bf_hi(u[e]);
      s += a; q = fmaf(a, a, q);
      s1 += d; q1 = fmaf(d, d, q1);
    }
  }
  s += s1;
  q += q1;
  st_msg(p.g->stats + (ln * 8 + c.n) * SEQ + 128 * c.m + 32 * c.w + c.lane, __float_as_uint(s),
         __float_as_uint(fmaxf(q - s * s * (1.f / 128.f), 0.f)), 0u, tag);
}

template <int QMASK, int J0 = 0, int J1 = 24>
__device__ __forceinline__ void rank1_update(const Params& p, float (&acc)[2][96], const Ctx& cx, int t) {
  float nm[4];
#pragma unroll
  for (int q = 0; q < 4; q++)
    if ((QMASK >> q) & 1) nm[q] = t == 6 ? 1.f : -lds_f(cx.sb + OFF_ROW + (32 * cx.w + 8 * q + (cx.lane >> 2)) * 8 + 4);
  const uint32_t ctab = cx.sb + OFF_CSQ + ((t & 3) * 192 + 2 * (cx.lane & 3)) * 4;
#pragma unroll
  for (int j = J0; j < J1; j++) {
    const float2 cs = lds_f2(ctab + j * 32);
#pragma unroll
    for (int q = 0; q < 4; q++) {
      if (!((QMASK >> q) & 1)) continue;
      const int k = 4 * j + q - 1;
      const float nq = QMASK == 15 && k >= 0 ? chain(nm[q], __float_as_uint(ACC(k & 3, k >> 2, 1)), p.zero) : nm[q];
      ACC(q, j, 0) = fmaf(nq, cs.x, ACC(q, j, 0));
      ACC(q, j, 1) = fmaf(nq, cs.y, ACC(q, j, 1));
    }
  }
}

template <int QMASK, int SEC>
__device__ __forceinline__ void pack_qkv(const float (&acc)[2][96], uint32_t (&F)[3][4][8]) {
#pragma unroll
  for (int q = 3; q >= 0; q--)
#pragma unroll
    for (int j = 0; j < 8; j++) {
      if (!((QMASK >> q) & 1)) continue;
      const uint32_t u = pack_bf16(ACC(q, 8 * SEC + j, 0), ACC(q, 8 * SEC + j, 1));
      F[SEC][q][j] = SEC == 2 ? movtrans(u) : u;
    }
}
template <int K0, int K1>
__device__ __forceinline__ void send_halo(const Params& p, const uint32_t (&F)[3][4][8], const Ctx& cx, int layer, int t) {
  uint32_t E[18];
#pragma unroll
  for (int j = 0; j < 8; j++) { E[j] = F[1][3][j]; E[8 + j] = F[2][3][j]; }
  if (cx.w < 2) {
#pragma unroll
    for (int k = K0; k < K1; k++)
      if (k < 4) sts_u4(cx.sb + OFF_STG + cx.w * 2048 + cx.lane * 16 + k * 512, E[4 * k], E[4 * k + 1], E[4 * k + 2], E[4 * k + 3]);
  } else {
    uint4* dst = p.g->halo + (((layer * 2 + t) * 16 + cx.m) * 8 + cx.n) * 384 + (cx.w & 1) * 192 + cx.lane;
    const uint32_t tag = lds_u(cx.sb + OFF_TAG);
    if (K1 == 6) {
      const float4 r = lds_f4(cx.sb + OFF_ROW + (32 * cx.w + 24 + 2 * (cx.lane & 3)) * 8);
      E[16] = __float_as_uint(r.x);
      E[17] = __float_as_uint(r.z);
    }
#pragma unroll
    for (int k = K0; k < K1; k++) st_msg(dst + k * 32, E[3 * k], E[3 * k + 1], E[3 * k + 2], tag);
  }
}

__device__ __forceinline__ void attn_scores(const uint32_t* qa, const uint32_t* qb, const uint32_t* kp, const uint32_t* ka,
                                            const uint32_t* kb, float (&l)[4], const float4& zero, const bool (&early)[2]) {
  float s[3][4];
#pragma unroll
  for (int x = 0; x < 3; x++) {
    const uint32_t* kk = x == 0 ? kp : x == 1 ? ka : kb;
    asm volatile("mma.sync.aligned.m16n8k16.row.col.f32.bf16.bf16.f32 {%0,%1,%2,%3}, {%4,%5,%6,%7}, {%8,%9}, {%10,%11,%12,%13};"
                 : "=f"(s[x][0]), "=f"(s[x][1]), "=f"(s[x][2]), "=f"(s[x][3])
                 : "r"(qa[0]), "r"(qb[0]), "r"(qa[1]), "r"(qb[1]), "r"(kk[0]), "r"(kk[1]), "f"(zero.x), "f"(zero.y),
                   "f"(zero.z), "f"(zero.w));
  }
#pragma unroll
  for (int x = 0; x < 3; x++) {
    const uint32_t* kk = x == 0 ? kp : x == 1 ? ka : kb;
    mma16816(s[x], qa[2], qb[2], qa[3], qb[3], kk[2], kk[3]);
  }
#pragma unroll
  for (int e = 0; e < 2; e++) {
    l[e] = early[e] ? s[0][e] : s[1][e];
    l[2 + e] = early[e] ? s[1][2 + e] : s[2][2 + e];
  }
}

__device__ __forceinline__ void attn_mix(const float (&l)[4], const float (&sc)[4], const float (&off)[4], const float (&rk)[4],
                                         const uint32_t* vp, const uint32_t* va, const uint32_t* vb, float (&o)[4][4],
                                         float (&sum)[2], uint32_t mask, uint32_t zero) {
  float x[4];
#pragma unroll
  for (int e = 0; e < 4; e++) x[e] = fmaf(l[e], sc[e], off[e]);
  const float ml = quad_max(fmaxf(x[0], x[1])), mh = quad_max(fmaxf(x[2], x[3]));
  x[0] = ex2(x[0] - ml); x[1] = ex2(x[1] - ml);
  x[2] = ex2(x[2] - mh); x[3] = ex2(x[3] - mh);
  sum[0] = x[0] + x[1];
  sum[1] = x[2] + x[3];
  const uint32_t pl = pack_bf16(x[0] * rk[0], x[1] * rk[1]), ph = pack_bf16(x[2] * rk[2], x[3] * rk[3]);
  const uint32_t a0 = pl & ~mask, a1 = ph & mask, a2 = pl & zero, a3 = ph & ~mask, c0 = pl & mask, c1 = ph & zero;
#pragma unroll
  for (int jn = 0; jn < 4; jn++) {
    o[jn][0] = o[jn][1] = o[jn][2] = o[jn][3] = 0.f;
    mma16816(o[jn], a0, a1, a2, a3, va[jn], vb[jn]);
  }
#pragma unroll
  for (int jn = 0; jn < 4; jn++) mma1688(o[jn], c0, c1, vp[jn]);
}

template <int t>
__device__ __forceinline__ void attn_epilogue(const Params& p, float (&acc)[2][96], uint32_t (&F)[3][4][8], const Ctx& cx, int layer, uint32_t tag) {
  UNPACK_CTX(cx);
  const uint32_t ktab = sb + OFF_ROW + (32 * w + 2 * (lane & 3)) * 8, exc = sb + OFF_STG + (w & 1) * 2048 + lane * 16;
  uint4* const halo = p.g->halo + (((layer * 2 + t) * 16 + m) * 8 + n) * 384 + (w & 1) * 192;
  (void)wg;
  uint32_t(&Q)[4][8] = F[0], (&K)[4][8] = F[1], (&V)[4][8] = F[2], P[18];
  float kr[5][2], qr[4];
  bar_arrive(BAR_PAIR + w, 64);
  if (layer == 0 && t == 1) {
    rank1_update<7, 8, 24>(p, acc, cx, 1);
    rank1_update<31, 0, 8>(p, acc, cx, 1);
  }
#pragma unroll
  for (int q = 0; q < 4; q++) {
    qr[q] = lds_f(sb + OFF_ROW + (32 * w + 8 * q + (lane >> 2)) * 8) * (0.17677669529663687f * 1.4426950408889634f);
    const float4 r = lds_f4(ktab + 64 * q);
    kr[1 + q][0] = r.x;
    kr[1 + q][1] = r.z;
  }
  pack_qkv<7, 1>(acc, F);
  uint32_t tg[6];
#pragma unroll
  for (int k = 0; k < 6; k++) {
    tg[k] = ~tag;
    if (t == 1)
      asm volatile("{\n.reg .b128 v;\n.reg .pred g;\nsetp.ne.u32 g, %5, 0;\nmov.b128 v, {%6, %6, %6, %6};\n"
                   "@g ld.relaxed.gpu.global.b128 v, [%4];\nmov.b128 {%0, %1, %2, %3}, v;\n}"
                   : "=r"(P[3 * k]), "=r"(P[3 * k + 1]), "=r"(P[3 * k + 2]), "=r"(tg[k])
                   : "l"(halo - 8 * 384 + k * 32 + lane), "r"((uint32_t)(w < 2 && m > 0) | ((K[0][7] | K[1][7] | K[2][7]) & p.zero)), "r"(~tag) : "memory");
  }
  pack_qkv<7, 2>(acc, F);
  pack_qkv<15, 0>(acc, F);
  bar_sync(BAR_PAIR + (w ^ 2), 64);
  if (w >= 2 || m == 0) {
#pragma unroll
    for (int k = 0; k < 4; k++) lds_u4(exc + k * 512, P[4 * k], P[4 * k + 1], P[4 * k + 2], P[4 * k + 3]);
    const float4 r = lds_f4(ktab - (w >> 1) * 320);
    P[16] = __float_as_uint(r.x);
    P[17] = __float_as_uint(r.z);
  } else {
    if ((m & 1) && t == 0) __nanosleep(HALO_NS);
#pragma unroll 1
    for (int it = 0; it < MSG_SPINS; it++) {
      if (t == 0 || it > 0) {
        if (it > 0 || !(m & 1)) poll_line(reinterpret_cast<const uint32_t*>(halo - 8 * 384 + 191) + 3, tag, 1u);
#pragma unroll
        for (int k = 0; k < 6; k++) ld_msg(halo - 8 * 384 + k * 32 + lane, P[3 * k], P[3 * k + 1], P[3 * k + 2], tg[k]);
      }
      uint32_t bad = 0;
#pragma unroll
      for (int k = 0; k < 6; k++) bad |= tg[k] ^ tag;
      if (__all_sync(0xffffffffu, bad == 0)) break;
    }
  }
  kr[0][0] = __uint_as_float(P[16]);
  kr[0][1] = __uint_as_float(P[17]);
  const bool early[2] = {2 * (lane & 3) > (lane >> 2), 2 * (lane & 3) + 1 > (lane >> 2)};
  const uint32_t mask = (early[0] ? 0xffffu : 0u) | (early[1] ? 0xffff0000u : 0u);
  float rk[2][4], sc[2][4], off[2][4];
#pragma unroll
  for (int g = 0; g < 2; g++) {
#pragma unroll
    for (int e = 0; e < 4; e++) {
      const int q = 2 * g + (e >> 1);
      const bool masked = q == 0 && m == 0 && w < 2 && early[e & 1];
      rk[g][e] = early[e & 1] ? kr[q][e & 1] : kr[q + 1][e & 1];
      sc[g][e] = masked ? 0.f : rk[g][e] * qr[q];
      off[g][e] = masked ? -1e30f : 0.f;
    }
  }
  if (w == 0 && elect_one()) asm volatile("prefetch.tensormap [%0];" ::"l"(&p.t.att_st) : "memory");
  bar_sync(BAR_GO, 256);
  const float4 zero = lds_f4(sb + OFF_ZERO);
  float l[2][2][4], o[2][2][4][4], sum[2][2][2];
#pragma unroll
  for (int h = 0; h < 2; h++) {
    if (h == 1) {
      Q[2][4] |= __float_as_uint(l[1][0][0]) & p.zero;
      Q[0][4] |= __float_as_uint(l[0][0][0]) & p.zero;
    }
    attn_scores(&Q[2][4 * h], &Q[3][4 * h], &K[1][4 * h], &K[2][4 * h], &K[3][4 * h], l[1][h], zero, early);
    attn_scores(&Q[0][4 * h], &Q[1][4 * h], &P[4 * h], &K[0][4 * h], &K[1][4 * h], l[0][h], zero, early);
  }
  const uint32_t stg = sb + OFF_STG + w * 4096, srow = stg + lane * 128 + ((lane & 7) << 4);
#pragma unroll
  for (int h = 0; h < 2; h++) {
    attn_mix(l[1][h], sc[1], off[1], rk[1], &V[1][4 * h], &V[2][4 * h], &V[3][4 * h], o[1][h], sum[1][h], mask, p.zero);
    attn_mix(l[0][h], sc[0], off[0], rk[0], &P[8 + 4 * h], &V[0][4 * h], &V[1][4 * h], o[0][h], sum[0][h], mask, p.zero);
  }
  if (t == 0 && p.zero == 0) {
    uint32_t dep = 0;
#pragma unroll
    for (int k = 0; k < 16; k++) dep |= __float_as_uint(o[k >> 3][(k >> 2) & 1][k & 3][0]);
    bar_arrive(BAR_DONE | (dep & __float_as_uint(zero.x)), 256);
  }
#pragma unroll
  for (int h = 0; h < 2; h++) {
    float inv[4];
#pragma unroll
    for (int q = 0; q < 4; q++) inv[q] = rcp_hw(quad_sum(sum[q >> 1][h][q & 1]));
#pragma unroll
    for (int j = 0; j < 4; j++) {
      const float(&a)[4] = o[0][h][j];
      const float(&c)[4] = o[1][h][j];
      stsm4(srow ^ ((4 * h + j) << 4), pack_bf16(a[0] * inv[0], a[1] * inv[0]), pack_bf16(a[2] * inv[1], a[3] * inv[1]),
            pack_bf16(c[0] * inv[2], c[1] * inv[2]), pack_bf16(c[2] * inv[3], c[3] * inv[3]));
    }
  }
  if (t == 1) bar_arrive(BAR_DONE, 256);
  fence_async_smem();
  __syncwarp();
  if (lane == 0) {
    tma_st2(&p.t.att_st, stg, 128 * n + 64 * t, 128 * m + 32 * w);
    bulk_commit();
  }
}

__device__ __forceinline__ void finish_stores(uint32_t sb, int i) {
  const int t = i >= 7 ? i - 7 : i;
  if ((threadIdx.x & 31) == 0) {
    bulk_wait_all();
    mbar_arrive(sb + BAR_PUB + 8 * (t < 2 ? t : t + 1));
  }
  __syncwarp();
  if (i < 12) bar_arrive(BAR_GUARD + ((i & 1) ^ 1), 256);
}

template <int N>
__device__ __forceinline__ bool mainloop(const Params& p, float (&acc)[2][96], uint32_t sb, int i, int step, int mn) {
  constexpr uint32_t Z16 = (2 + N / 64) * (UNIT >> 4);
  constexpr uint32_t A_OFF = Z16 - 1024 + (uint32_t)DESC_A - (uint32_t)DESC_B;
  const int wg = i & 1;
  const uint32_t s16 = (sb & 0x3FFFF) >> 4;
  const uint32_t blast = (uint32_t)DESC_B + s16 + RING16 - Z16, flast = sb + BAR_FULL + 8 * (NBAR - 1);
  uint32_t blo = (uint32_t)DESC_B + s16, alo = blo + A_OFF, aoff = A_OFF, misc = 16 << 6;
  if (N == 128 || i > 0) lds_u4(sb + OFF_RUN + (2 * i + step) * 16, blo, alo, aoff, misc);
  uint32_t keep = misc & 4;
  int run = (misc >> 6) & 63, rest = misc >> 12;
  uint32_t fb = sb + BAR_FULL + (misc & 0x38), ph = misc & 1;
  uint32_t prev = sb + BAR_DUMMY - 8 * NBAR;
  const uint32_t lane_id = __popc(__ballot_sync(0xffffffffu, true) & lanemask_lt()), rel = pair_offset(sb, lane_id & 1) + 8 * NBAR;
  pin_regs<N / 2>(acc);
  if (N == 128 || i > 0) bar_sync(BAR_ORDER + wg, 256);
  else bar_sync(BAR_INIT0, 160);
  mbar_wait(fb, ph);
  if (N == 192 && i == 0) cluster_wait();
  if (misc & 2) mbar_wait(sb + BAR_XGO, N == 192);
#pragma unroll 1
  while (true) {
    const uint64_t da = (DESC_A & ~0xffffffffull) | alo, db = (DESC_B & ~0xffffffffull) | blo;
    asm volatile("wgmma.fence.sync.aligned;" ::: "memory");
    wgmma_ss<N>(acc[0], da, db, keep);
    wgmma_ss<N>(acc[1], da + 64, db, keep);
    keep = 4;
    wgmma_ss<N>(acc[0], da + 2, db + 128);
    wgmma_ss<N>(acc[1], da + 66, db + 128);
    asm volatile("wgmma.commit_group.sync.aligned;" ::: "memory");
    asm volatile("wgmma.wait_group.sync.aligned 1;" ::: "memory");
    if (lane_id < 2) mbar_arrive_cluster(prev + rel);
    prev = fb;
    if (fb == flast) { fb -= 8 * NBAR; ph++; }
    fb += 8;
    if (blo == blast) blo -= RING16;
    blo += Z16;
    alo = blo + aoff;
    aoff = A_OFF;
    run--;
    const bool ready = mbar_test(fb, ph) && run != 0;
    asm volatile("wgmma.fence.sync.aligned;" ::: "memory");
    wgmma_ss<N>(acc[0], da + 4, db + 4 * N);
    wgmma_ss<N>(acc[1], da + 68, db + 4 * N);
    wgmma_ss<N>(acc[0], da + 6, db + 4 * N + 128);
    wgmma_ss<N>(acc[1], da + 70, db + 4 * N + 128);
    asm volatile("wgmma.commit_group.sync.aligned;" ::: "memory");
    if (!ready) {
      bool window = false;
      if (run == 0) {
        if (rest == 0) break;
        window = rest & 64;
        if (window) bar_arrive(BAR_GO, 256);
        else alo = (uint32_t)DESC_A + s16 + (OFF_STG >> 4);
        run = rest & 63;
        rest >>= 7;
      }
      mbar_wait(fb, ph);
      if (window) bar_sync(BAR_DONE, 256);
    }
  }
  if constexpr (N == 192) {
    if (misc >> 12) {
      const Ctx cx = make_ctx(sb, mn);
      uint32_t F[3][4][8];
      const uint32_t fb0 = fb, blo0 = blo;
#pragma unroll 1
      for (int x = 0; x < SKEW; x++) {
        const uint64_t da = (DESC_A & ~0xffffffffull) | (blo + A_OFF + 64), db = (DESC_B & ~0xffffffffull) | blo;
        mbar_wait(fb, ph);
        asm volatile("wgmma.fence.sync.aligned;" ::: "memory");
#pragma unroll
        for (int k = 0; k < 4; k++) wgmma_ss<N>(acc[1], da + 2 * k, db + (k >> 1) * 4 * N + (k & 1) * 128);
        asm volatile("wgmma.commit_group.sync.aligned;" ::: "memory");
        asm volatile("wgmma.wait_group.sync.aligned 1;" ::: "memory");
        if (x == 0) {
          if (lane_id < 2) mbar_arrive_cluster(prev + rel);
          bar_sync(BAR_GUARD + wg, 256);
        }
        if (fb == flast) { fb -= 8 * NBAR; ph++; }
        fb += 8;
        blo += Z16;
      }
      fb = fb0;
#pragma unroll
      for (int u = 0; u < 2 * SKEW; u++) {
        const uint64_t da = (DESC_A & ~0xffffffffull) | (blo0 + (u >> 1) * Z16 + A_OFF + 4 * (u & 1));
        const uint64_t db = (DESC_B & ~0xffffffffull) | (blo0 + (u >> 1) * Z16 + 4 * N * (u & 1));
        asm volatile("wgmma.fence.sync.aligned;" ::: "memory");
        wgmma_ss<N>(acc[0], da, db);
        wgmma_ss<N>(acc[0], da + 2, db + 128);
        asm volatile("wgmma.commit_group.sync.aligned;" ::: "memory");
        if (u == 2 * SKEW - 1) break;
        asm volatile("wgmma.wait_group.sync.aligned 1;" ::: "memory");
        if (u == 0) {
#pragma unroll
          for (int r = 0; r < 96; r++) asm volatile("" : "+f"(acc[1][r])::"memory");
        }
        if (u == 2 || u == 4) {
          if (lane_id < 2) mbar_arrive_cluster(fb + rel);
          fb = fb == flast ? fb - 8 * (NBAR - 1) : fb + 8;
        }
        if (u == 0) { if (i == 1) rank1_update<8, 8, 24>(p, acc, cx, 1); pack_qkv<8, 2>(acc, F); pack_qkv<8, 1>(acc, F); }
        if (u == 1) send_halo<0, 3>(p, F, cx, i >= 7, 1);
        if (u == 2) send_halo<3, 6>(p, F, cx, i >= 7, 1);
      }
      bar_arrive(BAR_ORDER + (wg ^ 1), 256);
      asm volatile("wgmma.wait_group.sync.aligned 0;" ::: "memory");
#pragma unroll
      for (int r = 0; r < 96; r++) asm volatile("" : "+f"(acc[0][r])::"memory");
      if (lane_id < 2) mbar_arrive_cluster(fb + rel);
      attn_epilogue<1>(p, acc, F, cx, i >= 7, lds_u(sb + OFF_TAG));
      finish_stores(sb, i);
#pragma unroll
      for (int r = 0; r < 192; r++)
        asm volatile("{\n.reg .b32 t;\nxor.b32 t, %1, %2;\nmov.b32 %0, t;\n}" : "=f"(acc[r & 1][r >> 1]) : "r"(lane_id), "r"(r + 64));
      return true;
    }
  }
  if (i < 13) bar_arrive(BAR_ORDER + (wg ^ 1), 256);
  if (N == 128 && ((0x2244 >> i) & 1)) {
    const Ctx cx = make_ctx(sb, mn);
    const uint32_t xrow = cx.sb + OFF_X + cx.w * 4096 + cx.lane * 128 + ((cx.lane & 7) << 4);
    const bool leader = elect_one();
    asm volatile("wgmma.wait_group.sync.aligned 0;" ::: "memory");
    pin_regs<64>(acc);
#pragma unroll
    for (int h = 0; h < 2; h++) {
      if (h == 1 && p.zero != 0) break;
#pragma unroll
      for (int j = 8 * h; j < 8 * h + 8; j++)
        stsm4((xrow ^ ((j & 7) << 4)) + h * 16384, pack_bf16(ACC(0, j, 0), ACC(0, j, 1)), pack_bf16(ACC(1, j, 0), ACC(1, j, 1)),
              pack_bf16(ACC(2, j, 0), ACC(2, j, 1)), pack_bf16(ACC(3, j, 0), ACC(3, j, 1)));
      fence_async_smem();
      __syncwarp();
      if (leader) {
        mbar_arrive(sb + BAR_XRDY + 8 * h);
        if (i == 13) {
          tma_st_warp(&p.t.out_w, cx.sb + OFF_X + h * 16384 + cx.w * 4096, 128 * cx.n + 64 * h, cx.m, cx.w);
          bulk_commit();
          if (h == 1) bulk_wait_read();
        }
      }
      if (h == 0 && lane_id < 2 && i < 13) mbar_arrive_cluster(prev + rel);
    }
    if (i == 2 || i == 9) write_partial_stats(p, cx, (i + 3) >> 2, lds_u(sb + OFF_TAG));
    return true;
  }
  asm volatile("wgmma.wait_group.sync.aligned 0;" ::: "memory");
  pin_regs<N / 2>(acc);
  if (lane_id < 2) mbar_arrive_cluster(prev + rel);
  return false;
}

__device__ __forceinline__ void finish_row_stats(const Params& p, const Ctx& c, int ln, uint32_t tag) {
  const uint4* src = p.g->stats + ln * 8 * SEQ + 128 * c.m + 32 * c.w + c.lane;
  uint32_t ps[8], pm[8];
#pragma unroll 1
  for (int it = 0; it < MSG_SPINS; it++) {
    uint32_t bad = 0, u, tg;
    if (ln == 2 || it > 0) __nanosleep(STAT_NS);
#pragma unroll
    for (int k = 0; k < 8; k++) { ld_msg(src + k * SEQ, ps[k], pm[k], u, tg); bad |= tg ^ tag; }
    if (__all_sync(0xffffffffu, bad == 0)) break;
  }
  float s = 0.f, m2 = 0.f;
#pragma unroll
  for (int k = 0; k < 8; k++) s += __uint_as_float(ps[k]);
  const float mean = s * (1.f / DM);
#pragma unroll
  for (int k = 0; k < 8; k++) {
    const float d = __uint_as_float(ps[k]) * (1.f / 128.f) - mean;
    m2 += fmaf(128.f * d, d, __uint_as_float(pm[k]));
  }
  sts_f2(c.sb + OFF_ROW + (32 * c.w + c.lane) * 8, rsqrtf(m2 * (1.f / DM) + 1e-5f), mean);
  __syncwarp();
}

__device__ __forceinline__ void gelu_epilogue(const Params& p, float (&acc)[2][96], const Ctx& cx, int t) {
  UNPACK_CTX(cx);
  (void)wg;
  float rs[4], rm[4];
#pragma unroll
  for (int q = 0; q < 4; q++) {
    const float2 v = lds_f2(sb + OFF_ROW + (32 * w + 8 * q + (lane >> 2)) * 8);
    rs[q] = 0.5f * v.x;
    rm[q] = -rs[q] * v.y;
  }
  const int col0 = 128 * (t - 3);
  const uint32_t stg = sb + OFF_STG + w * 4096;
  const uint32_t ctab = sb + OFF_CSF + (col0 / 2 + (lane & 3)) * 16, srow = stg + lane * 128 + ((lane & 7) << 4);
  if (t == 5) __nanosleep(STAG_NS * w);
  float4 nb = lds_f4(ctab);
#pragma unroll
  for (int c = 0; c < 3; c++) {
    if (c == 2 && t != 5) break;
    uint32_t hp[8][4];
#pragma unroll
    for (int j = 0; j < 8; j++) {
      const float4 cb = nb;
      if (8 * c + j < 23) nb = lds_f4(ctab + (8 * c + j + 1) * 64);
#pragma unroll
      for (int q = 0; q < 4; q++) {
        float y[2];
        const int k = 4 * j + q - GELU_DEP;
        const float rmq = k >= 0 ? chain(rm[q], hp[k >> 2][k & 3], p.zero) : rm[q];
#pragma unroll
        for (int e = 0; e < 2; e++) {
          const float z = fmaf(ACC(q, 8 * c + j, e), rs[q], fmaf(rmq, e ? cb.y : cb.x, e ? cb.w : cb.z));
          const float u = z * fmaf(z * z, 8.f * 0.7978845608028654f * 0.044715f, 2.f * 0.7978845608028654f);
          y[e] = fmaf(z, tanh_hw(u), z);
        }
        hp[j][q] = pack_bf16(y[0], y[1]);
      }
      if (j == STG_WAIT && c > 0) {
        if (lane == 0) bulk_wait_read();
        __syncwarp();
      }
      if (c == 0 || j > STG_WAIT) {
        stsm4(srow ^ (j << 4), hp[j][0], hp[j][1], hp[j][2], hp[j][3]);
      } else if (j == STG_WAIT) {
#pragma unroll
        for (int jj = 0; jj <= STG_WAIT; jj++) stsm4(srow ^ (jj << 4), hp[jj][0], hp[jj][1], hp[jj][2], hp[jj][3]);
      }
    }
    fence_async_smem();
    __syncwarp();
    if (lane == 0) {
      tma_st2(&p.t.h_st, stg, 448 * n + col0 + 64 * c, 128 * m + 32 * w);
      bulk_commit();
    }
  }
#pragma unroll
  for (int r = 0; r < 16; r++) acc[0][r] = acc[1][r] = 0.f;
}

__device__ __forceinline__ bool consumer_tile(const Params& p, float (&acc)[2][96], uint32_t sb0, int i, int mn) {
  const int layer = i >= 7, t = i - 7 * layer, wg = i & 1;
  const bool resid = t == 2 || t == 6;
  {
    if (resid) {
      const Ctx cx = make_ctx(sb0, mn);
      const uint32_t xrow = cx.sb + OFF_X + cx.w * 4096 + cx.lane * 128;
      const uint32_t sel_lo = 0x1044u | p.zero, sel_hi = 0x3244u | p.zero;
#pragma unroll
      for (int j = 0; j < 16; j++) {
        uint32_t r[4];
        ldsm4(xrow + (j >> 3) * 16384 + (((j & 7) ^ (cx.lane & 7)) << 4), r[0], r[1], r[2], r[3]);
#pragma unroll
        for (int q = 0; q < 4; q++) {
          ACC(q, j, 0) = prmt_f(r[q], sel_lo);
          ACC(q, j, 1) = prmt_f(r[q], sel_hi);
        }
      }
    }
    if (t >= 5 || i == 7) finish_stores(sb0, i - 2);
#pragma unroll 1
    for (int step = !tile_split(i);; step++) {
      if (step == 1 && (t == 1 || t == 4)) {
        const Ctx cx = make_ctx(sb0, mn);
        if (i == 1) {
          const uint32_t epoch = __ldcg(p.g->epoch + (mn & 127));
          cluster_wait();
          asm volatile("st.shared.u32 [%0], %1;" ::"r"(sb0 + OFF_TAG), "r"(epoch + 1) : "memory");
        }
        const uint32_t tag = lds_u(cx.sb + OFF_TAG);
        const int ln = (i + 1) >> 2;
#pragma unroll 1
        for (int r = 0; r < 2; r++) {
          if (i == 1) {
            if (cx.w < 3) {
              float a[8] = {0.f, 0.f, 0.f, 0.f, 0.f, 0.f, 0.f, 0.f};
              mbar_wait(sb0 + BAR_CSLD, r);
#pragma unroll 1
              for (int h = 0; h < 2; h++) sum_rows(cx.sb + OFF_STG + h * 12288 + cx.w * 4096, 4, a, cx.lane);
              publish_sums(a, p.g->csp + (cx.n * 17 + cx.m) * 224 + (3 * r + cx.w) * 32, cx.lane, tag);
            }
          }
          if (r == 1) break;
          if (i == 1) {
            bar_sync(BAR_WG + 1, 128);
            if (cx.w == 3 && elect_one()) {
              mbar_expect_tx(sb0 + BAR_CSLD, 24576);
              tma_ld3(sb0 + OFF_STG, &p.t.wqkv, sb0 + BAR_CSLD, 128 * cx.n + 64, 64 * cx.m, 0);
              tma_ld3(sb0 + OFF_STG + 12288, &p.t.wqkv, sb0 + BAR_CSLD, 128 * cx.n + 64, 64 * cx.m + 32, 0);
            }
            mbar_wait(sb0 + BAR_XRDY, 0);
            mbar_wait(sb0 + BAR_XRDY + 8, 0);
          }
          if (t == 1) write_partial_stats(p, cx, ln, tag);
        }
        if (i == 1) {
          bar_arrive(BAR_HLP, 160);
          bar_sync(BAR_INIT, 160);
        }
        if (i == 4) colsum_total(p, cx, 1, tag);
        if (i != 1) bar_sync(BAR_GUARD + wg, 256);
        finish_row_stats(p, cx, ln, tag);
        if (i == 4) {
          colsum_gather(p, cx, 1, tag);
          mbar_wait(sb0 + BAR_BIAS, 0);
        }
        bar_arrive(BAR_GUARD + (wg ^ 1), 256);
      }
      if (step == 2) bar_sync(BAR_GUARD + wg, 256);
      if (step == 2 && i == 0) {
        colsum_gather(p, make_ctx(sb0, mn), 0, lds_u(sb0 + OFF_TAG));
        bar_sync(BAR_WG, 128);
      }
      if ((t + step == 2 && i != 1) || t == 6) rank1_update<15>(p, acc, make_ctx(sb0, mn), t);
      if (step == 2) break;
      if (tile_wide(t)) {
        if (mainloop<192>(p, acc, sb0, i, step, mn)) return false;
      } else {
        if (mainloop<128>(p, acc, sb0, i, step, mn)) return false;
      }
    }
    if (t < 2) return true;
    gelu_epilogue(p, acc, make_ctx(sb0, mn), t);
    return false;
  }
}

template <bool BY_SMID>
__global__ void __cluster_dims__(2, 1, 1) __launch_bounds__(384, 1)
fused_layers_kernel(const Scalars scalars, const __grid_constant__ Maps maps) {
  if (threadIdx.x == 288 || threadIdx.x == 320)
    asm volatile("prefetch.tensormap [%0];" ::"l"(threadIdx.x == 288 ? &maps.xin : &maps.wqkv) : "memory");
  const Params p{scalars, maps};
  extern __shared__ __align__(1024) uint8_t smem_raw[];
  const uint32_t sb = uniform((uint32_t)__cvta_generic_to_shared(smem_raw));
  const int tid = threadIdx.x, lane = tid & 31, warp = uniform(tid >> 5), wg = warp >> 2, w = warp & 3;

  int mn;
  {
    int id = blockIdx.x;
    if (BY_SMID) asm volatile("mov.u32 %0, %%smid;" : "=r"(id));
    else if (id >= 120) id += 4;
    const int c = id >> 1;
    int g, j;
    if (c < 32) { g = c & 7; j = c >> 3; }
    else if (c < 60) { g = 1 + (c - 32) % 7; j = 4 + (c - 32) / 7; }
    else { g = 0; j = c - 58; }
    mn = (g * 2 + (blockIdx.x & 1)) * 8 + j;
    if (c == 60 || c == 61) {
      if (tid < 32) {
        const uint32_t tag = __ldcg(p.g->epoch + NCTA + (id & 3)) + 1;
#pragma unroll 1
        for (int mm = 0; mm < 16; mm++) poll_line(p.g->flags + mm * 32 + (lane & 7), 32 * tag, 0xffu);
        if (tid == 0) p.g->epoch[NCTA + (id & 3)] = tag;
      }
      return;
    }
  }
  const int m = mn >> 3, n = mn & 7;
  if (wg < 2) {
    cluster_arrive();
    asm volatile("setmaxnreg.inc.sync.aligned.u32 232;");
    const int id = mn | (warp << 7);
#pragma unroll 1
    for (int i = wg;; i += 2) {
      float acc[2][96];
#pragma unroll
      for (int r = 0; r < 96; r++) acc[0][r] = acc[1][r] = 0.f;
      pin_regs<96>(acc);
#pragma unroll 1
      while (!consumer_tile(p, acc, sb, i, id)) {
        i += 2;
        if (i >= 14) goto all_done;
      }
      const Ctx cx = make_ctx(sb, id);
      uint32_t F[3][4][8];
      pack_qkv<8, 2>(acc, F);
      pack_qkv<8, 1>(acc, F);
      send_halo<0, 6>(p, F, cx, i >= 7, 0);
      attn_epilogue<0>(p, acc, F, cx, i >= 7, lds_u(sb + OFF_TAG));
      finish_stores(sb, i);
    }
  all_done:
    if (wg == 0) {
      finish_stores(sb, 12);
    } else {
      cluster_arrive();
      cluster_wait();
    }
  } else {
    asm volatile("setmaxnreg.dec.sync.aligned.u32 40;");
    if (w != 0) {
      if (w == 1 && elect_one()) {
        mbar_init(sb + BAR_FULL + 32, 2);
#pragma unroll
        for (int k = 0; k < NBAR; k++) mbar_init(sb + BAR_EMPTY + 8 * k, 8);
#pragma unroll
        for (int k = 0; k < 3; k++) mbar_init(sb + BAR_XRDY + 8 * k, 4);
#pragma unroll
        for (int k = 0; k < 9; k++) mbar_init(sb + BAR_PUB + 8 * k, 4);
#pragma unroll
        for (int k = 0; k < 4; k++) mbar_init(sb + BAR_CSLD + 8 * k, 1);
        sts_f2(sb + OFF_ZERO, 0.f, 0.f);
        sts_f2(sb + OFF_ZERO + 8, 0.f, 0.f);
        asm volatile("fence.mbarrier_init.release.cluster;" ::: "memory");
      }
      __syncwarp();
      cluster_arrive();
      if (w == 2) {
        if (lane < 28) write_run_desc(sb, lane >> 1, lane & 1);
        bar_arrive(BAR_INIT, 160);
      }
      cluster_wait();
      if (w == 1) producer<true>(p, sb, m, n, lane);
      else if (w == 3) colsum_helper(p, sb, m, n, lane);
      else if (elect_one()) publisher(p, sb, m, n);
    } else {
      const bool leader = elect_one();
      if (leader) {
#pragma unroll
        for (int k = 0; k < 4; k++) mbar_init(sb + BAR_FULL + 8 * k, 2);
        asm volatile("fence.mbarrier_init.release.cluster;" ::: "memory");
      }
      __syncwarp();
      bar_arrive(BAR_INIT0, 160);
      cluster_arrive();
      if (leader) {
#pragma unroll 1
        for (int k = 0; k < 4; k++) {
          const uint32_t fb = sb + BAR_FULL + 8 * k;
          mbar_expect_tx(fb, 16384);
          tma_ld_act(sb + (5 * k + 3) * UNIT, &p.t.xin, fb, 64 * k, m);
          mbar_expect_tx(fb, 3 * UNIT);
          tma_ld3(sb + 5 * k * UNIT, &p.t.wqkv, fb, 128 * n, 64 * k, 0);
          tma_ld3(sb + 5 * k * UNIT + 12288, &p.t.wqkv, fb, 128 * n, 64 * k + 32, 0);
        }
      }
      __syncwarp();
      cluster_wait();
      producer<false>(p, sb, m, n, lane);
    }
  }
}

typedef CUresult (*EncodeFn)(CUtensorMap*, CUtensorMapDataType, cuuint32_t, void*, const cuuint64_t*, const cuuint64_t*,
                             const cuuint32_t*, const cuuint32_t*, CUtensorMapInterleave, CUtensorMapSwizzle,
                             CUtensorMapL2promotion, CUtensorMapFloatOOBfill);

void make_2d(EncodeFn enc, CUtensorMap* m, const void* ptr, uint64_t cols, uint64_t rows, uint32_t box_rows) {
  cuuint64_t d[2] = {cols, rows}, st[1] = {cols * 2};
  cuuint32_t b[2] = {64, box_rows}, e[2] = {1, 1};
  enc(m, CU_TENSOR_MAP_DATA_TYPE_BFLOAT16, 2, const_cast<void*>(ptr), d, st, b, e, CU_TENSOR_MAP_INTERLEAVE_NONE,
      CU_TENSOR_MAP_SWIZZLE_128B, CU_TENSOR_MAP_L2_PROMOTION_L2_128B, CU_TENSOR_MAP_FLOAT_OOB_FILL_NONE);
}
void make_act(EncodeFn enc, CUtensorMap* m, const void* ptr, uint64_t cols, bool split, uint32_t box = 2) {
  const uint64_t row = cols * 2;
  cuuint64_t d[4] = {cols, 32, 2, SEQ / 64}, st[3] = {split ? 2 * row : row, split ? row : 32 * row, 64 * row};
  cuuint32_t b[4] = {64, 32, box, box}, e[4] = {1, 1, 1, 1};
  enc(m, CU_TENSOR_MAP_DATA_TYPE_BFLOAT16, 4, const_cast<void*>(ptr), d, st, b, e, CU_TENSOR_MAP_INTERLEAVE_NONE,
      CU_TENSOR_MAP_SWIZZLE_128B, CU_TENSOR_MAP_L2_PROMOTION_L2_128B, CU_TENSOR_MAP_FLOAT_OOB_FILL_NONE);
}
void make_3d(EncodeFn enc, CUtensorMap* m, const void* ptr, uint64_t d0, uint64_t rows, uint64_t d2, uint64_t row_bytes,
             uint64_t chunk_bytes, uint32_t box_chunks) {
  cuuint64_t d[3] = {d0, rows, d2}, st[2] = {row_bytes, chunk_bytes};
  cuuint32_t b[3] = {64, 32, box_chunks}, e[3] = {1, 1, 1};
  enc(m, CU_TENSOR_MAP_DATA_TYPE_BFLOAT16, 3, const_cast<void*>(ptr), d, st, b, e, CU_TENSOR_MAP_INTERLEAVE_NONE,
      CU_TENSOR_MAP_SWIZZLE_128B, CU_TENSOR_MAP_L2_PROMOTION_L2_128B, CU_TENSOR_MAP_FLOAT_OOB_FILL_NONE);
}

}

extern "C" void kernel_launch(void* const* d_in, const int* in_sizes, int n_in, void* d_out, int out_size) {
  (void)in_sizes; (void)n_in; (void)out_size;
  static EncodeFn enc = nullptr;
  static void *att = nullptr, *hbuf = nullptr, *scratch = nullptr;
  static int by_smid = 0;
  if (!enc) {
    void* fn = nullptr;
    cudaDriverEntryPointQueryResult q;
    cudaGetDriverEntryPoint("cuTensorMapEncodeTiled", &fn, cudaEnableDefault, &q);
    enc = (EncodeFn)fn;
    cudaGetSymbolAddress(&att, g_att);
    cudaGetSymbolAddress(&hbuf, g_h);
    cudaGetSymbolAddress(&scratch, g_scratch);
    cudaFuncSetAttribute(fused_layers_kernel<true>, cudaFuncAttributeMaxDynamicSharedMemorySize, SMEM_BYTES);
    cudaFuncSetAttribute(fused_layers_kernel<false>, cudaFuncAttributeMaxDynamicSharedMemorySize, SMEM_BYTES);
    int sms = 0, clusters = 0, dev = 0;
    cudaGetDevice(&dev);
    cudaDeviceGetAttribute(&sms, cudaDevAttrMultiProcessorCount, dev);
    cudaLaunchConfig_t cfg = {};
    cfg.gridDim = dim3(132);
    cfg.blockDim = dim3(384);
    cfg.dynamicSmemBytes = SMEM_BYTES;
    cudaLaunchAttribute at[1];
    at[0].id = cudaLaunchAttributeClusterDimension;
    at[0].val.clusterDim.x = 2; at[0].val.clusterDim.y = 1; at[0].val.clusterDim.z = 1;
    cfg.attrs = at;
    cfg.numAttrs = 1;
    if (cudaOccupancyMaxActiveClusters(&clusters, fused_layers_kernel<true>, &cfg) != cudaSuccess) (void)cudaGetLastError();
    by_smid = sms == 132 && clusters == 66;
  }
  Maps p;
  Scalars sc;
  make_act(enc, &p.xin, d_in[0], DM, true);
  make_act(enc, &p.out, d_out, DM, true);
  make_act(enc, &p.out_w, d_out, DM, true, 1);
  make_act(enc, &p.att, att, DM, false);
  make_act(enc, &p.h, hbuf, FF, false);
  make_2d(enc, &p.att_st, att, DM, SEQ, 32);
  make_2d(enc, &p.h_st, hbuf, FF, SEQ, 32);
  make_2d(enc, &p.w1c, d_in[4], FF, DM, 32);
  make_3d(enc, &p.wqkv, d_in[1], DM, DM, 3, 3 * DM * 2, DM * 2, 3);
  make_3d(enc, &p.wo, d_in[2], 64, DM, DM / 64, DM * 2, 128, 2);
  make_3d(enc, &p.w1a, d_in[4], 64, DM, FF / 64, FF * 2, 128, 3);
  make_3d(enc, &p.w1b, d_in[4], 64, DM, FF / 64, FF * 2, 128, 2);
  make_3d(enc, &p.w2, d_in[6], 64, FF, DM / 64, DM * 2, 128, 2);
  sc.b1 = (const __nv_bfloat16*)d_in[5];
  sc.b2 = (const __nv_bfloat16*)d_in[7];
  sc.g = (Scratch*)scratch;
  sc.zero = 0;
  if (by_smid) fused_layers_kernel<true><<<132, 384, SMEM_BYTES>>>(sc, p);
  else fused_layers_kernel<false><<<NCTA, 384, SMEM_BYTES>>>(sc, p);
}
```

```cpp
#include <cuda_runtime.h>
#include <cuda_bf16.h>
#include <cuda.h>
#include <stdint.h>
#include <type_traits>

namespace {

constexpr int SEQ = 2048, DM = 1024, FF = 3584;
constexpr int NCTA = 128;
constexpr int NBAR = 5;

constexpr uint32_t RING_UNITS = 20, UNIT = 8192;
constexpr uint32_t OFF_X   = RING_UNITS * UNIT;
constexpr uint32_t OFF_STG = OFF_X + 32768;
constexpr uint32_t OFF_HLP = OFF_STG + 16384;
constexpr uint32_t OFF_RUN = OFF_STG + 24576;
constexpr uint32_t OFF_CSQ = OFF_RUN + 512;
constexpr uint32_t OFF_CSF = OFF_CSQ + 2048;
constexpr uint32_t OFF_ROW = OFF_CSF + 3584;
constexpr uint32_t OFF_HALF = OFF_ROW + 1024;
constexpr uint32_t OFF_BAR = OFF_HALF + 1024;
constexpr uint32_t SMEM_BYTES = OFF_BAR + 384;
constexpr uint32_t BAR_FULL = OFF_BAR, BAR_EMPTY = OFF_BAR + 8 * NBAR;
constexpr uint32_t BAR_XRDY = OFF_BAR + 80;
constexpr uint32_t BAR_DUMMY = OFF_BAR + 96, OFF_TAG = OFF_BAR + 104, OFF_ZERO = OFF_BAR + 112;
constexpr uint32_t BAR_PUB = OFF_BAR + 128;
constexpr uint32_t BAR_CSLD = OFF_BAR + 200;
constexpr uint32_t BAR_BIAS = OFF_BAR + 216;
constexpr uint32_t BAR_XGO = OFF_BAR + 224;

constexpr uint64_t DESC_A = (1ull << 62) | ((uint64_t)(2048 >> 4) << 32) | (1ull << 16);
constexpr uint64_t DESC_B = (1ull << 62) | ((uint64_t)(1024 >> 4) << 32) | ((uint64_t)(4096 >> 4) << 16);

constexpr int BAR_INIT = 0, BAR_ORDER = 1, BAR_GUARD = 3, BAR_WG = 5, BAR_GO = 7, BAR_DONE = 8, BAR_HLP = 9;
constexpr int BAR_INIT0 = 10, BAR_PAIR = 11, BAR_STAT = 15;

constexpr int WIN1 = 5;
constexpr int WIN0 = 7;
constexpr int SKEW = 3;
constexpr int WIN2 = 1;
constexpr int GELU_DEP = 2;
constexpr int STG_WAIT = 5;
constexpr int HALO_NS = 200;
constexpr int STAT_NS = 800;
constexpr int CS_NS = 500;
constexpr int XB_NS = 400;
constexpr int XB_GAP_NS = 50;
constexpr int STAG_NS = 450;
constexpr int PACE_M = 100;
constexpr int PACE_N = 300;

struct Scratch {
  uint4 stats[4 * 8 * SEQ];
  uint4 halo[2 * 2 * 16 * 8 * 384];
  uint4 csp[2 * 8 * 17 * 224];
  uint32_t flags[16 * 32];
  uint32_t epoch[NCTA + 4];
};

struct Maps {
  CUtensorMap xin, out, att, h, wqkv, wo, w1a, w1b, w2, att_st, h_st, w1c, out_w;
};
struct Scalars {
  Scratch* g;
  const __nv_bfloat16 *b1, *b2;
  uint32_t zero;
};
struct Params : Scalars {
  const Maps& t;
};

__device__ __nv_bfloat16 g_att[SEQ * DM];
__device__ __nv_bfloat16 g_h[SEQ * FF];
__device__ Scratch g_scratch;

__device__ __forceinline__ void mbar_init(uint32_t bar, int cnt) {
  asm volatile("mbarrier.init.shared::cta.b64 [%0], %1;" ::"r"(bar), "r"(cnt));
}
__device__ __forceinline__ void mbar_expect_tx(uint32_t bar, uint32_t bytes) {
  asm volatile("mbarrier.arrive.expect_tx.shared::cta.b64 _, [%0], %1;" ::"r"(bar), "r"(bytes) : "memory");
}
__device__ __forceinline__ void mbar_arrive(uint32_t bar) {
  asm volatile("mbarrier.arrive.shared::cta.b64 _, [%0];" ::"r"(bar) : "memory");
}
__device__ __forceinline__ bool mbar_test(uint32_t bar, uint32_t parity) {
  uint32_t ok;
  asm volatile("{\n.reg .pred p;\nmbarrier.test_wait.parity.shared::cta.b64 p, [%1], %2;\nselp.u32 %0, 1, 0, p;\n}"
               : "=r"(ok) : "r"(bar), "r"(parity) : "memory");
  return ok;
}
__device__ __forceinline__ void mbar_wait(uint32_t bar, uint32_t parity) {
  asm volatile(
      "{\n.reg .pred p;\n.reg .u32 it;\nmov.u32 it, 0;\n"
      "WAIT_LOOP:\n"
      "mbarrier.try_wait.parity.shared::cta.b64 p, [%0], %1;\n"
      "@p bra WAIT_DONE;\n"
      "add.u32 it, it, 1;\n"
      "setp.lt.u32 p, it, 0x400000;\n"
      "@p bra WAIT_LOOP;\n"
      "trap;\n"
      "WAIT_DONE:\n}"
      ::"r"(bar), "r"(parity) : "memory");
}
__device__ __forceinline__ void bar_sync(int id, int n) { asm volatile("bar.sync %0, %1;" ::"r"(id), "r"(n) : "memory"); }
__device__ __forceinline__ void bar_arrive(int id, int n) { asm volatile("bar.arrive %0, %1;" ::"r"(id), "r"(n) : "memory"); }
__device__ __forceinline__ void tma_ld2(uint32_t dst, const CUtensorMap* m, uint32_t bar, int c0, int c1) {
  asm volatile("cp.async.bulk.tensor.2d.shared::cluster.global.mbarrier::complete_tx::bytes [%0], [%1, {%3, %4}], [%2];"
               ::"r"(dst), "l"(m), "r"(bar), "r"(c0), "r"(c1) : "memory");
}
__device__ __forceinline__ void tma_ld_act(uint32_t dst, const CUtensorMap* m, uint32_t bar, int col, int blk) {
  asm volatile("cp.async.bulk.tensor.4d.shared::cluster.global.mbarrier::complete_tx::bytes [%0], [%1, {%3, %5, %5, %4}], [%2];"
               ::"r"(dst), "l"(m), "r"(bar), "r"(col), "r"(2 * blk), "r"(0) : "memory");
}
__device__ __forceinline__ void tma_st_act(const CUtensorMap* m, uint32_t src, int col, int blk) {
  asm volatile("cp.async.bulk.tensor.4d.global.shared::cta.bulk_group [%0, {%2, %4, %4, %3}], [%1];"
               ::"l"(m), "r"(src), "r"(col), "r"(2 * blk), "r"(0) : "memory");
}
__device__ __forceinline__ void tma_st_warp(const CUtensorMap* m, uint32_t src, int col, int blk, int w) {
  asm volatile("cp.async.bulk.tensor.4d.global.shared::cta.bulk_group [%0, {%2, %5, %3, %4}], [%1];"
               ::"l"(m), "r"(src), "r"(col), "r"(w & 1), "r"(2 * blk + (w >> 1)), "r"(0) : "memory");
}
__device__ __forceinline__ void tma_ld3(uint32_t dst, const CUtensorMap* m, uint32_t bar, int c0, int c1, int c2) {
  asm volatile("cp.async.bulk.tensor.3d.shared::cluster.global.mbarrier::complete_tx::bytes [%0], [%1, {%3, %4, %5}], [%2];"
               ::"r"(dst), "l"(m), "r"(bar), "r"(c0), "r"(c1), "r"(c2) : "memory");
}
__device__ __forceinline__ void tma_ld3_pair(uint32_t dst, const CUtensorMap* m, uint32_t bar, int c0, int c1, int c2) {
  asm volatile("cp.async.bulk.tensor.3d.shared::cluster.global.mbarrier::complete_tx::bytes.multicast::cluster"
               " [%0], [%1, {%3, %4, %5}], [%2], %6;"
               ::"r"(dst), "l"(m), "r"(bar), "r"(c0), "r"(c1), "r"(c2), "h"((uint16_t)3) : "memory");
}
__device__ __forceinline__ uint32_t pair_offset(uint32_t sb, uint32_t rank) {
  uint32_t r;
  asm volatile("mapa.shared::cluster.u32 %0, %1, %2;" : "=r"(r) : "r"(sb), "r"(rank));
  return r - sb;
}
__device__ __forceinline__ void mbar_arrive_cluster(uint32_t bar) {
  asm volatile("mbarrier.arrive.shared::cluster.b64 _, [%0];" ::"r"(bar) : "memory");
}
__device__ __forceinline__ void cluster_arrive() { asm volatile("barrier.cluster.arrive.relaxed;" ::: "memory"); }
__device__ __forceinline__ void cluster_wait() { asm volatile("barrier.cluster.wait.acquire;" ::: "memory"); }
__device__ __forceinline__ void tma_st2(const CUtensorMap* m, uint32_t src, int c0, int c1) {
  asm volatile("cp.async.bulk.tensor.2d.global.shared::cta.bulk_group [%0, {%2, %3}], [%1];"
               ::"l"(m), "r"(src), "r"(c0), "r"(c1) : "memory");
}
__device__ __forceinline__ void bulk_commit() { asm volatile("cp.async.bulk.commit_group;" ::: "memory"); }
__device__ __forceinline__ void bulk_wait_read() { asm volatile("cp.async.bulk.wait_group.read 0;" ::: "memory"); }
__device__ __forceinline__ void bulk_wait_all() { asm volatile("cp.async.bulk.wait_group 0;" ::: "memory"); }
__device__ __forceinline__ void fence_async_smem() { asm volatile("fence.proxy.async.shared::cta;" ::: "memory"); }
__device__ __forceinline__ void fence_async_global() { asm volatile("fence.proxy.async.global;" ::: "memory"); }
__device__ __forceinline__ void st_relaxed(uint32_t* p, uint32_t v) {
  asm volatile("st.relaxed.gpu.global.u32 [%0], %1;" ::"l"(p), "r"(v) : "memory");
}
__device__ __forceinline__ void st_msg(uint4* p, uint32_t a, uint32_t b, uint32_t c, uint32_t tag) {
  asm volatile("{\n.reg .b128 v;\nmov.b128 v, {%1, %2, %3, %4};\nst.relaxed.gpu.global.b128 [%0], v;\n}"
               ::"l"(p), "r"(a), "r"(b), "r"(c), "r"(tag) : "memory");
}
__device__ __forceinline__ void ld_msg(const uint4* p, uint32_t& a, uint32_t& b, uint32_t& c, uint32_t& tag) {
  asm volatile("{\n.reg .b128 v;\nld.relaxed.gpu.global.b128 v, [%4];\nmov.b128 {%0, %1, %2, %3}, v;\n}"
               : "=r"(a), "=r"(b), "=r"(c), "=r"(tag) : "l"(p) : "memory");
}
__device__ __forceinline__ bool elect_one() {
  uint32_t ok;
  asm volatile("{\n.reg .pred p;\nelect.sync _|p, 0xffffffff;\nselp.u32 %0, 1, 0, p;\n}" : "=r"(ok));
  return ok;
}
__device__ __forceinline__ uint32_t lanemask_lt() {
  uint32_t v;
  asm("mov.u32 %0, %%lanemask_lt;" : "=r"(v));
  return v;
}
__device__ __forceinline__ int uniform(int v) { return __shfl_sync(0xffffffffu, v, 0); }
__device__ __forceinline__ uint32_t pack_bf16(float lo, float hi) {
  uint32_t r;
  asm("cvt.rn.bf16x2.f32 %0, %1, %2;" : "=r"(r) : "f"(hi), "f"(lo));
  return r;
}
__device__ __forceinline__ float prmt_f(uint32_t a, uint32_t sel) {
  float r;
  asm("{\n.reg .b32 t;\nprmt.b32 t, %1, 0, %2;\nmov.b32 %0, t;\n}" : "=f"(r) : "r"(a), "r"(sel));
  return r;
}
__device__ __forceinline__ float bf_lo(uint32_t v) { return __uint_as_float(v << 16); }
__device__ __forceinline__ float bf_hi(uint32_t v) { return __uint_as_float(v & 0xffff0000u); }
__device__ __forceinline__ void stsm4(uint32_t addr, uint32_t r0, uint32_t r1, uint32_t r2, uint32_t r3) {
  asm volatile("stmatrix.sync.aligned.m8n8.x4.shared.b16 [%0], {%1, %2, %3, %4};"
               ::"r"(addr), "r"(r0), "r"(r1), "r"(r2), "r"(r3) : "memory");
}
__device__ __forceinline__ void ldsm4(uint32_t addr, uint32_t& r0, uint32_t& r1, uint32_t& r2, uint32_t& r3) {
  asm volatile("ldmatrix.sync.aligned.m8n8.x4.shared.b16 {%0, %1, %2, %3}, [%4];"
               : "=r"(r0), "=r"(r1), "=r"(r2), "=r"(r3) : "r"(addr) : "memory");
}
__device__ __forceinline__ uint32_t movtrans(uint32_t a) {
  uint32_t d;
  asm volatile("movmatrix.sync.aligned.m8n8.trans.b16 %0, %1;" : "=r"(d) : "r"(a));
  return d;
}
__device__ __forceinline__ void mma16816(float (&c)[4], uint32_t a0, uint32_t a1, uint32_t a2, uint32_t a3, uint32_t b0, uint32_t b1) {
  asm volatile("mma.sync.aligned.m16n8k16.row.col.f32.bf16.bf16.f32 {%0,%1,%2,%3}, {%4,%5,%6,%7}, {%8,%9}, {%0,%1,%2,%3};"
               : "+f"(c[0]), "+f"(c[1]), "+f"(c[2]), "+f"(c[3])
               : "r"(a0), "r"(a1), "r"(a2), "r"(a3), "r"(b0), "r"(b1));
}
__device__ __forceinline__ void mma1688(float (&c)[4], uint32_t a0, uint32_t a1, uint32_t b0) {
  asm volatile("mma.sync.aligned.m16n8k8.row.col.f32.bf16.bf16.f32 {%0,%1,%2,%3}, {%4,%5}, {%6}, {%0,%1,%2,%3};"
               : "+f"(c[0]), "+f"(c[1]), "+f"(c[2]), "+f"(c[3]) : "r"(a0), "r"(a1), "r"(b0));
}
__device__ __forceinline__ float2 lds_f2(uint32_t a) {
  float2 v;
  asm volatile("ld.shared.v2.f32 {%0, %1}, [%2];" : "=f"(v.x), "=f"(v.y) : "r"(a) : "memory");
  return v;
}
__device__ __forceinline__ float4 lds_f4(uint32_t a) {
  float4 v;
  asm volatile("ld.shared.v4.f32 {%0, %1, %2, %3}, [%4];" : "=f"(v.x), "=f"(v.y), "=f"(v.z), "=f"(v.w) : "r"(a) : "memory");
  return v;
}
__device__ __forceinline__ float lds_f(uint32_t a) {
  float v;
  asm volatile("ld.shared.f32 %0, [%1];" : "=f"(v) : "r"(a) : "memory");
  return v;
}
__device__ __forceinline__ uint32_t lds_u(uint32_t a) {
  uint32_t v;
  asm volatile("ld.shared.u32 %0, [%1];" : "=r"(v) : "r"(a) : "memory");
  return v;
}
__device__ __forceinline__ void sts_f2(uint32_t a, float x, float y) {
  asm volatile("st.shared.v2.f32 [%0], {%1, %2};" ::"r"(a), "f"(x), "f"(y) : "memory");
}
__device__ __forceinline__ void sts_u4(uint32_t a, uint32_t x, uint32_t y, uint32_t z, uint32_t w) {
  asm volatile("st.shared.v4.u32 [%0], {%1, %2, %3, %4};" ::"r"(a), "r"(x), "r"(y), "r"(z), "r"(w) : "memory");
}
__device__ __forceinline__ void lds_u4(uint32_t a, uint32_t& x, uint32_t& y, uint32_t& z, uint32_t& w) {
  asm volatile("ld.shared.v4.u32 {%0, %1, %2, %3}, [%4];" : "=r"(x), "=r"(y), "=r"(z), "=r"(w) : "r"(a) : "memory");
}
__device__ __forceinline__ float ex2(float x) {
  float y;
  asm("ex2.approx.ftz.f32 %0, %1;" : "=f"(y) : "f"(x));
  return y;
}
__device__ __forceinline__ float rcp_hw(float x) {
  float y;
  asm("rcp.approx.ftz.f32 %0, %1;" : "=f"(y) : "f"(x));
  return y;
}
__device__ __forceinline__ float tanh_hw(float x) {
  float y;
  asm("tanh.approx.f32 %0, %1;" : "=f"(y) : "f"(x));
  return y;
}
__device__ __forceinline__ float quad_sum(float v) {
  v += __shfl_xor_sync(0xffffffffu, v, 1);
  return v + __shfl_xor_sync(0xffffffffu, v, 2);
}
__device__ __forceinline__ float quad_max(float v) {
  v = fmaxf(v, __shfl_xor_sync(0xffffffffu, v, 1));
  return fmaxf(v, __shfl_xor_sync(0xffffffffu, v, 2));
}

template <int N> __device__ __forceinline__ void wgmma_ss(float (&d)[96], uint64_t da, uint64_t db, uint32_t keep = 1);
template <> __device__ __forceinline__ void wgmma_ss<128>(float (&d)[96], uint64_t da, uint64_t db, uint32_t keep) {
  asm volatile(
      "{\n.reg .pred p;\nsetp.ne.u32 p, %66, 0;\n"
      "wgmma.mma_async.sync.aligned.m64n128k16.f32.bf16.bf16 {%0, %1, %2, %3, %4, %5, %6, %7, %8, %9, %10, %11, %12, %13, %14, %15, %16, %17, %18, %19, %20, %21, %22, %23, %24, %25, %26, %27, %28, %29, %30, %31, %32, %33, %34, %35, %36, %37, %38, %39, %40, %41, %42, %43, %44, %45, %46, %47, %48, %49, %50, %51, %52, %53, %54, %55, %56, %57, %58, %59, %60, %61, %62, %63}, %64, %65, p, 1, 1, 0, 1;\n}"
      : "+f"(d[0]), "+f"(d[1]), "+f"(d[2]), "+f"(d[3]), "+f"(d[4]), "+f"(d[5]), "+f"(d[6]), "+f"(d[7]), "+f"(d[8]), "+f"(d[9]), "+f"(d[10]), "+f"(d[11]), "+f"(d[12]), "+f"(d[13]), "+f"(d[14]), "+f"(d[15]), "+f"(d[16]), "+f"(d[17]), "+f"(d[18]), "+f"(d[19]), "+f"(d[20]), "+f"(d[21]), "+f"(d[22]), "+f"(d[23]), "+f"(d[24]), "+f"(d[25]), "+f"(d[26]), "+f"(d[27]), "+f"(d[28]), "+f"(d[29]), "+f"(d[30]), "+f"(d[31]), "+f"(d[32]), "+f"(d[33]), "+f"(d[34]), "+f"(d[35]), "+f"(d[36]), "+f"(d[37]), "+f"(d[38]), "+f"(d[39]), "+f"(d[40]), "+f"(d[41]), "+f"(d[42]), "+f"(d[43]), "+f"(d[44]), "+f"(d[45]), "+f"(d[46]), "+f"(d[47]), "+f"(d[48]), "+f"(d[49]), "+f"(d[50]), "+f"(d[51]), "+f"(d[52]), "+f"(d[53]), "+f"(d[54]), "+f"(d[55]), "+f"(d[56]), "+f"(d[57]), "+f"(d[58]), "+f"(d[59]), "+f"(d[60]), "+f"(d[61]), "+f"(d[62]), "+f"(d[63])
      : "l"(da), "l"(db), "r"(keep));
}

template <> __device__ __forceinline__ void wgmma_ss<192>(float (&d)[96], uint64_t da, uint64_t db, uint32_t keep) {
  asm volatile(
      "{\n.reg .pred p;\nsetp.ne.u32 p, %98, 0;\n"
      "wgmma.mma_async.sync.aligned.m64n192k16.f32.bf16.bf16 {%0, %1, %2, %3, %4, %5, %6, %7, %8, %9, %10, %11, %12, %13, %14, %15, %16, %17, %18, %19, %20, %21, %22, %23, %24, %25, %26, %27, %28, %29, %30, %31, %32, %33, %34, %35, %36, %37, %38, %39, %40, %41, %42, %43, %44, %45, %46, %47, %48, %49, %50, %51, %52, %53, %54, %55, %56, %57, %58, %59, %60, %61, %62, %63, %64, %65, %66, %67, %68, %69, %70, %71, %72, %73, %74, %75, %76, %77, %78, %79, %80, %81, %82, %83, %84, %85, %86, %87, %88, %89, %90, %91, %92, %93, %94, %95}, %96, %97, p, 1, 1, 0, 1;\n}"
      : "+f"(d[0]), "+f"(d[1]), "+f"(d[2]), "+f"(d[3]), "+f"(d[4]), "+f"(d[5]), "+f"(d[6]), "+f"(d[7]), "+f"(d[8]), "+f"(d[9]), "+f"(d[10]), "+f"(d[11]), "+f"(d[12]), "+f"(d[13]), "+f"(d[14]), "+f"(d[15]), "+f"(d[16]), "+f"(d[17]), "+f"(d[18]), "+f"(d[19]), "+f"(d[20]), "+f"(d[21]), "+f"(d[22]), "+f"(d[23]), "+f"(d[24]), "+f"(d[25]), "+f"(d[26]), "+f"(d[27]), "+f"(d[28]), "+f"(d[29]), "+f"(d[30]), "+f"(d[31]), "+f"(d[32]), "+f"(d[33]), "+f"(d[34]), "+f"(d[35]), "+f"(d[36]), "+f"(d[37]), "+f"(d[38]), "+f"(d[39]), "+f"(d[40]), "+f"(d[41]), "+f"(d[42]), "+f"(d[43]), "+f"(d[44]), "+f"(d[45]), "+f"(d[46]), "+f"(d[47]), "+f"(d[48]), "+f"(d[49]), "+f"(d[50]), "+f"(d[51]), "+f"(d[52]), "+f"(d[53]), "+f"(d[54]), "+f"(d[55]), "+f"(d[56]), "+f"(d[57]), "+f"(d[58]), "+f"(d[59]), "+f"(d[60]), "+f"(d[61]), "+f"(d[62]), "+f"(d[63]), "+f"(d[64]), "+f"(d[65]), "+f"(d[66]), "+f"(d[67]), "+f"(d[68]), "+f"(d[69]), "+f"(d[70]), "+f"(d[71]), "+f"(d[72]), "+f"(d[73]), "+f"(d[74]), "+f"(d[75]), "+f"(d[76]), "+f"(d[77]), "+f"(d[78]), "+f"(d[79]), "+f"(d[80]), "+f"(d[81]), "+f"(d[82]), "+f"(d[83]), "+f"(d[84]), "+f"(d[85]), "+f"(d[86]), "+f"(d[87]), "+f"(d[88]), "+f"(d[89]), "+f"(d[90]), "+f"(d[91]), "+f"(d[92]), "+f"(d[93]), "+f"(d[94]), "+f"(d[95])
      : "l"(da), "l"(db), "r"(keep));
}

template <int R>
__device__ __forceinline__ void pin_regs(float (&a)[2][96]) {
#pragma unroll
  for (int m = 0; m < 2; m++)
#pragma unroll
    for (int i = 0; i < R; i++) asm volatile("" : "+f"(a[m][i])::"memory");
}

struct Ctx {
  uint32_t sb;
  int m, n, wg, w, lane;
};
__device__ __forceinline__ Ctx make_ctx(uint32_t sb, int id) {
  int lane;
  asm volatile("mov.u32 %0, %%laneid;" : "=r"(lane));
  asm volatile("" : "+r"(id), "+r"(sb));
  return Ctx{sb, (id >> 3) & 15, id & 7, id >> 9, (id >> 7) & 3, lane};
}
#define UNPACK_CTX(c) const uint32_t sb = c.sb; const int m = c.m, n = c.n, wg = c.wg, w = c.w, lane = c.lane

__device__ __forceinline__ uint32_t poll_line(const uint32_t* word, uint32_t target, uint32_t need) {
  uint32_t v;
  asm volatile(
      "{\n.reg .pred p;\n.reg .u32 it, m;\n.reg .s32 d;\nmov.u32 it, 0;\n"
      "POLL_LOOP:\n"
      "ld.relaxed.gpu.global.u32 %0, [%1];\n"
      "sub.s32 d, %0, %2;\n"
      "setp.ge.s32 p, d, 0;\n"
      "vote.sync.ballot.b32 m, p, 0xffffffff;\n"
      "and.b32 m, m, %3;\n"
      "setp.eq.u32 p, m, %3;\n"
      "@p bra.uni POLL_DONE;\n"
      "add.u32 it, it, 1;\n"
      "setp.lt.u32 p, it, 0x400000;\n"
      "@p bra.uni POLL_LOOP;\n"
      "trap;\n"
      "POLL_DONE:\n}"
      : "=&r"(v) : "l"(word), "r"(target), "r"(need) : "memory");
  return v;
}
__device__ __forceinline__ uint32_t ld_relaxed(const uint32_t* p) {
  uint32_t v;
  asm volatile("ld.relaxed.gpu.global.u32 %0, [%1];" : "=r"(v) : "l"(p) : "memory");
  return v;
}
__device__ __forceinline__ float chain(float x, uint32_t on, uint32_t zero) {
  return __uint_as_float(__float_as_uint(x) | (on & zero));
}
constexpr int MSG_SPINS = 1 << 20;

constexpr int STAGES_PER_LAYER = 152;
__device__ __forceinline__ int nib(uint64_t v, int i) { return (int)(v >> (4 * i)) & 15; }
__device__ __forceinline__ bool tile_wide(int t) { return (0x23 >> t) & 1; }
__device__ __forceinline__ void weight_coords(const Params& p, int t, int n, const CUtensorMap*& map, int& c0, int& c2) {
  map = &p.t.wqkv + nib(0x4233100ull, t);
  c0 = t < 2 ? 128 * n + 64 * t : 0;
  c2 = t < 2 ? 0 : (t == 2 || t == 6) ? 2 * n : 7 * n + 2 * t - 6;
}

template <bool IS_A>
__device__ __forceinline__ void producer(const Params& p, uint32_t sb, int m, int n, int lane) {
  const uint32_t low = (1u << (4 * n)) - 1, others = (0x6543210u & low) | (0x7654321u & ~low);
  const uint64_t order_x = (uint64_t)(others * 2 + 0x1111111u) << 36 | (uint64_t)others * 2 << 8 | (n * 0x22 + 0x10);
  int inflight = 4, cur = 0;
  uint32_t fb = sb + BAR_FULL + 32, rb = sb + BAR_EMPTY, rph = 0, pos = 0, tag32 = 0, seen = 0;
  const uint32_t fend = sb + BAR_FULL + 8 * NBAR, rend = sb + BAR_EMPTY + 8 * NBAR;
  const uint32_t* word = p.g->flags + m * 32 + (lane < 16 ? lane >> 1 : lane & 7);
#pragma unroll 1
  for (int sg = 1; sg < 22; sg++) {
    const int layer = sg >= 11, s = sg == 1 ? 2 : sg == 2 ? 1 : sg - 11 * layer;
    const int t = nib(0x65434321010ull, s), kind = nib(0x32110031100ull, s);
    const bool wide = tile_wide(t);
    const uint32_t bbytes = wide ? 3 * UNIT : 2 * UNIT, base = sb + (IS_A ? bbytes : (m & 1) * (bbytes / 2));
    if (IS_A && kind == 0) {
      if (sg == 2) seen = tag32 = (__ldcg(p.g->epoch + m * 8 + n) + 1) << 5;
#pragma unroll 1
      for (int k = 0; k < 2; k++) {
#pragma unroll 1
        for (; inflight > (wide ? 3 : 4); inflight--) {
          mbar_wait(rb, rph);
          rb += 8;
          if (rb == rend) { rb -= 8 * NBAR; rph ^= 1; }
        }
        if (elect_one()) mbar_arrive(fb);
        inflight++;
        fb += 8;
        if (fb == fend) fb -= 8 * NBAR;
        pos += bbytes + 2 * UNIT;
        if (pos >= RING_UNITS * UNIT) pos -= RING_UNITS * UNIT;
      }
      continue;
    }
    const int mul = t == 6 ? 448 : t == 2 ? 128 : 64, count = sg == 1 ? 12 : 2 * nib(0x4871ull, kind);
    uint64_t order0 = sg == 1 ? 0xFEDCBA987654ull : kind == 3 ? 0x76543210u : order_x >> (8 * (kind & 1));
    uint32_t special = (s == 4 || s == 10) ? 0x10 : s == 9 ? 0xF : s == 0;
    if (IS_A) special |= (kind & 1 ? 0 : 3) | (count >= 4 ? 1u << (count - 4) : 0);
    if (s >= 9) pos = (s + 6) * UNIT;
    const CUtensorMap* map;
    int c0 = 0, c2 = 0, ev = 0;
    if (IS_A) {
      map = &p.t.xin + (t == 2 ? 2 : t == 6 ? 3 : sg >= 4);
      ev = 9 * layer + (t < 2 ? 0 : t == 2 ? 1 : t < 6 ? 4 : 5);
      if (elect_one()) asm volatile("prefetch.tensormap [%0];" ::"l"(map) : "memory");
    } else {
      weight_coords(p, t, n, map, c0, c2);
    }
#pragma unroll 1
    for (int add = 0; add < mul; add += 64) {
      uint64_t order = order0;
      const int need = kind == 3 ? ev : ev - 1 + (lane & 1), sh = kind == 3 ? 16 : 0;
      uint32_t ready = IS_A ? __ballot_sync(0xffffffffu, cur >= need) >> sh : 0;
#pragma unroll 1
      for (int k = 0; k < count; k++) {
        const int code = order & 15, kc = code * mul + add;
        order >>= 4;
        if ((special >> k) & 1) {
          const int lag = wide ? (s == 9 && k == 2 ? 2 : 3) : ((s == 4 || s == 10) && add == 0 && k < 4) ? 3 : 4;
#pragma unroll 1
          for (; inflight > lag; inflight--) {
            mbar_wait(rb, rph);
            rb += 8;
            if (rb == rend) { rb -= 8 * NBAR; rph ^= 1; }
          }
          inflight++;
          if (IS_A) {
            if (kind == 3 ? t == 2 && add + k == 64 : !(kind & 1) && k < 2) {
              if (t == 2) mbar_wait(sb + BAR_PUB + 8, layer);
              if (elect_one()) mbar_arrive(fb);
              goto next_stage;
            }
            if (k == count - 4 && sg >= 3) seen = ld_relaxed(word);
          }
        } else {
          mbar_wait(rb, rph);
          rb += 8;
          if (rb == rend) { rb -= 8 * NBAR; rph ^= 1; }
        }
        if (IS_A && !((ready >> code) & 1)) {
          cur = max(cur, (int)(seen - tag32));
          ready = __ballot_sync(0xffffffffu, cur >= need) >> sh;
          if (!((ready >> code) & 1)) {
            cur = (int)(poll_line(word, tag32 + need, 1u << (code + sh)) - tag32);
            ready = __ballot_sync(0xffffffffu, cur >= need) >> sh;
          }
          asm volatile("fence.acquire.gpu;" ::: "memory");
          fence_async_global();
          seen = ld_relaxed(word);
        }
        if (elect_one()) {
          if (!IS_A) tma_ld3_pair(base + pos, map, fb, c0, kc + 32 * (m & 1), c2);
          else tma_ld_act(base + pos, map, fb, kc, m);
          mbar_expect_tx(fb, IS_A ? 16384 : bbytes);
        }
      next_stage:
        fb += 8;
        if (fb == fend) fb -= 8 * NBAR;
        pos += bbytes + 2 * UNIT;
        if (pos >= RING_UNITS * UNIT) pos -= RING_UNITS * UNIT;
      }
      special = !IS_A ? 0 : t == 2 ? 1 : add == 128 ? 0x10 : 0;
      if (t == 2) order0 = others << 4 | n;
      if (IS_A && (t == 2 || add == 64 || add == 192)) ev++;
    }
  }
}

__device__ __forceinline__ void publisher(const Params& p, uint32_t sb, int m, int n) {
  {
    const int ts = PACE_M * m, tx = PACE_N * n;
#pragma unroll 1
    for (int k = 0; k < 2; k++) {
      __nanosleep(k == 0 ? min(ts, tx) : abs(ts - tx));
      if ((ts <= tx) == (k == 0)) {
        mbar_expect_tx(sb + BAR_CSLD, 24576);
        tma_ld3(sb + OFF_STG, &p.t.wqkv, sb + BAR_CSLD, 128 * n, 64 * m, 0);
        tma_ld3(sb + OFF_STG + 12288, &p.t.wqkv, sb + BAR_CSLD, 128 * n, 64 * m + 32, 0);
      } else {
#pragma unroll 1
        for (int h = 0; h < 2; h++) {
          const uint32_t xr = sb + BAR_XRDY + 8 * h;
          mbar_expect_tx(xr, 16384);
          tma_ld_act(sb + OFF_X + h * 16384, &p.t.xin, xr, 128 * n + 64 * h, m);
          asm volatile("mbarrier.arrive.shared::cta.b64 _, [%0], 3;" ::"r"(xr) : "memory");
        }
      }
    }
  }
  const uint32_t tag = __ldcg(p.g->epoch + m * 8 + n) + 1;
  uint32_t* word = p.g->flags + m * 32 + n;
  st_relaxed(word, 32 * tag);
#pragma unroll 1
  for (int c = 0; c < 16; c++) {
    const int e = c >= 9 ? c - 9 : c;
    if (e == 2 || e == 7) {
      asm volatile("prefetch.tensormap [%0];" ::"l"(&p.t.out) : "memory");
      mbar_wait(sb + BAR_XRDY, e == 2);
      tma_st_act(&p.t.out, sb + OFF_X, 128 * n, m);
      bulk_commit();
      mbar_wait(sb + BAR_XRDY + 8, e == 2);
      bulk_wait_all();
      mbar_arrive(sb + BAR_XGO);
    } else {
      mbar_wait(sb + BAR_PUB + 8 * e, c >= 9);
    }
    asm volatile("fence.release.gpu;" ::: "memory");
    asm volatile("red.relaxed.gpu.global.add.u32 [%0], 1;" ::"l"(word) : "memory");
  }
  p.g->epoch[m * 8 + n] = tag;
}

__device__ __forceinline__ void sum_rows(uint32_t buf, int iters, float (&a)[8], int lane) {
  uint32_t addr = buf + (lane >> 3) * 128 + (((lane & 7) ^ (lane >> 3)) << 4);
#pragma unroll 1
  for (int it = 0; it < iters; it++) {
    uint32_t u[2][4];
    lds_u4(addr, u[0][0], u[0][1], u[0][2], u[0][3]);
    lds_u4((addr ^ 64) + 512, u[1][0], u[1][1], u[1][2], u[1][3]);
    addr += 1024;
#pragma unroll
    for (int e = 0; e < 8; e++) { a[2 * (e & 3)] += bf_lo(u[e >> 2][e & 3]); a[2 * (e & 3) + 1] += bf_hi(u[e >> 2][e & 3]); }
  }
}
__device__ __forceinline__ void publish_sums(const float (&a)[8], uint4* dst, int lane, uint32_t tag) {
  const bool u8 = lane & 8, u16 = lane & 16;
  float h4[4], h2[2];
#pragma unroll
  for (int e = 0; e < 4; e++) h4[e] = (u8 ? a[4 + e] : a[e]) + __shfl_xor_sync(0xffffffffu, u8 ? a[e] : a[4 + e], 8);
#pragma unroll
  for (int e = 0; e < 2; e++) h2[e] = (u16 ? h4[2 + e] : h4[e]) + __shfl_xor_sync(0xffffffffu, u16 ? h4[e] : h4[2 + e], 16);
  st_msg(dst + (lane & 7) * 4 + (u8 ? 2 : 0) + (u16 ? 1 : 0), __float_as_uint(h2[0]), __float_as_uint(h2[1]), 0u, tag);
}

__device__ __forceinline__ void colsum_helper(const Params& p, uint32_t sb, int m, int n, int lane) {
  const uint32_t tag = __ldcg(p.g->epoch + m * 8 + n) + 1;
#pragma unroll 1
  for (int k = lane; k < 288; k += 32) {
    const uint32_t bb = __ldg(reinterpret_cast<const uint32_t*>(k < 224 ? p.b1 + 448 * n : p.b2 + 128 * n - 448) + k);
    const float sc = k < 224 ? 0.5f : 1.f;
    sts_f2(sb + (k < 224 ? OFF_CSF + k * 16 + 8 : OFF_CSQ + 1536 + (k - 224) * 8), sc * bf_lo(bb), sc * bf_hi(bb));
  }
  __syncwarp();
  if (elect_one()) mbar_arrive(sb + BAR_BIAS);
  bar_sync(BAR_HLP, 160);
  {
    uint4* base = p.g->csp + n * 17 * 224 + 12 * m + min(lane & 15, 11);
    float s0 = 0.f, s1 = 0.f;
#pragma unroll 1
    for (int g = 0; g < 2; g++) {
      uint32_t x[4], y[4];
#pragma unroll 1
      for (int it = 0; it < MSG_SPINS; it++) {
        uint32_t bad = 0, z, tg;
        if (g == 0 || it > 0) __nanosleep(CS_NS);
#pragma unroll
        for (int k = 0; k < 4; k++) { ld_msg(base + (g * 8 + (lane >> 4) * 4 + k) * 224, x[k], y[k], z, tg); bad |= tg ^ tag; }
        if (__all_sync(0xffffffffu, bad == 0)) break;
      }
#pragma unroll
      for (int k = 0; k < 4; k++) { s0 += __uint_as_float(x[k]); s1 += __uint_as_float(y[k]); }
    }
    s0 += __shfl_xor_sync(0xffffffffu, s0, 16);
    s1 += __shfl_xor_sync(0xffffffffu, s1, 16);
    if (lane < 12) st_msg(base + 16 * 224, __float_as_uint(s0), __float_as_uint(s1), 0u, tag);
  }
#pragma unroll 1
  for (int c = 0; c < 7; c++) {
    float a[8] = {0.f, 0.f, 0.f, 0.f, 0.f, 0.f, 0.f, 0.f};
#pragma unroll 1
    for (int h = 0; h < 2; h++) {
      if (elect_one()) {
        mbar_expect_tx(sb + BAR_CSLD + 8, 4096);
        tma_ld2(sb + OFF_HLP, &p.t.w1c, sb + BAR_CSLD + 8, 448 * n + 64 * c, 64 * m + 32 * h);
        if (c < 6) asm volatile("cp.async.bulk.prefetch.tensor.2d.L2.global [%0, {%1, %2}];" ::"l"(&p.t.w1c), "r"(448 * n + 64 * c + 64), "r"(64 * m + 32 * h) : "memory");
      }
      mbar_wait(sb + BAR_CSLD + 8, h);
      sum_rows(sb + OFF_HLP, 4, a, lane);
      __syncwarp();
    }
    publish_sums(a, p.g->csp + ((8 + n) * 17 + m) * 224 + c * 32, lane, tag);
  }
  if (elect_one()) {
#pragma unroll 1
    for (int k = 0; k < 3; k++) {
      mbar_wait(sb + BAR_XGO, k & 1);
      __nanosleep(XB_NS);
#pragma unroll 1
      for (int w = 0; w < 4; w++) {
        tma_st_warp(&p.t.out_w, sb + OFF_X + 16384 + w * 4096, 128 * n + 64, m, w);
        bulk_commit();
        bulk_wait_read();
        if (w < 3) __nanosleep(XB_GAP_NS);
      }
      bulk_wait_all();
      asm volatile("mbarrier.arrive.shared::cta.b64 _, [%0], 4;" ::"r"(sb + BAR_PUB + (k & 1 ? 64 : 24)) : "memory");
    }
  }
}

__device__ __forceinline__ void poll_msgs2(const uint4* pa, const uint4* pb, float (&v)[4], uint32_t tag) {
#pragma unroll 1
  for (int it = 0; it < MSG_SPINS; it++) {
    uint32_t x[4], z, ta, tb;
    ld_msg(pa, x[0], x[1], z, ta);
    ld_msg(pb, x[2], x[3], z, tb);
#pragma unroll
    for (int e = 0; e < 4; e++) v[e] = __uint_as_float(x[e]);
    if (__all_sync(0xffffffffu, ta == tag && tb == tag)) break;
  }
}
__device__ __forceinline__ void colsum_total(const Params& p, const Ctx& cx, int mat, uint32_t tag) {
  uint4* base = p.g->csp + (mat * 8 + cx.n) * 17 * 224;
  const int per = 12 + 2 * mat, k = 2 * cx.w + (cx.lane >> 4), ia = per * cx.m + k, ib = per * cx.m + min(k + 8, per - 1);
  float v[4];
  poll_msgs2(base + (cx.lane & 15) * 224 + ia, base + (cx.lane & 15) * 224 + ib, v, tag);
#pragma unroll 1
  for (int d = 1; d < 16; d *= 2)
#pragma unroll
    for (int e = 0; e < 4; e++) v[e] += __shfl_xor_sync(0xffffffffu, v[e], d);
  const bool hi = cx.lane & 1;
  if ((cx.lane & 14) == 0) st_msg(base + 16 * 224 + (hi ? ib : ia), __float_as_uint(hi ? v[2] : v[0]), __float_as_uint(hi ? v[3] : v[1]), 0u, tag);
}
__device__ __forceinline__ void colsum_gather(const Params& p, const Ctx& cx, int mat, uint32_t tag) {
  const uint4* base = p.g->csp + ((mat * 8 + cx.n) * 17 + 16) * 224;
  const int ia = cx.w * 32 + cx.lane, ib = min(ia + 128, 191 + 32 * mat);
  float v[4];
  poll_msgs2(base + ia, base + ib, v, tag);
  const uint32_t tab = cx.sb + (mat ? OFF_CSF : OFF_CSQ);
  sts_f2(tab + (ia << (3 + mat)), v[0], v[1]);
  sts_f2(tab + (ib << (3 + mat)), v[2], v[3]);
}

#define ACC(q, j, e) acc[(q) & 1][4 * (j) + 2 * ((q) >> 1) + (e)]

constexpr uint32_t RING16 = RING_UNITS * (UNIT >> 4);
__device__ __forceinline__ bool tile_split(int i) { return (0xD98 >> i) & 1; }

__device__ __forceinline__ void write_run_desc(uint32_t sb, int i, int step) {
  const int layer = i >= 7, t = i - 7 * layer, part = tile_split(i) ? step : 2;
  const bool wide = tile_wide(t), own = t != 2 && t != 6 && part != 1 && i != 0, second = t == 1 || t == 4;
  const uint32_t z16 = (wide ? 5 : 4) * (UNIT >> 4), a_off = z16 - 1024 + (uint32_t)DESC_A - (uint32_t)DESC_B;
  const int gl = 16 * t + (part == 2 ? 0 : second ? 16 * part - 14 : 4 * part), g0 = layer * STAGES_PER_LAYER + gl;
  const uint32_t s16 = (sb & 0x3FFFF) >> 4, bfirst = (uint32_t)DESC_B + s16;
  const int nkb = t == 6 ? 56 : part == 0 ? 2 : 12 + 2 * part;
  const bool win1 = t == 1 && part != 0;
  const int win = layer ? WIN1 : WIN0;
  const int run = win1 ? win + 1 : t == 2 ? WIN2 + 1 : nkb;
  const int rest = win1 ? 64 | (nkb - 1 - SKEW - win) : t == 2 ? 64 | (7 - WIN2) | (8 << 7) : 0;
  const uint32_t blo = bfirst + z16 * (wide ? (gl + (t == 5 ? 3 : 0)) & 3 : (gl + 3) % 5);
  const uint32_t alo = own ? (uint32_t)DESC_A + s16 + (OFF_X >> 4) : blo + a_off;
  const uint32_t aoff = own ? alo + 1024 - (blo == bfirst + RING16 - z16 ? bfirst : blo + z16) : a_off;
  const bool xwait = part == 0 && !second, keep = !(part == 0 || t == 5);
  sts_u4(sb + OFF_RUN + (2 * i + step) * 16, blo, alo, aoff,
         ((g0 / NBAR) & 1) | xwait << 1 | keep << 2 | 8 * (g0 % NBAR) | run << 6 | rest << 12);
}

__device__ __forceinline__ float2 row_sums(const Ctx& c, int j0, int j1) {
  const uint32_t xrow = c.sb + OFF_X + c.w * 4096 + c.lane * 128;
  float s = 0.f, q = 0.f, s1 = 0.f, q1 = 0.f;
#pragma unroll 4
  for (int j = j0; j < j1; j++) {
    uint32_t u[4];
    lds_u4(xrow + (j >> 3) * 16384 + (((j & 7) ^ (c.lane & 7)) << 4), u[0], u[1], u[2], u[3]);
#pragma unroll
    for (int e = 0; e < 4; e++) {
      const float a = bf_lo(u[e]), d = bf_hi(u[e]);
      s += a; q = fmaf(a, a, q);
      s1 += d; q1 = fmaf(d, d, q1);
    }
  }
  return make_float2(s + s1, q + q1);
}
__device__ __forceinline__ void write_partial_stats(const Params& p, const Ctx& c, int ln, float2 v, uint32_t tag) {
  st_msg(p.g->stats + (ln * 8 + c.n) * SEQ + 128 * c.m + 32 * c.w + c.lane, __float_as_uint(v.x),
         __float_as_uint(fmaxf(v.y - v.x * v.x * (1.f / 128.f), 0.f)), 0u, tag);
}

template <int QMASK, int J0 = 0, int J1 = 24>
__device__ __forceinline__ void rank1_update(const Params& p, float (&acc)[2][96], const Ctx& cx, int t) {
  float nm[4];
#pragma unroll
  for (int q = 0; q < 4; q++)
    if ((QMASK >> q) & 1) nm[q] = t == 6 ? 1.f : -lds_f(cx.sb + OFF_ROW + (32 * cx.w + 8 * q + (cx.lane >> 2)) * 8 + 4);
  const uint32_t ctab = cx.sb + OFF_CSQ + ((t & 3) * 192 + 2 * (cx.lane & 3)) * 4;
#pragma unroll
  for (int j = J0; j < J1; j++) {
    const float2 cs = lds_f2(ctab + j * 32);
#pragma unroll
    for (int q = 0; q < 4; q++) {
      if (!((QMASK >> q) & 1)) continue;
      const int k = 4 * j + q - 1;
      const float nq = QMASK == 15 && k >= 0 ? chain(nm[q], __float_as_uint(ACC(k & 3, k >> 2, 1)), p.zero) : nm[q];
      ACC(q, j, 0) = fmaf(nq, cs.x, ACC(q, j, 0));
      ACC(q, j, 1) = fmaf(nq, cs.y, ACC(q, j, 1));
    }
  }
}

template <int QMASK, int SEC>
__device__ __forceinline__ void pack_qkv(const float (&acc)[2][96], uint32_t (&F)[3][4][8]) {
#pragma unroll
  for (int q = 3; q >= 0; q--)
#pragma unroll
    for (int j = 0; j < 8; j++) {
      if (!((QMASK >> q) & 1)) continue;
      const uint32_t u = pack_bf16(ACC(q, 8 * SEC + j, 0), ACC(q, 8 * SEC + j, 1));
      F[SEC][q][j] = SEC == 2 ? movtrans(u) : u;
    }
}
template <int K0, int K1>
__device__ __forceinline__ void send_halo(const Params& p, const uint32_t (&F)[3][4][8], const Ctx& cx, int layer, int t) {
  uint32_t E[18];
#pragma unroll
  for (int j = 0; j < 8; j++) { E[j] = F[1][3][j]; E[8 + j] = F[2][3][j]; }
  if (cx.w < 2) {
#pragma unroll
    for (int k = K0; k < K1; k++)
      if (k < 4) sts_u4(cx.sb + OFF_STG + cx.w * 2048 + cx.lane * 16 + k * 512, E[4 * k], E[4 * k + 1], E[4 * k + 2], E[4 * k + 3]);
  } else {
    uint4* dst = p.g->halo + (((layer * 2 + t) * 16 + cx.m) * 8 + cx.n) * 384 + (cx.w & 1) * 192 + cx.lane;
    const uint32_t tag = lds_u(cx.sb + OFF_TAG);
    if (K1 == 6) {
      const float4 r = lds_f4(cx.sb + OFF_ROW + (32 * cx.w + 24 + 2 * (cx.lane & 3)) * 8);
      E[16] = __float_as_uint(r.x);
      E[17] = __float_as_uint(r.z);
    }
#pragma unroll
    for (int k = K0; k < K1; k++) st_msg(dst + k * 32, E[3 * k], E[3 * k + 1], E[3 * k + 2], tag);
  }
}

__device__ __forceinline__ void attn_scores(const uint32_t* qa, const uint32_t* qb, const uint32_t* kp, const uint32_t* ka,
                                            const uint32_t* kb, float (&l)[4], const float4& zero, const bool (&early)[2]) {
  float s[3][4];
#pragma unroll
  for (int x = 0; x < 3; x++) {
    const uint32_t* kk = x == 0 ? kp : x == 1 ? ka : kb;
    asm volatile("mma.sync.aligned.m16n8k16.row.col.f32.bf16.bf16.f32 {%0,%1,%2,%3}, {%4,%5,%6,%7}, {%8,%9}, {%10,%11,%12,%13};"
                 : "=f"(s[x][0]), "=f"(s[x][1]), "=f"(s[x][2]), "=f"(s[x][3])
                 : "r"(qa[0]), "r"(qb[0]), "r"(qa[1]), "r"(qb[1]), "r"(kk[0]), "r"(kk[1]), "f"(zero.x), "f"(zero.y),
                   "f"(zero.z), "f"(zero.w));
  }
#pragma unroll
  for (int x = 0; x < 3; x++) {
    const uint32_t* kk = x == 0 ? kp : x == 1 ? ka : kb;
    mma16816(s[x], qa[2], qb[2], qa[3], qb[3], kk[2], kk[3]);
  }
#pragma unroll
  for (int e = 0; e < 2; e++) {
    l[e] = early[e] ? s[0][e] : s[1][e];
    l[2 + e] = early[e] ? s[1][2 + e] : s[2][2 + e];
  }
}

__device__ __forceinline__ void attn_mix(const float (&l)[4], const float (&sc)[4], const float (&off)[4], const float (&rk)[4],
                                         const uint32_t* vp, const uint32_t* va, const uint32_t* vb, float (&o)[4][4],
                                         float (&sum)[2], uint32_t mask, uint32_t zero) {
  float x[4];
#pragma unroll
  for (int e = 0; e < 4; e++) x[e] = fmaf(l[e], sc[e], off[e]);
  const float ml = quad_max(fmaxf(x[0], x[1])), mh = quad_max(fmaxf(x[2], x[3]));
  x[0] = ex2(x[0] - ml); x[1] = ex2(x[1] - ml);
  x[2] = ex2(x[2] - mh); x[3] = ex2(x[3] - mh);
  sum[0] = x[0] + x[1];
  sum[1] = x[2] + x[3];
  const uint32_t pl = pack_bf16(x[0] * rk[0], x[1] * rk[1]), ph = pack_bf16(x[2] * rk[2], x[3] * rk[3]);
  const uint32_t a0 = pl & ~mask, a1 = ph & mask, a2 = pl & zero, a3 = ph & ~mask, c0 = pl & mask, c1 = ph & zero;
#pragma unroll
  for (int jn = 0; jn < 4; jn++) {
    o[jn][0] = o[jn][1] = o[jn][2] = o[jn][3] = 0.f;
    mma16816(o[jn], a0, a1, a2, a3, va[jn], vb[jn]);
  }
#pragma unroll
  for (int jn = 0; jn < 4; jn++) mma1688(o[jn], c0, c1, vp[jn]);
}

template <int t>
__device__ __forceinline__ void attn_epilogue(const Params& p, float (&acc)[2][96], uint32_t (&F)[3][4][8], const Ctx& cx, int layer, uint32_t tag) {
  UNPACK_CTX(cx);
  const uint32_t ktab = sb + OFF_ROW + (32 * w + 2 * (lane & 3)) * 8, exc = sb + OFF_STG + (w & 1) * 2048 + lane * 16;
  uint4* const halo = p.g->halo + (((layer * 2 + t) * 16 + m) * 8 + n) * 384 + (w & 1) * 192;
  (void)wg;
  uint32_t(&Q)[4][8] = F[0], (&K)[4][8] = F[1], (&V)[4][8] = F[2], P[18];
  float kr[5][2], qr[4];
  bar_arrive(BAR_PAIR + w, 64);
  if (layer == 0 && t == 1) {
    rank1_update<7, 8, 24>(p, acc, cx, 1);
    rank1_update<31, 0, 8>(p, acc, cx, 1);
  }
#pragma unroll
  for (int q = 0; q < 4; q++) {
    qr[q] = lds_f(sb + OFF_ROW + (32 * w + 8 * q + (lane >> 2)) * 8) * (0.17677669529663687f * 1.4426950408889634f);
    const float4 r = lds_f4(ktab + 64 * q);
    kr[1 + q][0] = r.x;
    kr[1 + q][1] = r.z;
  }
  pack_qkv<7, 1>(acc, F);
  uint32_t tg[6];
#pragma unroll
  for (int k = 0; k < 6; k++) {
    tg[k] = ~tag;
    if (t == 1)
      asm volatile("{\n.reg .b128 v;\n.reg .pred g;\nsetp.ne.u32 g, %5, 0;\nmov.b128 v, {%6, %6, %6, %6};\n"
                   "@g ld.relaxed.gpu.global.b128 v, [%4];\nmov.b128 {%0, %1, %2, %3}, v;\n}"
                   : "=r"(P[3 * k]), "=r"(P[3 * k + 1]), "=r"(P[3 * k + 2]), "=r"(tg[k])
                   : "l"(halo - 8 * 384 + k * 32 + lane), "r"((uint32_t)(w < 2 && m > 0) | ((K[0][7] | K[1][7] | K[2][7]) & p.zero)), "r"(~tag) : "memory");
  }
  pack_qkv<7, 2>(acc, F);
  pack_qkv<15, 0>(acc, F);
  bar_sync(BAR_PAIR + (w ^ 2), 64);
  if (w >= 2 || m == 0) {
#pragma unroll
    for (int k = 0; k < 4; k++) lds_u4(exc + k * 512, P[4 * k], P[4 * k + 1], P[4 * k + 2], P[4 * k + 3]);
    const float4 r = lds_f4(ktab - (w >> 1) * 320);
    P[16] = __float_as_uint(r.x);
    P[17] = __float_as_uint(r.z);
  } else {
    if ((m & 1) && t == 0) __nanosleep(HALO_NS);
#pragma unroll 1
    for (int it = 0; it < MSG_SPINS; it++) {
      if (t == 0 || it > 0) {
        if (it > 0 || !(m & 1)) poll_line(reinterpret_cast<const uint32_t*>(halo - 8 * 384 + 191) + 3, tag, 1u);
#pragma unroll
        for (int k = 0; k < 6; k++) ld_msg(halo - 8 * 384 + k * 32 + lane, P[3 * k], P[3 * k + 1], P[3 * k + 2], tg[k]);
      }
      uint32_t bad = 0;
#pragma unroll
      for (int k = 0; k < 6; k++) bad |= tg[k] ^ tag;
      if (__all_sync(0xffffffffu, bad == 0)) break;
    }
  }
  kr[0][0] = __uint_as_float(P[16]);
  kr[0][1] = __uint_as_float(P[17]);
  const bool early[2] = {2 * (lane & 3) > (lane >> 2), 2 * (lane & 3) + 1 > (lane >> 2)};
  const uint32_t mask = (early[0] ? 0xffffu : 0u) | (early[1] ? 0xffff0000u : 0u);
  float rk[2][4], sc[2][4], off[2][4];
#pragma unroll
  for (int g = 0; g < 2; g++) {
#pragma unroll
    for (int e = 0; e < 4; e++) {
      const int q = 2 * g + (e >> 1);
      const bool masked = q == 0 && m == 0 && w < 2 && early[e & 1];
      rk[g][e] = early[e & 1] ? kr[q][e & 1] : kr[q + 1][e & 1];
      sc[g][e] = masked ? 0.f : rk[g][e] * qr[q];
      off[g][e] = masked ? -1e30f : 0.f;
    }
  }
  if (w == 0 && elect_one()) asm volatile("prefetch.tensormap [%0];" ::"l"(&p.t.att_st) : "memory");
  bar_sync(BAR_GO, 256);
  const float4 zero = lds_f4(sb + OFF_ZERO);
  float l[2][2][4], o[2][2][4][4], sum[2][2][2];
#pragma unroll
  for (int h = 0; h < 2; h++) {
    if (h == 1) {
      Q[2][4] |= __float_as_uint(l[1][0][0]) & p.zero;
      Q[0][4] |= __float_as_uint(l[0][0][0]) & p.zero;
    }
    attn_scores(&Q[2][4 * h], &Q[3][4 * h], &K[1][4 * h], &K[2][4 * h], &K[3][4 * h], l[1][h], zero, early);
    attn_scores(&Q[0][4 * h], &Q[1][4 * h], &P[4 * h], &K[0][4 * h], &K[1][4 * h], l[0][h], zero, early);
  }
  const uint32_t stg = sb + OFF_STG + w * 4096, srow = stg + lane * 128 + ((lane & 7) << 4);
#pragma unroll
  for (int h = 0; h < 2; h++) {
    attn_mix(l[1][h], sc[1], off[1], rk[1], &V[1][4 * h], &V[2][4 * h], &V[3][4 * h], o[1][h], sum[1][h], mask, p.zero);
    attn_mix(l[0][h], sc[0], off[0], rk[0], &P[8 + 4 * h], &V[0][4 * h], &V[1][4 * h], o[0][h], sum[0][h], mask, p.zero);
  }
  if (t == 0 && p.zero == 0) {
    uint32_t dep = 0;
#pragma unroll
    for (int k = 0; k < 16; k++) dep |= __float_as_uint(o[k >> 3][(k >> 2) & 1][k & 3][0]);
    bar_arrive(BAR_DONE | (dep & __float_as_uint(zero.x)), 256);
  }
#pragma unroll
  for (int h = 0; h < 2; h++) {
    float inv[4];
#pragma unroll
    for (int q = 0; q < 4; q++) inv[q] = rcp_hw(quad_sum(sum[q >> 1][h][q & 1]));
#pragma unroll
    for (int j = 0; j < 4; j++) {
      const float(&a)[4] = o[0][h][j];
      const float(&c)[4] = o[1][h][j];
      stsm4(srow ^ ((4 * h + j) << 4), pack_bf16(a[0] * inv[0], a[1] * inv[0]), pack_bf16(a[2] * inv[1], a[3] * inv[1]),
            pack_bf16(c[0] * inv[2], c[1] * inv[2]), pack_bf16(c[2] * inv[3], c[3] * inv[3]));
    }
  }
  if (t == 1) bar_arrive(BAR_DONE, 256);
  fence_async_smem();
  __syncwarp();
  if (lane == 0) {
    tma_st2(&p.t.att_st, stg, 128 * n + 64 * t, 128 * m + 32 * w);
    bulk_commit();
  }
}

__device__ __forceinline__ void finish_stores(uint32_t sb, int i) {
  const int t = i >= 7 ? i - 7 : i;
  if ((threadIdx.x & 31) == 0) {
    bulk_wait_all();
    mbar_arrive(sb + BAR_PUB + 8 * (t < 2 ? t : t + 1));
  }
  __syncwarp();
  if (i < 12) bar_arrive(BAR_GUARD + ((i & 1) ^ 1), 256);
}

template <int N>
__device__ __forceinline__ bool mainloop(const Params& p, float (&acc)[2][96], uint32_t sb, int i, int step, int mn) {
  constexpr uint32_t Z16 = (2 + N / 64) * (UNIT >> 4);
  constexpr uint32_t A_OFF = Z16 - 1024 + (uint32_t)DESC_A - (uint32_t)DESC_B;
  const int wg = i & 1;
  const uint32_t s16 = (sb & 0x3FFFF) >> 4;
  const uint32_t blast = (uint32_t)DESC_B + s16 + RING16 - Z16, flast = sb + BAR_FULL + 8 * (NBAR - 1);
  uint32_t blo = (uint32_t)DESC_B + s16, alo = blo + A_OFF, aoff = A_OFF, misc = 16 << 6;
  if (N == 128 || i > 0) lds_u4(sb + OFF_RUN + (2 * i + step) * 16, blo, alo, aoff, misc);
  uint32_t keep = misc & 4;
  int run = (misc >> 6) & 63, rest = misc >> 12;
  uint32_t fb = sb + BAR_FULL + (misc & 0x38), ph = misc & 1;
  uint32_t prev = sb + BAR_DUMMY - 8 * NBAR;
  const uint32_t lane_id = __popc(__ballot_sync(0xffffffffu, true) & lanemask_lt()), rel = pair_offset(sb, lane_id & 1) + 8 * NBAR;
  pin_regs<N / 2>(acc);
  if (N == 128 || i > 0) bar_sync(BAR_ORDER + wg, 256);
  else bar_sync(BAR_INIT0, 160);
  mbar_wait(fb, ph);
  if (N == 192 && i == 0) cluster_wait();
  if (misc & 2) {
    if (N == 128) {
      const Ctx cx = make_ctx(sb, mn);
      mbar_wait(sb + BAR_XRDY, 1);
      const float2 v = row_sums(cx, 0, 8);
      sts_f2(cx.sb + OFF_HALF + (32 * cx.w + cx.lane) * 8, v.x, v.y);
      bar_arrive(BAR_STAT, 256);
    }
    mbar_wait(sb + BAR_XGO, N == 192);
  }
#pragma unroll 1
  while (true) {
    const uint64_t da = (DESC_A & ~0xffffffffull) | alo, db = (DESC_B & ~0xffffffffull) | blo;
    asm volatile("wgmma.fence.sync.aligned;" ::: "memory");
    wgmma_ss<N>(acc[0], da, db, keep);
    wgmma_ss<N>(acc[1], da + 64, db, keep);
    keep = 4;
    wgmma_ss<N>(acc[0], da + 2, db + 128);
    wgmma_ss<N>(acc[1], da + 66, db + 128);
    asm volatile("wgmma.commit_group.sync.aligned;" ::: "memory");
    asm volatile("wgmma.wait_group.sync.aligned 1;" ::: "memory");
    if (lane_id < 2) mbar_arrive_cluster(prev + rel);
    prev = fb;
    if (fb == flast) { fb -= 8 * NBAR; ph++; }
    fb += 8;
    if (blo == blast) blo -= RING16;
    blo += Z16;
    alo = blo + aoff;
    aoff = A_OFF;
    run--;
    const bool ready = mbar_test(fb, ph) && run != 0;
    asm volatile("wgmma.fence.sync.aligned;" ::: "memory");
    wgmma_ss<N>(acc[0], da + 4, db + 4 * N);
    wgmma_ss<N>(acc[1], da + 68, db + 4 * N);
    wgmma_ss<N>(acc[0], da + 6, db + 4 * N + 128);
    wgmma_ss<N>(acc[1], da + 70, db + 4 * N + 128);
    asm volatile("wgmma.commit_group.sync.aligned;" ::: "memory");
    if (!ready) {
      bool window = false;
      if (run == 0) {
        if (rest == 0) break;
        window = rest & 64;
        if (window) bar_arrive(BAR_GO, 256);
        else alo = (uint32_t)DESC_A + s16 + (OFF_STG >> 4);
        run = rest & 63;
        rest >>= 7;
      }
      mbar_wait(fb, ph);
      if (window) bar_sync(BAR_DONE, 256);
    }
  }
  if constexpr (N == 192) {
    if (misc >> 12) {
      const Ctx cx = make_ctx(sb, mn);
      uint32_t F[3][4][8];
      const uint32_t fb0 = fb, blo0 = blo;
#pragma unroll 1
      for (int x = 0; x < SKEW; x++) {
        const uint64_t da = (DESC_A & ~0xffffffffull) | (blo + A_OFF + 64), db = (DESC_B & ~0xffffffffull) | blo;
        mbar_wait(fb, ph);
        asm volatile("wgmma.fence.sync.aligned;" ::: "memory");
#pragma unroll
        for (int k = 0; k < 4; k++) wgmma_ss<N>(acc[1], da + 2 * k, db + (k >> 1) * 4 * N + (k & 1) * 128);
        asm volatile("wgmma.commit_group.sync.aligned;" ::: "memory");
        asm volatile("wgmma.wait_group.sync.aligned 1;" ::: "memory");
        if (x == 0) {
          if (lane_id < 2) mbar_arrive_cluster(prev + rel);
          bar_sync(BAR_GUARD + wg, 256);
        }
        if (fb == flast) { fb -= 8 * NBAR; ph++; }
        fb += 8;
        blo += Z16;
      }
      fb = fb0;
#pragma unroll
      for (int u = 0; u < 2 * SKEW; u++) {
        const uint64_t da = (DESC_A & ~0xffffffffull) | (blo0 + (u >> 1) * Z16 + A_OFF + 4 * (u & 1));
        const uint64_t db = (DESC_B & ~0xffffffffull) | (blo0 + (u >> 1) * Z16 + 4 * N * (u & 1));
        asm volatile("wgmma.fence.sync.aligned;" ::: "memory");
        wgmma_ss<N>(acc[0], da, db);
        wgmma_ss<N>(acc[0], da + 2, db + 128);
        asm volatile("wgmma.commit_group.sync.aligned;" ::: "memory");
        if (u == 2 * SKEW - 1) break;
        asm volatile("wgmma.wait_group.sync.aligned 1;" ::: "memory");
        if (u == 0) {
#pragma unroll
          for (int r = 0; r < 96; r++) asm volatile("" : "+f"(acc[1][r])::"memory");
        }
        if (u == 2 || u == 4) {
          if (lane_id < 2) mbar_arrive_cluster(fb + rel);
          fb = fb == flast ? fb - 8 * (NBAR - 1) : fb + 8;
        }
        if (u == 0) { if (i == 1) rank1_update<8, 8, 24>(p, acc, cx, 1); pack_qkv<8, 2>(acc, F); pack_qkv<8, 1>(acc, F); }
        if (u == 1) send_halo<0, 3>(p, F, cx, i >= 7, 1);
        if (u == 2) send_halo<3, 6>(p, F, cx, i >= 7, 1);
      }
      bar_arrive(BAR_ORDER + (wg ^ 1), 256);
      asm volatile("wgmma.wait_group.sync.aligned 0;" ::: "memory");
#pragma unroll
      for (int r = 0; r < 96; r++) asm volatile("" : "+f"(acc[0][r])::"memory");
      if (lane_id < 2) mbar_arrive_cluster(fb + rel);
      attn_epilogue<1>(p, acc, F, cx, i >= 7, lds_u(sb + OFF_TAG));
      finish_stores(sb, i);
#pragma unroll
      for (int r = 0; r < 192; r++)
        asm volatile("{\n.reg .b32 t;\nxor.b32 t, %1, %2;\nmov.b32 %0, t;\n}" : "=f"(acc[r & 1][r >> 1]) : "r"(lane_id), "r"(r + 64));
      return true;
    }
  }
  if (i < 13) bar_arrive(BAR_ORDER + (wg ^ 1), 256);
  if (N == 128 && ((0x2244 >> i) & 1)) {
    const Ctx cx = make_ctx(sb, mn);
    const uint32_t xrow = cx.sb + OFF_X + cx.w * 4096 + cx.lane * 128 + ((cx.lane & 7) << 4);
    const bool leader = elect_one();
    asm volatile("wgmma.wait_group.sync.aligned 0;" ::: "memory");
    pin_regs<64>(acc);
#pragma unroll
    for (int h = 0; h < 2; h++) {
      if (h == 1 && p.zero != 0) break;
#pragma unroll
      for (int j = 8 * h; j < 8 * h + 8; j++)
        stsm4((xrow ^ ((j & 7) << 4)) + h * 16384, pack_bf16(ACC(0, j, 0), ACC(0, j, 1)), pack_bf16(ACC(1, j, 0), ACC(1, j, 1)),
              pack_bf16(ACC(2, j, 0), ACC(2, j, 1)), pack_bf16(ACC(3, j, 0), ACC(3, j, 1)));
      fence_async_smem();
      __syncwarp();
      if (leader) {
        mbar_arrive(sb + BAR_XRDY + 8 * h);
        if (i == 13) {
          tma_st_warp(&p.t.out_w, cx.sb + OFF_X + h * 16384 + cx.w * 4096, 128 * cx.n + 64 * h, cx.m, cx.w);
          bulk_commit();
          if (h == 1) bulk_wait_read();
        }
      }
      if (h == 0 && lane_id < 2 && i < 13) mbar_arrive_cluster(prev + rel);
    }
    if (i == 2 || i == 9) {
      const float2 v = row_sums(cx, 8, 16);
      bar_sync(BAR_STAT, 256);
      const float2 o = lds_f2(cx.sb + OFF_HALF + (32 * cx.w + cx.lane) * 8);
      write_partial_stats(p, cx, (i + 3) >> 2, make_float2(v.x + o.x, v.y + o.y), lds_u(sb + OFF_TAG));
    }
    return true;
  }
  asm volatile("wgmma.wait_group.sync.aligned 0;" ::: "memory");
  pin_regs<N / 2>(acc);
  if (lane_id < 2) mbar_arrive_cluster(prev + rel);
  return false;
}

__device__ __forceinline__ void finish_row_stats(const Params& p, const Ctx& c, int ln, uint32_t tag) {
  const uint4* src = p.g->stats + ln * 8 * SEQ + 128 * c.m + 32 * c.w + c.lane;
  uint32_t ps[8], pm[8];
#pragma unroll 1
  for (int it = 0; it < MSG_SPINS; it++) {
    uint32_t bad = 0, u, tg;
    if (ln == 2 || it > 0) __nanosleep(STAT_NS);
#pragma unroll
    for (int k = 0; k < 8; k++) { ld_msg(src + k * SEQ, ps[k], pm[k], u, tg); bad |= tg ^ tag; }
    if (__all_sync(0xffffffffu, bad == 0)) break;
  }
  float s = 0.f, m2 = 0.f;
#pragma unroll
  for (int k = 0; k < 8; k++) s += __uint_as_float(ps[k]);
  const float mean = s * (1.f / DM);
#pragma unroll
  for (int k = 0; k < 8; k++) {
    const float d = __uint_as_float(ps[k]) * (1.f / 128.f) - mean;
    m2 += fmaf(128.f * d, d, __uint_as_float(pm[k]));
  }
  sts_f2(c.sb + OFF_ROW + (32 * c.w + c.lane) * 8, rsqrtf(m2 * (1.f / DM) + 1e-5f), mean);
  __syncwarp();
}

__device__ __forceinline__ void gelu_epilogue(const Params& p, float (&acc)[2][96], const Ctx& cx, int t) {
  UNPACK_CTX(cx);
  (void)wg;
  float rs[4], rm[4];
#pragma unroll
  for (int q = 0; q < 4; q++) {
    const float2 v = lds_f2(sb + OFF_ROW + (32 * w + 8 * q + (lane >> 2)) * 8);
    rs[q] = 0.5f * v.x;
    rm[q] = -rs[q] * v.y;
  }
  const int col0 = 128 * (t - 3);
  const uint32_t stg = sb + OFF_STG + w * 4096;
  const uint32_t ctab = sb + OFF_CSF + (col0 / 2 + (lane & 3)) * 16, srow = stg + lane * 128 + ((lane & 7) << 4);
  if (t == 5) __nanosleep(STAG_NS * w);
  float4 nb = lds_f4(ctab);
  auto chunk = [&](auto first, int cc) {
    constexpr int c = decltype(first)::value ? 0 : 1;
    uint32_t hp[8][4];
#pragma unroll
    for (int j = 0; j < 8; j++) {
      const float4 cb = nb;
      nb = lds_f4(ctab + (8 * cc + j + 1) * 64);
#pragma unroll
      for (int q = 0; q < 4; q++) {
        float y[2];
        const int k = 4 * j + q - GELU_DEP;
        const float rmq = k >= 0 ? chain(rm[q], hp[k >> 2][k & 3], p.zero) : rm[q];
#pragma unroll
        for (int e = 0; e < 2; e++) {
          const float z = fmaf(ACC(q, 8 * c + j, e), rs[q], fmaf(rmq, e ? cb.y : cb.x, e ? cb.w : cb.z));
          const float u = z * fmaf(z * z, 8.f * 0.7978845608028654f * 0.044715f, 2.f * 0.7978845608028654f);
          y[e] = fmaf(z, tanh_hw(u), z);
        }
        hp[j][q] = pack_bf16(y[0], y[1]);
      }
      if (j == STG_WAIT && c > 0) {
        if (lane == 0) bulk_wait_read();
        __syncwarp();
      }
      if (c == 0 || j > STG_WAIT) {
        stsm4(srow ^ (j << 4), hp[j][0], hp[j][1], hp[j][2], hp[j][3]);
      } else if (j == STG_WAIT) {
#pragma unroll
        for (int jj = 0; jj <= STG_WAIT; jj++) stsm4(srow ^ (jj << 4), hp[jj][0], hp[jj][1], hp[jj][2], hp[jj][3]);
      }
    }
    fence_async_smem();
    __syncwarp();
    if (lane == 0) {
      tma_st2(&p.t.h_st, stg, 448 * n + col0 + 64 * cc, 128 * m + 32 * w);
      bulk_commit();
    }
    return hp[7][3];
  };
  chunk(std::true_type{}, 0);
#pragma unroll 1
  for (int cc = 1;; cc++) {
    const uint32_t zr = chunk(std::false_type{}, cc) & p.zero;
    if (cc == 2 || t != 5) break;
#pragma unroll
    for (int r = 0; r < 64; r++)
      asm volatile("{\n.reg .b32 x;\nmov.b32 x, %1;\nor.b32 x, x, %2;\nmov.b32 %0, x;\n}"
                   : "=f"(acc[r & 1][32 + (r >> 1)]) : "f"(acc[r & 1][64 + (r >> 1)]), "r"(zr));
  }
#pragma unroll
  for (int r = 0; r < 16; r++) acc[0][r] = acc[1][r] = 0.f;
}

__device__ __forceinline__ bool consumer_tile(const Params& p, float (&acc)[2][96], uint32_t sb0, int i, int mn) {
  const int layer = i >= 7, t = i - 7 * layer, wg = i & 1;
  const bool resid = t == 2 || t == 6;
  {
    if (resid) {
      const Ctx cx = make_ctx(sb0, mn);
      const uint32_t xrow = cx.sb + OFF_X + cx.w * 4096 + cx.lane * 128;
      const uint32_t sel_lo = 0x1044u | p.zero, sel_hi = 0x3244u | p.zero;
#pragma unroll
      for (int j = 0; j < 16; j++) {
        uint32_t r[4];
        ldsm4(xrow + (j >> 3) * 16384 + (((j & 7) ^ (cx.lane & 7)) << 4), r[0], r[1], r[2], r[3]);
#pragma unroll
        for (int q = 0; q < 4; q++) {
          ACC(q, j, 0) = prmt_f(r[q], sel_lo);
          ACC(q, j, 1) = prmt_f(r[q], sel_hi);
        }
      }
    }
    if (t >= 5 || i == 7) finish_stores(sb0, i - 2);
#pragma unroll 1
    for (int step = !tile_split(i);; step++) {
      if (step == 1 && (t == 1 || t == 4)) {
        const Ctx cx = make_ctx(sb0, mn);
        if (i == 1) {
          const uint32_t epoch = __ldcg(p.g->epoch + (mn & 127));
          cluster_wait();
          asm volatile("st.shared.u32 [%0], %1;" ::"r"(sb0 + OFF_TAG), "r"(epoch + 1) : "memory");
        }
        const uint32_t tag = lds_u(cx.sb + OFF_TAG);
        const int ln = (i + 1) >> 2;
#pragma unroll 1
        for (int r = 0; r < 2; r++) {
          if (i == 1) {
            if (cx.w < 3) {
              float a[8] = {0.f, 0.f, 0.f, 0.f, 0.f, 0.f, 0.f, 0.f};
              mbar_wait(sb0 + BAR_CSLD, r);
#pragma unroll 1
              for (int h = 0; h < 2; h++) sum_rows(cx.sb + OFF_STG + h * 12288 + cx.w * 4096, 4, a, cx.lane);
              publish_sums(a, p.g->csp + (cx.n * 17 + cx.m) * 224 + (3 * r + cx.w) * 32, cx.lane, tag);
            }
          }
          if (r == 1) break;
          if (i == 1) {
            bar_sync(BAR_WG + 1, 128);
            if (cx.w == 3 && elect_one()) {
              mbar_expect_tx(sb0 + BAR_CSLD, 24576);
              tma_ld3(sb0 + OFF_STG, &p.t.wqkv, sb0 + BAR_CSLD, 128 * cx.n + 64, 64 * cx.m, 0);
              tma_ld3(sb0 + OFF_STG + 12288, &p.t.wqkv, sb0 + BAR_CSLD, 128 * cx.n + 64, 64 * cx.m + 32, 0);
            }
            mbar_wait(sb0 + BAR_XRDY, 0);
            mbar_wait(sb0 + BAR_XRDY + 8, 0);
          }
          if (t == 1) write_partial_stats(p, cx, ln, row_sums(cx, 0, 16), tag);
        }
        if (i == 1) {
          bar_arrive(BAR_HLP, 160);
          bar_sync(BAR_INIT, 160);
        }
        if (i == 4) colsum_total(p, cx, 1, tag);
        if (i != 1) bar_sync(BAR_GUARD + wg, 256);
        finish_row_stats(p, cx, ln, tag);
        if (i == 4) {
          colsum_gather(p, cx, 1, tag);
          mbar_wait(sb0 + BAR_BIAS, 0);
        }
        bar_arrive(BAR_GUARD + (wg ^ 1), 256);
      }
      if (step == 2) bar_sync(BAR_GUARD + wg, 256);
      if (step == 2 && i == 0) {
        colsum_gather(p, make_ctx(sb0, mn), 0, lds_u(sb0 + OFF_TAG));
        bar_sync(BAR_WG, 128);
      }
      if ((t + step == 2 && i != 1) || t == 6) rank1_update<15>(p, acc, make_ctx(sb0, mn), t);
      if (step == 2) break;
      if (tile_wide(t)) {
        if (mainloop<192>(p, acc, sb0, i, step, mn)) return false;
      } else {
        if (mainloop<128>(p, acc, sb0, i, step, mn)) return false;
      }
    }
    if (t < 2) return true;
    gelu_epilogue(p, acc, make_ctx(sb0, mn), t);
    return false;
  }
}

template <bool BY_SMID>
__global__ void __cluster_dims__(2, 1, 1) __launch_bounds__(384, 1)
fused_layers_kernel(const Scalars scalars, const __grid_constant__ Maps maps) {
  if (threadIdx.x == 288 || threadIdx.x == 320)
    asm volatile("prefetch.tensormap [%0];" ::"l"(threadIdx.x == 288 ? &maps.xin : &maps.wqkv) : "memory");
  const Params p{scalars, maps};
  extern __shared__ __align__(1024) uint8_t smem_raw[];
  const uint32_t sb = uniform((uint32_t)__cvta_generic_to_shared(smem_raw));
  const int tid = threadIdx.x, lane = tid & 31, warp = uniform(tid >> 5), wg = warp >> 2, w = warp & 3;

  int mn;
  {
    int id = blockIdx.x;
    if (BY_SMID) asm volatile("mov.u32 %0, %%smid;" : "=r"(id));
    else if (id >= 120) id += 4;
    const int c = id >> 1;
    int g, j;
    if (c < 32) { g = c & 7; j = c >> 3; }
    else if (c < 60) { g = 1 + (c - 32) % 7; j = 4 + (c - 32) / 7; }
    else { g = 0; j = c - 58; }
    mn = (g * 2 + (blockIdx.x & 1)) * 8 + j;
    if (c == 60 || c == 61) {
      if (tid < 32) {
        const uint32_t tag = __ldcg(p.g->epoch + NCTA + (id & 3)) + 1;
#pragma unroll 1
        for (int mm = 0; mm < 16; mm++) poll_line(p.g->flags + mm * 32 + (lane & 7), 32 * tag, 0xffu);
        if (tid == 0) p.g->epoch[NCTA + (id & 3)] = tag;
      }
      return;
    }
  }
  const int m = mn >> 3, n = mn & 7;
  if (wg < 2) {
    cluster_arrive();
    asm volatile("setmaxnreg.inc.sync.aligned.u32 232;");
    const int id = mn | (warp << 7);
#pragma unroll 1
    for (int i = wg;; i += 2) {
      float acc[2][96];
#pragma unroll
      for (int r = 0; r < 96; r++) acc[0][r] = acc[1][r] = 0.f;
      pin_regs<96>(acc);
#pragma unroll 1
      while (!consumer_tile(p, acc, sb, i, id)) {
        i += 2;
        if (i >= 14) goto all_done;
      }
      const Ctx cx = make_ctx(sb, id);
      uint32_t F[3][4][8];
      pack_qkv<8, 2>(acc, F);
      pack_qkv<8, 1>(acc, F);
      send_halo<0, 6>(p, F, cx, i >= 7, 0);
      attn_epilogue<0>(p, acc, F, cx, i >= 7, lds_u(sb + OFF_TAG));
      finish_stores(sb, i);
    }
  all_done:
    if (wg == 0) {
      finish_stores(sb, 12);
    } else {
      cluster_arrive();
      cluster_wait();
    }
  } else {
    asm volatile("setmaxnreg.dec.sync.aligned.u32 40;");
    if (w != 0) {
      if (w == 1 && elect_one()) {
        mbar_init(sb + BAR_FULL + 32, 2);
#pragma unroll
        for (int k = 0; k < NBAR; k++) mbar_init(sb + BAR_EMPTY + 8 * k, 8);
#pragma unroll
        for (int k = 0; k < 3; k++) mbar_init(sb + BAR_XRDY + 8 * k, 4);
#pragma unroll
        for (int k = 0; k < 9; k++) mbar_init(sb + BAR_PUB + 8 * k, 4);
#pragma unroll
        for (int k = 0; k < 4; k++) mbar_init(sb + BAR_CSLD + 8 * k, 1);
        sts_f2(sb + OFF_ZERO, 0.f, 0.f);
        sts_f2(sb + OFF_ZERO + 8, 0.f, 0.f);
        asm volatile("fence.mbarrier_init.release.cluster;" ::: "memory");
      }
      __syncwarp();
      cluster_arrive();
      if (w == 2) {
        if (lane < 28) write_run_desc(sb, lane >> 1, lane & 1);
        bar_arrive(BAR_INIT, 160);
      }
      cluster_wait();
      if (w == 1) producer<true>(p, sb, m, n, lane);
      else if (w == 3) colsum_helper(p, sb, m, n, lane);
      else if (elect_one()) publisher(p, sb, m, n);
    } else {
      const bool leader = elect_one();
      if (leader) {
#pragma unroll
        for (int k = 0; k < 4; k++) mbar_init(sb + BAR_FULL + 8 * k, 2);
        asm volatile("fence.mbarrier_init.release.cluster;" ::: "memory");
      }
      __syncwarp();
      bar_arrive(BAR_INIT0, 160);
      cluster_arrive();
      if (leader) {
#pragma unroll 1
        for (int k = 0; k < 4; k++) {
          const uint32_t fb = sb + BAR_FULL + 8 * k;
          mbar_expect_tx(fb, 16384);
          tma_ld_act(sb + (5 * k + 3) * UNIT, &p.t.xin, fb, 64 * k, m);
          mbar_expect_tx(fb, 3 * UNIT);
          tma_ld3(sb + 5 * k * UNIT, &p.t.wqkv, fb, 128 * n, 64 * k, 0);
          tma_ld3(sb + 5 * k * UNIT + 12288, &p.t.wqkv, fb, 128 * n, 64 * k + 32, 0);
        }
      }
      __syncwarp();
      cluster_wait();
      producer<false>(p, sb, m, n, lane);
    }
  }
}

typedef CUresult (*EncodeFn)(CUtensorMap*, CUtensorMapDataType, cuuint32_t, void*, const cuuint64_t*, const cuuint64_t*,
                             const cuuint32_t*, const cuuint32_t*, CUtensorMapInterleave, CUtensorMapSwizzle,
                             CUtensorMapL2promotion, CUtensorMapFloatOOBfill);

void make_2d(EncodeFn enc, CUtensorMap* m, const void* ptr, uint64_t cols, uint64_t rows, uint32_t box_rows) {
  cuuint64_t d[2] = {cols, rows}, st[1] = {cols * 2};
  cuuint32_t b[2] = {64, box_rows}, e[2] = {1, 1};
  enc(m, CU_TENSOR_MAP_DATA_TYPE_BFLOAT16, 2, const_cast<void*>(ptr), d, st, b, e, CU_TENSOR_MAP_INTERLEAVE_NONE,
      CU_TENSOR_MAP_SWIZZLE_128B, CU_TENSOR_MAP_L2_PROMOTION_L2_128B, CU_TENSOR_MAP_FLOAT_OOB_FILL_NONE);
}
void make_act(EncodeFn enc, CUtensorMap* m, const void* ptr, uint64_t cols, bool split, uint32_t box = 2) {
  const uint64_t row = cols * 2;
  cuuint64_t d[4] = {cols, 32, 2, SEQ / 64}, st[3] = {split ? 2 * row : row, split ? row : 32 * row, 64 * row};
  cuuint32_t b[4] = {64, 32, box, box}, e[4] = {1, 1, 1, 1};
  enc(m, CU_TENSOR_MAP_DATA_TYPE_BFLOAT16, 4, const_cast<void*>(ptr), d, st, b, e, CU_TENSOR_MAP_INTERLEAVE_NONE,
      CU_TENSOR_MAP_SWIZZLE_128B, CU_TENSOR_MAP_L2_PROMOTION_L2_128B, CU_TENSOR_MAP_FLOAT_OOB_FILL_NONE);
}
void make_3d(EncodeFn enc, CUtensorMap* m, const void* ptr, uint64_t d0, uint64_t rows, uint64_t d2, uint64_t row_bytes,
             uint64_t chunk_bytes, uint32_t box_chunks) {
  cuuint64_t d[3] = {d0, rows, d2}, st[2] = {row_bytes, chunk_bytes};
  cuuint32_t b[3] = {64, 32, box_chunks}, e[3] = {1, 1, 1};
  enc(m, CU_TENSOR_MAP_DATA_TYPE_BFLOAT16, 3, const_cast<void*>(ptr), d, st, b, e, CU_TENSOR_MAP_INTERLEAVE_NONE,
      CU_TENSOR_MAP_SWIZZLE_128B, CU_TENSOR_MAP_L2_PROMOTION_L2_128B, CU_TENSOR_MAP_FLOAT_OOB_FILL_NONE);
}

}

extern "C" void kernel_launch(void* const* d_in, const int* in_sizes, int n_in, void* d_out, int out_size) {
  (void)in_sizes; (void)n_in; (void)out_size;
  static EncodeFn enc = nullptr;
  static void *att = nullptr, *hbuf = nullptr, *scratch = nullptr;
  static int by_smid = 0;
  if (!enc) {
    void* fn = nullptr;
    cudaDriverEntryPointQueryResult q;
    cudaGetDriverEntryPoint("cuTensorMapEncodeTiled", &fn, cudaEnableDefault, &q);
    enc = (EncodeFn)fn;
    cudaGetSymbolAddress(&att, g_att);
    cudaGetSymbolAddress(&hbuf, g_h);
    cudaGetSymbolAddress(&scratch, g_scratch);
    cudaFuncSetAttribute(fused_layers_kernel<true>, cudaFuncAttributeMaxDynamicSharedMemorySize, SMEM_BYTES);
    cudaFuncSetAttribute(fused_layers_kernel<false>, cudaFuncAttributeMaxDynamicSharedMemorySize, SMEM_BYTES);
    int sms = 0, clusters = 0, dev = 0;
    cudaGetDevice(&dev);
    cudaDeviceGetAttribute(&sms, cudaDevAttrMultiProcessorCount, dev);
    cudaLaunchConfig_t cfg = {};
    cfg.gridDim = dim3(132);
    cfg.blockDim = dim3(384);
    cfg.dynamicSmemBytes = SMEM_BYTES;
    cudaLaunchAttribute at[1];
    at[0].id = cudaLaunchAttributeClusterDimension;
    at[0].val.clusterDim.x = 2; at[0].val.clusterDim.y = 1; at[0].val.clusterDim.z = 1;
    cfg.attrs = at;
    cfg.numAttrs = 1;
    if (cudaOccupancyMaxActiveClusters(&clusters, fused_layers_kernel<true>, &cfg) != cudaSuccess) (void)cudaGetLastError();
    by_smid = sms == 132 && clusters == 66;
  }
  Maps p;
  Scalars sc;
  make_act(enc, &p.xin, d_in[0], DM, true);
  make_act(enc, &p.out, d_out, DM, true);
  make_act(enc, &p.out_w, d_out, DM, true, 1);
  make_act(enc, &p.att, att, DM, false);
  make_act(enc, &p.h, hbuf, FF, false);
  make_2d(enc, &p.att_st, att, DM, SEQ, 32);
  make_2d(enc, &p.h_st, hbuf, FF, SEQ, 32);
  make_2d(enc, &p.w1c, d_in[4], FF, DM, 32);
  make_3d(enc, &p.wqkv, d_in[1], DM, DM, 3, 3 * DM * 2, DM * 2, 3);
  make_3d(enc, &p.wo, d_in[2], 64, DM, DM / 64, DM * 2, 128, 2);
  make_3d(enc, &p.w1a, d_in[4], 64, DM, FF / 64, FF * 2, 128, 3);
  make_3d(enc, &p.w1b, d_in[4], 64, DM, FF / 64, FF * 2, 128, 2);
  make_3d(enc, &p.w2, d_in[6], 64, FF, DM / 64, DM * 2, 128, 2);
  sc.b1 = (const __nv_bfloat16*)d_in[5];
  sc.b2 = (const __nv_bfloat16*)d_in[7];
  sc.g = (Scratch*)scratch;
  sc.zero = 0;
  if (by_smid) fused_layers_kernel<true><<<132, 384, SMEM_BYTES>>>(sc, p);
  else fused_layers_kernel<false><<<NCTA, 384, SMEM_BYTES>>>(sc, p);
}
```

```cpp
#include <cuda_runtime.h>
#include <cuda_bf16.h>
#include <cuda.h>
#include <stdint.h>
#include <type_traits>

namespace {

constexpr int SEQ = 2048, DM = 1024, FF = 3584;
constexpr int NCTA = 128;
constexpr int NBAR = 5;

constexpr uint32_t RING_UNITS = 20, UNIT = 8192;
constexpr uint32_t OFF_X   = RING_UNITS * UNIT;
constexpr uint32_t OFF_STG = OFF_X + 32768;
constexpr uint32_t OFF_HLP = OFF_STG + 16384;
constexpr uint32_t OFF_RUN = OFF_STG + 24576;
constexpr uint32_t OFF_CSQ = OFF_RUN + 512;
constexpr uint32_t OFF_CSF = OFF_CSQ + 2048;
constexpr uint32_t OFF_ROW = OFF_CSF + 3584;
constexpr uint32_t OFF_HALF = OFF_ROW + 1024;
constexpr uint32_t OFF_BAR = OFF_HALF + 1024;
constexpr uint32_t SMEM_BYTES = OFF_BAR + 384;
constexpr uint32_t BAR_FULL = OFF_BAR, BAR_EMPTY = OFF_BAR + 8 * NBAR;
constexpr uint32_t BAR_XRDY = OFF_BAR + 80;
constexpr uint32_t BAR_DUMMY = OFF_BAR + 96, OFF_TAG = OFF_BAR + 104, OFF_ZERO = OFF_BAR + 112;
constexpr uint32_t BAR_PUB = OFF_BAR + 128;
constexpr uint32_t BAR_CSLD = OFF_BAR + 200;
constexpr uint32_t BAR_BIAS = OFF_BAR + 216;
constexpr uint32_t BAR_XGO = OFF_BAR + 224;

constexpr uint64_t DESC_A = (1ull << 62) | ((uint64_t)(2048 >> 4) << 32) | (1ull << 16);
constexpr uint64_t DESC_B = (1ull << 62) | ((uint64_t)(1024 >> 4) << 32) | ((uint64_t)(4096 >> 4) << 16);

constexpr int BAR_INIT = 0, BAR_ORDER = 1, BAR_GUARD = 3, BAR_WG = 5, BAR_GO = 7, BAR_DONE = 8, BAR_HLP = 9;
constexpr int BAR_INIT0 = 10, BAR_PAIR = 11, BAR_STAT = 15;

constexpr int WIN1 = 5;
constexpr int WIN0 = 7;
constexpr int SKEW = 3;
constexpr int WIN2 = 1;
constexpr int GELU_DEP = 2;
constexpr int STG_WAIT = 5;
constexpr int HALO_NS = 200;
constexpr int STAT_NS = 800;
constexpr int CS_NS = 500;
constexpr int XB_NS = 400;
constexpr int XB_GAP_NS = 50;
constexpr int STAG_NS = 450;
constexpr int STAG3_NS = 100;
constexpr int PACE_M = 100;
constexpr int PACE_N = 300;

struct Scratch {
  uint4 stats[4 * 8 * SEQ];
  uint4 halo[2 * 2 * 16 * 8 * 384];
  uint4 csp[2 * 8 * 17 * 224];
  uint32_t flags[16 * 32];
  uint32_t epoch[NCTA + 4];
};

struct Maps {
  CUtensorMap xin, out, att, h, wqkv, wo, w1a, w1b, w2, att_st, h_st, w1c, out_w;
};
struct Scalars {
  Scratch* g;
  const __nv_bfloat16 *b1, *b2;
  uint32_t zero;
};
struct Params : Scalars {
  const Maps& t;
};

__device__ __nv_bfloat16 g_att[SEQ * DM];
__device__ __nv_bfloat16 g_h[SEQ * FF];
__device__ Scratch g_scratch;

__device__ __forceinline__ void mbar_init(uint32_t bar, int cnt) {
  asm volatile("mbarrier.init.shared::cta.b64 [%0], %1;" ::"r"(bar), "r"(cnt));
}
__device__ __forceinline__ void mbar_expect_tx(uint32_t bar, uint32_t bytes) {
  asm volatile("mbarrier.arrive.expect_tx.shared::cta.b64 _, [%0], %1;" ::"r"(bar), "r"(bytes) : "memory");
}
__device__ __forceinline__ void mbar_arrive(uint32_t bar) {
  asm volatile("mbarrier.arrive.shared::cta.b64 _, [%0];" ::"r"(bar) : "memory");
}
__device__ __forceinline__ bool mbar_test(uint32_t bar, uint32_t parity) {
  uint32_t ok;
  asm volatile("{\n.reg .pred p;\nmbarrier.test_wait.parity.shared::cta.b64 p, [%1], %2;\nselp.u32 %0, 1, 0, p;\n}"
               : "=r"(ok) : "r"(bar), "r"(parity) : "memory");
  return ok;
}
__device__ __forceinline__ void mbar_wait(uint32_t bar, uint32_t parity) {
  asm volatile(
      "{\n.reg .pred p;\n.reg .u32 it;\nmov.u32 it, 0;\n"
      "WAIT_LOOP:\n"
      "mbarrier.try_wait.parity.shared::cta.b64 p, [%0], %1;\n"
      "@p bra WAIT_DONE;\n"
      "add.u32 it, it, 1;\n"
      "setp.lt.u32 p, it, 0x400000;\n"
      "@p bra WAIT_LOOP;\n"
      "trap;\n"
      "WAIT_DONE:\n}"
      ::"r"(bar), "r"(parity) : "memory");
}
__device__ __forceinline__ void bar_sync(int id, int n) { asm volatile("bar.sync %0, %1;" ::"r"(id), "r"(n) : "memory"); }
__device__ __forceinline__ void bar_arrive(int id, int n) { asm volatile("bar.arrive %0, %1;" ::"r"(id), "r"(n) : "memory"); }
__device__ __forceinline__ void tma_ld2(uint32_t dst, const CUtensorMap* m, uint32_t bar, int c0, int c1) {
  asm volatile("cp.async.bulk.tensor.2d.shared::cluster.global.mbarrier::complete_tx::bytes [%0], [%1, {%3, %4}], [%2];"
               ::"r"(dst), "l"(m), "r"(bar), "r"(c0), "r"(c1) : "memory");
}
__device__ __forceinline__ void tma_ld_act(uint32_t dst, const CUtensorMap* m, uint32_t bar, int col, int blk) {
  asm volatile("cp.async.bulk.tensor.4d.shared::cluster.global.mbarrier::complete_tx::bytes [%0], [%1, {%3, %5, %5, %4}], [%2];"
               ::"r"(dst), "l"(m), "r"(bar), "r"(col), "r"(2 * blk), "r"(0) : "memory");
}
__device__ __forceinline__ void tma_st_act(const CUtensorMap* m, uint32_t src, int col, int blk) {
  asm volatile("cp.async.bulk.tensor.4d.global.shared::cta.bulk_group [%0, {%2, %4, %4, %3}], [%1];"
               ::"l"(m), "r"(src), "r"(col), "r"(2 * blk), "r"(0) : "memory");
}
__device__ __forceinline__ void tma_st_warp(const CUtensorMap* m, uint32_t src, int col, int blk, int w) {
  asm volatile("cp.async.bulk.tensor.4d.global.shared::cta.bulk_group [%0, {%2, %5, %3, %4}], [%1];"
               ::"l"(m), "r"(src), "r"(col), "r"(w & 1), "r"(2 * blk + (w >> 1)), "r"(0) : "memory");
}
__device__ __forceinline__ void tma_ld3(uint32_t dst, const CUtensorMap* m, uint32_t bar, int c0, int c1, int c2) {
  asm volatile("cp.async.bulk.tensor.3d.shared::cluster.global.mbarrier::complete_tx::bytes [%0], [%1, {%3, %4, %5}], [%2];"
               ::"r"(dst), "l"(m), "r"(bar), "r"(c0), "r"(c1), "r"(c2) : "memory");
}
__device__ __forceinline__ void tma_ld3_pair(uint32_t dst, const CUtensorMap* m, uint32_t bar, int c0, int c1, int c2) {
  asm volatile("cp.async.bulk.tensor.3d.shared::cluster.global.mbarrier::complete_tx::bytes.multicast::cluster"
               " [%0], [%1, {%3, %4, %5}], [%2], %6;"
               ::"r"(dst), "l"(m), "r"(bar), "r"(c0), "r"(c1), "r"(c2), "h"((uint16_t)3) : "memory");
}
__device__ __forceinline__ uint32_t pair_offset(uint32_t sb, uint32_t rank) {
  uint32_t r;
  asm volatile("mapa.shared::cluster.u32 %0, %1, %2;" : "=r"(r) : "r"(sb), "r"(rank));
  return r - sb;
}
__device__ __forceinline__ void mbar_arrive_cluster(uint32_t bar) {
  asm volatile("mbarrier.arrive.shared::cluster.b64 _, [%0];" ::"r"(bar) : "memory");
}
__device__ __forceinline__ void cluster_arrive() { asm volatile("barrier.cluster.arrive.relaxed;" ::: "memory"); }
__device__ __forceinline__ void cluster_wait() { asm volatile("barrier.cluster.wait.acquire;" ::: "memory"); }
__device__ __forceinline__ void tma_st2(const CUtensorMap* m, uint32_t src, int c0, int c1) {
  asm volatile("cp.async.bulk.tensor.2d.global.shared::cta.bulk_group [%0, {%2, %3}], [%1];"
               ::"l"(m), "r"(src), "r"(c0), "r"(c1) : "memory");
}
__device__ __forceinline__ void bulk_commit() { asm volatile("cp.async.bulk.commit_group;" ::: "memory"); }
__device__ __forceinline__ void bulk_wait_read() { asm volatile("cp.async.bulk.wait_group.read 0;" ::: "memory"); }
__device__ __forceinline__ void bulk_wait_all() { asm volatile("cp.async.bulk.wait_group 0;" ::: "memory"); }
__device__ __forceinline__ void fence_async_smem() { asm volatile("fence.proxy.async.shared::cta;" ::: "memory"); }
__device__ __forceinline__ void fence_async_global() { asm volatile("fence.proxy.async.global;" ::: "memory"); }
__device__ __forceinline__ void st_relaxed(uint32_t* p, uint32_t v) {
  asm volatile("st.relaxed.gpu.global.u32 [%0], %1;" ::"l"(p), "r"(v) : "memory");
}
__device__ __forceinline__ void st_msg(uint4* p, uint32_t a, uint32_t b, uint32_t c, uint32_t tag) {
  asm volatile("{\n.reg .b128 v;\nmov.b128 v, {%1, %2, %3, %4};\nst.relaxed.gpu.global.b128 [%0], v;\n}"
               ::"l"(p), "r"(a), "r"(b), "r"(c), "r"(tag) : "memory");
}
__device__ __forceinline__ void ld_msg(const uint4* p, uint32_t& a, uint32_t& b, uint32_t& c, uint32_t& tag) {
  asm volatile("{\n.reg .b128 v;\nld.relaxed.gpu.global.b128 v, [%4];\nmov.b128 {%0, %1, %2, %3}, v;\n}"
               : "=r"(a), "=r"(b), "=r"(c), "=r"(tag) : "l"(p) : "memory");
}
__device__ __forceinline__ bool elect_one() {
  uint32_t ok;
  asm volatile("{\n.reg .pred p;\nelect.sync _|p, 0xffffffff;\nselp.u32 %0, 1, 0, p;\n}" : "=r"(ok));
  return ok;
}
__device__ __forceinline__ uint32_t lanemask_lt() {
  uint32_t v;
  asm("mov.u32 %0, %%lanemask_lt;" : "=r"(v));
  return v;
}
__device__ __forceinline__ int uniform(int v) { return __shfl_sync(0xffffffffu, v, 0); }
__device__ __forceinline__ uint32_t pack_bf16(float lo, float hi) {
  uint32_t r;
  asm("cvt.rn.bf16x2.f32 %0, %1, %2;" : "=r"(r) : "f"(hi), "f"(lo));
  return r;
}
__device__ __forceinline__ float prmt_f(uint32_t a, uint32_t sel) {
  float r;
  asm("{\n.reg .b32 t;\nprmt.b32 t, %1, 0, %2;\nmov.b32 %0, t;\n}" : "=f"(r) : "r"(a), "r"(sel));
  return r;
}
__device__ __forceinline__ float bf_lo(uint32_t v) { return __uint_as_float(v << 16); }
__device__ __forceinline__ float bf_hi(uint32_t v) { return __uint_as_float(v & 0xffff0000u); }
__device__ __forceinline__ void stsm4(uint32_t addr, uint32_t r0, uint32_t r1, uint32_t r2, uint32_t r3) {
  asm volatile("stmatrix.sync.aligned.m8n8.x4.shared.b16 [%0], {%1, %2, %3, %4};"
               ::"r"(addr), "r"(r0), "r"(r1), "r"(r2), "r"(r3) : "memory");
}
__device__ __forceinline__ void ldsm4(uint32_t addr, uint32_t& r0, uint32_t& r1, uint32_t& r2, uint32_t& r3) {
  asm volatile("ldmatrix.sync.aligned.m8n8.x4.shared.b16 {%0, %1, %2, %3}, [%4];"
               : "=r"(r0), "=r"(r1), "=r"(r2), "=r"(r3) : "r"(addr) : "memory");
}
__device__ __forceinline__ uint32_t movtrans(uint32_t a) {
  uint32_t d;
  asm volatile("movmatrix.sync.aligned.m8n8.trans.b16 %0, %1;" : "=r"(d) : "r"(a));
  return d;
}
__device__ __forceinline__ void mma16816(float (&c)[4], uint32_t a0, uint32_t a1, uint32_t a2, uint32_t a3, uint32_t b0, uint32_t b1) {
  asm volatile("mma.sync.aligned.m16n8k16.row.col.f32.bf16.bf16.f32 {%0,%1,%2,%3}, {%4,%5,%6,%7}, {%8,%9}, {%0,%1,%2,%3};"
               : "+f"(c[0]), "+f"(c[1]), "+f"(c[2]), "+f"(c[3])
               : "r"(a0), "r"(a1), "r"(a2), "r"(a3), "r"(b0), "r"(b1));
}
__device__ __forceinline__ void mma1688(float (&c)[4], uint32_t a0, uint32_t a1, uint32_t b0) {
  asm volatile("mma.sync.aligned.m16n8k8.row.col.f32.bf16.bf16.f32 {%0,%1,%2,%3}, {%4,%5}, {%6}, {%0,%1,%2,%3};"
               : "+f"(c[0]), "+f"(c[1]), "+f"(c[2]), "+f"(c[3]) : "r"(a0), "r"(a1), "r"(b0));
}
__device__ __forceinline__ float2 lds_f2(uint32_t a) {
  float2 v;
  asm volatile("ld.shared.v2.f32 {%0, %1}, [%2];" : "=f"(v.x), "=f"(v.y) : "r"(a) : "memory");
  return v;
}
__device__ __forceinline__ float4 lds_f4(uint32_t a) {
  float4 v;
  asm volatile("ld.shared.v4.f32 {%0, %1, %2, %3}, [%4];" : "=f"(v.x), "=f"(v.y), "=f"(v.z), "=f"(v.w) : "r"(a) : "memory");
  return v;
}
__device__ __forceinline__ float lds_f(uint32_t a) {
  float v;
  asm volatile("ld.shared.f32 %0, [%1];" : "=f"(v) : "r"(a) : "memory");
  return v;
}
__device__ __forceinline__ uint32_t lds_u(uint32_t a) {
  uint32_t v;
  asm volatile("ld.shared.u32 %0, [%1];" : "=r"(v) : "r"(a) : "memory");
  return v;
}
__device__ __forceinline__ void sts_f2(uint32_t a, float x, float y) {
  asm volatile("st.shared.v2.f32 [%0], {%1, %2};" ::"r"(a), "f"(x), "f"(y) : "memory");
}
__device__ __forceinline__ void sts_u4(uint32_t a, uint32_t x, uint32_t y, uint32_t z, uint32_t w) {
  asm volatile("st.shared.v4.u32 [%0], {%1, %2, %3, %4};" ::"r"(a), "r"(x), "r"(y), "r"(z), "r"(w) : "memory");
}
__device__ __forceinline__ void lds_u4(uint32_t a, uint32_t& x, uint32_t& y, uint32_t& z, uint32_t& w) {
  asm volatile("ld.shared.v4.u32 {%0, %1, %2, %3}, [%4];" : "=r"(x), "=r"(y), "=r"(z), "=r"(w) : "r"(a) : "memory");
}
__device__ __forceinline__ float ex2(float x) {
  float y;
  asm("ex2.approx.ftz.f32 %0, %1;" : "=f"(y) : "f"(x));
  return y;
}
__device__ __forceinline__ float rcp_hw(float x) {
  float y;
  asm("rcp.approx.ftz.f32 %0, %1;" : "=f"(y) : "f"(x));
  return y;
}
__device__ __forceinline__ float tanh_hw(float x) {
  float y;
  asm("tanh.approx.f32 %0, %1;" : "=f"(y) : "f"(x));
  return y;
}
__device__ __forceinline__ float quad_sum(float v) {
  v += __shfl_xor_sync(0xffffffffu, v, 1);
  return v + __shfl_xor_sync(0xffffffffu, v, 2);
}
__device__ __forceinline__ float quad_max(float v) {
  v = fmaxf(v, __shfl_xor_sync(0xffffffffu, v, 1));
  return fmaxf(v, __shfl_xor_sync(0xffffffffu, v, 2));
}

template <int N> __device__ __forceinline__ void wgmma_ss(float (&d)[96], uint64_t da, uint64_t db, uint32_t keep = 1);
template <> __device__ __forceinline__ void wgmma_ss<128>(float (&d)[96], uint64_t da, uint64_t db, uint32_t keep) {
  asm volatile(
      "{\n.reg .pred p;\nsetp.ne.u32 p, %66, 0;\n"
      "wgmma.mma_async.sync.aligned.m64n128k16.f32.bf16.bf16 {%0, %1, %2, %3, %4, %5, %6, %7, %8, %9, %10, %11, %12, %13, %14, %15, %16, %17, %18, %19, %20, %21, %22, %23, %24, %25, %26, %27, %28, %29, %30, %31, %32, %33, %34, %35, %36, %37, %38, %39, %40, %41, %42, %43, %44, %45, %46, %47, %48, %49, %50, %51, %52, %53, %54, %55, %56, %57, %58, %59, %60, %61, %62, %63}, %64, %65, p, 1, 1, 0, 1;\n}"
      : "+f"(d[0]), "+f"(d[1]), "+f"(d[2]), "+f"(d[3]), "+f"(d[4]), "+f"(d[5]), "+f"(d[6]), "+f"(d[7]), "+f"(d[8]), "+f"(d[9]), "+f"(d[10]), "+f"(d[11]), "+f"(d[12]), "+f"(d[13]), "+f"(d[14]), "+f"(d[15]), "+f"(d[16]), "+f"(d[17]), "+f"(d[18]), "+f"(d[19]), "+f"(d[20]), "+f"(d[21]), "+f"(d[22]), "+f"(d[23]), "+f"(d[24]), "+f"(d[25]), "+f"(d[26]), "+f"(d[27]), "+f"(d[28]), "+f"(d[29]), "+f"(d[30]), "+f"(d[31]), "+f"(d[32]), "+f"(d[33]), "+f"(d[34]), "+f"(d[35]), "+f"(d[36]), "+f"(d[37]), "+f"(d[38]), "+f"(d[39]), "+f"(d[40]), "+f"(d[41]), "+f"(d[42]), "+f"(d[43]), "+f"(d[44]), "+f"(d[45]), "+f"(d[46]), "+f"(d[47]), "+f"(d[48]), "+f"(d[49]), "+f"(d[50]), "+f"(d[51]), "+f"(d[52]), "+f"(d[53]), "+f"(d[54]), "+f"(d[55]), "+f"(d[56]), "+f"(d[57]), "+f"(d[58]), "+f"(d[59]), "+f"(d[60]), "+f"(d[61]), "+f"(d[62]), "+f"(d[63])
      : "l"(da), "l"(db), "r"(keep));
}

template <> __device__ __forceinline__ void wgmma_ss<192>(float (&d)[96], uint64_t da, uint64_t db, uint32_t keep) {
  asm volatile(
      "{\n.reg .pred p;\nsetp.ne.u32 p, %98, 0;\n"
      "wgmma.mma_async.sync.aligned.m64n192k16.f32.bf16.bf16 {%0, %1, %2, %3, %4, %5, %6, %7, %8, %9, %10, %11, %12, %13, %14, %15, %16, %17, %18, %19, %20, %21, %22, %23, %24, %25, %26, %27, %28, %29, %30, %31, %32, %33, %34, %35, %36, %37, %38, %39, %40, %41, %42, %43, %44, %45, %46, %47, %48, %49, %50, %51, %52, %53, %54, %55, %56, %57, %58, %59, %60, %61, %62, %63, %64, %65, %66, %67, %68, %69, %70, %71, %72, %73, %74, %75, %76, %77, %78, %79, %80, %81, %82, %83, %84, %85, %86, %87, %88, %89, %90, %91, %92, %93, %94, %95}, %96, %97, p, 1, 1, 0, 1;\n}"
      : "+f"(d[0]), "+f"(d[1]), "+f"(d[2]), "+f"(d[3]), "+f"(d[4]), "+f"(d[5]), "+f"(d[6]), "+f"(d[7]), "+f"(d[8]), "+f"(d[9]), "+f"(d[10]), "+f"(d[11]), "+f"(d[12]), "+f"(d[13]), "+f"(d[14]), "+f"(d[15]), "+f"(d[16]), "+f"(d[17]), "+f"(d[18]), "+f"(d[19]), "+f"(d[20]), "+f"(d[21]), "+f"(d[22]), "+f"(d[23]), "+f"(d[24]), "+f"(d[25]), "+f"(d[26]), "+f"(d[27]), "+f"(d[28]), "+f"(d[29]), "+f"(d[30]), "+f"(d[31]), "+f"(d[32]), "+f"(d[33]), "+f"(d[34]), "+f"(d[35]), "+f"(d[36]), "+f"(d[37]), "+f"(d[38]), "+f"(d[39]), "+f"(d[40]), "+f"(d[41]), "+f"(d[42]), "+f"(d[43]), "+f"(d[44]), "+f"(d[45]), "+f"(d[46]), "+f"(d[47]), "+f"(d[48]), "+f"(d[49]), "+f"(d[50]), "+f"(d[51]), "+f"(d[52]), "+f"(d[53]), "+f"(d[54]), "+f"(d[55]), "+f"(d[56]), "+f"(d[57]), "+f"(d[58]), "+f"(d[59]), "+f"(d[60]), "+f"(d[61]), "+f"(d[62]), "+f"(d[63]), "+f"(d[64]), "+f"(d[65]), "+f"(d[66]), "+f"(d[67]), "+f"(d[68]), "+f"(d[69]), "+f"(d[70]), "+f"(d[71]), "+f"(d[72]), "+f"(d[73]), "+f"(d[74]), "+f"(d[75]), "+f"(d[76]), "+f"(d[77]), "+f"(d[78]), "+f"(d[79]), "+f"(d[80]), "+f"(d[81]), "+f"(d[82]), "+f"(d[83]), "+f"(d[84]), "+f"(d[85]), "+f"(d[86]), "+f"(d[87]), "+f"(d[88]), "+f"(d[89]), "+f"(d[90]), "+f"(d[91]), "+f"(d[92]), "+f"(d[93]), "+f"(d[94]), "+f"(d[95])
      : "l"(da), "l"(db), "r"(keep));
}

template <int R>
__device__ __forceinline__ void pin_regs(float (&a)[2][96]) {
#pragma unroll
  for (int m = 0; m < 2; m++)
#pragma unroll
    for (int i = 0; i < R; i++) asm volatile("" : "+f"(a[m][i])::"memory");
}

struct Ctx {
  uint32_t sb;
  int m, n, wg, w, lane;
};
__device__ __forceinline__ Ctx make_ctx(uint32_t sb, int id) {
  int lane;
  asm volatile("mov.u32 %0, %%laneid;" : "=r"(lane));
  asm volatile("" : "+r"(id), "+r"(sb));
  return Ctx{sb, (id >> 3) & 15, id & 7, id >> 9, (id >> 7) & 3, lane};
}
#define UNPACK_CTX(c) const uint32_t sb = c.sb; const int m = c.m, n = c.n, wg = c.wg, w = c.w, lane = c.lane

__device__ __forceinline__ uint32_t poll_line(const uint32_t* word, uint32_t target, uint32_t need) {
  uint32_t v;
  asm volatile(
      "{\n.reg .pred p;\n.reg .u32 it, m;\n.reg .s32 d;\nmov.u32 it, 0;\n"
      "POLL_LOOP:\n"
      "ld.relaxed.gpu.global.u32 %0, [%1];\n"
      "sub.s32 d, %0, %2;\n"
      "setp.ge.s32 p, d, 0;\n"
      "vote.sync.ballot.b32 m, p, 0xffffffff;\n"
      "and.b32 m, m, %3;\n"
      "setp.eq.u32 p, m, %3;\n"
      "@p bra.uni POLL_DONE;\n"
      "add.u32 it, it, 1;\n"
      "setp.lt.u32 p, it, 0x400000;\n"
      "@p bra.uni POLL_LOOP;\n"
      "trap;\n"
      "POLL_DONE:\n}"
      : "=&r"(v) : "l"(word), "r"(target), "r"(need) : "memory");
  return v;
}
__device__ __forceinline__ uint32_t ld_relaxed(const uint32_t* p) {
  uint32_t v;
  asm volatile("ld.relaxed.gpu.global.u32 %0, [%1];" : "=r"(v) : "l"(p) : "memory");
  return v;
}
__device__ __forceinline__ float chain(float x, uint32_t on, uint32_t zero) {
  return __uint_as_float(__float_as_uint(x) | (on & zero));
}
constexpr int MSG_SPINS = 1 << 20;

constexpr int STAGES_PER_LAYER = 152;
__device__ __forceinline__ int nib(uint64_t v, int i) { return (int)(v >> (4 * i)) & 15; }
__device__ __forceinline__ bool tile_wide(int t) { return (0x23 >> t) & 1; }
__device__ __forceinline__ void weight_coords(const Params& p, int t, int n, const CUtensorMap*& map, int& c0, int& c2) {
  map = &p.t.wqkv + nib(0x4233100ull, t);
  c0 = t < 2 ? 128 * n + 64 * t : 0;
  c2 = t < 2 ? 0 : (t == 2 || t == 6) ? 2 * n : 7 * n + 2 * t - 6;
}

template <bool IS_A>
__device__ __forceinline__ void producer(const Params& p, uint32_t sb, int m, int n, int lane) {
  const uint32_t low = (1u << (4 * n)) - 1, others = (0x6543210u & low) | (0x7654321u & ~low);
  const uint64_t order_x = (uint64_t)(others * 2 + 0x1111111u) << 36 | (uint64_t)others * 2 << 8 | (n * 0x22 + 0x10);
  int inflight = 4, cur = 0;
  uint32_t fb = sb + BAR_FULL + 32, rb = sb + BAR_EMPTY, rph = 0, pos = 0, tag32 = 0, seen = 0;
  const uint32_t fend = sb + BAR_FULL + 8 * NBAR, rend = sb + BAR_EMPTY + 8 * NBAR;
  const uint32_t* word = p.g->flags + m * 32 + (lane < 16 ? lane >> 1 : lane & 7);
#pragma unroll 1
  for (int sg = 1; sg < 22; sg++) {
    const int layer = sg >= 11, s = sg == 1 ? 2 : sg == 2 ? 1 : sg - 11 * layer;
    const int t = nib(0x65434321010ull, s), kind = nib(0x32110031100ull, s);
    const bool wide = tile_wide(t);
    const uint32_t bbytes = wide ? 3 * UNIT : 2 * UNIT, base = sb + (IS_A ? bbytes : (m & 1) * (bbytes / 2));
    if (IS_A && kind == 0) {
      if (sg == 2) seen = tag32 = (__ldcg(p.g->epoch + m * 8 + n) + 1) << 5;
#pragma unroll 1
      for (int k = 0; k < 2; k++) {
#pragma unroll 1
        for (; inflight > (wide ? 3 : 4); inflight--) {
          mbar_wait(rb, rph);
          rb += 8;
          if (rb == rend) { rb -= 8 * NBAR; rph ^= 1; }
        }
        if (elect_one()) mbar_arrive(fb);
        inflight++;
        fb += 8;
        if (fb == fend) fb -= 8 * NBAR;
        pos += bbytes + 2 * UNIT;
        if (pos >= RING_UNITS * UNIT) pos -= RING_UNITS * UNIT;
      }
      continue;
    }
    const int mul = t == 6 ? 448 : t == 2 ? 128 : 64, count = sg == 1 ? 12 : 2 * nib(0x4871ull, kind);
    uint64_t order0 = sg == 1 ? 0xFEDCBA987654ull : kind == 3 ? 0x76543210u : order_x >> (8 * (kind & 1));
    uint32_t special = (s == 4 || s == 10) ? 0x10 : s == 9 ? 0xF : s == 0;
    if (IS_A) special |= (kind & 1 ? 0 : 3) | (count >= 4 ? 1u << (count - 4) : 0);
    if (s >= 9) pos = (s + 6) * UNIT;
    const CUtensorMap* map;
    int c0 = 0, c2 = 0, ev = 0;
    if (IS_A) {
      map = &p.t.xin + (t == 2 ? 2 : t == 6 ? 3 : sg >= 4);
      ev = 9 * layer + (t < 2 ? 0 : t == 2 ? 1 : t < 6 ? 4 : 5);
      if (elect_one()) asm volatile("prefetch.tensormap [%0];" ::"l"(map) : "memory");
    } else {
      weight_coords(p, t, n, map, c0, c2);
    }
#pragma unroll 1
    for (int add = 0; add < mul; add += 64) {
      uint64_t order = order0;
      const int need = kind == 3 ? ev : ev - 1 + (lane & 1), sh = kind == 3 ? 16 : 0;
      uint32_t ready = IS_A ? __ballot_sync(0xffffffffu, cur >= need) >> sh : 0;
#pragma unroll 1
      for (int k = 0; k < count; k++) {
        const int code = order & 15, kc = code * mul + add;
        order >>= 4;
        if ((special >> k) & 1) {
          const int lag = wide ? (s == 9 && k == 2 ? 2 : 3) : ((s == 4 || s == 10) && add == 0 && k < 4) ? 3 : 4;
#pragma unroll 1
          for (; inflight > lag; inflight--) {
            mbar_wait(rb, rph);
            rb += 8;
            if (rb == rend) { rb -= 8 * NBAR; rph ^= 1; }
          }
          inflight++;
          if (IS_A) {
            if (kind == 3 ? t == 2 && add + k == 64 : !(kind & 1) && k < 2) {
              if (t == 2) mbar_wait(sb + BAR_PUB + 8, layer);
              if (elect_one()) mbar_arrive(fb);
              goto next_stage;
            }
            if (k == count - 4 && sg >= 3) seen = ld_relaxed(word);
          }
        } else {
          mbar_wait(rb, rph);
          rb += 8;
          if (rb == rend) { rb -= 8 * NBAR; rph ^= 1; }
        }
        if (IS_A && !((ready >> code) & 1)) {
          cur = max(cur, (int)(seen - tag32));
          ready = __ballot_sync(0xffffffffu, cur >= need) >> sh;
          if (!((ready >> code) & 1)) {
            cur = (int)(poll_line(word, tag32 + need, 1u << (code + sh)) - tag32);
            ready = __ballot_sync(0xffffffffu, cur >= need) >> sh;
          }
          asm volatile("fence.acquire.gpu;" ::: "memory");
          fence_async_global();
          seen = ld_relaxed(word);
        }
        if (elect_one()) {
          if (!IS_A) tma_ld3_pair(base + pos, map, fb, c0, kc + 32 * (m & 1), c2);
          else tma_ld_act(base + pos, map, fb, kc, m);
          mbar_expect_tx(fb, IS_A ? 16384 : bbytes);
        }
      next_stage:
        fb += 8;
        if (fb == fend) fb -= 8 * NBAR;
        pos += bbytes + 2 * UNIT;
        if (pos >= RING_UNITS * UNIT) pos -= RING_UNITS * UNIT;
      }
      special = !IS_A ? 0 : t == 2 ? 1 : add == 128 ? 0x10 : 0;
      if (t == 2) order0 = others << 4 | n;
      if (IS_A && (t == 2 || add == 64 || add == 192)) ev++;
    }
  }
}

__device__ __forceinline__ void publisher(const Params& p, uint32_t sb, int m, int n) {
  {
    const int ts = PACE_M * m, tx = PACE_N * n;
#pragma unroll 1
    for (int k = 0; k < 2; k++) {
      __nanosleep(k == 0 ? min(ts, tx) : abs(ts - tx));
      if ((ts <= tx) == (k == 0)) {
        mbar_expect_tx(sb + BAR_CSLD, 24576);
        tma_ld3(sb + OFF_STG, &p.t.wqkv, sb + BAR_CSLD, 128 * n, 64 * m, 0);
        tma_ld3(sb + OFF_STG + 12288, &p.t.wqkv, sb + BAR_CSLD, 128 * n, 64 * m + 32, 0);
      } else {
#pragma unroll 1
        for (int h = 0; h < 2; h++) {
          const uint32_t xr = sb + BAR_XRDY + 8 * h;
          mbar_expect_tx(xr, 16384);
          tma_ld_act(sb + OFF_X + h * 16384, &p.t.xin, xr, 128 * n + 64 * h, m);
          asm volatile("mbarrier.arrive.shared::cta.b64 _, [%0], 3;" ::"r"(xr) : "memory");
        }
      }
    }
  }
  const uint32_t tag = __ldcg(p.g->epoch + m * 8 + n) + 1;
  uint32_t* word = p.g->flags + m * 32 + n;
  st_relaxed(word, 32 * tag);
#pragma unroll 1
  for (int c = 0; c < 16; c++) {
    const int e = c >= 9 ? c - 9 : c;
    if (e == 2 || e == 7) {
      asm volatile("prefetch.tensormap [%0];" ::"l"(&p.t.out) : "memory");
      mbar_wait(sb + BAR_XRDY, e == 2);
      tma_st_act(&p.t.out, sb + OFF_X, 128 * n, m);
      bulk_commit();
      mbar_wait(sb + BAR_XRDY + 8, e == 2);
      bulk_wait_all();
      mbar_arrive(sb + BAR_XGO);
    } else {
      mbar_wait(sb + BAR_PUB + 8 * e, c >= 9);
    }
    asm volatile("fence.release.gpu;" ::: "memory");
    asm volatile("red.relaxed.gpu.global.add.u32 [%0], 1;" ::"l"(word) : "memory");
  }
  p.g->epoch[m * 8 + n] = tag;
}

__device__ __forceinline__ void sum_rows(uint32_t buf, int iters, float (&a)[8], int lane) {
  uint32_t addr = buf + (lane >> 3) * 128 + (((lane & 7) ^ (lane >> 3)) << 4);
#pragma unroll 1
  for (int it = 0; it < iters; it++) {
    uint32_t u[2][4];
    lds_u4(addr, u[0][0], u[0][1], u[0][2], u[0][3]);
    lds_u4((addr ^ 64) + 512, u[1][0], u[1][1], u[1][2], u[1][3]);
    addr += 1024;
#pragma unroll
    for (int e = 0; e < 8; e++) { a[2 * (e & 3)] += bf_lo(u[e >> 2][e & 3]); a[2 * (e & 3) + 1] += bf_hi(u[e >> 2][e & 3]); }
  }
}
__device__ __forceinline__ void publish_sums(const float (&a)[8], uint4* dst, int lane, uint32_t tag) {
  const bool u8 = lane & 8, u16 = lane & 16;
  float h4[4], h2[2];
#pragma unroll
  for (int e = 0; e < 4; e++) h4[e] = (u8 ? a[4 + e] : a[e]) + __shfl_xor_sync(0xffffffffu, u8 ? a[e] : a[4 + e], 8);
#pragma unroll
  for (int e = 0; e < 2; e++) h2[e] = (u16 ? h4[2 + e] : h4[e]) + __shfl_xor_sync(0xffffffffu, u16 ? h4[e] : h4[2 + e], 16);
  st_msg(dst + (lane & 7) * 4 + (u8 ? 2 : 0) + (u16 ? 1 : 0), __float_as_uint(h2[0]), __float_as_uint(h2[1]), 0u, tag);
}

__device__ __forceinline__ void colsum_helper(const Params& p, uint32_t sb, int m, int n, int lane) {
  const uint32_t tag = __ldcg(p.g->epoch + m * 8 + n) + 1;
#pragma unroll 1
  for (int k = lane; k < 288; k += 32) {
    const uint32_t bb = __ldg(reinterpret_cast<const uint32_t*>(k < 224 ? p.b1 + 448 * n : p.b2 + 128 * n - 448) + k);
    const float sc = k < 224 ? 0.5f : 1.f;
    sts_f2(sb + (k < 224 ? OFF_CSF + k * 16 + 8 : OFF_CSQ + 1536 + (k - 224) * 8), sc * bf_lo(bb), sc * bf_hi(bb));
  }
  __syncwarp();
  if (elect_one()) mbar_arrive(sb + BAR_BIAS);
  bar_sync(BAR_HLP, 160);
  {
    uint4* base = p.g->csp + n * 17 * 224 + 12 * m + min(lane & 15, 11);
    float s0 = 0.f, s1 = 0.f;
#pragma unroll 1
    for (int g = 0; g < 2; g++) {
      uint32_t x[4], y[4];
#pragma unroll 1
      for (int it = 0; it < MSG_SPINS; it++) {
        uint32_t bad = 0, z, tg;
        if (g == 0 || it > 0) __nanosleep(CS_NS);
#pragma unroll
        for (int k = 0; k < 4; k++) { ld_msg(base + (g * 8 + (lane >> 4) * 4 + k) * 224, x[k], y[k], z, tg); bad |= tg ^ tag; }
        if (__all_sync(0xffffffffu, bad == 0)) break;
      }
#pragma unroll
      for (int k = 0; k < 4; k++) { s0 += __uint_as_float(x[k]); s1 += __uint_as_float(y[k]); }
    }
    s0 += __shfl_xor_sync(0xffffffffu, s0, 16);
    s1 += __shfl_xor_sync(0xffffffffu, s1, 16);
    if (lane < 12) st_msg(base + 16 * 224, __float_as_uint(s0), __float_as_uint(s1), 0u, tag);
  }
#pragma unroll 1
  for (int c = 0; c < 7; c++) {
    float a[8] = {0.f, 0.f, 0.f, 0.f, 0.f, 0.f, 0.f, 0.f};
#pragma unroll 1
    for (int h = 0; h < 2; h++) {
      if (elect_one()) {
        mbar_expect_tx(sb + BAR_CSLD + 8, 4096);
        tma_ld2(sb + OFF_HLP, &p.t.w1c, sb + BAR_CSLD + 8, 448 * n + 64 * c, 64 * m + 32 * h);
        if (c < 6) asm volatile("cp.async.bulk.prefetch.tensor.2d.L2.global [%0, {%1, %2}];" ::"l"(&p.t.w1c), "r"(448 * n + 64 * c + 64), "r"(64 * m + 32 * h) : "memory");
      }
      mbar_wait(sb + BAR_CSLD + 8, h);
      sum_rows(sb + OFF_HLP, 4, a, lane);
      __syncwarp();
    }
    publish_sums(a, p.g->csp + ((8 + n) * 17 + m) * 224 + c * 32, lane, tag);
  }
  if (elect_one()) {
#pragma unroll 1
    for (int k = 0; k < 3; k++) {
      mbar_wait(sb + BAR_XGO, k & 1);
      __nanosleep(XB_NS);
#pragma unroll 1
      for (int w = 0; w < 4; w++) {
        tma_st_warp(&p.t.out_w, sb + OFF_X + 16384 + w * 4096, 128 * n + 64, m, w);
        bulk_commit();
        bulk_wait_read();
        if (w < 3) __nanosleep(XB_GAP_NS);
      }
      bulk_wait_all();
      asm volatile("mbarrier.arrive.shared::cta.b64 _, [%0], 4;" ::"r"(sb + BAR_PUB + (k & 1 ? 64 : 24)) : "memory");
    }
  }
}

__device__ __forceinline__ void poll_msgs2(const uint4* pa, const uint4* pb, float (&v)[4], uint32_t tag) {
#pragma unroll 1
  for (int it = 0; it < MSG_SPINS; it++) {
    uint32_t x[4], z, ta, tb;
    ld_msg(pa, x[0], x[1], z, ta);
    ld_msg(pb, x[2], x[3], z, tb);
#pragma unroll
    for (int e = 0; e < 4; e++) v[e] = __uint_as_float(x[e]);
    if (__all_sync(0xffffffffu, ta == tag && tb == tag)) break;
  }
}
__device__ __forceinline__ void colsum_total(const Params& p, const Ctx& cx, int mat, uint32_t tag) {
  uint4* base = p.g->csp + (mat * 8 + cx.n) * 17 * 224;
  const int per = 12 + 2 * mat, k = 2 * cx.w + (cx.lane >> 4), ia = per * cx.m + k, ib = per * cx.m + min(k + 8, per - 1);
  float v[4];
  poll_msgs2(base + (cx.lane & 15) * 224 + ia, base + (cx.lane & 15) * 224 + ib, v, tag);
#pragma unroll 1
  for (int d = 1; d < 16; d *= 2)
#pragma unroll
    for (int e = 0; e < 4; e++) v[e] += __shfl_xor_sync(0xffffffffu, v[e], d);
  const bool hi = cx.lane & 1;
  if ((cx.lane & 14) == 0) st_msg(base + 16 * 224 + (hi ? ib : ia), __float_as_uint(hi ? v[2] : v[0]), __float_as_uint(hi ? v[3] : v[1]), 0u, tag);
}
__device__ __forceinline__ void colsum_gather(const Params& p, const Ctx& cx, int mat, uint32_t tag) {
  const uint4* base = p.g->csp + ((mat * 8 + cx.n) * 17 + 16) * 224;
  const int ia = cx.w * 32 + cx.lane, ib = min(ia + 128, 191 + 32 * mat);
  float v[4];
  poll_msgs2(base + ia, base + ib, v, tag);
  const uint32_t tab = cx.sb + (mat ? OFF_CSF : OFF_CSQ);
  sts_f2(tab + (ia << (3 + mat)), v[0], v[1]);
  sts_f2(tab + (ib << (3 + mat)), v[2], v[3]);
}

#define ACC(q, j, e) acc[(q) & 1][4 * (j) + 2 * ((q) >> 1) + (e)]

constexpr uint32_t RING16 = RING_UNITS * (UNIT >> 4);
__device__ __forceinline__ bool tile_split(int i) { return (0xD98 >> i) & 1; }

__device__ __forceinline__ void write_run_desc(uint32_t sb, int i, int step) {
  const int layer = i >= 7, t = i - 7 * layer, part = tile_split(i) ? step : 2;
  const bool wide = tile_wide(t), own = t != 2 && t != 6 && part != 1 && i != 0, second = t == 1 || t == 4;
  const uint32_t z16 = (wide ? 5 : 4) * (UNIT >> 4), a_off = z16 - 1024 + (uint32_t)DESC_A - (uint32_t)DESC_B;
  const int gl = 16 * t + (part == 2 ? 0 : second ? 16 * part - 14 : 4 * part), g0 = layer * STAGES_PER_LAYER + gl;
  const uint32_t s16 = (sb & 0x3FFFF) >> 4, bfirst = (uint32_t)DESC_B + s16;
  const int nkb = t == 6 ? 56 : part == 0 ? 2 : 12 + 2 * part;
  const bool win1 = t == 1 && part != 0;
  const int win = layer ? WIN1 : WIN0;
  const int run = win1 ? win + 1 : t == 2 ? WIN2 + 1 : nkb;
  const int rest = win1 ? 64 | (nkb - 1 - SKEW - win) : t == 2 ? 64 | (7 - WIN2) | (8 << 7) : 0;
  const uint32_t blo = bfirst + z16 * (wide ? (gl + (t == 5 ? 3 : 0)) & 3 : (gl + 3) % 5);
  const uint32_t alo = own ? (uint32_t)DESC_A + s16 + (OFF_X >> 4) : blo + a_off;
  const uint32_t aoff = own ? alo + 1024 - (blo == bfirst + RING16 - z16 ? bfirst : blo + z16) : a_off;
  const bool xwait = part == 0 && !second, keep = !(part == 0 || t == 5);
  sts_u4(sb + OFF_RUN + (2 * i + step) * 16, blo, alo, aoff,
         ((g0 / NBAR) & 1) | xwait << 1 | keep << 2 | 8 * (g0 % NBAR) | run << 6 | rest << 12);
}

__device__ __forceinline__ float2 row_sums(const Ctx& c, int j0, int j1) {
  const uint32_t xrow = c.sb + OFF_X + c.w * 4096 + c.lane * 128;
  float s = 0.f, q = 0.f, s1 = 0.f, q1 = 0.f;
#pragma unroll 4
  for (int j = j0; j < j1; j++) {
    uint32_t u[4];
    lds_u4(xrow + (j >> 3) * 16384 + (((j & 7) ^ (c.lane & 7)) << 4), u[0], u[1], u[2], u[3]);
#pragma unroll
    for (int e = 0; e < 4; e++) {
      const float a = bf_lo(u[e]), d = bf_hi(u[e]);
      s += a; q = fmaf(a, a, q);
      s1 += d; q1 = fmaf(d, d, q1);
    }
  }
  return make_float2(s + s1, q + q1);
}
__device__ __forceinline__ void write_partial_stats(const Params& p, const Ctx& c, int ln, float2 v, uint32_t tag) {
  st_msg(p.g->stats + (ln * 8 + c.n) * SEQ + 128 * c.m + 32 * c.w + c.lane, __float_as_uint(v.x),
         __float_as_uint(fmaxf(v.y - v.x * v.x * (1.f / 128.f), 0.f)), 0u, tag);
}

template <int QMASK, int J0 = 0, int J1 = 24>
__device__ __forceinline__ void rank1_update(const Params& p, float (&acc)[2][96], const Ctx& cx, int t) {
  float nm[4];
#pragma unroll
  for (int q = 0; q < 4; q++)
    if ((QMASK >> q) & 1) nm[q] = t == 6 ? 1.f : -lds_f(cx.sb + OFF_ROW + (32 * cx.w + 8 * q + (cx.lane >> 2)) * 8 + 4);
  const uint32_t ctab = cx.sb + OFF_CSQ + ((t & 3) * 192 + 2 * (cx.lane & 3)) * 4;
#pragma unroll
  for (int j = J0; j < J1; j++) {
    const float2 cs = lds_f2(ctab + j * 32);
#pragma unroll
    for (int q = 0; q < 4; q++) {
      if (!((QMASK >> q) & 1)) continue;
      const int k = 4 * j + q - 1;
      const float nq = QMASK == 15 && k >= 0 ? chain(nm[q], __float_as_uint(ACC(k & 3, k >> 2, 1)), p.zero) : nm[q];
      ACC(q, j, 0) = fmaf(nq, cs.x, ACC(q, j, 0));
      ACC(q, j, 1) = fmaf(nq, cs.y, ACC(q, j, 1));
    }
  }
}

template <int QMASK, int SEC>
__device__ __forceinline__ void pack_qkv(const float (&acc)[2][96], uint32_t (&F)[3][4][8]) {
#pragma unroll
  for (int q = 3; q >= 0; q--)
#pragma unroll
    for (int j = 0; j < 8; j++) {
      if (!((QMASK >> q) & 1)) continue;
      const uint32_t u = pack_bf16(ACC(q, 8 * SEC + j, 0), ACC(q, 8 * SEC + j, 1));
      F[SEC][q][j] = SEC == 2 ? movtrans(u) : u;
    }
}
template <int K0, int K1>
__device__ __forceinline__ void send_halo(const Params& p, const uint32_t (&F)[3][4][8], const Ctx& cx, int layer, int t) {
  uint32_t E[18];
#pragma unroll
  for (int j = 0; j < 8; j++) { E[j] = F[1][3][j]; E[8 + j] = F[2][3][j]; }
  if (cx.w < 2) {
#pragma unroll
    for (int k = K0; k < K1; k++)
      if (k < 4) sts_u4(cx.sb + OFF_STG + cx.w * 2048 + cx.lane * 16 + k * 512, E[4 * k], E[4 * k + 1], E[4 * k + 2], E[4 * k + 3]);
  } else {
    uint4* dst = p.g->halo + (((layer * 2 + t) * 16 + cx.m) * 8 + cx.n) * 384 + (cx.w & 1) * 192 + cx.lane;
    const uint32_t tag = lds_u(cx.sb + OFF_TAG);
    if (K1 == 6) {
      const float4 r = lds_f4(cx.sb + OFF_ROW + (32 * cx.w + 24 + 2 * (cx.lane & 3)) * 8);
      E[16] = __float_as_uint(r.x);
      E[17] = __float_as_uint(r.z);
    }
#pragma unroll
    for (int k = K0; k < K1; k++) st_msg(dst + k * 32, E[3 * k], E[3 * k + 1], E[3 * k + 2], tag);
  }
}

__device__ __forceinline__ void attn_scores(const uint32_t* qa, const uint32_t* qb, const uint32_t* kp, const uint32_t* ka,
                                            const uint32_t* kb, float (&l)[4], const float4& zero, const bool (&early)[2]) {
  float s[3][4];
#pragma unroll
  for (int x = 0; x < 3; x++) {
    const uint32_t* kk = x == 0 ? kp : x == 1 ? ka : kb;
    asm volatile("mma.sync.aligned.m16n8k16.row.col.f32.bf16.bf16.f32 {%0,%1,%2,%3}, {%4,%5,%6,%7}, {%8,%9}, {%10,%11,%12,%13};"
                 : "=f"(s[x][0]), "=f"(s[x][1]), "=f"(s[x][2]), "=f"(s[x][3])
                 : "r"(qa[0]), "r"(qb[0]), "r"(qa[1]), "r"(qb[1]), "r"(kk[0]), "r"(kk[1]), "f"(zero.x), "f"(zero.y),
                   "f"(zero.z), "f"(zero.w));
  }
#pragma unroll
  for (int x = 0; x < 3; x++) {
    const uint32_t* kk = x == 0 ? kp : x == 1 ? ka : kb;
    mma16816(s[x], qa[2], qb[2], qa[3], qb[3], kk[2], kk[3]);
  }
#pragma unroll
  for (int e = 0; e < 2; e++) {
    l[e] = early[e] ? s[0][e] : s[1][e];
    l[2 + e] = early[e] ? s[1][2 + e] : s[2][2 + e];
  }
}

__device__ __forceinline__ void attn_mix(const float (&l)[4], const float (&sc)[4], const float (&off)[4], const float (&rk)[4],
                                         const uint32_t* vp, const uint32_t* va, const uint32_t* vb, float (&o)[4][4],
                                         float (&sum)[2], uint32_t mask, uint32_t zero) {
  float x[4];
#pragma unroll
  for (int e = 0; e < 4; e++) x[e] = fmaf(l[e], sc[e], off[e]);
  const float ml = quad_max(fmaxf(x[0], x[1])), mh = quad_max(fmaxf(x[2], x[3]));
  x[0] = ex2(x[0] - ml); x[1] = ex2(x[1] - ml);
  x[2] = ex2(x[2] - mh); x[3] = ex2(x[3] - mh);
  sum[0] = x[0] + x[1];
  sum[1] = x[2] + x[3];
  const uint32_t pl = pack_bf16(x[0] * rk[0], x[1] * rk[1]), ph = pack_bf16(x[2] * rk[2], x[3] * rk[3]);
  const uint32_t a0 = pl & ~mask, a1 = ph & mask, a2 = pl & zero, a3 = ph & ~mask, c0 = pl & mask, c1 = ph & zero;
#pragma unroll
  for (int jn = 0; jn < 4; jn++) {
    o[jn][0] = o[jn][1] = o[jn][2] = o[jn][3] = 0.f;
    mma16816(o[jn], a0, a1, a2, a3, va[jn], vb[jn]);
  }
#pragma unroll
  for (int jn = 0; jn < 4; jn++) mma1688(o[jn], c0, c1, vp[jn]);
}

template <int t>
__device__ __forceinline__ void attn_epilogue(const Params& p, float (&acc)[2][96], uint32_t (&F)[3][4][8], const Ctx& cx, int layer, uint32_t tag) {
  UNPACK_CTX(cx);
  const uint32_t ktab = sb + OFF_ROW + (32 * w + 2 * (lane & 3)) * 8, exc = sb + OFF_STG + (w & 1) * 2048 + lane * 16;
  uint4* const halo = p.g->halo + (((layer * 2 + t) * 16 + m) * 8 + n) * 384 + (w & 1) * 192;
  (void)wg;
  uint32_t(&Q)[4][8] = F[0], (&K)[4][8] = F[1], (&V)[4][8] = F[2], P[18];
  float kr[5][2], qr[4];
  bar_arrive(BAR_PAIR + w, 64);
  if (layer == 0 && t == 1) {
    rank1_update<7, 8, 24>(p, acc, cx, 1);
    rank1_update<31, 0, 8>(p, acc, cx, 1);
  }
#pragma unroll
  for (int q = 0; q < 4; q++) {
    qr[q] = lds_f(sb + OFF_ROW + (32 * w + 8 * q + (lane >> 2)) * 8) * (0.17677669529663687f * 1.4426950408889634f);
    const float4 r = lds_f4(ktab + 64 * q);
    kr[1 + q][0] = r.x;
    kr[1 + q][1] = r.z;
  }
  pack_qkv<7, 1>(acc, F);
  uint32_t tg[6];
#pragma unroll
  for (int k = 0; k < 6; k++) {
    tg[k] = ~tag;
    if (t == 1)
      asm volatile("{\n.reg .b128 v;\n.reg .pred g;\nsetp.ne.u32 g, %5, 0;\nmov.b128 v, {%6, %6, %6, %6};\n"
                   "@g ld.relaxed.gpu.global.b128 v, [%4];\nmov.b128 {%0, %1, %2, %3}, v;\n}"
                   : "=r"(P[3 * k]), "=r"(P[3 * k + 1]), "=r"(P[3 * k + 2]), "=r"(tg[k])
                   : "l"(halo - 8 * 384 + k * 32 + lane), "r"((uint32_t)(w < 2 && m > 0) | ((K[0][7] | K[1][7] | K[2][7]) & p.zero)), "r"(~tag) : "memory");
  }
  pack_qkv<7, 2>(acc, F);
  pack_qkv<15, 0>(acc, F);
  bar_sync(BAR_PAIR + (w ^ 2), 64);
  if (w >= 2 || m == 0) {
#pragma unroll
    for (int k = 0; k < 4; k++) lds_u4(exc + k * 512, P[4 * k], P[4 * k + 1], P[4 * k + 2], P[4 * k + 3]);
    const float4 r = lds_f4(ktab - (w >> 1) * 320);
    P[16] = __float_as_uint(r.x);
    P[17] = __float_as_uint(r.z);
  } else {
    if ((m & 1) && t == 0) __nanosleep(HALO_NS);
#pragma unroll 1
    for (int it = 0; it < MSG_SPINS; it++) {
      if (t == 0 || it > 0) {
        if (it > 0 || !(m & 1)) poll_line(reinterpret_cast<const uint32_t*>(halo - 8 * 384 + 191) + 3, tag, 1u);
#pragma unroll
        for (int k = 0; k < 6; k++) ld_msg(halo - 8 * 384 + k * 32 + lane, P[3 * k], P[3 * k + 1], P[3 * k + 2], tg[k]);
      }
      uint32_t bad = 0;
#pragma unroll
      for (int k = 0; k < 6; k++) bad |= tg[k] ^ tag;
      if (__all_sync(0xffffffffu, bad == 0)) break;
    }
  }
  kr[0][0] = __uint_as_float(P[16]);
  kr[0][1] = __uint_as_float(P[17]);
  const bool early[2] = {2 * (lane & 3) > (lane >> 2), 2 * (lane & 3) + 1 > (lane >> 2)};
  const uint32_t mask = (early[0] ? 0xffffu : 0u) | (early[1] ? 0xffff0000u : 0u);
  float rk[2][4], sc[2][4], off[2][4];
#pragma unroll
  for (int g = 0; g < 2; g++) {
#pragma unroll
    for (int e = 0; e < 4; e++) {
      const int q = 2 * g + (e >> 1);
      const bool masked = q == 0 && m == 0 && w < 2 && early[e & 1];
      rk[g][e] = early[e & 1] ? kr[q][e & 1] : kr[q + 1][e & 1];
      sc[g][e] = masked ? 0.f : rk[g][e] * qr[q];
      off[g][e] = masked ? -1e30f : 0.f;
    }
  }
  if (w == 0 && elect_one()) asm volatile("prefetch.tensormap [%0];" ::"l"(&p.t.att_st) : "memory");
  bar_sync(BAR_GO, 256);
  const float4 zero = lds_f4(sb + OFF_ZERO);
  float l[2][2][4], o[2][2][4][4], sum[2][2][2];
#pragma unroll
  for (int h = 0; h < 2; h++) {
    if (h == 1) {
      Q[2][4] |= __float_as_uint(l[1][0][0]) & p.zero;
      Q[0][4] |= __float_as_uint(l[0][0][0]) & p.zero;
    }
    attn_scores(&Q[2][4 * h], &Q[3][4 * h], &K[1][4 * h], &K[2][4 * h], &K[3][4 * h], l[1][h], zero, early);
    attn_scores(&Q[0][4 * h], &Q[1][4 * h], &P[4 * h], &K[0][4 * h], &K[1][4 * h], l[0][h], zero, early);
  }
  const uint32_t stg = sb + OFF_STG + w * 4096, srow = stg + lane * 128 + ((lane & 7) << 4);
#pragma unroll
  for (int h = 0; h < 2; h++) {
    attn_mix(l[1][h], sc[1], off[1], rk[1], &V[1][4 * h], &V[2][4 * h], &V[3][4 * h], o[1][h], sum[1][h], mask, p.zero);
    attn_mix(l[0][h], sc[0], off[0], rk[0], &P[8 + 4 * h], &V[0][4 * h], &V[1][4 * h], o[0][h], sum[0][h], mask, p.zero);
  }
  if (t == 0 && p.zero == 0) {
    uint32_t dep = 0;
#pragma unroll
    for (int k = 0; k < 16; k++) dep |= __float_as_uint(o[k >> 3][(k >> 2) & 1][k & 3][0]);
    bar_arrive(BAR_DONE | (dep & __float_as_uint(zero.x)), 256);
  }
#pragma unroll
  for (int h = 0; h < 2; h++) {
    float inv[4];
#pragma unroll
    for (int q = 0; q < 4; q++) inv[q] = rcp_hw(quad_sum(sum[q >> 1][h][q & 1]));
#pragma unroll
    for (int j = 0; j < 4; j++) {
      const float(&a)[4] = o[0][h][j];
      const float(&c)[4] = o[1][h][j];
      stsm4(srow ^ ((4 * h + j) << 4), pack_bf16(a[0] * inv[0], a[1] * inv[0]), pack_bf16(a[2] * inv[1], a[3] * inv[1]),
            pack_bf16(c[0] * inv[2], c[1] * inv[2]), pack_bf16(c[2] * inv[3], c[3] * inv[3]));
    }
  }
  if (t == 1) bar_arrive(BAR_DONE, 256);
  fence_async_smem();
  __syncwarp();
  if (lane == 0) {
    tma_st2(&p.t.att_st, stg, 128 * n + 64 * t, 128 * m + 32 * w);
    bulk_commit();
  }
}

__device__ __forceinline__ void finish_stores(uint32_t sb, int i) {
  const int t = i >= 7 ? i - 7 : i;
  if ((threadIdx.x & 31) == 0) {
    bulk_wait_all();
    mbar_arrive(sb + BAR_PUB + 8 * (t < 2 ? t : t + 1));
  }
  __syncwarp();
  if (i < 12) bar_arrive(BAR_GUARD + ((i & 1) ^ 1), 256);
}

template <int N>
__device__ __forceinline__ bool mainloop(const Params& p, float (&acc)[2][96], uint32_t sb, int i, int step, int mn) {
  constexpr uint32_t Z16 = (2 + N / 64) * (UNIT >> 4);
  constexpr uint32_t A_OFF = Z16 - 1024 + (uint32_t)DESC_A - (uint32_t)DESC_B;
  const int wg = i & 1;
  const uint32_t s16 = (sb & 0x3FFFF) >> 4;
  const uint32_t blast = (uint32_t)DESC_B + s16 + RING16 - Z16, flast = sb + BAR_FULL + 8 * (NBAR - 1);
  uint32_t blo = (uint32_t)DESC_B + s16, alo = blo + A_OFF, aoff = A_OFF, misc = 16 << 6;
  if (N == 128 || i > 0) lds_u4(sb + OFF_RUN + (2 * i + step) * 16, blo, alo, aoff, misc);
  uint32_t keep = misc & 4;
  int run = (misc >> 6) & 63, rest = misc >> 12;
  uint32_t fb = sb + BAR_FULL + (misc & 0x38), ph = misc & 1;
  uint32_t prev = sb + BAR_DUMMY - 8 * NBAR;
  const uint32_t lane_id = __popc(__ballot_sync(0xffffffffu, true) & lanemask_lt()), rel = pair_offset(sb, lane_id & 1) + 8 * NBAR;
  pin_regs<N / 2>(acc);
  if (N == 128 || i > 0) bar_sync(BAR_ORDER + wg, 256);
  else bar_sync(BAR_INIT0, 160);
  mbar_wait(fb, ph);
  if (N == 192 && i == 0) cluster_wait();
  if (misc & 2) {
    if (N == 128) {
      const Ctx cx = make_ctx(sb, mn);
      mbar_wait(sb + BAR_XRDY, 1);
      const float2 v = row_sums(cx, 0, 8);
      sts_f2(cx.sb + OFF_HALF + (32 * cx.w + cx.lane) * 8, v.x, v.y);
      bar_arrive(BAR_STAT, 256);
    }
    mbar_wait(sb + BAR_XGO, N == 192);
  }
#pragma unroll 1
  while (true) {
    const uint64_t da = (DESC_A & ~0xffffffffull) | alo, db = (DESC_B & ~0xffffffffull) | blo;
    asm volatile("wgmma.fence.sync.aligned;" ::: "memory");
    wgmma_ss<N>(acc[0], da, db, keep);
    wgmma_ss<N>(acc[1], da + 64, db, keep);
    keep = 4;
    wgmma_ss<N>(acc[0], da + 2, db + 128);
    wgmma_ss<N>(acc[1], da + 66, db + 128);
    asm volatile("wgmma.commit_group.sync.aligned;" ::: "memory");
    asm volatile("wgmma.wait_group.sync.aligned 1;" ::: "memory");
    if (lane_id < 2) mbar_arrive_cluster(prev + rel);
    prev = fb;
    if (fb == flast) { fb -= 8 * NBAR; ph++; }
    fb += 8;
    if (blo == blast) blo -= RING16;
    blo += Z16;
    alo = blo + aoff;
    aoff = A_OFF;
    run--;
    const bool ready = mbar_test(fb, ph) && run != 0;
    asm volatile("wgmma.fence.sync.aligned;" ::: "memory");
    wgmma_ss<N>(acc[0], da + 4, db + 4 * N);
    wgmma_ss<N>(acc[1], da + 68, db + 4 * N);
    wgmma_ss<N>(acc[0], da + 6, db + 4 * N + 128);
    wgmma_ss<N>(acc[1], da + 70, db + 4 * N + 128);
    asm volatile("wgmma.commit_group.sync.aligned;" ::: "memory");
    if (!ready) {
      bool window = false;
      if (run == 0) {
        if (rest == 0) break;
        window = rest & 64;
        if (window) bar_arrive(BAR_GO, 256);
        else alo = (uint32_t)DESC_A + s16 + (OFF_STG >> 4);
        run = rest & 63;
        rest >>= 7;
      }
      mbar_wait(fb, ph);
      if (window) bar_sync(BAR_DONE, 256);
    }
  }
  if constexpr (N == 192) {
    if (misc >> 12) {
      const Ctx cx = make_ctx(sb, mn);
      uint32_t F[3][4][8];
      const uint32_t fb0 = fb, blo0 = blo;
#pragma unroll 1
      for (int x = 0; x < SKEW; x++) {
        const uint64_t da = (DESC_A & ~0xffffffffull) | (blo + A_OFF + 64), db = (DESC_B & ~0xffffffffull) | blo;
        mbar_wait(fb, ph);
        asm volatile("wgmma.fence.sync.aligned;" ::: "memory");
#pragma unroll
        for (int k = 0; k < 4; k++) wgmma_ss<N>(acc[1], da + 2 * k, db + (k >> 1) * 4 * N + (k & 1) * 128);
        asm volatile("wgmma.commit_group.sync.aligned;" ::: "memory");
        asm volatile("wgmma.wait_group.sync.aligned 1;" ::: "memory");
        if (x == 0) {
          if (lane_id < 2) mbar_arrive_cluster(prev + rel);
          bar_sync(BAR_GUARD + wg, 256);
        }
        if (fb == flast) { fb -= 8 * NBAR; ph++; }
        fb += 8;
        blo += Z16;
      }
      fb = fb0;
#pragma unroll
      for (int u = 0; u < 2 * SKEW; u++) {
        const uint64_t da = (DESC_A & ~0xffffffffull) | (blo0 + (u >> 1) * Z16 + A_OFF + 4 * (u & 1));
        const uint64_t db = (DESC_B & ~0xffffffffull) | (blo0 + (u >> 1) * Z16 + 4 * N * (u & 1));
        asm volatile("wgmma.fence.sync.aligned;" ::: "memory");
        wgmma_ss<N>(acc[0], da, db);
        wgmma_ss<N>(acc[0], da + 2, db + 128);
        asm volatile("wgmma.commit_group.sync.aligned;" ::: "memory");
        if (u == 2 * SKEW - 1) break;
        asm volatile("wgmma.wait_group.sync.aligned 1;" ::: "memory");
        if (u == 0) {
#pragma unroll
          for (int r = 0; r < 96; r++) asm volatile("" : "+f"(acc[1][r])::"memory");
        }
        if (u == 2 || u == 4) {
          if (lane_id < 2) mbar_arrive_cluster(fb + rel);
          fb = fb == flast ? fb - 8 * (NBAR - 1) : fb + 8;
        }
        if (u == 0) { if (i == 1) rank1_update<8, 8, 24>(p, acc, cx, 1); pack_qkv<8, 2>(acc, F); pack_qkv<8, 1>(acc, F); }
        if (u == 1) send_halo<0, 3>(p, F, cx, i >= 7, 1);
        if (u == 2) send_halo<3, 6>(p, F, cx, i >= 7, 1);
      }
      bar_arrive(BAR_ORDER + (wg ^ 1), 256);
      asm volatile("wgmma.wait_group.sync.aligned 0;" ::: "memory");
#pragma unroll
      for (int r = 0; r < 96; r++) asm volatile("" : "+f"(acc[0][r])::"memory");
      if (lane_id < 2) mbar_arrive_cluster(fb + rel);
      attn_epilogue<1>(p, acc, F, cx, i >= 7, lds_u(sb + OFF_TAG));
      finish_stores(sb, i);
#pragma unroll
      for (int r = 0; r < 48; r++) {
        float* d = &acc[r & 1][4 * (r >> 1)];
        asm volatile("ld.shared.v4.f32 {%0, %1, %2, %3}, [%4];" : "=f"(d[0]), "=f"(d[1]), "=f"(d[2]), "=f"(d[3]) : "r"(sb + OFF_CSQ + 16 * r));
      }
      return true;
    }
  }
  if (i < 13) bar_arrive(BAR_ORDER + (wg ^ 1), 256);
  if (N == 128 && ((0x2244 >> i) & 1)) {
    const Ctx cx = make_ctx(sb, mn);
    const uint32_t xrow = cx.sb + OFF_X + cx.w * 4096 + cx.lane * 128 + ((cx.lane & 7) << 4);
    const bool leader = elect_one();
    asm volatile("wgmma.wait_group.sync.aligned 0;" ::: "memory");
    pin_regs<64>(acc);
#pragma unroll
    for (int h = 0; h < 2; h++) {
      if (h == 1 && p.zero != 0) break;
#pragma unroll
      for (int j = 8 * h; j < 8 * h + 8; j++)
        stsm4((xrow ^ ((j & 7) << 4)) + h * 16384, pack_bf16(ACC(0, j, 0), ACC(0, j, 1)), pack_bf16(ACC(1, j, 0), ACC(1, j, 1)),
              pack_bf16(ACC(2, j, 0), ACC(2, j, 1)), pack_bf16(ACC(3, j, 0), ACC(3, j, 1)));
      fence_async_smem();
      __syncwarp();
      if (leader) {
        mbar_arrive(sb + BAR_XRDY + 8 * h);
        if (i == 13) {
          tma_st_warp(&p.t.out_w, cx.sb + OFF_X + h * 16384 + cx.w * 4096, 128 * cx.n + 64 * h, cx.m, cx.w);
          bulk_commit();
          if (h == 1) bulk_wait_read();
        }
      }
      if (h == 0 && lane_id < 2 && i < 13) mbar_arrive_cluster(prev + rel);
    }
    if (i == 2 || i == 9) {
      const float2 v = row_sums(cx, 8, 16);
      bar_sync(BAR_STAT, 256);
      const float2 o = lds_f2(cx.sb + OFF_HALF + (32 * cx.w + cx.lane) * 8);
      write_partial_stats(p, cx, (i + 3) >> 2, make_float2(v.x + o.x, v.y + o.y), lds_u(sb + OFF_TAG));
    }
    return true;
  }
  asm volatile("wgmma.wait_group.sync.aligned 0;" ::: "memory");
  pin_regs<N / 2>(acc);
  if (lane_id < 2) mbar_arrive_cluster(prev + rel);
  return false;
}

__device__ __forceinline__ void finish_row_stats(const Params& p, const Ctx& c, int ln, uint32_t tag) {
  const uint4* src = p.g->stats + ln * 8 * SEQ + 128 * c.m + 32 * c.w + c.lane;
  uint32_t ps[8], pm[8];
#pragma unroll 1
  for (int it = 0; it < MSG_SPINS; it++) {
    uint32_t bad = 0, u, tg;
    if (ln == 2 || it > 0) __nanosleep(STAT_NS);
#pragma unroll
    for (int k = 0; k < 8; k++) { ld_msg(src + k * SEQ, ps[k], pm[k], u, tg); bad |= tg ^ tag; }
    if (__all_sync(0xffffffffu, bad == 0)) break;
  }
  float s = 0.f, m2 = 0.f;
#pragma unroll
  for (int k = 0; k < 8; k++) s += __uint_as_float(ps[k]);
  const float mean = s * (1.f / DM);
#pragma unroll
  for (int k = 0; k < 8; k++) {
    const float d = __uint_as_float(ps[k]) * (1.f / 128.f) - mean;
    m2 += fmaf(128.f * d, d, __uint_as_float(pm[k]));
  }
  sts_f2(c.sb + OFF_ROW + (32 * c.w + c.lane) * 8, rsqrtf(m2 * (1.f / DM) + 1e-5f), mean);
  __syncwarp();
}

__device__ __forceinline__ void gelu_epilogue(const Params& p, float (&acc)[2][96], const Ctx& cx, int t) {
  UNPACK_CTX(cx);
  (void)wg;
  float rs[4], rm[4];
#pragma unroll
  for (int q = 0; q < 4; q++) {
    const float2 v = lds_f2(sb + OFF_ROW + (32 * w + 8 * q + (lane >> 2)) * 8);
    rs[q] = 0.5f * v.x;
    rm[q] = -rs[q] * v.y;
  }
  const int col0 = 128 * (t - 3);
  const uint32_t stg = sb + OFF_STG + w * 4096;
  const uint32_t ctab = sb + OFF_CSF + (col0 / 2 + (lane & 3)) * 16, srow = stg + lane * 128 + ((lane & 7) << 4);
  if (t != 4) __nanosleep((t == 5 ? STAG_NS : STAG3_NS) * w);
  float4 nb = lds_f4(ctab);
  auto chunk = [&](auto first, int cc) {
    constexpr int c = decltype(first)::value ? 0 : 1;
    uint32_t hp[8][4];
#pragma unroll
    for (int j = 0; j < 8; j++) {
      const float4 cb = nb;
      nb = lds_f4(ctab + (8 * cc + j + 1) * 64);
#pragma unroll
      for (int q = 0; q < 4; q++) {
        float y[2];
        const int k = 4 * j + q - GELU_DEP;
        const float rmq = k >= 0 ? chain(rm[q], hp[k >> 2][k & 3], p.zero) : rm[q];
#pragma unroll
        for (int e = 0; e < 2; e++) {
          const float z = fmaf(ACC(q, 8 * c + j, e), rs[q], fmaf(rmq, e ? cb.y : cb.x, e ? cb.w : cb.z));
          const float u = z * fmaf(z * z, 8.f * 0.7978845608028654f * 0.044715f, 2.f * 0.7978845608028654f);
          y[e] = fmaf(z, tanh_hw(u), z);
        }
        hp[j][q] = pack_bf16(y[0], y[1]);
      }
      if (j == STG_WAIT && c > 0) {
        if (lane == 0) bulk_wait_read();
        __syncwarp();
      }
      if (c == 0 || j > STG_WAIT) {
        stsm4(srow ^ (j << 4), hp[j][0], hp[j][1], hp[j][2], hp[j][3]);
      } else if (j == STG_WAIT) {
#pragma unroll
        for (int jj = 0; jj <= STG_WAIT; jj++) stsm4(srow ^ (jj << 4), hp[jj][0], hp[jj][1], hp[jj][2], hp[jj][3]);
      }
    }
    fence_async_smem();
    __syncwarp();
    if (lane == 0) {
      tma_st2(&p.t.h_st, stg, 448 * n + col0 + 64 * cc, 128 * m + 32 * w);
      bulk_commit();
    }
    return hp[7][3];
  };
  chunk(std::true_type{}, 0);
#pragma unroll 1
  for (int cc = 1;; cc++) {
    const uint32_t zr = chunk(std::false_type{}, cc) & p.zero;
    if (cc == 2 || t != 5) break;
#pragma unroll
    for (int r = 0; r < 64; r++)
      asm volatile("{\n.reg .b32 x;\nmov.b32 x, %1;\nor.b32 x, x, %2;\nmov.b32 %0, x;\n}"
                   : "=f"(acc[r & 1][32 + (r >> 1)]) : "f"(acc[r & 1][64 + (r >> 1)]), "r"(zr));
  }
#pragma unroll
  for (int r = 0; r < 16; r++) acc[0][r] = acc[1][r] = 0.f;
}

__device__ __forceinline__ bool consumer_tile(const Params& p, float (&acc)[2][96], uint32_t sb0, int i, int mn) {
  const int layer = i >= 7, t = i - 7 * layer, wg = i & 1;
  const bool resid = t == 2 || t == 6;
  {
    if (resid) {
      const Ctx cx = make_ctx(sb0, mn);
      const uint32_t xrow = cx.sb + OFF_X + cx.w * 4096 + cx.lane * 128;
      const uint32_t sel_lo = 0x1044u | p.zero, sel_hi = 0x3244u | p.zero;
#pragma unroll
      for (int j = 0; j < 16; j++) {
        uint32_t r[4];
        ldsm4(xrow + (j >> 3) * 16384 + (((j & 7) ^ (cx.lane & 7)) << 4), r[0], r[1], r[2], r[3]);
#pragma unroll
        for (int q = 0; q < 4; q++) {
          ACC(q, j, 0) = prmt_f(r[q], sel_lo);
          ACC(q, j, 1) = prmt_f(r[q], sel_hi);
        }
      }
    }
    if (t >= 5 || i == 7) finish_stores(sb0, i - 2);
#pragma unroll 1
    for (int step = !tile_split(i);; step++) {
      if (step == 1 && (t == 1 || t == 4)) {
        const Ctx cx = make_ctx(sb0, mn);
        if (i == 1) {
          const uint32_t epoch = __ldcg(p.g->epoch + (mn & 127));
          cluster_wait();
          asm volatile("st.shared.u32 [%0], %1;" ::"r"(sb0 + OFF_TAG), "r"(epoch + 1) : "memory");
        }
        const uint32_t tag = lds_u(cx.sb + OFF_TAG);
        const int ln = (i + 1) >> 2;
#pragma unroll 1
        for (int r = 0; r < 2; r++) {
          if (i == 1) {
            if (cx.w < 3) {
              float a[8] = {0.f, 0.f, 0.f, 0.f, 0.f, 0.f, 0.f, 0.f};
              mbar_wait(sb0 + BAR_CSLD, r);
#pragma unroll 1
              for (int h = 0; h < 2; h++) sum_rows(cx.sb + OFF_STG + h * 12288 + cx.w * 4096, 4, a, cx.lane);
              publish_sums(a, p.g->csp + (cx.n * 17 + cx.m) * 224 + (3 * r + cx.w) * 32, cx.lane, tag);
            }
          }
          if (r == 1) break;
          if (i == 1) {
            bar_sync(BAR_WG + 1, 128);
            if (cx.w == 3 && elect_one()) {
              mbar_expect_tx(sb0 + BAR_CSLD, 24576);
              tma_ld3(sb0 + OFF_STG, &p.t.wqkv, sb0 + BAR_CSLD, 128 * cx.n + 64, 64 * cx.m, 0);
              tma_ld3(sb0 + OFF_STG + 12288, &p.t.wqkv, sb0 + BAR_CSLD, 128 * cx.n + 64, 64 * cx.m + 32, 0);
            }
            mbar_wait(sb0 + BAR_XRDY, 0);
            mbar_wait(sb0 + BAR_XRDY + 8, 0);
          }
          if (t == 1) write_partial_stats(p, cx, ln, row_sums(cx, 0, 16), tag);
        }
        if (i == 1) {
          bar_arrive(BAR_HLP, 160);
          bar_sync(BAR_INIT, 160);
        }
        if (i == 4) colsum_total(p, cx, 1, tag);
        if (i != 1) bar_sync(BAR_GUARD + wg, 256);
        finish_row_stats(p, cx, ln, tag);
        if (i == 4) {
          colsum_gather(p, cx, 1, tag);
          mbar_wait(sb0 + BAR_BIAS, 0);
        }
        bar_arrive(BAR_GUARD + (wg ^ 1), 256);
      }
      if (step == 2) bar_sync(BAR_GUARD + wg, 256);
      if (step == 2 && i == 0) {
        colsum_gather(p, make_ctx(sb0, mn), 0, lds_u(sb0 + OFF_TAG));
        bar_sync(BAR_WG, 128);
      }
      if ((t + step == 2 && i != 1) || t == 6) rank1_update<15>(p, acc, make_ctx(sb0, mn), t);
      if (step == 2) break;
      if (tile_wide(t)) {
        if (mainloop<192>(p, acc, sb0, i, step, mn)) return false;
      } else {
        if (mainloop<128>(p, acc, sb0, i, step, mn)) return false;
      }
    }
    if (t < 2) return true;
    gelu_epilogue(p, acc, make_ctx(sb0, mn), t);
    return false;
  }
}

template <bool BY_SMID>
__global__ void __cluster_dims__(2, 1, 1) __launch_bounds__(384, 1)
fused_layers_kernel(const Scalars scalars, const __grid_constant__ Maps maps) {
  if (threadIdx.x == 288 || threadIdx.x == 320)
    asm volatile("prefetch.tensormap [%0];" ::"l"(threadIdx.x == 288 ? &maps.xin : &maps.wqkv) : "memory");
  const Params p{scalars, maps};
  extern __shared__ __align__(1024) uint8_t smem_raw[];
  const uint32_t sb = uniform((uint32_t)__cvta_generic_to_shared(smem_raw));
  const int tid = threadIdx.x, lane = tid & 31, warp = uniform(tid >> 5), wg = warp >> 2, w = warp & 3;

  int mn;
  {
    int id = blockIdx.x;
    if (BY_SMID) asm volatile("mov.u32 %0, %%smid;" : "=r"(id));
    else if (id >= 120) id += 4;
    const int c = id >> 1;
    int g, j;
    if (c < 32) { g = c & 7; j = c >> 3; }
    else if (c < 60) { g = 1 + (c - 32) % 7; j = 4 + (c - 32) / 7; }
    else { g = 0; j = c - 58; }
    mn = (g * 2 + (blockIdx.x & 1)) * 8 + j;
    if (c == 60 || c == 61) {
      if (tid < 32) {
        const uint32_t tag = __ldcg(p.g->epoch + NCTA + (id & 3)) + 1;
#pragma unroll 1
        for (int mm = 0; mm < 16; mm++) poll_line(p.g->flags + mm * 32 + (lane & 7), 32 * tag, 0xffu);
        if (tid == 0) p.g->epoch[NCTA + (id & 3)] = tag;
      }
      return;
    }
  }
  const int m = mn >> 3, n = mn & 7;
  if (wg < 2) {
    cluster_arrive();
    asm volatile("setmaxnreg.inc.sync.aligned.u32 232;");
    const int id = mn | (warp << 7);
#pragma unroll 1
    for (int i = wg;; i += 2) {
      float acc[2][96];
#pragma unroll
      for (int r = 0; r < 96; r++) acc[0][r] = acc[1][r] = 0.f;
      pin_regs<96>(acc);
#pragma unroll 1
      while (!consumer_tile(p, acc, sb, i, id)) {
        i += 2;
        if (i >= 14) goto all_done;
      }
      const Ctx cx = make_ctx(sb, id);
      uint32_t F[3][4][8];
      pack_qkv<8, 2>(acc, F);
      pack_qkv<8, 1>(acc, F);
      send_halo<0, 6>(p, F, cx, i >= 7, 0);
      attn_epilogue<0>(p, acc, F, cx, i >= 7, lds_u(sb + OFF_TAG));
      finish_stores(sb, i);
    }
  all_done:
    if (wg == 0) {
      finish_stores(sb, 12);
    } else {
      cluster_arrive();
      cluster_wait();
    }
  } else {
    asm volatile("setmaxnreg.dec.sync.aligned.u32 40;");
    if (w != 0) {
      if (w == 1 && elect_one()) {
        mbar_init(sb + BAR_FULL + 32, 2);
#pragma unroll
        for (int k = 0; k < NBAR; k++) mbar_init(sb + BAR_EMPTY + 8 * k, 8);
#pragma unroll
        for (int k = 0; k < 3; k++) mbar_init(sb + BAR_XRDY + 8 * k, 4);
#pragma unroll
        for (int k = 0; k < 9; k++) mbar_init(sb + BAR_PUB + 8 * k, 4);
#pragma unroll
        for (int k = 0; k < 4; k++) mbar_init(sb + BAR_CSLD + 8 * k, 1);
        sts_f2(sb + OFF_ZERO, 0.f, 0.f);
        sts_f2(sb + OFF_ZERO + 8, 0.f, 0.f);
        asm volatile("fence.mbarrier_init.release.cluster;" ::: "memory");
      }
      __syncwarp();
      cluster_arrive();
      if (w == 2) {
        if (lane < 28) write_run_desc(sb, lane >> 1, lane & 1);
        bar_arrive(BAR_INIT, 160);
      }
      cluster_wait();
      if (w == 1) producer<true>(p, sb, m, n, lane);
      else if (w == 3) colsum_helper(p, sb, m, n, lane);
      else if (elect_one()) publisher(p, sb, m, n);
    } else {
      const bool leader = elect_one();
      if (leader) {
#pragma unroll
        for (int k = 0; k < 4; k++) mbar_init(sb + BAR_FULL + 8 * k, 2);
        asm volatile("fence.mbarrier_init.release.cluster;" ::: "memory");
      }
      __syncwarp();
      bar_arrive(BAR_INIT0, 160);
      cluster_arrive();
      if (leader) {
#pragma unroll 1
        for (int k = 0; k < 4; k++) {
          const uint32_t fb = sb + BAR_FULL + 8 * k;
          mbar_expect_tx(fb, 16384);
          tma_ld_act(sb + (5 * k + 3) * UNIT, &p.t.xin, fb, 64 * k, m);
          mbar_expect_tx(fb, 3 * UNIT);
          tma_ld3(sb + 5 * k * UNIT, &p.t.wqkv, fb, 128 * n, 64 * k, 0);
          tma_ld3(sb + 5 * k * UNIT + 12288, &p.t.wqkv, fb, 128 * n, 64 * k + 32, 0);
        }
      }
      __syncwarp();
      cluster_wait();
      producer<false>(p, sb, m, n, lane);
    }
  }
}

typedef CUresult (*EncodeFn)(CUtensorMap*, CUtensorMapDataType, cuuint32_t, void*, const cuuint64_t*, const cuuint64_t*,
                             const cuuint32_t*, const cuuint32_t*, CUtensorMapInterleave, CUtensorMapSwizzle,
                             CUtensorMapL2promotion, CUtensorMapFloatOOBfill);

void make_2d(EncodeFn enc, CUtensorMap* m, const void* ptr, uint64_t cols, uint64_t rows, uint32_t box_rows) {
  cuuint64_t d[2] = {cols, rows}, st[1] = {cols * 2};
  cuuint32_t b[2] = {64, box_rows}, e[2] = {1, 1};
  enc(m, CU_TENSOR_MAP_DATA_TYPE_BFLOAT16, 2, const_cast<void*>(ptr), d, st, b, e, CU_TENSOR_MAP_INTERLEAVE_NONE,
      CU_TENSOR_MAP_SWIZZLE_128B, CU_TENSOR_MAP_L2_PROMOTION_L2_128B, CU_TENSOR_MAP_FLOAT_OOB_FILL_NONE);
}
void make_act(EncodeFn enc, CUtensorMap* m, const void* ptr, uint64_t cols, bool split, uint32_t box = 2) {
  const uint64_t row = cols * 2;
  cuuint64_t d[4] = {cols, 32, 2, SEQ / 64}, st[3] = {split ? 2 * row : row, split ? row : 32 * row, 64 * row};
  cuuint32_t b[4] = {64, 32, box, box}, e[4] = {1, 1, 1, 1};
  enc(m, CU_TENSOR_MAP_DATA_TYPE_BFLOAT16, 4, const_cast<void*>(ptr), d, st, b, e, CU_TENSOR_MAP_INTERLEAVE_NONE,
      CU_TENSOR_MAP_SWIZZLE_128B, CU_TENSOR_MAP_L2_PROMOTION_L2_128B, CU_TENSOR_MAP_FLOAT_OOB_FILL_NONE);
}
void make_3d(EncodeFn enc, CUtensorMap* m, const void* ptr, uint64_t d0, uint64_t rows, uint64_t d2, uint64_t row_bytes,
             uint64_t chunk_bytes, uint32_t box_chunks) {
  cuuint64_t d[3] = {d0, rows, d2}, st[2] = {row_bytes, chunk_bytes};
  cuuint32_t b[3] = {64, 32, box_chunks}, e[3] = {1, 1, 1};
  enc(m, CU_TENSOR_MAP_DATA_TYPE_BFLOAT16, 3, const_cast<void*>(ptr), d, st, b, e, CU_TENSOR_MAP_INTERLEAVE_NONE,
      CU_TENSOR_MAP_SWIZZLE_128B, CU_TENSOR_MAP_L2_PROMOTION_L2_128B, CU_TENSOR_MAP_FLOAT_OOB_FILL_NONE);
}

}

extern "C" void kernel_launch(void* const* d_in, const int* in_sizes, int n_in, void* d_out, int out_size) {
  (void)in_sizes; (void)n_in; (void)out_size;
  static EncodeFn enc = nullptr;
  static void *att = nullptr, *hbuf = nullptr, *scratch = nullptr;
  static int by_smid = 0;
  if (!enc) {
    void* fn = nullptr;
    cudaDriverEntryPointQueryResult q;
    cudaGetDriverEntryPoint("cuTensorMapEncodeTiled", &fn, cudaEnableDefault, &q);
    enc = (EncodeFn)fn;
    cudaGetSymbolAddress(&att, g_att);
    cudaGetSymbolAddress(&hbuf, g_h);
    cudaGetSymbolAddress(&scratch, g_scratch);
    cudaFuncSetAttribute(fused_layers_kernel<true>, cudaFuncAttributeMaxDynamicSharedMemorySize, SMEM_BYTES);
    cudaFuncSetAttribute(fused_layers_kernel<false>, cudaFuncAttributeMaxDynamicSharedMemorySize, SMEM_BYTES);
    int sms = 0, clusters = 0, dev = 0;
    cudaGetDevice(&dev);
    cudaDeviceGetAttribute(&sms, cudaDevAttrMultiProcessorCount, dev);
    cudaLaunchConfig_t cfg = {};
    cfg.gridDim = dim3(132);
    cfg.blockDim = dim3(384);
    cfg.dynamicSmemBytes = SMEM_BYTES;
    cudaLaunchAttribute at[1];
    at[0].id = cudaLaunchAttributeClusterDimension;
    at[0].val.clusterDim.x = 2; at[0].val.clusterDim.y = 1; at[0].val.clusterDim.z = 1;
    cfg.attrs = at;
    cfg.numAttrs = 1;
    if (cudaOccupancyMaxActiveClusters(&clusters, fused_layers_kernel<true>, &cfg) != cudaSuccess) (void)cudaGetLastError();
    by_smid = sms == 132 && clusters == 66;
  }
  Maps p;
  Scalars sc;
  make_act(enc, &p.xin, d_in[0], DM, true);
  make_act(enc, &p.out, d_out, DM, true);
  make_act(enc, &p.out_w, d_out, DM, true, 1);
  make_act(enc, &p.att, att, DM, false);
  make_act(enc, &p.h, hbuf, FF, false);
  make_2d(enc, &p.att_st, att, DM, SEQ, 32);
  make_2d(enc, &p.h_st, hbuf, FF, SEQ, 32);
  make_2d(enc, &p.w1c, d_in[4], FF, DM, 32);
  make_3d(enc, &p.wqkv, d_in[1], DM, DM, 3, 3 * DM * 2, DM * 2, 3);
  make_3d(enc, &p.wo, d_in[2], 64, DM, DM / 64, DM * 2, 128, 2);
  make_3d(enc, &p.w1a, d_in[4], 64, DM, FF / 64, FF * 2, 128, 3);
  make_3d(enc, &p.w1b, d_in[4], 64, DM, FF / 64, FF * 2, 128, 2);
  make_3d(enc, &p.w2, d_in[6], 64, FF, DM / 64, DM * 2, 128, 2);
  sc.b1 = (const __nv_bfloat16*)d_in[5];
  sc.b2 = (const __nv_bfloat16*)d_in[7];
  sc.g = (Scratch*)scratch;
  sc.zero = 0;
  if (by_smid) fused_layers_kernel<true><<<132, 384, SMEM_BYTES>>>(sc, p);
  else fused_layers_kernel<false><<<NCTA, 384, SMEM_BYTES>>>(sc, p);
}
```

```cpp
#include <cuda_runtime.h>
#include <cuda_bf16.h>
#include <cuda.h>
#include <stdint.h>
#include <type_traits>

namespace {

constexpr int SEQ = 2048, DM = 1024, FF = 3584;
constexpr int NCTA = 128;
constexpr int NBAR = 5;

constexpr uint32_t RING_UNITS = 20, UNIT = 8192;
constexpr uint32_t OFF_X   = RING_UNITS * UNIT;
constexpr uint32_t OFF_STG = OFF_X + 32768;
constexpr uint32_t OFF_HLP = OFF_STG + 16384;
constexpr uint32_t OFF_RUN = OFF_STG + 24576;
constexpr uint32_t OFF_CSQ = OFF_RUN + 512;
constexpr uint32_t OFF_CSF = OFF_CSQ + 2048;
constexpr uint32_t OFF_ROW = OFF_CSF + 3584;
constexpr uint32_t OFF_HALF = OFF_ROW + 1024;
constexpr uint32_t OFF_BAR = OFF_HALF + 1024;
constexpr uint32_t SMEM_BYTES = OFF_BAR + 384;
constexpr uint32_t BAR_FULL = OFF_BAR, BAR_EMPTY = OFF_BAR + 8 * NBAR;
constexpr uint32_t BAR_XRDY = OFF_BAR + 80;
constexpr uint32_t BAR_DUMMY = OFF_BAR + 96, OFF_TAG = OFF_BAR + 104, OFF_ZERO = OFF_BAR + 112;
constexpr uint32_t BAR_PUB = OFF_BAR + 128;
constexpr uint32_t BAR_CSLD = OFF_BAR + 200;
constexpr uint32_t BAR_BIAS = OFF_BAR + 216;
constexpr uint32_t BAR_XGO = OFF_BAR + 224;

constexpr uint64_t DESC_A = (1ull << 62) | ((uint64_t)(2048 >> 4) << 32) | (1ull << 16);
constexpr uint64_t DESC_B = (1ull << 62) | ((uint64_t)(1024 >> 4) << 32) | ((uint64_t)(4096 >> 4) << 16);

constexpr int BAR_INIT = 0, BAR_ORDER = 1, BAR_GUARD = 3, BAR_WG = 5, BAR_GO = 7, BAR_DONE = 8, BAR_HLP = 9;
constexpr int BAR_INIT0 = 10, BAR_PAIR = 11, BAR_STAT = 15;

constexpr int WIN1 = 5;
constexpr int WIN0 = 7;
constexpr int SKEW = 3;
constexpr int WIN2 = 1;
constexpr int GELU_DEP = 2;
constexpr int STG_WAIT = 5;
constexpr int HALO_NS = 200;
constexpr int STAT_NS = 800;
constexpr int CS_NS = 500;
constexpr int XB_NS = 400;
constexpr int XB_GAP_NS = 50;
constexpr int STAG_NS = 450;
constexpr int STAG3_NS = 100;
constexpr int PACE_M = 100;
constexpr int PACE_N = 300;

struct Scratch {
  uint4 stats[4 * 8 * SEQ];
  uint4 halo[2 * 2 * 16 * 8 * 384];
  uint4 csp[2 * 8 * 17 * 224];
  uint32_t flags[16 * 32];
  uint32_t epoch[NCTA + 4];
};

struct Maps {
  CUtensorMap xin, out, att, h, wqkv, wo, w1a, w1b, w2, att_st, h_st, w1c, out_w, out_8;
};
struct Scalars {
  Scratch* g;
  const __nv_bfloat16 *b1, *b2;
  uint32_t zero;
};
struct Params : Scalars {
  const Maps& t;
};

__device__ __nv_bfloat16 g_att[SEQ * DM];
__device__ __nv_bfloat16 g_h[SEQ * FF];
__device__ Scratch g_scratch;

__device__ __forceinline__ void mbar_init(uint32_t bar, int cnt) {
  asm volatile("mbarrier.init.shared::cta.b64 [%0], %1;" ::"r"(bar), "r"(cnt));
}
__device__ __forceinline__ void mbar_expect_tx(uint32_t bar, uint32_t bytes) {
  asm volatile("mbarrier.arrive.expect_tx.shared::cta.b64 _, [%0], %1;" ::"r"(bar), "r"(bytes) : "memory");
}
__device__ __forceinline__ void mbar_arrive(uint32_t bar) {
  asm volatile("mbarrier.arrive.shared::cta.b64 _, [%0];" ::"r"(bar) : "memory");
}
__device__ __forceinline__ bool mbar_test(uint32_t bar, uint32_t parity) {
  uint32_t ok;
  asm volatile("{\n.reg .pred p;\nmbarrier.test_wait.parity.shared::cta.b64 p, [%1], %2;\nselp.u32 %0, 1, 0, p;\n}"
               : "=r"(ok) : "r"(bar), "r"(parity) : "memory");
  return ok;
}
__device__ __forceinline__ void mbar_wait(uint32_t bar, uint32_t parity) {
  asm volatile(
      "{\n.reg .pred p;\n.reg .u32 it;\nmov.u32 it, 0;\n"
      "WAIT_LOOP:\n"
      "mbarrier.try_wait.parity.shared::cta.b64 p, [%0], %1;\n"
      "@p bra WAIT_DONE;\n"
      "add.u32 it, it, 1;\n"
      "setp.lt.u32 p, it, 0x400000;\n"
      "@p bra WAIT_LOOP;\n"
      "trap;\n"
      "WAIT_DONE:\n}"
      ::"r"(bar), "r"(parity) : "memory");
}
__device__ __forceinline__ void bar_sync(int id, int n) { asm volatile("bar.sync %0, %1;" ::"r"(id), "r"(n) : "memory"); }
__device__ __forceinline__ void bar_arrive(int id, int n) { asm volatile("bar.arrive %0, %1;" ::"r"(id), "r"(n) : "memory"); }
__device__ __forceinline__ void tma_ld2(uint32_t dst, const CUtensorMap* m, uint32_t bar, int c0, int c1) {
  asm volatile("cp.async.bulk.tensor.2d.shared::cluster.global.mbarrier::complete_tx::bytes [%0], [%1, {%3, %4}], [%2];"
               ::"r"(dst), "l"(m), "r"(bar), "r"(c0), "r"(c1) : "memory");
}
__device__ __forceinline__ void tma_ld_act(uint32_t dst, const CUtensorMap* m, uint32_t bar, int col, int blk) {
  asm volatile("cp.async.bulk.tensor.4d.shared::cluster.global.mbarrier::complete_tx::bytes [%0], [%1, {%3, %5, %5, %4}], [%2];"
               ::"r"(dst), "l"(m), "r"(bar), "r"(col), "r"(2 * blk), "r"(0) : "memory");
}
__device__ __forceinline__ void tma_st_warp(const CUtensorMap* m, uint32_t src, int col, int blk, int w, int row = 0) {
  asm volatile("cp.async.bulk.tensor.4d.global.shared::cta.bulk_group [%0, {%2, %5, %3, %4}], [%1];"
               ::"l"(m), "r"(src), "r"(col), "r"(w & 1), "r"(2 * blk + (w >> 1)), "r"(row) : "memory");
}
__device__ __forceinline__ void tma_ld3(uint32_t dst, const CUtensorMap* m, uint32_t bar, int c0, int c1, int c2) {
  asm volatile("cp.async.bulk.tensor.3d.shared::cluster.global.mbarrier::complete_tx::bytes [%0], [%1, {%3, %4, %5}], [%2];"
               ::"r"(dst), "l"(m), "r"(bar), "r"(c0), "r"(c1), "r"(c2) : "memory");
}
__device__ __forceinline__ void tma_ld3_pair(uint32_t dst, const CUtensorMap* m, uint32_t bar, int c0, int c1, int c2) {
  asm volatile("cp.async.bulk.tensor.3d.shared::cluster.global.mbarrier::complete_tx::bytes.multicast::cluster"
               " [%0], [%1, {%3, %4, %5}], [%2], %6;"
               ::"r"(dst), "l"(m), "r"(bar), "r"(c0), "r"(c1), "r"(c2), "h"((uint16_t)3) : "memory");
}
__device__ __forceinline__ uint32_t pair_offset(uint32_t sb, uint32_t rank) {
  uint32_t r;
  asm volatile("mapa.shared::cluster.u32 %0, %1, %2;" : "=r"(r) : "r"(sb), "r"(rank));
  return r - sb;
}
__device__ __forceinline__ void mbar_arrive_cluster(uint32_t bar) {
  asm volatile("mbarrier.arrive.shared::cluster.b64 _, [%0];" ::"r"(bar) : "memory");
}
__device__ __forceinline__ void cluster_arrive() { asm volatile("barrier.cluster.arrive.relaxed;" ::: "memory"); }
__device__ __forceinline__ void cluster_wait() { asm volatile("barrier.cluster.wait.acquire;" ::: "memory"); }
__device__ __forceinline__ void tma_st2(const CUtensorMap* m, uint32_t src, int c0, int c1) {
  asm volatile("cp.async.bulk.tensor.2d.global.shared::cta.bulk_group [%0, {%2, %3}], [%1];"
               ::"l"(m), "r"(src), "r"(c0), "r"(c1) : "memory");
}
__device__ __forceinline__ void bulk_commit() { asm volatile("cp.async.bulk.commit_group;" ::: "memory"); }
__device__ __forceinline__ void bulk_wait_read() { asm volatile("cp.async.bulk.wait_group.read 0;" ::: "memory"); }
__device__ __forceinline__ void bulk_wait_all() { asm volatile("cp.async.bulk.wait_group 0;" ::: "memory"); }
__device__ __forceinline__ void fence_async_smem() { asm volatile("fence.proxy.async.shared::cta;" ::: "memory"); }
__device__ __forceinline__ void fence_async_global() { asm volatile("fence.proxy.async.global;" ::: "memory"); }
__device__ __forceinline__ void st_relaxed(uint32_t* p, uint32_t v) {
  asm volatile("st.relaxed.gpu.global.u32 [%0], %1;" ::"l"(p), "r"(v) : "memory");
}
__device__ __forceinline__ void st_msg(uint4* p, uint32_t a, uint32_t b, uint32_t c, uint32_t tag) {
  asm volatile("{\n.reg .b128 v;\nmov.b128 v, {%1, %2, %3, %4};\nst.relaxed.gpu.global.b128 [%0], v;\n}"
               ::"l"(p), "r"(a), "r"(b), "r"(c), "r"(tag) : "memory");
}
__device__ __forceinline__ void ld_msg(const uint4* p, uint32_t& a, uint32_t& b, uint32_t& c, uint32_t& tag) {
  asm volatile("{\n.reg .b128 v;\nld.relaxed.gpu.global.b128 v, [%4];\nmov.b128 {%0, %1, %2, %3}, v;\n}"
               : "=r"(a), "=r"(b), "=r"(c), "=r"(tag) : "l"(p) : "memory");
}
__device__ __forceinline__ bool elect_one() {
  uint32_t ok;
  asm volatile("{\n.reg .pred p;\nelect.sync _|p, 0xffffffff;\nselp.u32 %0, 1, 0, p;\n}" : "=r"(ok));
  return ok;
}
__device__ __forceinline__ uint32_t lanemask_lt() {
  uint32_t v;
  asm("mov.u32 %0, %%lanemask_lt;" : "=r"(v));
  return v;
}
__device__ __forceinline__ int uniform(int v) { return __shfl_sync(0xffffffffu, v, 0); }
__device__ __forceinline__ uint32_t pack_bf16(float lo, float hi) {
  uint32_t r;
  asm("cvt.rn.bf16x2.f32 %0, %1, %2;" : "=r"(r) : "f"(hi), "f"(lo));
  return r;
}
__device__ __forceinline__ float prmt_f(uint32_t a, uint32_t sel) {
  float r;
  asm("{\n.reg .b32 t;\nprmt.b32 t, %1, 0, %2;\nmov.b32 %0, t;\n}" : "=f"(r) : "r"(a), "r"(sel));
  return r;
}
__device__ __forceinline__ float bf_lo(uint32_t v) { return __uint_as_float(v << 16); }
__device__ __forceinline__ float bf_hi(uint32_t v) { return __uint_as_float(v & 0xffff0000u); }
__device__ __forceinline__ void stsm4(uint32_t addr, uint32_t r0, uint32_t r1, uint32_t r2, uint32_t r3) {
  asm volatile("stmatrix.sync.aligned.m8n8.x4.shared.b16 [%0], {%1, %2, %3, %4};"
               ::"r"(addr), "r"(r0), "r"(r1), "r"(r2), "r"(r3) : "memory");
}
__device__ __forceinline__ void ldsm4(uint32_t addr, uint32_t& r0, uint32_t& r1, uint32_t& r2, uint32_t& r3) {
  asm volatile("ldmatrix.sync.aligned.m8n8.x4.shared.b16 {%0, %1, %2, %3}, [%4];"
               : "=r"(r0), "=r"(r1), "=r"(r2), "=r"(r3) : "r"(addr) : "memory");
}
__device__ __forceinline__ uint32_t movtrans(uint32_t a) {
  uint32_t d;
  asm volatile("movmatrix.sync.aligned.m8n8.trans.b16 %0, %1;" : "=r"(d) : "r"(a));
  return d;
}
__device__ __forceinline__ void mma16816(float (&c)[4], uint32_t a0, uint32_t a1, uint32_t a2, uint32_t a3, uint32_t b0, uint32_t b1) {
  asm volatile("mma.sync.aligned.m16n8k16.row.col.f32.bf16.bf16.f32 {%0,%1,%2,%3}, {%4,%5,%6,%7}, {%8,%9}, {%0,%1,%2,%3};"
               : "+f"(c[0]), "+f"(c[1]), "+f"(c[2]), "+f"(c[3])
               : "r"(a0), "r"(a1), "r"(a2), "r"(a3), "r"(b0), "r"(b1));
}
__device__ __forceinline__ void mma1688(float (&c)[4], uint32_t a0, uint32_t a1, uint32_t b0) {
  asm volatile("mma.sync.aligned.m16n8k8.row.col.f32.bf16.bf16.f32 {%0,%1,%2,%3}, {%4,%5}, {%6}, {%0,%1,%2,%3};"
               : "+f"(c[0]), "+f"(c[1]), "+f"(c[2]), "+f"(c[3]) : "r"(a0), "r"(a1), "r"(b0));
}
__device__ __forceinline__ float2 lds_f2(uint32_t a) {
  float2 v;
  asm volatile("ld.shared.v2.f32 {%0, %1}, [%2];" : "=f"(v.x), "=f"(v.y) : "r"(a) : "memory");
  return v;
}
__device__ __forceinline__ float4 lds_f4(uint32_t a) {
  float4 v;
  asm volatile("ld.shared.v4.f32 {%0, %1, %2, %3}, [%4];" : "=f"(v.x), "=f"(v.y), "=f"(v.z), "=f"(v.w) : "r"(a) : "memory");
  return v;
}
__device__ __forceinline__ float lds_f(uint32_t a) {
  float v;
  asm volatile("ld.shared.f32 %0, [%1];" : "=f"(v) : "r"(a) : "memory");
  return v;
}
__device__ __forceinline__ uint32_t lds_u(uint32_t a) {
  uint32_t v;
  asm volatile("ld.shared.u32 %0, [%1];" : "=r"(v) : "r"(a) : "memory");
  return v;
}
__device__ __forceinline__ void sts_f2(uint32_t a, float x, float y) {
  asm volatile("st.shared.v2.f32 [%0], {%1, %2};" ::"r"(a), "f"(x), "f"(y) : "memory");
}
__device__ __forceinline__ void sts_u4(uint32_t a, uint32_t x, uint32_t y, uint32_t z, uint32_t w) {
  asm volatile("st.shared.v4.u32 [%0], {%1, %2, %3, %4};" ::"r"(a), "r"(x), "r"(y), "r"(z), "r"(w) : "memory");
}
__device__ __forceinline__ void lds_u4(uint32_t a, uint32_t& x, uint32_t& y, uint32_t& z, uint32_t& w) {
  asm volatile("ld.shared.v4.u32 {%0, %1, %2, %3}, [%4];" : "=r"(x), "=r"(y), "=r"(z), "=r"(w) : "r"(a) : "memory");
}
__device__ __forceinline__ float ex2(float x) {
  float y;
  asm("ex2.approx.ftz.f32 %0, %1;" : "=f"(y) : "f"(x));
  return y;
}
__device__ __forceinline__ float rcp_hw(float x) {
  float y;
  asm("rcp.approx.ftz.f32 %0, %1;" : "=f"(y) : "f"(x));
  return y;
}
__device__ __forceinline__ float tanh_hw(float x) {
  float y;
  asm("tanh.approx.f32 %0, %1;" : "=f"(y) : "f"(x));
  return y;
}
__device__ __forceinline__ float quad_sum(float v) {
  v += __shfl_xor_sync(0xffffffffu, v, 1);
  return v + __shfl_xor_sync(0xffffffffu, v, 2);
}
__device__ __forceinline__ float quad_max(float v) {
  v = fmaxf(v, __shfl_xor_sync(0xffffffffu, v, 1));
  return fmaxf(v, __shfl_xor_sync(0xffffffffu, v, 2));
}

template <int N> __device__ __forceinline__ void wgmma_ss(float (&d)[96], uint64_t da, uint64_t db, uint32_t keep = 1);
template <> __device__ __forceinline__ void wgmma_ss<128>(float (&d)[96], uint64_t da, uint64_t db, uint32_t keep) {
  asm volatile(
      "{\n.reg .pred p;\nsetp.ne.u32 p, %66, 0;\n"
      "wgmma.mma_async.sync.aligned.m64n128k16.f32.bf16.bf16 {%0, %1, %2, %3, %4, %5, %6, %7, %8, %9, %10, %11, %12, %13, %14, %15, %16, %17, %18, %19, %20, %21, %22, %23, %24, %25, %26, %27, %28, %29, %30, %31, %32, %33, %34, %35, %36, %37, %38, %39, %40, %41, %42, %43, %44, %45, %46, %47, %48, %49, %50, %51, %52, %53, %54, %55, %56, %57, %58, %59, %60, %61, %62, %63}, %64, %65, p, 1, 1, 0, 1;\n}"
      : "+f"(d[0]), "+f"(d[1]), "+f"(d[2]), "+f"(d[3]), "+f"(d[4]), "+f"(d[5]), "+f"(d[6]), "+f"(d[7]), "+f"(d[8]), "+f"(d[9]), "+f"(d[10]), "+f"(d[11]), "+f"(d[12]), "+f"(d[13]), "+f"(d[14]), "+f"(d[15]), "+f"(d[16]), "+f"(d[17]), "+f"(d[18]), "+f"(d[19]), "+f"(d[20]), "+f"(d[21]), "+f"(d[22]), "+f"(d[23]), "+f"(d[24]), "+f"(d[25]), "+f"(d[26]), "+f"(d[27]), "+f"(d[28]), "+f"(d[29]), "+f"(d[30]), "+f"(d[31]), "+f"(d[32]), "+f"(d[33]), "+f"(d[34]), "+f"(d[35]), "+f"(d[36]), "+f"(d[37]), "+f"(d[38]), "+f"(d[39]), "+f"(d[40]), "+f"(d[41]), "+f"(d[42]), "+f"(d[43]), "+f"(d[44]), "+f"(d[45]), "+f"(d[46]), "+f"(d[47]), "+f"(d[48]), "+f"(d[49]), "+f"(d[50]), "+f"(d[51]), "+f"(d[52]), "+f"(d[53]), "+f"(d[54]), "+f"(d[55]), "+f"(d[56]), "+f"(d[57]), "+f"(d[58]), "+f"(d[59]), "+f"(d[60]), "+f"(d[61]), "+f"(d[62]), "+f"(d[63])
      : "l"(da), "l"(db), "r"(keep));
}

template <> __device__ __forceinline__ void wgmma_ss<192>(float (&d)[96], uint64_t da, uint64_t db, uint32_t keep) {
  asm volatile(
      "{\n.reg .pred p;\nsetp.ne.u32 p, %98, 0;\n"
      "wgmma.mma_async.sync.aligned.m64n192k16.f32.bf16.bf16 {%0, %1, %2, %3, %4, %5, %6, %7, %8, %9, %10, %11, %12, %13, %14, %15, %16, %17, %18, %19, %20, %21, %22, %23, %24, %25, %26, %27, %28, %29, %30, %31, %32, %33, %34, %35, %36, %37, %38, %39, %40, %41, %42, %43, %44, %45, %46, %47, %48, %49, %50, %51, %52, %53, %54, %55, %56, %57, %58, %59, %60, %61, %62, %63, %64, %65, %66, %67, %68, %69, %70, %71, %72, %73, %74, %75, %76, %77, %78, %79, %80, %81, %82, %83, %84, %85, %86, %87, %88, %89, %90, %91, %92, %93, %94, %95}, %96, %97, p, 1, 1, 0, 1;\n}"
      : "+f"(d[0]), "+f"(d[1]), "+f"(d[2]), "+f"(d[3]), "+f"(d[4]), "+f"(d[5]), "+f"(d[6]), "+f"(d[7]), "+f"(d[8]), "+f"(d[9]), "+f"(d[10]), "+f"(d[11]), "+f"(d[12]), "+f"(d[13]), "+f"(d[14]), "+f"(d[15]), "+f"(d[16]), "+f"(d[17]), "+f"(d[18]), "+f"(d[19]), "+f"(d[20]), "+f"(d[21]), "+f"(d[22]), "+f"(d[23]), "+f"(d[24]), "+f"(d[25]), "+f"(d[26]), "+f"(d[27]), "+f"(d[28]), "+f"(d[29]), "+f"(d[30]), "+f"(d[31]), "+f"(d[32]), "+f"(d[33]), "+f"(d[34]), "+f"(d[35]), "+f"(d[36]), "+f"(d[37]), "+f"(d[38]), "+f"(d[39]), "+f"(d[40]), "+f"(d[41]), "+f"(d[42]), "+f"(d[43]), "+f"(d[44]), "+f"(d[45]), "+f"(d[46]), "+f"(d[47]), "+f"(d[48]), "+f"(d[49]), "+f"(d[50]), "+f"(d[51]), "+f"(d[52]), "+f"(d[53]), "+f"(d[54]), "+f"(d[55]), "+f"(d[56]), "+f"(d[57]), "+f"(d[58]), "+f"(d[59]), "+f"(d[60]), "+f"(d[61]), "+f"(d[62]), "+f"(d[63]), "+f"(d[64]), "+f"(d[65]), "+f"(d[66]), "+f"(d[67]), "+f"(d[68]), "+f"(d[69]), "+f"(d[70]), "+f"(d[71]), "+f"(d[72]), "+f"(d[73]), "+f"(d[74]), "+f"(d[75]), "+f"(d[76]), "+f"(d[77]), "+f"(d[78]), "+f"(d[79]), "+f"(d[80]), "+f"(d[81]), "+f"(d[82]), "+f"(d[83]), "+f"(d[84]), "+f"(d[85]), "+f"(d[86]), "+f"(d[87]), "+f"(d[88]), "+f"(d[89]), "+f"(d[90]), "+f"(d[91]), "+f"(d[92]), "+f"(d[93]), "+f"(d[94]), "+f"(d[95])
      : "l"(da), "l"(db), "r"(keep));
}

template <int R>
__device__ __forceinline__ void pin_regs(float (&a)[2][96]) {
#pragma unroll
  for (int m = 0; m < 2; m++)
#pragma unroll
    for (int i = 0; i < R; i++) asm volatile("" : "+f"(a[m][i])::"memory");
}

struct Ctx {
  uint32_t sb;
  int m, n, wg, w, lane;
};
__device__ __forceinline__ Ctx make_ctx(uint32_t sb, int id) {
  int lane;
  asm volatile("mov.u32 %0, %%laneid;" : "=r"(lane));
  asm volatile("" : "+r"(id), "+r"(sb));
  return Ctx{sb, (id >> 3) & 15, id & 7, id >> 9, (id >> 7) & 3, lane};
}
#define UNPACK_CTX(c) const uint32_t sb = c.sb; const int m = c.m, n = c.n, wg = c.wg, w = c.w, lane = c.lane

__device__ __forceinline__ uint32_t poll_line(const uint32_t* word, uint32_t target, uint32_t need) {
  uint32_t v;
  asm volatile(
      "{\n.reg .pred p;\n.reg .u32 it, m;\n.reg .s32 d;\nmov.u32 it, 0;\n"
      "POLL_LOOP:\n"
      "ld.relaxed.gpu.global.u32 %0, [%1];\n"
      "sub.s32 d, %0, %2;\n"
      "setp.ge.s32 p, d, 0;\n"
      "vote.sync.ballot.b32 m, p, 0xffffffff;\n"
      "and.b32 m, m, %3;\n"
      "setp.eq.u32 p, m, %3;\n"
      "@p bra.uni POLL_DONE;\n"
      "add.u32 it, it, 1;\n"
      "setp.lt.u32 p, it, 0x400000;\n"
      "@p bra.uni POLL_LOOP;\n"
      "trap;\n"
      "POLL_DONE:\n}"
      : "=&r"(v) : "l"(word), "r"(target), "r"(need) : "memory");
  return v;
}
__device__ __forceinline__ uint32_t ld_relaxed(const uint32_t* p) {
  uint32_t v;
  asm volatile("ld.relaxed.gpu.global.u32 %0, [%1];" : "=r"(v) : "l"(p) : "memory");
  return v;
}
__device__ __forceinline__ float chain(float x, uint32_t on, uint32_t zero) {
  return __uint_as_float(__float_as_uint(x) | (on & zero));
}
constexpr int MSG_SPINS = 1 << 20;

constexpr int STAGES_PER_LAYER = 152;
__device__ __forceinline__ int nib(uint64_t v, int i) { return (int)(v >> (4 * i)) & 15; }
__device__ __forceinline__ bool tile_wide(int t) { return (0x23 >> t) & 1; }
__device__ __forceinline__ void weight_coords(const Params& p, int t, int n, const CUtensorMap*& map, int& c0, int& c2) {
  map = &p.t.wqkv + nib(0x4233100ull, t);
  c0 = t < 2 ? 128 * n + 64 * t : 0;
  c2 = t < 2 ? 0 : (t == 2 || t == 6) ? 2 * n : 7 * n + 2 * t - 6;
}

template <bool IS_A>
__device__ __forceinline__ void producer(const Params& p, uint32_t sb, int m, int n, int lane) {
  const uint32_t low = (1u << (4 * n)) - 1, others = (0x6543210u & low) | (0x7654321u & ~low);
  const uint64_t order_x = (uint64_t)(others * 2 + 0x1111111u) << 36 | (uint64_t)others * 2 << 8 | (n * 0x22 + 0x10);
  int inflight = 4, cur = 0;
  uint32_t fb = sb + BAR_FULL + 32, rb = sb + BAR_EMPTY, rph = 0, pos = 0, tag32 = 0, seen = 0;
  const uint32_t fend = sb + BAR_FULL + 8 * NBAR, rend = sb + BAR_EMPTY + 8 * NBAR;
  const uint32_t* word = p.g->flags + m * 32 + (lane < 16 ? lane >> 1 : lane & 7);
#pragma unroll 1
  for (int sg = 1; sg < 22; sg++) {
    const int layer = sg >= 11, s = sg == 1 ? 2 : sg == 2 ? 1 : sg - 11 * layer;
    const int t = nib(0x65434321010ull, s), kind = nib(0x32110031100ull, s);
    const bool wide = tile_wide(t);
    const uint32_t bbytes = wide ? 3 * UNIT : 2 * UNIT, base = sb + (IS_A ? bbytes : (m & 1) * (bbytes / 2));
    if (IS_A && kind == 0) {
      if (sg == 2) seen = tag32 = (__ldcg(p.g->epoch + m * 8 + n) + 1) << 5;
#pragma unroll 1
      for (int k = 0; k < 2; k++) {
#pragma unroll 1
        for (; inflight > (wide ? 3 : 4); inflight--) {
          mbar_wait(rb, rph);
          rb += 8;
          if (rb == rend) { rb -= 8 * NBAR; rph ^= 1; }
        }
        if (elect_one()) mbar_arrive(fb);
        inflight++;
        fb += 8;
        if (fb == fend) fb -= 8 * NBAR;
        pos += bbytes + 2 * UNIT;
        if (pos >= RING_UNITS * UNIT) pos -= RING_UNITS * UNIT;
      }
      continue;
    }
    const int mul = t == 6 ? 448 : t == 2 ? 128 : 64, count = sg == 1 ? 12 : 2 * nib(0x4871ull, kind);
    uint64_t order0 = sg == 1 ? 0xFEDCBA987654ull : kind == 3 ? 0x76543210u : order_x >> (8 * (kind & 1));
    uint32_t special = (s == 4 || s == 10) ? 0x10 : s == 9 ? 0xF : s == 0;
    if (IS_A) special |= (kind & 1 ? 0 : 3) | (count >= 4 ? 1u << (count - 4) : 0);
    if (s >= 9) pos = (s + 6) * UNIT;
    const CUtensorMap* map;
    int c0 = 0, c2 = 0, ev = 0;
    if (IS_A) {
      map = &p.t.xin + (t == 2 ? 2 : t == 6 ? 3 : sg >= 4);
      ev = 9 * layer + (t < 2 ? 0 : t == 2 ? 1 : t < 6 ? 4 : 5);
      if (elect_one()) asm volatile("prefetch.tensormap [%0];" ::"l"(map) : "memory");
    } else {
      weight_coords(p, t, n, map, c0, c2);
    }
#pragma unroll 1
    for (int add = 0; add < mul; add += 64) {
      uint64_t order = order0;
      const int need = kind == 3 ? ev : ev - 1 + (lane & 1), sh = kind == 3 ? 16 : 0;
      uint32_t ready = IS_A ? __ballot_sync(0xffffffffu, cur >= need) >> sh : 0;
#pragma unroll 1
      for (int k = 0; k < count; k++) {
        const int code = order & 15, kc = code * mul + add;
        order >>= 4;
        if ((special >> k) & 1) {
          const int lag = wide ? (s == 9 && k == 2 ? 2 : 3) : ((s == 4 || s == 10) && add == 0 && k < 4) ? 3 : 4;
#pragma unroll 1
          for (; inflight > lag; inflight--) {
            mbar_wait(rb, rph);
            rb += 8;
            if (rb == rend) { rb -= 8 * NBAR; rph ^= 1; }
          }
          inflight++;
          if (IS_A) {
            if (kind == 3 ? t == 2 && add + k == 64 : !(kind & 1) && k < 2) {
              if (t == 2) mbar_wait(sb + BAR_PUB + 8, layer);
              if (elect_one()) mbar_arrive(fb);
              goto next_stage;
            }
            if (k == count - 4 && sg >= 3) seen = ld_relaxed(word);
          }
        } else {
          mbar_wait(rb, rph);
          rb += 8;
          if (rb == rend) { rb -= 8 * NBAR; rph ^= 1; }
        }
        if (IS_A && !((ready >> code) & 1)) {
          cur = max(cur, (int)(seen - tag32));
          ready = __ballot_sync(0xffffffffu, cur >= need) >> sh;
          if (!((ready >> code) & 1)) {
            cur = (int)(poll_line(word, tag32 + need, 1u << (code + sh)) - tag32);
            ready = __ballot_sync(0xffffffffu, cur >= need) >> sh;
          }
          asm volatile("fence.acquire.gpu;" ::: "memory");
          fence_async_global();
          seen = ld_relaxed(word);
        }
        if (elect_one()) {
          if (!IS_A) tma_ld3_pair(base + pos, map, fb, c0, kc + 32 * (m & 1), c2);
          else tma_ld_act(base + pos, map, fb, kc, m);
          mbar_expect_tx(fb, IS_A ? 16384 : bbytes);
        }
      next_stage:
        fb += 8;
        if (fb == fend) fb -= 8 * NBAR;
        pos += bbytes + 2 * UNIT;
        if (pos >= RING_UNITS * UNIT) pos -= RING_UNITS * UNIT;
      }
      special = !IS_A ? 0 : t == 2 ? 1 : add == 128 ? 0x10 : 0;
      if (t == 2) order0 = others << 4 | n;
      if (IS_A && (t == 2 || add == 64 || add == 192)) ev++;
    }
  }
}

__device__ __forceinline__ void publisher(const Params& p, uint32_t sb, int m, int n) {
  {
    const int ts = PACE_M * m, tx = PACE_N * n;
#pragma unroll 1
    for (int k = 0; k < 2; k++) {
      __nanosleep(k == 0 ? min(ts, tx) : abs(ts - tx));
      if ((ts <= tx) == (k == 0)) {
        mbar_expect_tx(sb + BAR_CSLD, 24576);
        tma_ld3(sb + OFF_STG, &p.t.wqkv, sb + BAR_CSLD, 128 * n, 64 * m, 0);
        tma_ld3(sb + OFF_STG + 12288, &p.t.wqkv, sb + BAR_CSLD, 128 * n, 64 * m + 32, 0);
      } else {
#pragma unroll 1
        for (int h = 0; h < 2; h++) {
          const uint32_t xr = sb + BAR_XRDY + 8 * h;
          mbar_expect_tx(xr, 16384);
          tma_ld_act(sb + OFF_X + h * 16384, &p.t.xin, xr, 128 * n + 64 * h, m);
          asm volatile("mbarrier.arrive.shared::cta.b64 _, [%0], 3;" ::"r"(xr) : "memory");
        }
      }
    }
  }
  const uint32_t tag = __ldcg(p.g->epoch + m * 8 + n) + 1;
  uint32_t* word = p.g->flags + m * 32 + n;
  st_relaxed(word, 32 * tag);
#pragma unroll 1
  for (int c = 0; c < 16; c++) {
    const int e = c >= 9 ? c - 9 : c;
    if (e == 2 || e == 7) mbar_wait(sb + BAR_XGO, e == 7);
    else mbar_wait(sb + BAR_PUB + 8 * e, c >= 9);
    asm volatile("fence.release.gpu;" ::: "memory");
    asm volatile("red.relaxed.gpu.global.add.u32 [%0], 1;" ::"l"(word) : "memory");
  }
  p.g->epoch[m * 8 + n] = tag;
}

__device__ __forceinline__ void sum_rows(uint32_t buf, int iters, float (&a)[8], int lane) {
  uint32_t addr = buf + (lane >> 3) * 128 + (((lane & 7) ^ (lane >> 3)) << 4);
#pragma unroll 1
  for (int it = 0; it < iters; it++) {
    uint32_t u[2][4];
    lds_u4(addr, u[0][0], u[0][1], u[0][2], u[0][3]);
    lds_u4((addr ^ 64) + 512, u[1][0], u[1][1], u[1][2], u[1][3]);
    addr += 1024;
#pragma unroll
    for (int e = 0; e < 8; e++) { a[2 * (e & 3)] += bf_lo(u[e >> 2][e & 3]); a[2 * (e & 3) + 1] += bf_hi(u[e >> 2][e & 3]); }
  }
}
__device__ __forceinline__ void publish_sums(const float (&a)[8], uint4* dst, int lane, uint32_t tag) {
  const bool u8 = lane & 8, u16 = lane & 16;
  float h4[4], h2[2];
#pragma unroll
  for (int e = 0; e < 4; e++) h4[e] = (u8 ? a[4 + e] : a[e]) + __shfl_xor_sync(0xffffffffu, u8 ? a[e] : a[4 + e], 8);
#pragma unroll
  for (int e = 0; e < 2; e++) h2[e] = (u16 ? h4[2 + e] : h4[e]) + __shfl_xor_sync(0xffffffffu, u16 ? h4[e] : h4[2 + e], 16);
  st_msg(dst + (lane & 7) * 4 + (u8 ? 2 : 0) + (u16 ? 1 : 0), __float_as_uint(h2[0]), __float_as_uint(h2[1]), 0u, tag);
}

__device__ __forceinline__ void colsum_helper(const Params& p, uint32_t sb, int m, int n, int lane) {
  const uint32_t tag = __ldcg(p.g->epoch + m * 8 + n) + 1;
#pragma unroll 1
  for (int k = lane; k < 288; k += 32) {
    const uint32_t bb = __ldg(reinterpret_cast<const uint32_t*>(k < 224 ? p.b1 + 448 * n : p.b2 + 128 * n - 448) + k);
    const float sc = k < 224 ? 0.5f : 1.f;
    sts_f2(sb + (k < 224 ? OFF_CSF + k * 16 + 8 : OFF_CSQ + 1536 + (k - 224) * 8), sc * bf_lo(bb), sc * bf_hi(bb));
  }
  __syncwarp();
  if (elect_one()) mbar_arrive(sb + BAR_BIAS);
  bar_sync(BAR_HLP, 160);
  {
    uint4* base = p.g->csp + n * 17 * 224 + 12 * m + min(lane & 15, 11);
    float s0 = 0.f, s1 = 0.f;
#pragma unroll 1
    for (int g = 0; g < 2; g++) {
      uint32_t x[4], y[4];
#pragma unroll 1
      for (int it = 0; it < MSG_SPINS; it++) {
        uint32_t bad = 0, z, tg;
        if (g == 0 || it > 0) __nanosleep(CS_NS);
#pragma unroll
        for (int k = 0; k < 4; k++) { ld_msg(base + (g * 8 + (lane >> 4) * 4 + k) * 224, x[k], y[k], z, tg); bad |= tg ^ tag; }
        if (__all_sync(0xffffffffu, bad == 0)) break;
      }
#pragma unroll
      for (int k = 0; k < 4; k++) { s0 += __uint_as_float(x[k]); s1 += __uint_as_float(y[k]); }
    }
    s0 += __shfl_xor_sync(0xffffffffu, s0, 16);
    s1 += __shfl_xor_sync(0xffffffffu, s1, 16);
    if (lane < 12) st_msg(base + 16 * 224, __float_as_uint(s0), __float_as_uint(s1), 0u, tag);
  }
#pragma unroll 1
  for (int c = 0; c < 7; c++) {
    float a[8] = {0.f, 0.f, 0.f, 0.f, 0.f, 0.f, 0.f, 0.f};
#pragma unroll 1
    for (int h = 0; h < 2; h++) {
      if (elect_one()) {
        mbar_expect_tx(sb + BAR_CSLD + 8, 4096);
        tma_ld2(sb + OFF_HLP, &p.t.w1c, sb + BAR_CSLD + 8, 448 * n + 64 * c, 64 * m + 32 * h);
        if (c < 6) asm volatile("cp.async.bulk.prefetch.tensor.2d.L2.global [%0, {%1, %2}];" ::"l"(&p.t.w1c), "r"(448 * n + 64 * c + 64), "r"(64 * m + 32 * h) : "memory");
      }
      mbar_wait(sb + BAR_CSLD + 8, h);
      sum_rows(sb + OFF_HLP, 4, a, lane);
      __syncwarp();
    }
    publish_sums(a, p.g->csp + ((8 + n) * 17 + m) * 224 + c * 32, lane, tag);
  }
  if (elect_one()) {
#pragma unroll 1
    for (int k = 0; k < 3; k++) {
      mbar_wait(sb + BAR_XGO, k & 1);
      __nanosleep(XB_NS);
#pragma unroll 1
      for (int w = 0; w < 4; w++) {
        tma_st_warp(&p.t.out_w, sb + OFF_X + 16384 + w * 4096, 128 * n + 64, m, w);
        bulk_commit();
        bulk_wait_read();
        if (w < 3) __nanosleep(XB_GAP_NS);
      }
      bulk_wait_all();
      asm volatile("mbarrier.arrive.shared::cta.b64 _, [%0], 4;" ::"r"(sb + BAR_PUB + (k & 1 ? 64 : 24)) : "memory");
    }
  }
}

__device__ __forceinline__ void poll_msgs2(const uint4* pa, const uint4* pb, float (&v)[4], uint32_t tag) {
#pragma unroll 1
  for (int it = 0; it < MSG_SPINS; it++) {
    uint32_t x[4], z, ta, tb;
    ld_msg(pa, x[0], x[1], z, ta);
    ld_msg(pb, x[2], x[3], z, tb);
#pragma unroll
    for (int e = 0; e < 4; e++) v[e] = __uint_as_float(x[e]);
    if (__all_sync(0xffffffffu, ta == tag && tb == tag)) break;
  }
}
__device__ __forceinline__ void colsum_total(const Params& p, const Ctx& cx, int mat, uint32_t tag) {
  uint4* base = p.g->csp + (mat * 8 + cx.n) * 17 * 224;
  const int per = 12 + 2 * mat, k = 2 * cx.w + (cx.lane >> 4), ia = per * cx.m + k, ib = per * cx.m + min(k + 8, per - 1);
  float v[4];
  poll_msgs2(base + (cx.lane & 15) * 224 + ia, base + (cx.lane & 15) * 224 + ib, v, tag);
#pragma unroll 1
  for (int d = 1; d < 16; d *= 2)
#pragma unroll
    for (int e = 0; e < 4; e++) v[e] += __shfl_xor_sync(0xffffffffu, v[e], d);
  const bool hi = cx.lane & 1;
  if ((cx.lane & 14) == 0) st_msg(base + 16 * 224 + (hi ? ib : ia), __float_as_uint(hi ? v[2] : v[0]), __float_as_uint(hi ? v[3] : v[1]), 0u, tag);
}
__device__ __forceinline__ void colsum_gather(const Params& p, const Ctx& cx, int mat, uint32_t tag) {
  const uint4* base = p.g->csp + ((mat * 8 + cx.n) * 17 + 16) * 224;
  const int ia = cx.w * 32 + cx.lane, ib = min(ia + 128, 191 + 32 * mat);
  float v[4];
  poll_msgs2(base + ia, base + ib, v, tag);
  const uint32_t tab = cx.sb + (mat ? OFF_CSF : OFF_CSQ);
  sts_f2(tab + (ia << (3 + mat)), v[0], v[1]);
  sts_f2(tab + (ib << (3 + mat)), v[2], v[3]);
}

#define ACC(q, j, e) acc[(q) & 1][4 * (j) + 2 * ((q) >> 1) + (e)]

constexpr uint32_t RING16 = RING_UNITS * (UNIT >> 4);
__device__ __forceinline__ bool tile_split(int i) { return (0xD98 >> i) & 1; }

__device__ __forceinline__ void write_run_desc(uint32_t sb, int i, int step) {
  const int layer = i >= 7, t = i - 7 * layer, part = tile_split(i) ? step : 2;
  const bool wide = tile_wide(t), own = t != 2 && t != 6 && part != 1 && i != 0, second = t == 1 || t == 4;
  const uint32_t z16 = (wide ? 5 : 4) * (UNIT >> 4), a_off = z16 - 1024 + (uint32_t)DESC_A - (uint32_t)DESC_B;
  const int gl = 16 * t + (part == 2 ? 0 : second ? 16 * part - 14 : 4 * part), g0 = layer * STAGES_PER_LAYER + gl;
  const uint32_t s16 = (sb & 0x3FFFF) >> 4, bfirst = (uint32_t)DESC_B + s16;
  const int nkb = t == 6 ? 56 - SKEW : part == 0 ? 2 : 12 + 2 * part;
  const bool win1 = t == 1 && part != 0;
  const int win = layer ? WIN1 : WIN0;
  const int run = win1 ? win + 1 : t == 2 ? WIN2 + 1 : nkb;
  const int rest = win1 ? 64 | (nkb - 1 - SKEW - win) : t == 2 ? 64 | (7 - WIN2) | ((8 - SKEW) << 7) : 0;
  const uint32_t blo = bfirst + z16 * (wide ? (gl + (t == 5 ? 3 : 0)) & 3 : (gl + 3) % 5);
  const uint32_t alo = own ? (uint32_t)DESC_A + s16 + (OFF_X >> 4) : blo + a_off;
  const uint32_t aoff = own ? alo + 1024 - (blo == bfirst + RING16 - z16 ? bfirst : blo + z16) : a_off;
  const bool xwait = part == 0 && !second, keep = !(part == 0 || t == 5);
  sts_u4(sb + OFF_RUN + (2 * i + step) * 16, blo, alo, aoff,
         ((g0 / NBAR) & 1) | xwait << 1 | keep << 2 | 8 * (g0 % NBAR) | run << 6 | rest << 12);
}

__device__ __forceinline__ float2 row_sums(const Ctx& c, int j0, int j1) {
  const uint32_t xrow = c.sb + OFF_X + c.w * 4096 + c.lane * 128;
  float s = 0.f, q = 0.f, s1 = 0.f, q1 = 0.f;
#pragma unroll 4
  for (int j = j0; j < j1; j++) {
    uint32_t u[4];
    lds_u4(xrow + (j >> 3) * 16384 + (((j & 7) ^ (c.lane & 7)) << 4), u[0], u[1], u[2], u[3]);
#pragma unroll
    for (int e = 0; e < 4; e++) {
      const float a = bf_lo(u[e]), d = bf_hi(u[e]);
      s += a; q = fmaf(a, a, q);
      s1 += d; q1 = fmaf(d, d, q1);
    }
  }
  return make_float2(s + s1, q + q1);
}
__device__ __forceinline__ void write_partial_stats(const Params& p, const Ctx& c, int ln, float2 v, uint32_t tag) {
  st_msg(p.g->stats + (ln * 8 + c.n) * SEQ + 128 * c.m + 32 * c.w + c.lane, __float_as_uint(v.x),
         __float_as_uint(fmaxf(v.y - v.x * v.x * (1.f / 128.f), 0.f)), 0u, tag);
}

template <int QMASK, int J0 = 0, int J1 = 24>
__device__ __forceinline__ void rank1_update(const Params& p, float (&acc)[2][96], const Ctx& cx, int t) {
  float nm[4];
#pragma unroll
  for (int q = 0; q < 4; q++)
    if ((QMASK >> q) & 1) nm[q] = t == 6 ? 1.f : -lds_f(cx.sb + OFF_ROW + (32 * cx.w + 8 * q + (cx.lane >> 2)) * 8 + 4);
  const uint32_t ctab = cx.sb + OFF_CSQ + ((t & 3) * 192 + 2 * (cx.lane & 3)) * 4;
#pragma unroll
  for (int j = J0; j < J1; j++) {
    const float2 cs = lds_f2(ctab + j * 32);
#pragma unroll
    for (int q = 0; q < 4; q++) {
      if (!((QMASK >> q) & 1)) continue;
      const int k = 4 * j + q - 1;
      const float nq = QMASK == 15 && k >= 0 ? chain(nm[q], __float_as_uint(ACC(k & 3, k >> 2, 1)), p.zero) : nm[q];
      ACC(q, j, 0) = fmaf(nq, cs.x, ACC(q, j, 0));
      ACC(q, j, 1) = fmaf(nq, cs.y, ACC(q, j, 1));
    }
  }
}

template <int QMASK, int SEC>
__device__ __forceinline__ void pack_qkv(const float (&acc)[2][96], uint32_t (&F)[3][4][8]) {
#pragma unroll
  for (int q = 3; q >= 0; q--)
#pragma unroll
    for (int j = 0; j < 8; j++) {
      if (!((QMASK >> q) & 1)) continue;
      const uint32_t u = pack_bf16(ACC(q, 8 * SEC + j, 0), ACC(q, 8 * SEC + j, 1));
      F[SEC][q][j] = SEC == 2 ? movtrans(u) : u;
    }
}
template <int K0, int K1>
__device__ __forceinline__ void send_halo(const Params& p, const uint32_t (&F)[3][4][8], const Ctx& cx, int layer, int t) {
  uint32_t E[18];
#pragma unroll
  for (int j = 0; j < 8; j++) { E[j] = F[1][3][j]; E[8 + j] = F[2][3][j]; }
  if (cx.w < 2) {
#pragma unroll
    for (int k = K0; k < K1; k++)
      if (k < 4) sts_u4(cx.sb + OFF_STG + cx.w * 2048 + cx.lane * 16 + k * 512, E[4 * k], E[4 * k + 1], E[4 * k + 2], E[4 * k + 3]);
  } else {
    uint4* dst = p.g->halo + (((layer * 2 + t) * 16 + cx.m) * 8 + cx.n) * 384 + (cx.w & 1) * 192 + cx.lane;
    const uint32_t tag = lds_u(cx.sb + OFF_TAG);
    if (K1 == 6) {
      const float4 r = lds_f4(cx.sb + OFF_ROW + (32 * cx.w + 24 + 2 * (cx.lane & 3)) * 8);
      E[16] = __float_as_uint(r.x);
      E[17] = __float_as_uint(r.z);
    }
#pragma unroll
    for (int k = K0; k < K1; k++) st_msg(dst + k * 32, E[3 * k], E[3 * k + 1], E[3 * k + 2], tag);
  }
}

__device__ __forceinline__ void attn_scores(const uint32_t* qa, const uint32_t* qb, const uint32_t* kp, const uint32_t* ka,
                                            const uint32_t* kb, float (&l)[4], const float4& zero, const bool (&early)[2]) {
  float s[3][4];
#pragma unroll
  for (int x = 0; x < 3; x++) {
    const uint32_t* kk = x == 0 ? kp : x == 1 ? ka : kb;
    asm volatile("mma.sync.aligned.m16n8k16.row.col.f32.bf16.bf16.f32 {%0,%1,%2,%3}, {%4,%5,%6,%7}, {%8,%9}, {%10,%11,%12,%13};"
                 : "=f"(s[x][0]), "=f"(s[x][1]), "=f"(s[x][2]), "=f"(s[x][3])
                 : "r"(qa[0]), "r"(qb[0]), "r"(qa[1]), "r"(qb[1]), "r"(kk[0]), "r"(kk[1]), "f"(zero.x), "f"(zero.y),
                   "f"(zero.z), "f"(zero.w));
  }
#pragma unroll
  for (int x = 0; x < 3; x++) {
    const uint32_t* kk = x == 0 ? kp : x == 1 ? ka : kb;
    mma16816(s[x], qa[2], qb[2], qa[3], qb[3], kk[2], kk[3]);
  }
#pragma unroll
  for (int e = 0; e < 2; e++) {
    l[e] = early[e] ? s[0][e] : s[1][e];
    l[2 + e] = early[e] ? s[1][2 + e] : s[2][2 + e];
  }
}

__device__ __forceinline__ void attn_mix(const float (&l)[4], const float (&sc)[4], const float (&off)[4], const float (&rk)[4],
                                         const uint32_t* vp, const uint32_t* va, const uint32_t* vb, float (&o)[4][4],
                                         float (&sum)[2], uint32_t mask, uint32_t zero) {
  float x[4];
#pragma unroll
  for (int e = 0; e < 4; e++) x[e] = fmaf(l[e], sc[e], off[e]);
  const float ml = quad_max(fmaxf(x[0], x[1])), mh = quad_max(fmaxf(x[2], x[3]));
  x[0] = ex2(x[0] - ml); x[1] = ex2(x[1] - ml);
  x[2] = ex2(x[2] - mh); x[3] = ex2(x[3] - mh);
  sum[0] = x[0] + x[1];
  sum[1] = x[2] + x[3];
  const uint32_t pl = pack_bf16(x[0] * rk[0], x[1] * rk[1]), ph = pack_bf16(x[2] * rk[2], x[3] * rk[3]);
  const uint32_t a0 = pl & ~mask, a1 = ph & mask, a2 = pl & zero, a3 = ph & ~mask, c0 = pl & mask, c1 = ph & zero;
#pragma unroll
  for (int jn = 0; jn < 4; jn++) {
    o[jn][0] = o[jn][1] = o[jn][2] = o[jn][3] = 0.f;
    mma16816(o[jn], a0, a1, a2, a3, va[jn], vb[jn]);
  }
#pragma unroll
  for (int jn = 0; jn < 4; jn++) mma1688(o[jn], c0, c1, vp[jn]);
}

template <int t>
__device__ __forceinline__ void attn_epilogue(const Params& p, float (&acc)[2][96], uint32_t (&F)[3][4][8], const Ctx& cx, int layer, uint32_t tag) {
  UNPACK_CTX(cx);
  const uint32_t ktab = sb + OFF_ROW + (32 * w + 2 * (lane & 3)) * 8, exc = sb + OFF_STG + (w & 1) * 2048 + lane * 16;
  uint4* const halo = p.g->halo + (((layer * 2 + t) * 16 + m) * 8 + n) * 384 + (w & 1) * 192;
  (void)wg;
  uint32_t(&Q)[4][8] = F[0], (&K)[4][8] = F[1], (&V)[4][8] = F[2], P[18];
  float kr[5][2], qr[4];
  bar_arrive(BAR_PAIR + w, 64);
  if (layer == 0 && t == 1) {
    rank1_update<7, 8, 24>(p, acc, cx, 1);
    rank1_update<31, 0, 8>(p, acc, cx, 1);
  }
#pragma unroll
  for (int q = 0; q < 4; q++) {
    qr[q] = lds_f(sb + OFF_ROW + (32 * w + 8 * q + (lane >> 2)) * 8) * (0.17677669529663687f * 1.4426950408889634f);
    const float4 r = lds_f4(ktab + 64 * q);
    kr[1 + q][0] = r.x;
    kr[1 + q][1] = r.z;
  }
  pack_qkv<7, 1>(acc, F);
  uint32_t tg[6];
#pragma unroll
  for (int k = 0; k < 6; k++) {
    tg[k] = ~tag;
    if (t == 1)
      asm volatile("{\n.reg .b128 v;\n.reg .pred g;\nsetp.ne.u32 g, %5, 0;\nmov.b128 v, {%6, %6, %6, %6};\n"
                   "@g ld.relaxed.gpu.global.b128 v, [%4];\nmov.b128 {%0, %1, %2, %3}, v;\n}"
                   : "=r"(P[3 * k]), "=r"(P[3 * k + 1]), "=r"(P[3 * k + 2]), "=r"(tg[k])
                   : "l"(halo - 8 * 384 + k * 32 + lane), "r"((uint32_t)(w < 2 && m > 0) | ((K[0][7] | K[1][7] | K[2][7]) & p.zero)), "r"(~tag) : "memory");
  }
  pack_qkv<7, 2>(acc, F);
  pack_qkv<15, 0>(acc, F);
  bar_sync(BAR_PAIR + (w ^ 2), 64);
  if (w >= 2 || m == 0) {
#pragma unroll
    for (int k = 0; k < 4; k++) lds_u4(exc + k * 512, P[4 * k], P[4 * k + 1], P[4 * k + 2], P[4 * k + 3]);
    const float4 r = lds_f4(ktab - (w >> 1) * 320);
    P[16] = __float_as_uint(r.x);
    P[17] = __float_as_uint(r.z);
  } else {
    if ((m & 1) && t == 0) __nanosleep(HALO_NS);
#pragma unroll 1
    for (int it = 0; it < MSG_SPINS; it++) {
      if (t == 0 || it > 0) {
        if (it > 0 || !(m & 1)) poll_line(reinterpret_cast<const uint32_t*>(halo - 8 * 384 + 191) + 3, tag, 1u);
#pragma unroll
        for (int k = 0; k < 6; k++) ld_msg(halo - 8 * 384 + k * 32 + lane, P[3 * k], P[3 * k + 1], P[3 * k + 2], tg[k]);
      }
      uint32_t bad = 0;
#pragma unroll
      for (int k = 0; k < 6; k++) bad |= tg[k] ^ tag;
      if (__all_sync(0xffffffffu, bad == 0)) break;
    }
  }
  kr[0][0] = __uint_as_float(P[16]);
  kr[0][1] = __uint_as_float(P[17]);
  const bool early[2] = {2 * (lane & 3) > (lane >> 2), 2 * (lane & 3) + 1 > (lane >> 2)};
  const uint32_t mask = (early[0] ? 0xffffu : 0u) | (early[1] ? 0xffff0000u : 0u);
  float rk[2][4], sc[2][4], off[2][4];
#pragma unroll
  for (int g = 0; g < 2; g++) {
#pragma unroll
    for (int e = 0; e < 4; e++) {
      const int q = 2 * g + (e >> 1);
      const bool masked = q == 0 && m == 0 && w < 2 && early[e & 1];
      rk[g][e] = early[e & 1] ? kr[q][e & 1] : kr[q + 1][e & 1];
      sc[g][e] = masked ? 0.f : rk[g][e] * qr[q];
      off[g][e] = masked ? -1e30f : 0.f;
    }
  }
  if (w == 0 && elect_one()) asm volatile("prefetch.tensormap [%0];" ::"l"(&p.t.att_st) : "memory");
  bar_sync(BAR_GO, 256);
  const float4 zero = lds_f4(sb + OFF_ZERO);
  float l[2][2][4], o[2][2][4][4], sum[2][2][2];
#pragma unroll
  for (int h = 0; h < 2; h++) {
    if (h == 1) {
      Q[2][4] |= __float_as_uint(l[1][0][0]) & p.zero;
      Q[0][4] |= __float_as_uint(l[0][0][0]) & p.zero;
    }
    attn_scores(&Q[2][4 * h], &Q[3][4 * h], &K[1][4 * h], &K[2][4 * h], &K[3][4 * h], l[1][h], zero, early);
    attn_scores(&Q[0][4 * h], &Q[1][4 * h], &P[4 * h], &K[0][4 * h], &K[1][4 * h], l[0][h], zero, early);
  }
  const uint32_t stg = sb + OFF_STG + w * 4096, srow = stg + lane * 128 + ((lane & 7) << 4);
#pragma unroll
  for (int h = 0; h < 2; h++) {
    attn_mix(l[1][h], sc[1], off[1], rk[1], &V[1][4 * h], &V[2][4 * h], &V[3][4 * h], o[1][h], sum[1][h], mask, p.zero);
    attn_mix(l[0][h], sc[0], off[0], rk[0], &P[8 + 4 * h], &V[0][4 * h], &V[1][4 * h], o[0][h], sum[0][h], mask, p.zero);
  }
  if (t == 0 && p.zero == 0) {
    uint32_t dep = 0;
#pragma unroll
    for (int k = 0; k < 16; k++) dep |= __float_as_uint(o[k >> 3][(k >> 2) & 1][k & 3][0]);
    bar_arrive(BAR_DONE | (dep & __float_as_uint(zero.x)), 256);
  }
#pragma unroll
  for (int h = 0; h < 2; h++) {
    float inv[4];
#pragma unroll
    for (int q = 0; q < 4; q++) inv[q] = rcp_hw(quad_sum(sum[q >> 1][h][q & 1]));
#pragma unroll
    for (int j = 0; j < 4; j++) {
      const float(&a)[4] = o[0][h][j];
      const float(&c)[4] = o[1][h][j];
      stsm4(srow ^ ((4 * h + j) << 4), pack_bf16(a[0] * inv[0], a[1] * inv[0]), pack_bf16(a[2] * inv[1], a[3] * inv[1]),
            pack_bf16(c[0] * inv[2], c[1] * inv[2]), pack_bf16(c[2] * inv[3], c[3] * inv[3]));
    }
  }
  if (t == 1) bar_arrive(BAR_DONE, 256);
  fence_async_smem();
  __syncwarp();
  if (lane == 0) {
    tma_st2(&p.t.att_st, stg, 128 * n + 64 * t, 128 * m + 32 * w);
    bulk_commit();
  }
}

__device__ __forceinline__ void finish_stores(uint32_t sb, int i) {
  const int t = i >= 7 ? i - 7 : i;
  if ((threadIdx.x & 31) == 0) {
    bulk_wait_all();
    mbar_arrive(sb + BAR_PUB + 8 * (t < 2 ? t : t + 1));
  }
  __syncwarp();
  if (i < 12) bar_arrive(BAR_GUARD + ((i & 1) ^ 1), 256);
}

template <int N>
__device__ __forceinline__ bool mainloop(const Params& p, float (&acc)[2][96], uint32_t sb, int i, int step, int mn) {
  constexpr uint32_t Z16 = (2 + N / 64) * (UNIT >> 4);
  constexpr uint32_t A_OFF = Z16 - 1024 + (uint32_t)DESC_A - (uint32_t)DESC_B;
  const int wg = i & 1;
  const uint32_t s16 = (sb & 0x3FFFF) >> 4;
  const uint32_t blast = (uint32_t)DESC_B + s16 + RING16 - Z16, flast = sb + BAR_FULL + 8 * (NBAR - 1);
  uint32_t blo = (uint32_t)DESC_B + s16, alo = blo + A_OFF, aoff = A_OFF, misc = 16 << 6;
  if (N == 128 || i > 0) lds_u4(sb + OFF_RUN + (2 * i + step) * 16, blo, alo, aoff, misc);
  uint32_t keep = misc & 4;
  int run = (misc >> 6) & 63, rest = misc >> 12;
  uint32_t fb = sb + BAR_FULL + (misc & 0x38), ph = misc & 1;
  uint32_t prev = sb + BAR_DUMMY - 8 * NBAR;
  const uint32_t lane_id = __popc(__ballot_sync(0xffffffffu, true) & lanemask_lt()), rel = pair_offset(sb, lane_id & 1) + 8 * NBAR;
  pin_regs<N / 2>(acc);
  if (N == 128 || i > 0) bar_sync(BAR_ORDER + wg, 256);
  else bar_sync(BAR_INIT0, 160);
  mbar_wait(fb, ph);
  if (N == 192 && i == 0) cluster_wait();
  if (misc & 2) {
    if (N == 128) {
      const Ctx cx = make_ctx(sb, mn);
      mbar_wait(sb + BAR_XRDY, 1);
      const float2 v = row_sums(cx, 0, 8);
      sts_f2(cx.sb + OFF_HALF + (32 * cx.w + cx.lane) * 8, v.x, v.y);
      bar_arrive(BAR_STAT, 256);
    }
    mbar_wait(sb + BAR_XGO, N == 192);
  }
#pragma unroll 1
  while (true) {
    const uint64_t da = (DESC_A & ~0xffffffffull) | alo, db = (DESC_B & ~0xffffffffull) | blo;
    asm volatile("wgmma.fence.sync.aligned;" ::: "memory");
    wgmma_ss<N>(acc[0], da, db, keep);
    wgmma_ss<N>(acc[1], da + 64, db, keep);
    keep = 4;
    wgmma_ss<N>(acc[0], da + 2, db + 128);
    wgmma_ss<N>(acc[1], da + 66, db + 128);
    asm volatile("wgmma.commit_group.sync.aligned;" ::: "memory");
    asm volatile("wgmma.wait_group.sync.aligned 1;" ::: "memory");
    if (lane_id < 2) mbar_arrive_cluster(prev + rel);
    prev = fb;
    if (fb == flast) { fb -= 8 * NBAR; ph++; }
    fb += 8;
    if (blo == blast) blo -= RING16;
    blo += Z16;
    alo = blo + aoff;
    aoff = A_OFF;
    run--;
    const bool ready = mbar_test(fb, ph) && run != 0;
    asm volatile("wgmma.fence.sync.aligned;" ::: "memory");
    wgmma_ss<N>(acc[0], da + 4, db + 4 * N);
    wgmma_ss<N>(acc[1], da + 68, db + 4 * N);
    wgmma_ss<N>(acc[0], da + 6, db + 4 * N + 128);
    wgmma_ss<N>(acc[1], da + 70, db + 4 * N + 128);
    asm volatile("wgmma.commit_group.sync.aligned;" ::: "memory");
    if (!ready) {
      bool window = false;
      if (run == 0) {
        if (rest == 0) break;
        window = rest & 64;
        if (window) bar_arrive(BAR_GO, 256);
        else alo = (uint32_t)DESC_A + s16 + (OFF_STG >> 4);
        run = rest & 63;
        rest >>= 7;
      }
      mbar_wait(fb, ph);
      if (window) bar_sync(BAR_DONE, 256);
    }
  }
  if constexpr (N == 192) {
    if (misc >> 12) {
      const Ctx cx = make_ctx(sb, mn);
      uint32_t F[3][4][8];
      const uint32_t fb0 = fb, blo0 = blo;
#pragma unroll 1
      for (int x = 0; x < SKEW; x++) {
        const uint64_t da = (DESC_A & ~0xffffffffull) | (blo + A_OFF + 64), db = (DESC_B & ~0xffffffffull) | blo;
        mbar_wait(fb, ph);
        asm volatile("wgmma.fence.sync.aligned;" ::: "memory");
#pragma unroll
        for (int k = 0; k < 4; k++) wgmma_ss<N>(acc[1], da + 2 * k, db + (k >> 1) * 4 * N + (k & 1) * 128);
        asm volatile("wgmma.commit_group.sync.aligned;" ::: "memory");
        asm volatile("wgmma.wait_group.sync.aligned 1;" ::: "memory");
        if (x == 0) {
          if (lane_id < 2) mbar_arrive_cluster(prev + rel);
          bar_sync(BAR_GUARD + wg, 256);
        }
        if (fb == flast) { fb -= 8 * NBAR; ph++; }
        fb += 8;
        blo += Z16;
      }
      fb = fb0;
#pragma unroll
      for (int u = 0; u < 2 * SKEW; u++) {
        const uint64_t da = (DESC_A & ~0xffffffffull) | (blo0 + (u >> 1) * Z16 + A_OFF + 4 * (u & 1));
        const uint64_t db = (DESC_B & ~0xffffffffull) | (blo0 + (u >> 1) * Z16 + 4 * N * (u & 1));
        asm volatile("wgmma.fence.sync.aligned;" ::: "memory");
        wgmma_ss<N>(acc[0], da, db);
        wgmma_ss<N>(acc[0], da + 2, db + 128);
        asm volatile("wgmma.commit_group.sync.aligned;" ::: "memory");
        if (u == 2 * SKEW - 1) break;
        asm volatile("wgmma.wait_group.sync.aligned 1;" ::: "memory");
        if (u == 0) {
#pragma unroll
          for (int r = 0; r < 96; r++) asm volatile("" : "+f"(acc[1][r])::"memory");
        }
        if (u == 2 || u == 4) {
          if (lane_id < 2) mbar_arrive_cluster(fb + rel);
          fb = fb == flast ? fb - 8 * (NBAR - 1) : fb + 8;
        }
        if (u == 0) { if (i == 1) rank1_update<8, 8, 24>(p, acc, cx, 1); pack_qkv<8, 2>(acc, F); pack_qkv<8, 1>(acc, F); }
        if (u == 1) send_halo<0, 3>(p, F, cx, i >= 7, 1);
        if (u == 2) send_halo<3, 6>(p, F, cx, i >= 7, 1);
      }
      bar_arrive(BAR_ORDER + (wg ^ 1), 256);
      asm volatile("wgmma.wait_group.sync.aligned 0;" ::: "memory");
#pragma unroll
      for (int r = 0; r < 96; r++) asm volatile("" : "+f"(acc[0][r])::"memory");
      if (lane_id < 2) mbar_arrive_cluster(fb + rel);
      attn_epilogue<1>(p, acc, F, cx, i >= 7, lds_u(sb + OFF_TAG));
      finish_stores(sb, i);
#pragma unroll
      for (int r = 0; r < 48; r++) {
        float* d = &acc[r & 1][4 * (r >> 1)];
        asm volatile("ld.shared.v4.f32 {%0, %1, %2, %3}, [%4];" : "=f"(d[0]), "=f"(d[1]), "=f"(d[2]), "=f"(d[3]) : "r"(sb + OFF_CSQ + 16 * r));
      }
      return true;
    }
  }
  if (N == 128 && ((0x2244 >> i) & 1)) {
    const Ctx cx = make_ctx(sb, mn);
    const uint32_t xw = cx.sb + OFF_X + cx.w * 4096;
    const uint32_t xrow = xw + (cx.lane & 8) * 256 + (cx.lane & 7) * 128 + (((cx.lane & 7) ^ (cx.lane >> 4)) << 4);
    auto write_x = [&](int mb, int j) {
      stsm4((xrow ^ ((j & 7) << 4)) + (j >> 3) * 16384 + mb * 1024, pack_bf16(ACC(mb, j, 0), ACC(mb, j, 1)),
            pack_bf16(ACC(mb + 2, j, 0), ACC(mb + 2, j, 1)), pack_bf16(ACC(mb, j + 1, 0), ACC(mb, j + 1, 1)),
            pack_bf16(ACC(mb + 2, j + 1, 0), ACC(mb + 2, j + 1, 1)));
    };
    auto send_x = [&](int mb, int h) {
      fence_async_smem();
      __syncwarp();
      if (cx.lane == 0 && (h == 0 || i == 13)) {
        tma_st_warp(&p.t.out_8, xw + h * 16384 + mb * 1024, 128 * cx.n + 64 * h, cx.m, cx.w, 8 * mb);
        tma_st_warp(&p.t.out_8, xw + h * 16384 + mb * 1024 + 2048, 128 * cx.n + 64 * h, cx.m, cx.w, 8 * mb + 16);
        bulk_commit();
      }
    };
    uint32_t rb = fb, rlo = blo;
#pragma unroll 1
    for (int x = 0; x < SKEW; x++) {
      const uint64_t da = (DESC_A & ~0xffffffffull) | (blo + A_OFF), db = (DESC_B & ~0xffffffffull) | blo;
      mbar_wait(fb, ph);
      asm volatile("wgmma.fence.sync.aligned;" ::: "memory");
#pragma unroll
      for (int k = 0; k < 4; k++) wgmma_ss<N>(acc[0], da + 2 * k, db + (k >> 1) * 4 * N + (k & 1) * 128);
      asm volatile("wgmma.commit_group.sync.aligned;" ::: "memory");
      asm volatile("wgmma.wait_group.sync.aligned 1;" ::: "memory");
      if (x == 0 && lane_id < 2) mbar_arrive_cluster(prev + rel);
      if (fb == flast) { fb -= 8 * NBAR; ph++; }
      fb += 8;
      if (blo == blast) blo -= RING16;
      blo += Z16;
    }
#pragma unroll
    for (int u = 0; u < 2 * SKEW; u++) {
      const uint64_t da = (DESC_A & ~0xffffffffull) | (rlo + A_OFF + 64 + 4 * (u & 1));
      const uint64_t db = (DESC_B & ~0xffffffffull) | (rlo + 4 * N * (u & 1));
      asm volatile("wgmma.fence.sync.aligned;" ::: "memory");
      wgmma_ss<N>(acc[1], da, db);
      wgmma_ss<N>(acc[1], da + 2, db + 128);
      asm volatile("wgmma.commit_group.sync.aligned;" ::: "memory");
      if (u == 2 * SKEW - 1) break;
      asm volatile("wgmma.wait_group.sync.aligned 1;" ::: "memory");
      if (u == 0) {
#pragma unroll
        for (int r = 0; r < 64; r++) asm volatile("" : "+f"(acc[0][r])::"memory");
      }
      if (u & 1) rlo = rlo == blast ? rlo + Z16 - RING16 : rlo + Z16;
      if (u == 2 || u == 4) {
        if (lane_id < 2) mbar_arrive_cluster(rb + rel);
        rb = rb == flast ? rb - 8 * (NBAR - 1) : rb + 8;
      }
      if (u == 2) send_x(0, 0);
      else { write_x(0, 4 * (u - (u > 2))); write_x(0, 4 * (u - (u > 2)) + 2); }
    }
    if (i < 13) bar_arrive(BAR_ORDER + (wg ^ 1), 256);
    else send_x(0, 1);
    asm volatile("wgmma.wait_group.sync.aligned 0;" ::: "memory");
    pin_regs<64>(acc);
#pragma unroll
    for (int h = 0; h < 2; h++) {
      if (h == 1 && p.zero != 0) break;
#pragma unroll
      for (int j = 8 * h; j < 8 * h + 8; j += 2) write_x(1, j);
      send_x(1, h);
      if (h == 0) {
        if (cx.lane == 0) mbar_arrive(sb + BAR_XRDY);
        if (lane_id < 2 && i < 13) mbar_arrive_cluster(rb + rel);
      }
    }
    if (cx.lane == 0) {
      bulk_wait_all();
      mbar_arrive(sb + BAR_XGO);
    }
    __syncwarp();
    if (i == 2 || i == 9) {
      const float2 v = row_sums(cx, 8, 16);
      bar_sync(BAR_STAT, 256);
      const float2 o = lds_f2(cx.sb + OFF_HALF + (32 * cx.w + cx.lane) * 8);
      write_partial_stats(p, cx, (i + 3) >> 2, make_float2(v.x + o.x, v.y + o.y), lds_u(sb + OFF_TAG));
    }
    return true;
  }
  bar_arrive(BAR_ORDER + (wg ^ 1), 256);
  asm volatile("wgmma.wait_group.sync.aligned 0;" ::: "memory");
  pin_regs<N / 2>(acc);
  if (lane_id < 2) mbar_arrive_cluster(prev + rel);
  return false;
}

__device__ __forceinline__ void finish_row_stats(const Params& p, const Ctx& c, int ln, uint32_t tag) {
  const uint4* src = p.g->stats + ln * 8 * SEQ + 128 * c.m + 32 * c.w + c.lane;
  uint32_t ps[8], pm[8];
#pragma unroll 1
  for (int it = 0; it < MSG_SPINS; it++) {
    uint32_t bad = 0, u, tg;
    if (ln == 2 || it > 0) __nanosleep(STAT_NS);
#pragma unroll
    for (int k = 0; k < 8; k++) { ld_msg(src + k * SEQ, ps[k], pm[k], u, tg); bad |= tg ^ tag; }
    if (__all_sync(0xffffffffu, bad == 0)) break;
  }
  float s = 0.f, m2 = 0.f;
#pragma unroll
  for (int k = 0; k < 8; k++) s += __uint_as_float(ps[k]);
  const float mean = s * (1.f / DM);
#pragma unroll
  for (int k = 0; k < 8; k++) {
    const float d = __uint_as_float(ps[k]) * (1.f / 128.f) - mean;
    m2 += fmaf(128.f * d, d, __uint_as_float(pm[k]));
  }
  sts_f2(c.sb + OFF_ROW + (32 * c.w + c.lane) * 8, rsqrtf(m2 * (1.f / DM) + 1e-5f), mean);
  __syncwarp();
}

__device__ __forceinline__ void gelu_epilogue(const Params& p, float (&acc)[2][96], const Ctx& cx, int t) {
  UNPACK_CTX(cx);
  (void)wg;
  float rs[4], rm[4];
#pragma unroll
  for (int q = 0; q < 4; q++) {
    const float2 v = lds_f2(sb + OFF_ROW + (32 * w + 8 * q + (lane >> 2)) * 8);
    rs[q] = 0.5f * v.x;
    rm[q] = -rs[q] * v.y;
  }
  const int col0 = 128 * (t - 3);
  const uint32_t stg = sb + OFF_STG + w * 4096;
  const uint32_t ctab = sb + OFF_CSF + (col0 / 2 + (lane & 3)) * 16, srow = stg + lane * 128 + ((lane & 7) << 4);
  if (t != 4) __nanosleep((t == 5 ? STAG_NS : STAG3_NS) * w);
  float4 nb = lds_f4(ctab);
  auto chunk = [&](auto first, int cc) {
    constexpr int c = decltype(first)::value ? 0 : 1;
    uint32_t hp[8][4];
#pragma unroll
    for (int j = 0; j < 8; j++) {
      const float4 cb = nb;
      nb = lds_f4(ctab + (8 * cc + j + 1) * 64);
#pragma unroll
      for (int q = 0; q < 4; q++) {
        float y[2];
        const int k = 4 * j + q - GELU_DEP;
        const float rmq = k >= 0 ? chain(rm[q], hp[k >> 2][k & 3], p.zero) : rm[q];
#pragma unroll
        for (int e = 0; e < 2; e++) {
          const float z = fmaf(ACC(q, 8 * c + j, e), rs[q], fmaf(rmq, e ? cb.y : cb.x, e ? cb.w : cb.z));
          const float u = z * fmaf(z * z, 8.f * 0.7978845608028654f * 0.044715f, 2.f * 0.7978845608028654f);
          y[e] = fmaf(z, tanh_hw(u), z);
        }
        hp[j][q] = pack_bf16(y[0], y[1]);
      }
      if (j == STG_WAIT && c > 0) {
        if (lane == 0) bulk_wait_read();
        __syncwarp();
      }
      if (c == 0 || j > STG_WAIT) {
        stsm4(srow ^ (j << 4), hp[j][0], hp[j][1], hp[j][2], hp[j][3]);
      } else if (j == STG_WAIT) {
#pragma unroll
        for (int jj = 0; jj <= STG_WAIT; jj++) stsm4(srow ^ (jj << 4), hp[jj][0], hp[jj][1], hp[jj][2], hp[jj][3]);
      }
    }
    fence_async_smem();
    __syncwarp();
    if (lane == 0) {
      tma_st2(&p.t.h_st, stg, 448 * n + col0 + 64 * cc, 128 * m + 32 * w);
      bulk_commit();
    }
    return hp[7][3];
  };
  chunk(std::true_type{}, 0);
#pragma unroll 1
  for (int cc = 1;; cc++) {
    const uint32_t zr = chunk(std::false_type{}, cc) & p.zero;
    if (cc == 2 || t != 5) break;
#pragma unroll
    for (int r = 0; r < 64; r++)
      asm volatile("{\n.reg .b32 x;\nmov.b32 x, %1;\nor.b32 x, x, %2;\nmov.b32 %0, x;\n}"
                   : "=f"(acc[r & 1][32 + (r >> 1)]) : "f"(acc[r & 1][64 + (r >> 1)]), "r"(zr));
  }
#pragma unroll
  for (int r = 0; r < 16; r++) acc[0][r] = acc[1][r] = 0.f;
}

__device__ __forceinline__ bool consumer_tile(const Params& p, float (&acc)[2][96], uint32_t sb0, int i, int mn) {
  const int layer = i >= 7, t = i - 7 * layer, wg = i & 1;
  const bool resid = t == 2 || t == 6;
  {
    if (resid) {
      const Ctx cx = make_ctx(sb0, mn);
      const uint32_t xrow = cx.sb + OFF_X + cx.w * 4096 + cx.lane * 128;
      const uint32_t sel_lo = 0x1044u | p.zero, sel_hi = 0x3244u | p.zero;
#pragma unroll
      for (int j = 0; j < 16; j++) {
        uint32_t r[4];
        ldsm4(xrow + (j >> 3) * 16384 + (((j & 7) ^ (cx.lane & 7)) << 4), r[0], r[1], r[2], r[3]);
#pragma unroll
        for (int q = 0; q < 4; q++) {
          ACC(q, j, 0) = prmt_f(r[q], sel_lo);
          ACC(q, j, 1) = prmt_f(r[q], sel_hi);
        }
      }
    }
    if (t >= 5 || i == 7) finish_stores(sb0, i - 2);
#pragma unroll 1
    for (int step = !tile_split(i);; step++) {
      if (step == 1 && (t == 1 || t == 4)) {
        const Ctx cx = make_ctx(sb0, mn);
        if (i == 1) {
          const uint32_t epoch = __ldcg(p.g->epoch + (mn & 127));
          cluster_wait();
          asm volatile("st.shared.u32 [%0], %1;" ::"r"(sb0 + OFF_TAG), "r"(epoch + 1) : "memory");
        }
        const uint32_t tag = lds_u(cx.sb + OFF_TAG);
        const int ln = (i + 1) >> 2;
#pragma unroll 1
        for (int r = 0; r < 2; r++) {
          if (i == 1) {
            if (cx.w < 3) {
              float a[8] = {0.f, 0.f, 0.f, 0.f, 0.f, 0.f, 0.f, 0.f};
              mbar_wait(sb0 + BAR_CSLD, r);
#pragma unroll 1
              for (int h = 0; h < 2; h++) sum_rows(cx.sb + OFF_STG + h * 12288 + cx.w * 4096, 4, a, cx.lane);
              publish_sums(a, p.g->csp + (cx.n * 17 + cx.m) * 224 + (3 * r + cx.w) * 32, cx.lane, tag);
            }
          }
          if (r == 1) break;
          if (i == 1) {
            bar_sync(BAR_WG + 1, 128);
            if (cx.w == 3 && elect_one()) {
              mbar_expect_tx(sb0 + BAR_CSLD, 24576);
              tma_ld3(sb0 + OFF_STG, &p.t.wqkv, sb0 + BAR_CSLD, 128 * cx.n + 64, 64 * cx.m, 0);
              tma_ld3(sb0 + OFF_STG + 12288, &p.t.wqkv, sb0 + BAR_CSLD, 128 * cx.n + 64, 64 * cx.m + 32, 0);
            }
            mbar_wait(sb0 + BAR_XRDY, 0);
            mbar_wait(sb0 + BAR_XRDY + 8, 0);
          }
          if (t == 1) write_partial_stats(p, cx, ln, row_sums(cx, 0, 16), tag);
        }
        if (i == 1) {
          bar_arrive(BAR_HLP, 160);
          bar_sync(BAR_INIT, 160);
        }
        if (i == 4) colsum_total(p, cx, 1, tag);
        if (i != 1) bar_sync(BAR_GUARD + wg, 256);
        finish_row_stats(p, cx, ln, tag);
        if (i == 4) {
          colsum_gather(p, cx, 1, tag);
          mbar_wait(sb0 + BAR_BIAS, 0);
        }
        bar_arrive(BAR_GUARD + (wg ^ 1), 256);
      }
      if (step == 2) bar_sync(BAR_GUARD + wg, 256);
      if (step == 2 && i == 0) {
        colsum_gather(p, make_ctx(sb0, mn), 0, lds_u(sb0 + OFF_TAG));
        bar_sync(BAR_WG, 128);
      }
      if ((t + step == 2 && i != 1) || t == 6) rank1_update<15>(p, acc, make_ctx(sb0, mn), t);
      if (step == 2) break;
      if (tile_wide(t)) {
        if (mainloop<192>(p, acc, sb0, i, step, mn)) return false;
      } else {
        if (mainloop<128>(p, acc, sb0, i, step, mn)) return false;
      }
    }
    if (t < 2) return true;
    gelu_epilogue(p, acc, make_ctx(sb0, mn), t);
    return false;
  }
}

template <bool BY_SMID>
__global__ void __cluster_dims__(2, 1, 1) __launch_bounds__(384, 1)
fused_layers_kernel(const Scalars scalars, const __grid_constant__ Maps maps) {
  if (threadIdx.x == 288 || threadIdx.x == 320)
    asm volatile("prefetch.tensormap [%0];" ::"l"(threadIdx.x == 288 ? &maps.xin : &maps.wqkv) : "memory");
  const Params p{scalars, maps};
  extern __shared__ __align__(1024) uint8_t smem_raw[];
  const uint32_t sb = uniform((uint32_t)__cvta_generic_to_shared(smem_raw));
  const int tid = threadIdx.x, lane = tid & 31, warp = uniform(tid >> 5), wg = warp >> 2, w = warp & 3;

  int mn;
  {
    int id = blockIdx.x;
    if (BY_SMID) asm volatile("mov.u32 %0, %%smid;" : "=r"(id));
    else if (id >= 120) id += 4;
    const int c = id >> 1;
    int g, j;
    if (c < 32) { g = c & 7; j = c >> 3; }
    else if (c < 60) { g = 1 + (c - 32) % 7; j = 4 + (c - 32) / 7; }
    else { g = 0; j = c - 58; }
    mn = (g * 2 + (blockIdx.x & 1)) * 8 + j;
    if (c == 60 || c == 61) {
      if (tid < 32) {
        const uint32_t tag = __ldcg(p.g->epoch + NCTA + (id & 3)) + 1;
#pragma unroll 1
        for (int mm = 0; mm < 16; mm++) poll_line(p.g->flags + mm * 32 + (lane & 7), 32 * tag, 0xffu);
        if (tid == 0) p.g->epoch[NCTA + (id & 3)] = tag;
      }
      return;
    }
  }
  const int m = mn >> 3, n = mn & 7;
  if (wg < 2) {
    cluster_arrive();
    asm volatile("setmaxnreg.inc.sync.aligned.u32 232;");
    const int id = mn | (warp << 7);
#pragma unroll 1
    for (int i = wg;; i += 2) {
      float acc[2][96];
#pragma unroll
      for (int r = 0; r < 96; r++) acc[0][r] = acc[1][r] = 0.f;
      pin_regs<96>(acc);
#pragma unroll 1
      while (!consumer_tile(p, acc, sb, i, id)) {
        i += 2;
        if (i >= 14) goto all_done;
      }
      const Ctx cx = make_ctx(sb, id);
      uint32_t F[3][4][8];
      pack_qkv<8, 2>(acc, F);
      pack_qkv<8, 1>(acc, F);
      send_halo<0, 6>(p, F, cx, i >= 7, 0);
      attn_epilogue<0>(p, acc, F, cx, i >= 7, lds_u(sb + OFF_TAG));
      finish_stores(sb, i);
    }
  all_done:
    if (wg == 0) {
      finish_stores(sb, 12);
    } else {
      cluster_arrive();
      cluster_wait();
    }
  } else {
    asm volatile("setmaxnreg.dec.sync.aligned.u32 40;");
    if (w != 0) {
      if (w == 1 && elect_one()) {
        mbar_init(sb + BAR_FULL + 32, 2);
#pragma unroll
        for (int k = 0; k < NBAR; k++) mbar_init(sb + BAR_EMPTY + 8 * k, 8);
#pragma unroll
        for (int k = 0; k < 3; k++) mbar_init(sb + BAR_XRDY + 8 * k, 4);
#pragma unroll
        for (int k = 0; k < 9; k++) mbar_init(sb + BAR_PUB + 8 * k, 4);
#pragma unroll
        for (int k = 0; k < 3; k++) mbar_init(sb + BAR_CSLD + 8 * k, 1);
        mbar_init(sb + BAR_XGO, 4);
        sts_f2(sb + OFF_ZERO, 0.f, 0.f);
        sts_f2(sb + OFF_ZERO + 8, 0.f, 0.f);
        asm volatile("fence.mbarrier_init.release.cluster;" ::: "memory");
      }
      __syncwarp();
      cluster_arrive();
      if (w == 2) {
        if (lane < 28) write_run_desc(sb, lane >> 1, lane & 1);
        bar_arrive(BAR_INIT, 160);
      }
      cluster_wait();
      if (w == 1) producer<true>(p, sb, m, n, lane);
      else if (w == 3) colsum_helper(p, sb, m, n, lane);
      else if (elect_one()) publisher(p, sb, m, n);
    } else {
      const bool leader = elect_one();
      if (leader) {
#pragma unroll
        for (int k = 0; k < 4; k++) mbar_init(sb + BAR_FULL + 8 * k, 2);
        asm volatile("fence.mbarrier_init.release.cluster;" ::: "memory");
      }
      __syncwarp();
      bar_arrive(BAR_INIT0, 160);
      cluster_arrive();
      if (leader) {
#pragma unroll 1
        for (int k = 0; k < 4; k++) {
          const uint32_t fb = sb + BAR_FULL + 8 * k;
          mbar_expect_tx(fb, 16384);
          tma_ld_act(sb + (5 * k + 3) * UNIT, &p.t.xin, fb, 64 * k, m);
          mbar_expect_tx(fb, 3 * UNIT);
          tma_ld3(sb + 5 * k * UNIT, &p.t.wqkv, fb, 128 * n, 64 * k, 0);
          tma_ld3(sb + 5 * k * UNIT + 12288, &p.t.wqkv, fb, 128 * n, 64 * k + 32, 0);
        }
      }
      __syncwarp();
      cluster_wait();
      producer<false>(p, sb, m, n, lane);
    }
  }
}

typedef CUresult (*EncodeFn)(CUtensorMap*, CUtensorMapDataType, cuuint32_t, void*, const cuuint64_t*, const cuuint64_t*,
                             const cuuint32_t*, const cuuint32_t*, CUtensorMapInterleave, CUtensorMapSwizzle,
                             CUtensorMapL2promotion, CUtensorMapFloatOOBfill);

void make_2d(EncodeFn enc, CUtensorMap* m, const void* ptr, uint64_t cols, uint64_t rows, uint32_t box_rows) {
  cuuint64_t d[2] = {cols, rows}, st[1] = {cols * 2};
  cuuint32_t b[2] = {64, box_rows}, e[2] = {1, 1};
  enc(m, CU_TENSOR_MAP_DATA_TYPE_BFLOAT16, 2, const_cast<void*>(ptr), d, st, b, e, CU_TENSOR_MAP_INTERLEAVE_NONE,
      CU_TENSOR_MAP_SWIZZLE_128B, CU_TENSOR_MAP_L2_PROMOTION_L2_128B, CU_TENSOR_MAP_FLOAT_OOB_FILL_NONE);
}
void make_act(EncodeFn enc, CUtensorMap* m, const void* ptr, uint64_t cols, bool split, uint32_t box = 2, uint32_t rows = 32) {
  const uint64_t row = cols * 2;
  cuuint64_t d[4] = {cols, 32, 2, SEQ / 64}, st[3] = {split ? 2 * row : row, split ? row : 32 * row, 64 * row};
  cuuint32_t b[4] = {64, rows, box, box}, e[4] = {1, 1, 1, 1};
  enc(m, CU_TENSOR_MAP_DATA_TYPE_BFLOAT16, 4, const_cast<void*>(ptr), d, st, b, e, CU_TENSOR_MAP_INTERLEAVE_NONE,
      CU_TENSOR_MAP_SWIZZLE_128B, CU_TENSOR_MAP_L2_PROMOTION_L2_128B, CU_TENSOR_MAP_FLOAT_OOB_FILL_NONE);
}
void make_3d(EncodeFn enc, CUtensorMap* m, const void* ptr, uint64_t d0, uint64_t rows, uint64_t d2, uint64_t row_bytes,
             uint64_t chunk_bytes, uint32_t box_chunks) {
  cuuint64_t d[3] = {d0, rows, d2}, st[2] = {row_bytes, chunk_bytes};
  cuuint32_t b[3] = {64, 32, box_chunks}, e[3] = {1, 1, 1};
  enc(m, CU_TENSOR_MAP_DATA_TYPE_BFLOAT16, 3, const_cast<void*>(ptr), d, st, b, e, CU_TENSOR_MAP_INTERLEAVE_NONE,
      CU_TENSOR_MAP_SWIZZLE_128B, CU_TENSOR_MAP_L2_PROMOTION_L2_128B, CU_TENSOR_MAP_FLOAT_OOB_FILL_NONE);
}

}

extern "C" void kernel_launch(void* const* d_in, const int* in_sizes, int n_in, void* d_out, int out_size) {
  (void)in_sizes; (void)n_in; (void)out_size;
  static EncodeFn enc = nullptr;
  static void *att = nullptr, *hbuf = nullptr, *scratch = nullptr;
  static int by_smid = 0;
  if (!enc) {
    void* fn = nullptr;
    cudaDriverEntryPointQueryResult q;
    cudaGetDriverEntryPoint("cuTensorMapEncodeTiled", &fn, cudaEnableDefault, &q);
    enc = (EncodeFn)fn;
    cudaGetSymbolAddress(&att, g_att);
    cudaGetSymbolAddress(&hbuf, g_h);
    cudaGetSymbolAddress(&scratch, g_scratch);
    cudaFuncSetAttribute(fused_layers_kernel<true>, cudaFuncAttributeMaxDynamicSharedMemorySize, SMEM_BYTES);
    cudaFuncSetAttribute(fused_layers_kernel<false>, cudaFuncAttributeMaxDynamicSharedMemorySize, SMEM_BYTES);
    int sms = 0, clusters = 0, dev = 0;
    cudaGetDevice(&dev);
    cudaDeviceGetAttribute(&sms, cudaDevAttrMultiProcessorCount, dev);
    cudaLaunchConfig_t cfg = {};
    cfg.gridDim = dim3(132);
    cfg.blockDim = dim3(384);
    cfg.dynamicSmemBytes = SMEM_BYTES;
    cudaLaunchAttribute at[1];
    at[0].id = cudaLaunchAttributeClusterDimension;
    at[0].val.clusterDim.x = 2; at[0].val.clusterDim.y = 1; at[0].val.clusterDim.z = 1;
    cfg.attrs = at;
    cfg.numAttrs = 1;
    if (cudaOccupancyMaxActiveClusters(&clusters, fused_layers_kernel<true>, &cfg) != cudaSuccess) (void)cudaGetLastError();
    by_smid = sms == 132 && clusters == 66;
  }
  Maps p;
  Scalars sc;
  make_act(enc, &p.xin, d_in[0], DM, true);
  make_act(enc, &p.out, d_out, DM, true);
  make_act(enc, &p.out_w, d_out, DM, true, 1);
  make_act(enc, &p.out_8, d_out, DM, true, 1, 8);
  make_act(enc, &p.att, att, DM, false);
  make_act(enc, &p.h, hbuf, FF, false);
  make_2d(enc, &p.att_st, att, DM, SEQ, 32);
  make_2d(enc, &p.h_st, hbuf, FF, SEQ, 32);
  make_2d(enc, &p.w1c, d_in[4], FF, DM, 32);
  make_3d(enc, &p.wqkv, d_in[1], DM, DM, 3, 3 * DM * 2, DM * 2, 3);
  make_3d(enc, &p.wo, d_in[2], 64, DM, DM / 64, DM * 2, 128, 2);
  make_3d(enc, &p.w1a, d_in[4], 64, DM, FF / 64, FF * 2, 128, 3);
  make_3d(enc, &p.w1b, d_in[4], 64, DM, FF / 64, FF * 2, 128, 2);
  make_3d(enc, &p.w2, d_in[6], 64, FF, DM / 64, DM * 2, 128, 2);
  sc.b1 = (const __nv_bfloat16*)d_in[5];
  sc.b2 = (const __nv_bfloat16*)d_in[7];
  sc.g = (Scratch*)scratch;
  sc.zero = 0;
  if (by_smid) fused_layers_kernel<true><<<132, 384, SMEM_BYTES>>>(sc, p);
  else fused_layers_kernel<false><<<NCTA, 384, SMEM_BYTES>>>(sc, p);
}
```

```cpp
#include <cuda_runtime.h>
#include <cuda_bf16.h>
#include <cuda.h>
#include <stdint.h>
#include <type_traits>

namespace {

constexpr int SEQ = 2048, DM = 1024, FF = 3584;
constexpr int NCTA = 128;
constexpr int NBAR = 5;

constexpr uint32_t RING_UNITS = 20, UNIT = 8192;
constexpr uint32_t OFF_X   = RING_UNITS * UNIT;
constexpr uint32_t OFF_STG = OFF_X + 32768;
constexpr uint32_t OFF_HLP = OFF_STG + 16384;
constexpr uint32_t OFF_RUN = OFF_STG + 24576;
constexpr uint32_t OFF_CSQ = OFF_RUN + 512;
constexpr uint32_t OFF_CSF = OFF_CSQ + 2048;
constexpr uint32_t OFF_ROW = OFF_CSF + 3584;
constexpr uint32_t OFF_HALF = OFF_ROW + 1024;
constexpr uint32_t OFF_BAR = OFF_HALF + 1024;
constexpr uint32_t SMEM_BYTES = OFF_BAR + 384;
constexpr uint32_t BAR_FULL = OFF_BAR, BAR_EMPTY = OFF_BAR + 8 * NBAR;
constexpr uint32_t BAR_XRDY = OFF_BAR + 80;
constexpr uint32_t BAR_DUMMY = OFF_BAR + 96, OFF_TAG = OFF_BAR + 104, OFF_ZERO = OFF_BAR + 112;
constexpr uint32_t BAR_PUB = OFF_BAR + 128;
constexpr uint32_t BAR_CSLD = OFF_BAR + 200;
constexpr uint32_t BAR_BIAS = OFF_BAR + 216;
constexpr uint32_t BAR_XGO = OFF_BAR + 224;

constexpr uint64_t DESC_A = (1ull << 62) | ((uint64_t)(2048 >> 4) << 32) | (1ull << 16);
constexpr uint64_t DESC_B = (1ull << 62) | ((uint64_t)(1024 >> 4) << 32) | ((uint64_t)(4096 >> 4) << 16);

constexpr int BAR_INIT = 0, BAR_ORDER = 1, BAR_GUARD = 3, BAR_WG = 5, BAR_GO = 7, BAR_DONE = 8, BAR_HLP = 9;
constexpr int BAR_INIT0 = 10, BAR_PAIR = 11, BAR_STAT = 15;

constexpr int WIN1 = 5;
constexpr int WIN0 = 7;
constexpr int SKEW = 3;
static_assert(SKEW == 3, "the slices of the skewed tails assume three k-blocks");
constexpr int WIN2 = 1;
constexpr int GELU_DEP = 2;
constexpr int STG_WAIT = 5;
constexpr int HALO_NS = 200;
constexpr int STAT_NS = 800;
constexpr int CS_NS = 500;
constexpr int XB_NS = 400;
constexpr int XB_GAP_NS = 50;
constexpr int STAG_NS = 450;
constexpr int STAG3_NS = 100;
constexpr int PACE_M = 100;
constexpr int PACE_N = 300;

struct Scratch {
  uint4 stats[4 * 8 * SEQ];
  uint4 halo[2 * 2 * 16 * 8 * 384];
  uint4 csp[2 * 8 * 17 * 224];
  uint32_t flags[16 * 32];
  uint32_t epoch[NCTA + 4];
};

struct Maps {
  CUtensorMap xin, out, att, h, wqkv, wo, w1a, w1b, w2, att_st, h_st, w1c, out_w, out_8;
};
struct Scalars {
  Scratch* g;
  const __nv_bfloat16 *b1, *b2;
  uint32_t zero;
};
struct Params : Scalars {
  const Maps& t;
};

__device__ __align__(1024) __nv_bfloat16 g_att[SEQ * DM];
__device__ __align__(1024) __nv_bfloat16 g_h[SEQ * FF];
__device__ __align__(1024) Scratch g_scratch;

__device__ __forceinline__ void mbar_init(uint32_t bar, int cnt) {
  asm volatile("mbarrier.init.shared::cta.b64 [%0], %1;" ::"r"(bar), "r"(cnt));
}
__device__ __forceinline__ void mbar_expect_tx(uint32_t bar, uint32_t bytes) {
  asm volatile("mbarrier.arrive.expect_tx.shared::cta.b64 _, [%0], %1;" ::"r"(bar), "r"(bytes) : "memory");
}
__device__ __forceinline__ void mbar_arrive(uint32_t bar) {
  asm volatile("mbarrier.arrive.shared::cta.b64 _, [%0];" ::"r"(bar) : "memory");
}
__device__ __forceinline__ bool mbar_test(uint32_t bar, uint32_t parity) {
  uint32_t ok;
  asm volatile("{\n.reg .pred p;\nmbarrier.test_wait.parity.shared::cta.b64 p, [%1], %2;\nselp.u32 %0, 1, 0, p;\n}"
               : "=r"(ok) : "r"(bar), "r"(parity) : "memory");
  return ok;
}
__device__ __forceinline__ void mbar_wait(uint32_t bar, uint32_t parity) {
  asm volatile(
      "{\n.reg .pred p;\n.reg .u32 it;\nmov.u32 it, 0;\n"
      "WAIT_LOOP:\n"
      "mbarrier.try_wait.parity.shared::cta.b64 p, [%0], %1;\n"
      "@p bra WAIT_DONE;\n"
      "add.u32 it, it, 1;\n"
      "setp.lt.u32 p, it, 0x400000;\n"
      "@p bra WAIT_LOOP;\n"
      "trap;\n"
      "WAIT_DONE:\n}"
      ::"r"(bar), "r"(parity) : "memory");
}
__device__ __forceinline__ void bar_sync(int id, int n) { asm volatile("bar.sync %0, %1;" ::"r"(id), "r"(n) : "memory"); }
__device__ __forceinline__ void bar_arrive(int id, int n) { asm volatile("bar.arrive %0, %1;" ::"r"(id), "r"(n) : "memory"); }
__device__ __forceinline__ void tma_ld2(uint32_t dst, const CUtensorMap* m, uint32_t bar, int c0, int c1) {
  asm volatile("cp.async.bulk.tensor.2d.shared::cluster.global.mbarrier::complete_tx::bytes [%0], [%1, {%3, %4}], [%2];"
               ::"r"(dst), "l"(m), "r"(bar), "r"(c0), "r"(c1) : "memory");
}
__device__ __forceinline__ void tma_ld_act(uint32_t dst, const CUtensorMap* m, uint32_t bar, int col, int blk) {
  asm volatile("cp.async.bulk.tensor.4d.shared::cluster.global.mbarrier::complete_tx::bytes [%0], [%1, {%3, %5, %5, %4}], [%2];"
               ::"r"(dst), "l"(m), "r"(bar), "r"(col), "r"(2 * blk), "r"(0) : "memory");
}
__device__ __forceinline__ void tma_st_warp(const CUtensorMap* m, uint32_t src, int col, int blk, int w, int row = 0) {
  asm volatile("cp.async.bulk.tensor.4d.global.shared::cta.bulk_group [%0, {%2, %5, %3, %4}], [%1];"
               ::"l"(m), "r"(src), "r"(col), "r"(w & 1), "r"(2 * blk + (w >> 1)), "r"(row) : "memory");
}
__device__ __forceinline__ void tma_ld3(uint32_t dst, const CUtensorMap* m, uint32_t bar, int c0, int c1, int c2) {
  asm volatile("cp.async.bulk.tensor.3d.shared::cluster.global.mbarrier::complete_tx::bytes [%0], [%1, {%3, %4, %5}], [%2];"
               ::"r"(dst), "l"(m), "r"(bar), "r"(c0), "r"(c1), "r"(c2) : "memory");
}
__device__ __forceinline__ void tma_ld3_pair(uint32_t dst, const CUtensorMap* m, uint32_t bar, int c0, int c1, int c2) {
  asm volatile("cp.async.bulk.tensor.3d.shared::cluster.global.mbarrier::complete_tx::bytes.multicast::cluster"
               " [%0], [%1, {%3, %4, %5}], [%2], %6;"
               ::"r"(dst), "l"(m), "r"(bar), "r"(c0), "r"(c1), "r"(c2), "h"((uint16_t)3) : "memory");
}
__device__ __forceinline__ uint32_t pair_offset(uint32_t sb, uint32_t rank) {
  uint32_t r;
  asm volatile("mapa.shared::cluster.u32 %0, %1, %2;" : "=r"(r) : "r"(sb), "r"(rank));
  return r - sb;
}
__device__ __forceinline__ void mbar_arrive_cluster(uint32_t bar) {
  asm volatile("mbarrier.arrive.shared::cluster.b64 _, [%0];" ::"r"(bar) : "memory");
}
__device__ __forceinline__ void cluster_arrive() { asm volatile("barrier.cluster.arrive.relaxed;" ::: "memory"); }
__device__ __forceinline__ void cluster_wait() { asm volatile("barrier.cluster.wait.acquire;" ::: "memory"); }
__device__ __forceinline__ void tma_st2(const CUtensorMap* m, uint32_t src, int c0, int c1) {
  asm volatile("cp.async.bulk.tensor.2d.global.shared::cta.bulk_group [%0, {%2, %3}], [%1];"
               ::"l"(m), "r"(src), "r"(c0), "r"(c1) : "memory");
}
__device__ __forceinline__ void bulk_commit() { asm volatile("cp.async.bulk.commit_group;" ::: "memory"); }
__device__ __forceinline__ void bulk_wait_read() { asm volatile("cp.async.bulk.wait_group.read 0;" ::: "memory"); }
__device__ __forceinline__ void bulk_wait_all() { asm volatile("cp.async.bulk.wait_group 0;" ::: "memory"); }
__device__ __forceinline__ void fence_async_smem() { asm volatile("fence.proxy.async.shared::cta;" ::: "memory"); }
__device__ __forceinline__ void fence_async_global() { asm volatile("fence.proxy.async.global;" ::: "memory"); }
__device__ __forceinline__ void st_relaxed(uint32_t* p, uint32_t v) {
  asm volatile("st.relaxed.gpu.global.u32 [%0], %1;" ::"l"(p), "r"(v) : "memory");
}
__device__ __forceinline__ void st_msg(uint4* p, uint32_t a, uint32_t b, uint32_t c, uint32_t tag) {
  asm volatile("{\n.reg .b128 v;\nmov.b128 v, {%1, %2, %3, %4};\nst.relaxed.gpu.global.b128 [%0], v;\n}"
               ::"l"(p), "r"(a), "r"(b), "r"(c), "r"(tag) : "memory");
}
__device__ __forceinline__ void ld_msg(const uint4* p, uint32_t& a, uint32_t& b, uint32_t& c, uint32_t& tag) {
  asm volatile("{\n.reg .b128 v;\nld.relaxed.gpu.global.b128 v, [%4];\nmov.b128 {%0, %1, %2, %3}, v;\n}"
               : "=r"(a), "=r"(b), "=r"(c), "=r"(tag) : "l"(p) : "memory");
}
__device__ __forceinline__ bool elect_one() {
  uint32_t ok;
  asm volatile("{\n.reg .pred p;\nelect.sync _|p, 0xffffffff;\nselp.u32 %0, 1, 0, p;\n}" : "=r"(ok));
  return ok;
}
__device__ __forceinline__ uint32_t lanemask_lt() {
  uint32_t v;
  asm("mov.u32 %0, %%lanemask_lt;" : "=r"(v));
  return v;
}
__device__ __forceinline__ int uniform(int v) { return __shfl_sync(0xffffffffu, v, 0); }
__device__ __forceinline__ uint32_t pack_bf16(float lo, float hi) {
  uint32_t r;
  asm("cvt.rn.bf16x2.f32 %0, %1, %2;" : "=r"(r) : "f"(hi), "f"(lo));
  return r;
}
__device__ __forceinline__ float prmt_f(uint32_t a, uint32_t sel) {
  float r;
  asm("{\n.reg .b32 t;\nprmt.b32 t, %1, 0, %2;\nmov.b32 %0, t;\n}" : "=f"(r) : "r"(a), "r"(sel));
  return r;
}
__device__ __forceinline__ float bf_lo(uint32_t v) { return __uint_as_float(v << 16); }
__device__ __forceinline__ float bf_hi(uint32_t v) { return __uint_as_float(v & 0xffff0000u); }
__device__ __forceinline__ void stsm4(uint32_t addr, uint32_t r0, uint32_t r1, uint32_t r2, uint32_t r3) {
  asm volatile("stmatrix.sync.aligned.m8n8.x4.shared.b16 [%0], {%1, %2, %3, %4};"
               ::"r"(addr), "r"(r0), "r"(r1), "r"(r2), "r"(r3) : "memory");
}
__device__ __forceinline__ void ldsm4(uint32_t addr, uint32_t& r0, uint32_t& r1, uint32_t& r2, uint32_t& r3) {
  asm volatile("ldmatrix.sync.aligned.m8n8.x4.shared.b16 {%0, %1, %2, %3}, [%4];"
               : "=r"(r0), "=r"(r1), "=r"(r2), "=r"(r3) : "r"(addr) : "memory");
}
__device__ __forceinline__ uint32_t movtrans(uint32_t a) {
  uint32_t d;
  asm volatile("movmatrix.sync.aligned.m8n8.trans.b16 %0, %1;" : "=r"(d) : "r"(a));
  return d;
}
__device__ __forceinline__ void mma16816(float (&c)[4], uint32_t a0, uint32_t a1, uint32_t a2, uint32_t a3, uint32_t b0, uint32_t b1) {
  asm volatile("mma.sync.aligned.m16n8k16.row.col.f32.bf16.bf16.f32 {%0,%1,%2,%3}, {%4,%5,%6,%7}, {%8,%9}, {%0,%1,%2,%3};"
               : "+f"(c[0]), "+f"(c[1]), "+f"(c[2]), "+f"(c[3])
               : "r"(a0), "r"(a1), "r"(a2), "r"(a3), "r"(b0), "r"(b1));
}
__device__ __forceinline__ void mma1688(float (&c)[4], uint32_t a0, uint32_t a1, uint32_t b0) {
  asm volatile("mma.sync.aligned.m16n8k8.row.col.f32.bf16.bf16.f32 {%0,%1,%2,%3}, {%4,%5}, {%6}, {%0,%1,%2,%3};"
               : "+f"(c[0]), "+f"(c[1]), "+f"(c[2]), "+f"(c[3]) : "r"(a0), "r"(a1), "r"(b0));
}
__device__ __forceinline__ float2 lds_f2(uint32_t a) {
  float2 v;
  asm volatile("ld.shared.v2.f32 {%0, %1}, [%2];" : "=f"(v.x), "=f"(v.y) : "r"(a) : "memory");
  return v;
}
__device__ __forceinline__ float4 lds_f4(uint32_t a) {
  float4 v;
  asm volatile("ld.shared.v4.f32 {%0, %1, %2, %3}, [%4];" : "=f"(v.x), "=f"(v.y), "=f"(v.z), "=f"(v.w) : "r"(a) : "memory");
  return v;
}
__device__ __forceinline__ float lds_f(uint32_t a) {
  float v;
  asm volatile("ld.shared.f32 %0, [%1];" : "=f"(v) : "r"(a) : "memory");
  return v;
}
__device__ __forceinline__ uint32_t lds_u(uint32_t a) {
  uint32_t v;
  asm volatile("ld.shared.u32 %0, [%1];" : "=r"(v) : "r"(a) : "memory");
  return v;
}
__device__ __forceinline__ void sts_f2(uint32_t a, float x, float y) {
  asm volatile("st.shared.v2.f32 [%0], {%1, %2};" ::"r"(a), "f"(x), "f"(y) : "memory");
}
__device__ __forceinline__ void sts_u4(uint32_t a, uint32_t x, uint32_t y, uint32_t z, uint32_t w) {
  asm volatile("st.shared.v4.u32 [%0], {%1, %2, %3, %4};" ::"r"(a), "r"(x), "r"(y), "r"(z), "r"(w) : "memory");
}
__device__ __forceinline__ void lds_u4(uint32_t a, uint32_t& x, uint32_t& y, uint32_t& z, uint32_t& w) {
  asm volatile("ld.shared.v4.u32 {%0, %1, %2, %3}, [%4];" : "=r"(x), "=r"(y), "=r"(z), "=r"(w) : "r"(a) : "memory");
}
__device__ __forceinline__ float ex2(float x) {
  float y;
  asm("ex2.approx.ftz.f32 %0, %1;" : "=f"(y) : "f"(x));
  return y;
}
__device__ __forceinline__ float rcp_hw(float x) {
  float y;
  asm("rcp.approx.ftz.f32 %0, %1;" : "=f"(y) : "f"(x));
  return y;
}
__device__ __forceinline__ float tanh_hw(float x) {
  float y;
  asm("tanh.approx.f32 %0, %1;" : "=f"(y) : "f"(x));
  return y;
}
__device__ __forceinline__ float quad_sum(float v) {
  v += __shfl_xor_sync(0xffffffffu, v, 1);
  return v + __shfl_xor_sync(0xffffffffu, v, 2);
}
__device__ __forceinline__ float quad_max(float v) {
  v = fmaxf(v, __shfl_xor_sync(0xffffffffu, v, 1));
  return fmaxf(v, __shfl_xor_sync(0xffffffffu, v, 2));
}

template <int N> __device__ __forceinline__ void wgmma_ss(float (&d)[96], uint64_t da, uint64_t db, uint32_t keep = 1);
template <> __device__ __forceinline__ void wgmma_ss<128>(float (&d)[96], uint64_t da, uint64_t db, uint32_t keep) {
  asm volatile(
      "{\n.reg .pred p;\nsetp.ne.u32 p, %66, 0;\n"
      "wgmma.mma_async.sync.aligned.m64n128k16.f32.bf16.bf16 {%0, %1, %2, %3, %4, %5, %6, %7, %8, %9, %10, %11, %12, %13, %14, %15, %16, %17, %18, %19, %20, %21, %22, %23, %24, %25, %26, %27, %28, %29, %30, %31, %32, %33, %34, %35, %36, %37, %38, %39, %40, %41, %42, %43, %44, %45, %46, %47, %48, %49, %50, %51, %52, %53, %54, %55, %56, %57, %58, %59, %60, %61, %62, %63}, %64, %65, p, 1, 1, 0, 1;\n}"
      : "+f"(d[0]), "+f"(d[1]), "+f"(d[2]), "+f"(d[3]), "+f"(d[4]), "+f"(d[5]), "+f"(d[6]), "+f"(d[7]), "+f"(d[8]), "+f"(d[9]), "+f"(d[10]), "+f"(d[11]), "+f"(d[12]), "+f"(d[13]), "+f"(d[14]), "+f"(d[15]), "+f"(d[16]), "+f"(d[17]), "+f"(d[18]), "+f"(d[19]), "+f"(d[20]), "+f"(d[21]), "+f"(d[22]), "+f"(d[23]), "+f"(d[24]), "+f"(d[25]), "+f"(d[26]), "+f"(d[27]), "+f"(d[28]), "+f"(d[29]), "+f"(d[30]), "+f"(d[31]), "+f"(d[32]), "+f"(d[33]), "+f"(d[34]), "+f"(d[35]), "+f"(d[36]), "+f"(d[37]), "+f"(d[38]), "+f"(d[39]), "+f"(d[40]), "+f"(d[41]), "+f"(d[42]), "+f"(d[43]), "+f"(d[44]), "+f"(d[45]), "+f"(d[46]), "+f"(d[47]), "+f"(d[48]), "+f"(d[49]), "+f"(d[50]), "+f"(d[51]), "+f"(d[52]), "+f"(d[53]), "+f"(d[54]), "+f"(d[55]), "+f"(d[56]), "+f"(d[57]), "+f"(d[58]), "+f"(d[59]), "+f"(d[60]), "+f"(d[61]), "+f"(d[62]), "+f"(d[63])
      : "l"(da), "l"(db), "r"(keep));
}

template <> __device__ __forceinline__ void wgmma_ss<192>(float (&d)[96], uint64_t da, uint64_t db, uint32_t keep) {
  asm volatile(
      "{\n.reg .pred p;\nsetp.ne.u32 p, %98, 0;\n"
      "wgmma.mma_async.sync.aligned.m64n192k16.f32.bf16.bf16 {%0, %1, %2, %3, %4, %5, %6, %7, %8, %9, %10, %11, %12, %13, %14, %15, %16, %17, %18, %19, %20, %21, %22, %23, %24, %25, %26, %27, %28, %29, %30, %31, %32, %33, %34, %35, %36, %37, %38, %39, %40, %41, %42, %43, %44, %45, %46, %47, %48, %49, %50, %51, %52, %53, %54, %55, %56, %57, %58, %59, %60, %61, %62, %63, %64, %65, %66, %67, %68, %69, %70, %71, %72, %73, %74, %75, %76, %77, %78, %79, %80, %81, %82, %83, %84, %85, %86, %87, %88, %89, %90, %91, %92, %93, %94, %95}, %96, %97, p, 1, 1, 0, 1;\n}"
      : "+f"(d[0]), "+f"(d[1]), "+f"(d[2]), "+f"(d[3]), "+f"(d[4]), "+f"(d[5]), "+f"(d[6]), "+f"(d[7]), "+f"(d[8]), "+f"(d[9]), "+f"(d[10]), "+f"(d[11]), "+f"(d[12]), "+f"(d[13]), "+f"(d[14]), "+f"(d[15]), "+f"(d[16]), "+f"(d[17]), "+f"(d[18]), "+f"(d[19]), "+f"(d[20]), "+f"(d[21]), "+f"(d[22]), "+f"(d[23]), "+f"(d[24]), "+f"(d[25]), "+f"(d[26]), "+f"(d[27]), "+f"(d[28]), "+f"(d[29]), "+f"(d[30]), "+f"(d[31]), "+f"(d[32]), "+f"(d[33]), "+f"(d[34]), "+f"(d[35]), "+f"(d[36]), "+f"(d[37]), "+f"(d[38]), "+f"(d[39]), "+f"(d[40]), "+f"(d[41]), "+f"(d[42]), "+f"(d[43]), "+f"(d[44]), "+f"(d[45]), "+f"(d[46]), "+f"(d[47]), "+f"(d[48]), "+f"(d[49]), "+f"(d[50]), "+f"(d[51]), "+f"(d[52]), "+f"(d[53]), "+f"(d[54]), "+f"(d[55]), "+f"(d[56]), "+f"(d[57]), "+f"(d[58]), "+f"(d[59]), "+f"(d[60]), "+f"(d[61]), "+f"(d[62]), "+f"(d[63]), "+f"(d[64]), "+f"(d[65]), "+f"(d[66]), "+f"(d[67]), "+f"(d[68]), "+f"(d[69]), "+f"(d[70]), "+f"(d[71]), "+f"(d[72]), "+f"(d[73]), "+f"(d[74]), "+f"(d[75]), "+f"(d[76]), "+f"(d[77]), "+f"(d[78]), "+f"(d[79]), "+f"(d[80]), "+f"(d[81]), "+f"(d[82]), "+f"(d[83]), "+f"(d[84]), "+f"(d[85]), "+f"(d[86]), "+f"(d[87]), "+f"(d[88]), "+f"(d[89]), "+f"(d[90]), "+f"(d[91]), "+f"(d[92]), "+f"(d[93]), "+f"(d[94]), "+f"(d[95])
      : "l"(da), "l"(db), "r"(keep));
}

template <int R>
__device__ __forceinline__ void pin_regs(float (&a)[2][96]) {
#pragma unroll
  for (int m = 0; m < 2; m++)
#pragma unroll
    for (int i = 0; i < R; i++) asm volatile("" : "+f"(a[m][i])::"memory");
}

struct Ctx {
  uint32_t sb;
  int m, n, wg, w, lane;
};
__device__ __forceinline__ Ctx make_ctx(uint32_t sb, int id) {
  int lane;
  asm volatile("mov.u32 %0, %%laneid;" : "=r"(lane));
  asm volatile("" : "+r"(id), "+r"(sb));
  return Ctx{sb, (id >> 3) & 15, id & 7, id >> 9, (id >> 7) & 3, lane};
}
#define UNPACK_CTX(c) const uint32_t sb = c.sb; const int m = c.m, n = c.n, wg = c.wg, w = c.w, lane = c.lane

__device__ __forceinline__ uint32_t poll_line(const uint32_t* word, uint32_t target, uint32_t need) {
  uint32_t v;
  asm volatile(
      "{\n.reg .pred p;\n.reg .u32 it, m;\n.reg .s32 d;\nmov.u32 it, 0;\n"
      "POLL_LOOP:\n"
      "ld.relaxed.gpu.global.u32 %0, [%1];\n"
      "sub.s32 d, %0, %2;\n"
      "setp.ge.s32 p, d, 0;\n"
      "vote.sync.ballot.b32 m, p, 0xffffffff;\n"
      "and.b32 m, m, %3;\n"
      "setp.eq.u32 p, m, %3;\n"
      "@p bra.uni POLL_DONE;\n"
      "add.u32 it, it, 1;\n"
      "setp.lt.u32 p, it, 0x400000;\n"
      "@p bra.uni POLL_LOOP;\n"
      "trap;\n"
      "POLL_DONE:\n}"
      : "=&r"(v) : "l"(word), "r"(target), "r"(need) : "memory");
  return v;
}
__device__ __forceinline__ uint32_t ld_relaxed(const uint32_t* p) {
  uint32_t v;
  asm volatile("ld.relaxed.gpu.global.u32 %0, [%1];" : "=r"(v) : "l"(p) : "memory");
  return v;
}
__device__ __forceinline__ float chain(float x, uint32_t on, uint32_t zero) {
  return __uint_as_float(__float_as_uint(x) | (on & zero));
}
constexpr int MSG_SPINS = 1 << 20;

constexpr int STAGES_PER_LAYER = 152;
__device__ __forceinline__ int nib(uint64_t v, int i) { return (int)(v >> (4 * i)) & 15; }
__device__ __forceinline__ bool tile_wide(int t) { return (0x23 >> t) & 1; }
__device__ __forceinline__ void weight_coords(const Params& p, int t, int n, const CUtensorMap*& map, int& c0, int& c2) {
  map = &p.t.wqkv + nib(0x4233100ull, t);
  c0 = t < 2 ? 128 * n + 64 * t : 0;
  c2 = t < 2 ? 0 : (t == 2 || t == 6) ? 2 * n : 7 * n + 2 * t - 6;
}

template <bool IS_A>
__device__ __forceinline__ void producer(const Params& p, uint32_t sb, int m, int n, int lane) {
  const uint32_t low = (1u << (4 * n)) - 1, others = (0x6543210u & low) | (0x7654321u & ~low);
  const uint64_t order_x = (uint64_t)(others * 2 + 0x1111111u) << 36 | (uint64_t)others * 2 << 8 | (n * 0x22 + 0x10);
  int inflight = 4, cur = 0;
  uint32_t fb = sb + BAR_FULL + 32, rb = sb + BAR_EMPTY, rph = 0, pos = 0, tag32 = 0, seen = 0;
  const uint32_t fend = sb + BAR_FULL + 8 * NBAR, rend = sb + BAR_EMPTY + 8 * NBAR;
  const uint32_t* word = p.g->flags + m * 32 + (lane < 16 ? lane >> 1 : lane & 7);
#pragma unroll 1
  for (int sg = 1; sg < 22; sg++) {
    const int layer = sg >= 11, s = sg == 1 ? 2 : sg == 2 ? 1 : sg - 11 * layer;
    const int t = nib(0x65434321010ull, s), kind = nib(0x32110031100ull, s);
    const bool wide = tile_wide(t);
    const uint32_t bbytes = wide ? 3 * UNIT : 2 * UNIT, base = sb + (IS_A ? bbytes : (m & 1) * (bbytes / 2));
    if (IS_A && kind == 0) {
      if (sg == 2) seen = tag32 = (__ldcg(p.g->epoch + m * 8 + n) + 1) << 5;
#pragma unroll 1
      for (int k = 0; k < 2; k++) {
#pragma unroll 1
        for (; inflight > (wide ? 3 : 4); inflight--) {
          mbar_wait(rb, rph);
          rb += 8;
          if (rb == rend) { rb -= 8 * NBAR; rph ^= 1; }
        }
        if (elect_one()) mbar_arrive(fb);
        inflight++;
        fb += 8;
        if (fb == fend) fb -= 8 * NBAR;
        pos += bbytes + 2 * UNIT;
        if (pos >= RING_UNITS * UNIT) pos -= RING_UNITS * UNIT;
      }
      continue;
    }
    const int mul = t == 6 ? 448 : t == 2 ? 128 : 64, count = sg == 1 ? 12 : 2 * nib(0x4871ull, kind);
    uint64_t order0 = sg == 1 ? 0xFEDCBA987654ull : kind == 3 ? 0x76543210u : order_x >> (8 * (kind & 1));
    uint32_t special = (s == 4 || s == 10) ? 0x10 : s == 9 ? 0xF : s == 0;
    if (IS_A) special |= (kind & 1 ? 0 : 3) | (count >= 4 ? 1u << (count - 4) : 0);
    if (s >= 9) pos = (s + 6) * UNIT;
    const CUtensorMap* map;
    int c0 = 0, c2 = 0, ev = 0;
    if (IS_A) {
      map = &p.t.xin + (t == 2 ? 2 : t == 6 ? 3 : sg >= 4);
      ev = 9 * layer + (t < 2 ? 0 : t == 2 ? 1 : t < 6 ? 4 : 5);
      if (elect_one()) asm volatile("prefetch.tensormap [%0];" ::"l"(map) : "memory");
    } else {
      weight_coords(p, t, n, map, c0, c2);
    }
#pragma unroll 1
    for (int add = 0; add < mul; add += 64) {
      uint64_t order = order0;
      const int need = kind == 3 ? ev : ev - 1 + (lane & 1), sh = kind == 3 ? 16 : 0;
      uint32_t ready = IS_A ? __ballot_sync(0xffffffffu, cur >= need) >> sh : 0;
#pragma unroll 1
      for (int k = 0; k < count; k++) {
        const int code = order & 15, kc = code * mul + add;
        order >>= 4;
        if ((special >> k) & 1) {
          const int lag = wide ? (s == 9 && k == 2 ? 2 : 3) : ((s == 4 || s == 10) && add == 0 && k < 4) ? 3 : 4;
#pragma unroll 1
          for (; inflight > lag; inflight--) {
            mbar_wait(rb, rph);
            rb += 8;
            if (rb == rend) { rb -= 8 * NBAR; rph ^= 1; }
          }
          inflight++;
          if (IS_A) {
            if (kind == 3 ? t == 2 && add + k == 64 : !(kind & 1) && k < 2) {
              if (t == 2) mbar_wait(sb + BAR_PUB + 8, layer);
              if (elect_one()) mbar_arrive(fb);
              goto next_stage;
            }
            if (k == count - 4 && sg >= 3) seen = ld_relaxed(word);
          }
        } else {
          mbar_wait(rb, rph);
          rb += 8;
          if (rb == rend) { rb -= 8 * NBAR; rph ^= 1; }
        }
        if (IS_A && !((ready >> code) & 1)) {
          cur = max(cur, (int)(seen - tag32));
          ready = __ballot_sync(0xffffffffu, cur >= need) >> sh;
          if (!((ready >> code) & 1)) {
            cur = (int)(poll_line(word, tag32 + need, 1u << (code + sh)) - tag32);
            ready = __ballot_sync(0xffffffffu, cur >= need) >> sh;
          }
          asm volatile("fence.acquire.gpu;" ::: "memory");
          fence_async_global();
          seen = ld_relaxed(word);
        }
        if (elect_one()) {
          if (!IS_A) tma_ld3_pair(base + pos, map, fb, c0, kc + 32 * (m & 1), c2);
          else tma_ld_act(base + pos, map, fb, kc, m);
          mbar_expect_tx(fb, IS_A ? 16384 : bbytes);
        }
      next_stage:
        fb += 8;
        if (fb == fend) fb -= 8 * NBAR;
        pos += bbytes + 2 * UNIT;
        if (pos >= RING_UNITS * UNIT) pos -= RING_UNITS * UNIT;
      }
      special = !IS_A ? 0 : t == 2 ? 1 : add == 128 ? 0x10 : 0;
      if (t == 2) order0 = others << 4 | n;
      if (IS_A && (t == 2 || add == 64 || add == 192)) ev++;
    }
  }
}

__device__ __forceinline__ void publisher(const Params& p, uint32_t sb, int m, int n) {
  {
    const int ts = PACE_M * m, tx = PACE_N * n;
#pragma unroll 1
    for (int k = 0; k < 2; k++) {
      __nanosleep(k == 0 ? min(ts, tx) : abs(ts - tx));
      if ((ts <= tx) == (k == 0)) {
        mbar_expect_tx(sb + BAR_CSLD, 24576);
        tma_ld3(sb + OFF_STG, &p.t.wqkv, sb + BAR_CSLD, 128 * n, 64 * m, 0);
        tma_ld3(sb + OFF_STG + 12288, &p.t.wqkv, sb + BAR_CSLD, 128 * n, 64 * m + 32, 0);
      } else {
#pragma unroll 1
        for (int h = 0; h < 2; h++) {
          const uint32_t xr = sb + BAR_XRDY + 8 * h;
          mbar_expect_tx(xr, 16384);
          tma_ld_act(sb + OFF_X + h * 16384, &p.t.xin, xr, 128 * n + 64 * h, m);
          asm volatile("mbarrier.arrive.shared::cta.b64 _, [%0], 3;" ::"r"(xr) : "memory");
        }
      }
    }
  }
  const uint32_t tag = __ldcg(p.g->epoch + m * 8 + n) + 1;
  uint32_t* word = p.g->flags + m * 32 + n;
  st_relaxed(word, 32 * tag);
#pragma unroll 1
  for (int c = 0; c < 16; c++) {
    const int e = c >= 9 ? c - 9 : c;
    if (e == 2 || e == 7) mbar_wait(sb + BAR_XGO, e == 7);
    else mbar_wait(sb + BAR_PUB + 8 * e, c >= 9);
    asm volatile("fence.release.gpu;" ::: "memory");
    asm volatile("red.relaxed.gpu.global.add.u32 [%0], 1;" ::"l"(word) : "memory");
  }
  p.g->epoch[m * 8 + n] = tag;
}

__device__ __forceinline__ void sum_rows(uint32_t buf, int iters, float (&a)[8], int lane) {
  uint32_t addr = buf + (lane >> 3) * 128 + (((lane & 7) ^ (lane >> 3)) << 4);
#pragma unroll 1
  for (int it = 0; it < iters; it++) {
    uint32_t u[2][4];
    lds_u4(addr, u[0][0], u[0][1], u[0][2], u[0][3]);
    lds_u4((addr ^ 64) + 512, u[1][0], u[1][1], u[1][2], u[1][3]);
    addr += 1024;
#pragma unroll
    for (int e = 0; e < 8; e++) { a[2 * (e & 3)] += bf_lo(u[e >> 2][e & 3]); a[2 * (e & 3) + 1] += bf_hi(u[e >> 2][e & 3]); }
  }
}
__device__ __forceinline__ void publish_sums(const float (&a)[8], uint4* dst, int lane, uint32_t tag) {
  const bool u8 = lane & 8, u16 = lane & 16;
  float h4[4], h2[2];
#pragma unroll
  for (int e = 0; e < 4; e++) h4[e] = (u8 ? a[4 + e] : a[e]) + __shfl_xor_sync(0xffffffffu, u8 ? a[e] : a[4 + e], 8);
#pragma unroll
  for (int e = 0; e < 2; e++) h2[e] = (u16 ? h4[2 + e] : h4[e]) + __shfl_xor_sync(0xffffffffu, u16 ? h4[e] : h4[2 + e], 16);
  st_msg(dst + (lane & 7) * 4 + (u8 ? 2 : 0) + (u16 ? 1 : 0), __float_as_uint(h2[0]), __float_as_uint(h2[1]), 0u, tag);
}

__device__ __forceinline__ void colsum_helper(const Params& p, uint32_t sb, int m, int n, int lane) {
  const uint32_t tag = __ldcg(p.g->epoch + m * 8 + n) + 1;
#pragma unroll 1
  for (int k = lane; k < 288; k += 32) {
    const uint32_t bb = __ldg(reinterpret_cast<const uint32_t*>(k < 224 ? p.b1 + 448 * n : p.b2 + 128 * n - 448) + k);
    const float sc = k < 224 ? 0.5f : 1.f;
    sts_f2(sb + (k < 224 ? OFF_CSF + k * 16 + 8 : OFF_CSQ + 1536 + (k - 224) * 8), sc * bf_lo(bb), sc * bf_hi(bb));
  }
  __syncwarp();
  if (elect_one()) mbar_arrive(sb + BAR_BIAS);
  bar_sync(BAR_HLP, 160);
  {
    uint4* base = p.g->csp + n * 17 * 224 + 12 * m + min(lane & 15, 11);
    float s0 = 0.f, s1 = 0.f;
#pragma unroll 1
    for (int g = 0; g < 2; g++) {
      uint32_t x[4], y[4];
#pragma unroll 1
      for (int it = 0; it < MSG_SPINS; it++) {
        uint32_t bad = 0, z, tg;
        if (g == 0 || it > 0) __nanosleep(CS_NS);
#pragma unroll
        for (int k = 0; k < 4; k++) { ld_msg(base + (g * 8 + (lane >> 4) * 4 + k) * 224, x[k], y[k], z, tg); bad |= tg ^ tag; }
        if (__all_sync(0xffffffffu, bad == 0)) break;
      }
#pragma unroll
      for (int k = 0; k < 4; k++) { s0 += __uint_as_float(x[k]); s1 += __uint_as_float(y[k]); }
    }
    s0 += __shfl_xor_sync(0xffffffffu, s0, 16);
    s1 += __shfl_xor_sync(0xffffffffu, s1, 16);
    if (lane < 12) st_msg(base + 16 * 224, __float_as_uint(s0), __float_as_uint(s1), 0u, tag);
  }
#pragma unroll 1
  for (int c = 0; c < 7; c++) {
    float a[8] = {0.f, 0.f, 0.f, 0.f, 0.f, 0.f, 0.f, 0.f};
#pragma unroll 1
    for (int h = 0; h < 2; h++) {
      if (elect_one()) {
        mbar_expect_tx(sb + BAR_CSLD + 8, 4096);
        tma_ld2(sb + OFF_HLP, &p.t.w1c, sb + BAR_CSLD + 8, 448 * n + 64 * c, 64 * m + 32 * h);
        if (c < 6) asm volatile("cp.async.bulk.prefetch.tensor.2d.L2.global [%0, {%1, %2}];" ::"l"(&p.t.w1c), "r"(448 * n + 64 * c + 64), "r"(64 * m + 32 * h) : "memory");
      }
      mbar_wait(sb + BAR_CSLD + 8, h);
      sum_rows(sb + OFF_HLP, 4, a, lane);
      __syncwarp();
    }
    publish_sums(a, p.g->csp + ((8 + n) * 17 + m) * 224 + c * 32, lane, tag);
  }
  if (elect_one()) {
#pragma unroll 1
    for (int k = 0; k < 3; k++) {
      mbar_wait(sb + BAR_XGO, k & 1);
      __nanosleep(XB_NS);
#pragma unroll 1
      for (int w = 0; w < 4; w++) {
        tma_st_warp(&p.t.out_w, sb + OFF_X + 16384 + w * 4096, 128 * n + 64, m, w);
        bulk_commit();
        bulk_wait_read();
        if (w < 3) __nanosleep(XB_GAP_NS);
      }
      bulk_wait_all();
      asm volatile("mbarrier.arrive.shared::cta.b64 _, [%0], 4;" ::"r"(sb + BAR_PUB + (k & 1 ? 64 : 24)) : "memory");
    }
  }
}

__device__ __forceinline__ void poll_msgs2(const uint4* pa, const uint4* pb, float (&v)[4], uint32_t tag) {
#pragma unroll 1
  for (int it = 0; it < MSG_SPINS; it++) {
    uint32_t x[4], z, ta, tb;
    ld_msg(pa, x[0], x[1], z, ta);
    ld_msg(pb, x[2], x[3], z, tb);
#pragma unroll
    for (int e = 0; e < 4; e++) v[e] = __uint_as_float(x[e]);
    if (__all_sync(0xffffffffu, ta == tag && tb == tag)) break;
  }
}
__device__ __forceinline__ void colsum_total(const Params& p, const Ctx& cx, int mat, uint32_t tag) {
  uint4* base = p.g->csp + (mat * 8 + cx.n) * 17 * 224;
  const int per = 12 + 2 * mat, k = 2 * cx.w + (cx.lane >> 4), ia = per * cx.m + k, ib = per * cx.m + min(k + 8, per - 1);
  float v[4];
  poll_msgs2(base + (cx.lane & 15) * 224 + ia, base + (cx.lane & 15) * 224 + ib, v, tag);
#pragma unroll 1
  for (int d = 1; d < 16; d *= 2)
#pragma unroll
    for (int e = 0; e < 4; e++) v[e] += __shfl_xor_sync(0xffffffffu, v[e], d);
  const bool hi = cx.lane & 1;
  if ((cx.lane & 14) == 0) st_msg(base + 16 * 224 + (hi ? ib : ia), __float_as_uint(hi ? v[2] : v[0]), __float_as_uint(hi ? v[3] : v[1]), 0u, tag);
}
__device__ __forceinline__ void colsum_gather(const Params& p, const Ctx& cx, int mat, uint32_t tag) {
  const uint4* base = p.g->csp + ((mat * 8 + cx.n) * 17 + 16) * 224;
  const int ia = cx.w * 32 + cx.lane, ib = min(ia + 128, 191 + 32 * mat);
  float v[4];
  poll_msgs2(base + ia, base + ib, v, tag);
  const uint32_t tab = cx.sb + (mat ? OFF_CSF : OFF_CSQ);
  sts_f2(tab + (ia << (3 + mat)), v[0], v[1]);
  sts_f2(tab + (ib << (3 + mat)), v[2], v[3]);
}

#define ACC(q, j, e) acc[(q) & 1][4 * (j) + 2 * ((q) >> 1) + (e)]

constexpr uint32_t RING16 = RING_UNITS * (UNIT >> 4);
__device__ __forceinline__ bool tile_split(int i) { return (0xD98 >> i) & 1; }

__device__ __forceinline__ void write_run_desc(uint32_t sb, int i, int step) {
  const int layer = i >= 7, t = i - 7 * layer, part = tile_split(i) ? step : 2;
  const bool wide = tile_wide(t), own = t != 2 && t != 6 && part != 1 && i != 0, second = t == 1 || t == 4;
  const uint32_t z16 = (wide ? 5 : 4) * (UNIT >> 4), a_off = z16 - 1024 + (uint32_t)DESC_A - (uint32_t)DESC_B;
  const int gl = 16 * t + (part == 2 ? 0 : second ? 16 * part - 14 : 4 * part), g0 = layer * STAGES_PER_LAYER + gl;
  const uint32_t s16 = (sb & 0x3FFFF) >> 4, bfirst = (uint32_t)DESC_B + s16;
  const int nkb = t == 6 ? 56 - SKEW : part == 0 ? 2 : 12 + 2 * part;
  const bool win1 = t == 1 && part != 0;
  const int win = layer ? WIN1 : WIN0;
  const int run = win1 ? win + 1 : t == 2 ? WIN2 + 1 : nkb;
  const int rest = win1 ? 64 | (nkb - 1 - SKEW - win) : t == 2 ? 64 | (7 - WIN2) | ((8 - SKEW) << 7) : 0;
  const uint32_t blo = bfirst + z16 * (wide ? (gl + (t == 5 ? 3 : 0)) & 3 : (gl + 3) % 5);
  const uint32_t alo = own ? (uint32_t)DESC_A + s16 + (OFF_X >> 4) : blo + a_off;
  const uint32_t aoff = own ? alo + 1024 - (blo == bfirst + RING16 - z16 ? bfirst : blo + z16) : a_off;
  const bool xwait = part == 0 && !second, keep = !(part == 0 || t == 5);
  sts_u4(sb + OFF_RUN + (2 * i + step) * 16, blo, alo, aoff,
         ((g0 / NBAR) & 1) | xwait << 1 | keep << 2 | 8 * (g0 % NBAR) | run << 6 | rest << 12);
}

__device__ __forceinline__ float2 row_sums(const Ctx& c, int j0, int j1) {
  const uint32_t xrow = c.sb + OFF_X + c.w * 4096 + c.lane * 128;
  float s = 0.f, q = 0.f, s1 = 0.f, q1 = 0.f;
#pragma unroll 4
  for (int j = j0; j < j1; j++) {
    uint32_t u[4];
    lds_u4(xrow + (j >> 3) * 16384 + (((j & 7) ^ (c.lane & 7)) << 4), u[0], u[1], u[2], u[3]);
#pragma unroll
    for (int e = 0; e < 4; e++) {
      const float a = bf_lo(u[e]), d = bf_hi(u[e]);
      s += a; q = fmaf(a, a, q);
      s1 += d; q1 = fmaf(d, d, q1);
    }
  }
  return make_float2(s + s1, q + q1);
}
__device__ __forceinline__ void write_partial_stats(const Params& p, const Ctx& c, int ln, float2 v, uint32_t tag) {
  st_msg(p.g->stats + (ln * 8 + c.n) * SEQ + 128 * c.m + 32 * c.w + c.lane, __float_as_uint(v.x),
         __float_as_uint(fmaxf(v.y - v.x * v.x * (1.f / 128.f), 0.f)), 0u, tag);
}

template <bool PACED>
__device__ __forceinline__ void rank1_update(const Params& p, float (&acc)[2][96], const Ctx& cx, int t) {
  float nm[4];
#pragma unroll
  for (int q = 0; q < 4; q++) nm[q] = t == 6 ? 1.f : -lds_f(cx.sb + OFF_ROW + (32 * cx.w + 8 * q + (cx.lane >> 2)) * 8 + 4);
  const uint32_t ctab = cx.sb + OFF_CSQ + ((t & 3) * 192 + 2 * (cx.lane & 3)) * 4;
#pragma unroll
  for (int j = 0; j < 24; j++) {
    const float2 cs = lds_f2(ctab + j * 32);
#pragma unroll
    for (int q = 0; q < 4; q++) {
      const int k = 4 * j + q - 1;
      const float nq = PACED && k >= 0 ? chain(nm[q], __float_as_uint(ACC(k & 3, k >> 2, 1)), p.zero) : nm[q];
      ACC(q, j, 0) = fmaf(nq, cs.x, ACC(q, j, 0));
      ACC(q, j, 1) = fmaf(nq, cs.y, ACC(q, j, 1));
    }
  }
}

template <int QMASK, int SEC>
__device__ __forceinline__ void pack_qkv(const float (&acc)[2][96], uint32_t (&F)[3][4][8]) {
#pragma unroll
  for (int q = 3; q >= 0; q--)
#pragma unroll
    for (int j = 0; j < 8; j++) {
      if (!((QMASK >> q) & 1)) continue;
      const uint32_t u = pack_bf16(ACC(q, 8 * SEC + j, 0), ACC(q, 8 * SEC + j, 1));
      F[SEC][q][j] = SEC == 2 ? movtrans(u) : u;
    }
}
template <int K0, int K1>
__device__ __forceinline__ void send_halo(const Params& p, const uint32_t (&F)[3][4][8], const Ctx& cx, int layer, int t) {
  uint32_t E[18];
#pragma unroll
  for (int j = 0; j < 8; j++) { E[j] = F[1][3][j]; E[8 + j] = F[2][3][j]; }
  if (cx.w < 2) {
#pragma unroll
    for (int k = K0; k < K1; k++)
      if (k < 4) sts_u4(cx.sb + OFF_STG + cx.w * 2048 + cx.lane * 16 + k * 512, E[4 * k], E[4 * k + 1], E[4 * k + 2], E[4 * k + 3]);
  } else {
    uint4* dst = p.g->halo + (((layer * 2 + t) * 16 + cx.m) * 8 + cx.n) * 384 + (cx.w & 1) * 192 + cx.lane;
    const uint32_t tag = lds_u(cx.sb + OFF_TAG);
    if (K1 == 6) {
      const float4 r = lds_f4(cx.sb + OFF_ROW + (32 * cx.w + 24 + 2 * (cx.lane & 3)) * 8);
      E[16] = __float_as_uint(r.x);
      E[17] = __float_as_uint(r.z);
    }
#pragma unroll
    for (int k = K0; k < K1; k++) st_msg(dst + k * 32, E[3 * k], E[3 * k + 1], E[3 * k + 2], tag);
  }
}

__device__ __forceinline__ void attn_scores(const uint32_t* qa, const uint32_t* qb, const uint32_t* kp, const uint32_t* ka,
                                            const uint32_t* kb, float (&l)[4], const float4& zero, const bool (&early)[2]) {
  float s[3][4];
#pragma unroll
  for (int x = 0; x < 3; x++) {
    const uint32_t* kk = x == 0 ? kp : x == 1 ? ka : kb;
    asm volatile("mma.sync.aligned.m16n8k16.row.col.f32.bf16.bf16.f32 {%0,%1,%2,%3}, {%4,%5,%6,%7}, {%8,%9}, {%10,%11,%12,%13};"
                 : "=f"(s[x][0]), "=f"(s[x][1]), "=f"(s[x][2]), "=f"(s[x][3])
                 : "r"(qa[0]), "r"(qb[0]), "r"(qa[1]), "r"(qb[1]), "r"(kk[0]), "r"(kk[1]), "f"(zero.x), "f"(zero.y),
                   "f"(zero.z), "f"(zero.w));
  }
#pragma unroll
  for (int x = 0; x < 3; x++) {
    const uint32_t* kk = x == 0 ? kp : x == 1 ? ka : kb;
    mma16816(s[x], qa[2], qb[2], qa[3], qb[3], kk[2], kk[3]);
  }
#pragma unroll
  for (int e = 0; e < 2; e++) {
    l[e] = early[e] ? s[0][e] : s[1][e];
    l[2 + e] = early[e] ? s[1][2 + e] : s[2][2 + e];
  }
}

__device__ __forceinline__ void attn_mix(const float (&l)[4], const float (&sc)[4], const float (&off)[4], const float (&rk)[4],
                                         const uint32_t* vp, const uint32_t* va, const uint32_t* vb, float (&o)[4][4],
                                         float (&sum)[2], uint32_t mask, uint32_t zero) {
  float x[4];
#pragma unroll
  for (int e = 0; e < 4; e++) x[e] = fmaf(l[e], sc[e], off[e]);
  const float ml = quad_max(fmaxf(x[0], x[1])), mh = quad_max(fmaxf(x[2], x[3]));
  x[0] = ex2(x[0] - ml); x[1] = ex2(x[1] - ml);
  x[2] = ex2(x[2] - mh); x[3] = ex2(x[3] - mh);
  sum[0] = x[0] + x[1];
  sum[1] = x[2] + x[3];
  const uint32_t pl = pack_bf16(x[0] * rk[0], x[1] * rk[1]), ph = pack_bf16(x[2] * rk[2], x[3] * rk[3]);
  const uint32_t a0 = pl & ~mask, a1 = ph & mask, a2 = pl & zero, a3 = ph & ~mask, c0 = pl & mask, c1 = ph & zero;
#pragma unroll
  for (int jn = 0; jn < 4; jn++) {
    o[jn][0] = o[jn][1] = o[jn][2] = o[jn][3] = 0.f;
    mma16816(o[jn], a0, a1, a2, a3, va[jn], vb[jn]);
  }
#pragma unroll
  for (int jn = 0; jn < 4; jn++) mma1688(o[jn], c0, c1, vp[jn]);
}

template <int t>
__device__ __forceinline__ void attn_epilogue(const Params& p, float (&acc)[2][96], uint32_t (&F)[3][4][8], const Ctx& cx, int layer, uint32_t tag) {
  UNPACK_CTX(cx);
  const uint32_t ktab = sb + OFF_ROW + (32 * w + 2 * (lane & 3)) * 8, exc = sb + OFF_STG + (w & 1) * 2048 + lane * 16;
  uint4* const halo = p.g->halo + (((layer * 2 + t) * 16 + m) * 8 + n) * 384 + (w & 1) * 192;
  (void)wg;
  uint32_t(&Q)[4][8] = F[0], (&K)[4][8] = F[1], (&V)[4][8] = F[2], P[18];
  float kr[5][2], qr[4];
  bar_arrive(BAR_PAIR + w, 64);
#pragma unroll
  for (int q = 0; q < 4; q++) {
    qr[q] = lds_f(sb + OFF_ROW + (32 * w + 8 * q + (lane >> 2)) * 8) * (0.17677669529663687f * 1.4426950408889634f);
    const float4 r = lds_f4(ktab + 64 * q);
    kr[1 + q][0] = r.x;
    kr[1 + q][1] = r.z;
  }
  pack_qkv<7, 1>(acc, F);
  uint32_t tg[6];
#pragma unroll
  for (int k = 0; k < 6; k++) {
    tg[k] = ~tag;
    if (t == 1)
      asm volatile("{\n.reg .b128 v;\n.reg .pred g;\nsetp.ne.u32 g, %5, 0;\nmov.b128 v, {%6, %6, %6, %6};\n"
                   "@g ld.relaxed.gpu.global.b128 v, [%4];\nmov.b128 {%0, %1, %2, %3}, v;\n}"
                   : "=r"(P[3 * k]), "=r"(P[3 * k + 1]), "=r"(P[3 * k + 2]), "=r"(tg[k])
                   : "l"(halo - 8 * 384 + k * 32 + lane), "r"((uint32_t)(w < 2 && m > 0) | ((K[0][7] | K[1][7] | K[2][7]) & p.zero)), "r"(~tag) : "memory");
  }
  pack_qkv<7, 2>(acc, F);
  pack_qkv<15, 0>(acc, F);
  bar_sync(BAR_PAIR + (w ^ 2), 64);
  if (w >= 2 || m == 0) {
#pragma unroll
    for (int k = 0; k < 4; k++) lds_u4(exc + k * 512, P[4 * k], P[4 * k + 1], P[4 * k + 2], P[4 * k + 3]);
    const float4 r = lds_f4(ktab - (w >> 1) * 320);
    P[16] = __float_as_uint(r.x);
    P[17] = __float_as_uint(r.z);
  } else {
    if ((m & 1) && t == 0) __nanosleep(HALO_NS);
#pragma unroll 1
    for (int it = 0; it < MSG_SPINS; it++) {
      if (t == 0 || it > 0) {
        if (it > 0 || !(m & 1)) poll_line(reinterpret_cast<const uint32_t*>(halo - 8 * 384 + 191) + 3, tag, 1u);
#pragma unroll
        for (int k = 0; k < 6; k++) ld_msg(halo - 8 * 384 + k * 32 + lane, P[3 * k], P[3 * k + 1], P[3 * k + 2], tg[k]);
      }
      uint32_t bad = 0;
#pragma unroll
      for (int k = 0; k < 6; k++) bad |= tg[k] ^ tag;
      if (__all_sync(0xffffffffu, bad == 0)) break;
    }
  }
  kr[0][0] = __uint_as_float(P[16]);
  kr[0][1] = __uint_as_float(P[17]);
  const bool early[2] = {2 * (lane & 3) > (lane >> 2), 2 * (lane & 3) + 1 > (lane >> 2)};
  const uint32_t mask = (early[0] ? 0xffffu : 0u) | (early[1] ? 0xffff0000u : 0u);
  float rk[2][4], sc[2][4], off[2][4];
#pragma unroll
  for (int g = 0; g < 2; g++) {
#pragma unroll
    for (int e = 0; e < 4; e++) {
      const int q = 2 * g + (e >> 1);
      const bool masked = q == 0 && m == 0 && w < 2 && early[e & 1];
      rk[g][e] = early[e & 1] ? kr[q][e & 1] : kr[q + 1][e & 1];
      sc[g][e] = masked ? 0.f : rk[g][e] * qr[q];
      off[g][e] = masked ? -1e30f : 0.f;
    }
  }
  if (w == 0 && elect_one()) asm volatile("prefetch.tensormap [%0];" ::"l"(&p.t.att_st) : "memory");
  bar_sync(BAR_GO, 256);
  const float4 zero = lds_f4(sb + OFF_ZERO);
  float l[2][2][4], o[2][2][4][4], sum[2][2][2];
#pragma unroll
  for (int h = 0; h < 2; h++) {
    if (h == 1) {
      Q[2][4] |= __float_as_uint(l[1][0][0]) & p.zero;
      Q[0][4] |= __float_as_uint(l[0][0][0]) & p.zero;
    }
    attn_scores(&Q[2][4 * h], &Q[3][4 * h], &K[1][4 * h], &K[2][4 * h], &K[3][4 * h], l[1][h], zero, early);
    attn_scores(&Q[0][4 * h], &Q[1][4 * h], &P[4 * h], &K[0][4 * h], &K[1][4 * h], l[0][h], zero, early);
  }
  const uint32_t stg = sb + OFF_STG + w * 4096, srow = stg + lane * 128 + ((lane & 7) << 4);
#pragma unroll
  for (int h = 0; h < 2; h++) {
    attn_mix(l[1][h], sc[1], off[1], rk[1], &V[1][4 * h], &V[2][4 * h], &V[3][4 * h], o[1][h], sum[1][h], mask, p.zero);
    attn_mix(l[0][h], sc[0], off[0], rk[0], &P[8 + 4 * h], &V[0][4 * h], &V[1][4 * h], o[0][h], sum[0][h], mask, p.zero);
  }
  if (t == 0 && p.zero == 0) {
    uint32_t dep = 0;
#pragma unroll
    for (int k = 0; k < 16; k++) dep |= __float_as_uint(o[k >> 3][(k >> 2) & 1][k & 3][0]);
    bar_arrive(BAR_DONE | (dep & __float_as_uint(zero.x)), 256);
  }
#pragma unroll
  for (int h = 0; h < 2; h++) {
    float inv[4];
#pragma unroll
    for (int q = 0; q < 4; q++) inv[q] = rcp_hw(quad_sum(sum[q >> 1][h][q & 1]));
#pragma unroll
    for (int j = 0; j < 4; j++) {
      const float(&a)[4] = o[0][h][j];
      const float(&c)[4] = o[1][h][j];
      stsm4(srow ^ ((4 * h + j) << 4), pack_bf16(a[0] * inv[0], a[1] * inv[0]), pack_bf16(a[2] * inv[1], a[3] * inv[1]),
            pack_bf16(c[0] * inv[2], c[1] * inv[2]), pack_bf16(c[2] * inv[3], c[3] * inv[3]));
    }
  }
  if (t == 1) bar_arrive(BAR_DONE, 256);
  fence_async_smem();
  __syncwarp();
  if (lane == 0) {
    tma_st2(&p.t.att_st, stg, 128 * n + 64 * t, 128 * m + 32 * w);
    bulk_commit();
  }
}

__device__ __forceinline__ void finish_stores(uint32_t sb, int i) {
  const int t = i >= 7 ? i - 7 : i;
  if ((threadIdx.x & 31) == 0) {
    bulk_wait_all();
    mbar_arrive(sb + BAR_PUB + 8 * (t < 2 ? t : t + 1));
  }
  __syncwarp();
  if (i < 12) bar_arrive(BAR_GUARD + ((i & 1) ^ 1), 256);
}

template <int N>
__device__ __forceinline__ bool mainloop(const Params& p, float (&acc)[2][96], uint32_t sb, int i, int step, int mn) {
  constexpr uint32_t Z16 = (2 + N / 64) * (UNIT >> 4);
  constexpr uint32_t A_OFF = Z16 - 1024 + (uint32_t)DESC_A - (uint32_t)DESC_B;
  const int wg = i & 1;
  const uint32_t s16 = (sb & 0x3FFFF) >> 4;
  const uint32_t blast = (uint32_t)DESC_B + s16 + RING16 - Z16, flast = sb + BAR_FULL + 8 * (NBAR - 1);
  uint32_t blo = (uint32_t)DESC_B + s16, alo = blo + A_OFF, aoff = A_OFF, misc = 16 << 6;
  if (N == 128 || i > 0) lds_u4(sb + OFF_RUN + (2 * i + step) * 16, blo, alo, aoff, misc);
  uint32_t keep = misc & 4;
  int run = (misc >> 6) & 63, rest = misc >> 12;
  uint32_t fb = sb + BAR_FULL + (misc & 0x38), ph = misc & 1;
  uint32_t prev = sb + BAR_DUMMY - 8 * NBAR;
  const uint32_t lane_id = __popc(__ballot_sync(0xffffffffu, true) & lanemask_lt()), rel = pair_offset(sb, lane_id & 1) + 8 * NBAR;
  pin_regs<N / 2>(acc);
  if (N == 128 || i > 0) bar_sync(BAR_ORDER + wg, 256);
  else bar_sync(BAR_INIT0, 160);
  mbar_wait(fb, ph);
  if (N == 192 && i == 0) cluster_wait();
  if (misc & 2) {
    if (N == 128) {
      const Ctx cx = make_ctx(sb, mn);
      mbar_wait(sb + BAR_XRDY, 1);
      const float2 v = row_sums(cx, 0, 8);
      sts_f2(cx.sb + OFF_HALF + (32 * cx.w + cx.lane) * 8, v.x, v.y);
      bar_arrive(BAR_STAT, 256);
    }
    mbar_wait(sb + BAR_XGO, N == 192);
  }
#pragma unroll 1
  while (true) {
    const uint64_t da = (DESC_A & ~0xffffffffull) | alo, db = (DESC_B & ~0xffffffffull) | blo;
    asm volatile("wgmma.fence.sync.aligned;" ::: "memory");
    wgmma_ss<N>(acc[0], da, db, keep);
    wgmma_ss<N>(acc[1], da + 64, db, keep);
    keep = 4;
    wgmma_ss<N>(acc[0], da + 2, db + 128);
    wgmma_ss<N>(acc[1], da + 66, db + 128);
    asm volatile("wgmma.commit_group.sync.aligned;" ::: "memory");
    asm volatile("wgmma.wait_group.sync.aligned 1;" ::: "memory");
    if (lane_id < 2) mbar_arrive_cluster(prev + rel);
    prev = fb;
    if (fb == flast) { fb -= 8 * NBAR; ph++; }
    fb += 8;
    if (blo == blast) blo -= RING16;
    blo += Z16;
    alo = blo + aoff;
    aoff = A_OFF;
    run--;
    const bool ready = mbar_test(fb, ph) && run != 0;
    asm volatile("wgmma.fence.sync.aligned;" ::: "memory");
    wgmma_ss<N>(acc[0], da + 4, db + 4 * N);
    wgmma_ss<N>(acc[1], da + 68, db + 4 * N);
    wgmma_ss<N>(acc[0], da + 6, db + 4 * N + 128);
    wgmma_ss<N>(acc[1], da + 70, db + 4 * N + 128);
    asm volatile("wgmma.commit_group.sync.aligned;" ::: "memory");
    if (!ready) {
      bool window = false;
      if (run == 0) {
        if (rest == 0) break;
        window = rest & 64;
        if (N == 192 && i == 1) {
          bar_sync(BAR_GO, 256);
          asm volatile("wgmma.wait_group.sync.aligned 0;" ::: "memory");
          pin_regs<96>(acc);
          rank1_update<false>(p, acc, make_ctx(sb, mn), 1);
          pin_regs<96>(acc);
        } else if (window) bar_arrive(BAR_GO, 256);
        else alo = (uint32_t)DESC_A + s16 + (OFF_STG >> 4);
        run = rest & 63;
        rest >>= 7;
      }
      mbar_wait(fb, ph);
      if (window) bar_sync(BAR_DONE, 256);
    }
  }
  if constexpr (N == 192) {
    if (misc >> 12) {
      const Ctx cx = make_ctx(sb, mn);
      uint32_t F[3][4][8];
      const uint32_t fb0 = fb, blo0 = blo;
#pragma unroll 1
      for (int x = 0; x < SKEW; x++) {
        const uint64_t da = (DESC_A & ~0xffffffffull) | (blo + A_OFF + 64), db = (DESC_B & ~0xffffffffull) | blo;
        mbar_wait(fb, ph);
        asm volatile("wgmma.fence.sync.aligned;" ::: "memory");
#pragma unroll
        for (int k = 0; k < 4; k++) wgmma_ss<N>(acc[1], da + 2 * k, db + (k >> 1) * 4 * N + (k & 1) * 128);
        asm volatile("wgmma.commit_group.sync.aligned;" ::: "memory");
        asm volatile("wgmma.wait_group.sync.aligned 1;" ::: "memory");
        if (x == 0) {
          if (lane_id < 2) mbar_arrive_cluster(prev + rel);
          bar_sync(BAR_GUARD + wg, 256);
        }
        if (fb == flast) { fb -= 8 * NBAR; ph++; }
        fb += 8;
        blo += Z16;
      }
      fb = fb0;
#pragma unroll
      for (int u = 0; u < 2 * SKEW; u++) {
        const uint64_t da = (DESC_A & ~0xffffffffull) | (blo0 + (u >> 1) * Z16 + A_OFF + 4 * (u & 1));
        const uint64_t db = (DESC_B & ~0xffffffffull) | (blo0 + (u >> 1) * Z16 + 4 * N * (u & 1));
        asm volatile("wgmma.fence.sync.aligned;" ::: "memory");
        wgmma_ss<N>(acc[0], da, db);
        wgmma_ss<N>(acc[0], da + 2, db + 128);
        asm volatile("wgmma.commit_group.sync.aligned;" ::: "memory");
        if (u == 2 * SKEW - 1) break;
        asm volatile("wgmma.wait_group.sync.aligned 1;" ::: "memory");
        if (u == 0) {
#pragma unroll
          for (int r = 0; r < 96; r++) asm volatile("" : "+f"(acc[1][r])::"memory");
        }
        if (u == 2 || u == 4) {
          if (lane_id < 2) mbar_arrive_cluster(fb + rel);
          fb = fb == flast ? fb - 8 * (NBAR - 1) : fb + 8;
        }
        if (u == 0) { pack_qkv<8, 2>(acc, F); pack_qkv<8, 1>(acc, F); }
        if (u == 1) send_halo<0, 3>(p, F, cx, i >= 7, 1);
        if (u == 2) send_halo<3, 6>(p, F, cx, i >= 7, 1);
      }
      bar_arrive(BAR_ORDER + (wg ^ 1), 256);
      asm volatile("wgmma.wait_group.sync.aligned 0;" ::: "memory");
#pragma unroll
      for (int r = 0; r < 96; r++) asm volatile("" : "+f"(acc[0][r])::"memory");
      if (lane_id < 2) mbar_arrive_cluster(fb + rel);
      attn_epilogue<1>(p, acc, F, cx, i >= 7, lds_u(sb + OFF_TAG));
      finish_stores(sb, i);
#pragma unroll
      for (int r = 0; r < 48; r++) {
        float* d = &acc[r & 1][4 * (r >> 1)];
        asm volatile("ld.shared.v4.f32 {%0, %1, %2, %3}, [%4];" : "=f"(d[0]), "=f"(d[1]), "=f"(d[2]), "=f"(d[3]) : "r"(sb + OFF_CSQ + 16 * r));
      }
      return true;
    }
  }
  if (N == 128 && ((0x2244 >> i) & 1)) {
    const Ctx cx = make_ctx(sb, mn);
    const uint32_t xw = cx.sb + OFF_X + cx.w * 4096;
    const uint32_t xrow = xw + (cx.lane & 8) * 256 + (cx.lane & 7) * 128 + (((cx.lane & 7) ^ (cx.lane >> 4)) << 4);
    auto write_x = [&](int mb, int j) {
      stsm4((xrow ^ ((j & 7) << 4)) + (j >> 3) * 16384 + mb * 1024, pack_bf16(ACC(mb, j, 0), ACC(mb, j, 1)),
            pack_bf16(ACC(mb + 2, j, 0), ACC(mb + 2, j, 1)), pack_bf16(ACC(mb, j + 1, 0), ACC(mb, j + 1, 1)),
            pack_bf16(ACC(mb + 2, j + 1, 0), ACC(mb + 2, j + 1, 1)));
    };
    auto send_x = [&](int mb, int h) {
      fence_async_smem();
      __syncwarp();
      if (cx.lane == 0 && (h == 0 || i == 13)) {
        tma_st_warp(&p.t.out_8, xw + h * 16384 + mb * 1024, 128 * cx.n + 64 * h, cx.m, cx.w, 8 * mb);
        tma_st_warp(&p.t.out_8, xw + h * 16384 + mb * 1024 + 2048, 128 * cx.n + 64 * h, cx.m, cx.w, 8 * mb + 16);
        bulk_commit();
      }
    };
    uint32_t rb = fb, rlo = blo;
#pragma unroll 1
    for (int x = 0; x < SKEW; x++) {
      const uint64_t da = (DESC_A & ~0xffffffffull) | (blo + A_OFF), db = (DESC_B & ~0xffffffffull) | blo;
      mbar_wait(fb, ph);
      asm volatile("wgmma.fence.sync.aligned;" ::: "memory");
#pragma unroll
      for (int k = 0; k < 4; k++) wgmma_ss<N>(acc[0], da + 2 * k, db + (k >> 1) * 4 * N + (k & 1) * 128);
      asm volatile("wgmma.commit_group.sync.aligned;" ::: "memory");
      asm volatile("wgmma.wait_group.sync.aligned 1;" ::: "memory");
      if (x == 0 && lane_id < 2) mbar_arrive_cluster(prev + rel);
      if (fb == flast) { fb -= 8 * NBAR; ph++; }
      fb += 8;
      if (blo == blast) blo -= RING16;
      blo += Z16;
    }
#pragma unroll
    for (int u = 0; u < 2 * SKEW; u++) {
      const uint64_t da = (DESC_A & ~0xffffffffull) | (rlo + A_OFF + 64 + 4 * (u & 1));
      const uint64_t db = (DESC_B & ~0xffffffffull) | (rlo + 4 * N * (u & 1));
      asm volatile("wgmma.fence.sync.aligned;" ::: "memory");
      wgmma_ss<N>(acc[1], da, db);
      wgmma_ss<N>(acc[1], da + 2, db + 128);
      asm volatile("wgmma.commit_group.sync.aligned;" ::: "memory");
      if (u == 2 * SKEW - 1) break;
      asm volatile("wgmma.wait_group.sync.aligned 1;" ::: "memory");
      if (u == 0) {
#pragma unroll
        for (int r = 0; r < 64; r++) asm volatile("" : "+f"(acc[0][r])::"memory");
      }
      if (u & 1) rlo = rlo == blast ? rlo + Z16 - RING16 : rlo + Z16;
      if (u == 2 || u == 4) {
        if (lane_id < 2) mbar_arrive_cluster(rb + rel);
        rb = rb == flast ? rb - 8 * (NBAR - 1) : rb + 8;
      }
      if (u == 2) send_x(0, 0);
      else { write_x(0, 4 * (u - (u > 2))); write_x(0, 4 * (u - (u > 2)) + 2); }
    }
    if (i < 13) bar_arrive(BAR_ORDER + (wg ^ 1), 256);
    else send_x(0, 1);
    asm volatile("wgmma.wait_group.sync.aligned 0;" ::: "memory");
    pin_regs<64>(acc);
#pragma unroll
    for (int h = 0; h < 2; h++) {
      if (h == 1 && p.zero != 0) break;
#pragma unroll
      for (int j = 8 * h; j < 8 * h + 8; j += 2) write_x(1, j);
      send_x(1, h);
      if (h == 0) {
        if (cx.lane == 0) mbar_arrive(sb + BAR_XRDY);
        if (lane_id < 2 && i < 13) mbar_arrive_cluster(rb + rel);
      }
    }
    if (cx.lane == 0) {
      bulk_wait_all();
      mbar_arrive(sb + BAR_XGO);
    }
    __syncwarp();
    if (i == 2 || i == 9) {
      const float2 v = row_sums(cx, 8, 16);
      bar_sync(BAR_STAT, 256);
      const float2 o = lds_f2(cx.sb + OFF_HALF + (32 * cx.w + cx.lane) * 8);
      write_partial_stats(p, cx, (i + 3) >> 2, make_float2(v.x + o.x, v.y + o.y), lds_u(sb + OFF_TAG));
    }
    return true;
  }
  bar_arrive(BAR_ORDER + (wg ^ 1), 256);
  asm volatile("wgmma.wait_group.sync.aligned 0;" ::: "memory");
  pin_regs<N / 2>(acc);
  if (lane_id < 2) mbar_arrive_cluster(prev + rel);
  return false;
}

__device__ __forceinline__ void finish_row_stats(const Params& p, const Ctx& c, int ln, uint32_t tag) {
  const uint4* src = p.g->stats + ln * 8 * SEQ + 128 * c.m + 32 * c.w + c.lane;
  uint32_t ps[8], pm[8];
#pragma unroll 1
  for (int it = 0; it < MSG_SPINS; it++) {
    uint32_t bad = 0, u, tg;
    if (ln == 2 || it > 0) __nanosleep(STAT_NS);
#pragma unroll
    for (int k = 0; k < 8; k++) { ld_msg(src + k * SEQ, ps[k], pm[k], u, tg); bad |= tg ^ tag; }
    if (__all_sync(0xffffffffu, bad == 0)) break;
  }
  float s = 0.f, m2 = 0.f;
#pragma unroll
  for (int k = 0; k < 8; k++) s += __uint_as_float(ps[k]);
  const float mean = s * (1.f / DM);
#pragma unroll
  for (int k = 0; k < 8; k++) {
    const float d = __uint_as_float(ps[k]) * (1.f / 128.f) - mean;
    m2 += fmaf(128.f * d, d, __uint_as_float(pm[k]));
  }
  sts_f2(c.sb + OFF_ROW + (32 * c.w + c.lane) * 8, rsqrtf(m2 * (1.f / DM) + 1e-5f), mean);
  __syncwarp();
}

__device__ __forceinline__ void gelu_epilogue(const Params& p, float (&acc)[2][96], const Ctx& cx, int t) {
  UNPACK_CTX(cx);
  (void)wg;
  float rs[4], rm[4];
#pragma unroll
  for (int q = 0; q < 4; q++) {
    const float2 v = lds_f2(sb + OFF_ROW + (32 * w + 8 * q + (lane >> 2)) * 8);
    rs[q] = 0.5f * v.x;
    rm[q] = -rs[q] * v.y;
  }
  const int col0 = 128 * (t - 3);
  const uint32_t stg = sb + OFF_STG + w * 4096;
  const uint32_t ctab = sb + OFF_CSF + (col0 / 2 + (lane & 3)) * 16, srow = stg + lane * 128 + ((lane & 7) << 4);
  if (t != 4) __nanosleep((t == 5 ? STAG_NS : STAG3_NS) * w);
  float4 nb = lds_f4(ctab);
  auto chunk = [&](auto first, int cc) {
    constexpr int c = decltype(first)::value ? 0 : 1;
    uint32_t hp[8][4];
#pragma unroll
    for (int j = 0; j < 8; j++) {
      const float4 cb = nb;
      nb = lds_f4(ctab + (8 * cc + j + 1) * 64);
#pragma unroll
      for (int q = 0; q < 4; q++) {
        float y[2];
        const int k = 4 * j + q - GELU_DEP;
        const float rmq = k >= 0 ? chain(rm[q], hp[k >> 2][k & 3], p.zero) : rm[q];
#pragma unroll
        for (int e = 0; e < 2; e++) {
          const float z = fmaf(ACC(q, 8 * c + j, e), rs[q], fmaf(rmq, e ? cb.y : cb.x, e ? cb.w : cb.z));
          const float u = z * fmaf(z * z, 8.f * 0.7978845608028654f * 0.044715f, 2.f * 0.7978845608028654f);
          y[e] = fmaf(z, tanh_hw(u), z);
        }
        hp[j][q] = pack_bf16(y[0], y[1]);
      }
      if (j == STG_WAIT && c > 0) {
        if (lane == 0) bulk_wait_read();
        __syncwarp();
      }
      if (c == 0 || j > STG_WAIT) {
        stsm4(srow ^ (j << 4), hp[j][0], hp[j][1], hp[j][2], hp[j][3]);
      } else if (j == STG_WAIT) {
#pragma unroll
        for (int jj = 0; jj <= STG_WAIT; jj++) stsm4(srow ^ (jj << 4), hp[jj][0], hp[jj][1], hp[jj][2], hp[jj][3]);
      }
    }
    fence_async_smem();
    __syncwarp();
    if (lane == 0) {
      tma_st2(&p.t.h_st, stg, 448 * n + col0 + 64 * cc, 128 * m + 32 * w);
      bulk_commit();
    }
    return hp[7][3];
  };
  chunk(std::true_type{}, 0);
#pragma unroll 1
  for (int cc = 1;; cc++) {
    const uint32_t zr = chunk(std::false_type{}, cc) & p.zero;
    if (cc == 2 || t != 5) break;
#pragma unroll
    for (int r = 0; r < 64; r++)
      asm volatile("{\n.reg .b32 x;\nmov.b32 x, %1;\nor.b32 x, x, %2;\nmov.b32 %0, x;\n}"
                   : "=f"(acc[r & 1][32 + (r >> 1)]) : "f"(acc[r & 1][64 + (r >> 1)]), "r"(zr));
  }
#pragma unroll
  for (int r = 0; r < 16; r++) acc[0][r] = acc[1][r] = 0.f;
}

__device__ __forceinline__ bool consumer_tile(const Params& p, float (&acc)[2][96], uint32_t sb0, int i, int mn) {
  const int layer = i >= 7, t = i - 7 * layer, wg = i & 1;
  const bool resid = t == 2 || t == 6;
  {
    if (resid) {
      const Ctx cx = make_ctx(sb0, mn);
      const uint32_t xrow = cx.sb + OFF_X + cx.w * 4096 + cx.lane * 128;
      const uint32_t sel_lo = 0x1044u | p.zero, sel_hi = 0x3244u | p.zero;
#pragma unroll
      for (int j = 0; j < 16; j++) {
        uint32_t r[4];
        ldsm4(xrow + (j >> 3) * 16384 + (((j & 7) ^ (cx.lane & 7)) << 4), r[0], r[1], r[2], r[3]);
#pragma unroll
        for (int q = 0; q < 4; q++) {
          ACC(q, j, 0) = prmt_f(r[q], sel_lo);
          ACC(q, j, 1) = prmt_f(r[q], sel_hi);
        }
      }
    }
    if (t >= 5 || i == 7) finish_stores(sb0, i - 2);
#pragma unroll 1
    for (int step = !tile_split(i);; step++) {
      if (step == 1 && (t == 1 || t == 4)) {
        const Ctx cx = make_ctx(sb0, mn);
        if (i == 1) {
          const uint32_t epoch = __ldcg(p.g->epoch + (mn & 127));
          cluster_wait();
          asm volatile("st.shared.u32 [%0], %1;" ::"r"(sb0 + OFF_TAG), "r"(epoch + 1) : "memory");
        }
        const uint32_t tag = lds_u(cx.sb + OFF_TAG);
        const int ln = (i + 1) >> 2;
#pragma unroll 1
        for (int r = 0; r < 2; r++) {
          if (i == 1) {
            if (cx.w < 3) {
              float a[8] = {0.f, 0.f, 0.f, 0.f, 0.f, 0.f, 0.f, 0.f};
              mbar_wait(sb0 + BAR_CSLD, r);
#pragma unroll 1
              for (int h = 0; h < 2; h++) sum_rows(cx.sb + OFF_STG + h * 12288 + cx.w * 4096, 4, a, cx.lane);
              publish_sums(a, p.g->csp + (cx.n * 17 + cx.m) * 224 + (3 * r + cx.w) * 32, cx.lane, tag);
            }
          }
          if (r == 1) break;
          if (i == 1) {
            bar_sync(BAR_WG + 1, 128);
            if (cx.w == 3 && elect_one()) {
              mbar_expect_tx(sb0 + BAR_CSLD, 24576);
              tma_ld3(sb0 + OFF_STG, &p.t.wqkv, sb0 + BAR_CSLD, 128 * cx.n + 64, 64 * cx.m, 0);
              tma_ld3(sb0 + OFF_STG + 12288, &p.t.wqkv, sb0 + BAR_CSLD, 128 * cx.n + 64, 64 * cx.m + 32, 0);
            }
            mbar_wait(sb0 + BAR_XRDY, 0);
            mbar_wait(sb0 + BAR_XRDY + 8, 0);
          }
          if (t == 1) write_partial_stats(p, cx, ln, row_sums(cx, 0, 16), tag);
        }
        if (i == 1) {
          bar_arrive(BAR_HLP, 160);
          bar_sync(BAR_INIT, 160);
        }
        if (i == 4) colsum_total(p, cx, 1, tag);
        if (i != 1) bar_sync(BAR_GUARD + wg, 256);
        finish_row_stats(p, cx, ln, tag);
        if (i == 4) {
          colsum_gather(p, cx, 1, tag);
          mbar_wait(sb0 + BAR_BIAS, 0);
        }
        bar_arrive(BAR_GUARD + (wg ^ 1), 256);
      }
      if (step == 2) bar_sync(BAR_GUARD + wg, 256);
      if (step == 2 && i == 0) {
        colsum_gather(p, make_ctx(sb0, mn), 0, lds_u(sb0 + OFF_TAG));
        bar_sync(BAR_WG, 128);
      }
      if ((t + step == 2 && i != 1) || t == 6) rank1_update<true>(p, acc, make_ctx(sb0, mn), t);
      if (step == 2) break;
      if (tile_wide(t)) {
        if (mainloop<192>(p, acc, sb0, i, step, mn)) return false;
      } else {
        if (mainloop<128>(p, acc, sb0, i, step, mn)) return false;
      }
    }
    if (t < 2) return true;
    gelu_epilogue(p, acc, make_ctx(sb0, mn), t);
    return false;
  }
}

template <bool BY_SMID>
__global__ void __cluster_dims__(2, 1, 1) __launch_bounds__(384, 1)
fused_layers_kernel(const Scalars scalars, const __grid_constant__ Maps maps) {
  if (threadIdx.x == 288 || threadIdx.x == 320)
    asm volatile("prefetch.tensormap [%0];" ::"l"(threadIdx.x == 288 ? &maps.xin : &maps.wqkv) : "memory");
  const Params p{scalars, maps};
  extern __shared__ __align__(1024) uint8_t smem_raw[];
  const uint32_t sb = uniform((uint32_t)__cvta_generic_to_shared(smem_raw));
  const int tid = threadIdx.x, lane = tid & 31, warp = uniform(tid >> 5), wg = warp >> 2, w = warp & 3;

  int mn;
  {
    int id = blockIdx.x;
    if (BY_SMID) asm volatile("mov.u32 %0, %%smid;" : "=r"(id));
    else if (id >= 120) id += 4;
    const int c = id >> 1;
    int g, j;
    if (c < 32) { g = c & 7; j = c >> 3; }
    else if (c < 60) { g = 1 + (c - 32) % 7; j = 4 + (c - 32) / 7; }
    else { g = 0; j = c - 58; }
    mn = (g * 2 + (blockIdx.x & 1)) * 8 + j;
    if (c == 60 || c == 61) {
      if (tid < 32) {
        const uint32_t tag = __ldcg(p.g->epoch + NCTA + (id & 3)) + 1;
#pragma unroll 1
        for (int mm = 0; mm < 16; mm++) poll_line(p.g->flags + mm * 32 + (lane & 7), 32 * tag, 0xffu);
        if (tid == 0) p.g->epoch[NCTA + (id & 3)] = tag;
      }
      return;
    }
  }
  const int m = mn >> 3, n = mn & 7;
  if (wg < 2) {
    cluster_arrive();
    asm volatile("setmaxnreg.inc.sync.aligned.u32 232;");
    const int id = mn | (warp << 7);
#pragma unroll 1
    for (int i = wg;; i += 2) {
      float acc[2][96];
#pragma unroll
      for (int r = 0; r < 96; r++) acc[0][r] = acc[1][r] = 0.f;
      pin_regs<96>(acc);
#pragma unroll 1
      while (!consumer_tile(p, acc, sb, i, id)) {
        i += 2;
        if (i >= 14) goto all_done;
      }
      const Ctx cx = make_ctx(sb, id);
      uint32_t F[3][4][8];
      pack_qkv<8, 2>(acc, F);
      pack_qkv<8, 1>(acc, F);
      send_halo<0, 6>(p, F, cx, i >= 7, 0);
      attn_epilogue<0>(p, acc, F, cx, i >= 7, lds_u(sb + OFF_TAG));
      finish_stores(sb, i);
    }
  all_done:
    if (wg == 0) {
      finish_stores(sb, 12);
    } else {
      cluster_arrive();
      cluster_wait();
    }
  } else {
    asm volatile("setmaxnreg.dec.sync.aligned.u32 40;");
    if (w != 0) {
      if (w == 1 && elect_one()) {
        mbar_init(sb + BAR_FULL + 32, 2);
#pragma unroll
        for (int k = 0; k < NBAR; k++) mbar_init(sb + BAR_EMPTY + 8 * k, 8);
#pragma unroll
        for (int k = 0; k < 3; k++) mbar_init(sb + BAR_XRDY + 8 * k, 4);
#pragma unroll
        for (int k = 0; k < 9; k++) mbar_init(sb + BAR_PUB + 8 * k, 4);
#pragma unroll
        for (int k = 0; k < 3; k++) mbar_init(sb + BAR_CSLD + 8 * k, 1);
        mbar_init(sb + BAR_XGO, 4);
        sts_f2(sb + OFF_ZERO, 0.f, 0.f);
        sts_f2(sb + OFF_ZERO + 8, 0.f, 0.f);
        asm volatile("fence.mbarrier_init.release.cluster;" ::: "memory");
      }
      __syncwarp();
      cluster_arrive();
      if (w == 2) {
        if (lane < 28) write_run_desc(sb, lane >> 1, lane & 1);
        bar_arrive(BAR_INIT, 160);
      }
      cluster_wait();
      if (w == 1) producer<true>(p, sb, m, n, lane);
      else if (w == 3) colsum_helper(p, sb, m, n, lane);
      else if (elect_one()) publisher(p, sb, m, n);
    } else {
      const bool leader = elect_one();
      if (leader) {
#pragma unroll
        for (int k = 0; k < 4; k++) mbar_init(sb + BAR_FULL + 8 * k, 2);
        asm volatile("fence.mbarrier_init.release.cluster;" ::: "memory");
      }
      __syncwarp();
      bar_arrive(BAR_INIT0, 160);
      cluster_arrive();
      if (leader) {
#pragma unroll 1
        for (int k = 0; k < 4; k++) {
          const uint32_t fb = sb + BAR_FULL + 8 * k;
          mbar_expect_tx(fb, 16384);
          tma_ld_act(sb + (5 * k + 3) * UNIT, &p.t.xin, fb, 64 * k, m);
          mbar_expect_tx(fb, 3 * UNIT);
          tma_ld3(sb + 5 * k * UNIT, &p.t.wqkv, fb, 128 * n, 64 * k, 0);
          tma_ld3(sb + 5 * k * UNIT + 12288, &p.t.wqkv, fb, 128 * n, 64 * k + 32, 0);
        }
      }
      __syncwarp();
      cluster_wait();
      producer<false>(p, sb, m, n, lane);
    }
  }
}

typedef CUresult (*EncodeFn)(CUtensorMap*, CUtensorMapDataType, cuuint32_t, void*, const cuuint64_t*, const cuuint64_t*,
                             const cuuint32_t*, const cuuint32_t*, CUtensorMapInterleave, CUtensorMapSwizzle,
                             CUtensorMapL2promotion, CUtensorMapFloatOOBfill);

void make_2d(EncodeFn enc, CUtensorMap* m, const void* ptr, uint64_t cols, uint64_t rows, uint32_t box_rows) {
  cuuint64_t d[2] = {cols, rows}, st[1] = {cols * 2};
  cuuint32_t b[2] = {64, box_rows}, e[2] = {1, 1};
  enc(m, CU_TENSOR_MAP_DATA_TYPE_BFLOAT16, 2, const_cast<void*>(ptr), d, st, b, e, CU_TENSOR_MAP_INTERLEAVE_NONE,
      CU_TENSOR_MAP_SWIZZLE_128B, CU_TENSOR_MAP_L2_PROMOTION_L2_128B, CU_TENSOR_MAP_FLOAT_OOB_FILL_NONE);
}
void make_act(EncodeFn enc, CUtensorMap* m, const void* ptr, uint64_t cols, bool split, uint32_t box = 2, uint32_t rows = 32) {
  const uint64_t row = cols * 2;
  cuuint64_t d[4] = {cols, 32, 2, SEQ / 64}, st[3] = {split ? 2 * row : row, split ? row : 32 * row, 64 * row};
  cuuint32_t b[4] = {64, rows, box, box}, e[4] = {1, 1, 1, 1};
  enc(m, CU_TENSOR_MAP_DATA_TYPE_BFLOAT16, 4, const_cast<void*>(ptr), d, st, b, e, CU_TENSOR_MAP_INTERLEAVE_NONE,
      CU_TENSOR_MAP_SWIZZLE_128B, CU_TENSOR_MAP_L2_PROMOTION_L2_128B, CU_TENSOR_MAP_FLOAT_OOB_FILL_NONE);
}
void make_3d(EncodeFn enc, CUtensorMap* m, const void* ptr, uint64_t d0, uint64_t rows, uint64_t d2, uint64_t row_bytes,
             uint64_t chunk_bytes, uint32_t box_chunks) {
  cuuint64_t d[3] = {d0, rows, d2}, st[2] = {row_bytes, chunk_bytes};
  cuuint32_t b[3] = {64, 32, box_chunks}, e[3] = {1, 1, 1};
  enc(m, CU_TENSOR_MAP_DATA_TYPE_BFLOAT16, 3, const_cast<void*>(ptr), d, st, b, e, CU_TENSOR_MAP_INTERLEAVE_NONE,
      CU_TENSOR_MAP_SWIZZLE_128B, CU_TENSOR_MAP_L2_PROMOTION_L2_128B, CU_TENSOR_MAP_FLOAT_OOB_FILL_NONE);
}

}

extern "C" void kernel_launch(void* const* d_in, const int* in_sizes, int n_in, void* d_out, int out_size) {
  (void)in_sizes; (void)n_in; (void)out_size;
  static EncodeFn enc = nullptr;
  static void *att = nullptr, *hbuf = nullptr, *scratch = nullptr;
  static int by_smid = 0;
  if (!enc) {
    void* fn = nullptr;
    cudaDriverEntryPointQueryResult q;
    cudaGetDriverEntryPoint("cuTensorMapEncodeTiled", &fn, cudaEnableDefault, &q);
    enc = (EncodeFn)fn;
    cudaGetSymbolAddress(&att, g_att);
    cudaGetSymbolAddress(&hbuf, g_h);
    cudaGetSymbolAddress(&scratch, g_scratch);
    cudaFuncSetAttribute(fused_layers_kernel<true>, cudaFuncAttributeMaxDynamicSharedMemorySize, SMEM_BYTES);
    cudaFuncSetAttribute(fused_layers_kernel<false>, cudaFuncAttributeMaxDynamicSharedMemorySize, SMEM_BYTES);
    int sms = 0, clusters = 0, dev = 0;
    cudaGetDevice(&dev);
    cudaDeviceGetAttribute(&sms, cudaDevAttrMultiProcessorCount, dev);
    cudaLaunchConfig_t cfg = {};
    cfg.gridDim = dim3(132);
    cfg.blockDim = dim3(384);
    cfg.dynamicSmemBytes = SMEM_BYTES;
    cudaLaunchAttribute at[1];
    at[0].id = cudaLaunchAttributeClusterDimension;
    at[0].val.clusterDim.x = 2; at[0].val.clusterDim.y = 1; at[0].val.clusterDim.z = 1;
    cfg.attrs = at;
    cfg.numAttrs = 1;
    if (cudaOccupancyMaxActiveClusters(&clusters, fused_layers_kernel<true>, &cfg) != cudaSuccess) (void)cudaGetLastError();
    by_smid = sms == 132 && clusters == 66;
  }
  Maps p;
  Scalars sc;
  make_act(enc, &p.xin, d_in[0], DM, true);
  make_act(enc, &p.out, d_out, DM, true);
  make_act(enc, &p.out_w, d_out, DM, true, 1);
  make_act(enc, &p.out_8, d_out, DM, true, 1, 8);
  make_act(enc, &p.att, att, DM, false);
  make_act(enc, &p.h, hbuf, FF, false);
  make_2d(enc, &p.att_st, att, DM, SEQ, 32);
  make_2d(enc, &p.h_st, hbuf, FF, SEQ, 32);
  make_2d(enc, &p.w1c, d_in[4], FF, DM, 32);
  make_3d(enc, &p.wqkv, d_in[1], DM, DM, 3, 3 * DM * 2, DM * 2, 3);
  make_3d(enc, &p.wo, d_in[2], 64, DM, DM / 64, DM * 2, 128, 2);
  make_3d(enc, &p.w1a, d_in[4], 64, DM, FF / 64, FF * 2, 128, 3);
  make_3d(enc, &p.w1b, d_in[4], 64, DM, FF / 64, FF * 2, 128, 2);
  make_3d(enc, &p.w2, d_in[6], 64, FF, DM / 64, DM * 2, 128, 2);
  sc.b1 = (const __nv_bfloat16*)d_in[5];
  sc.b2 = (const __nv_bfloat16*)d_in[7];
  sc.g = (Scratch*)scratch;
  sc.zero = 0;
  if (by_smid) fused_layers_kernel<true><<<132, 384, SMEM_BYTES>>>(sc, p);
  else fused_layers_kernel<false><<<NCTA, 384, SMEM_BYTES>>>(sc, p);
}
```

```cpp
#include <cuda_runtime.h>
#include <cuda_bf16.h>
#include <cuda.h>
#include <stdint.h>
#include <type_traits>

namespace {

constexpr int SEQ = 2048, DM = 1024, FF = 3584;
constexpr int NCTA = 128;
constexpr int NBAR = 5;

constexpr uint32_t RING_UNITS = 20, UNIT = 8192;
constexpr uint32_t OFF_X   = RING_UNITS * UNIT;
constexpr uint32_t OFF_STG = OFF_X + 32768;
constexpr uint32_t OFF_HLP = OFF_STG + 16384;
constexpr uint32_t OFF_RUN = OFF_STG + 24576;
constexpr uint32_t OFF_CSQ = OFF_RUN + 512;
constexpr uint32_t OFF_CSF = OFF_CSQ + 2048;
constexpr uint32_t OFF_ROW = OFF_CSF + 3584;
constexpr uint32_t OFF_HALF = OFF_ROW + 1024;
constexpr uint32_t OFF_BAR = OFF_HALF + 1024;
constexpr uint32_t SMEM_BYTES = OFF_BAR + 384;
constexpr uint32_t BAR_FULL = OFF_BAR, BAR_EMPTY = OFF_BAR + 8 * NBAR;
constexpr uint32_t BAR_XRDY = OFF_BAR + 80;
constexpr uint32_t BAR_DUMMY = OFF_BAR + 96, OFF_TAG = OFF_BAR + 104, OFF_ZERO = OFF_BAR + 112;
constexpr uint32_t BAR_PUB = OFF_BAR + 128;
constexpr uint32_t BAR_CSLD = OFF_BAR + 200;
constexpr uint32_t BAR_BIAS = OFF_BAR + 216;
constexpr uint32_t BAR_XGO = OFF_BAR + 224;

constexpr uint64_t DESC_A = (1ull << 62) | ((uint64_t)(2048 >> 4) << 32) | (1ull << 16);
constexpr uint64_t DESC_B = (1ull << 62) | ((uint64_t)(1024 >> 4) << 32) | ((uint64_t)(4096 >> 4) << 16);

constexpr int BAR_INIT = 0, BAR_ORDER = 1, BAR_GUARD = 3, BAR_WG = 5, BAR_GO = 7, BAR_DONE = 8, BAR_HLP = 9;
constexpr int BAR_INIT0 = 10, BAR_PAIR = 11, BAR_STAT = 15;

constexpr int WIN1 = 5;
constexpr int WIN0 = 7;
constexpr int SKEW = 3;
static_assert(SKEW == 3, "the slices of the skewed tails assume three k-blocks");
constexpr int WIN2 = 1;
constexpr int GELU_DEP = 2;
constexpr int STG_WAIT = 5;
constexpr int HALO_NS = 200;
constexpr int STAT_NS = 800;
constexpr int CS_NS = 500;
constexpr int XB_NS = 400;
constexpr int XB_GAP_NS = 50;
constexpr int STAG_NS = 450;
constexpr int PACE_M = 100;
constexpr int PACE_N = 300;

struct Scratch {
  uint4 stats[4 * 8 * SEQ];
  uint4 halo[2 * 2 * 16 * 8 * 384];
  uint4 csp[2 * 8 * 17 * 224];
  uint32_t flags[16 * 32];
  uint32_t epoch[NCTA + 4];
};

struct Maps {
  CUtensorMap xin, out, att, h, wqkv, wo, w1a, w1b, w2, att_st, h_st, w1c, out_w, out_8;
};
struct Scalars {
  Scratch* g;
  const __nv_bfloat16 *b1, *b2;
  uint32_t zero;
};
struct Params : Scalars {
  const Maps& t;
};

__device__ __align__(1024) __nv_bfloat16 g_att[SEQ * DM];
__device__ __align__(1024) __nv_bfloat16 g_h[SEQ * FF];
__device__ __align__(1024) Scratch g_scratch;

__device__ __forceinline__ void mbar_init(uint32_t bar, int cnt) {
  asm volatile("mbarrier.init.shared::cta.b64 [%0], %1;" ::"r"(bar), "r"(cnt));
}
__device__ __forceinline__ void mbar_expect_tx(uint32_t bar, uint32_t bytes) {
  asm volatile("mbarrier.arrive.expect_tx.shared::cta.b64 _, [%0], %1;" ::"r"(bar), "r"(bytes) : "memory");
}
__device__ __forceinline__ void mbar_arrive(uint32_t bar) {
  asm volatile("mbarrier.arrive.shared::cta.b64 _, [%0];" ::"r"(bar) : "memory");
}
__device__ __forceinline__ bool mbar_test(uint32_t bar, uint32_t parity) {
  uint32_t ok;
  asm volatile("{\n.reg .pred p;\nmbarrier.test_wait.parity.shared::cta.b64 p, [%1], %2;\nselp.u32 %0, 1, 0, p;\n}"
               : "=r"(ok) : "r"(bar), "r"(parity) : "memory");
  return ok;
}
__device__ __forceinline__ void mbar_wait(uint32_t bar, uint32_t parity) {
  asm volatile(
      "{\n.reg .pred p;\n.reg .u32 it;\nmov.u32 it, 0;\n"
      "WAIT_LOOP:\n"
      "mbarrier.try_wait.parity.shared::cta.b64 p, [%0], %1;\n"
      "@p bra WAIT_DONE;\n"
      "add.u32 it, it, 1;\n"
      "setp.lt.u32 p, it, 0x400000;\n"
      "@p bra WAIT_LOOP;\n"
      "trap;\n"
      "WAIT_DONE:\n}"
      ::"r"(bar), "r"(parity) : "memory");
}
__device__ __forceinline__ void bar_sync(int id, int n) { asm volatile("bar.sync %0, %1;" ::"r"(id), "r"(n) : "memory"); }
__device__ __forceinline__ void bar_arrive(int id, int n) { asm volatile("bar.arrive %0, %1;" ::"r"(id), "r"(n) : "memory"); }
__device__ __forceinline__ void tma_ld2(uint32_t dst, const CUtensorMap* m, uint32_t bar, int c0, int c1) {
  asm volatile("cp.async.bulk.tensor.2d.shared::cluster.global.mbarrier::complete_tx::bytes [%0], [%1, {%3, %4}], [%2];"
               ::"r"(dst), "l"(m), "r"(bar), "r"(c0), "r"(c1) : "memory");
}
__device__ __forceinline__ void tma_ld_act(uint32_t dst, const CUtensorMap* m, uint32_t bar, int col, int blk) {
  asm volatile("cp.async.bulk.tensor.4d.shared::cluster.global.mbarrier::complete_tx::bytes [%0], [%1, {%3, %5, %5, %4}], [%2];"
               ::"r"(dst), "l"(m), "r"(bar), "r"(col), "r"(2 * blk), "r"(0) : "memory");
}
__device__ __forceinline__ void tma_st_warp(const CUtensorMap* m, uint32_t src, int col, int blk, int w, int row = 0) {
  asm volatile("cp.async.bulk.tensor.4d.global.shared::cta.bulk_group [%0, {%2, %5, %3, %4}], [%1];"
               ::"l"(m), "r"(src), "r"(col), "r"(w & 1), "r"(2 * blk + (w >> 1)), "r"(row) : "memory");
}
__device__ __forceinline__ void tma_ld3(uint32_t dst, const CUtensorMap* m, uint32_t bar, int c0, int c1, int c2) {
  asm volatile("cp.async.bulk.tensor.3d.shared::cluster.global.mbarrier::complete_tx::bytes [%0], [%1, {%3, %4, %5}], [%2];"
               ::"r"(dst), "l"(m), "r"(bar), "r"(c0), "r"(c1), "r"(c2) : "memory");
}
__device__ __forceinline__ void tma_ld3_pair(uint32_t dst, const CUtensorMap* m, uint32_t bar, int c0, int c1, int c2) {
  asm volatile("cp.async.bulk.tensor.3d.shared::cluster.global.mbarrier::complete_tx::bytes.multicast::cluster"
               " [%0], [%1, {%3, %4, %5}], [%2], %6;"
               ::"r"(dst), "l"(m), "r"(bar), "r"(c0), "r"(c1), "r"(c2), "h"((uint16_t)3) : "memory");
}
__device__ __forceinline__ uint32_t pair_offset(uint32_t sb, uint32_t rank) {
  uint32_t r;
  asm volatile("mapa.shared::cluster.u32 %0, %1, %2;" : "=r"(r) : "r"(sb), "r"(rank));
  return r - sb;
}
__device__ __forceinline__ void mbar_arrive_cluster(uint32_t bar) {
  asm volatile("mbarrier.arrive.shared::cluster.b64 _, [%0];" ::"r"(bar) : "memory");
}
__device__ __forceinline__ void cluster_arrive() { asm volatile("barrier.cluster.arrive.relaxed;" ::: "memory"); }
__device__ __forceinline__ void cluster_wait() { asm volatile("barrier.cluster.wait.acquire;" ::: "memory"); }
__device__ __forceinline__ void tma_st2(const CUtensorMap* m, uint32_t src, int c0, int c1) {
  asm volatile("cp.async.bulk.tensor.2d.global.shared::cta.bulk_group [%0, {%2, %3}], [%1];"
               ::"l"(m), "r"(src), "r"(c0), "r"(c1) : "memory");
}
__device__ __forceinline__ void bulk_commit() { asm volatile("cp.async.bulk.commit_group;" ::: "memory"); }
__device__ __forceinline__ void bulk_wait_read() { asm volatile("cp.async.bulk.wait_group.read 0;" ::: "memory"); }
__device__ __forceinline__ void bulk_wait_all() { asm volatile("cp.async.bulk.wait_group 0;" ::: "memory"); }
__device__ __forceinline__ void fence_async_smem() { asm volatile("fence.proxy.async.shared::cta;" ::: "memory"); }
__device__ __forceinline__ void fence_async_global() { asm volatile("fence.proxy.async.global;" ::: "memory"); }
__device__ __forceinline__ void st_relaxed(uint32_t* p, uint32_t v) {
  asm volatile("st.relaxed.gpu.global.u32 [%0], %1;" ::"l"(p), "r"(v) : "memory");
}
__device__ __forceinline__ void st_msg(uint4* p, uint32_t a, uint32_t b, uint32_t c, uint32_t tag) {
  asm volatile("{\n.reg .b128 v;\nmov.b128 v, {%1, %2, %3, %4};\nst.relaxed.gpu.global.b128 [%0], v;\n}"
               ::"l"(p), "r"(a), "r"(b), "r"(c), "r"(tag) : "memory");
}
__device__ __forceinline__ void ld_msg(const uint4* p, uint32_t& a, uint32_t& b, uint32_t& c, uint32_t& tag) {
  asm volatile("{\n.reg .b128 v;\nld.relaxed.gpu.global.b128 v, [%4];\nmov.b128 {%0, %1, %2, %3}, v;\n}"
               : "=r"(a), "=r"(b), "=r"(c), "=r"(tag) : "l"(p) : "memory");
}
__device__ __forceinline__ bool elect_one() {
  uint32_t ok;
  asm volatile("{\n.reg .pred p;\nelect.sync _|p, 0xffffffff;\nselp.u32 %0, 1, 0, p;\n}" : "=r"(ok));
  return ok;
}
__device__ __forceinline__ uint32_t lanemask_lt() {
  uint32_t v;
  asm("mov.u32 %0, %%lanemask_lt;" : "=r"(v));
  return v;
}
__device__ __forceinline__ int uniform(int v) { return __shfl_sync(0xffffffffu, v, 0); }
__device__ __forceinline__ uint32_t pack_bf16(float lo, float hi) {
  uint32_t r;
  asm("cvt.rn.bf16x2.f32 %0, %1, %2;" : "=r"(r) : "f"(hi), "f"(lo));
  return r;
}
__device__ __forceinline__ float prmt_f(uint32_t a, uint32_t sel) {
  float r;
  asm("{\n.reg .b32 t;\nprmt.b32 t, %1, 0, %2;\nmov.b32 %0, t;\n}" : "=f"(r) : "r"(a), "r"(sel));
  return r;
}
__device__ __forceinline__ float bf_lo(uint32_t v) { return __uint_as_float(v << 16); }
__device__ __forceinline__ float bf_hi(uint32_t v) { return __uint_as_float(v & 0xffff0000u); }
__device__ __forceinline__ void stsm4(uint32_t addr, uint32_t r0, uint32_t r1, uint32_t r2, uint32_t r3) {
  asm volatile("stmatrix.sync.aligned.m8n8.x4.shared.b16 [%0], {%1, %2, %3, %4};"
               ::"r"(addr), "r"(r0), "r"(r1), "r"(r2), "r"(r3) : "memory");
}
__device__ __forceinline__ void ldsm4(uint32_t addr, uint32_t& r0, uint32_t& r1, uint32_t& r2, uint32_t& r3) {
  asm volatile("ldmatrix.sync.aligned.m8n8.x4.shared.b16 {%0, %1, %2, %3}, [%4];"
               : "=r"(r0), "=r"(r1), "=r"(r2), "=r"(r3) : "r"(addr) : "memory");
}
__device__ __forceinline__ uint32_t movtrans(uint32_t a) {
  uint32_t d;
  asm volatile("movmatrix.sync.aligned.m8n8.trans.b16 %0, %1;" : "=r"(d) : "r"(a));
  return d;
}
__device__ __forceinline__ void mma16816(float (&c)[4], uint32_t a0, uint32_t a1, uint32_t a2, uint32_t a3, uint32_t b0, uint32_t b1) {
  asm volatile("mma.sync.aligned.m16n8k16.row.col.f32.bf16.bf16.f32 {%0,%1,%2,%3}, {%4,%5,%6,%7}, {%8,%9}, {%0,%1,%2,%3};"
               : "+f"(c[0]), "+f"(c[1]), "+f"(c[2]), "+f"(c[3])
               : "r"(a0), "r"(a1), "r"(a2), "r"(a3), "r"(b0), "r"(b1));
}
__device__ __forceinline__ void mma1688(float (&c)[4], uint32_t a0, uint32_t a1, uint32_t b0) {
  asm volatile("mma.sync.aligned.m16n8k8.row.col.f32.bf16.bf16.f32 {%0,%1,%2,%3}, {%4,%5}, {%6}, {%0,%1,%2,%3};"
               : "+f"(c[0]), "+f"(c[1]), "+f"(c[2]), "+f"(c[3]) : "r"(a0), "r"(a1), "r"(b0));
}
__device__ __forceinline__ float2 lds_f2(uint32_t a) {
  float2 v;
  asm volatile("ld.shared.v2.f32 {%0, %1}, [%2];" : "=f"(v.x), "=f"(v.y) : "r"(a) : "memory");
  return v;
}
__device__ __forceinline__ float4 lds_f4(uint32_t a) {
  float4 v;
  asm volatile("ld.shared.v4.f32 {%0, %1, %2, %3}, [%4];" : "=f"(v.x), "=f"(v.y), "=f"(v.z), "=f"(v.w) : "r"(a) : "memory");
  return v;
}
__device__ __forceinline__ float lds_f(uint32_t a) {
  float v;
  asm volatile("ld.shared.f32 %0, [%1];" : "=f"(v) : "r"(a) : "memory");
  return v;
}
__device__ __forceinline__ uint32_t lds_u(uint32_t a) {
  uint32_t v;
  asm volatile("ld.shared.u32 %0, [%1];" : "=r"(v) : "r"(a) : "memory");
  return v;
}
__device__ __forceinline__ void sts_f2(uint32_t a, float x, float y) {
  asm volatile("st.shared.v2.f32 [%0], {%1, %2};" ::"r"(a), "f"(x), "f"(y) : "memory");
}
__device__ __forceinline__ void sts_u4(uint32_t a, uint32_t x, uint32_t y, uint32_t z, uint32_t w) {
  asm volatile("st.shared.v4.u32 [%0], {%1, %2, %3, %4};" ::"r"(a), "r"(x), "r"(y), "r"(z), "r"(w) : "memory");
}
__device__ __forceinline__ void lds_u4(uint32_t a, uint32_t& x, uint32_t& y, uint32_t& z, uint32_t& w) {
  asm volatile("ld.shared.v4.u32 {%0, %1, %2, %3}, [%4];" : "=r"(x), "=r"(y), "=r"(z), "=r"(w) : "r"(a) : "memory");
}
__device__ __forceinline__ float ex2(float x) {
  float y;
  asm("ex2.approx.ftz.f32 %0, %1;" : "=f"(y) : "f"(x));
  return y;
}
__device__ __forceinline__ float rcp_hw(float x) {
  float y;
  asm("rcp.approx.ftz.f32 %0, %1;" : "=f"(y) : "f"(x));
  return y;
}
__device__ __forceinline__ float tanh_hw(float x) {
  float y;
  asm("tanh.approx.f32 %0, %1;" : "=f"(y) : "f"(x));
  return y;
}
__device__ __forceinline__ float quad_sum(float v) {
  v += __shfl_xor_sync(0xffffffffu, v, 1);
  return v + __shfl_xor_sync(0xffffffffu, v, 2);
}
__device__ __forceinline__ float quad_max(float v) {
  v = fmaxf(v, __shfl_xor_sync(0xffffffffu, v, 1));
  return fmaxf(v, __shfl_xor_sync(0xffffffffu, v, 2));
}

template <int N> __device__ __forceinline__ void wgmma_ss(float (&d)[96], uint64_t da, uint64_t db, uint32_t keep = 1);
template <> __device__ __forceinline__ void wgmma_ss<128>(float (&d)[96], uint64_t da, uint64_t db, uint32_t keep) {
  asm volatile(
      "{\n.reg .pred p;\nsetp.ne.u32 p, %66, 0;\n"
      "wgmma.mma_async.sync.aligned.m64n128k16.f32.bf16.bf16 {%0, %1, %2, %3, %4, %5, %6, %7, %8, %9, %10, %11, %12, %13, %14, %15, %16, %17, %18, %19, %20, %21, %22, %23, %24, %25, %26, %27, %28, %29, %30, %31, %32, %33, %34, %35, %36, %37, %38, %39, %40, %41, %42, %43, %44, %45, %46, %47, %48, %49, %50, %51, %52, %53, %54, %55, %56, %57, %58, %59, %60, %61, %62, %63}, %64, %65, p, 1, 1, 0, 1;\n}"
      : "+f"(d[0]), "+f"(d[1]), "+f"(d[2]), "+f"(d[3]), "+f"(d[4]), "+f"(d[5]), "+f"(d[6]), "+f"(d[7]), "+f"(d[8]), "+f"(d[9]), "+f"(d[10]), "+f"(d[11]), "+f"(d[12]), "+f"(d[13]), "+f"(d[14]), "+f"(d[15]), "+f"(d[16]), "+f"(d[17]), "+f"(d[18]), "+f"(d[19]), "+f"(d[20]), "+f"(d[21]), "+f"(d[22]), "+f"(d[23]), "+f"(d[24]), "+f"(d[25]), "+f"(d[26]), "+f"(d[27]), "+f"(d[28]), "+f"(d[29]), "+f"(d[30]), "+f"(d[31]), "+f"(d[32]), "+f"(d[33]), "+f"(d[34]), "+f"(d[35]), "+f"(d[36]), "+f"(d[37]), "+f"(d[38]), "+f"(d[39]), "+f"(d[40]), "+f"(d[41]), "+f"(d[42]), "+f"(d[43]), "+f"(d[44]), "+f"(d[45]), "+f"(d[46]), "+f"(d[47]), "+f"(d[48]), "+f"(d[49]), "+f"(d[50]), "+f"(d[51]), "+f"(d[52]), "+f"(d[53]), "+f"(d[54]), "+f"(d[55]), "+f"(d[56]), "+f"(d[57]), "+f"(d[58]), "+f"(d[59]), "+f"(d[60]), "+f"(d[61]), "+f"(d[62]), "+f"(d[63])
      : "l"(da), "l"(db), "r"(keep));
}

template <> __device__ __forceinline__ void wgmma_ss<192>(float (&d)[96], uint64_t da, uint64_t db, uint32_t keep) {
  asm volatile(
      "{\n.reg .pred p;\nsetp.ne.u32 p, %98, 0;\n"
      "wgmma.mma_async.sync.aligned.m64n192k16.f32.bf16.bf16 {%0, %1, %2, %3, %4, %5, %6, %7, %8, %9, %10, %11, %12, %13, %14, %15, %16, %17, %18, %19, %20, %21, %22, %23, %24, %25, %26, %27, %28, %29, %30, %31, %32, %33, %34, %35, %36, %37, %38, %39, %40, %41, %42, %43, %44, %45, %46, %47, %48, %49, %50, %51, %52, %53, %54, %55, %56, %57, %58, %59, %60, %61, %62, %63, %64, %65, %66, %67, %68, %69, %70, %71, %72, %73, %74, %75, %76, %77, %78, %79, %80, %81, %82, %83, %84, %85, %86, %87, %88, %89, %90, %91, %92, %93, %94, %95}, %96, %97, p, 1, 1, 0, 1;\n}"
      : "+f"(d[0]), "+f"(d[1]), "+f"(d[2]), "+f"(d[3]), "+f"(d[4]), "+f"(d[5]), "+f"(d[6]), "+f"(d[7]), "+f"(d[8]), "+f"(d[9]), "+f"(d[10]), "+f"(d[11]), "+f"(d[12]), "+f"(d[13]), "+f"(d[14]), "+f"(d[15]), "+f"(d[16]), "+f"(d[17]), "+f"(d[18]), "+f"(d[19]), "+f"(d[20]), "+f"(d[21]), "+f"(d[22]), "+f"(d[23]), "+f"(d[24]), "+f"(d[25]), "+f"(d[26]), "+f"(d[27]), "+f"(d[28]), "+f"(d[29]), "+f"(d[30]), "+f"(d[31]), "+f"(d[32]), "+f"(d[33]), "+f"(d[34]), "+f"(d[35]), "+f"(d[36]), "+f"(d[37]), "+f"(d[38]), "+f"(d[39]), "+f"(d[40]), "+f"(d[41]), "+f"(d[42]), "+f"(d[43]), "+f"(d[44]), "+f"(d[45]), "+f"(d[46]), "+f"(d[47]), "+f"(d[48]), "+f"(d[49]), "+f"(d[50]), "+f"(d[51]), "+f"(d[52]), "+f"(d[53]), "+f"(d[54]), "+f"(d[55]), "+f"(d[56]), "+f"(d[57]), "+f"(d[58]), "+f"(d[59]), "+f"(d[60]), "+f"(d[61]), "+f"(d[62]), "+f"(d[63]), "+f"(d[64]), "+f"(d[65]), "+f"(d[66]), "+f"(d[67]), "+f"(d[68]), "+f"(d[69]), "+f"(d[70]), "+f"(d[71]), "+f"(d[72]), "+f"(d[73]), "+f"(d[74]), "+f"(d[75]), "+f"(d[76]), "+f"(d[77]), "+f"(d[78]), "+f"(d[79]), "+f"(d[80]), "+f"(d[81]), "+f"(d[82]), "+f"(d[83]), "+f"(d[84]), "+f"(d[85]), "+f"(d[86]), "+f"(d[87]), "+f"(d[88]), "+f"(d[89]), "+f"(d[90]), "+f"(d[91]), "+f"(d[92]), "+f"(d[93]), "+f"(d[94]), "+f"(d[95])
      : "l"(da), "l"(db), "r"(keep));
}

template <int R>
__device__ __forceinline__ void pin_regs(float (&a)[2][96]) {
#pragma unroll
  for (int m = 0; m < 2; m++)
#pragma unroll
    for (int i = 0; i < R; i++) asm volatile("" : "+f"(a[m][i])::"memory");
}

struct Ctx {
  uint32_t sb;
  int m, n, wg, w, lane;
};
__device__ __forceinline__ Ctx make_ctx(uint32_t sb, int id) {
  int lane;
  asm volatile("mov.u32 %0, %%laneid;" : "=r"(lane));
  asm volatile("" : "+r"(id), "+r"(sb));
  return Ctx{sb, (id >> 3) & 15, id & 7, id >> 9, (id >> 7) & 3, lane};
}
#define UNPACK_CTX(c) const uint32_t sb = c.sb; const int m = c.m, n = c.n, wg = c.wg, w = c.w, lane = c.lane

__device__ __forceinline__ uint32_t poll_line(const uint32_t* word, uint32_t target, uint32_t need) {
  uint32_t v;
  asm volatile(
      "{\n.reg .pred p;\n.reg .u32 it, m;\n.reg .s32 d;\nmov.u32 it, 0;\n"
      "POLL_LOOP:\n"
      "ld.relaxed.gpu.global.u32 %0, [%1];\n"
      "sub.s32 d, %0, %2;\n"
      "setp.ge.s32 p, d, 0;\n"
      "vote.sync.ballot.b32 m, p, 0xffffffff;\n"
      "and.b32 m, m, %3;\n"
      "setp.eq.u32 p, m, %3;\n"
      "@p bra.uni POLL_DONE;\n"
      "add.u32 it, it, 1;\n"
      "setp.lt.u32 p, it, 0x400000;\n"
      "@p bra.uni POLL_LOOP;\n"
      "trap;\n"
      "POLL_DONE:\n}"
      : "=&r"(v) : "l"(word), "r"(target), "r"(need) : "memory");
  return v;
}
__device__ __forceinline__ uint32_t ld_relaxed(const uint32_t* p) {
  uint32_t v;
  asm volatile("ld.relaxed.gpu.global.u32 %0, [%1];" : "=r"(v) : "l"(p) : "memory");
  return v;
}
__device__ __forceinline__ float chain(float x, uint32_t on, uint32_t zero) {
  return __uint_as_float(__float_as_uint(x) | (on & zero));
}
constexpr int MSG_SPINS = 1 << 20;

constexpr int STAGES_PER_LAYER = 152;
__device__ __forceinline__ int nib(uint64_t v, int i) { return (int)(v >> (4 * i)) & 15; }
__device__ __forceinline__ bool tile_wide(int t) { return (0x23 >> t) & 1; }
__device__ __forceinline__ void weight_coords(const Params& p, int t, int n, const CUtensorMap*& map, int& c0, int& c2) {
  map = &p.t.wqkv + nib(0x4233100ull, t);
  c0 = t < 2 ? 128 * n + 64 * t : 0;
  c2 = t < 2 ? 0 : (t == 2 || t == 6) ? 2 * n : 7 * n + 2 * t - 6;
}

template <bool IS_A>
__device__ __forceinline__ void producer(const Params& p, uint32_t sb, int m, int n, int lane) {
  const uint32_t low = (1u << (4 * n)) - 1, others = (0x6543210u & low) | (0x7654321u & ~low);
  const uint64_t order_x = (uint64_t)(others * 2 + 0x1111111u) << 36 | (uint64_t)others * 2 << 8 | (n * 0x22 + 0x10);
  int inflight = 4, cur = 0;
  uint32_t fb = sb + BAR_FULL + 32, rb = sb + BAR_EMPTY, rph = 0, pos = 0, tag32 = 0, seen = 0;
  const uint32_t fend = sb + BAR_FULL + 8 * NBAR, rend = sb + BAR_EMPTY + 8 * NBAR;
  const uint32_t* word = p.g->flags + m * 32 + (lane < 16 ? lane >> 1 : lane & 7);
#pragma unroll 1
  for (int sg = 1; sg < 22; sg++) {
    const int layer = sg >= 11, s = sg == 1 ? 2 : sg == 2 ? 1 : sg - 11 * layer;
    const int t = nib(0x65434321010ull, s), kind = nib(0x32110031100ull, s);
    const bool wide = tile_wide(t);
    const uint32_t bbytes = wide ? 3 * UNIT : 2 * UNIT, base = sb + (IS_A ? bbytes : (m & 1) * (bbytes / 2));
    if (IS_A && kind == 0) {
      if (sg == 2) seen = tag32 = (__ldcg(p.g->epoch + m * 8 + n) + 1) << 5;
#pragma unroll 1
      for (int k = 0; k < 2; k++) {
#pragma unroll 1
        for (; inflight > (wide ? 3 : 4); inflight--) {
          mbar_wait(rb, rph);
          rb += 8;
          if (rb == rend) { rb -= 8 * NBAR; rph ^= 1; }
        }
        if (elect_one()) mbar_arrive(fb);
        inflight++;
        fb += 8;
        if (fb == fend) fb -= 8 * NBAR;
        pos += bbytes + 2 * UNIT;
        if (pos >= RING_UNITS * UNIT) pos -= RING_UNITS * UNIT;
      }
      continue;
    }
    const int mul = t == 6 ? 448 : t == 2 ? 128 : 64, count = sg == 1 ? 12 : 2 * nib(0x4871ull, kind);
    uint64_t order0 = sg == 1 ? 0xFEDCBA987654ull : kind == 3 ? 0x76543210u : order_x >> (8 * (kind & 1));
    uint32_t special = (s == 4 || s == 10) ? 0x10 : s == 9 ? 0x1F : s == 0;
    if (IS_A) special |= (kind & 1 ? 0 : 3) | (count >= 4 ? 1u << (count - 4) : 0);
    if (s >= 9) pos = (4 * s - 24) * UNIT;
    const CUtensorMap* map;
    int c0 = 0, c2 = 0, ev = 0;
    if (IS_A) {
      map = &p.t.xin + (t == 2 ? 2 : t == 6 ? 3 : sg >= 4);
      ev = 9 * layer + (t < 2 ? 0 : t == 2 ? 1 : t < 6 ? 4 : 5);
      if (elect_one()) asm volatile("prefetch.tensormap [%0];" ::"l"(map) : "memory");
    } else {
      weight_coords(p, t, n, map, c0, c2);
    }
#pragma unroll 1
    for (int add = 0; add < mul; add += 64) {
      uint64_t order = order0;
      const int need = kind == 3 ? ev : ev - 1 + (lane & 1), sh = kind == 3 ? 16 : 0;
      uint32_t ready = IS_A ? __ballot_sync(0xffffffffu, cur >= need) >> sh : 0;
#pragma unroll 1
      for (int k = 0; k < count; k++) {
        const int code = order & 15, kc = code * mul + add;
        order >>= 4;
        if ((special >> k) & 1) {
          const int lag = wide ? (s == 9 && k < 4 ? nib(0x2234, k) : 3) : ((s == 4 || s == 10) && add == 0 && k < 4) ? 3 : 4;
#pragma unroll 1
          for (; inflight > lag; inflight--) {
            mbar_wait(rb, rph);
            rb += 8;
            if (rb == rend) { rb -= 8 * NBAR; rph ^= 1; }
          }
          inflight++;
          if (IS_A) {
            if (kind == 3 ? t == 2 && add + k == 64 : !(kind & 1) && k < 2) {
              if (t == 2) mbar_wait(sb + BAR_PUB + 8, layer);
              if (elect_one()) mbar_arrive(fb);
              goto next_stage;
            }
            if (k == count - 4 && sg >= 3) seen = ld_relaxed(word);
          }
        } else {
          mbar_wait(rb, rph);
          rb += 8;
          if (rb == rend) { rb -= 8 * NBAR; rph ^= 1; }
        }
        if (IS_A && !((ready >> code) & 1)) {
          cur = max(cur, (int)(seen - tag32));
          ready = __ballot_sync(0xffffffffu, cur >= need) >> sh;
          if (!((ready >> code) & 1)) {
            cur = (int)(poll_line(word, tag32 + need, 1u << (code + sh)) - tag32);
            ready = __ballot_sync(0xffffffffu, cur >= need) >> sh;
          }
          asm volatile("fence.acquire.gpu;" ::: "memory");
          fence_async_global();
          seen = ld_relaxed(word);
        }
        if (elect_one()) {
          if (!IS_A) tma_ld3_pair(base + pos, map, fb, c0, kc + 32 * (m & 1), c2);
          else tma_ld_act(base + pos, map, fb, kc, m);
          mbar_expect_tx(fb, IS_A ? 16384 : bbytes);
        }
      next_stage:
        fb += 8;
        if (fb == fend) fb -= 8 * NBAR;
        pos += bbytes + 2 * UNIT;
        if (pos > 16 * UNIT) pos = 0;
      }
      special = !IS_A ? 0 : t == 2 ? 1 : add == 128 ? 0x10 : 0;
      if (t == 2) order0 = others << 4 | n;
      if (IS_A && (t == 2 || add == 64 || add == 192)) ev++;
    }
  }
}

__device__ __forceinline__ void publisher(const Params& p, uint32_t sb, int m, int n) {
  {
    const int ts = PACE_M * m, tx = PACE_N * n;
#pragma unroll 1
    for (int k = 0; k < 2; k++) {
      __nanosleep(k == 0 ? min(ts, tx) : abs(ts - tx));
      if ((ts <= tx) == (k == 0)) {
        mbar_expect_tx(sb + BAR_CSLD, 24576);
        tma_ld3(sb + OFF_STG, &p.t.wqkv, sb + BAR_CSLD, 128 * n, 64 * m, 0);
        tma_ld3(sb + OFF_STG + 12288, &p.t.wqkv, sb + BAR_CSLD, 128 * n, 64 * m + 32, 0);
      } else {
#pragma unroll 1
        for (int h = 0; h < 2; h++) {
          const uint32_t xr = sb + BAR_XRDY + 8 * h;
          mbar_expect_tx(xr, 16384);
          tma_ld_act(sb + OFF_X + h * 16384, &p.t.xin, xr, 128 * n + 64 * h, m);
          asm volatile("mbarrier.arrive.shared::cta.b64 _, [%0], 3;" ::"r"(xr) : "memory");
        }
      }
    }
  }
  const uint32_t tag = __ldcg(p.g->epoch + m * 8 + n) + 1;
  uint32_t* word = p.g->flags + m * 32 + n;
  st_relaxed(word, 32 * tag);
#pragma unroll 1
  for (int c = 0; c < 16; c++) {
    const int e = c >= 9 ? c - 9 : c;
    if (e == 2 || e == 7) mbar_wait(sb + BAR_XGO, e == 7);
    else mbar_wait(sb + BAR_PUB + 8 * e, c >= 9);
    asm volatile("fence.release.gpu;" ::: "memory");
    asm volatile("red.relaxed.gpu.global.add.u32 [%0], 1;" ::"l"(word) : "memory");
  }
  p.g->epoch[m * 8 + n] = tag;
}

__device__ __forceinline__ void sum_rows(uint32_t buf, int iters, float (&a)[8], int lane) {
  uint32_t addr = buf + (lane >> 3) * 128 + (((lane & 7) ^ (lane >> 3)) << 4);
#pragma unroll 1
  for (int it = 0; it < iters; it++) {
    uint32_t u[2][4];
    lds_u4(addr, u[0][0], u[0][1], u[0][2], u[0][3]);
    lds_u4((addr ^ 64) + 512, u[1][0], u[1][1], u[1][2], u[1][3]);
    addr += 1024;
#pragma unroll
    for (int e = 0; e < 8; e++) { a[2 * (e & 3)] += bf_lo(u[e >> 2][e & 3]); a[2 * (e & 3) + 1] += bf_hi(u[e >> 2][e & 3]); }
  }
}
__device__ __forceinline__ void publish_sums(const float (&a)[8], uint4* dst, int lane, uint32_t tag) {
  const bool u8 = lane & 8, u16 = lane & 16;
  float h4[4], h2[2];
#pragma unroll
  for (int e = 0; e < 4; e++) h4[e] = (u8 ? a[4 + e] : a[e]) + __shfl_xor_sync(0xffffffffu, u8 ? a[e] : a[4 + e], 8);
#pragma unroll
  for (int e = 0; e < 2; e++) h2[e] = (u16 ? h4[2 + e] : h4[e]) + __shfl_xor_sync(0xffffffffu, u16 ? h4[e] : h4[2 + e], 16);
  st_msg(dst + (lane & 7) * 4 + (u8 ? 2 : 0) + (u16 ? 1 : 0), __float_as_uint(h2[0]), __float_as_uint(h2[1]), 0u, tag);
}

__device__ __forceinline__ void colsum_helper(const Params& p, uint32_t sb, int m, int n, int lane) {
  const uint32_t tag = __ldcg(p.g->epoch + m * 8 + n) + 1;
#pragma unroll 1
  for (int k = lane; k < 288; k += 32) {
    const uint32_t bb = __ldg(reinterpret_cast<const uint32_t*>(k < 224 ? p.b1 + 448 * n : p.b2 + 128 * n - 448) + k);
    const float sc = k < 224 ? 0.5f : 1.f;
    sts_f2(sb + (k < 224 ? OFF_CSF + k * 16 + 8 : OFF_CSQ + 1536 + (k - 224) * 8), sc * bf_lo(bb), sc * bf_hi(bb));
  }
  __syncwarp();
  if (elect_one()) mbar_arrive(sb + BAR_BIAS);
  bar_sync(BAR_HLP, 160);
  {
    uint4* base = p.g->csp + n * 17 * 224 + 12 * m + min(lane & 15, 11);
    float s0 = 0.f, s1 = 0.f;
#pragma unroll 1
    for (int g = 0; g < 2; g++) {
      uint32_t x[4], y[4];
#pragma unroll 1
      for (int it = 0; it < MSG_SPINS; it++) {
        uint32_t bad = 0, z, tg;
        if (g == 0 || it > 0) __nanosleep(CS_NS);
#pragma unroll
        for (int k = 0; k < 4; k++) { ld_msg(base + (g * 8 + (lane >> 4) * 4 + k) * 224, x[k], y[k], z, tg); bad |= tg ^ tag; }
        if (__all_sync(0xffffffffu, bad == 0)) break;
      }
#pragma unroll
      for (int k = 0; k < 4; k++) { s0 += __uint_as_float(x[k]); s1 += __uint_as_float(y[k]); }
    }
    s0 += __shfl_xor_sync(0xffffffffu, s0, 16);
    s1 += __shfl_xor_sync(0xffffffffu, s1, 16);
    if (lane < 12) st_msg(base + 16 * 224, __float_as_uint(s0), __float_as_uint(s1), 0u, tag);
  }
#pragma unroll 1
  for (int c = 0; c < 7; c++) {
    float a[8] = {0.f, 0.f, 0.f, 0.f, 0.f, 0.f, 0.f, 0.f};
#pragma unroll 1
    for (int h = 0; h < 2; h++) {
      if (elect_one()) {
        mbar_expect_tx(sb + BAR_CSLD + 8, 4096);
        tma_ld2(sb + OFF_HLP, &p.t.w1c, sb + BAR_CSLD + 8, 448 * n + 64 * c, 64 * m + 32 * h);
        if (c < 6) asm volatile("cp.async.bulk.prefetch.tensor.2d.L2.global [%0, {%1, %2}];" ::"l"(&p.t.w1c), "r"(448 * n + 64 * c + 64), "r"(64 * m + 32 * h) : "memory");
      }
      mbar_wait(sb + BAR_CSLD + 8, h);
      sum_rows(sb + OFF_HLP, 4, a, lane);
      __syncwarp();
    }
    publish_sums(a, p.g->csp + ((8 + n) * 17 + m) * 224 + c * 32, lane, tag);
  }
  if (elect_one()) {
#pragma unroll 1
    for (int k = 0; k < 3; k++) {
      mbar_wait(sb + BAR_XGO, k & 1);
      __nanosleep(XB_NS);
#pragma unroll 1
      for (int w = 0; w < 4; w++) {
        tma_st_warp(&p.t.out_w, sb + OFF_X + 16384 + w * 4096, 128 * n + 64, m, w);
        bulk_commit();
        bulk_wait_read();
        if (w < 3) __nanosleep(XB_GAP_NS);
      }
      bulk_wait_all();
      asm volatile("mbarrier.arrive.shared::cta.b64 _, [%0], 4;" ::"r"(sb + BAR_PUB + (k & 1 ? 64 : 24)) : "memory");
    }
  }
}

__device__ __forceinline__ void poll_msgs2(const uint4* pa, const uint4* pb, float (&v)[4], uint32_t tag) {
#pragma unroll 1
  for (int it = 0; it < MSG_SPINS; it++) {
    uint32_t x[4], z, ta, tb;
    ld_msg(pa, x[0], x[1], z, ta);
    ld_msg(pb, x[2], x[3], z, tb);
#pragma unroll
    for (int e = 0; e < 4; e++) v[e] = __uint_as_float(x[e]);
    if (__all_sync(0xffffffffu, ta == tag && tb == tag)) break;
  }
}
__device__ __forceinline__ void colsum_total(const Params& p, const Ctx& cx, int mat, uint32_t tag) {
  uint4* base = p.g->csp + (mat * 8 + cx.n) * 17 * 224;
  const int per = 12 + 2 * mat, k = 2 * cx.w + (cx.lane >> 4), ia = per * cx.m + k, ib = per * cx.m + min(k + 8, per - 1);
  float v[4];
  poll_msgs2(base + (cx.lane & 15) * 224 + ia, base + (cx.lane & 15) * 224 + ib, v, tag);
#pragma unroll 1
  for (int d = 1; d < 16; d *= 2)
#pragma unroll
    for (int e = 0; e < 4; e++) v[e] += __shfl_xor_sync(0xffffffffu, v[e], d);
  const bool hi = cx.lane & 1;
  if ((cx.lane & 14) == 0) st_msg(base + 16 * 224 + (hi ? ib : ia), __float_as_uint(hi ? v[2] : v[0]), __float_as_uint(hi ? v[3] : v[1]), 0u, tag);
}
__device__ __forceinline__ void colsum_gather(const Params& p, const Ctx& cx, int mat, uint32_t tag) {
  const uint4* base = p.g->csp + ((mat * 8 + cx.n) * 17 + 16) * 224;
  const int ia = cx.w * 32 + cx.lane, ib = min(ia + 128, 191 + 32 * mat);
  float v[4];
  poll_msgs2(base + ia, base + ib, v, tag);
  const uint32_t tab = cx.sb + (mat ? OFF_CSF : OFF_CSQ);
  sts_f2(tab + (ia << (3 + mat)), v[0], v[1]);
  sts_f2(tab + (ib << (3 + mat)), v[2], v[3]);
}

#define ACC(q, j, e) acc[(q) & 1][4 * (j) + 2 * ((q) >> 1) + (e)]

constexpr uint32_t RING16 = RING_UNITS * (UNIT >> 4);
__device__ __forceinline__ bool tile_split(int i) { return (0xD98 >> i) & 1; }

__device__ __forceinline__ void write_run_desc(uint32_t sb, int i, int step) {
  const int layer = i >= 7, t = i - 7 * layer, part = tile_split(i) ? step : 2;
  const bool wide = tile_wide(t), own = t != 2 && t != 6 && part != 1 && i != 0, second = t == 1 || t == 4;
  const uint32_t z16 = (wide ? 5 : 4) * (UNIT >> 4), a_off = z16 - 1024 + (uint32_t)DESC_A - (uint32_t)DESC_B;
  const int gl = 16 * t + (part == 2 ? 0 : second ? 16 * part - 14 : 4 * part), g0 = layer * STAGES_PER_LAYER + gl;
  const uint32_t s16 = (sb & 0x3FFFF) >> 4, bfirst = (uint32_t)DESC_B + s16;
  const int nkb = t == 6 ? 56 - SKEW : part == 0 ? 2 : 12 + 2 * part;
  const bool win1 = t == 1 && part != 0;
  const int win = layer ? WIN1 : WIN0;
  const int run = win1 ? win + 1 : t == 2 ? WIN2 + 1 : nkb;
  const int rest = win1 ? 64 | (nkb - 1 - SKEW - win) : t == 2 ? 64 | (7 - WIN2) | ((8 - SKEW) << 7) : 0;
  const uint32_t blo = bfirst + (t == 5 ? 12 * (UNIT >> 4) : z16 * (wide ? gl & 3 : (gl + 3) % 5));
  const uint32_t alo = own ? (uint32_t)DESC_A + s16 + (OFF_X >> 4) : blo + a_off;
  const uint32_t aoff = own ? alo + 1024 - (blo > bfirst + RING16 - 2 * z16 ? bfirst : blo + z16) : a_off;
  const bool xwait = part == 0 && !second, keep = !(part == 0 || t == 5);
  sts_u4(sb + OFF_RUN + (2 * i + step) * 16, blo, alo, aoff,
         ((g0 / NBAR) & 1) | xwait << 1 | keep << 2 | 8 * (g0 % NBAR) | run << 6 | rest << 12);
}

__device__ __forceinline__ float2 row_sums(const Ctx& c, int j0, int j1) {
  const uint32_t xrow = c.sb + OFF_X + c.w * 4096 + c.lane * 128;
  float s = 0.f, q = 0.f, s1 = 0.f, q1 = 0.f;
#pragma unroll 4
  for (int j = j0; j < j1; j++) {
    uint32_t u[4];
    lds_u4(xrow + (j >> 3) * 16384 + (((j & 7) ^ (c.lane & 7)) << 4), u[0], u[1], u[2], u[3]);
#pragma unroll
    for (int e = 0; e < 4; e++) {
      const float a = bf_lo(u[e]), d = bf_hi(u[e]);
      s += a; q = fmaf(a, a, q);
      s1 += d; q1 = fmaf(d, d, q1);
    }
  }
  return make_float2(s + s1, q + q1);
}
__device__ __forceinline__ void write_partial_stats(const Params& p, const Ctx& c, int ln, float2 v, uint32_t tag) {
  st_msg(p.g->stats + (ln * 8 + c.n) * SEQ + 128 * c.m + 32 * c.w + c.lane, __float_as_uint(v.x),
         __float_as_uint(fmaxf(v.y - v.x * v.x * (1.f / 128.f), 0.f)), 0u, tag);
}

template <bool PACED>
__device__ __forceinline__ void rank1_update(const Params& p, float (&acc)[2][96], const Ctx& cx, int t) {
  float nm[4];
#pragma unroll
  for (int q = 0; q < 4; q++) nm[q] = t == 6 ? 1.f : -lds_f(cx.sb + OFF_ROW + (32 * cx.w + 8 * q + (cx.lane >> 2)) * 8 + 4);
  const uint32_t ctab = cx.sb + OFF_CSQ + ((t & 3) * 192 + 2 * (cx.lane & 3)) * 4;
#pragma unroll
  for (int j = 0; j < 24; j++) {
    const float2 cs = lds_f2(ctab + j * 32);
#pragma unroll
    for (int q = 0; q < 4; q++) {
      const int k = 4 * j + q - 1;
      const float nq = PACED && k >= 0 ? chain(nm[q], __float_as_uint(ACC(k & 3, k >> 2, 1)), p.zero) : nm[q];
      ACC(q, j, 0) = fmaf(nq, cs.x, ACC(q, j, 0));
      ACC(q, j, 1) = fmaf(nq, cs.y, ACC(q, j, 1));
    }
  }
}

template <int QMASK, int SEC>
__device__ __forceinline__ void pack_qkv(const float (&acc)[2][96], uint32_t (&F)[3][4][8]) {
#pragma unroll
  for (int q = 3; q >= 0; q--)
#pragma unroll
    for (int j = 0; j < 8; j++) {
      if (!((QMASK >> q) & 1)) continue;
      const uint32_t u = pack_bf16(ACC(q, 8 * SEC + j, 0), ACC(q, 8 * SEC + j, 1));
      F[SEC][q][j] = SEC == 2 ? movtrans(u) : u;
    }
}
template <int K0, int K1>
__device__ __forceinline__ void send_halo(const Params& p, const uint32_t (&F)[3][4][8], const Ctx& cx, int layer, int t) {
  uint32_t E[18];
#pragma unroll
  for (int j = 0; j < 8; j++) { E[j] = F[1][3][j]; E[8 + j] = F[2][3][j]; }
  if (cx.w < 2) {
#pragma unroll
    for (int k = K0; k < K1; k++)
      if (k < 4) sts_u4(cx.sb + OFF_STG + cx.w * 2048 + cx.lane * 16 + k * 512, E[4 * k], E[4 * k + 1], E[4 * k + 2], E[4 * k + 3]);
  } else {
    uint4* dst = p.g->halo + (((layer * 2 + t) * 16 + cx.m) * 8 + cx.n) * 384 + (cx.w & 1) * 192 + cx.lane;
    const uint32_t tag = lds_u(cx.sb + OFF_TAG);
    if (K1 == 6) {
      const float4 r = lds_f4(cx.sb + OFF_ROW + (32 * cx.w + 24 + 2 * (cx.lane & 3)) * 8);
      E[16] = __float_as_uint(r.x);
      E[17] = __float_as_uint(r.z);
    }
#pragma unroll
    for (int k = K0; k < K1; k++) st_msg(dst + k * 32, E[3 * k], E[3 * k + 1], E[3 * k + 2], tag);
  }
}

__device__ __forceinline__ void attn_scores(const uint32_t* qa, const uint32_t* qb, const uint32_t* kp, const uint32_t* ka,
                                            const uint32_t* kb, float (&l)[4], const float4& zero, const bool (&early)[2]) {
  float s[3][4];
#pragma unroll
  for (int x = 0; x < 3; x++) {
    const uint32_t* kk = x == 0 ? kp : x == 1 ? ka : kb;
    asm volatile("mma.sync.aligned.m16n8k16.row.col.f32.bf16.bf16.f32 {%0,%1,%2,%3}, {%4,%5,%6,%7}, {%8,%9}, {%10,%11,%12,%13};"
                 : "=f"(s[x][0]), "=f"(s[x][1]), "=f"(s[x][2]), "=f"(s[x][3])
                 : "r"(qa[0]), "r"(qb[0]), "r"(qa[1]), "r"(qb[1]), "r"(kk[0]), "r"(kk[1]), "f"(zero.x), "f"(zero.y),
                   "f"(zero.z), "f"(zero.w));
  }
#pragma unroll
  for (int x = 0; x < 3; x++) {
    const uint32_t* kk = x == 0 ? kp : x == 1 ? ka : kb;
    mma16816(s[x], qa[2], qb[2], qa[3], qb[3], kk[2], kk[3]);
  }
#pragma unroll
  for (int e = 0; e < 2; e++) {
    l[e] = early[e] ? s[0][e] : s[1][e];
    l[2 + e] = early[e] ? s[1][2 + e] : s[2][2 + e];
  }
}

__device__ __forceinline__ void attn_mix(const float (&l)[4], const float (&sc)[4], const float (&off)[4], const float (&rk)[4],
                                         const uint32_t* vp, const uint32_t* va, const uint32_t* vb, float (&o)[4][4],
                                         float (&sum)[2], uint32_t mask, uint32_t zero) {
  float x[4];
#pragma unroll
  for (int e = 0; e < 4; e++) x[e] = fmaf(l[e], sc[e], off[e]);
  const float ml = quad_max(fmaxf(x[0], x[1])), mh = quad_max(fmaxf(x[2], x[3]));
  x[0] = ex2(x[0] - ml); x[1] = ex2(x[1] - ml);
  x[2] = ex2(x[2] - mh); x[3] = ex2(x[3] - mh);
  sum[0] = x[0] + x[1];
  sum[1] = x[2] + x[3];
  const uint32_t pl = pack_bf16(x[0] * rk[0], x[1] * rk[1]), ph = pack_bf16(x[2] * rk[2], x[3] * rk[3]);
  const uint32_t a0 = pl & ~mask, a1 = ph & mask, a2 = pl & zero, a3 = ph & ~mask, c0 = pl & mask, c1 = ph & zero;
#pragma unroll
  for (int jn = 0; jn < 4; jn++) {
    o[jn][0] = o[jn][1] = o[jn][2] = o[jn][3] = 0.f;
    mma16816(o[jn], a0, a1, a2, a3, va[jn], vb[jn]);
  }
#pragma unroll
  for (int jn = 0; jn < 4; jn++) mma1688(o[jn], c0, c1, vp[jn]);
}

template <int t>
__device__ __forceinline__ void attn_epilogue(const Params& p, float (&acc)[2][96], uint32_t (&F)[3][4][8], const Ctx& cx, int layer, uint32_t tag) {
  UNPACK_CTX(cx);
  const uint32_t ktab = sb + OFF_ROW + (32 * w + 2 * (lane & 3)) * 8, exc = sb + OFF_STG + (w & 1) * 2048 + lane * 16;
  uint4* const halo = p.g->halo + (((layer * 2 + t) * 16 + m) * 8 + n) * 384 + (w & 1) * 192;
  (void)wg;
  uint32_t(&Q)[4][8] = F[0], (&K)[4][8] = F[1], (&V)[4][8] = F[2], P[18];
  float kr[5][2], qr[4];
  bar_arrive(BAR_PAIR + w, 64);
#pragma unroll
  for (int q = 0; q < 4; q++) {
    qr[q] = lds_f(sb + OFF_ROW + (32 * w + 8 * q + (lane >> 2)) * 8) * (0.17677669529663687f * 1.4426950408889634f);
    const float4 r = lds_f4(ktab + 64 * q);
    kr[1 + q][0] = r.x;
    kr[1 + q][1] = r.z;
  }
  pack_qkv<7, 1>(acc, F);
  uint32_t tg[6];
#pragma unroll
  for (int k = 0; k < 6; k++) {
    tg[k] = ~tag;
    if (t == 1)
      asm volatile("{\n.reg .b128 v;\n.reg .pred g;\nsetp.ne.u32 g, %5, 0;\nmov.b128 v, {%6, %6, %6, %6};\n"
                   "@g ld.relaxed.gpu.global.b128 v, [%4];\nmov.b128 {%0, %1, %2, %3}, v;\n}"
                   : "=r"(P[3 * k]), "=r"(P[3 * k + 1]), "=r"(P[3 * k + 2]), "=r"(tg[k])
                   : "l"(halo - 8 * 384 + k * 32 + lane), "r"((uint32_t)(w < 2 && m > 0) | ((K[0][7] | K[1][7] | K[2][7]) & p.zero)), "r"(~tag) : "memory");
  }
  pack_qkv<7, 2>(acc, F);
  pack_qkv<15, 0>(acc, F);
  bar_sync(BAR_PAIR + (w ^ 2), 64);
  if (w >= 2 || m == 0) {
#pragma unroll
    for (int k = 0; k < 4; k++) lds_u4(exc + k * 512, P[4 * k], P[4 * k + 1], P[4 * k + 2], P[4 * k + 3]);
    const float4 r = lds_f4(ktab - (w >> 1) * 320);
    P[16] = __float_as_uint(r.x);
    P[17] = __float_as_uint(r.z);
  } else {
    if ((m & 1) && t == 0) __nanosleep(HALO_NS);
#pragma unroll 1
    for (int it = 0; it < MSG_SPINS; it++) {
      if (t == 0 || it > 0) {
        if (it > 0 || !(m & 1)) poll_line(reinterpret_cast<const uint32_t*>(halo - 8 * 384 + 191) + 3, tag, 1u);
#pragma unroll
        for (int k = 0; k < 6; k++) ld_msg(halo - 8 * 384 + k * 32 + lane, P[3 * k], P[3 * k + 1], P[3 * k + 2], tg[k]);
      }
      uint32_t bad = 0;
#pragma unroll
      for (int k = 0; k < 6; k++) bad |= tg[k] ^ tag;
      if (__all_sync(0xffffffffu, bad == 0)) break;
    }
  }
  kr[0][0] = __uint_as_float(P[16]);
  kr[0][1] = __uint_as_float(P[17]);
  const bool early[2] = {2 * (lane & 3) > (lane >> 2), 2 * (lane & 3) + 1 > (lane >> 2)};
  const uint32_t mask = (early[0] ? 0xffffu : 0u) | (early[1] ? 0xffff0000u : 0u);
  float rk[2][4], sc[2][4], off[2][4];
#pragma unroll
  for (int g = 0; g < 2; g++) {
#pragma unroll
    for (int e = 0; e < 4; e++) {
      const int q = 2 * g + (e >> 1);
      const bool masked = q == 0 && m == 0 && w < 2 && early[e & 1];
      rk[g][e] = early[e & 1] ? kr[q][e & 1] : kr[q + 1][e & 1];
      sc[g][e] = masked ? 0.f : rk[g][e] * qr[q];
      off[g][e] = masked ? -1e30f : 0.f;
    }
  }
  if (w == 0 && elect_one()) asm volatile("prefetch.tensormap [%0];" ::"l"(&p.t.att_st) : "memory");
  bar_sync(BAR_GO, 256);
  const float4 zero = lds_f4(sb + OFF_ZERO);
  float l[2][2][4], o[2][2][4][4], sum[2][2][2];
#pragma unroll
  for (int h = 0; h < 2; h++) {
    if (h == 1) {
      Q[2][4] |= __float_as_uint(l[1][0][0]) & p.zero;
      Q[0][4] |= __float_as_uint(l[0][0][0]) & p.zero;
    }
    attn_scores(&Q[2][4 * h], &Q[3][4 * h], &K[1][4 * h], &K[2][4 * h], &K[3][4 * h], l[1][h], zero, early);
    attn_scores(&Q[0][4 * h], &Q[1][4 * h], &P[4 * h], &K[0][4 * h], &K[1][4 * h], l[0][h], zero, early);
  }
  const uint32_t stg = sb + OFF_STG + w * 4096, srow = stg + lane * 128 + ((lane & 7) << 4);
#pragma unroll
  for (int h = 0; h < 2; h++) {
    attn_mix(l[1][h], sc[1], off[1], rk[1], &V[1][4 * h], &V[2][4 * h], &V[3][4 * h], o[1][h], sum[1][h], mask, p.zero);
    attn_mix(l[0][h], sc[0], off[0], rk[0], &P[8 + 4 * h], &V[0][4 * h], &V[1][4 * h], o[0][h], sum[0][h], mask, p.zero);
  }
  if (t == 0 && p.zero == 0) {
    uint32_t dep = 0;
#pragma unroll
    for (int k = 0; k < 16; k++) dep |= __float_as_uint(o[k >> 3][(k >> 2) & 1][k & 3][0]);
    bar_arrive(BAR_DONE | (dep & __float_as_uint(zero.x)), 256);
  }
#pragma unroll
  for (int h = 0; h < 2; h++) {
    float inv[4];
#pragma unroll
    for (int q = 0; q < 4; q++) inv[q] = rcp_hw(quad_sum(sum[q >> 1][h][q & 1]));
#pragma unroll
    for (int j = 0; j < 4; j++) {
      const float(&a)[4] = o[0][h][j];
      const float(&c)[4] = o[1][h][j];
      stsm4(srow ^ ((4 * h + j) << 4), pack_bf16(a[0] * inv[0], a[1] * inv[0]), pack_bf16(a[2] * inv[1], a[3] * inv[1]),
            pack_bf16(c[0] * inv[2], c[1] * inv[2]), pack_bf16(c[2] * inv[3], c[3] * inv[3]));
    }
  }
  if (t == 1) bar_arrive(BAR_DONE, 256);
  fence_async_smem();
  __syncwarp();
  if (lane == 0) {
    tma_st2(&p.t.att_st, stg, 128 * n + 64 * t, 128 * m + 32 * w);
    bulk_commit();
  }
}

__device__ __forceinline__ void finish_stores(uint32_t sb, int i) {
  const int t = i >= 7 ? i - 7 : i;
  if ((threadIdx.x & 31) == 0) {
    bulk_wait_all();
    mbar_arrive(sb + BAR_PUB + 8 * (t < 2 ? t : t + 1));
  }
  __syncwarp();
  if (i < 12) bar_arrive(BAR_GUARD + ((i & 1) ^ 1), 256);
}

template <int N>
__device__ __forceinline__ bool mainloop(const Params& p, float (&acc)[2][96], uint32_t sb, int i, int step, int mn) {
  constexpr uint32_t Z16 = (2 + N / 64) * (UNIT >> 4);
  constexpr uint32_t A_OFF = Z16 - 1024 + (uint32_t)DESC_A - (uint32_t)DESC_B;
  const int wg = i & 1;
  const uint32_t s16 = (sb & 0x3FFFF) >> 4;
  const uint32_t blast = (uint32_t)DESC_B + s16 + RING16 - Z16, flast = sb + BAR_FULL + 8 * (NBAR - 1);
  uint32_t blo = (uint32_t)DESC_B + s16, alo = blo + A_OFF, aoff = A_OFF, misc = 16 << 6;
  if (N == 128 || i > 0) lds_u4(sb + OFF_RUN + (2 * i + step) * 16, blo, alo, aoff, misc);
  uint32_t keep = misc & 4;
  int run = (misc >> 6) & 63, rest = misc >> 12;
  uint32_t fb = sb + BAR_FULL + (misc & 0x38), ph = misc & 1;
  uint32_t prev = sb + BAR_DUMMY - 8 * NBAR;
  const uint32_t lane_id = __popc(__ballot_sync(0xffffffffu, true) & lanemask_lt()), rel = pair_offset(sb, lane_id & 1) + 8 * NBAR;
  pin_regs<N / 2>(acc);
  if (N == 128 || i > 0) bar_sync(BAR_ORDER + wg, 256);
  else bar_sync(BAR_INIT0, 160);
  mbar_wait(fb, ph);
  if (N == 192 && i == 0) cluster_wait();
  if (misc & 2) {
    if (N == 128) {
      const Ctx cx = make_ctx(sb, mn);
      mbar_wait(sb + BAR_XRDY, 1);
      const float2 v = row_sums(cx, 0, 8);
      sts_f2(cx.sb + OFF_HALF + (32 * cx.w + cx.lane) * 8, v.x, v.y);
      bar_arrive(BAR_STAT, 256);
    }
    mbar_wait(sb + BAR_XGO, N == 192);
  }
#pragma unroll 1
  while (true) {
    const uint64_t da = (DESC_A & ~0xffffffffull) | alo, db = (DESC_B & ~0xffffffffull) | blo;
    asm volatile("wgmma.fence.sync.aligned;" ::: "memory");
    wgmma_ss<N>(acc[0], da, db, keep);
    wgmma_ss<N>(acc[1], da + 64, db, keep);
    keep = 4;
    wgmma_ss<N>(acc[0], da + 2, db + 128);
    wgmma_ss<N>(acc[1], da + 66, db + 128);
    asm volatile("wgmma.commit_group.sync.aligned;" ::: "memory");
    asm volatile("wgmma.wait_group.sync.aligned 1;" ::: "memory");
    if (lane_id < 2) mbar_arrive_cluster(prev + rel);
    prev = fb;
    if (fb == flast) { fb -= 8 * NBAR; ph++; }
    fb += 8;
    blo = blo > blast - Z16 ? blast + Z16 - RING16 : blo + Z16;
    alo = blo + aoff;
    aoff = A_OFF;
    run--;
    const bool ready = mbar_test(fb, ph) && run != 0;
    asm volatile("wgmma.fence.sync.aligned;" ::: "memory");
    wgmma_ss<N>(acc[0], da + 4, db + 4 * N);
    wgmma_ss<N>(acc[1], da + 68, db + 4 * N);
    wgmma_ss<N>(acc[0], da + 6, db + 4 * N + 128);
    wgmma_ss<N>(acc[1], da + 70, db + 4 * N + 128);
    asm volatile("wgmma.commit_group.sync.aligned;" ::: "memory");
    if (!ready) {
      bool window = false;
      if (run == 0) {
        if (rest == 0) break;
        window = rest & 64;
        if (N == 192 && i == 1) {
          bar_sync(BAR_GO, 256);
          asm volatile("wgmma.wait_group.sync.aligned 0;" ::: "memory");
          pin_regs<96>(acc);
          rank1_update<false>(p, acc, make_ctx(sb, mn), 1);
          pin_regs<96>(acc);
        } else if (window) bar_arrive(BAR_GO, 256);
        else alo = (uint32_t)DESC_A + s16 + (OFF_STG >> 4);
        run = rest & 63;
        rest >>= 7;
      }
      mbar_wait(fb, ph);
      if (window) bar_sync(BAR_DONE, 256);
    }
  }
  if constexpr (N == 192) {
    if (misc >> 12) {
      const Ctx cx = make_ctx(sb, mn);
      uint32_t F[3][4][8];
      const uint32_t fb0 = fb, blo0 = blo;
#pragma unroll 1
      for (int x = 0; x < SKEW; x++) {
        const uint64_t da = (DESC_A & ~0xffffffffull) | (blo + A_OFF + 64), db = (DESC_B & ~0xffffffffull) | blo;
        mbar_wait(fb, ph);
        asm volatile("wgmma.fence.sync.aligned;" ::: "memory");
#pragma unroll
        for (int k = 0; k < 4; k++) wgmma_ss<N>(acc[1], da + 2 * k, db + (k >> 1) * 4 * N + (k & 1) * 128);
        asm volatile("wgmma.commit_group.sync.aligned;" ::: "memory");
        asm volatile("wgmma.wait_group.sync.aligned 1;" ::: "memory");
        if (x == 0) {
          if (lane_id < 2) mbar_arrive_cluster(prev + rel);
          bar_sync(BAR_GUARD + wg, 256);
        }
        if (fb == flast) { fb -= 8 * NBAR; ph++; }
        fb += 8;
        blo += Z16;
      }
      fb = fb0;
#pragma unroll
      for (int u = 0; u < 2 * SKEW; u++) {
        const uint64_t da = (DESC_A & ~0xffffffffull) | (blo0 + (u >> 1) * Z16 + A_OFF + 4 * (u & 1));
        const uint64_t db = (DESC_B & ~0xffffffffull) | (blo0 + (u >> 1) * Z16 + 4 * N * (u & 1));
        asm volatile("wgmma.fence.sync.aligned;" ::: "memory");
        wgmma_ss<N>(acc[0], da, db);
        wgmma_ss<N>(acc[0], da + 2, db + 128);
        asm volatile("wgmma.commit_group.sync.aligned;" ::: "memory");
        if (u == 2 * SKEW - 1) break;
        asm volatile("wgmma.wait_group.sync.aligned 1;" ::: "memory");
        if (u == 0) {
#pragma unroll
          for (int r = 0; r < 96; r++) asm volatile("" : "+f"(acc[1][r])::"memory");
        }
        if (u == 2 || u == 4) {
          if (lane_id < 2) mbar_arrive_cluster(fb + rel);
          fb = fb == flast ? fb - 8 * (NBAR - 1) : fb + 8;
        }
        if (u == 0) { pack_qkv<8, 2>(acc, F); pack_qkv<8, 1>(acc, F); }
        if (u == 1) send_halo<0, 3>(p, F, cx, i >= 7, 1);
        if (u == 2) send_halo<3, 6>(p, F, cx, i >= 7, 1);
      }
      bar_arrive(BAR_ORDER + (wg ^ 1), 256);
      asm volatile("wgmma.wait_group.sync.aligned 0;" ::: "memory");
#pragma unroll
      for (int r = 0; r < 96; r++) asm volatile("" : "+f"(acc[0][r])::"memory");
      if (lane_id < 2) mbar_arrive_cluster(fb + rel);
      attn_epilogue<1>(p, acc, F, cx, i >= 7, lds_u(sb + OFF_TAG));
      finish_stores(sb, i);
#pragma unroll
      for (int r = 0; r < 48; r++) {
        float* d = &acc[r & 1][4 * (r >> 1)];
        asm volatile("ld.shared.v4.f32 {%0, %1, %2, %3}, [%4];" : "=f"(d[0]), "=f"(d[1]), "=f"(d[2]), "=f"(d[3]) : "r"(sb + OFF_CSQ + 16 * r));
      }
      return true;
    }
  }
  if (N == 128 && ((0x2244 >> i) & 1)) {
    const Ctx cx = make_ctx(sb, mn);
    const uint32_t xw = cx.sb + OFF_X + cx.w * 4096;
    const uint32_t xrow = xw + (cx.lane & 8) * 256 + (cx.lane & 7) * 128 + (((cx.lane & 7) ^ (cx.lane >> 4)) << 4);
    auto write_x = [&](int mb, int j) {
      stsm4((xrow ^ ((j & 7) << 4)) + (j >> 3) * 16384 + mb * 1024, pack_bf16(ACC(mb, j, 0), ACC(mb, j, 1)),
            pack_bf16(ACC(mb + 2, j, 0), ACC(mb + 2, j, 1)), pack_bf16(ACC(mb, j + 1, 0), ACC(mb, j + 1, 1)),
            pack_bf16(ACC(mb + 2, j + 1, 0), ACC(mb + 2, j + 1, 1)));
    };
    auto send_x = [&](int mb, int h) {
      fence_async_smem();
      __syncwarp();
      if (cx.lane == 0 && (h == 0 || i == 13)) {
        tma_st_warp(&p.t.out_8, xw + h * 16384 + mb * 1024, 128 * cx.n + 64 * h, cx.m, cx.w, 8 * mb);
        tma_st_warp(&p.t.out_8, xw + h * 16384 + mb * 1024 + 2048, 128 * cx.n + 64 * h, cx.m, cx.w, 8 * mb + 16);
        bulk_commit();
      }
    };
    uint32_t rb = fb, rlo = blo;
#pragma unroll 1
    for (int x = 0; x < SKEW; x++) {
      const uint64_t da = (DESC_A & ~0xffffffffull) | (blo + A_OFF), db = (DESC_B & ~0xffffffffull) | blo;
      mbar_wait(fb, ph);
      asm volatile("wgmma.fence.sync.aligned;" ::: "memory");
#pragma unroll
      for (int k = 0; k < 4; k++) wgmma_ss<N>(acc[0], da + 2 * k, db + (k >> 1) * 4 * N + (k & 1) * 128);
      asm volatile("wgmma.commit_group.sync.aligned;" ::: "memory");
      asm volatile("wgmma.wait_group.sync.aligned 1;" ::: "memory");
      if (x == 0 && lane_id < 2) mbar_arrive_cluster(prev + rel);
      if (fb == flast) { fb -= 8 * NBAR; ph++; }
      fb += 8;
      if (blo == blast) blo -= RING16;
      blo += Z16;
    }
#pragma unroll
    for (int u = 0; u < 2 * SKEW; u++) {
      const uint64_t da = (DESC_A & ~0xffffffffull) | (rlo + A_OFF + 64 + 4 * (u & 1));
      const uint64_t db = (DESC_B & ~0xffffffffull) | (rlo + 4 * N * (u & 1));
      asm volatile("wgmma.fence.sync.aligned;" ::: "memory");
      wgmma_ss<N>(acc[1], da, db);
      wgmma_ss<N>(acc[1], da + 2, db + 128);
      asm volatile("wgmma.commit_group.sync.aligned;" ::: "memory");
      if (u == 2 * SKEW - 1) break;
      asm volatile("wgmma.wait_group.sync.aligned 1;" ::: "memory");
      if (u == 0) {
#pragma unroll
        for (int r = 0; r < 64; r++) asm volatile("" : "+f"(acc[0][r])::"memory");
      }
      if (u & 1) rlo = rlo == blast ? rlo + Z16 - RING16 : rlo + Z16;
      if (u == 2 || u == 4) {
        if (lane_id < 2) mbar_arrive_cluster(rb + rel);
        rb = rb == flast ? rb - 8 * (NBAR - 1) : rb + 8;
      }
      if (u == 2) send_x(0, 0);
      else { write_x(0, 4 * (u - (u > 2))); write_x(0, 4 * (u - (u > 2)) + 2); }
    }
    if (i < 13) bar_arrive(BAR_ORDER + (wg ^ 1), 256);
    else send_x(0, 1);
    asm volatile("wgmma.wait_group.sync.aligned 0;" ::: "memory");
    pin_regs<64>(acc);
#pragma unroll
    for (int h = 0; h < 2; h++) {
      if (h == 1 && p.zero != 0) break;
#pragma unroll
      for (int j = 8 * h; j < 8 * h + 8; j += 2) write_x(1, j);
      send_x(1, h);
      if (h == 0) {
        if (cx.lane == 0) mbar_arrive(sb + BAR_XRDY);
        if (lane_id < 2 && i < 13) mbar_arrive_cluster(rb + rel);
      }
    }
    if (cx.lane == 0) {
      bulk_wait_all();
      mbar_arrive(sb + BAR_XGO);
    }
    __syncwarp();
    if (i == 2 || i == 9) {
      const float2 v = row_sums(cx, 8, 16);
      bar_sync(BAR_STAT, 256);
      const float2 o = lds_f2(cx.sb + OFF_HALF + (32 * cx.w + cx.lane) * 8);
      write_partial_stats(p, cx, (i + 3) >> 2, make_float2(v.x + o.x, v.y + o.y), lds_u(sb + OFF_TAG));
    }
    return true;
  }
  bar_arrive(BAR_ORDER + (wg ^ 1), 256);
  asm volatile("wgmma.wait_group.sync.aligned 0;" ::: "memory");
  pin_regs<N / 2>(acc);
  if (lane_id < 2) mbar_arrive_cluster(prev + rel);
  return false;
}

__device__ __forceinline__ void finish_row_stats(const Params& p, const Ctx& c, int ln, uint32_t tag) {
  const uint4* src = p.g->stats + ln * 8 * SEQ + 128 * c.m + 32 * c.w + c.lane;
  uint32_t ps[8], pm[8];
#pragma unroll 1
  for (int it = 0; it < MSG_SPINS; it++) {
    uint32_t bad = 0, u, tg;
    if (ln == 2 || it > 0) __nanosleep(STAT_NS);
#pragma unroll
    for (int k = 0; k < 8; k++) { ld_msg(src + k * SEQ, ps[k], pm[k], u, tg); bad |= tg ^ tag; }
    if (__all_sync(0xffffffffu, bad == 0)) break;
  }
  float s = 0.f, m2 = 0.f;
#pragma unroll
  for (int k = 0; k < 8; k++) s += __uint_as_float(ps[k]);
  const float mean = s * (1.f / DM);
#pragma unroll
  for (int k = 0; k < 8; k++) {
    const float d = __uint_as_float(ps[k]) * (1.f / 128.f) - mean;
    m2 += fmaf(128.f * d, d, __uint_as_float(pm[k]));
  }
  sts_f2(c.sb + OFF_ROW + (32 * c.w + c.lane) * 8, rsqrtf(m2 * (1.f / DM) + 1e-5f), mean);
  __syncwarp();
}

__device__ __forceinline__ void gelu_epilogue(const Params& p, float (&acc)[2][96], const Ctx& cx, int t) {
  UNPACK_CTX(cx);
  (void)wg;
  float rs[4], rm[4];
#pragma unroll
  for (int q = 0; q < 4; q++) {
    const float2 v = lds_f2(sb + OFF_ROW + (32 * w + 8 * q + (lane >> 2)) * 8);
    rs[q] = 0.5f * v.x;
    rm[q] = -rs[q] * v.y;
  }
  const int col0 = 128 * (t - 3);
  const uint32_t stg = sb + OFF_STG + w * 4096;
  const uint32_t ctab = sb + OFF_CSF + (col0 / 2 + (lane & 3)) * 16, srow = stg + lane * 128 + ((lane & 7) << 4);
  if (t == 5) __nanosleep(STAG_NS * w);
  float4 nb = lds_f4(ctab);
  auto chunk = [&](auto first, int cc) {
    constexpr int c = decltype(first)::value ? 0 : 1;
    uint32_t hp[8][4];
#pragma unroll
    for (int j = 0; j < 8; j++) {
      const float4 cb = nb;
      nb = lds_f4(ctab + (8 * cc + j + 1) * 64);
#pragma unroll
      for (int q = 0; q < 4; q++) {
        float y[2];
        const int k = 4 * j + q - GELU_DEP;
        const float rmq = k >= 0 ? chain(rm[q], hp[k >> 2][k & 3], p.zero) : rm[q];
#pragma unroll
        for (int e = 0; e < 2; e++) {
          const float z = fmaf(ACC(q, 8 * c + j, e), rs[q], fmaf(rmq, e ? cb.y : cb.x, e ? cb.w : cb.z));
          const float u = z * fmaf(z * z, 8.f * 0.7978845608028654f * 0.044715f, 2.f * 0.7978845608028654f);
          y[e] = fmaf(z, tanh_hw(u), z);
        }
        hp[j][q] = pack_bf16(y[0], y[1]);
      }
      if (j == STG_WAIT && c > 0) {
        if (lane == 0) bulk_wait_read();
        __syncwarp();
      }
      if (c == 0 || j > STG_WAIT) {
        stsm4(srow ^ (j << 4), hp[j][0], hp[j][1], hp[j][2], hp[j][3]);
      } else if (j == STG_WAIT) {
#pragma unroll
        for (int jj = 0; jj <= STG_WAIT; jj++) stsm4(srow ^ (jj << 4), hp[jj][0], hp[jj][1], hp[jj][2], hp[jj][3]);
      }
    }
    fence_async_smem();
    __syncwarp();
    if (lane == 0) {
      tma_st2(&p.t.h_st, stg, 448 * n + col0 + 64 * cc, 128 * m + 32 * w);
      bulk_commit();
    }
    return hp[7][3];
  };
  chunk(std::true_type{}, 0);
#pragma unroll 1
  for (int cc = 1;; cc++) {
    const uint32_t zr = chunk(std::false_type{}, cc) & p.zero;
    if (cc == 2 || t != 5) break;
#pragma unroll
    for (int r = 0; r < 64; r++)
      asm volatile("{\n.reg .b32 x;\nmov.b32 x, %1;\nor.b32 x, x, %2;\nmov.b32 %0, x;\n}"
                   : "=f"(acc[r & 1][32 + (r >> 1)]) : "f"(acc[r & 1][64 + (r >> 1)]), "r"(zr));
  }
#pragma unroll
  for (int r = 0; r < 16; r++) acc[0][r] = acc[1][r] = 0.f;
}

__device__ __forceinline__ bool consumer_tile(const Params& p, float (&acc)[2][96], uint32_t sb0, int i, int mn) {
  const int layer = i >= 7, t = i - 7 * layer, wg = i & 1;
  const bool resid = t == 2 || t == 6;
  {
    if (resid) {
      const Ctx cx = make_ctx(sb0, mn);
      const uint32_t xrow = cx.sb + OFF_X + cx.w * 4096 + cx.lane * 128;
      const uint32_t sel_lo = 0x1044u | p.zero, sel_hi = 0x3244u | p.zero;
#pragma unroll
      for (int j = 0; j < 16; j++) {
        uint32_t r[4];
        ldsm4(xrow + (j >> 3) * 16384 + (((j & 7) ^ (cx.lane & 7)) << 4), r[0], r[1], r[2], r[3]);
#pragma unroll
        for (int q = 0; q < 4; q++) {
          ACC(q, j, 0) = prmt_f(r[q], sel_lo);
          ACC(q, j, 1) = prmt_f(r[q], sel_hi);
        }
      }
    }
    if (t >= 5 || i == 7) finish_stores(sb0, i - 2);
#pragma unroll 1
    for (int step = !tile_split(i);; step++) {
      if (step == 1 && (t == 1 || t == 4)) {
        const Ctx cx = make_ctx(sb0, mn);
        if (i == 1) {
          const uint32_t epoch = __ldcg(p.g->epoch + (mn & 127));
          cluster_wait();
          asm volatile("st.shared.u32 [%0], %1;" ::"r"(sb0 + OFF_TAG), "r"(epoch + 1) : "memory");
        }
        const uint32_t tag = lds_u(cx.sb + OFF_TAG);
        const int ln = (i + 1) >> 2;
#pragma unroll 1
        for (int r = 0; r < 2; r++) {
          if (i == 1) {
            if (cx.w < 3) {
              float a[8] = {0.f, 0.f, 0.f, 0.f, 0.f, 0.f, 0.f, 0.f};
              mbar_wait(sb0 + BAR_CSLD, r);
#pragma unroll 1
              for (int h = 0; h < 2; h++) sum_rows(cx.sb + OFF_STG + h * 12288 + cx.w * 4096, 4, a, cx.lane);
              publish_sums(a, p.g->csp + (cx.n * 17 + cx.m) * 224 + (3 * r + cx.w) * 32, cx.lane, tag);
            }
          }
          if (r == 1) break;
          if (i == 1) {
            bar_sync(BAR_WG + 1, 128);
            if (cx.w == 3 && elect_one()) {
              mbar_expect_tx(sb0 + BAR_CSLD, 24576);
              tma_ld3(sb0 + OFF_STG, &p.t.wqkv, sb0 + BAR_CSLD, 128 * cx.n + 64, 64 * cx.m, 0);
              tma_ld3(sb0 + OFF_STG + 12288, &p.t.wqkv, sb0 + BAR_CSLD, 128 * cx.n + 64, 64 * cx.m + 32, 0);
            }
            mbar_wait(sb0 + BAR_XRDY, 0);
            mbar_wait(sb0 + BAR_XRDY + 8, 0);
          }
          if (t == 1) write_partial_stats(p, cx, ln, row_sums(cx, 0, 16), tag);
        }
        if (i == 1) {
          bar_arrive(BAR_HLP, 160);
          bar_sync(BAR_INIT, 160);
        }
        if (i == 4) colsum_total(p, cx, 1, tag);
        if (i != 1) bar_sync(BAR_GUARD + wg, 256);
        finish_row_stats(p, cx, ln, tag);
        if (i == 4) {
          colsum_gather(p, cx, 1, tag);
          mbar_wait(sb0 + BAR_BIAS, 0);
        }
        bar_arrive(BAR_GUARD + (wg ^ 1), 256);
      }
      if (step == 2) bar_sync(BAR_GUARD + wg, 256);
      if (step == 2 && i == 0) {
        colsum_gather(p, make_ctx(sb0, mn), 0, lds_u(sb0 + OFF_TAG));
        bar_sync(BAR_WG, 128);
      }
      if ((t + step == 2 && i != 1) || t == 6) rank1_update<true>(p, acc, make_ctx(sb0, mn), t);
      if (step == 2) break;
      if (tile_wide(t)) {
        if (mainloop<192>(p, acc, sb0, i, step, mn)) return false;
      } else {
        if (mainloop<128>(p, acc, sb0, i, step, mn)) return false;
      }
    }
    if (t < 2) return true;
    gelu_epilogue(p, acc, make_ctx(sb0, mn), t);
    return false;
  }
}

template <bool BY_SMID>
__global__ void __cluster_dims__(2, 1, 1) __launch_bounds__(384, 1)
fused_layers_kernel(const Scalars scalars, const __grid_constant__ Maps maps) {
  if (threadIdx.x == 288 || threadIdx.x == 320)
    asm volatile("prefetch.tensormap [%0];" ::"l"(threadIdx.x == 288 ? &maps.xin : &maps.wqkv) : "memory");
  const Params p{scalars, maps};
  extern __shared__ __align__(1024) uint8_t smem_raw[];
  const uint32_t sb = uniform((uint32_t)__cvta_generic_to_shared(smem_raw));
  const int tid = threadIdx.x, lane = tid & 31, warp = uniform(tid >> 5), wg = warp >> 2, w = warp & 3;

  int mn;
  {
    int id = blockIdx.x;
    if (BY_SMID) asm volatile("mov.u32 %0, %%smid;" : "=r"(id));
    else if (id >= 120) id += 4;
    const int c = id >> 1;
    int g, j;
    if (c < 32) { g = c & 7; j = c >> 3; }
    else if (c < 60) { g = 1 + (c - 32) % 7; j = 4 + (c - 32) / 7; }
    else { g = 0; j = c - 58; }
    mn = (g * 2 + (blockIdx.x & 1)) * 8 + j;
    if (c == 60 || c == 61) {
      if (tid < 32) {
        const uint32_t tag = __ldcg(p.g->epoch + NCTA + (id & 3)) + 1;
#pragma unroll 1
        for (int mm = 0; mm < 16; mm++) poll_line(p.g->flags + mm * 32 + (lane & 7), 32 * tag, 0xffu);
        if (tid == 0) p.g->epoch[NCTA + (id & 3)] = tag;
      }
      return;
    }
  }
  const int m = mn >> 3, n = mn & 7;
  if (wg < 2) {
    cluster_arrive();
    asm volatile("setmaxnreg.inc.sync.aligned.u32 232;");
    const int id = mn | (warp << 7);
#pragma unroll 1
    for (int i = wg;; i += 2) {
      float acc[2][96];
#pragma unroll
      for (int r = 0; r < 96; r++) acc[0][r] = acc[1][r] = 0.f;
      pin_regs<96>(acc);
#pragma unroll 1
      while (!consumer_tile(p, acc, sb, i, id)) {
        i += 2;
        if (i >= 14) goto all_done;
      }
      const Ctx cx = make_ctx(sb, id);
      uint32_t F[3][4][8];
      pack_qkv<8, 2>(acc, F);
      pack_qkv<8, 1>(acc, F);
      send_halo<0, 6>(p, F, cx, i >= 7, 0);
      attn_epilogue<0>(p, acc, F, cx, i >= 7, lds_u(sb + OFF_TAG));
      finish_stores(sb, i);
    }
  all_done:
    if (wg == 0) {
      finish_stores(sb, 12);
    } else {
      cluster_arrive();
      cluster_wait();
    }
  } else {
    asm volatile("setmaxnreg.dec.sync.aligned.u32 40;");
    if (w != 0) {
      if (w == 1 && elect_one()) {
        mbar_init(sb + BAR_FULL + 32, 2);
#pragma unroll
        for (int k = 0; k < NBAR; k++) mbar_init(sb + BAR_EMPTY + 8 * k, 8);
#pragma unroll
        for (int k = 0; k < 3; k++) mbar_init(sb + BAR_XRDY + 8 * k, 4);
#pragma unroll
        for (int k = 0; k < 9; k++) mbar_init(sb + BAR_PUB + 8 * k, 4);
#pragma unroll
        for (int k = 0; k < 3; k++) mbar_init(sb + BAR_CSLD + 8 * k, 1);
        mbar_init(sb + BAR_XGO, 4);
        sts_f2(sb + OFF_ZERO, 0.f, 0.f);
        sts_f2(sb + OFF_ZERO + 8, 0.f, 0.f);
        asm volatile("fence.mbarrier_init.release.cluster;" ::: "memory");
      }
      __syncwarp();
      cluster_arrive();
      if (w == 2) {
        if (lane < 28) write_run_desc(sb, lane >> 1, lane & 1);
        bar_arrive(BAR_INIT, 160);
      }
      cluster_wait();
      if (w == 1) producer<true>(p, sb, m, n, lane);
      else if (w == 3) colsum_helper(p, sb, m, n, lane);
      else if (elect_one()) publisher(p, sb, m, n);
    } else {
      const bool leader = elect_one();
      if (leader) {
#pragma unroll
        for (int k = 0; k < 4; k++) mbar_init(sb + BAR_FULL + 8 * k, 2);
        asm volatile("fence.mbarrier_init.release.cluster;" ::: "memory");
      }
      __syncwarp();
      bar_arrive(BAR_INIT0, 160);
      cluster_arrive();
      if (leader) {
#pragma unroll 1
        for (int k = 0; k < 4; k++) {
          const uint32_t fb = sb + BAR_FULL + 8 * k;
          mbar_expect_tx(fb, 16384);
          tma_ld_act(sb + (5 * k + 3) * UNIT, &p.t.xin, fb, 64 * k, m);
          mbar_expect_tx(fb, 3 * UNIT);
          tma_ld3(sb + 5 * k * UNIT, &p.t.wqkv, fb, 128 * n, 64 * k, 0);
          tma_ld3(sb + 5 * k * UNIT + 12288, &p.t.wqkv, fb, 128 * n, 64 * k + 32, 0);
        }
      }
      __syncwarp();
      cluster_wait();
      producer<false>(p, sb, m, n, lane);
    }
  }
}

typedef CUresult (*EncodeFn)(CUtensorMap*, CUtensorMapDataType, cuuint32_t, void*, const cuuint64_t*, const cuuint64_t*,
                             const cuuint32_t*, const cuuint32_t*, CUtensorMapInterleave, CUtensorMapSwizzle,
                             CUtensorMapL2promotion, CUtensorMapFloatOOBfill);

void make_2d(EncodeFn enc, CUtensorMap* m, const void* ptr, uint64_t cols, uint64_t rows, uint32_t box_rows) {
  cuuint64_t d[2] = {cols, rows}, st[1] = {cols * 2};
  cuuint32_t b[2] = {64, box_rows}, e[2] = {1, 1};
  enc(m, CU_TENSOR_MAP_DATA_TYPE_BFLOAT16, 2, const_cast<void*>(ptr), d, st, b, e, CU_TENSOR_MAP_INTERLEAVE_NONE,
      CU_TENSOR_MAP_SWIZZLE_128B, CU_TENSOR_MAP_L2_PROMOTION_L2_128B, CU_TENSOR_MAP_FLOAT_OOB_FILL_NONE);
}
void make_act(EncodeFn enc, CUtensorMap* m, const void* ptr, uint64_t cols, bool split, uint32_t box = 2, uint32_t rows = 32) {
  const uint64_t row = cols * 2;
  cuuint64_t d[4] = {cols, 32, 2, SEQ / 64}, st[3] = {split ? 2 * row : row, split ? row : 32 * row, 64 * row};
  cuuint32_t b[4] = {64, rows, box, box}, e[4] = {1, 1, 1, 1};
  enc(m, CU_TENSOR_MAP_DATA_TYPE_BFLOAT16, 4, const_cast<void*>(ptr), d, st, b, e, CU_TENSOR_MAP_INTERLEAVE_NONE,
      CU_TENSOR_MAP_SWIZZLE_128B, CU_TENSOR_MAP_L2_PROMOTION_L2_128B, CU_TENSOR_MAP_FLOAT_OOB_FILL_NONE);
}
void make_3d(EncodeFn enc, CUtensorMap* m, const void* ptr, uint64_t d0, uint64_t rows, uint64_t d2, uint64_t row_bytes,
             uint64_t chunk_bytes, uint32_t box_chunks) {
  cuuint64_t d[3] = {d0, rows, d2}, st[2] = {row_bytes, chunk_bytes};
  cuuint32_t b[3] = {64, 32, box_chunks}, e[3] = {1, 1, 1};
  enc(m, CU_TENSOR_MAP_DATA_TYPE_BFLOAT16, 3, const_cast<void*>(ptr), d, st, b, e, CU_TENSOR_MAP_INTERLEAVE_NONE,
      CU_TENSOR_MAP_SWIZZLE_128B, CU_TENSOR_MAP_L2_PROMOTION_L2_128B, CU_TENSOR_MAP_FLOAT_OOB_FILL_NONE);
}

}

extern "C" void kernel_launch(void* const* d_in, const int* in_sizes, int n_in, void* d_out, int out_size) {
  (void)in_sizes; (void)n_in; (void)out_size;
  static EncodeFn enc = nullptr;
  static void *att = nullptr, *hbuf = nullptr, *scratch = nullptr;
  static int by_smid = 0;
  if (!enc) {
    void* fn = nullptr;
    cudaDriverEntryPointQueryResult q;
    cudaGetDriverEntryPoint("cuTensorMapEncodeTiled", &fn, cudaEnableDefault, &q);
    enc = (EncodeFn)fn;
    cudaGetSymbolAddress(&att, g_att);
    cudaGetSymbolAddress(&hbuf, g_h);
    cudaGetSymbolAddress(&scratch, g_scratch);
    cudaFuncSetAttribute(fused_layers_kernel<true>, cudaFuncAttributeMaxDynamicSharedMemorySize, SMEM_BYTES);
    cudaFuncSetAttribute(fused_layers_kernel<false>, cudaFuncAttributeMaxDynamicSharedMemorySize, SMEM_BYTES);
    int sms = 0, clusters = 0, dev = 0;
    cudaGetDevice(&dev);
    cudaDeviceGetAttribute(&sms, cudaDevAttrMultiProcessorCount, dev);
    cudaLaunchConfig_t cfg = {};
    cfg.gridDim = dim3(132);
    cfg.blockDim = dim3(384);
    cfg.dynamicSmemBytes = SMEM_BYTES;
    cudaLaunchAttribute at[1];
    at[0].id = cudaLaunchAttributeClusterDimension;
    at[0].val.clusterDim.x = 2; at[0].val.clusterDim.y = 1; at[0].val.clusterDim.z = 1;
    cfg.attrs = at;
    cfg.numAttrs = 1;
    if (cudaOccupancyMaxActiveClusters(&clusters, fused_layers_kernel<true>, &cfg) != cudaSuccess) (void)cudaGetLastError();
    by_smid = sms == 132 && clusters == 66;
  }
  Maps p;
  Scalars sc;
  make_act(enc, &p.xin, d_in[0], DM, true);
  make_act(enc, &p.out, d_out, DM, true);
  make_act(enc, &p.out_w, d_out, DM, true, 1);
  make_act(enc, &p.out_8, d_out, DM, true, 1, 8);
  make_act(enc, &p.att, att, DM, false);
  make_act(enc, &p.h, hbuf, FF, false);
  make_2d(enc, &p.att_st, att, DM, SEQ, 32);
  make_2d(enc, &p.h_st, hbuf, FF, SEQ, 32);
  make_2d(enc, &p.w1c, d_in[4], FF, DM, 32);
  make_3d(enc, &p.wqkv, d_in[1], DM, DM, 3, 3 * DM * 2, DM * 2, 3);
  make_3d(enc, &p.wo, d_in[2], 64, DM, DM / 64, DM * 2, 128, 2);
  make_3d(enc, &p.w1a, d_in[4], 64, DM, FF / 64, FF * 2, 128, 3);
  make_3d(enc, &p.w1b, d_in[4], 64, DM, FF / 64, FF * 2, 128, 2);
  make_3d(enc, &p.w2, d_in[6], 64, FF, DM / 64, DM * 2, 128, 2);
  sc.b1 = (const __nv_bfloat16*)d_in[5];
  sc.b2 = (const __nv_bfloat16*)d_in[7];
  sc.g = (Scratch*)scratch;
  sc.zero = 0;
  if (by_smid) fused_layers_kernel<true><<<132, 384, SMEM_BYTES>>>(sc, p);
  else fused_layers_kernel<false><<<NCTA, 384, SMEM_BYTES>>>(sc, p);
}
```
